```python
import torch

def _softmax(x, axis=-1):
    return torch.softmax(x, dim=axis)
def _gelu(x):
    return torch.nn.functional.gelu(x, approximate="tanh")
def _silu(x):
    return torch.nn.functional.silu(x)
def _sigmoid(x):
    return torch.sigmoid(x)
def _layernorm(x, axis=-1, eps=1e-5):
    m = x.mean(dim=axis, keepdim=True)
    v = x.var(dim=axis, keepdim=True, unbiased=False)
    return (x - m) / torch.sqrt(v + eps)
def _scatter_add(tgt, idx, src, axis=0):
    return tgt.clone().index_add_(axis, idx, src)
def _segment_sum(src, seg, n):
    out = torch.zeros((n,) + src.shape[1:], dtype=src.dtype)
    return out.index_add_(0, seg, src)
def _pad(x, pw):
    flat = tuple(v for pair in reversed(pw) for v in pair)
    return torch.nn.functional.pad(x, flat)

kernel_name = 'gated_mix__ssm_conv_h3__compressed_kv_cla__prompt'

def setup_inputs():

    _w = (lambda a: (lambda t: t.to(torch.bfloat16) if t.is_floating_point() else t)(torch.as_tensor(a)))
    def _A_setup():
        B, S, D = 1, 2048, 1024
        ks = 4
        return {
            "q": _w((lambda *s: torch.randn(*s, dtype=torch.bfloat16) * 0.05)(B, S, D)),
            "k": _w((lambda *s: torch.randn(*s, dtype=torch.bfloat16) * 0.4)(B, S, D)),
            "v": _w((lambda *s: torch.randn(*s, dtype=torch.bfloat16) * 0.4)(B, S, D)),
            "shift_k": _w((lambda *s: torch.randn(*s, dtype=torch.bfloat16) * 0.4)(D, ks) * 0.5),
            "ssm_k": _w((lambda *s: torch.randn(*s, dtype=torch.bfloat16) * 0.8)(D, S) * (1.0 / S ** 0.5)),
            "ssm_D": _w((lambda *s: torch.randn(*s, dtype=torch.bfloat16) * 0.4)(D)),
        }
    _A_in = _A_setup()

    def _B_setup():
        B, H, Sq, Sk, D, M = 1, 32, 2048, 2048, 128, 1024
        Dc = 4 * D
        return {
            "x": _w((lambda *s: torch.randn(*s, dtype=torch.bfloat16) * 0.05)(B, Sq, M)),
            "c_kv": _w((lambda *s: torch.randn(*s, dtype=torch.bfloat16) * 0.4)(B, Sk, Dc)),
            "w_q": _w((lambda *s: torch.randn(*s, dtype=torch.bfloat16) * 6.4)(M, H, D) * (M ** -0.5)),
            "w_uk": _w((lambda *s: torch.randn(*s, dtype=torch.bfloat16) * 6.4)(Dc, H, D) * (Dc ** -0.5)),
            "w_uv": _w((lambda *s: torch.randn(*s, dtype=torch.bfloat16) * 0.4)(Dc, H, D) * (Dc ** -0.5)),
            "w_o": _w((lambda *s: torch.randn(*s, dtype=torch.bfloat16) * 0.4)(H, D, M) * ((H * D) ** -0.5)),
        }
    _B_in = _B_setup()

    return {
        "A_q": _A_in["q"],
        "A_k": _A_in["k"],
        "A_v": _A_in["v"],
        "A_shift_k": _A_in["shift_k"],
        "A_ssm_k": _A_in["ssm_k"],
        "A_ssm_D": _A_in["ssm_D"],
        "B_x": _B_in["x"],
        "B_c_kv": _B_in["c_kv"],
        "B_w_q": _B_in["w_q"],
        "B_w_uk": _B_in["w_uk"],
        "B_w_uv": _B_in["w_uv"],
        "B_w_o": _B_in["w_o"],
        "gate_w": _w((lambda *s: torch.randn(*s, dtype=torch.bfloat16) * 0.05)(1024) * 16.0),
    }

def reference(A_q, A_k, A_v, A_shift_k, A_ssm_k, A_ssm_D, B_x, B_c_kv, B_w_q, B_w_uk, B_w_uv, B_w_o, gate_w):
    def _A_ref(q, k, v, shift_k, ssm_k, ssm_D):
        B, S, D = q.shape
        ks = shift_k.shape[-1]
        k_pad = _pad(k, ((0, 0), (ks - 1, 0), (0, 0)))
        k_shift = torch.zeros_like(k)
        for t in range(ks):
            k_shift = k_shift + k_pad[:, t:t + S, :] * shift_k[:, ks - 1 - t][None, None, :]
        kv = k_shift * v
        L = 2 * S
        kv_pad = _pad(kv, ((0, 0), (0, S), (0, 0)))
        kf_pad = _pad(ssm_k, ((0, 0), (0, S)))
        kv_f = (lambda x, axes=(-2,-1): torch.fft.rfft2(x.float(), dim=axes))(kv_pad[:, None, :, :], axes=(1, 2))
        kf_f = (lambda x, axes=(-2,-1): torch.fft.rfft2(x.float(), dim=axes))(kf_pad[:, None, :], axes=(1, 2))
        kf_f = (lambda x, *d: x.permute(*d))(kf_f, 1, 2, 0)
        y_f = kv_f * kf_f[None, :, :, :]
        y = (lambda x, s, axes=(-2,-1): torch.fft.irfft2(x, s=s, dim=axes).to(torch.bfloat16))(y_f, (1, L), axes=(1, 2))[:, 0, :S, :]
        y = y + kv * ssm_D[None, None, :]
        return q * y

    def _B_ref(x, c_kv, w_q, w_uk, w_uv, w_o):
        B, Sq, M = x.shape[0], x.shape[1], x.shape[2]
        Sk = c_kv.shape[1]
        H, D = w_q.shape[1], w_q.shape[2]
        q = torch.einsum("bqm,mhd->bhqd", x, w_q)
        k = torch.einsum("bkc,chd->bhkd", c_kv, w_uk)
        v = torch.einsum("bkc,chd->bhkd", c_kv, w_uv)
        scores = torch.einsum("bhqd,bhkd->bhqk", q, k) * (D ** -0.5)
        off = Sk - Sq
        qi = torch.arange(Sq)[:, None]
        kj = torch.arange(Sk)[None, :]
        cmask = kj <= (qi + off)
        scores = torch.where(cmask[None, None], scores, -1e9)
        p = _softmax(scores, axis=-1)
        ctx = torch.einsum("bhqk,bhkd->bhqd", p, v)
        return torch.einsum("bhqd,hdm->bqm", ctx, w_o)

    x = A_q
    g = _sigmoid((x * gate_w).sum(-1, keepdims=True))
    a = _A_ref(x, A_k, A_v, A_shift_k, A_ssm_k, A_ssm_D)
    b = _B_ref(x, B_c_kv, B_w_q, B_w_uk, B_w_uv, B_w_o)
    return g * a + (1 - g) * b
```

```cpp
#include <cuda_runtime.h>
#include <cuda.h>
#include <cuda_bf16.h>
#include <stdint.h>

namespace {

constexpr int SEQ = 2048, DM = 1024, DC = 512, NH = 32, HD = 128;
constexpr int GR = 16384;
constexpr int NGR = 14;
constexpr int SM_BAR = NGR * GR;
constexpr int SM_GATE = SM_BAR + 512;
constexpr int SMEM_BYTES = SM_GATE + 512 + 1024;
constexpr int NTHREADS = 384;
#define SPLIT 10
constexpr int NMAIN = 128;

constexpr int B_FULL = 0, B_EMPTY = 14, B_EV = 28, B_DONE = 36;

__device__ __align__(1024) uint8_t g_kimg[NH * 16 * 32768];
__device__ __align__(1024) uint8_t g_vimg[NH * 16 * 32768];
__device__ __align__(1024) uint8_t g_cimg[16 * NH * 32768];
__device__ __align__(1024) __nv_bfloat16 g_yT[DM * SEQ];
__device__ __align__(1024) float g_gate[SEQ];
__device__ unsigned g_flags[128 * 8];
constexpr int F_KV = 0, F_CTX = 16, F_GATE = 48, F_EXIT = 49, F_NUM = 50;
#define FLAG(i) (&g_flags[(i) * 8])

#define TS(slot)
#define FT(it, k)

__device__ __forceinline__ uint32_t smem_u32(const void* p) { return (uint32_t)__cvta_generic_to_shared(p); }
__device__ __forceinline__ void mbar_init(uint32_t bar, int cnt) { asm volatile("mbarrier.init.shared::cta.b64 [%0], %1;" ::"r"(bar), "r"(cnt) : "memory"); }
__device__ __forceinline__ void mbar_expect_tx(uint32_t bar, uint32_t bytes) { asm volatile("mbarrier.arrive.expect_tx.shared::cta.b64 _, [%0], %1;" ::"r"(bar), "r"(bytes) : "memory"); }
__device__ __forceinline__ void mbar_arrive(uint32_t bar) { asm volatile("mbarrier.arrive.shared::cta.b64 _, [%0];" ::"r"(bar) : "memory"); }
__device__ __forceinline__ void mbar_arrive_cluster(uint32_t bar, uint32_t cta) {
  asm volatile("{\n.reg .b32 r;\nmapa.shared::cluster.u32 r, %0, %1;\nmbarrier.arrive.shared::cluster.b64 _, [r];\n}\n" ::"r"(bar), "r"(cta) : "memory");
}
__device__ __forceinline__ bool mbar_try(uint32_t bar, uint32_t parity) {
  uint32_t ok;
  asm volatile("{\n.reg .pred p;\nmbarrier.try_wait.parity.shared::cta.b64 p, [%1], %2;\nselp.u32 %0, 1, 0, p;\n}\n" : "=r"(ok) : "r"(bar), "r"(parity) : "memory");
  return ok;
}
__device__ __forceinline__ void mbar_wait(uint32_t bar, uint32_t parity) {
  asm volatile("{\n.reg .pred p;\nWAIT_LOOP:\nmbarrier.try_wait.parity.shared::cta.b64 p, [%0], %1;\n@p bra WAIT_DONE;\nbra WAIT_LOOP;\nWAIT_DONE:\n}\n" ::"r"(bar), "r"(parity) : "memory");
}
__device__ __forceinline__ void tma2d(uint32_t dst, const CUtensorMap* tm, int c0, int c1, uint32_t bar) {
  asm volatile("cp.async.bulk.tensor.2d.shared::cluster.global.mbarrier::complete_tx::bytes [%0], [%1, {%3, %4}], [%2];"
               ::"r"(dst), "l"(tm), "r"(bar), "r"(c0), "r"(c1) : "memory");
}
__device__ __forceinline__ void tma2d_mc(uint32_t dst, const CUtensorMap* tm, int c0, int c1, uint32_t bar) {
  asm volatile("cp.async.bulk.tensor.2d.shared::cluster.global.mbarrier::complete_tx::bytes.multicast::cluster [%0], [%1, {%3, %4}], [%2], %5;"
               ::"r"(dst), "l"(tm), "r"(bar), "r"(c0), "r"(c1), "h"((uint16_t)3) : "memory");
}
__device__ __forceinline__ void tma3d(uint32_t dst, const CUtensorMap* tm, int c0, int c1, int c2, uint32_t bar) {
  asm volatile("cp.async.bulk.tensor.3d.shared::cluster.global.mbarrier::complete_tx::bytes [%0], [%1, {%3, %4, %5}], [%2];"
               ::"r"(dst), "l"(tm), "r"(bar), "r"(c0), "r"(c1), "r"(c2) : "memory");
}
__device__ __forceinline__ void tma3d_mc(uint32_t dst, const CUtensorMap* tm, int c0, int c1, int c2, uint32_t bar) {
  asm volatile("cp.async.bulk.tensor.3d.shared::cluster.global.mbarrier::complete_tx::bytes.multicast::cluster [%0], [%1, {%3, %4, %5}], [%2], %6;"
               ::"r"(dst), "l"(tm), "r"(bar), "r"(c0), "r"(c1), "r"(c2), "h"((uint16_t)3) : "memory");
}
__device__ __forceinline__ void bulk_g2s(uint32_t dst, const void* src, uint32_t bytes, uint32_t bar) {
  asm volatile("cp.async.bulk.shared::cluster.global.mbarrier::complete_tx::bytes [%0], [%1], %2, [%3];"
               ::"r"(dst), "l"(src), "r"(bytes), "r"(bar) : "memory");
}
__device__ __forceinline__ void tma2d_store(const CUtensorMap* tm, uint32_t src, int c0, int c1) {
  asm volatile("cp.async.bulk.tensor.2d.global.shared::cta.bulk_group [%0, {%2, %3}], [%1];" ::"l"(tm), "r"(src), "r"(c0), "r"(c1) : "memory");
}
__device__ __forceinline__ void prefetch_tm(const CUtensorMap* tm) { asm volatile("prefetch.tensormap [%0];" ::"l"(tm) : "memory"); }
__device__ __forceinline__ void wg_fence() { asm volatile("wgmma.fence.sync.aligned;" ::: "memory"); }
__device__ __forceinline__ void wg_commit() { asm volatile("wgmma.commit_group.sync.aligned;" ::: "memory"); }
template <int N> __device__ __forceinline__ void wg_wait() { asm volatile("wgmma.wait_group.sync.aligned %0;" ::"n"(N) : "memory"); }
__device__ __forceinline__ void bar_sync(int id, int n) { asm volatile("bar.sync %0, %1;" ::"r"(id), "r"(n) : "memory"); }
__device__ __forceinline__ void bar_arrive(int id, int n) { asm volatile("bar.arrive %0, %1;" ::"r"(id), "r"(n) : "memory"); }
__device__ __forceinline__ void fence_async_smem() { asm volatile("fence.proxy.async.shared::cta;" ::: "memory"); }
__device__ __forceinline__ void fence_async_all() { asm volatile("fence.proxy.async;" ::: "memory"); }
__device__ __forceinline__ void cluster_sync() { asm volatile("barrier.cluster.arrive.release.aligned;\nbarrier.cluster.wait.acquire.aligned;" ::: "memory"); }
__device__ __forceinline__ uint32_t pack_bf16(float lo, float hi) { uint32_t r; asm("cvt.rn.bf16x2.f32 %0, %1, %2;" : "=r"(r) : "f"(hi), "f"(lo)); return r; }
__device__ __forceinline__ float ex2(float x) { float r; asm("ex2.approx.ftz.f32 %0, %1;" : "=f"(r) : "f"(x)); return r; }
__device__ __forceinline__ float bf_lo(uint32_t v) { return __uint_as_float(v << 16); }
__device__ __forceinline__ float bf_hi(uint32_t v) { return __uint_as_float(v & 0xffff0000u); }
__device__ __forceinline__ void flag_wait(const unsigned* f, unsigned target) {
  unsigned v;
  do { asm volatile("ld.acquire.gpu.global.u32 %0, [%1];" : "=r"(v) : "l"(f) : "memory"); } while (v < target);
}
__device__ __forceinline__ void flag_add(unsigned* f) {
  asm volatile("fence.acq_rel.gpu;\nred.relaxed.gpu.global.add.u32 [%0], 1;" ::"l"(f) : "memory");
}
__device__ __forceinline__ uint32_t desc_k(uint32_t addr) { return ((addr & 0x3FFFF) >> 4) | (1u << 16); }
template <int LBO> __device__ __forceinline__ uint32_t desc_mn(uint32_t addr) { return ((addr & 0x3FFFF) >> 4) | ((uint32_t)(LBO >> 4) << 16); }
#define DHI "0x40000040"

#define R8(d, o) "+f"(d[o]), "+f"(d[o + 1]), "+f"(d[o + 2]), "+f"(d[o + 3]), "+f"(d[o + 4]), "+f"(d[o + 5]), "+f"(d[o + 6]), "+f"(d[o + 7])
#define R32(d, o) R8(d, o), R8(d, o + 8), R8(d, o + 16), R8(d, o + 24)
#define R64(d, o) R32(d, o), R32(d, o + 32)
#define L64 "%0,%1,%2,%3,%4,%5,%6,%7,%8,%9,%10,%11,%12,%13,%14,%15,%16,%17,%18,%19,%20,%21,%22,%23,%24,%25,%26,%27,%28,%29,%30,%31," \
            "%32,%33,%34,%35,%36,%37,%38,%39,%40,%41,%42,%43,%44,%45,%46,%47,%48,%49,%50,%51,%52,%53,%54,%55,%56,%57,%58,%59,%60,%61,%62,%63"
#define L128 L64 ",%64,%65,%66,%67,%68,%69,%70,%71,%72,%73,%74,%75,%76,%77,%78,%79,%80,%81,%82,%83,%84,%85,%86,%87,%88,%89,%90,%91,%92,%93,%94,%95," \
            "%96,%97,%98,%99,%100,%101,%102,%103,%104,%105,%106,%107,%108,%109,%110,%111,%112,%113,%114,%115,%116,%117,%118,%119,%120,%121,%122,%123,%124,%125,%126,%127"

template <int TB> __device__ __forceinline__ void mma_ss_n128(float (&d)[64], uint32_t da, uint32_t db) {
  asm volatile("{\n.reg .b64 da, db;\nmov.b64 da, {%64, " DHI "};\nmov.b64 db, {%65, " DHI "};\n"
               "wgmma.mma_async.sync.aligned.m64n128k16.f32.bf16.bf16 {" L64 "}, da, db, 1, 1, 1, 0, %66;\n}\n"
               : R64(d, 0) : "r"(da), "r"(db), "n"(TB));
}
template <int TB> __device__ __forceinline__ void mma_rs_n128(float (&d)[64], uint32_t a0, uint32_t a1, uint32_t a2, uint32_t a3, uint32_t db, int sd) {
  asm volatile("{\n.reg .pred p;\n.reg .b64 db;\nsetp.ne.b32 p, %69, 0;\nmov.b64 db, {%68, " DHI "};\n"
               "wgmma.mma_async.sync.aligned.m64n128k16.f32.bf16.bf16 {" L64 "}, {%64,%65,%66,%67}, db, p, 1, 1, %70;\n}\n"
               : R64(d, 0) : "r"(a0), "r"(a1), "r"(a2), "r"(a3), "r"(db), "r"(sd), "n"(TB));
}
template <int TB> __device__ __forceinline__ void mma_ss_n256(float (&d)[128], uint32_t da, uint32_t db) {
  asm volatile("{\n.reg .b64 da, db;\nmov.b64 da, {%128, " DHI "};\nmov.b64 db, {%129, " DHI "};\n"
               "wgmma.mma_async.sync.aligned.m64n256k16.f32.bf16.bf16 {" L128 "}, da, db, 1, 1, 1, 0, %130;\n}\n"
               : R64(d, 0), R64(d, 64) : "r"(da), "r"(db), "n"(TB));
}
#define W8(d, o) "=f"(d[o]), "=f"(d[o + 1]), "=f"(d[o + 2]), "=f"(d[o + 3]), "=f"(d[o + 4]), "=f"(d[o + 5]), "=f"(d[o + 6]), "=f"(d[o + 7])
#define W32(d, o) W8(d, o), W8(d, o + 8), W8(d, o + 16), W8(d, o + 24)
#define W64(d, o) W32(d, o), W32(d, o + 32)
template <int TB> __device__ __forceinline__ void mma_ss_n128_init(float (&d)[64], uint32_t da, uint32_t db) {
  asm volatile("{\n.reg .b64 da, db;\nmov.b64 da, {%64, " DHI "};\nmov.b64 db, {%65, " DHI "};\n"
               "wgmma.mma_async.sync.aligned.m64n128k16.f32.bf16.bf16 {" L64 "}, da, db, 0, 1, 1, 0, %66;\n}\n"
               : W64(d, 0) : "r"(da), "r"(db), "n"(TB));
}
template <int TB> __device__ __forceinline__ void mma_ss_n256_init(float (&d)[128], uint32_t da, uint32_t db) {
  asm volatile("{\n.reg .b64 da, db;\nmov.b64 da, {%128, " DHI "};\nmov.b64 db, {%129, " DHI "};\n"
               "wgmma.mma_async.sync.aligned.m64n256k16.f32.bf16.bf16 {" L128 "}, da, db, 0, 1, 1, 0, %130;\n}\n"
               : W64(d, 0), W64(d, 64) : "r"(da), "r"(db), "n"(TB));
}
template <int N> __device__ __forceinline__ void reg_fence(float (&d)[N]) {
#pragma unroll
  for (int i = 0; i < N; i++) asm volatile("" : "+f"(d[i])::"memory");
}
template <int N> __device__ __forceinline__ void reg_fence(uint32_t (&d)[N]) {
#pragma unroll
  for (int i = 0; i < N; i++) asm volatile("" : "+r"(d[i])::"memory");
}

struct __align__(64) Params {
  CUtensorMap x, c, wq, wuk, wuv, wo, y, out;
  const __nv_bfloat16* xp;
  const __nv_bfloat16* gate_w;
};

template <int O, int N, bool SMEM>
__device__ __forceinline__ void store_img(const float (&acc)[N], float s0, float s1, uint8_t* gbase, uint32_t sbase, int row, int t) {
  const int g = row & 7;
#pragma unroll
  for (int a = 0; a < 4; a++) {
    const uint32_t off = (a >> 1) * 16384 + row * 128 + ((((a & 1) * 4 + t) ^ g) << 4);
#pragma unroll
    for (int h = 0; h < 2; h++) {
      const float s = h ? s1 : s0;
      uint32_t v0 = pack_bf16(acc[O + 16 * a + 2 * h] * s, acc[O + 16 * a + 2 * h + 1] * s);
      uint32_t v1 = pack_bf16(acc[O + 16 * a + 4 + 2 * h] * s, acc[O + 16 * a + 4 + 2 * h + 1] * s);
      uint32_t v2 = pack_bf16(acc[O + 16 * a + 8 + 2 * h] * s, acc[O + 16 * a + 8 + 2 * h + 1] * s);
      uint32_t v3 = pack_bf16(acc[O + 16 * a + 12 + 2 * h] * s, acc[O + 16 * a + 12 + 2 * h + 1] * s);
      if (SMEM) asm volatile("st.shared.v4.b32 [%0], {%1,%2,%3,%4};" ::"r"(sbase + off + h * 1024), "r"(v0), "r"(v1), "r"(v2), "r"(v3) : "memory");
      else asm volatile("st.global.v4.b32 [%0], {%1,%2,%3,%4};" ::"l"(gbase + off + h * 1024), "r"(v0), "r"(v1), "r"(v2), "r"(v3) : "memory");
    }
  }
}

struct Cons {
  uint32_t sb;
  uint32_t pf;
  uint32_t rank;
  int wg, tid;
  __device__ __forceinline__ void wait_full(int g) { mbar_wait(sb + SM_BAR + (B_FULL + g) * 8, (pf >> g) & 1); pf ^= 1u << g; }
  __device__ __forceinline__ void release(int g, int n, bool cross) {
    if (tid < 2 * n) mbar_arrive_cluster(sb + SM_BAR + (B_EMPTY + g + (tid >> 1)) * 8, cross ? (uint32_t)(tid & 1) : rank);
  }
  __device__ __forceinline__ void turn_begin() { bar_sync(1 + wg, 256); }
  __device__ __forceinline__ void turn_end() { bar_arrive(2 - wg, 256); }
  __device__ __forceinline__ void event(int e) { __syncwarp(); if ((tid & 31) == 0) mbar_arrive(sb + SM_BAR + (B_EV + e) * 8); }
};

constexpr float SM_C = 0.08838834764831845f * 1.4426950408889634f;
struct SoftState { float m0, m1, l0, l1, sc0, sc1, n0, n1, s0, s1, r0, r1; };
__device__ __forceinline__ void softmax_max(const float (&S)[64], SoftState& z) {
  float a0 = fmaxf(S[0], S[1]), a1 = fmaxf(S[2], S[3]), b0 = fmaxf(S[4], S[5]), b1 = fmaxf(S[6], S[7]);
#pragma unroll
  for (int j = 2; j < 16; j += 2) {
    a0 = fmaxf(a0, fmaxf(S[4 * j], S[4 * j + 1]));
    a1 = fmaxf(a1, fmaxf(S[4 * j + 2], S[4 * j + 3]));
    b0 = fmaxf(b0, fmaxf(S[4 * j + 4], S[4 * j + 5]));
    b1 = fmaxf(b1, fmaxf(S[4 * j + 6], S[4 * j + 7]));
  }
  a0 = fmaxf(a0, b0); a1 = fmaxf(a1, b1);
  a0 = fmaxf(a0, __shfl_xor_sync(0xffffffffu, a0, 1)); a1 = fmaxf(a1, __shfl_xor_sync(0xffffffffu, a1, 1));
  a0 = fmaxf(a0, __shfl_xor_sync(0xffffffffu, a0, 2)); a1 = fmaxf(a1, __shfl_xor_sync(0xffffffffu, a1, 2));
  a0 = fmaxf(a0, z.m0); a1 = fmaxf(a1, z.m1);
  z.sc0 = ex2((z.m0 - a0) * SM_C); z.sc1 = ex2((z.m1 - a1) * SM_C);
  z.m0 = a0; z.m1 = a1;
  z.n0 = -a0 * SM_C; z.n1 = -a1 * SM_C;
  z.s0 = z.l0 * z.sc0; z.s1 = z.l1 * z.sc1; z.r0 = 0.f; z.r1 = 0.f;
}
template <int J0, int J1> __device__ __forceinline__ void softmax_exp(float (&S)[64], SoftState& z) {
#pragma unroll
  for (int j = J0; j < J1; j++) {
    S[4 * j] = ex2(fmaf(S[4 * j], SM_C, z.n0));
    S[4 * j + 1] = ex2(fmaf(S[4 * j + 1], SM_C, z.n0));
    S[4 * j + 2] = ex2(fmaf(S[4 * j + 2], SM_C, z.n1));
    S[4 * j + 3] = ex2(fmaf(S[4 * j + 3], SM_C, z.n1));
    z.s0 += S[4 * j]; z.r0 += S[4 * j + 1]; z.s1 += S[4 * j + 2]; z.r1 += S[4 * j + 3];
  }
  if (J1 == 16) { z.l0 = z.s0 + z.r0; z.l1 = z.s1 + z.r1; }
}
__device__ __forceinline__ void pin(float a, float b, float c, float d, uint32_t never_zero) {
  asm volatile("{\n.reg .pred p;\nsetp.eq.u32 p, %4, 0;\n@p st.shared.v4.f32 [%4], {%0,%1,%2,%3};\n}\n" ::"f"(a), "f"(b), "f"(c), "f"(d), "r"(never_zero) : "memory");
}
__device__ __forceinline__ void mask_diag(float (&S)[64], int row, int t) {
  const int d = row - 2 * t;
#pragma unroll
  for (int j = 0; j < 16; j++) {
    if (8 * j > d) S[4 * j] = -INFINITY;
    if (8 * j + 1 > d) S[4 * j + 1] = -INFINITY;
    if (8 * j > d + 8) S[4 * j + 2] = -INFINITY;
    if (8 * j + 1 > d + 8) S[4 * j + 3] = -INFINITY;
  }
}
__device__ __forceinline__ void to_p(const float (&S)[64], uint32_t (&P)[32]) {
#pragma unroll
  for (int i = 0; i < 32; i++) P[i] = pack_bf16(S[2 * i], S[2 * i + 1]);
}
__device__ __forceinline__ float quad_sum(float v) {
  v += __shfl_xor_sync(0xffffffffu, v, 1);
  v += __shfl_xor_sync(0xffffffffu, v, 2);
  return v;
}
__device__ __forceinline__ void issue_qk(float (&S)[64], uint32_t dq, uint32_t dk) {
  mma_ss_n128_init<0>(S, dq, dk);
#pragma unroll
  for (int s = 1; s < 8; s++) mma_ss_n128<0>(S, dq + (s >> 2) * 1024 + (s & 3) * 2, dk + (s >> 2) * 1024 + (s & 3) * 2);
}
__device__ __forceinline__ void issue_pv(float (&O)[64], const uint32_t (&P)[32], uint32_t dv, int acc) {
#pragma unroll
  for (int s = 0; s < 8; s++) mma_rs_n128<1>(O, P[4 * s], P[4 * s + 1], P[4 * s + 2], P[4 * s + 3], dv + s * 128, s != 0 ? 1 : acc);
}

__global__ void __cluster_dims__(2, 1, 1) __launch_bounds__(NTHREADS, 1) mega_kernel(const __grid_constant__ Params p) {
  extern __shared__ uint8_t smem_raw[];
  const uint32_t sb = (smem_u32(smem_raw) + 1023) & ~1023u;
  const int wgi = __shfl_sync(0xffffffffu, threadIdx.x >> 7, 0);
  const int warp = __shfl_sync(0xffffffffu, threadIdx.x >> 5, 0);
  const uint32_t rank = blockIdx.x & 1;
  const int cl = blockIdx.x >> 1;
  const int grp = cl >> 3, idx = cl & 7;

  if (threadIdx.x == 0) {
    for (int i = 0; i < NGR; i++) { mbar_init(sb + SM_BAR + (B_FULL + i) * 8, 1); mbar_init(sb + SM_BAR + (B_EMPTY + i) * 8, 4); }
    for (int i = 0; i < 8; i++) mbar_init(sb + SM_BAR + (B_EV + i) * 8, 8);
    mbar_init(sb + SM_BAR + B_DONE * 8, 11);
    asm volatile("fence.mbarrier_init.release.cluster;" ::: "memory");
    prefetch_tm(&p.c); prefetch_tm(&p.wuk); prefetch_tm(&p.wuv); prefetch_tm(&p.x); prefetch_tm(&p.wq);
  }
  cluster_sync();
  TS(0);

  if (wgi == 0) {
    asm volatile("setmaxnreg.dec.sync.aligned.u32 40;");
    const int lane = threadIdx.x & 31;
    if (warp == 0) {
      if (lane == 0) {
        uint32_t pe = 0x3FFC;
        auto acquire = [&](int g) { mbar_wait(sb + SM_BAR + (B_EMPTY + g) * 8, (pe >> g) & 1); pe ^= 1u << g; };
#pragma unroll 1
        for (int rnd = 0; rnd < 2; rnd++) {
          const int hp = 16 * rnd + 2 * grp;
#pragma unroll 1
          for (int kk = 0; kk < 16; kk++) {
            const int g0 = 2 + 3 * (kk & 3), kb = kk & 7, head = hp + (kk >> 3);
            acquire(g0); acquire(g0 + 1); acquire(g0 + 2);
            const uint32_t fb = sb + SM_BAR + (B_FULL + g0) * 8;
            mbar_expect_tx(fb, 3 * GR);
            tma2d(sb + g0 * GR, &p.c, kb * 64, (2 * idx + rank) * 128, fb);
            tma3d_mc(sb + (g0 + 1 + rank) * GR, rank ? &p.wuv : &p.wuk, 0, kb * 64, head * 2, fb);
          }
          const int head = hp + rank;
#pragma unroll 1
          for (int kb = 0; kb < 16; kb++) {
            const int g0 = 2 + 3 * (kb & 3);
            acquire(g0); acquire(g0 + 1); acquire(g0 + 2);
            const uint32_t fb = sb + SM_BAR + (B_FULL + g0) * 8;
            mbar_expect_tx(fb, 3 * GR);
            tma2d_mc(sb + (g0 + rank) * GR, &p.x, kb * 64, (rank ? idx : 15 - idx) * 128, fb);
            tma3d(sb + (g0 + 2) * GR, &p.wq, 0, kb * 64, head * 2, fb);
          }
          flag_wait(FLAG(F_KV + rnd * 8 + grp), 16);
          fence_async_all();
          acquire(2); acquire(3);
          const int nA = 16 - idx;
          int slot = 1;
#pragma unroll 1
          for (int f = 0; f < 34; f++) {
            const bool isk = (f == 0) || ((f & 1) && f < 33);
            const int it = (f == 0) ? 0 : (f == 33) ? 16 : isk ? (f + 1) >> 1 : (f >> 1) - 1;
            const int blk = it < nA ? it : 16 - it;
            const int g0 = 4 + 2 * slot;
            acquire(g0); acquire(g0 + 1);
            const uint32_t fb = sb + SM_BAR + (B_FULL + g0) * 8;
            mbar_expect_tx(fb, 2 * GR);
            bulk_g2s(sb + g0 * GR, (isk ? g_kimg : g_vimg) + (size_t)(head * 16 + blk) * 32768, 2 * GR, fb);
            slot = slot == 4 ? 0 : slot + 1;
          }
        }
        const int rt = 2 * idx + rank, ct = grp;
        int st = 1;
#pragma unroll 1
        for (int kb = 0; kb < 66; kb++) {
          if (kb == 0 || kb == 32) { flag_wait(FLAG(F_CTX + rt * 2 + (kb >> 5)), 16); fence_async_all(); }
          const int g0 = 2 * st;
          acquire(g0); acquire(g0 + 1);
          const uint32_t fb = sb + SM_BAR + (B_FULL + g0) * 8;
          if (kb < 64) {
            mbar_expect_tx(fb, 2 * GR);
            bulk_g2s(sb + g0 * GR, g_cimg + (size_t)(rt * 64 + kb) * GR, GR, fb);
            tma2d_mc(sb + (g0 + 1) * GR + rank * 8192, &p.wo, ct * 128 + rank * 64, kb * 64, fb);
          } else if (kb == 64) {
            mbar_expect_tx(fb, 2 * GR);
            tma2d(sb + g0 * GR, &p.x, ct * 128, rt * 128, fb);
            tma2d(sb + (g0 + 1) * GR, &p.x, ct * 128 + 64, rt * 128, fb);
          } else {
            flag_wait(FLAG(F_GATE), 2 * NMAIN);
            fence_async_all();
            mbar_expect_tx(fb, 2 * GR + 512);
            tma2d(sb + g0 * GR, &p.y, rt * 128, ct * 128, fb);
            tma2d(sb + (g0 + 1) * GR, &p.y, rt * 128 + 64, ct * 128, fb);
            bulk_g2s(sb + SM_GATE, g_gate + rt * 128, 512, fb);
          }
          st = st == 6 ? 0 : st + 1;
        }
        mbar_arrive(sb + SM_BAR + B_DONE * 8);
      }
    } else if (warp == 1) {
      if (lane == 0) {
#pragma unroll 1
        for (int e = 0; e < 6; e++) {
          mbar_wait(sb + SM_BAR + (B_EV + e) * 8, 0);
          const int rnd = e / 3, k = e % 3;
          flag_add(k == 0 ? FLAG(F_KV + rnd * 8 + grp) : FLAG(F_CTX + (k == 1 ? 15 - idx : idx) * 2 + rnd));
        }
        mbar_arrive(sb + SM_BAR + B_DONE * 8);
      }
    } else {
      const uint4* gw = reinterpret_cast<const uint4*>(p.gate_w);
#pragma unroll 1
      for (int r = 0; r < 8; r++) {
        const int row = blockIdx.x * 16 + (warp - 2) * 8 + r;
        const uint4* xr = reinterpret_cast<const uint4*>(p.xp + (size_t)row * DM);
        float s = 0.f;
#pragma unroll 2
        for (int i = 0; i < 4; i++) {
          const uint4 a = __ldg(xr + lane + 32 * i), b = __ldg(gw + lane + 32 * i);
          s += bf_lo(a.x) * bf_lo(b.x) + bf_hi(a.x) * bf_hi(b.x) + bf_lo(a.y) * bf_lo(b.y) + bf_hi(a.y) * bf_hi(b.y);
          s += bf_lo(a.z) * bf_lo(b.z) + bf_hi(a.z) * bf_hi(b.z) + bf_lo(a.w) * bf_lo(b.w) + bf_hi(a.w) * bf_hi(b.w);
        }
#pragma unroll
        for (int o = 16; o > 0; o >>= 1) s += __shfl_xor_sync(0xffffffffu, s, o);
        if (lane == 0) g_gate[row] = 1.f / (1.f + __expf(-s));
      }
      if (lane == 0) {
        flag_add(FLAG(F_GATE));
        if (warp == 2) mbar_arrive(sb + SM_BAR + B_DONE * 8);
        else {
          unsigned long long t0, t1;
          asm volatile("mov.u64 %0, %globaltimer;" : "=l"(t0));
          while (!mbar_try(sb + SM_BAR + B_DONE * 8, 0)) {
            asm volatile("mov.u64 %0, %globaltimer;" : "=l"(t1));
            if (t1 - t0 > 2000000000ull) __trap();
          }
          __threadfence();
          if (atomicAdd(FLAG(F_EXIT), 1) == gridDim.x - 1) {
            for (int i = 0; i < F_NUM; i++) *FLAG(i) = 0;
          }
        }
      }
    }
    __syncwarp();
    cluster_sync();
  } else {
    asm volatile("setmaxnreg.inc.sync.aligned.u32 232;");
    Cons c;
    c.sb = sb; c.pf = 0; c.rank = rank; c.wg = wgi - 1; c.tid = threadIdx.x & 127;
    const int lane = threadIdx.x & 31, t = lane & 3;
    const int row = c.wg * 64 + (warp & 3) * 16 + (lane >> 2);
    constexpr uint32_t DG = GR >> 4;
    const uint32_t dkk = desc_k(sb), dk0 = dkk + c.wg * 512, dm0 = desc_mn<8192>(sb), dv0 = desc_mn<16384>(sb);
    if (c.wg == 1) bar_arrive(1, 256);
    uint32_t q2par = 1;

#pragma unroll 1
    for (int rnd = 0; rnd < 2; rnd++) {
      const int hp = 16 * rnd + 2 * grp;
#pragma unroll 1
      for (int tile = 0; tile < 2; tile++) {
        float acc[128];
        {
          c.wait_full(2);
          const uint32_t a = dk0 + 2 * DG, b = dm0 + 3 * DG;
          c.turn_begin();
          wg_fence();
          mma_ss_n256_init<1>(acc, a, b);
#pragma unroll
          for (int k = 1; k < 4; k++) mma_ss_n256<1>(acc, a + k * 2, b + k * 128);
          wg_commit();
          c.turn_end();
        }
#pragma unroll 1
        for (int kb = 1; kb < 8; kb++) {
          const int g0 = 2 + 3 * (kb & 3);
          c.wait_full(g0);
          const uint32_t a = dk0 + g0 * DG, b = dm0 + (g0 + 1) * DG;
          c.turn_begin();
          wg_fence();
#pragma unroll
          for (int k = 0; k < 4; k++) mma_ss_n256<1>(acc, a + k * 2, b + k * 128);
          wg_commit();
          c.turn_end();
          wg_wait<1>();
          c.release(2 + 3 * ((kb - 1) & 3), 3, true);
        }
        wg_wait<0>();
        reg_fence(acc);
        c.release(11, 3, true);
        const size_t o = (size_t)((hp + tile) * 16 + 2 * idx + rank) * 32768;
        store_img<0, 128, false>(acc, 1.f, 1.f, g_kimg + o, 0, row, t);
        store_img<64, 128, false>(acc, 1.f, 1.f, g_vimg + o, 0, row, t);
      }
      c.event(rnd * 3);
      TS(1 + rnd * 3);
      {
        float qa[64], qb[64];
        {
          c.wait_full(2);
          const uint32_t a = dk0 + 2 * DG, b = dm0 + 4 * DG;
          c.turn_begin();
          wg_fence();
          mma_ss_n128_init<1>(qa, a, b);
          mma_ss_n128_init<1>(qb, a + DG, b);
#pragma unroll
          for (int k = 1; k < 4; k++) {
            mma_ss_n128<1>(qa, a + k * 2, b + k * 128);
            mma_ss_n128<1>(qb, a + DG + k * 2, b + k * 128);
          }
          wg_commit();
          c.turn_end();
        }
#pragma unroll 1
        for (int kb = 1; kb < 16; kb++) {
          const int g0 = 2 + 3 * (kb & 3);
          c.wait_full(g0);
          const uint32_t a = dk0 + g0 * DG, b = dm0 + (g0 + 2) * DG;
          c.turn_begin();
          wg_fence();
#pragma unroll
          for (int k = 0; k < 4; k++) {
            mma_ss_n128<1>(qa, a + k * 2, b + k * 128);
            mma_ss_n128<1>(qb, a + DG + k * 2, b + k * 128);
          }
          wg_commit();
          c.turn_end();
          wg_wait<1>();
          c.release(2 + 3 * ((kb - 1) & 3), 3, true);
        }
        wg_wait<0>();
        reg_fence(qa); reg_fence(qb);
        c.release(11, 3, true);
        mbar_wait(sb + SM_BAR + (B_EMPTY + 2) * 8, q2par);
        mbar_wait(sb + SM_BAR + (B_EMPTY + 3) * 8, q2par);
        q2par ^= 1;
        store_img<0, 64, true>(qa, 1.f, 1.f, nullptr, sb + 2 * GR, row, t);
        store_img<0, 64, true>(qb, 1.f, 1.f, nullptr, sb, row, t);
        fence_async_smem();
        bar_sync(3 + c.wg, 128);
      }
      TS(2 + rnd * 3);
      {
        const int head = hp + rank, nA = 16 - idx;
        float O[64], S[64];
        uint32_t P[32];
        SoftState z;
        z.m0 = z.m1 = -INFINITY; z.l0 = z.l1 = 0.f;
        int slot = 1;
        auto nxt = [](int s) { return s == 4 ? 0 : s + 1; };
        {
          const int g0 = 4 + 2 * slot;
          c.wait_full(g0);
          c.turn_begin();
          wg_fence();
          issue_qk(S, dk0 + 2 * DG, dkk + g0 * DG);
          wg_commit();
          c.turn_end();
#pragma unroll
          for (int i = 0; i < 64; i++) O[i] = 0.f;
          wg_wait<0>();
          reg_fence(S);
          c.release(g0, 2, true);
          softmax_max(S, z);
          softmax_exp<0, 16>(S, z);
          to_p(S, P);
          slot = nxt(slot);
        }
#pragma unroll 1
        for (int it = 1; it <= 16; it++) {
          const int gk = 4 + 2 * slot; slot = nxt(slot);
          const int gv = 4 + 2 * slot; slot = nxt(slot);
          FT(it, 0);
          c.wait_full(gk);
          c.wait_full(gv);
          FT(it, 1);
          const uint32_t q = dk0 + (it < nA ? 2 * DG : 0);
          c.turn_begin();
          FT(it, 2);
          wg_fence();
          issue_qk(S, q, dkk + gk * DG);
          wg_commit();
          issue_pv(O, P, dv0 + gv * DG, (it != 1 && it != nA + 1));
          wg_commit();
          c.turn_end();
          FT(it, 3);
          wg_wait<1>();
          reg_fence(S);
          FT(it, 4);
          c.release(gk, 2, true);
          if (it == nA - 1) c.release(2, 2, true);
          if (it == 16 && rnd == 1) c.release(0, 2, true);
          if (it == nA - 1 || it == nA) mask_diag(S, row, t);
          if (it == nA) {
            const float i0 = 1.f / quad_sum(z.l0), i1 = 1.f / quad_sum(z.l1);
            z.m0 = -INFINITY; z.m1 = -INFINITY;
            softmax_max(S, z);
            softmax_exp<0, SPLIT>(S, z);
            pin(z.s0, z.s1, z.r0, z.r1, sb);
            FT(it, 5);
            wg_wait<0>();
            reg_fence(O); reg_fence(P);
            FT(it, 6);
            c.release(gv, 2, true);
            softmax_exp<SPLIT, 16>(S, z);
            store_img<0, 64, false>(O, i0, i1, g_cimg + (size_t)((15 - idx) * 32 + head) * 32768, 0, row, t);
            c.event(rnd * 3 + 1);
            to_p(S, P);
          } else {
            softmax_max(S, z);
            softmax_exp<0, SPLIT>(S, z);
            pin(z.s0, z.s1, z.r0, z.r1, sb);
            FT(it, 5);
            wg_wait<0>();
            reg_fence(O); reg_fence(P);
            FT(it, 6);
            c.release(gv, 2, true);
            softmax_exp<SPLIT, 16>(S, z);
#pragma unroll
            for (int j = 0; j < 16; j++) { O[4 * j] *= z.sc0; O[4 * j + 1] *= z.sc0; O[4 * j + 2] *= z.sc1; O[4 * j + 3] *= z.sc1; }
            to_p(S, P);
          }
        }
        {
          const int gv = 4 + 2 * slot;
          c.wait_full(gv);
          c.turn_begin();
          wg_fence();
          issue_pv(O, P, dv0 + gv * DG, nA != 16);
          wg_commit();
          c.turn_end();
          wg_wait<0>();
          reg_fence(O); reg_fence(P);
          c.release(gv, 2, true);
          store_img<0, 64, false>(O, 1.f / quad_sum(z.l0), 1.f / quad_sum(z.l1), g_cimg + (size_t)(idx * 32 + head) * 32768, 0, row, t);
          c.event(rnd * 3 + 2);
        }
      }
      TS(3 + rnd * 3);
    }
    if (c.wg == 0) bar_sync(1, 256);
    {
      const int rt = 2 * idx + rank, ct = grp;
      float acc[64];
      int st = 2, pst = 1;
      {
        c.wait_full(2);
        const uint32_t a = dk0 + 2 * DG, b = dm0 + 3 * DG;
        wg_fence();
        mma_ss_n128_init<1>(acc, a, b);
#pragma unroll
        for (int k = 1; k < 4; k++) mma_ss_n128<1>(acc, a + k * 2, b + k * 128);
        wg_commit();
      }
#pragma unroll 1
      for (int kb = 1; kb < 64; kb++) {
        const int g0 = 2 * st;
        c.wait_full(g0);
        const uint32_t a = dk0 + g0 * DG, b = dm0 + (g0 + 1) * DG;
        wg_fence();
#pragma unroll
        for (int k = 0; k < 4; k++) mma_ss_n128<1>(acc, a + k * 2, b + k * 128);
        wg_commit();
        wg_wait<1>();
        if (kb <= 59) c.release(2 * pst, 2, true);
        pst = st;
        st = st == 6 ? 0 : st + 1;
      }
      wg_wait<0>();
      reg_fence(acc);
      TS(7);
      const uint32_t xs = sb + 2 * st * GR;
      c.wait_full(2 * st);
      st = st == 6 ? 0 : st + 1;
      const uint32_t ys = sb + 2 * st * GR;
      c.wait_full(2 * st);
      float g0, g1;
      asm volatile("ld.shared.f32 %0, [%1];" : "=f"(g0) : "r"(sb + SM_GATE + row * 4));
      asm volatile("ld.shared.f32 %0, [%1];" : "=f"(g1) : "r"(sb + SM_GATE + row * 4 + 32));
      const int mi = lane >> 3, lr = lane & 7, w = warp & 3;
#pragma unroll
      for (int jj = 0; jj < 8; jj++) {
        const int j = 2 * jj + (mi >> 1);
        const uint32_t xa = xs + (jj >> 2) * 16384 + (c.wg * 64 + w * 16 + (mi & 1) * 8 + lr) * 128 + (((j & 7) ^ lr) << 4);
        const uint32_t ya = ys + c.wg * 16384 + (8 * j + lr) * 128 + (((2 * w + (mi & 1)) ^ lr) << 4);
        uint32_t x[4], y[4], o[4];
        asm volatile("ldmatrix.sync.aligned.m8n8.x4.shared.b16 {%0,%1,%2,%3}, [%4];" : "=r"(x[0]), "=r"(x[1]), "=r"(x[2]), "=r"(x[3]) : "r"(xa) : "memory");
        asm volatile("ldmatrix.sync.aligned.m8n8.x4.trans.shared.b16 {%0,%1,%2,%3}, [%4];" : "=r"(y[0]), "=r"(y[1]), "=r"(y[2]), "=r"(y[3]) : "r"(ya) : "memory");
#pragma unroll
        for (int i = 0; i < 4; i++) {
          const float g = (i & 1) ? g1 : g0;
          const float b0 = acc[8 * jj + 2 * i], b1 = acc[8 * jj + 2 * i + 1];
          o[i] = pack_bf16(fmaf(g, bf_lo(x[i]) * bf_lo(y[i]) - b0, b0), fmaf(g, bf_hi(x[i]) * bf_hi(y[i]) - b1, b1));
        }
        asm volatile("stmatrix.sync.aligned.m8n8.x4.shared.b16 [%0], {%1,%2,%3,%4};" ::"r"(xa), "r"(o[0]), "r"(o[1]), "r"(o[2]), "r"(o[3]) : "memory");
      }
      fence_async_smem();
      __syncwarp();
      if (lane == 0) {
        const int r0 = c.wg * 64 + w * 16;
        tma2d_store(&p.out, xs + r0 * 128, ct * 128, rt * 128 + r0);
        tma2d_store(&p.out, xs + 16384 + r0 * 128, ct * 128 + 64, rt * 128 + r0);
        asm volatile("cp.async.bulk.commit_group;\ncp.async.bulk.wait_group 0;" ::: "memory");
        mbar_arrive(sb + SM_BAR + B_DONE * 8);
      }
      __syncwarp();
      TS(8);
    }
    cluster_sync();
  }
}

__global__ void __launch_bounds__(256) conv_naive(const __nv_bfloat16* __restrict__ k, const __nv_bfloat16* __restrict__ v,
                                                  const __nv_bfloat16* __restrict__ shiftk, const __nv_bfloat16* __restrict__ h,
                                                  const __nv_bfloat16* __restrict__ dvec) {
  __shared__ float su[SEQ], sh[SEQ];
  const int ch = blockIdx.x;
  for (int s = threadIdx.x; s < SEQ; s += 256) {
    float a = 0.f;
    for (int j = 3; j >= 0; j--) if (s - j >= 0) a += __bfloat162float(k[(size_t)(s - j) * DM + ch]) * __bfloat162float(shiftk[ch * 4 + j]);
    su[s] = __bfloat162float(__float2bfloat16(a * __bfloat162float(v[(size_t)s * DM + ch])));
    sh[s] = __bfloat162float(h[(size_t)ch * SEQ + s]);
  }
  __syncthreads();
  const float dd = __bfloat162float(dvec[ch]);
  for (int s = threadIdx.x; s < SEQ; s += 256) {
    float a = su[s] * dd;
    for (int j = 0; j <= s; j++) a += sh[j] * su[s - j];
    g_yT[(size_t)ch * SEQ + s] = __float2bfloat16(a);
  }
}

typedef CUresult (*EncFn)(CUtensorMap*, CUtensorMapDataType, cuuint32_t, void*, const cuuint64_t*, const cuuint64_t*, const cuuint32_t*,
                          const cuuint32_t*, CUtensorMapInterleave, CUtensorMapSwizzle, CUtensorMapL2promotion, CUtensorMapFloatOOBfill);

void enc2d(EncFn enc, CUtensorMap* tm, const void* base, uint64_t cols, uint64_t rows, uint32_t bc, uint32_t br) {
  cuuint64_t dims[2] = {cols, rows}; cuuint64_t strides[1] = {cols * 2}; cuuint32_t box[2] = {bc, br}; cuuint32_t es[2] = {1, 1};
  enc(tm, CU_TENSOR_MAP_DATA_TYPE_BFLOAT16, 2, const_cast<void*>(base), dims, strides, box, es, CU_TENSOR_MAP_INTERLEAVE_NONE,
      CU_TENSOR_MAP_SWIZZLE_128B, CU_TENSOR_MAP_L2_PROMOTION_L2_256B, CU_TENSOR_MAP_FLOAT_OOB_FILL_NONE);
}
void enc3d(EncFn enc, CUtensorMap* tm, const void* base, uint64_t K, uint64_t N) {
  cuuint64_t dims[3] = {64, K, N / 64}; cuuint64_t strides[2] = {N * 2, 128}; cuuint32_t box[3] = {64, 64, 2}; cuuint32_t es[3] = {1, 1, 1};
  enc(tm, CU_TENSOR_MAP_DATA_TYPE_BFLOAT16, 3, const_cast<void*>(base), dims, strides, box, es, CU_TENSOR_MAP_INTERLEAVE_NONE,
      CU_TENSOR_MAP_SWIZZLE_128B, CU_TENSOR_MAP_L2_PROMOTION_L2_256B, CU_TENSOR_MAP_FLOAT_OOB_FILL_NONE);
}

}

extern "C" void kernel_launch(void* const* d_in, const int* in_sizes, int n_in, void* d_out, int out_size) {
  (void)in_sizes; (void)n_in; (void)out_size;
  typedef const __nv_bfloat16* BP;
  BP xq = (BP)d_in[0], ak = (BP)d_in[1], av = (BP)d_in[2], shk = (BP)d_in[3], ssk = (BP)d_in[4], ssd = (BP)d_in[5];
  BP ckv = (BP)d_in[7], wq = (BP)d_in[8], wuk = (BP)d_in[9], wuv = (BP)d_in[10], wo = (BP)d_in[11], gw = (BP)d_in[12];

  static EncFn enc = nullptr;
  if (!enc) {
    cudaDriverEntryPointQueryResult qr;
    cudaGetDriverEntryPoint("cuTensorMapEncodeTiled", (void**)&enc, cudaEnableDefault, &qr);
    cudaFuncSetAttribute(mega_kernel, cudaFuncAttributeMaxDynamicSharedMemorySize, SMEM_BYTES);
  }
  Params p;
  void* yT = nullptr;
  cudaGetSymbolAddress(&yT, g_yT);
  enc2d(enc, &p.x, xq, DM, SEQ, 64, 128);
  enc2d(enc, &p.c, ckv, DC, SEQ, 64, 128);
  enc3d(enc, &p.wq, wq, DM, NH * HD);
  enc3d(enc, &p.wuk, wuk, DC, NH * HD);
  enc3d(enc, &p.wuv, wuv, DC, NH * HD);
  enc2d(enc, &p.wo, wo, DM, NH * HD, 64, 64);
  enc2d(enc, &p.y, yT, SEQ, DM, 64, 128);
  enc2d(enc, &p.out, d_out, DM, SEQ, 64, 16);
  p.xp = xq; p.gate_w = gw;

  conv_naive<<<DM, 256>>>(ak, av, shk, ssk, ssd);
  mega_kernel<<<NMAIN, NTHREADS, SMEM_BYTES>>>(p);
}
```

```cpp
#include <cuda_runtime.h>
#include <cuda.h>
#include <cuda_bf16.h>
#include <stdint.h>

namespace {

constexpr int SEQ = 2048, DM = 1024, DC = 512, NH = 32, HD = 128;
constexpr int GR = 16384;
constexpr int NGR = 14;
constexpr int SM_BAR = NGR * GR;
constexpr int SM_GATE = SM_BAR + 512;
constexpr int SMEM_BYTES = SM_GATE + 512 + 1024;
constexpr int NTHREADS = 384;
#define SM_LIMIT 1048576.f
constexpr int NMAIN = 128;

constexpr int B_FULL = 0, B_EMPTY = 14, B_EV = 28, B_DONE = 36;

__device__ __align__(1024) uint8_t g_kimg[NH * 16 * 32768];
__device__ __align__(1024) uint8_t g_vimg[NH * 16 * 32768];
__device__ __align__(1024) uint8_t g_cimg[16 * NH * 32768];
__device__ __align__(1024) __nv_bfloat16 g_yT[DM * SEQ];
__device__ __align__(1024) float g_gate[SEQ];
__device__ unsigned g_flags[128 * 8];
constexpr int F_KV = 0, F_CTX = 16, F_GATE = 48, F_EXIT = 49, F_NUM = 50;
#define FLAG(i) (&g_flags[(i) * 8])

#define TS(slot)
#define FT(it, k)

__device__ __forceinline__ uint32_t smem_u32(const void* p) { return (uint32_t)__cvta_generic_to_shared(p); }
__device__ __forceinline__ void mbar_init(uint32_t bar, int cnt) { asm volatile("mbarrier.init.shared::cta.b64 [%0], %1;" ::"r"(bar), "r"(cnt) : "memory"); }
__device__ __forceinline__ void mbar_expect_tx(uint32_t bar, uint32_t bytes) { asm volatile("mbarrier.arrive.expect_tx.shared::cta.b64 _, [%0], %1;" ::"r"(bar), "r"(bytes) : "memory"); }
__device__ __forceinline__ void mbar_arrive(uint32_t bar) { asm volatile("mbarrier.arrive.shared::cta.b64 _, [%0];" ::"r"(bar) : "memory"); }
__device__ __forceinline__ void mbar_arrive_cluster(uint32_t bar, uint32_t cta) {
  asm volatile("{\n.reg .b32 r;\nmapa.shared::cluster.u32 r, %0, %1;\nmbarrier.arrive.shared::cluster.b64 _, [r];\n}\n" ::"r"(bar), "r"(cta) : "memory");
}
__device__ __forceinline__ bool mbar_try(uint32_t bar, uint32_t parity) {
  uint32_t ok;
  asm volatile("{\n.reg .pred p;\nmbarrier.try_wait.parity.shared::cta.b64 p, [%1], %2;\nselp.u32 %0, 1, 0, p;\n}\n" : "=r"(ok) : "r"(bar), "r"(parity) : "memory");
  return ok;
}
__device__ __forceinline__ void mbar_wait(uint32_t bar, uint32_t parity) {
  asm volatile("{\n.reg .pred p;\nWAIT_LOOP:\nmbarrier.try_wait.parity.shared::cta.b64 p, [%0], %1;\n@p bra WAIT_DONE;\nbra WAIT_LOOP;\nWAIT_DONE:\n}\n" ::"r"(bar), "r"(parity) : "memory");
}
__device__ __forceinline__ void tma2d(uint32_t dst, const CUtensorMap* tm, int c0, int c1, uint32_t bar) {
  asm volatile("cp.async.bulk.tensor.2d.shared::cluster.global.mbarrier::complete_tx::bytes [%0], [%1, {%3, %4}], [%2];"
               ::"r"(dst), "l"(tm), "r"(bar), "r"(c0), "r"(c1) : "memory");
}
__device__ __forceinline__ void tma2d_mc(uint32_t dst, const CUtensorMap* tm, int c0, int c1, uint32_t bar) {
  asm volatile("cp.async.bulk.tensor.2d.shared::cluster.global.mbarrier::complete_tx::bytes.multicast::cluster [%0], [%1, {%3, %4}], [%2], %5;"
               ::"r"(dst), "l"(tm), "r"(bar), "r"(c0), "r"(c1), "h"((uint16_t)3) : "memory");
}
__device__ __forceinline__ void tma3d(uint32_t dst, const CUtensorMap* tm, int c0, int c1, int c2, uint32_t bar) {
  asm volatile("cp.async.bulk.tensor.3d.shared::cluster.global.mbarrier::complete_tx::bytes [%0], [%1, {%3, %4, %5}], [%2];"
               ::"r"(dst), "l"(tm), "r"(bar), "r"(c0), "r"(c1), "r"(c2) : "memory");
}
__device__ __forceinline__ void tma3d_mc(uint32_t dst, const CUtensorMap* tm, int c0, int c1, int c2, uint32_t bar) {
  asm volatile("cp.async.bulk.tensor.3d.shared::cluster.global.mbarrier::complete_tx::bytes.multicast::cluster [%0], [%1, {%3, %4, %5}], [%2], %6;"
               ::"r"(dst), "l"(tm), "r"(bar), "r"(c0), "r"(c1), "r"(c2), "h"((uint16_t)3) : "memory");
}
__device__ __forceinline__ void bulk_g2s(uint32_t dst, const void* src, uint32_t bytes, uint32_t bar) {
  asm volatile("cp.async.bulk.shared::cluster.global.mbarrier::complete_tx::bytes [%0], [%1], %2, [%3];"
               ::"r"(dst), "l"(src), "r"(bytes), "r"(bar) : "memory");
}
__device__ __forceinline__ void tma2d_store(const CUtensorMap* tm, uint32_t src, int c0, int c1) {
  asm volatile("cp.async.bulk.tensor.2d.global.shared::cta.bulk_group [%0, {%2, %3}], [%1];" ::"l"(tm), "r"(src), "r"(c0), "r"(c1) : "memory");
}
__device__ __forceinline__ void prefetch_tm(const CUtensorMap* tm) { asm volatile("prefetch.tensormap [%0];" ::"l"(tm) : "memory"); }
__device__ __forceinline__ void wg_fence() { asm volatile("wgmma.fence.sync.aligned;" ::: "memory"); }
__device__ __forceinline__ void wg_commit() { asm volatile("wgmma.commit_group.sync.aligned;" ::: "memory"); }
template <int N> __device__ __forceinline__ void wg_wait() { asm volatile("wgmma.wait_group.sync.aligned %0;" ::"n"(N) : "memory"); }
__device__ __forceinline__ void bar_sync(int id, int n) { asm volatile("bar.sync %0, %1;" ::"r"(id), "r"(n) : "memory"); }
__device__ __forceinline__ void bar_arrive(int id, int n) { asm volatile("bar.arrive %0, %1;" ::"r"(id), "r"(n) : "memory"); }
__device__ __forceinline__ void fence_async_smem() { asm volatile("fence.proxy.async.shared::cta;" ::: "memory"); }
__device__ __forceinline__ void fence_async_all() { asm volatile("fence.proxy.async;" ::: "memory"); }
__device__ __forceinline__ void cluster_sync() { asm volatile("barrier.cluster.arrive.release.aligned;\nbarrier.cluster.wait.acquire.aligned;" ::: "memory"); }
__device__ __forceinline__ uint32_t pack_bf16(float lo, float hi) { uint32_t r; asm("cvt.rn.bf16x2.f32 %0, %1, %2;" : "=r"(r) : "f"(hi), "f"(lo)); return r; }
__device__ __forceinline__ float ex2(float x) { float r; asm("ex2.approx.ftz.f32 %0, %1;" : "=f"(r) : "f"(x)); return r; }
__device__ __forceinline__ float bf_lo(uint32_t v) { return __uint_as_float(v << 16); }
__device__ __forceinline__ float bf_hi(uint32_t v) { return __uint_as_float(v & 0xffff0000u); }
__device__ __forceinline__ void flag_wait(const unsigned* f, unsigned target) {
  unsigned v;
  do { asm volatile("ld.acquire.gpu.global.u32 %0, [%1];" : "=r"(v) : "l"(f) : "memory"); } while (v < target);
}
__device__ __forceinline__ void flag_add(unsigned* f) {
  asm volatile("fence.acq_rel.gpu;\nred.relaxed.gpu.global.add.u32 [%0], 1;" ::"l"(f) : "memory");
}
__device__ __forceinline__ uint32_t desc_k(uint32_t addr) { return ((addr & 0x3FFFF) >> 4) | (1u << 16); }
template <int LBO> __device__ __forceinline__ uint32_t desc_mn(uint32_t addr) { return ((addr & 0x3FFFF) >> 4) | ((uint32_t)(LBO >> 4) << 16); }
#define DHI "0x40000040"

#define R8(d, o) "+f"(d[o]), "+f"(d[o + 1]), "+f"(d[o + 2]), "+f"(d[o + 3]), "+f"(d[o + 4]), "+f"(d[o + 5]), "+f"(d[o + 6]), "+f"(d[o + 7])
#define R32(d, o) R8(d, o), R8(d, o + 8), R8(d, o + 16), R8(d, o + 24)
#define R64(d, o) R32(d, o), R32(d, o + 32)
#define L64 "%0,%1,%2,%3,%4,%5,%6,%7,%8,%9,%10,%11,%12,%13,%14,%15,%16,%17,%18,%19,%20,%21,%22,%23,%24,%25,%26,%27,%28,%29,%30,%31," \
            "%32,%33,%34,%35,%36,%37,%38,%39,%40,%41,%42,%43,%44,%45,%46,%47,%48,%49,%50,%51,%52,%53,%54,%55,%56,%57,%58,%59,%60,%61,%62,%63"
#define L128 L64 ",%64,%65,%66,%67,%68,%69,%70,%71,%72,%73,%74,%75,%76,%77,%78,%79,%80,%81,%82,%83,%84,%85,%86,%87,%88,%89,%90,%91,%92,%93,%94,%95," \
            "%96,%97,%98,%99,%100,%101,%102,%103,%104,%105,%106,%107,%108,%109,%110,%111,%112,%113,%114,%115,%116,%117,%118,%119,%120,%121,%122,%123,%124,%125,%126,%127"

template <int TB> __device__ __forceinline__ void mma_ss_n128(float (&d)[64], uint32_t da, uint32_t db) {
  asm volatile("{\n.reg .b64 da, db;\nmov.b64 da, {%64, " DHI "};\nmov.b64 db, {%65, " DHI "};\n"
               "wgmma.mma_async.sync.aligned.m64n128k16.f32.bf16.bf16 {" L64 "}, da, db, 1, 1, 1, 0, %66;\n}\n"
               : R64(d, 0) : "r"(da), "r"(db), "n"(TB));
}
template <int TB> __device__ __forceinline__ void mma_rs_n128(float (&d)[64], uint32_t a0, uint32_t a1, uint32_t a2, uint32_t a3, uint32_t db, int sd) {
  asm volatile("{\n.reg .pred p;\n.reg .b64 db;\nsetp.ne.b32 p, %69, 0;\nmov.b64 db, {%68, " DHI "};\n"
               "wgmma.mma_async.sync.aligned.m64n128k16.f32.bf16.bf16 {" L64 "}, {%64,%65,%66,%67}, db, p, 1, 1, %70;\n}\n"
               : R64(d, 0) : "r"(a0), "r"(a1), "r"(a2), "r"(a3), "r"(db), "r"(sd), "n"(TB));
}
template <int TB> __device__ __forceinline__ void mma_ss_n256(float (&d)[128], uint32_t da, uint32_t db) {
  asm volatile("{\n.reg .b64 da, db;\nmov.b64 da, {%128, " DHI "};\nmov.b64 db, {%129, " DHI "};\n"
               "wgmma.mma_async.sync.aligned.m64n256k16.f32.bf16.bf16 {" L128 "}, da, db, 1, 1, 1, 0, %130;\n}\n"
               : R64(d, 0), R64(d, 64) : "r"(da), "r"(db), "n"(TB));
}
#define W8(d, o) "=f"(d[o]), "=f"(d[o + 1]), "=f"(d[o + 2]), "=f"(d[o + 3]), "=f"(d[o + 4]), "=f"(d[o + 5]), "=f"(d[o + 6]), "=f"(d[o + 7])
#define W32(d, o) W8(d, o), W8(d, o + 8), W8(d, o + 16), W8(d, o + 24)
#define W64(d, o) W32(d, o), W32(d, o + 32)
template <int TB> __device__ __forceinline__ void mma_ss_n128_init(float (&d)[64], uint32_t da, uint32_t db) {
  asm volatile("{\n.reg .b64 da, db;\nmov.b64 da, {%64, " DHI "};\nmov.b64 db, {%65, " DHI "};\n"
               "wgmma.mma_async.sync.aligned.m64n128k16.f32.bf16.bf16 {" L64 "}, da, db, 0, 1, 1, 0, %66;\n}\n"
               : W64(d, 0) : "r"(da), "r"(db), "n"(TB));
}
template <int TB> __device__ __forceinline__ void mma_ss_n256_init(float (&d)[128], uint32_t da, uint32_t db) {
  asm volatile("{\n.reg .b64 da, db;\nmov.b64 da, {%128, " DHI "};\nmov.b64 db, {%129, " DHI "};\n"
               "wgmma.mma_async.sync.aligned.m64n256k16.f32.bf16.bf16 {" L128 "}, da, db, 0, 1, 1, 0, %130;\n}\n"
               : W64(d, 0), W64(d, 64) : "r"(da), "r"(db), "n"(TB));
}
template <int N> __device__ __forceinline__ void reg_fence(float (&d)[N]) {
#pragma unroll
  for (int i = 0; i < N; i++) asm volatile("" : "+f"(d[i])::"memory");
}
template <int N> __device__ __forceinline__ void reg_fence(uint32_t (&d)[N]) {
#pragma unroll
  for (int i = 0; i < N; i++) asm volatile("" : "+r"(d[i])::"memory");
}

struct __align__(64) Params {
  CUtensorMap x, c, wq, wuk, wuv, wo, y, out;
  const __nv_bfloat16* xp;
  const __nv_bfloat16* gate_w;
};

template <int O, int N, bool SMEM>
__device__ __forceinline__ void store_img(const float (&acc)[N], float s0, float s1, uint8_t* gbase, uint32_t sbase, int row, int t) {
  const int g = row & 7;
#pragma unroll
  for (int a = 0; a < 4; a++) {
    const uint32_t off = (a >> 1) * 16384 + row * 128 + ((((a & 1) * 4 + t) ^ g) << 4);
#pragma unroll
    for (int h = 0; h < 2; h++) {
      const float s = h ? s1 : s0;
      uint32_t v0 = pack_bf16(acc[O + 16 * a + 2 * h] * s, acc[O + 16 * a + 2 * h + 1] * s);
      uint32_t v1 = pack_bf16(acc[O + 16 * a + 4 + 2 * h] * s, acc[O + 16 * a + 4 + 2 * h + 1] * s);
      uint32_t v2 = pack_bf16(acc[O + 16 * a + 8 + 2 * h] * s, acc[O + 16 * a + 8 + 2 * h + 1] * s);
      uint32_t v3 = pack_bf16(acc[O + 16 * a + 12 + 2 * h] * s, acc[O + 16 * a + 12 + 2 * h + 1] * s);
      if (SMEM) asm volatile("st.shared.v4.b32 [%0], {%1,%2,%3,%4};" ::"r"(sbase + off + h * 1024), "r"(v0), "r"(v1), "r"(v2), "r"(v3) : "memory");
      else asm volatile("st.global.v4.b32 [%0], {%1,%2,%3,%4};" ::"l"(gbase + off + h * 1024), "r"(v0), "r"(v1), "r"(v2), "r"(v3) : "memory");
    }
  }
}

struct Cons {
  uint32_t sb;
  uint32_t pf;
  uint32_t rank;
  int wg, tid;
  __device__ __forceinline__ void wait_full(int g) { mbar_wait(sb + SM_BAR + (B_FULL + g) * 8, (pf >> g) & 1); pf ^= 1u << g; }
  __device__ __forceinline__ void release(int g, int n, bool cross) {
    if (tid < 2 * n) mbar_arrive_cluster(sb + SM_BAR + (B_EMPTY + g + (tid >> 1)) * 8, cross ? (uint32_t)(tid & 1) : rank);
  }
  __device__ __forceinline__ void turn_begin() { bar_sync(1 + wg, 256); }
  __device__ __forceinline__ void turn_end() { bar_arrive(2 - wg, 256); }
  __device__ __forceinline__ void event(int e) { __syncwarp(); if ((tid & 31) == 0) mbar_arrive(sb + SM_BAR + (B_EV + e) * 8); }
};

constexpr float SM_C = 0.08838834764831845f * 1.4426950408889634f;
struct SoftState { float m0, m1, n0, n1, l0, l1; };
template <int Q> __device__ __forceinline__ void exp_quarter(const float (&S)[64], float (&e)[16], const SoftState& z, float& s0, float& s1) {
#pragma unroll
  for (int i = 0; i < 16; i++) e[i] = ex2(fmaf(S[16 * Q + i], SM_C, (i & 2) ? z.n1 : z.n0));
#pragma unroll
  for (int i = 0; i < 16; i += 4) { s0 += e[i]; s1 += e[i + 2]; s0 += e[i + 1]; s1 += e[i + 3]; }
}
template <int Q> __device__ __forceinline__ void pack_quarter(const float (&e)[16], uint32_t (&P)[32]) {
#pragma unroll
  for (int i = 0; i < 8; i++) P[8 * Q + i] = pack_bf16(e[2 * i], e[2 * i + 1]);
}
__device__ __forceinline__ void update_max(const float (&S)[64], SoftState& z, float& sc0, float& sc1) {
  float a0 = fmaxf(S[0], S[1]), a1 = fmaxf(S[2], S[3]), b0 = fmaxf(S[4], S[5]), b1 = fmaxf(S[6], S[7]);
#pragma unroll
  for (int j = 2; j < 16; j += 2) {
    a0 = fmaxf(a0, fmaxf(S[4 * j], S[4 * j + 1]));
    a1 = fmaxf(a1, fmaxf(S[4 * j + 2], S[4 * j + 3]));
    b0 = fmaxf(b0, fmaxf(S[4 * j + 4], S[4 * j + 5]));
    b1 = fmaxf(b1, fmaxf(S[4 * j + 6], S[4 * j + 7]));
  }
  a0 = fmaxf(a0, b0); a1 = fmaxf(a1, b1);
  a0 = fmaxf(a0, __shfl_xor_sync(0xffffffffu, a0, 1)); a1 = fmaxf(a1, __shfl_xor_sync(0xffffffffu, a1, 1));
  a0 = fmaxf(a0, __shfl_xor_sync(0xffffffffu, a0, 2)); a1 = fmaxf(a1, __shfl_xor_sync(0xffffffffu, a1, 2));
  a0 = fmaxf(a0, z.m0); a1 = fmaxf(a1, z.m1);
  sc0 = ex2((z.m0 - a0) * SM_C); sc1 = ex2((z.m1 - a1) * SM_C);
  z.m0 = a0; z.m1 = a1;
  z.n0 = -a0 * SM_C; z.n1 = -a1 * SM_C;
}
__device__ __forceinline__ void exp_all(const float (&S)[64], uint32_t (&P)[32], const SoftState& z, float& s0, float& s1) {
  float e[16];
  exp_quarter<0>(S, e, z, s0, s1); pack_quarter<0>(e, P);
  exp_quarter<1>(S, e, z, s0, s1); pack_quarter<1>(e, P);
  exp_quarter<2>(S, e, z, s0, s1); pack_quarter<2>(e, P);
  exp_quarter<3>(S, e, z, s0, s1); pack_quarter<3>(e, P);
}
__device__ __forceinline__ void pin(float a, uint32_t never_zero) {
  asm volatile("{\n.reg .pred p;\nsetp.eq.u32 p, %1, 0;\n@p st.shared.f32 [%1], %0;\n}\n" ::"f"(a), "r"(never_zero) : "memory");
}
template <int O, int N> __device__ __forceinline__ void reg_fence_part(uint32_t (&d)[32]) {
#pragma unroll
  for (int i = O; i < O + N; i++) asm volatile("" : "+r"(d[i])::"memory");
}
__device__ __forceinline__ void mask_diag(float (&S)[64], int row, int t) {
  const int d = row - 2 * t;
#pragma unroll
  for (int j = 0; j < 16; j++) {
    if (8 * j > d) S[4 * j] = -INFINITY;
    if (8 * j + 1 > d) S[4 * j + 1] = -INFINITY;
    if (8 * j > d + 8) S[4 * j + 2] = -INFINITY;
    if (8 * j + 1 > d + 8) S[4 * j + 3] = -INFINITY;
  }
}
__device__ __forceinline__ float quad_sum(float v) {
  v += __shfl_xor_sync(0xffffffffu, v, 1);
  v += __shfl_xor_sync(0xffffffffu, v, 2);
  return v;
}
__device__ __forceinline__ void issue_qk(float (&S)[64], uint32_t dq, uint32_t dk) {
  mma_ss_n128_init<0>(S, dq, dk);
#pragma unroll
  for (int s = 1; s < 8; s++) mma_ss_n128<0>(S, dq + (s >> 2) * 1024 + (s & 3) * 2, dk + (s >> 2) * 1024 + (s & 3) * 2);
}
__device__ __forceinline__ void issue_pv(float (&O)[64], const uint32_t (&P)[32], uint32_t dv, int acc) {
#pragma unroll
  for (int s = 0; s < 8; s++) {
    mma_rs_n128<1>(O, P[4 * s], P[4 * s + 1], P[4 * s + 2], P[4 * s + 3], dv + s * 128, s != 0 ? 1 : acc);
    if (s & 1) wg_commit();
  }
}

__global__ void __cluster_dims__(2, 1, 1) __launch_bounds__(NTHREADS, 1) mega_kernel(const __grid_constant__ Params p) {
  extern __shared__ uint8_t smem_raw[];
  const uint32_t sb = (smem_u32(smem_raw) + 1023) & ~1023u;
  const int wgi = __shfl_sync(0xffffffffu, threadIdx.x >> 7, 0);
  const int warp = __shfl_sync(0xffffffffu, threadIdx.x >> 5, 0);
  const uint32_t rank = blockIdx.x & 1;
  const int cl = blockIdx.x >> 1;
  const int grp = cl >> 3, idx = cl & 7;

  if (threadIdx.x == 0) {
    for (int i = 0; i < NGR; i++) { mbar_init(sb + SM_BAR + (B_FULL + i) * 8, 1); mbar_init(sb + SM_BAR + (B_EMPTY + i) * 8, 4); }
    for (int i = 0; i < 8; i++) mbar_init(sb + SM_BAR + (B_EV + i) * 8, 8);
    mbar_init(sb + SM_BAR + B_DONE * 8, 11);
    asm volatile("fence.mbarrier_init.release.cluster;" ::: "memory");
    prefetch_tm(&p.c); prefetch_tm(&p.wuk); prefetch_tm(&p.wuv); prefetch_tm(&p.x); prefetch_tm(&p.wq);
  }
  cluster_sync();
  TS(0);

  if (wgi == 0) {
    asm volatile("setmaxnreg.dec.sync.aligned.u32 40;");
    const int lane = threadIdx.x & 31;
    if (warp == 0) {
      if (lane == 0) {
        uint32_t pe = 0x3FFC;
        auto acquire = [&](int g) { mbar_wait(sb + SM_BAR + (B_EMPTY + g) * 8, (pe >> g) & 1); pe ^= 1u << g; };
#pragma unroll 1
        for (int rnd = 0; rnd < 2; rnd++) {
          const int hp = 16 * rnd + 2 * grp;
#pragma unroll 1
          for (int kk = 0; kk < 16; kk++) {
            const int g0 = 2 + 3 * (kk & 3), kb = kk & 7, head = hp + (kk >> 3);
            acquire(g0); acquire(g0 + 1); acquire(g0 + 2);
            const uint32_t fb = sb + SM_BAR + (B_FULL + g0) * 8;
            mbar_expect_tx(fb, 3 * GR);
            tma2d(sb + g0 * GR, &p.c, kb * 64, (2 * idx + rank) * 128, fb);
            tma3d_mc(sb + (g0 + 1 + rank) * GR, rank ? &p.wuv : &p.wuk, 0, kb * 64, head * 2, fb);
          }
          const int head = hp + rank;
#pragma unroll 1
          for (int kb = 0; kb < 16; kb++) {
            const int g0 = 2 + 3 * (kb & 3);
            acquire(g0); acquire(g0 + 1); acquire(g0 + 2);
            const uint32_t fb = sb + SM_BAR + (B_FULL + g0) * 8;
            mbar_expect_tx(fb, 3 * GR);
            tma2d_mc(sb + (g0 + rank) * GR, &p.x, kb * 64, (rank ? idx : 15 - idx) * 128, fb);
            tma3d(sb + (g0 + 2) * GR, &p.wq, 0, kb * 64, head * 2, fb);
          }
          flag_wait(FLAG(F_KV + rnd * 8 + grp), 16);
          fence_async_all();
          acquire(2); acquire(3);
          const int nA = 16 - idx;
          int slot = 1;
#pragma unroll 1
          for (int f = 0; f < 34; f++) {
            const bool isk = (f == 0) || ((f & 1) && f < 33);
            const int it = (f == 0) ? 0 : (f == 33) ? 16 : isk ? (f + 1) >> 1 : (f >> 1) - 1;
            const int blk = it < nA ? it : 16 - it;
            const int g0 = 4 + 2 * slot;
            acquire(g0); acquire(g0 + 1);
            const uint32_t fb = sb + SM_BAR + (B_FULL + g0) * 8;
            mbar_expect_tx(fb, 2 * GR);
            bulk_g2s(sb + g0 * GR, (isk ? g_kimg : g_vimg) + (size_t)(head * 16 + blk) * 32768, 2 * GR, fb);
            slot = slot == 4 ? 0 : slot + 1;
          }
        }
        const int rt = 2 * idx + rank, ct = grp;
        int st = 1;
#pragma unroll 1
        for (int kb = 0; kb < 66; kb++) {
          if (kb == 0 || kb == 32) { flag_wait(FLAG(F_CTX + rt * 2 + (kb >> 5)), 16); fence_async_all(); }
          const int g0 = 2 * st;
          acquire(g0); acquire(g0 + 1);
          const uint32_t fb = sb + SM_BAR + (B_FULL + g0) * 8;
          if (kb < 64) {
            mbar_expect_tx(fb, 2 * GR);
            bulk_g2s(sb + g0 * GR, g_cimg + (size_t)(rt * 64 + kb) * GR, GR, fb);
            tma2d_mc(sb + (g0 + 1) * GR + rank * 8192, &p.wo, ct * 128 + rank * 64, kb * 64, fb);
          } else if (kb == 64) {
            mbar_expect_tx(fb, 2 * GR);
            tma2d(sb + g0 * GR, &p.x, ct * 128, rt * 128, fb);
            tma2d(sb + (g0 + 1) * GR, &p.x, ct * 128 + 64, rt * 128, fb);
          } else {
            flag_wait(FLAG(F_GATE), 2 * NMAIN);
            fence_async_all();
            mbar_expect_tx(fb, 2 * GR + 512);
            tma2d(sb + g0 * GR, &p.y, rt * 128, ct * 128, fb);
            tma2d(sb + (g0 + 1) * GR, &p.y, rt * 128 + 64, ct * 128, fb);
            bulk_g2s(sb + SM_GATE, g_gate + rt * 128, 512, fb);
          }
          st = st == 6 ? 0 : st + 1;
        }
        mbar_arrive(sb + SM_BAR + B_DONE * 8);
      }
    } else if (warp == 1) {
      if (lane == 0) {
#pragma unroll 1
        for (int e = 0; e < 6; e++) {
          mbar_wait(sb + SM_BAR + (B_EV + e) * 8, 0);
          const int rnd = e / 3, k = e % 3;
          flag_add(k == 0 ? FLAG(F_KV + rnd * 8 + grp) : FLAG(F_CTX + (k == 1 ? 15 - idx : idx) * 2 + rnd));
        }
        mbar_arrive(sb + SM_BAR + B_DONE * 8);
      }
    } else {
      const uint4* gw = reinterpret_cast<const uint4*>(p.gate_w);
#pragma unroll 1
      for (int r = 0; r < 8; r++) {
        const int row = blockIdx.x * 16 + (warp - 2) * 8 + r;
        const uint4* xr = reinterpret_cast<const uint4*>(p.xp + (size_t)row * DM);
        float s = 0.f;
#pragma unroll 2
        for (int i = 0; i < 4; i++) {
          const uint4 a = __ldg(xr + lane + 32 * i), b = __ldg(gw + lane + 32 * i);
          s += bf_lo(a.x) * bf_lo(b.x) + bf_hi(a.x) * bf_hi(b.x) + bf_lo(a.y) * bf_lo(b.y) + bf_hi(a.y) * bf_hi(b.y);
          s += bf_lo(a.z) * bf_lo(b.z) + bf_hi(a.z) * bf_hi(b.z) + bf_lo(a.w) * bf_lo(b.w) + bf_hi(a.w) * bf_hi(b.w);
        }
#pragma unroll
        for (int o = 16; o > 0; o >>= 1) s += __shfl_xor_sync(0xffffffffu, s, o);
        if (lane == 0) g_gate[row] = 1.f / (1.f + __expf(-s));
      }
      if (lane == 0) {
        flag_add(FLAG(F_GATE));
        if (warp == 2) mbar_arrive(sb + SM_BAR + B_DONE * 8);
        else {
          unsigned long long t0, t1;
          asm volatile("mov.u64 %0, %globaltimer;" : "=l"(t0));
          while (!mbar_try(sb + SM_BAR + B_DONE * 8, 0)) {
            asm volatile("mov.u64 %0, %globaltimer;" : "=l"(t1));
            if (t1 - t0 > 2000000000ull) __trap();
          }
          __threadfence();
          if (atomicAdd(FLAG(F_EXIT), 1) == gridDim.x - 1) {
            for (int i = 0; i < F_NUM; i++) *FLAG(i) = 0;
          }
        }
      }
    }
    __syncwarp();
    cluster_sync();
  } else {
    asm volatile("setmaxnreg.inc.sync.aligned.u32 232;");
    Cons c;
    c.sb = sb; c.pf = 0; c.rank = rank; c.wg = wgi - 1; c.tid = threadIdx.x & 127;
    const int lane = threadIdx.x & 31, t = lane & 3;
    const int row = c.wg * 64 + (warp & 3) * 16 + (lane >> 2);
    constexpr uint32_t DG = GR >> 4;
    const uint32_t dkk = desc_k(sb), dk0 = dkk + c.wg * 512, dm0 = desc_mn<8192>(sb), dv0 = desc_mn<16384>(sb);
    if (c.wg == 1) bar_arrive(1, 256);
    uint32_t q2par = 1;

#pragma unroll 1
    for (int rnd = 0; rnd < 2; rnd++) {
      const int hp = 16 * rnd + 2 * grp;
#pragma unroll 1
      for (int tile = 0; tile < 2; tile++) {
        float acc[128];
        {
          c.wait_full(2);
          const uint32_t a = dk0 + 2 * DG, b = dm0 + 3 * DG;
          c.turn_begin();
          wg_fence();
          mma_ss_n256_init<1>(acc, a, b);
#pragma unroll
          for (int k = 1; k < 4; k++) mma_ss_n256<1>(acc, a + k * 2, b + k * 128);
          wg_commit();
          c.turn_end();
        }
#pragma unroll 1
        for (int kb = 1; kb < 8; kb++) {
          const int g0 = 2 + 3 * (kb & 3);
          c.wait_full(g0);
          const uint32_t a = dk0 + g0 * DG, b = dm0 + (g0 + 1) * DG;
          c.turn_begin();
          wg_fence();
#pragma unroll
          for (int k = 0; k < 4; k++) mma_ss_n256<1>(acc, a + k * 2, b + k * 128);
          wg_commit();
          c.turn_end();
          wg_wait<1>();
          c.release(2 + 3 * ((kb - 1) & 3), 3, true);
        }
        wg_wait<0>();
        reg_fence(acc);
        c.release(11, 3, true);
        const size_t o = (size_t)((hp + tile) * 16 + 2 * idx + rank) * 32768;
        store_img<0, 128, false>(acc, 1.f, 1.f, g_kimg + o, 0, row, t);
        store_img<64, 128, false>(acc, 1.f, 1.f, g_vimg + o, 0, row, t);
      }
      c.event(rnd * 3);
      TS(1 + rnd * 3);
      {
        float qa[64], qb[64];
        {
          c.wait_full(2);
          const uint32_t a = dk0 + 2 * DG, b = dm0 + 4 * DG;
          c.turn_begin();
          wg_fence();
          mma_ss_n128_init<1>(qa, a, b);
          mma_ss_n128_init<1>(qb, a + DG, b);
#pragma unroll
          for (int k = 1; k < 4; k++) {
            mma_ss_n128<1>(qa, a + k * 2, b + k * 128);
            mma_ss_n128<1>(qb, a + DG + k * 2, b + k * 128);
          }
          wg_commit();
          c.turn_end();
        }
#pragma unroll 1
        for (int kb = 1; kb < 16; kb++) {
          const int g0 = 2 + 3 * (kb & 3);
          c.wait_full(g0);
          const uint32_t a = dk0 + g0 * DG, b = dm0 + (g0 + 2) * DG;
          c.turn_begin();
          wg_fence();
#pragma unroll
          for (int k = 0; k < 4; k++) {
            mma_ss_n128<1>(qa, a + k * 2, b + k * 128);
            mma_ss_n128<1>(qb, a + DG + k * 2, b + k * 128);
          }
          wg_commit();
          c.turn_end();
          wg_wait<1>();
          c.release(2 + 3 * ((kb - 1) & 3), 3, true);
        }
        wg_wait<0>();
        reg_fence(qa); reg_fence(qb);
        c.release(11, 3, true);
        mbar_wait(sb + SM_BAR + (B_EMPTY + 2) * 8, q2par);
        mbar_wait(sb + SM_BAR + (B_EMPTY + 3) * 8, q2par);
        q2par ^= 1;
        store_img<0, 64, true>(qa, 1.f, 1.f, nullptr, sb + 2 * GR, row, t);
        store_img<0, 64, true>(qb, 1.f, 1.f, nullptr, sb, row, t);
        fence_async_smem();
        bar_sync(3 + c.wg, 128);
      }
      TS(2 + rnd * 3);
      {
        const int head = hp + rank, nA = 16 - idx;
        float O[64], S[64];
        uint32_t P[32];
        SoftState z;
        z.m0 = z.m1 = -INFINITY; z.l0 = z.l1 = 0.f;
        int slot = 1;
        auto nxt = [](int s) { return s == 4 ? 0 : s + 1; };
        {
          const int g0 = 4 + 2 * slot;
          c.wait_full(g0);
          c.turn_begin();
          wg_fence();
          issue_qk(S, dk0 + 2 * DG, dkk + g0 * DG);
          wg_commit();
          c.turn_end();
#pragma unroll
          for (int i = 0; i < 64; i++) O[i] = 0.f;
          wg_wait<0>();
          reg_fence(S);
          c.release(g0, 2, true);
          float sc0, sc1;
          update_max(S, z, sc0, sc1);
          exp_all(S, P, z, z.l0, z.l1);
          slot = nxt(slot);
        }
#pragma unroll 1
        for (int it = 1; it <= 16; it++) {
          const int gk = 4 + 2 * slot; slot = nxt(slot);
          const int gv = 4 + 2 * slot; slot = nxt(slot);
          FT(it, 0);
          c.wait_full(gk);
          c.wait_full(gv);
          FT(it, 1);
          const uint32_t q = dk0 + (it < nA ? 2 * DG : 0);
          c.turn_begin();
          FT(it, 2);
          wg_fence();
          issue_qk(S, q, dkk + gk * DG);
          wg_commit();
          issue_pv(O, P, dv0 + gv * DG, (it != 1 && it != nA + 1));
          c.turn_end();
          FT(it, 3);
          wg_wait<4>();
          reg_fence(S);
          FT(it, 4);
          c.release(gk, 2, true);
          if (it == nA - 1) c.release(2, 2, true);
          if (it == 16 && rnd == 1) c.release(0, 2, true);
          float i0, i1;
          if (it == nA - 1 || it == nA) {
            mask_diag(S, row, t);
            if (it == nA) {
              i0 = 1.f / quad_sum(z.l0); i1 = 1.f / quad_sum(z.l1);
              z.m0 = z.m1 = -INFINITY; z.l0 = z.l1 = 0.f;
              float sc0, sc1;
              update_max(S, z, sc0, sc1);
            }
          }
          float s0 = 0.f, s1 = 0.f;
          {
            float e[16];
            exp_quarter<0>(S, e, z, s0, s1); pin(s1, sb); wg_wait<3>(); reg_fence_part<0, 8>(P); pack_quarter<0>(e, P);
            exp_quarter<1>(S, e, z, s0, s1); pin(s1, sb); wg_wait<2>(); reg_fence_part<8, 8>(P); pack_quarter<1>(e, P);
            exp_quarter<2>(S, e, z, s0, s1); pin(s1, sb); wg_wait<1>(); reg_fence_part<16, 8>(P); pack_quarter<2>(e, P);
            exp_quarter<3>(S, e, z, s0, s1); pin(s1, sb); wg_wait<0>(); reg_fence_part<24, 8>(P); reg_fence(O); pack_quarter<3>(e, P);
          }
          FT(it, 5);
          c.release(gv, 2, true);
          if (it == nA) {
            store_img<0, 64, false>(O, i0, i1, g_cimg + (size_t)((15 - idx) * 32 + head) * 32768, 0, row, t);
            c.event(rnd * 3 + 1);
          } else if (__any_sync(0xffffffffu, !(s0 + s1 <= SM_LIMIT))) {
            float sc0, sc1;
            update_max(S, z, sc0, sc1);
            z.l0 *= sc0; z.l1 *= sc1;
#pragma unroll
            for (int j = 0; j < 16; j++) { O[4 * j] *= sc0; O[4 * j + 1] *= sc0; O[4 * j + 2] *= sc1; O[4 * j + 3] *= sc1; }
            s0 = 0.f; s1 = 0.f;
            exp_all(S, P, z, s0, s1);
          }
          z.l0 += s0; z.l1 += s1;
          FT(it, 6);
        }
        {
          const int gv = 4 + 2 * slot;
          c.wait_full(gv);
          c.turn_begin();
          wg_fence();
          issue_pv(O, P, dv0 + gv * DG, nA != 16);
          c.turn_end();
          wg_wait<0>();
          reg_fence(O); reg_fence(P);
          c.release(gv, 2, true);
          store_img<0, 64, false>(O, 1.f / quad_sum(z.l0), 1.f / quad_sum(z.l1), g_cimg + (size_t)(idx * 32 + head) * 32768, 0, row, t);
          c.event(rnd * 3 + 2);
        }
      }
      TS(3 + rnd * 3);
    }
    if (c.wg == 0) bar_sync(1, 256);
    {
      const int rt = 2 * idx + rank, ct = grp;
      float acc[64];
      int st = 2, pst = 1;
      {
        c.wait_full(2);
        const uint32_t a = dk0 + 2 * DG, b = dm0 + 3 * DG;
        wg_fence();
        mma_ss_n128_init<1>(acc, a, b);
#pragma unroll
        for (int k = 1; k < 4; k++) mma_ss_n128<1>(acc, a + k * 2, b + k * 128);
        wg_commit();
      }
#pragma unroll 1
      for (int kb = 1; kb < 64; kb++) {
        const int g0 = 2 * st;
        c.wait_full(g0);
        const uint32_t a = dk0 + g0 * DG, b = dm0 + (g0 + 1) * DG;
        wg_fence();
#pragma unroll
        for (int k = 0; k < 4; k++) mma_ss_n128<1>(acc, a + k * 2, b + k * 128);
        wg_commit();
        wg_wait<1>();
        if (kb <= 59) c.release(2 * pst, 2, true);
        pst = st;
        st = st == 6 ? 0 : st + 1;
      }
      wg_wait<0>();
      reg_fence(acc);
      TS(7);
      const uint32_t xs = sb + 2 * st * GR;
      c.wait_full(2 * st);
      st = st == 6 ? 0 : st + 1;
      const uint32_t ys = sb + 2 * st * GR;
      c.wait_full(2 * st);
      float g0, g1;
      asm volatile("ld.shared.f32 %0, [%1];" : "=f"(g0) : "r"(sb + SM_GATE + row * 4));
      asm volatile("ld.shared.f32 %0, [%1];" : "=f"(g1) : "r"(sb + SM_GATE + row * 4 + 32));
      const int mi = lane >> 3, lr = lane & 7, w = warp & 3;
#pragma unroll
      for (int jj = 0; jj < 8; jj++) {
        const int j = 2 * jj + (mi >> 1);
        const uint32_t xa = xs + (jj >> 2) * 16384 + (c.wg * 64 + w * 16 + (mi & 1) * 8 + lr) * 128 + (((j & 7) ^ lr) << 4);
        const uint32_t ya = ys + c.wg * 16384 + (8 * j + lr) * 128 + (((2 * w + (mi & 1)) ^ lr) << 4);
        uint32_t x[4], y[4], o[4];
        asm volatile("ldmatrix.sync.aligned.m8n8.x4.shared.b16 {%0,%1,%2,%3}, [%4];" : "=r"(x[0]), "=r"(x[1]), "=r"(x[2]), "=r"(x[3]) : "r"(xa) : "memory");
        asm volatile("ldmatrix.sync.aligned.m8n8.x4.trans.shared.b16 {%0,%1,%2,%3}, [%4];" : "=r"(y[0]), "=r"(y[1]), "=r"(y[2]), "=r"(y[3]) : "r"(ya) : "memory");
#pragma unroll
        for (int i = 0; i < 4; i++) {
          const float g = (i & 1) ? g1 : g0;
          const float b0 = acc[8 * jj + 2 * i], b1 = acc[8 * jj + 2 * i + 1];
          o[i] = pack_bf16(fmaf(g, bf_lo(x[i]) * bf_lo(y[i]) - b0, b0), fmaf(g, bf_hi(x[i]) * bf_hi(y[i]) - b1, b1));
        }
        asm volatile("stmatrix.sync.aligned.m8n8.x4.shared.b16 [%0], {%1,%2,%3,%4};" ::"r"(xa), "r"(o[0]), "r"(o[1]), "r"(o[2]), "r"(o[3]) : "memory");
      }
      fence_async_smem();
      __syncwarp();
      if (lane == 0) {
        const int r0 = c.wg * 64 + w * 16;
        tma2d_store(&p.out, xs + r0 * 128, ct * 128, rt * 128 + r0);
        tma2d_store(&p.out, xs + 16384 + r0 * 128, ct * 128 + 64, rt * 128 + r0);
        asm volatile("cp.async.bulk.commit_group;\ncp.async.bulk.wait_group 0;" ::: "memory");
        mbar_arrive(sb + SM_BAR + B_DONE * 8);
      }
      __syncwarp();
      TS(8);
    }
    cluster_sync();
  }
}

__global__ void __launch_bounds__(256) conv_naive(const __nv_bfloat16* __restrict__ k, const __nv_bfloat16* __restrict__ v,
                                                  const __nv_bfloat16* __restrict__ shiftk, const __nv_bfloat16* __restrict__ h,
                                                  const __nv_bfloat16* __restrict__ dvec) {
  __shared__ float su[SEQ], sh[SEQ];
  const int ch = blockIdx.x;
  for (int s = threadIdx.x; s < SEQ; s += 256) {
    float a = 0.f;
    for (int j = 3; j >= 0; j--) if (s - j >= 0) a += __bfloat162float(k[(size_t)(s - j) * DM + ch]) * __bfloat162float(shiftk[ch * 4 + j]);
    su[s] = __bfloat162float(__float2bfloat16(a * __bfloat162float(v[(size_t)s * DM + ch])));
    sh[s] = __bfloat162float(h[(size_t)ch * SEQ + s]);
  }
  __syncthreads();
  const float dd = __bfloat162float(dvec[ch]);
  for (int s = threadIdx.x; s < SEQ; s += 256) {
    float a = su[s] * dd;
    for (int j = 0; j <= s; j++) a += sh[j] * su[s - j];
    g_yT[(size_t)ch * SEQ + s] = __float2bfloat16(a);
  }
}

typedef CUresult (*EncFn)(CUtensorMap*, CUtensorMapDataType, cuuint32_t, void*, const cuuint64_t*, const cuuint64_t*, const cuuint32_t*,
                          const cuuint32_t*, CUtensorMapInterleave, CUtensorMapSwizzle, CUtensorMapL2promotion, CUtensorMapFloatOOBfill);

void enc2d(EncFn enc, CUtensorMap* tm, const void* base, uint64_t cols, uint64_t rows, uint32_t bc, uint32_t br) {
  cuuint64_t dims[2] = {cols, rows}; cuuint64_t strides[1] = {cols * 2}; cuuint32_t box[2] = {bc, br}; cuuint32_t es[2] = {1, 1};
  enc(tm, CU_TENSOR_MAP_DATA_TYPE_BFLOAT16, 2, const_cast<void*>(base), dims, strides, box, es, CU_TENSOR_MAP_INTERLEAVE_NONE,
      CU_TENSOR_MAP_SWIZZLE_128B, CU_TENSOR_MAP_L2_PROMOTION_L2_256B, CU_TENSOR_MAP_FLOAT_OOB_FILL_NONE);
}
void enc3d(EncFn enc, CUtensorMap* tm, const void* base, uint64_t K, uint64_t N) {
  cuuint64_t dims[3] = {64, K, N / 64}; cuuint64_t strides[2] = {N * 2, 128}; cuuint32_t box[3] = {64, 64, 2}; cuuint32_t es[3] = {1, 1, 1};
  enc(tm, CU_TENSOR_MAP_DATA_TYPE_BFLOAT16, 3, const_cast<void*>(base), dims, strides, box, es, CU_TENSOR_MAP_INTERLEAVE_NONE,
      CU_TENSOR_MAP_SWIZZLE_128B, CU_TENSOR_MAP_L2_PROMOTION_L2_256B, CU_TENSOR_MAP_FLOAT_OOB_FILL_NONE);
}

}

extern "C" void kernel_launch(void* const* d_in, const int* in_sizes, int n_in, void* d_out, int out_size) {
  (void)in_sizes; (void)n_in; (void)out_size;
  typedef const __nv_bfloat16* BP;
  BP xq = (BP)d_in[0], ak = (BP)d_in[1], av = (BP)d_in[2], shk = (BP)d_in[3], ssk = (BP)d_in[4], ssd = (BP)d_in[5];
  BP ckv = (BP)d_in[7], wq = (BP)d_in[8], wuk = (BP)d_in[9], wuv = (BP)d_in[10], wo = (BP)d_in[11], gw = (BP)d_in[12];

  static EncFn enc = nullptr;
  if (!enc) {
    cudaDriverEntryPointQueryResult qr;
    cudaGetDriverEntryPoint("cuTensorMapEncodeTiled", (void**)&enc, cudaEnableDefault, &qr);
    cudaFuncSetAttribute(mega_kernel, cudaFuncAttributeMaxDynamicSharedMemorySize, SMEM_BYTES);
  }
  Params p;
  void* yT = nullptr;
  cudaGetSymbolAddress(&yT, g_yT);
  enc2d(enc, &p.x, xq, DM, SEQ, 64, 128);
  enc2d(enc, &p.c, ckv, DC, SEQ, 64, 128);
  enc3d(enc, &p.wq, wq, DM, NH * HD);
  enc3d(enc, &p.wuk, wuk, DC, NH * HD);
  enc3d(enc, &p.wuv, wuv, DC, NH * HD);
  enc2d(enc, &p.wo, wo, DM, NH * HD, 64, 64);
  enc2d(enc, &p.y, yT, SEQ, DM, 64, 128);
  enc2d(enc, &p.out, d_out, DM, SEQ, 64, 16);
  p.xp = xq; p.gate_w = gw;

  conv_naive<<<DM, 256>>>(ak, av, shk, ssk, ssd);
  mega_kernel<<<NMAIN, NTHREADS, SMEM_BYTES>>>(p);
}
```

```cpp
#include <cuda_runtime.h>
#include <cuda.h>
#include <cuda_bf16.h>
#include <stdint.h>

namespace {

constexpr int SEQ = 2048, DM = 1024, DC = 512, NH = 32, HD = 128;
constexpr int GR = 16384;
constexpr int NGR = 14;
constexpr int SM_BAR = NGR * GR;
constexpr int SM_GATE = SM_BAR + 512;
constexpr int SMEM_BYTES = SM_GATE + 512 + 1024;
constexpr int NTHREADS = 384;
#define SM_LIMIT 1048576.f
constexpr int NMAIN = 128;

constexpr int B_FULL = 0, B_EMPTY = 14, B_EV = 28, B_DONE = 34;

__device__ __align__(1024) uint8_t g_kimg[NH * 16 * 32768];
__device__ __align__(1024) uint8_t g_vimg[NH * 16 * 32768];
__device__ __align__(1024) uint8_t g_cimg[16 * NH * 32768];
__device__ __align__(1024) __nv_bfloat16 g_yT[DM * SEQ];
__device__ __align__(1024) float g_gate[SEQ];
constexpr int WSTRIDE = 8832, WBYTES = 8736;
__device__ __align__(1024) uint8_t g_w[DM * WSTRIDE];
__device__ unsigned g_flags[128 * 8];
constexpr int F_KV = 0, F_CTX = 16, F_U = 48, F_Y = 64, F_GATE = 72, F_EXIT = 73, F_NUM = 74;
#define FLAG(i) (&g_flags[(i) * 8])

#define TS(slot)
#define TSW(slot)
#define FT(i)
#define FINE_EXTRA 0

#define ST_PZ 2048
#define ST_OUT 1
#define QFLUSH 4
#define FINE_MODE 0
#define FINE_RND 1
#define FTA(i) do { if (FINE_MODE == 0) FT(i); } while (0)
#define FTG(i) do { if ((FINE_MODE == 1 || (FINE_MODE == 3 && c.wg == 0)) && rnd == FINE_RND) FT(i); } while (0)
#define FTP(i)
#define FTM(i) do { if (FINE_MODE == 4) FT(i); } while (0)
#define FTO(i) do { if (FINE_MODE == 2) FT(i); } while (0)

__device__ __forceinline__ uint32_t smem_u32(const void* p) { return (uint32_t)__cvta_generic_to_shared(p); }
__device__ __forceinline__ void mbar_init(uint32_t bar, int cnt) { asm volatile("mbarrier.init.shared::cta.b64 [%0], %1;" ::"r"(bar), "r"(cnt) : "memory"); }
__device__ __forceinline__ void mbar_expect_tx(uint32_t bar, uint32_t bytes) { asm volatile("mbarrier.arrive.expect_tx.shared::cta.b64 _, [%0], %1;" ::"r"(bar), "r"(bytes) : "memory"); }
__device__ __forceinline__ void mbar_arrive(uint32_t bar) { asm volatile("mbarrier.arrive.shared::cta.b64 _, [%0];" ::"r"(bar) : "memory"); }
__device__ __forceinline__ void mbar_arrive_cluster(uint32_t bar, uint32_t cta) {
  asm volatile("{\n.reg .b32 r;\nmapa.shared::cluster.u32 r, %0, %1;\nmbarrier.arrive.shared::cluster.b64 _, [r];\n}\n" ::"r"(bar), "r"(cta) : "memory");
}
__device__ __forceinline__ bool mbar_try(uint32_t bar, uint32_t parity) {
  uint32_t ok;
  asm volatile("{\n.reg .pred p;\nmbarrier.try_wait.parity.shared::cta.b64 p, [%1], %2;\nselp.u32 %0, 1, 0, p;\n}\n" : "=r"(ok) : "r"(bar), "r"(parity) : "memory");
  return ok;
}
__device__ __forceinline__ bool mbar_test(uint32_t bar, uint32_t parity) {
  uint32_t ok;
  asm volatile("{\n.reg .pred p;\nmbarrier.test_wait.parity.shared::cta.b64 p, [%1], %2;\nselp.u32 %0, 1, 0, p;\n}\n" : "=r"(ok) : "r"(bar), "r"(parity) : "memory");
  return ok;
}
__device__ __forceinline__ void mbar_wait(uint32_t bar, uint32_t parity) {
  asm volatile("{\n.reg .pred p;\nWAIT_LOOP:\nmbarrier.try_wait.parity.shared::cta.b64 p, [%0], %1;\n@p bra WAIT_DONE;\nbra WAIT_LOOP;\nWAIT_DONE:\n}\n" ::"r"(bar), "r"(parity) : "memory");
}
__device__ __forceinline__ void tma2d(uint32_t dst, const CUtensorMap* tm, int c0, int c1, uint32_t bar) {
  asm volatile("cp.async.bulk.tensor.2d.shared::cluster.global.mbarrier::complete_tx::bytes [%0], [%1, {%3, %4}], [%2];"
               ::"r"(dst), "l"(tm), "r"(bar), "r"(c0), "r"(c1) : "memory");
}
__device__ __forceinline__ void tma2d_mc(uint32_t dst, const CUtensorMap* tm, int c0, int c1, uint32_t bar) {
  asm volatile("cp.async.bulk.tensor.2d.shared::cluster.global.mbarrier::complete_tx::bytes.multicast::cluster [%0], [%1, {%3, %4}], [%2], %5;"
               ::"r"(dst), "l"(tm), "r"(bar), "r"(c0), "r"(c1), "h"((uint16_t)3) : "memory");
}
__device__ __forceinline__ void tma3d(uint32_t dst, const CUtensorMap* tm, int c0, int c1, int c2, uint32_t bar) {
  asm volatile("cp.async.bulk.tensor.3d.shared::cluster.global.mbarrier::complete_tx::bytes [%0], [%1, {%3, %4, %5}], [%2];"
               ::"r"(dst), "l"(tm), "r"(bar), "r"(c0), "r"(c1), "r"(c2) : "memory");
}
__device__ __forceinline__ void tma3d_mc(uint32_t dst, const CUtensorMap* tm, int c0, int c1, int c2, uint32_t bar) {
  asm volatile("cp.async.bulk.tensor.3d.shared::cluster.global.mbarrier::complete_tx::bytes.multicast::cluster [%0], [%1, {%3, %4, %5}], [%2], %6;"
               ::"r"(dst), "l"(tm), "r"(bar), "r"(c0), "r"(c1), "r"(c2), "h"((uint16_t)3) : "memory");
}
__device__ __forceinline__ void bulk_g2s(uint32_t dst, const void* src, uint32_t bytes, uint32_t bar) {
  asm volatile("cp.async.bulk.shared::cluster.global.mbarrier::complete_tx::bytes [%0], [%1], %2, [%3];"
               ::"r"(dst), "l"(src), "r"(bytes), "r"(bar) : "memory");
}
__device__ __forceinline__ void tma2d_store(const CUtensorMap* tm, uint32_t src, int c0, int c1) {
  asm volatile("cp.async.bulk.tensor.2d.global.shared::cta.bulk_group [%0, {%2, %3}], [%1];" ::"l"(tm), "r"(src), "r"(c0), "r"(c1) : "memory");
}
__device__ __forceinline__ void pf2d(const CUtensorMap* tm, int c0, int c1) {
  asm volatile("cp.async.bulk.prefetch.tensor.2d.L2.global [%0, {%1, %2}];" ::"l"(tm), "r"(c0), "r"(c1) : "memory");
}
__device__ __forceinline__ void pf3d(const CUtensorMap* tm, int c0, int c1, int c2) {
  asm volatile("cp.async.bulk.prefetch.tensor.3d.L2.global [%0, {%1, %2, %3}];" ::"l"(tm), "r"(c0), "r"(c1), "r"(c2) : "memory");
}
__device__ __forceinline__ void prefetch_tm(const CUtensorMap* tm) { asm volatile("prefetch.tensormap [%0];" ::"l"(tm) : "memory"); }
__device__ __forceinline__ void wg_fence() { asm volatile("wgmma.fence.sync.aligned;" ::: "memory"); }
__device__ __forceinline__ void wg_commit() { asm volatile("wgmma.commit_group.sync.aligned;" ::: "memory"); }
template <int N> __device__ __forceinline__ void wg_wait() { asm volatile("wgmma.wait_group.sync.aligned %0;" ::"n"(N) : "memory"); }
__device__ __forceinline__ void bar_sync(int id, int n) { asm volatile("bar.sync %0, %1;" ::"r"(id), "r"(n) : "memory"); }
__device__ __forceinline__ void bar_arrive(int id, int n) { asm volatile("bar.arrive %0, %1;" ::"r"(id), "r"(n) : "memory"); }
__device__ __forceinline__ void fence_async_smem() { asm volatile("fence.proxy.async.shared::cta;" ::: "memory"); }
__device__ __forceinline__ void fence_async_all() { asm volatile("fence.proxy.async.global;" ::: "memory"); }
__device__ __forceinline__ uint32_t pack_bf16(float lo, float hi) { uint32_t r; asm("cvt.rn.bf16x2.f32 %0, %1, %2;" : "=r"(r) : "f"(hi), "f"(lo)); return r; }
__device__ __forceinline__ float ex2(float x) { float r; asm("ex2.approx.ftz.f32 %0, %1;" : "=f"(r) : "f"(x)); return r; }
__device__ __forceinline__ float rcp(float x) { float r; asm("rcp.approx.ftz.f32 %0, %1;" : "=f"(r) : "f"(x)); return r; }
__device__ __forceinline__ float bf_lo(uint32_t v) { return __uint_as_float(v << 16); }
__device__ __forceinline__ float bf_hi(uint32_t v) { return __uint_as_float(v & 0xffff0000u); }
__device__ __forceinline__ void flag_wait(const unsigned* f, unsigned target) {
  unsigned v;
  do { asm volatile("ld.acquire.gpu.global.u32 %0, [%1];" : "=r"(v) : "l"(f) : "memory"); } while (v < target);
}
__device__ __forceinline__ void fence_release() { asm volatile("fence.release.gpu;" ::: "memory"); }
__device__ __forceinline__ void flag_add(unsigned* f) { asm volatile("red.relaxed.gpu.global.add.u32 [%0], 1;" ::"l"(f) : "memory"); }
__device__ __forceinline__ void cluster_arrive() { asm volatile("barrier.cluster.arrive.relaxed.aligned;" ::: "memory"); }
__device__ __forceinline__ void cluster_wait() { asm volatile("barrier.cluster.wait.aligned;" ::: "memory"); }
__device__ __forceinline__ uint32_t hmul2(uint32_t a, uint32_t b) { uint32_t r; asm("mul.rn.bf16x2 %0, %1, %2;" : "=r"(r) : "r"(a), "r"(b)); return r; }
__device__ __forceinline__ uint32_t hadd2(uint32_t a, uint32_t b) { uint32_t r; asm("add.rn.bf16x2 %0, %1, %2;" : "=r"(r) : "r"(a), "r"(b)); return r; }
__device__ __forceinline__ uint32_t hfma2(uint32_t a, uint32_t b, uint32_t c) { uint32_t r; asm("fma.rn.bf16x2 %0, %1, %2, %3;" : "=r"(r) : "r"(a), "r"(b), "r"(c)); return r; }
__device__ __forceinline__ uint32_t lds32(uint32_t a) { uint32_t r; asm volatile("ld.shared.b32 %0, [%1];" : "=r"(r) : "r"(a) : "memory"); return r; }
__device__ __forceinline__ uint4 lds128(uint32_t a) { uint4 r; asm volatile("ld.shared.v4.b32 {%0,%1,%2,%3}, [%4];" : "=r"(r.x), "=r"(r.y), "=r"(r.z), "=r"(r.w) : "r"(a) : "memory"); return r; }
__device__ __forceinline__ uint32_t desc_k(uint32_t addr) { return ((addr & 0x3FFFF) >> 4) | (1u << 16); }
template <int LBO> __device__ __forceinline__ uint32_t desc_mn(uint32_t addr) { return ((addr & 0x3FFFF) >> 4) | ((uint32_t)(LBO >> 4) << 16); }
#define DHI "0x40000040"

#define R8(d, o) "+f"(d[o]), "+f"(d[o + 1]), "+f"(d[o + 2]), "+f"(d[o + 3]), "+f"(d[o + 4]), "+f"(d[o + 5]), "+f"(d[o + 6]), "+f"(d[o + 7])
#define R32(d, o) R8(d, o), R8(d, o + 8), R8(d, o + 16), R8(d, o + 24)
#define R64(d, o) R32(d, o), R32(d, o + 32)
#define L64 "%0,%1,%2,%3,%4,%5,%6,%7,%8,%9,%10,%11,%12,%13,%14,%15,%16,%17,%18,%19,%20,%21,%22,%23,%24,%25,%26,%27,%28,%29,%30,%31," \
            "%32,%33,%34,%35,%36,%37,%38,%39,%40,%41,%42,%43,%44,%45,%46,%47,%48,%49,%50,%51,%52,%53,%54,%55,%56,%57,%58,%59,%60,%61,%62,%63"
#define L128 L64 ",%64,%65,%66,%67,%68,%69,%70,%71,%72,%73,%74,%75,%76,%77,%78,%79,%80,%81,%82,%83,%84,%85,%86,%87,%88,%89,%90,%91,%92,%93,%94,%95," \
            "%96,%97,%98,%99,%100,%101,%102,%103,%104,%105,%106,%107,%108,%109,%110,%111,%112,%113,%114,%115,%116,%117,%118,%119,%120,%121,%122,%123,%124,%125,%126,%127"

template <int TB> __device__ __forceinline__ void mma_ss_n128(float (&d)[64], uint32_t da, uint32_t db) {
  asm volatile("{\n.reg .b64 da, db;\nmov.b64 da, {%64, " DHI "};\nmov.b64 db, {%65, " DHI "};\n"
               "wgmma.mma_async.sync.aligned.m64n128k16.f32.bf16.bf16 {" L64 "}, da, db, 1, 1, 1, 0, %66;\n}\n"
               : R64(d, 0) : "r"(da), "r"(db), "n"(TB));
}
template <int TB> __device__ __forceinline__ void mma_rs_n128(float (&d)[64], uint32_t a0, uint32_t a1, uint32_t a2, uint32_t a3, uint32_t db, int sd) {
  asm volatile("{\n.reg .pred p;\n.reg .b64 db;\nsetp.ne.b32 p, %69, 0;\nmov.b64 db, {%68, " DHI "};\n"
               "wgmma.mma_async.sync.aligned.m64n128k16.f32.bf16.bf16 {" L64 "}, {%64,%65,%66,%67}, db, p, 1, 1, %70;\n}\n"
               : R64(d, 0) : "r"(a0), "r"(a1), "r"(a2), "r"(a3), "r"(db), "r"(sd), "n"(TB));
}
template <int TB> __device__ __forceinline__ void mma_ss_n256(float (&d)[128], uint32_t da, uint32_t db) {
  asm volatile("{\n.reg .b64 da, db;\nmov.b64 da, {%128, " DHI "};\nmov.b64 db, {%129, " DHI "};\n"
               "wgmma.mma_async.sync.aligned.m64n256k16.f32.bf16.bf16 {" L128 "}, da, db, 1, 1, 1, 0, %130;\n}\n"
               : R64(d, 0), R64(d, 64) : "r"(da), "r"(db), "n"(TB));
}
#define W8(d, o) "=f"(d[o]), "=f"(d[o + 1]), "=f"(d[o + 2]), "=f"(d[o + 3]), "=f"(d[o + 4]), "=f"(d[o + 5]), "=f"(d[o + 6]), "=f"(d[o + 7])
#define W32(d, o) W8(d, o), W8(d, o + 8), W8(d, o + 16), W8(d, o + 24)
#define W64(d, o) W32(d, o), W32(d, o + 32)
template <int TB> __device__ __forceinline__ void mma_ss_n128_init(float (&d)[64], uint32_t da, uint32_t db) {
  asm volatile("{\n.reg .b64 da, db;\nmov.b64 da, {%64, " DHI "};\nmov.b64 db, {%65, " DHI "};\n"
               "wgmma.mma_async.sync.aligned.m64n128k16.f32.bf16.bf16 {" L64 "}, da, db, 0, 1, 1, 0, %66;\n}\n"
               : W64(d, 0) : "r"(da), "r"(db), "n"(TB));
}
template <int TB> __device__ __forceinline__ void mma_ss_n256_init(float (&d)[128], uint32_t da, uint32_t db) {
  asm volatile("{\n.reg .b64 da, db;\nmov.b64 da, {%128, " DHI "};\nmov.b64 db, {%129, " DHI "};\n"
               "wgmma.mma_async.sync.aligned.m64n256k16.f32.bf16.bf16 {" L128 "}, da, db, 0, 1, 1, 0, %130;\n}\n"
               : W64(d, 0), W64(d, 64) : "r"(da), "r"(db), "n"(TB));
}
#define L32 "%0,%1,%2,%3,%4,%5,%6,%7,%8,%9,%10,%11,%12,%13,%14,%15,%16,%17,%18,%19,%20,%21,%22,%23,%24,%25,%26,%27,%28,%29,%30,%31"
__device__ __forceinline__ void mma_ss_n64(float (&d)[32], uint32_t da, uint32_t db) {
  asm volatile("{\n.reg .b64 da, db;\nmov.b64 da, {%32, " DHI "};\nmov.b64 db, {%33, " DHI "};\n"
               "wgmma.mma_async.sync.aligned.m64n64k16.f32.bf16.bf16 {" L32 "}, da, db, 1, 1, 1, 0, 0;\n}\n"
               : R32(d, 0) : "r"(da), "r"(db));
}
__device__ __forceinline__ void mma_ss_n64_init(float (&d)[32], uint32_t da, uint32_t db) {
  asm volatile("{\n.reg .b64 da, db;\nmov.b64 da, {%32, " DHI "};\nmov.b64 db, {%33, " DHI "};\n"
               "wgmma.mma_async.sync.aligned.m64n64k16.f32.bf16.bf16 {" L32 "}, da, db, 0, 1, 1, 0, 0;\n}\n"
               : W32(d, 0) : "r"(da), "r"(db));
}
#define L16 "%0,%1,%2,%3,%4,%5,%6,%7,%8,%9,%10,%11,%12,%13,%14,%15"
__device__ __forceinline__ void mma_rs_n32(float (&d)[16], uint32_t a0, uint32_t a1, uint32_t a2, uint32_t a3, uint32_t db) {
  asm volatile("{\n.reg .b64 db;\nmov.b64 db, {%20, 0xC0000010};\n"
               "wgmma.mma_async.sync.aligned.m64n32k16.f32.bf16.bf16 {" L16 "}, {%16,%17,%18,%19}, db, 1, 1, 1, 0;\n}\n"
               : R8(d, 0), R8(d, 8) : "r"(a0), "r"(a1), "r"(a2), "r"(a3), "r"(db));
}
__device__ __forceinline__ void mma_rs_n32_init(float (&d)[16], uint32_t a0, uint32_t a1, uint32_t a2, uint32_t a3, uint32_t db) {
  asm volatile("{\n.reg .b64 db;\nmov.b64 db, {%20, 0xC0000010};\n"
               "wgmma.mma_async.sync.aligned.m64n32k16.f32.bf16.bf16 {" L16 "}, {%16,%17,%18,%19}, db, 0, 1, 1, 0;\n}\n"
               : W8(d, 0), W8(d, 8) : "r"(a0), "r"(a1), "r"(a2), "r"(a3), "r"(db));
}
template <int N> __device__ __forceinline__ void reg_fence(float (&d)[N]) {
#pragma unroll
  for (int i = 0; i < N; i++) asm volatile("" : "+f"(d[i])::"memory");
}
template <int N> __device__ __forceinline__ void reg_fence(uint32_t (&d)[N]) {
#pragma unroll
  for (int i = 0; i < N; i++) asm volatile("" : "+r"(d[i])::"memory");
}

struct __align__(64) Params {
  CUtensorMap x, c, wq, wuk, wuv, wo, y, out;
  const __nv_bfloat16* xp;
  const __nv_bfloat16* gate_w;
  const __nv_bfloat16 *ak, *av, *shk, *ssk, *ssd;
};

template <int O, int N> __device__ __forceinline__ void pack_frag(const float (&acc)[N], uint32_t (&pk)[32]) {
#pragma unroll
  for (int i = 0; i < 32; i++) pk[i] = pack_bf16(acc[O + 2 * i], acc[O + 2 * i + 1]);
}
__device__ __forceinline__ void pack_frag_scaled(const float (&acc)[64], uint32_t (&pk)[32], float s0, float s1) {
#pragma unroll
  for (int i = 0; i < 32; i++) { const float s = (i & 1) ? s1 : s0; pk[i] = pack_bf16(acc[2 * i] * s, acc[2 * i + 1] * s); }
}
__device__ __forceinline__ void stsm_frag(const uint32_t (&pk)[32], uint32_t a) {
#pragma unroll
  for (int jj = 0; jj < 8; jj++)
    asm volatile("stmatrix.sync.aligned.m8n8.x4.shared.b16 [%0], {%1,%2,%3,%4};" ::"r"((a ^ ((jj & 3) << 5)) + (jj >> 2) * 16384),
                 "r"(pk[4 * jj]), "r"(pk[4 * jj + 1]), "r"(pk[4 * jj + 2]), "r"(pk[4 * jj + 3]) : "memory");
}

struct Cons {
  uint32_t sb;
  uint32_t pf;
  uint32_t rank;
  int wg, tid;
  __device__ __forceinline__ void wait_full(int g) { mbar_wait(sb + SM_BAR + (B_FULL + g) * 8, (pf >> g) & 1); pf ^= 1u << g; }
  __device__ __forceinline__ void release(int g, int n, bool cross) {
    if (tid < 2 * n) mbar_arrive_cluster(sb + SM_BAR + (B_EMPTY + g + (tid >> 1)) * 8, cross ? (uint32_t)(tid & 1) : rank);
  }
  __device__ __forceinline__ void turn_begin() { bar_sync(1 + wg, 256); }
  __device__ __forceinline__ void turn_end() { bar_arrive(2 - wg, 256); }
  __device__ __forceinline__ void staged(int e) { __syncwarp(); if ((tid & 31) == 0) mbar_arrive(sb + SM_BAR + (B_EV + 2 * e + wg) * 8); }
  uint32_t pfree;
  __device__ __forceinline__ void wait_stage_free() { mbar_wait(sb + SM_BAR + (B_EV + 4 + wg) * 8, pfree); pfree ^= 1; }
  __device__ __forceinline__ bool try_full(int g) { return mbar_test(sb + SM_BAR + (B_FULL + g) * 8, (pf >> g) & 1); }
};

constexpr float SM_C = 0.08838834764831845f * 1.4426950408889634f;
struct SoftState { float m0, m1, n0, n1, l0, l1; };
template <int Q, int N> __device__ __forceinline__ void exp_quarter(const float (&S)[N], float (&e)[16], const SoftState& z, float& s0, float& s1) {
#pragma unroll
  for (int i = 0; i < 16; i++) e[i] = ex2(fmaf(S[16 * Q + i], SM_C, (i & 2) ? z.n1 : z.n0));
#pragma unroll
  for (int i = 0; i < 16; i += 4) { s0 += e[i]; s1 += e[i + 2]; s0 += e[i + 1]; s1 += e[i + 3]; }
}
template <int Q> __device__ __forceinline__ void pack_quarter(const float (&e)[16], uint32_t (&P)[32]) {
#pragma unroll
  for (int i = 0; i < 8; i++) P[8 * Q + i] = pack_bf16(e[2 * i], e[2 * i + 1]);
}
template <int NV, int N> __device__ __forceinline__ void update_max(const float (&S)[N], SoftState& z, float& sc0, float& sc1) {
  float a0 = fmaxf(S[0], S[1]), a1 = fmaxf(S[2], S[3]), b0 = fmaxf(S[4], S[5]), b1 = fmaxf(S[6], S[7]);
#pragma unroll
  for (int j = 2; j < NV / 4; j += 2) {
    a0 = fmaxf(a0, fmaxf(S[4 * j], S[4 * j + 1]));
    a1 = fmaxf(a1, fmaxf(S[4 * j + 2], S[4 * j + 3]));
    b0 = fmaxf(b0, fmaxf(S[4 * j + 4], S[4 * j + 5]));
    b1 = fmaxf(b1, fmaxf(S[4 * j + 6], S[4 * j + 7]));
  }
  a0 = fmaxf(a0, b0); a1 = fmaxf(a1, b1);
  a0 = fmaxf(a0, __shfl_xor_sync(0xffffffffu, a0, 1)); a1 = fmaxf(a1, __shfl_xor_sync(0xffffffffu, a1, 1));
  a0 = fmaxf(a0, __shfl_xor_sync(0xffffffffu, a0, 2)); a1 = fmaxf(a1, __shfl_xor_sync(0xffffffffu, a1, 2));
  a0 = fmaxf(a0, z.m0); a1 = fmaxf(a1, z.m1);
  sc0 = ex2((z.m0 - a0) * SM_C); sc1 = ex2((z.m1 - a1) * SM_C);
  z.m0 = a0; z.m1 = a1;
  z.n0 = -a0 * SM_C; z.n1 = -a1 * SM_C;
}
template <int N> __device__ __forceinline__ void soft_start(const float (&S)[N], SoftState& z) {
  z.m0 = z.m1 = -INFINITY; z.l0 = z.l1 = 0.f;
  float sc0, sc1;
  update_max<8>(S, z, sc0, sc1);
}
template <int N> __device__ __forceinline__ void exp_all(const float (&S)[N], uint32_t (&P)[32], const SoftState& z, float& s0, float& s1) {
  float e[16];
  exp_quarter<0>(S, e, z, s0, s1); pack_quarter<0>(e, P);
  exp_quarter<1>(S, e, z, s0, s1); pack_quarter<1>(e, P);
  if (N == 64) {
    exp_quarter<N == 64 ? 2 : 0>(S, e, z, s0, s1); pack_quarter<2>(e, P);
    exp_quarter<N == 64 ? 3 : 0>(S, e, z, s0, s1); pack_quarter<3>(e, P);
  }
}
template <bool HAS_O, int N> __device__ __forceinline__ void soft_fix(const float (&S)[N], float (&O)[64], SoftState& z) {
  float sc0, sc1;
  update_max<N>(S, z, sc0, sc1);
  if (HAS_O) {
    z.l0 *= sc0; z.l1 *= sc1;
#pragma unroll
    for (int j = 0; j < 16; j++) { O[4 * j] *= sc0; O[4 * j + 1] *= sc0; O[4 * j + 2] *= sc1; O[4 * j + 3] *= sc1; }
  }
}
__device__ __forceinline__ bool soft_bad(float s0, float s1) { return !(s0 + s1 <= SM_LIMIT); }
__device__ __forceinline__ void pin(float a, uint32_t never_zero) {
  asm volatile("{\n.reg .pred p;\nsetp.eq.u32 p, %1, 0;\n@p st.shared.f32 [%1], %0;\n}\n" ::"f"(a), "r"(never_zero) : "memory");
}
__device__ __forceinline__ void pin32(const uint32_t (&v)[32], uint32_t never_zero) {
#pragma unroll
  for (int i = 0; i < 32; i += 4)
    asm volatile("{\n.reg .pred p;\nsetp.eq.u32 p, %4, 0;\n@p st.shared.v4.b32 [%4], {%0,%1,%2,%3};\n}\n" ::"r"(v[i]), "r"(v[i + 1]), "r"(v[i + 2]), "r"(v[i + 3]), "r"(never_zero) : "memory");
}
template <int O, int N> __device__ __forceinline__ void reg_fence_part(uint32_t (&d)[32]) {
#pragma unroll
  for (int i = O; i < O + N; i++) asm volatile("" : "+r"(d[i])::"memory");
}
template <int N> __device__ __forceinline__ void mask_diag(float (&S)[N], int d) {
#pragma unroll
  for (int j = 0; j < 8; j++) {
    if (8 * j > d) S[N - 32 + 4 * j] = -INFINITY;
    if (8 * j + 1 > d) S[N - 32 + 4 * j + 1] = -INFINITY;
    if (8 * j > d + 8) S[N - 32 + 4 * j + 2] = -INFINITY;
    if (8 * j + 1 > d + 8) S[N - 32 + 4 * j + 3] = -INFINITY;
  }
}
__device__ __forceinline__ float quad_sum(float v) {
  v += __shfl_xor_sync(0xffffffffu, v, 1);
  v += __shfl_xor_sync(0xffffffffu, v, 2);
  return v;
}
__device__ __forceinline__ void issue_qk(float (&S)[64], uint32_t dq, uint32_t dk) {
  mma_ss_n128_init<0>(S, dq, dk);
#pragma unroll
  for (int s = 1; s < 8; s++) mma_ss_n128<0>(S, dq + (s >> 2) * 1024 + (s & 3) * 2, dk + (s >> 2) * 1024 + (s & 3) * 2);
}
__device__ __forceinline__ void issue_qk(float (&S)[32], uint32_t dq, uint32_t dk) {
  mma_ss_n64_init(S, dq, dk);
#pragma unroll
  for (int s = 1; s < 8; s++) mma_ss_n64(S, dq + (s >> 2) * 1024 + (s & 3) * 2, dk + (s >> 2) * 1024 + (s & 3) * 2);
}
template <int NS> __device__ __forceinline__ void issue_pv(float (&O)[64], const uint32_t (&P)[32], uint32_t dv, int acc) {
#pragma unroll
  for (int s = 0; s < NS; s++) {
    mma_rs_n128<1>(O, P[4 * s], P[4 * s + 1], P[4 * s + 2], P[4 * s + 3], dv + s * 128, s != 0 ? 1 : acc);
    if (s & 1) wg_commit();
  }
}
constexpr uint32_t DG = GR >> 4;
template <int N>
__device__ __forceinline__ void attn_head(Cons& c, float (&O)[64], uint32_t (&P)[32], SoftState& z, uint32_t dq, uint32_t dkk, int dmask) {
  float S[N];
  c.turn_begin();
  wg_fence();
  issue_qk(S, dq, dkk + 6 * DG);
  wg_commit();
  c.turn_end();
#pragma unroll
  for (int i = N / 2; i < 32; i++) P[i] = 0u;
  wg_wait<0>();
  reg_fence(S);
  c.release(6, 2, true);
  mask_diag(S, dmask);
  soft_start(S, z);
#pragma unroll 1
  for (int pass = 0;; pass++) {
    z.l0 = 0.f; z.l1 = 0.f;
    exp_all(S, P, z, z.l0, z.l1);
    if (pass || !__any_sync(0xffffffffu, soft_bad(z.l0, z.l1))) break;
    soft_fix<false>(S, O, z);
  }
}
__device__ __forceinline__ void attn_tail32(Cons& c, float (&O)[64], uint32_t (&P)[32], SoftState& z, uint32_t dq, uint32_t dkk, uint32_t dv0, int dmask) {
  float S[32];
  c.turn_begin();
  wg_fence();
  issue_qk(S, dq, dkk + 8 * DG);
  wg_commit();
  issue_pv<8>(O, P, dv0 + 10 * DG, 1);
  c.turn_end();
  wg_wait<4>();
  reg_fence(S);
  c.release(8, 2, true);
  mask_diag(S, dmask);
  float s0, s1;
#pragma unroll 1
  for (int pass = 0;; pass++) {
    float e[16];
    s0 = 0.f; s1 = 0.f;
    exp_quarter<0>(S, e, z, s0, s1); pin(s1, c.sb); wg_wait<3>(); reg_fence_part<0, 8>(P); pack_quarter<0>(e, P);
    exp_quarter<1>(S, e, z, s0, s1); pin(s1, c.sb); wg_wait<0>(); reg_fence_part<8, 24>(P); reg_fence(O); pack_quarter<1>(e, P);
    if (pass || !__any_sync(0xffffffffu, soft_bad(s0, s1))) break;
    soft_fix<true>(S, O, z);
  }
  z.l0 += s0; z.l1 += s1;
  c.release(10, 2, true);
  c.wait_full(12);
}
template <int NS> __device__ __forceinline__ void attn_last_pv(Cons& c, float (&O)[64], uint32_t (&P)[32], SoftState& z, uint32_t dv0) {
  c.turn_begin();
  wg_fence();
  issue_pv<NS>(O, P, dv0 + 12 * DG, 1);
  c.turn_end();
  z.l0 = rcp(quad_sum(z.l0)); z.l1 = rcp(quad_sum(z.l1));
  wg_wait<0>();
  reg_fence(O); reg_fence(P);
}

__device__ __forceinline__ void conv_tasks(Cons& c, const Params& p, int ntask, int g, int ch, int chstep, uint32_t dkk, int w, int lane) {
  const uint32_t sb = c.sb;
#pragma unroll 1
  for (int i = 0; i < ntask; i++) {
    const float dd = __bfloat162float(p.ssd[ch]);
    const uint32_t base = sb + g * GR;
    c.wait_full(g);
    uint32_t a[64];
    const uint32_t hb = base + WBYTES - 28 + (8 * w + (lane >> 2) + (lane & 3)) * 4;
#pragma unroll
    for (int s = 0; s < 16; s++) {
      a[4 * s] = lds32(hb + s * 256); a[4 * s + 1] = lds32(hb + s * 256 + 128);
      a[4 * s + 2] = lds32(hb + s * 256 + 16); a[4 * s + 3] = lds32(hb + s * 256 + 144);
    }
    const uint32_t ub = base + 512 + (c.tid >> 1) * 64 + 32 + ((((c.tid & 1) ^ 1) ^ ((c.tid >> 2) & 1)) << 4);
    const uint4 u0 = lds128(ub), u1 = lds128(ub + 4096);
    float acc[8][16];
    const uint32_t db = dkk + g * DG + 32;
    c.turn_begin();
    wg_fence();
#pragma unroll
    for (int s = 0; s < 16; s++) {
#pragma unroll
      for (int J = s >> 1; J < 8; J++) {
        if (s == 0) mma_rs_n32_init(acc[J], a[0], a[1], a[2], a[3], db + J * 64);
        else mma_rs_n32(acc[J], a[4 * s], a[4 * s + 1], a[4 * s + 2], a[4 * s + 3], db + (2 * J - s) * 32);
      }
    }
    wg_commit();
    c.turn_end();
    c.wait_stage_free();
    wg_wait<0>();
#pragma unroll
    for (int J = 0; J < 8; J++) reg_fence(acc[J]);
    reg_fence(a);
    bar_sync(3 + c.wg, 128);
    const int tw = (lane & 3) + w;
    const uint32_t xb = base + w * 4096 + tw * 32 + (lane >> 2) * 4;
#pragma unroll
    for (int j = 0; j < 32; j++) {
      float v0 = acc[j >> 2][(j & 3) * 4], v1 = acc[j >> 2][(j & 3) * 4 + 1];
      if (j > 0) { v0 += acc[(j - 1) >> 2][((j - 1) & 3) * 4 + 2]; v1 += acc[(j - 1) >> 2][((j - 1) & 3) * 4 + 3]; }
      uint32_t v = pack_bf16(v0, v1), ad = xb + j * 128;
      if (j == 31 && tw >= 4) { v = 0; ad -= 4096; }
      asm volatile("st.shared.b32 [%0], %1;" ::"r"(ad), "r"(v) : "memory");
    }
    bar_sync(3 + c.wg, 128);
#pragma unroll
    for (int h = 0; h < 2; h++) {
      const uint32_t rb = base + c.tid * 16 + h * 2048;
      const uint4 q0 = lds128(rb), q1 = lds128(rb + 4096), q2 = lds128(rb + 8192), q3 = lds128(rb + 12288), u = h ? u1 : u0;
      auto fin = [&](uint32_t x0, uint32_t x1, uint32_t x2, uint32_t x3, uint32_t uu) {
        return pack_bf16(fmaf(dd, bf_hi(uu), (bf_lo(x0) + bf_lo(x1)) + (bf_lo(x2) + bf_lo(x3))),
                         fmaf(dd, bf_lo(uu), (bf_hi(x0) + bf_hi(x1)) + (bf_hi(x2) + bf_hi(x3))));
      };
      asm volatile("st.shared.v4.b32 [%0], {%1,%2,%3,%4};" ::"r"(rb), "r"(fin(q0.x, q1.x, q2.x, q3.x, u.w)), "r"(fin(q0.y, q1.y, q2.y, q3.y, u.z)),
                   "r"(fin(q0.z, q1.z, q2.z, q3.z, u.y)), "r"(fin(q0.w, q1.w, q2.w, q3.w, u.x)) : "memory");
    }
    c.staged(0);
    g += 2; if (g >= NGR) g -= NGR;
    ch += chstep;
  }
}

__global__ void __cluster_dims__(2, 1, 1) __launch_bounds__(NTHREADS, 1) mega_kernel(const __grid_constant__ Params p) {
  extern __shared__ uint8_t smem_raw[];
  const uint32_t sb = (smem_u32(smem_raw) + 1023) & ~1023u;
  const int wgi = __shfl_sync(0xffffffffu, threadIdx.x >> 7, 0);
  const int warp = __shfl_sync(0xffffffffu, threadIdx.x >> 5, 0);
  const uint32_t rank = blockIdx.x & 1;
  int grp, idx;
  {
    uint32_t smid; asm volatile("mov.u32 %0, %smid;" : "=r"(smid));
    const int tp = smid >> 1;
    if (tp < 32) { grp = tp & 7; idx = tp >> 3; }
    else if (tp < 60) { grp = 1 + (tp - 32) % 7; idx = 4 + (tp - 32) / 7; }
    else if (tp < 62) { grp = 8; idx = tp - 60; }
    else { grp = 0; idx = tp - 58; }
  }
  const int lb = (grp * 8 + idx) * 2 + rank;
  const bool spare = grp == 8;
  const int cn = spare ? 128 : 4, cch = spare ? lb - NMAIN : 512 + 4 * lb, cstep = spare ? 4 : 1, cg0 = spare ? 0 : 2;

  if (threadIdx.x == 0) {
    prefetch_tm(&p.c); prefetch_tm(rank ? &p.wuv : &p.wuk);
#pragma unroll 1
    for (int i = 0; i < 2 * NGR + 6; i++) mbar_init(sb + SM_BAR + i * 8, i < NGR || i >= 2 * NGR + 4 ? 1 : 4);
    mbar_init(sb + SM_BAR + B_DONE * 8, 11);
    asm volatile("fence.mbarrier_init.release.cluster;" ::: "memory");
  }
  cluster_arrive();
  cluster_wait();
  TS(0);

  if (wgi == 0) {
    asm volatile("setmaxnreg.dec.sync.aligned.u32 40;");
    const int lane = threadIdx.x & 31;
    cluster_arrive();
    if (warp == 0) {
      if (lane == 0) {
        uint32_t pe = spare ? 0x3FFF : 0x3FFC;
        auto acquire = [&](int g) { mbar_wait(sb + SM_BAR + (B_EMPTY + g) * 8, (pe >> g) & 1); pe ^= 1u << g; };
#pragma unroll 1
        for (int rnd = 0; rnd < (spare ? 0 : 2); rnd++) {
          const int hp = 16 * rnd + 2 * grp;
#pragma unroll 1
          for (int kk = 0; kk < 16; kk++) {
            const int g0 = 2 + 3 * (kk & 3), kb = kk & 7, head = hp + (kk >> 3);
            FTP(kk * 4);
            acquire(g0);
            if (kk < 4) { acquire(g0 + 1); acquire(g0 + 2); } else pe ^= 6u << g0;
            FTP(kk * 4 + 1);
            const uint32_t fb = sb + SM_BAR + (B_FULL + g0) * 8;
            mbar_expect_tx(fb, 3 * GR);
            tma2d(sb + g0 * GR, &p.c, kb * 64, (2 * idx + rank) * 128, fb);
            tma3d_mc(sb + (g0 + 1 + rank) * GR, rank ? &p.wuv : &p.wuk, 0, kb * 64, head * 2, fb);
            if (kk == 4) { prefetch_tm(&p.x); prefetch_tm(&p.wq); }
          }
          const int head = hp + rank;
#pragma unroll 1
          for (int kb = 0; kb < 16; kb++) {
            const int g0 = 2 + 3 * (kb & 3);
            FTP(64 + kb * 4);
            acquire(g0); pe ^= 6u << g0;
            FTP(64 + kb * 4 + 1);
            const uint32_t fb = sb + SM_BAR + (B_FULL + g0) * 8;
            mbar_expect_tx(fb, 3 * GR);
            tma2d_mc(sb + (g0 + rank) * GR, &p.x, kb * 64, (rank ? 15 - idx : idx) * 128, fb);
            tma3d(sb + (g0 + 2) * GR, &p.wq, 0, kb * 64, head * 2, fb);
          }
          flag_wait(FLAG(F_KV + rnd * 8 + grp), 32);
          fence_async_all();
          acquire(2); pe ^= 8u;
          int g0 = 6;
#pragma unroll 1
          for (int f = 0; f < 34; f++) {
            const bool isk = (f == 0) || ((f & 1) && f < 33);
            const int it = (f == 0) ? 0 : (f == 33) ? 16 : isk ? (f + 1) >> 1 : (f >> 1) - 1;
            const int blk = it == 0 ? idx : it <= idx ? it - 1 : it < 16 ? 15 - it : 15 - idx;
            acquire(g0); acquire(g0 + 1);
            const uint32_t fb = sb + SM_BAR + (B_FULL + g0) * 8;
            mbar_expect_tx(fb, 2 * GR);
            bulk_g2s(sb + g0 * GR, (isk ? g_kimg : g_vimg) + (size_t)(head * 16 + blk) * 32768, 2 * GR, fb);
            g0 = g0 == 12 ? 4 : g0 + 2;
            if (rnd == 0) {
              if (f == 20 || f == 22) pf3d(rank ? &p.wuv : &p.wuk, 0, idx * 64, (hp + 16 + (f == 22)) * 2);
              if (f == 24) pf2d(&p.c, grp * 64, (2 * idx + rank) * 128);
              if (f == 26 || f == 28) pf3d(&p.wq, 0, (idx + 4 * (f - 26)) * 64, (hp + 16 + rank) * 2);
            } else if (f >= 18 && !(f & 1)) pf2d(&p.wo, grp * 128 + rank * 64, (idx + 4 * (f - 18)) * 64);
          }
        }
        {
          int g = cg0;
#pragma unroll 1
          for (int i = 0, ch = cch; i < cn; i++, ch += cstep) {
            if ((i & 15) == 0) { flag_wait(FLAG(F_U + (ch >> 6)), NMAIN); fence_async_all(); }
            acquire(g);
            const uint32_t fb = sb + SM_BAR + (B_FULL + g) * 8;
            mbar_expect_tx(fb, WBYTES + 4096);
            bulk_g2s(sb + g * GR, g_w + (size_t)ch * WSTRIDE, WBYTES, fb);
            bulk_g2s(sb + g * GR + WBYTES, p.ssk + (size_t)ch * SEQ, 4096, fb);
            g = g == NGR - 1 ? 0 : g + 1;
          }
        }
        if (!spare) {
          prefetch_tm(&p.y); prefetch_tm(&p.out);
          const int rt = 2 * grp + rank, ct = idx;
          int g0 = 6;
#pragma unroll 1
          for (int kb = 0; kb < 66; kb++) {
            if ((kb & 31) == 0) {
              if (kb < 64) flag_wait(FLAG(F_CTX + rt * 2 + (kb >> 5)), 32);
              else { flag_wait(FLAG(F_GATE), NMAIN); flag_wait(FLAG(F_Y + ct), 128); }
              fence_async_all();
            }
            acquire(g0); acquire(g0 + 1);
            const uint32_t fb = sb + SM_BAR + (B_FULL + g0) * 8;
            mbar_expect_tx(fb, kb == 65 ? 2 * GR + 512 : 2 * GR);
            if (kb < 64) {
              bulk_g2s(sb + g0 * GR, g_cimg + (size_t)(rt * 64 + kb) * GR, GR, fb);
              tma2d_mc(sb + (g0 + 1) * GR + rank * 8192, &p.wo, ct * 128 + rank * 64, kb * 64, fb);
            } else {
              const CUtensorMap* tm = kb == 64 ? &p.x : &p.y;
              const int c0 = (kb == 64 ? ct : rt) * 128, c1 = (kb == 64 ? rt : ct) * 128;
              tma2d(sb + g0 * GR, tm, c0, c1, fb);
              tma2d(sb + (g0 + 1) * GR, tm, c0 + 64, c1, fb);
              if (kb == 65) bulk_g2s(sb + SM_GATE, g_gate + rt * 128, 512, fb);
            }
            g0 = g0 == 12 ? 0 : g0 + 2;
          }
          if (atomicAdd(FLAG(F_EXIT), 1) == NMAIN - 1) {
#pragma unroll 1
            for (int i = 0; i < F_NUM; i++) *FLAG(i) = 0;
          }
        }
        mbar_arrive(sb + SM_BAR + B_DONE * 8);
      }
    } else if (warp < 3) {
      if (lane == 0) {
        const int w = warp - 1;
        uint32_t p0 = 0;
        int cg = cg0 + w, ch = cch + w * cstep;
#pragma unroll 1
        for (int e = spare ? 12 : 0; e < 12 + cn / 2; e++) {
          const int rnd = e >= 6, k = e - 6 * rnd, hp = 16 * rnd + 2 * grp;
          uint8_t* dst;
          unsigned* fl = nullptr;
          int npc = 16384 / ST_PZ, rel = -1;
          uint32_t src = sb + w * 8192;
          if (k < 4) {
            dst = ((k & 1) ? g_vimg : g_kimg) + (size_t)((hp + (k >> 1)) * 16 + 2 * idx + rank) * 32768 + w * 8192;
            if (k == 3) fl = FLAG(F_KV + rnd * 8 + grp);
          } else if (k < 6) {
            const int rt = k == 4 ? idx : 15 - idx;
            dst = g_cimg + (size_t)(rt * 32 + hp + rank) * 32768 + w * 8192;
            fl = FLAG(F_CTX + rt * 2 + rnd);
            if (k == 4) { src += 2 * GR; rel = 2; } else if (rnd) rel = 0;
          } else {
            dst = reinterpret_cast<uint8_t*>(g_yT + (size_t)ch * SEQ);
            fl = FLAG(F_Y + (ch >> 7));
            src = sb + cg * GR; npc = 4096 / ST_PZ;
          }
          if (k == 4) mbar_wait(sb + SM_BAR + (B_EV + 2 + w) * 8, rnd);
          else { mbar_wait(sb + SM_BAR + (B_EV + w) * 8, p0); p0 ^= 1; }
          if (w == 0) FTP(k * 4 + 2);
          fence_async_smem();
#pragma unroll 1
          for (int i = 0; i < npc; i++) {
            const uint32_t o = (i * ST_PZ >> 13) * 16384 + ((i * ST_PZ) & 8191);
            asm volatile("cp.async.bulk.global.shared::cta.bulk_group [%0], [%1], %2;" ::"l"(dst + o), "r"(src + o), "r"(ST_PZ) : "memory");
            asm volatile("cp.async.bulk.commit_group;\ncp.async.bulk.wait_group %0;" ::"n"(ST_OUT) : "memory");
          }
          asm volatile("cp.async.bulk.wait_group.read 0;" ::: "memory");
          if (w == 0) FTP(k * 4 + 3);
          if (k != 4) mbar_arrive(sb + SM_BAR + (B_EV + 4 + w) * 8);
          if (rel >= 0 || (k >= 6 && (!spare || e < 12 + cn / 2 - NGR / 2))) {
#pragma unroll 1
            for (int i = 0; i < 4; i++) mbar_arrive_cluster(sb + SM_BAR + (B_EMPTY + (k >= 6 ? cg : rel + (i >> 1))) * 8, i & 1);
          }
          if (k >= 6) { cg += 2; if (cg >= NGR) cg -= NGR; ch += 2 * cstep; }
          if (fl) {
            asm volatile("cp.async.bulk.wait_group 0;" ::: "memory");
            fence_release();
            flag_add(fl);
          }
        }
        mbar_arrive(sb + SM_BAR + B_DONE * 8);
      }
    } else {
      if (!spare) {
        const int s0 = lb * 16;
#pragma unroll 1
        for (int cg = 0; cg < 16; cg++) {
          const int ch = cg * 64 + 2 * lane;
          const uint32_t* kp = reinterpret_cast<const uint32_t*>(p.ak + (size_t)s0 * DM + ch);
          const uint32_t* vp = reinterpret_cast<const uint32_t*>(p.av + (size_t)s0 * DM + ch);
          if (cg < 15) {
            const __nv_bfloat16* pf = (lane < 16 ? p.ak : p.av) + (size_t)(s0 + (lane & 15)) * DM + cg * 64 + 64;
            asm volatile("prefetch.global.L2 [%0];" ::"l"(pf));
          }
          if (cg == 1) {
#pragma unroll 1
            for (int i = 0; i < 8; i++) asm volatile("prefetch.global.L2 [%0];" ::"l"(p.xp + (size_t)s0 * DM + (i * 32 + lane) * 64));
          }
          const uint4 sw = __ldg(reinterpret_cast<const uint4*>(p.shk + ch * 4));
          uint32_t k3 = 0, k2 = 0, k1 = 0, k0 = 0, up = 0;
          if (lb > 0) { k3 = __ldg(kp - 4 * 512); k2 = __ldg(kp - 3 * 512); k1 = __ldg(kp - 2 * 512); k0 = __ldg(kp - 512); up = __ldg(vp - 512); }
          const uint32_t w0 = __byte_perm(sw.x, sw.z, 0x5410), w1 = __byte_perm(sw.x, sw.z, 0x7632);
          const uint32_t w2 = __byte_perm(sw.y, sw.w, 0x5410), w3 = __byte_perm(sw.y, sw.w, 0x7632);
          up = hmul2(hadd2(hadd2(hadd2(hmul2(k3, w3), hmul2(k2, w2)), hmul2(k1, w1)), hmul2(k0, w0)), up);
#pragma unroll 1
          for (int hb = 0; hb < 2; hb++) {
            uint32_t kk[8], u[8];
#pragma unroll
            for (int r = 0; r < 8; r++) { kk[r] = __ldg(kp + r * 512); u[r] = __ldg(vp + r * 512); }
#pragma unroll
            for (int r = 0; r < 8; r++) {
              k3 = k2; k2 = k1; k1 = k0; k0 = kk[r];
              u[r] = hmul2(hadd2(hadd2(hadd2(hmul2(k3, w3), hmul2(k2, w2)), hmul2(k1, w1)), hmul2(k0, w0)), u[r]);
            }
            uint8_t* dst = g_w + (size_t)ch * WSTRIDE + 512 + lb * 64 + (((hb ^ 1) ^ ((lb >> 1) & 1)) << 4);
#pragma unroll
            for (int cc = 0; cc < 2; cc++) {
              const uint32_t sel = cc ? 0x7632 : 0x5410;
              *reinterpret_cast<uint4*>(dst + cc * WSTRIDE) =
                  make_uint4(__byte_perm(u[6], u[5], sel), __byte_perm(u[4], u[3], sel), __byte_perm(u[2], u[1], sel), __byte_perm(u[0], up, sel));
              *reinterpret_cast<uint4*>(dst + cc * WSTRIDE + 32) =
                  make_uint4(__byte_perm(u[7], u[6], sel), __byte_perm(u[5], u[4], sel), __byte_perm(u[3], u[2], sel), __byte_perm(u[1], u[0], sel));
            }
            up = u[7];
            kp += 8 * 512; vp += 8 * 512;
          }
          fence_release();
          __syncwarp();
          if (lane == 0) flag_add(FLAG(F_U + cg));
        }
        const uint4* gw = reinterpret_cast<const uint4*>(p.gate_w);
#pragma unroll 1
        for (int r = 0; r < 16; r++) {
          const uint4* xr = reinterpret_cast<const uint4*>(p.xp + (size_t)(s0 + r) * DM);
          float s = 0.f;
#pragma unroll 1
          for (int i = 0; i < 4; i++) {
            const uint4 a = __ldg(xr + lane + 32 * i), b = __ldg(gw + lane + 32 * i);
            s += bf_lo(a.x) * bf_lo(b.x) + bf_hi(a.x) * bf_hi(b.x) + bf_lo(a.y) * bf_lo(b.y) + bf_hi(a.y) * bf_hi(b.y);
            s += bf_lo(a.z) * bf_lo(b.z) + bf_hi(a.z) * bf_hi(b.z) + bf_lo(a.w) * bf_lo(b.w) + bf_hi(a.w) * bf_hi(b.w);
          }
#pragma unroll
          for (int o = 16; o > 0; o >>= 1) s += __shfl_xor_sync(0xffffffffu, s, o);
          if (lane == 0) g_gate[s0 + r] = rcp(1.f + __expf(-s));
        }
        if (lane == 0) { fence_release(); flag_add(FLAG(F_GATE)); }
        TSW(9);
      }
      if (lane == 0) {
        unsigned long long t0, t1;
        asm volatile("mov.u64 %0, %globaltimer;" : "=l"(t0));
        while (!mbar_try(sb + SM_BAR + B_DONE * 8, 0)) {
          asm volatile("mov.u64 %0, %globaltimer;" : "=l"(t1));
          if (t1 - t0 > 2000000000ull) __trap();
        }
      }
    }
    __syncwarp();
    cluster_wait();
  } else {
    asm volatile("setmaxnreg.inc.sync.aligned.u32 232;");
    Cons c;
    c.sb = sb; c.pf = 0; c.rank = rank; c.wg = wgi - 1; c.tid = threadIdx.x & 127;
    const int lane = threadIdx.x & 31, t = lane & 3;
    const int row = c.wg * 64 + (warp & 3) * 16 + (lane >> 2);
    const uint32_t dkk = desc_k(sb), dk0 = dkk + c.wg * 512, dm0 = desc_mn<8192>(sb), dv0 = desc_mn<16384>(sb);
    if (c.wg == 1) bar_arrive(1, 256);
    uint32_t q2par = 1;

    c.pfree = 1;
    const uint32_t stg = sb + (c.wg * 64 + (warp & 3) * 16 + ((lane >> 3) & 1) * 8 + (lane & 7)) * 128 + (((lane >> 4) ^ (lane & 7)) << 4);

#pragma unroll 1
    for (int rnd = 0; rnd < (spare ? 0 : 2); rnd++) {
      uint32_t pv[32];
      FTM(rnd * 8);
      c.wait_full(2);
      FTM(rnd * 8 + 1);
#pragma unroll
      for (int tile = 0; tile < 2; tile++) {
        float acc[128];
        {
          FTG(tile * 32); FTG(tile * 32 + 1);
          const uint32_t a = dk0 + 2 * DG, b = dm0 + 3 * DG;
          c.turn_begin();
          FTG(tile * 32 + 2);
          wg_fence();
          mma_ss_n256_init<1>(acc, a, b);
#pragma unroll
          for (int k = 1; k < 4; k++) mma_ss_n256<1>(acc, a + k * 2, b + k * 128);
          wg_commit();
          c.turn_end();
          FTG(tile * 32 + 3);
        }
#pragma unroll 1
        for (int kb = 1; kb < 8; kb++) {
          const int g0 = 2 + 3 * (kb & 3);
          const uint32_t a = dk0 + g0 * DG, b = dm0 + (g0 + 1) * DG;
          FTG(tile * 32 + kb * 4);
          wg_wait<0>();
          c.release(2 + 3 * ((kb - 1) & 3), 3, true);
          FTG(tile * 32 + kb * 4 + 1);
          c.wait_full(g0);
          c.turn_begin();
          FTG(tile * 32 + kb * 4 + 2);
          wg_fence();
#pragma unroll
          for (int k = 0; k < 4; k++) mma_ss_n256<1>(acc, a + k * 2, b + k * 128);
          wg_commit();
          c.turn_end();
          FTG(tile * 32 + kb * 4 + 3);
          if (tile == 1 && kb == 4) { c.wait_stage_free(); stsm_frag(pv, stg); c.staged(0); }
        }
        c.wait_stage_free();
        const bool nxt = c.try_full(2);
        wg_wait<0>();
        reg_fence(acc);
        c.release(11, 3, true);
        pack_frag<0>(acc, pv);
        stsm_frag(pv, stg);
        c.staged(0);
        pack_frag<64>(acc, pv);
        pin32(pv, sb);
        if (!nxt) mbar_wait(sb + SM_BAR + (B_FULL + 2) * 8, (c.pf >> 2) & 1);
        c.pf ^= 4;
      }
      TS(1 + rnd * 3);
      FTM(rnd * 8 + 2);
      {
        float qa[64], qb[64];
        {
          FTG(64); FTG(65);
          const uint32_t a = dk0 + 2 * DG, b = dm0 + 4 * DG;
          c.turn_begin();
          FTG(66);
          wg_fence();
          mma_ss_n128_init<1>(qa, a, b);
          mma_ss_n128_init<1>(qb, a + DG, b);
#pragma unroll
          for (int k = 1; k < 4; k++) {
            mma_ss_n128<1>(qa, a + k * 2, b + k * 128);
            mma_ss_n128<1>(qb, a + DG + k * 2, b + k * 128);
          }
          wg_commit();
          c.turn_end();
          FTG(67);
        }
#pragma unroll 1
        for (int kb = 1; kb < 16; kb++) {
          const int g0 = 2 + 3 * (kb & 3);
          const uint32_t a = dk0 + g0 * DG, b = dm0 + (g0 + 2) * DG;
          FTG(64 + kb * 4);
          wg_wait<0>();
          c.release(2 + 3 * ((kb - 1) & 3), 3, true);
          FTG(65 + kb * 4);
          c.wait_full(g0);
          c.turn_begin();
          FTG(66 + kb * 4);
          wg_fence();
#pragma unroll
          for (int k = 0; k < 4; k++) {
            mma_ss_n128<1>(qa, a + k * 2, b + k * 128);
            mma_ss_n128<1>(qb, a + DG + k * 2, b + k * 128);
          }
          wg_commit();
          c.turn_end();
          FTG(67 + kb * 4);
          if (kb == QFLUSH) { c.wait_stage_free(); stsm_frag(pv, stg); c.staged(0); }
        }
        c.wait_stage_free();
        mbar_wait(sb + SM_BAR + (B_EMPTY + 2) * 8, q2par);
        mbar_wait(sb + SM_BAR + (B_EMPTY + 3) * 8, q2par);
        q2par ^= 1;
        FTM(rnd * 8 + 3);
        wg_wait<0>();
        reg_fence(qa); reg_fence(qb);
        c.release(11, 3, true);
        pack_frag<0>(qa, pv);
        stsm_frag(pv, stg + 2 * GR);
        pack_frag<0>(qb, pv);
        stsm_frag(pv, stg);
        c.wait_full(6);
        fence_async_smem();
        bar_sync(3 + c.wg, 128);
      }
      TS(2 + rnd * 3);
      FTM(rnd * 8 + 4);
      {
        const int nA = idx + 1;
        float O[64];
        uint32_t P[32];
        SoftState z;
        const int dmask = (row & 63) - 2 * t;
        if (c.wg == 0) attn_head<32>(c, O, P, z, dk0 + 2 * DG, dkk, dmask);
        else attn_head<64>(c, O, P, z, dk0 + 2 * DG, dkk, dmask);
#pragma unroll
        for (int i = 0; i < 64; i++) O[i] = 0.f;
        c.wait_full(8);
        c.wait_full(10);
        FTM(rnd * 8 + 5);
        int gk = 8, gv = 10;
#pragma unroll 1
        for (int it = 1; it < 16 + c.wg; it++) {
          float S[64];
          FTA(it * 7 + 0);
          c.turn_begin();
          FTA(it * 7 + 2);
          wg_fence();
          issue_qk(S, dk0 + (it < nA ? 2 * DG : 0), dkk + gk * DG);
          wg_commit();
          issue_pv<8>(O, P, dv0 + gv * DG, it != nA + 1);
          c.turn_end();
          FTA(it * 7 + 3);
          wg_wait<4>();
          reg_fence(S);
          FTA(it * 7 + 4);
          c.release(gk, 2, true);
          float i0, i1;
          if (it == nA || it == 16) {
            if (it == 16) mask_diag(S, dmask);
            else {
              i0 = rcp(quad_sum(z.l0)); i1 = rcp(quad_sum(z.l1));
              soft_start(S, z);
            }
          }
          float s0, s1;
          const int gvo = gv;
          gk = gv == 12 ? 4 : gv + 2;
          gv = it == 16 ? gk : gk == 12 ? 4 : gk + 2;
#pragma unroll 1
          for (int pass = 0;; pass++) {
            float e[16];
            s0 = 0.f; s1 = 0.f;
            exp_quarter<0>(S, e, z, s0, s1); pin(s1, sb); wg_wait<3>(); reg_fence_part<0, 8>(P); pack_quarter<0>(e, P);
            exp_quarter<1>(S, e, z, s0, s1); pin(s1, sb); wg_wait<2>(); reg_fence_part<8, 8>(P); pack_quarter<1>(e, P);
            exp_quarter<2>(S, e, z, s0, s1); pin(s1, sb); wg_wait<1>(); reg_fence_part<16, 8>(P); pack_quarter<2>(e, P);
            exp_quarter<3>(S, e, z, s0, s1); pin(s1, sb); wg_wait<0>(); reg_fence_part<24, 8>(P); reg_fence(O);
            c.release(gvo, pass ? 0 : 2, true);
            const bool ok = c.try_full(gk) & c.try_full(gv);
            pack_quarter<3>(e, P);
            FTA(it * 7 + 5);
            if (!__any_sync(0xffffffffu, soft_bad(s0, s1) || !ok || it == nA) || pass) break;
            if (it == nA) {
              uint32_t pk[32];
              pack_frag_scaled(O, pk, i0, i1);
              stsm_frag(pk, stg + 2 * GR);
              c.staged(1);
            }
            mbar_wait(sb + SM_BAR + (B_FULL + gk) * 8, (c.pf >> gk) & 1);
            mbar_wait(sb + SM_BAR + (B_FULL + gv) * 8, (c.pf >> gv) & 1);
            if (!__any_sync(0xffffffffu, soft_bad(s0, s1))) break;
            soft_fix<true>(S, O, z);
          }
          c.pf ^= (1u << gk) | (1u << gv);
          z.l0 += s0; z.l1 += s1;
          FTA(it * 7 + 6);
        }
        FTM(rnd * 8 + 6);
        if (c.wg == 0) {
          attn_tail32(c, O, P, z, dk0, dkk, dv0, dmask);
          attn_last_pv<4>(c, O, P, z, dv0);
        } else attn_last_pv<8>(c, O, P, z, dv0);
        c.release(12, 2, true);
        pack_frag_scaled(O, P, z.l0, z.l1);
        stsm_frag(P, stg);
        c.staged(0);
        FTM(rnd * 8 + 7);
      }
      TS(3 + rnd * 3);
    }
    conv_tasks(c, p, cn / 2, cg0 + c.wg, cch + c.wg * cstep, 2 * cstep, dkk, warp & 3, lane);
    TS(7);
    if (c.wg == 0) bar_sync(1, 256);
    else c.pf ^= 0x14;
    if (!spare) {
      const int rt = 2 * grp + rank, ct = idx;
      float acc[64];
      int g0 = 8, pg = 6;
      {
        FTO(0);
        c.wait_full(6);
        FTO(1);
        const uint32_t a = dk0 + 6 * DG, b = dm0 + 7 * DG;
        wg_fence();
        mma_ss_n128_init<1>(acc, a, b);
#pragma unroll
        for (int k = 1; k < 4; k++) mma_ss_n128<1>(acc, a + k * 2, b + k * 128);
        wg_commit();
      }
#pragma unroll 1
      for (int kb = 1; kb < 64; kb++) {
        FTO(kb * 2);
        c.wait_full(g0);
        FTO(kb * 2 + 1);
        const uint32_t a = dk0 + g0 * DG, b = dm0 + (g0 + 1) * DG;
        wg_fence();
#pragma unroll
        for (int k = 0; k < 4; k++) mma_ss_n128<1>(acc, a + k * 2, b + k * 128);
        wg_commit();
        wg_wait<1>();
        c.release(pg, kb <= 59 ? 2 : 0, true);
        pg = g0;
        g0 = g0 == 12 ? 0 : g0 + 2;
      }
      cluster_arrive();
      c.wait_full(8);
      c.wait_full(10);
      const float g0f = __uint_as_float(lds32(sb + SM_GATE + row * 4)), g1f = __uint_as_float(lds32(sb + SM_GATE + row * 4 + 32));
      const uint32_t gp0 = pack_bf16(g0f, g0f), gp1 = pack_bf16(g1f, g1f);
      const float h0 = 1.f - g0f, h1 = 1.f - g1f;
      const int w = warp & 3;
      const uint32_t xa = stg + 8 * GR;
      const uint32_t ya = sb + 10 * GR + c.wg * 16384 + ((lane >> 4) * 8 + (lane & 7)) * 128 + (((2 * w + ((lane >> 3) & 1)) ^ (lane & 7)) << 4);
      uint32_t xy[32];
#pragma unroll
      for (int jj = 0; jj < 8; jj++) {
        uint32_t x[4], y[4];
        asm volatile("ldmatrix.sync.aligned.m8n8.x4.shared.b16 {%0,%1,%2,%3}, [%4];" : "=r"(x[0]), "=r"(x[1]), "=r"(x[2]), "=r"(x[3]) : "r"((xa ^ ((jj & 3) << 5)) + (jj >> 2) * 16384) : "memory");
        asm volatile("ldmatrix.sync.aligned.m8n8.x4.trans.shared.b16 {%0,%1,%2,%3}, [%4];" : "=r"(y[0]), "=r"(y[1]), "=r"(y[2]), "=r"(y[3]) : "r"(ya + jj * 2048) : "memory");
#pragma unroll
        for (int i = 0; i < 4; i++) xy[4 * jj + i] = hmul2(x[i], y[i]);
      }
      wg_wait<0>();
      reg_fence(acc);
      TS(8);
      FTM(16);
#pragma unroll
      for (int i = 0; i < 32; i++) {
        const float h = (i & 1) ? h1 : h0;
        xy[i] = hfma2((i & 1) ? gp1 : gp0, xy[i], pack_bf16(acc[2 * i] * h, acc[2 * i + 1] * h));
      }
      stsm_frag(xy, xa);
      FTM(19);
      fence_async_smem();
      __syncwarp();
      FTM(20);
      if (lane == 0) {
        const int r0 = c.wg * 64 + w * 16;
        tma2d_store(&p.out, sb + 8 * GR + r0 * 128, ct * 128, rt * 128 + r0);
        tma2d_store(&p.out, sb + 9 * GR + r0 * 128, ct * 128 + 64, rt * 128 + r0);
        asm volatile("cp.async.bulk.commit_group;\ncp.async.bulk.wait_group.read 0;" ::: "memory");
      }
      FTM(21);
    } else cluster_arrive();
    if (lane == 0) mbar_arrive(sb + SM_BAR + B_DONE * 8);
    __syncwarp();
    TS(9);
    cluster_wait();
  }
}

typedef CUresult (*EncFn)(CUtensorMap*, CUtensorMapDataType, cuuint32_t, void*, const cuuint64_t*, const cuuint64_t*, const cuuint32_t*,
                          const cuuint32_t*, CUtensorMapInterleave, CUtensorMapSwizzle, CUtensorMapL2promotion, CUtensorMapFloatOOBfill);

void enc2d(EncFn enc, CUtensorMap* tm, const void* base, uint64_t cols, uint64_t rows, uint32_t bc, uint32_t br) {
  cuuint64_t dims[2] = {cols, rows}; cuuint64_t strides[1] = {cols * 2}; cuuint32_t box[2] = {bc, br}; cuuint32_t es[2] = {1, 1};
  enc(tm, CU_TENSOR_MAP_DATA_TYPE_BFLOAT16, 2, const_cast<void*>(base), dims, strides, box, es, CU_TENSOR_MAP_INTERLEAVE_NONE,
      CU_TENSOR_MAP_SWIZZLE_128B, CU_TENSOR_MAP_L2_PROMOTION_L2_256B, CU_TENSOR_MAP_FLOAT_OOB_FILL_NONE);
}
void enc3d(EncFn enc, CUtensorMap* tm, const void* base, uint64_t K, uint64_t N) {
  cuuint64_t dims[3] = {64, K, N / 64}; cuuint64_t strides[2] = {N * 2, 128}; cuuint32_t box[3] = {64, 64, 2}; cuuint32_t es[3] = {1, 1, 1};
  enc(tm, CU_TENSOR_MAP_DATA_TYPE_BFLOAT16, 3, const_cast<void*>(base), dims, strides, box, es, CU_TENSOR_MAP_INTERLEAVE_NONE,
      CU_TENSOR_MAP_SWIZZLE_128B, CU_TENSOR_MAP_L2_PROMOTION_L2_256B, CU_TENSOR_MAP_FLOAT_OOB_FILL_NONE);
}

}

extern "C" void kernel_launch(void* const* d_in, const int* in_sizes, int n_in, void* d_out, int out_size) {
  (void)in_sizes; (void)n_in; (void)out_size;
  typedef const __nv_bfloat16* BP;
  BP xq = (BP)d_in[0], ak = (BP)d_in[1], av = (BP)d_in[2], shk = (BP)d_in[3], ssk = (BP)d_in[4], ssd = (BP)d_in[5];
  BP ckv = (BP)d_in[7], wq = (BP)d_in[8], wuk = (BP)d_in[9], wuv = (BP)d_in[10], wo = (BP)d_in[11], gw = (BP)d_in[12];

  static EncFn enc = nullptr;
  if (!enc) {
    cudaDriverEntryPointQueryResult qr;
    cudaGetDriverEntryPoint("cuTensorMapEncodeTiled", (void**)&enc, cudaEnableDefault, &qr);
    cudaFuncSetAttribute(mega_kernel, cudaFuncAttributeMaxDynamicSharedMemorySize, SMEM_BYTES + FINE_EXTRA);
  }
  Params p;
  void* yT = nullptr;
  cudaGetSymbolAddress(&yT, g_yT);
  enc2d(enc, &p.x, xq, DM, SEQ, 64, 128);
  enc2d(enc, &p.c, ckv, DC, SEQ, 64, 128);
  enc3d(enc, &p.wq, wq, DM, NH * HD);
  enc3d(enc, &p.wuk, wuk, DC, NH * HD);
  enc3d(enc, &p.wuv, wuv, DC, NH * HD);
  enc2d(enc, &p.wo, wo, DM, NH * HD, 64, 64);
  enc2d(enc, &p.y, yT, SEQ, DM, 64, 128);
  enc2d(enc, &p.out, d_out, DM, SEQ, 64, 16);
  p.xp = xq; p.gate_w = gw; p.ak = ak; p.av = av; p.shk = shk; p.ssk = ssk; p.ssd = ssd;

  mega_kernel<<<132, NTHREADS, SMEM_BYTES + FINE_EXTRA>>>(p);
}
```

```cpp
#include <cuda_runtime.h>
#include <cuda.h>
#include <cuda_bf16.h>
#include <stdint.h>

namespace {

constexpr int SEQ = 2048, DM = 1024, DC = 512, NH = 32, HD = 128;
constexpr int GR = 16384;
constexpr int NGR = 14;
constexpr int SM_BAR = NGR * GR;
constexpr int SM_GATE = SM_BAR + 512;
constexpr int SM_UST = SM_GATE + 512;
constexpr int SMEM_BYTES = SM_UST + 2048;
constexpr int NTHREADS = 384;
#define SM_LIMIT 1048576.f
constexpr int CN_MAIN = 5, CN_SPARE = 96;
constexpr int P3G = 8, P3X = 10, P3Y = 12;
constexpr int NMAIN = 128;

constexpr int B_FULL = 0, B_EMPTY = 14, B_EV = 28, B_DONE = 34;

__device__ __align__(1024) uint8_t g_kimg[NH * 16 * 32768];
__device__ __align__(1024) uint8_t g_vimg[NH * 16 * 32768];
__device__ __align__(1024) uint8_t g_cimg[16 * NH * 32768];
__device__ __align__(1024) __nv_bfloat16 g_yT[DM * SEQ];
__device__ __align__(1024) float g_gate[SEQ];
constexpr int WSTRIDE = 8832, WBYTES = 8736;
__device__ __align__(1024) uint8_t g_w[DM * WSTRIDE];
__device__ unsigned g_flags[128 * 8];
constexpr int F_KV = 0, F_CTX = 16, F_U = 48, F_Y = 64, F_GATE = 72, F_EXIT = 73, F_NUM = 74;
#define FLAG(i) (&g_flags[(i) * 8])

#define TS(slot)
#define TSW(slot)
#define FT(i)

#define ST_PZ 2048
#define ST_OUT 1
#define QFLUSH 4
#define CONV_LAST 7
#define FINE_MODE 0
#define FINE_RND 1
#define FTA(i) do { if (FINE_MODE == 0) FT(i); } while (0)
#define FTG(i) do { if ((FINE_MODE == 1 || (FINE_MODE == 3 && c.wg == 0)) && rnd == FINE_RND) FT(i); } while (0)
#define FTP(i)
#define FTM(i) do { if (FINE_MODE == 4) FT(i); } while (0)
#define FTC(k) do { if (FINE_MODE == 5 && (i >> 4) == FINE_RND) FT((i & 15) * 8 + (k)); } while (0)
#define FTO(i) do { if (FINE_MODE == 2) FT(i); } while (0)

__device__ __forceinline__ uint32_t smem_u32(const void* p) { return (uint32_t)__cvta_generic_to_shared(p); }
__device__ __forceinline__ void mbar_init(uint32_t bar, int cnt) { asm volatile("mbarrier.init.shared::cta.b64 [%0], %1;" ::"r"(bar), "r"(cnt) : "memory"); }
__device__ __forceinline__ void mbar_expect_tx(uint32_t bar, uint32_t bytes) { asm volatile("mbarrier.arrive.expect_tx.shared::cta.b64 _, [%0], %1;" ::"r"(bar), "r"(bytes) : "memory"); }
__device__ __forceinline__ void mbar_arrive(uint32_t bar) { asm volatile("mbarrier.arrive.shared::cta.b64 _, [%0];" ::"r"(bar) : "memory"); }
__device__ __forceinline__ void mbar_arrive_cluster(uint32_t bar, uint32_t cta) {
  asm volatile("{\n.reg .b32 r;\nmapa.shared::cluster.u32 r, %0, %1;\nmbarrier.arrive.shared::cluster.b64 _, [r];\n}\n" ::"r"(bar), "r"(cta) : "memory");
}
__device__ __forceinline__ bool mbar_try(uint32_t bar, uint32_t parity) {
  uint32_t ok;
  asm volatile("{\n.reg .pred p;\nmbarrier.try_wait.parity.shared::cta.b64 p, [%1], %2;\nselp.u32 %0, 1, 0, p;\n}\n" : "=r"(ok) : "r"(bar), "r"(parity) : "memory");
  return ok;
}
__device__ __forceinline__ bool mbar_test(uint32_t bar, uint32_t parity) {
  uint32_t ok;
  asm volatile("{\n.reg .pred p;\nmbarrier.test_wait.parity.shared::cta.b64 p, [%1], %2;\nselp.u32 %0, 1, 0, p;\n}\n" : "=r"(ok) : "r"(bar), "r"(parity) : "memory");
  return ok;
}
__device__ __forceinline__ void mbar_wait(uint32_t bar, uint32_t parity) {
  asm volatile("{\n.reg .pred p;\nWAIT_LOOP:\nmbarrier.try_wait.parity.shared::cta.b64 p, [%0], %1;\n@p bra WAIT_DONE;\nbra WAIT_LOOP;\nWAIT_DONE:\n}\n" ::"r"(bar), "r"(parity) : "memory");
}
__device__ __forceinline__ void tma2d(uint32_t dst, const CUtensorMap* tm, int c0, int c1, uint32_t bar) {
  asm volatile("cp.async.bulk.tensor.2d.shared::cluster.global.mbarrier::complete_tx::bytes [%0], [%1, {%3, %4}], [%2];"
               ::"r"(dst), "l"(tm), "r"(bar), "r"(c0), "r"(c1) : "memory");
}
__device__ __forceinline__ void tma2d_mc(uint32_t dst, const CUtensorMap* tm, int c0, int c1, uint32_t bar) {
  asm volatile("cp.async.bulk.tensor.2d.shared::cluster.global.mbarrier::complete_tx::bytes.multicast::cluster [%0], [%1, {%3, %4}], [%2], %5;"
               ::"r"(dst), "l"(tm), "r"(bar), "r"(c0), "r"(c1), "h"((uint16_t)3) : "memory");
}
__device__ __forceinline__ void tma3d(uint32_t dst, const CUtensorMap* tm, int c0, int c1, int c2, uint32_t bar) {
  asm volatile("cp.async.bulk.tensor.3d.shared::cluster.global.mbarrier::complete_tx::bytes [%0], [%1, {%3, %4, %5}], [%2];"
               ::"r"(dst), "l"(tm), "r"(bar), "r"(c0), "r"(c1), "r"(c2) : "memory");
}
__device__ __forceinline__ void tma3d_mc(uint32_t dst, const CUtensorMap* tm, int c0, int c1, int c2, uint32_t bar) {
  asm volatile("cp.async.bulk.tensor.3d.shared::cluster.global.mbarrier::complete_tx::bytes.multicast::cluster [%0], [%1, {%3, %4, %5}], [%2], %6;"
               ::"r"(dst), "l"(tm), "r"(bar), "r"(c0), "r"(c1), "r"(c2), "h"((uint16_t)3) : "memory");
}
__device__ __forceinline__ void bulk_g2s(uint32_t dst, const void* src, uint32_t bytes, uint32_t bar) {
  asm volatile("cp.async.bulk.shared::cluster.global.mbarrier::complete_tx::bytes [%0], [%1], %2, [%3];"
               ::"r"(dst), "l"(src), "r"(bytes), "r"(bar) : "memory");
}
__device__ __forceinline__ void tma2d_store(const CUtensorMap* tm, uint32_t src, int c0, int c1) {
  asm volatile("cp.async.bulk.tensor.2d.global.shared::cta.bulk_group [%0, {%2, %3}], [%1];" ::"l"(tm), "r"(src), "r"(c0), "r"(c1) : "memory");
}
__device__ __forceinline__ void pf2d(const CUtensorMap* tm, int c0, int c1) {
  asm volatile("cp.async.bulk.prefetch.tensor.2d.L2.global [%0, {%1, %2}];" ::"l"(tm), "r"(c0), "r"(c1) : "memory");
}
__device__ __forceinline__ void pf3d(const CUtensorMap* tm, int c0, int c1, int c2) {
  asm volatile("cp.async.bulk.prefetch.tensor.3d.L2.global [%0, {%1, %2, %3}];" ::"l"(tm), "r"(c0), "r"(c1), "r"(c2) : "memory");
}
__device__ __forceinline__ void prefetch_tm(const CUtensorMap* tm) { asm volatile("prefetch.tensormap [%0];" ::"l"(tm) : "memory"); }
__device__ __forceinline__ void wg_fence() { asm volatile("wgmma.fence.sync.aligned;" ::: "memory"); }
__device__ __forceinline__ void wg_commit() { asm volatile("wgmma.commit_group.sync.aligned;" ::: "memory"); }
template <int N> __device__ __forceinline__ void wg_wait() { asm volatile("wgmma.wait_group.sync.aligned %0;" ::"n"(N) : "memory"); }
__device__ __forceinline__ void bar_sync(int id, int n) { asm volatile("bar.sync %0, %1;" ::"r"(id), "r"(n) : "memory"); }
__device__ __forceinline__ void bar_arrive(int id, int n) { asm volatile("bar.arrive %0, %1;" ::"r"(id), "r"(n) : "memory"); }
__device__ __forceinline__ void fence_async_smem() { asm volatile("fence.proxy.async.shared::cta;" ::: "memory"); }
__device__ __forceinline__ void fence_async_all() { asm volatile("fence.proxy.async.global;" ::: "memory"); }
__device__ __forceinline__ uint32_t pack_bf16(float lo, float hi) { uint32_t r; asm("cvt.rn.bf16x2.f32 %0, %1, %2;" : "=r"(r) : "f"(hi), "f"(lo)); return r; }
__device__ __forceinline__ float ex2(float x) { float r; asm("ex2.approx.ftz.f32 %0, %1;" : "=f"(r) : "f"(x)); return r; }
__device__ __forceinline__ float rcp(float x) { float r; asm("rcp.approx.ftz.f32 %0, %1;" : "=f"(r) : "f"(x)); return r; }
__device__ __forceinline__ float bf_lo(uint32_t v) { return __uint_as_float(v << 16); }
__device__ __forceinline__ float bf_hi(uint32_t v) { return __uint_as_float(v & 0xffff0000u); }
__device__ __forceinline__ void flag_wait(const unsigned* f, unsigned target) {
  unsigned v;
  do { asm volatile("ld.acquire.gpu.global.u32 %0, [%1];" : "=r"(v) : "l"(f) : "memory"); } while (v < target);
}
__device__ __forceinline__ void fence_release() { asm volatile("fence.release.gpu;" ::: "memory"); }
__device__ __forceinline__ void flag_add(unsigned* f) { asm volatile("red.relaxed.gpu.global.add.u32 [%0], 1;" ::"l"(f) : "memory"); }
__device__ __forceinline__ void cluster_arrive() { asm volatile("barrier.cluster.arrive.relaxed.aligned;" ::: "memory"); }
__device__ __forceinline__ void cluster_wait() { asm volatile("barrier.cluster.wait.aligned;" ::: "memory"); }
__device__ __forceinline__ uint32_t hmul2(uint32_t a, uint32_t b) { uint32_t r; asm("mul.rn.bf16x2 %0, %1, %2;" : "=r"(r) : "r"(a), "r"(b)); return r; }
__device__ __forceinline__ uint32_t hadd2(uint32_t a, uint32_t b) { uint32_t r; asm("add.rn.bf16x2 %0, %1, %2;" : "=r"(r) : "r"(a), "r"(b)); return r; }
__device__ __forceinline__ uint32_t hfma2(uint32_t a, uint32_t b, uint32_t c) { uint32_t r; asm("fma.rn.bf16x2 %0, %1, %2, %3;" : "=r"(r) : "r"(a), "r"(b), "r"(c)); return r; }
__device__ __forceinline__ uint32_t lds32(uint32_t a) { uint32_t r; asm volatile("ld.shared.b32 %0, [%1];" : "=r"(r) : "r"(a) : "memory"); return r; }
__device__ __forceinline__ uint4 lds128(uint32_t a) { uint4 r; asm volatile("ld.shared.v4.b32 {%0,%1,%2,%3}, [%4];" : "=r"(r.x), "=r"(r.y), "=r"(r.z), "=r"(r.w) : "r"(a) : "memory"); return r; }
__device__ __forceinline__ uint32_t desc_k(uint32_t addr) { return ((addr & 0x3FFFF) >> 4) | (1u << 16); }
template <int LBO> __device__ __forceinline__ uint32_t desc_mn(uint32_t addr) { return ((addr & 0x3FFFF) >> 4) | ((uint32_t)(LBO >> 4) << 16); }
#define DHI "0x40000040"

#define R8(d, o) "+f"(d[o]), "+f"(d[o + 1]), "+f"(d[o + 2]), "+f"(d[o + 3]), "+f"(d[o + 4]), "+f"(d[o + 5]), "+f"(d[o + 6]), "+f"(d[o + 7])
#define R32(d, o) R8(d, o), R8(d, o + 8), R8(d, o + 16), R8(d, o + 24)
#define R64(d, o) R32(d, o), R32(d, o + 32)
#define L64 "%0,%1,%2,%3,%4,%5,%6,%7,%8,%9,%10,%11,%12,%13,%14,%15,%16,%17,%18,%19,%20,%21,%22,%23,%24,%25,%26,%27,%28,%29,%30,%31," \
            "%32,%33,%34,%35,%36,%37,%38,%39,%40,%41,%42,%43,%44,%45,%46,%47,%48,%49,%50,%51,%52,%53,%54,%55,%56,%57,%58,%59,%60,%61,%62,%63"
#define L128 L64 ",%64,%65,%66,%67,%68,%69,%70,%71,%72,%73,%74,%75,%76,%77,%78,%79,%80,%81,%82,%83,%84,%85,%86,%87,%88,%89,%90,%91,%92,%93,%94,%95," \
            "%96,%97,%98,%99,%100,%101,%102,%103,%104,%105,%106,%107,%108,%109,%110,%111,%112,%113,%114,%115,%116,%117,%118,%119,%120,%121,%122,%123,%124,%125,%126,%127"

template <int TB> __device__ __forceinline__ void mma_ss_n128(float (&d)[64], uint32_t da, uint32_t db) {
  asm volatile("{\n.reg .b64 da, db;\nmov.b64 da, {%64, " DHI "};\nmov.b64 db, {%65, " DHI "};\n"
               "wgmma.mma_async.sync.aligned.m64n128k16.f32.bf16.bf16 {" L64 "}, da, db, 1, 1, 1, 0, %66;\n}\n"
               : R64(d, 0) : "r"(da), "r"(db), "n"(TB));
}
template <int TB> __device__ __forceinline__ void mma_rs_n128(float (&d)[64], uint32_t a0, uint32_t a1, uint32_t a2, uint32_t a3, uint32_t db, int sd) {
  asm volatile("{\n.reg .pred p;\n.reg .b64 db;\nsetp.ne.b32 p, %69, 0;\nmov.b64 db, {%68, " DHI "};\n"
               "wgmma.mma_async.sync.aligned.m64n128k16.f32.bf16.bf16 {" L64 "}, {%64,%65,%66,%67}, db, p, 1, 1, %70;\n}\n"
               : R64(d, 0) : "r"(a0), "r"(a1), "r"(a2), "r"(a3), "r"(db), "r"(sd), "n"(TB));
}
template <int TB> __device__ __forceinline__ void mma_ss_n256(float (&d)[128], uint32_t da, uint32_t db) {
  asm volatile("{\n.reg .b64 da, db;\nmov.b64 da, {%128, " DHI "};\nmov.b64 db, {%129, " DHI "};\n"
               "wgmma.mma_async.sync.aligned.m64n256k16.f32.bf16.bf16 {" L128 "}, da, db, 1, 1, 1, 0, %130;\n}\n"
               : R64(d, 0), R64(d, 64) : "r"(da), "r"(db), "n"(TB));
}
#define W8(d, o) "=f"(d[o]), "=f"(d[o + 1]), "=f"(d[o + 2]), "=f"(d[o + 3]), "=f"(d[o + 4]), "=f"(d[o + 5]), "=f"(d[o + 6]), "=f"(d[o + 7])
#define W32(d, o) W8(d, o), W8(d, o + 8), W8(d, o + 16), W8(d, o + 24)
#define W64(d, o) W32(d, o), W32(d, o + 32)
template <int TB> __device__ __forceinline__ void mma_ss_n128_init(float (&d)[64], uint32_t da, uint32_t db) {
  asm volatile("{\n.reg .b64 da, db;\nmov.b64 da, {%64, " DHI "};\nmov.b64 db, {%65, " DHI "};\n"
               "wgmma.mma_async.sync.aligned.m64n128k16.f32.bf16.bf16 {" L64 "}, da, db, 0, 1, 1, 0, %66;\n}\n"
               : W64(d, 0) : "r"(da), "r"(db), "n"(TB));
}
template <int TB> __device__ __forceinline__ void mma_ss_n256_init(float (&d)[128], uint32_t da, uint32_t db) {
  asm volatile("{\n.reg .b64 da, db;\nmov.b64 da, {%128, " DHI "};\nmov.b64 db, {%129, " DHI "};\n"
               "wgmma.mma_async.sync.aligned.m64n256k16.f32.bf16.bf16 {" L128 "}, da, db, 0, 1, 1, 0, %130;\n}\n"
               : W64(d, 0), W64(d, 64) : "r"(da), "r"(db), "n"(TB));
}
#define L32 "%0,%1,%2,%3,%4,%5,%6,%7,%8,%9,%10,%11,%12,%13,%14,%15,%16,%17,%18,%19,%20,%21,%22,%23,%24,%25,%26,%27,%28,%29,%30,%31"
__device__ __forceinline__ void mma_ss_n64(float (&d)[32], uint32_t da, uint32_t db) {
  asm volatile("{\n.reg .b64 da, db;\nmov.b64 da, {%32, " DHI "};\nmov.b64 db, {%33, " DHI "};\n"
               "wgmma.mma_async.sync.aligned.m64n64k16.f32.bf16.bf16 {" L32 "}, da, db, 1, 1, 1, 0, 0;\n}\n"
               : R32(d, 0) : "r"(da), "r"(db));
}
__device__ __forceinline__ void mma_ss_n64_init(float (&d)[32], uint32_t da, uint32_t db) {
  asm volatile("{\n.reg .b64 da, db;\nmov.b64 da, {%32, " DHI "};\nmov.b64 db, {%33, " DHI "};\n"
               "wgmma.mma_async.sync.aligned.m64n64k16.f32.bf16.bf16 {" L32 "}, da, db, 0, 1, 1, 0, 0;\n}\n"
               : W32(d, 0) : "r"(da), "r"(db));
}
#define L16 "%0,%1,%2,%3,%4,%5,%6,%7,%8,%9,%10,%11,%12,%13,%14,%15"
__device__ __forceinline__ void mma_rs_n32(float (&d)[16], uint32_t a0, uint32_t a1, uint32_t a2, uint32_t a3, uint32_t db) {
  asm volatile("{\n.reg .b64 db;\nmov.b64 db, {%20, 0x00000008};\n"
               "wgmma.mma_async.sync.aligned.m64n32k16.f32.bf16.bf16 {" L16 "}, {%16,%17,%18,%19}, db, 1, 1, 1, 0;\n}\n"
               : R8(d, 0), R8(d, 8) : "r"(a0), "r"(a1), "r"(a2), "r"(a3), "r"(db));
}
__device__ __forceinline__ void mma_rs_n32_init(float (&d)[16], uint32_t a0, uint32_t a1, uint32_t a2, uint32_t a3, uint32_t db) {
  asm volatile("{\n.reg .b64 db;\nmov.b64 db, {%20, 0x00000008};\n"
               "wgmma.mma_async.sync.aligned.m64n32k16.f32.bf16.bf16 {" L16 "}, {%16,%17,%18,%19}, db, 0, 1, 1, 0;\n}\n"
               : W8(d, 0), W8(d, 8) : "r"(a0), "r"(a1), "r"(a2), "r"(a3), "r"(db));
}
template <int N> __device__ __forceinline__ void reg_fence(float (&d)[N]) {
#pragma unroll
  for (int i = 0; i < N; i++) asm volatile("" : "+f"(d[i])::"memory");
}
template <int N> __device__ __forceinline__ void reg_fence(uint32_t (&d)[N]) {
#pragma unroll
  for (int i = 0; i < N; i++) asm volatile("" : "+r"(d[i])::"memory");
}

struct __align__(64) Params {
  CUtensorMap x, c, wq, wuk, wuv, wo, y, out, w;
  const __nv_bfloat16* xp;
  const __nv_bfloat16* gate_w;
  const __nv_bfloat16 *ak, *av, *shk, *ssk, *ssd;
};

template <int O, int N> __device__ __forceinline__ void pack_frag(const float (&acc)[N], uint32_t (&pk)[32]) {
#pragma unroll
  for (int i = 0; i < 32; i++) pk[i] = pack_bf16(acc[O + 2 * i], acc[O + 2 * i + 1]);
}
__device__ __forceinline__ void pack_frag_scaled(const float (&acc)[64], uint32_t (&pk)[32], float s0, float s1) {
#pragma unroll
  for (int i = 0; i < 32; i++) { const float s = (i & 1) ? s1 : s0; pk[i] = pack_bf16(acc[2 * i] * s, acc[2 * i + 1] * s); }
}
__device__ __forceinline__ void stsm_frag(const uint32_t (&pk)[32], uint32_t a) {
#pragma unroll
  for (int jj = 0; jj < 8; jj++)
    asm volatile("stmatrix.sync.aligned.m8n8.x4.shared.b16 [%0], {%1,%2,%3,%4};" ::"r"((a ^ ((jj & 3) << 5)) + (jj >> 2) * 16384),
                 "r"(pk[4 * jj]), "r"(pk[4 * jj + 1]), "r"(pk[4 * jj + 2]), "r"(pk[4 * jj + 3]) : "memory");
}

struct Cons {
  uint32_t sb;
  uint32_t pf;
  uint32_t rank;
  int wg, tid;
  __device__ __forceinline__ void wait_full(int g) { mbar_wait(sb + SM_BAR + (B_FULL + g) * 8, (pf >> g) & 1); pf ^= 1u << g; }
  __device__ __forceinline__ void release(int g, int n, bool cross) {
    if (tid < 2 * n) mbar_arrive_cluster(sb + SM_BAR + (B_EMPTY + g + (tid >> 1)) * 8, cross ? (uint32_t)(tid & 1) : rank);
  }
  __device__ __forceinline__ void turn_begin() { bar_sync(1 + wg, 256); }
  __device__ __forceinline__ void turn_end() { bar_arrive(2 - wg, 256); }
  __device__ __forceinline__ void staged(int e) { __syncwarp(); if ((tid & 31) == 0) mbar_arrive(sb + SM_BAR + (B_EV + 2 * e + wg) * 8); }
  uint32_t pfree;
  __device__ __forceinline__ void wait_stage_free() { mbar_wait(sb + SM_BAR + (B_EV + 4 + wg) * 8, pfree); pfree ^= 1; }
  __device__ __forceinline__ bool try_full(int g) { return mbar_test(sb + SM_BAR + (B_FULL + g) * 8, (pf >> g) & 1); }
};

constexpr float SM_C = 0.08838834764831845f * 1.4426950408889634f;
struct SoftState { float m0, m1, n0, n1, l0, l1; };
template <int Q, int N> __device__ __forceinline__ void exp_quarter(const float (&S)[N], float (&e)[16], const SoftState& z, float& s0, float& s1) {
#pragma unroll
  for (int i = 0; i < 16; i++) e[i] = ex2(fmaf(S[16 * Q + i], SM_C, (i & 2) ? z.n1 : z.n0));
#pragma unroll
  for (int i = 0; i < 16; i += 4) { s0 += e[i]; s1 += e[i + 2]; s0 += e[i + 1]; s1 += e[i + 3]; }
}
template <int Q> __device__ __forceinline__ void pack_quarter(const float (&e)[16], uint32_t (&P)[32]) {
#pragma unroll
  for (int i = 0; i < 8; i++) P[8 * Q + i] = pack_bf16(e[2 * i], e[2 * i + 1]);
}
template <int NV, int N> __device__ __forceinline__ void update_max(const float (&S)[N], SoftState& z, float& sc0, float& sc1) {
  float a0 = fmaxf(S[0], S[1]), a1 = fmaxf(S[2], S[3]), b0 = fmaxf(S[4], S[5]), b1 = fmaxf(S[6], S[7]);
#pragma unroll
  for (int j = 2; j < NV / 4; j += 2) {
    a0 = fmaxf(a0, fmaxf(S[4 * j], S[4 * j + 1]));
    a1 = fmaxf(a1, fmaxf(S[4 * j + 2], S[4 * j + 3]));
    b0 = fmaxf(b0, fmaxf(S[4 * j + 4], S[4 * j + 5]));
    b1 = fmaxf(b1, fmaxf(S[4 * j + 6], S[4 * j + 7]));
  }
  a0 = fmaxf(a0, b0); a1 = fmaxf(a1, b1);
  a0 = fmaxf(a0, __shfl_xor_sync(0xffffffffu, a0, 1)); a1 = fmaxf(a1, __shfl_xor_sync(0xffffffffu, a1, 1));
  a0 = fmaxf(a0, __shfl_xor_sync(0xffffffffu, a0, 2)); a1 = fmaxf(a1, __shfl_xor_sync(0xffffffffu, a1, 2));
  a0 = fmaxf(a0, z.m0); a1 = fmaxf(a1, z.m1);
  sc0 = ex2((z.m0 - a0) * SM_C); sc1 = ex2((z.m1 - a1) * SM_C);
  z.m0 = a0; z.m1 = a1;
  z.n0 = -a0 * SM_C; z.n1 = -a1 * SM_C;
}
template <int N> __device__ __forceinline__ void soft_start(const float (&S)[N], SoftState& z) {
  z.m0 = z.m1 = -INFINITY; z.l0 = z.l1 = 0.f;
  float sc0, sc1;
  update_max<8>(S, z, sc0, sc1);
}
template <int N> __device__ __forceinline__ void exp_all(const float (&S)[N], uint32_t (&P)[32], const SoftState& z, float& s0, float& s1) {
  float e[16];
  exp_quarter<0>(S, e, z, s0, s1); pack_quarter<0>(e, P);
  exp_quarter<1>(S, e, z, s0, s1); pack_quarter<1>(e, P);
  if (N == 64) {
    exp_quarter<N == 64 ? 2 : 0>(S, e, z, s0, s1); pack_quarter<2>(e, P);
    exp_quarter<N == 64 ? 3 : 0>(S, e, z, s0, s1); pack_quarter<3>(e, P);
  }
}
template <bool HAS_O, int N> __device__ __forceinline__ void soft_fix(const float (&S)[N], float (&O)[64], SoftState& z) {
  float sc0, sc1;
  update_max<N>(S, z, sc0, sc1);
  if (HAS_O) {
    z.l0 *= sc0; z.l1 *= sc1;
#pragma unroll
    for (int j = 0; j < 16; j++) { O[4 * j] *= sc0; O[4 * j + 1] *= sc0; O[4 * j + 2] *= sc1; O[4 * j + 3] *= sc1; }
  }
}
__device__ __forceinline__ bool soft_bad(float s0, float s1) { return !(s0 + s1 <= SM_LIMIT); }
__device__ __forceinline__ void pin(float a, uint32_t never_zero) {
  asm volatile("{\n.reg .pred p;\nsetp.eq.u32 p, %1, 0;\n@p st.shared.f32 [%1], %0;\n}\n" ::"f"(a), "r"(never_zero) : "memory");
}
__device__ __forceinline__ void pin32(const uint32_t (&v)[32], uint32_t never_zero) {
#pragma unroll
  for (int i = 0; i < 32; i += 4)
    asm volatile("{\n.reg .pred p;\nsetp.eq.u32 p, %4, 0;\n@p st.shared.v4.b32 [%4], {%0,%1,%2,%3};\n}\n" ::"r"(v[i]), "r"(v[i + 1]), "r"(v[i + 2]), "r"(v[i + 3]), "r"(never_zero) : "memory");
}
template <int O, int N> __device__ __forceinline__ void reg_fence_part(uint32_t (&d)[32]) {
#pragma unroll
  for (int i = O; i < O + N; i++) asm volatile("" : "+r"(d[i])::"memory");
}
template <int N> __device__ __forceinline__ void mask_diag(float (&S)[N], int d) {
#pragma unroll
  for (int j = 0; j < 8; j++) {
    if (8 * j > d) S[N - 32 + 4 * j] = -INFINITY;
    if (8 * j + 1 > d) S[N - 32 + 4 * j + 1] = -INFINITY;
    if (8 * j > d + 8) S[N - 32 + 4 * j + 2] = -INFINITY;
    if (8 * j + 1 > d + 8) S[N - 32 + 4 * j + 3] = -INFINITY;
  }
}
__device__ __forceinline__ float quad_sum(float v) {
  v += __shfl_xor_sync(0xffffffffu, v, 1);
  v += __shfl_xor_sync(0xffffffffu, v, 2);
  return v;
}
__device__ __forceinline__ void issue_qk(float (&S)[64], uint32_t dq, uint32_t dk) {
  mma_ss_n128_init<0>(S, dq, dk);
#pragma unroll
  for (int s = 1; s < 8; s++) mma_ss_n128<0>(S, dq + (s >> 2) * 1024 + (s & 3) * 2, dk + (s >> 2) * 1024 + (s & 3) * 2);
}
__device__ __forceinline__ void issue_qk(float (&S)[32], uint32_t dq, uint32_t dk) {
  mma_ss_n64_init(S, dq, dk);
#pragma unroll
  for (int s = 1; s < 8; s++) mma_ss_n64(S, dq + (s >> 2) * 1024 + (s & 3) * 2, dk + (s >> 2) * 1024 + (s & 3) * 2);
}
template <int NS> __device__ __forceinline__ void issue_pv(float (&O)[64], const uint32_t (&P)[32], uint32_t dv, int acc) {
#pragma unroll
  for (int s = 0; s < NS; s++) {
    mma_rs_n128<1>(O, P[4 * s], P[4 * s + 1], P[4 * s + 2], P[4 * s + 3], dv + s * 128, s != 0 ? 1 : acc);
    if (s & 1) wg_commit();
  }
}
constexpr uint32_t DG = GR >> 4;
template <int N>
__device__ __forceinline__ void attn_head(Cons& c, float (&O)[64], uint32_t (&P)[32], SoftState& z, uint32_t dq, uint32_t dkk, int dmask) {
  float S[N];
  c.turn_begin();
  wg_fence();
  issue_qk(S, dq, dkk + 6 * DG);
  wg_commit();
  c.turn_end();
#pragma unroll
  for (int i = N / 2; i < 32; i++) P[i] = 0u;
  wg_wait<0>();
  reg_fence(S);
  c.release(6, 2, true);
  mask_diag(S, dmask);
  soft_start(S, z);
#pragma unroll 1
  for (int pass = 0;; pass++) {
    z.l0 = 0.f; z.l1 = 0.f;
    exp_all(S, P, z, z.l0, z.l1);
    if (pass || !__any_sync(0xffffffffu, soft_bad(z.l0, z.l1))) break;
    soft_fix<false>(S, O, z);
  }
}
__device__ __forceinline__ void attn_tail32(Cons& c, float (&O)[64], uint32_t (&P)[32], SoftState& z, uint32_t dq, uint32_t dkk, uint32_t dv0, int dmask) {
  float S[32];
  c.turn_begin();
  wg_fence();
  issue_qk(S, dq, dkk + 8 * DG);
  wg_commit();
  issue_pv<8>(O, P, dv0 + 10 * DG, 1);
  c.turn_end();
  wg_wait<4>();
  reg_fence(S);
  c.release(8, 2, true);
  mask_diag(S, dmask);
  float s0, s1;
#pragma unroll 1
  for (int pass = 0;; pass++) {
    float e[16];
    s0 = 0.f; s1 = 0.f;
    exp_quarter<0>(S, e, z, s0, s1); pin(s1, c.sb); wg_wait<3>(); reg_fence_part<0, 8>(P); pack_quarter<0>(e, P);
    exp_quarter<1>(S, e, z, s0, s1); pin(s1, c.sb); wg_wait<0>(); reg_fence_part<8, 24>(P); reg_fence(O); pack_quarter<1>(e, P);
    if (pass || !__any_sync(0xffffffffu, soft_bad(s0, s1))) break;
    soft_fix<true>(S, O, z);
  }
  z.l0 += s0; z.l1 += s1;
  c.release(10, 2, true);
  c.wait_full(12);
}
template <int NS> __device__ __forceinline__ void attn_last_pv(Cons& c, float (&O)[64], uint32_t (&P)[32], SoftState& z, uint32_t dv0) {
  c.turn_begin();
  wg_fence();
  issue_pv<NS>(O, P, dv0 + 12 * DG, 1);
  c.turn_end();
  z.l0 = rcp(quad_sum(z.l0)); z.l1 = rcp(quad_sum(z.l1));
  wg_wait<0>();
  reg_fence(O); reg_fence(P);
}

__device__ __forceinline__ void conv_final(uint32_t rb, const uint4& u, uint32_t dd, bool on) {
  const uint4 q0 = lds128(rb), q1 = lds128(rb + 4096), q2 = lds128(rb + 8192), q3 = lds128(rb + 12288);
  auto fin = [&](uint32_t x0, uint32_t x1, uint32_t x2, uint32_t x3, uint32_t uu) {
    return hfma2(dd, __byte_perm(uu, uu, 0x1032), hadd2(hadd2(x0, x1), hadd2(x2, x3)));
  };
  asm volatile("{\n.reg .pred p;\nsetp.ne.b32 p, %5, 0;\n@p st.shared.v4.b32 [%0], {%1,%2,%3,%4};\n}\n" ::"r"(rb), "r"(fin(q0.x, q1.x, q2.x, q3.x, u.w)),
               "r"(fin(q0.y, q1.y, q2.y, q3.y, u.z)), "r"(fin(q0.z, q1.z, q2.z, q3.z, u.y)), "r"(fin(q0.w, q1.w, q2.w, q3.w, u.x)), "r"((int)on) : "memory");
}
__device__ __forceinline__ void conv_tasks(Cons& c, const Params& p, int ntask, bool last, int g, int ch, int chstep, uint32_t dkk, int w, int lane) {
  const uint32_t sb = c.sb;
  uint4 u0 = make_uint4(0, 0, 0, 0), u1 = u0;
  uint32_t dd = 0, rb = sb + g * GR;
  c.wait_full(g);
#pragma unroll 1
  for (int i = 0; i < ntask; i++) {
    const uint32_t base = sb + g * GR;
    FTC(0);
    uint32_t a[64];
    const uint32_t hb = base + WBYTES - 28 + (8 * w + (lane >> 2) + (lane & 3)) * 4;
    auto lda = [&](int s) {
      a[4 * s] = lds32(hb + s * 256); a[4 * s + 1] = lds32(hb + s * 256 + 128);
      a[4 * s + 2] = lds32(hb + s * 256 + 16); a[4 * s + 3] = lds32(hb + s * 256 + 144);
    };
    lda(0); lda(15); lda(1); lda(14);
    float acc[8][16];
    const uint32_t db = dkk + ((4352 / 16 - 1) << 16) + g * DG + 16;
    FTC(2);
    c.turn_begin();
    FTC(3);
#pragma unroll
    for (int k = 0; k < 8; k++) {
      if (k < 7) wg_fence();
      if (k == 7 && !(last && i == ntask - 1)) c.turn_end();
#pragma unroll
      for (int J = 7; J >= (k >> 1); J--) {
        if (k == 0) mma_rs_n32_init(acc[J], a[0], a[1], a[2], a[3], db + J * 32);
        else mma_rs_n32(acc[J], a[4 * k], a[4 * k + 1], a[4 * k + 2], a[4 * k + 3], db + (2 * J - k) * 16);
      }
      const int s = 15 - k;
#pragma unroll
      for (int J = 7; J >= (s >> 1); J--) mma_rs_n32(acc[J], a[4 * s], a[4 * s + 1], a[4 * s + 2], a[4 * s + 3], db + (2 * J - s) * 16);
      if (k < 6) { lda(k + 2); lda(13 - k); }
      if (k == 0) conv_final(rb, u0, dd, i > 0);
      if (k == 1) {
        conv_final(rb + 2048, u1, dd, i > 0);
        __syncwarp();
        if (lane == 0 && i > 0) mbar_arrive(sb + SM_BAR + (B_EV + c.wg) * 8);
      }
      if (k == 6) {
        const uint32_t ub = base + 256 + 16 + (c.tid >> 1) * 32 + ((c.tid & 1) ^ 1) * 4352;
        u0 = lds128(ub); u1 = lds128(ub + 2048);
        dd = __bfloat16_as_ushort(p.ssd[ch]) * 0x10001u;
      }
    }
    wg_commit();
    FTC(4);
    g += 2; if (g >= NGR) g -= NGR;
    ch += chstep;
    rb = base + c.tid * 16;
    if (i + 1 < ntask) c.wait_full(g);
    wg_wait<0>();
#pragma unroll
    for (int J = 0; J < 8; J++) reg_fence(acc[J]);
    reg_fence(a);
    bar_sync(3 + c.wg, 128);
    FTC(5);
    const int tw = (lane & 3) + w;
    const uint32_t xb = base + w * 4096 + tw * 32 + (lane >> 2) * 4;
#pragma unroll
    for (int j = 0; j < 32; j++) {
      float v0 = acc[j >> 2][(j & 3) * 4], v1 = acc[j >> 2][(j & 3) * 4 + 1];
      if (j > 0) { v0 += acc[(j - 1) >> 2][((j - 1) & 3) * 4 + 2]; v1 += acc[(j - 1) >> 2][((j - 1) & 3) * 4 + 3]; }
      uint32_t v = pack_bf16(v0, v1), ad = xb + j * 128;
      if (j == 31 && tw >= 4) { v = 0; ad -= 4096; }
      asm volatile("st.shared.b32 [%0], %1;" ::"r"(ad), "r"(v) : "memory");
    }
    c.wait_stage_free();
    bar_sync(3 + c.wg, 128);
    FTC(6);
  }
  conv_final(rb, u0, dd, true);
  conv_final(rb + 2048, u1, dd, true);
  c.staged(0);
}

__global__ void __cluster_dims__(2, 1, 1) __launch_bounds__(NTHREADS, 1) mega_kernel(const __grid_constant__ Params p) {
  extern __shared__ __align__(1024) uint8_t smem_raw[];
  const uint32_t sb = smem_u32(smem_raw);
  const int wgi = __shfl_sync(0xffffffffu, threadIdx.x >> 7, 0);
  const int warp = __shfl_sync(0xffffffffu, threadIdx.x >> 5, 0);
  const uint32_t rank = blockIdx.x & 1;
  int grp, idx;
  {
    uint32_t smid; asm volatile("mov.u32 %0, %smid;" : "=r"(smid));
    const int tp = smid >> 1;
    if (tp < 32) { grp = tp & 7; idx = tp >> 3; }
    else if (tp < 60) { grp = 1 + (tp - 32) % 7; idx = 4 + (tp - 32) / 7; }
    else if (tp < 62) { grp = 8; idx = tp - 60; }
    else { grp = 0; idx = tp - 58; }
  }
  const int lb = (grp * 8 + idx) * 2 + rank;
  const bool spare = grp == 8;
  const int cn = spare ? CN_SPARE : CN_MAIN, cch = spare ? lb - NMAIN : 4 * CN_SPARE + CN_MAIN * lb, cstep = spare ? 4 : 1, cg0 = spare ? 0 : 2;

  if (threadIdx.x == 0) {
    prefetch_tm(&p.c); prefetch_tm(rank ? &p.wuv : &p.wuk);
#pragma unroll 1
    for (int i = 0; i < 2 * NGR + 6; i++) mbar_init(sb + SM_BAR + i * 8, i < NGR || i >= 2 * NGR + 4 ? 1 : 4);
    mbar_init(sb + SM_BAR + B_DONE * 8, 11);
    asm volatile("fence.mbarrier_init.release.cluster;" ::: "memory");
  }
  cluster_arrive();
  cluster_wait();
  TS(0);

  if (wgi == 0) {
    asm volatile("setmaxnreg.dec.sync.aligned.u32 40;");
    const int lane = threadIdx.x & 31;
    cluster_arrive();
    if (warp == 0) {
      if (lane == 0) {
        uint32_t pe = spare ? 0x3FFF : 0x3FFC;
        auto acquire = [&](int g) { mbar_wait(sb + SM_BAR + (B_EMPTY + g) * 8, (pe >> g) & 1); pe ^= 1u << g; };
#pragma unroll 1
        for (int rnd = 0; rnd < (spare ? 0 : 2); rnd++) {
          const int hp = 16 * rnd + 2 * grp;
#pragma unroll 1
          for (int kk = 0; kk < 16; kk++) {
            const int g0 = 2 + 3 * (kk & 3), kb = kk & 7, head = hp + (kk >> 3);
            FTP(kk * 4);
            acquire(g0);
            if (kk < 4) { acquire(g0 + 1); acquire(g0 + 2); } else pe ^= 6u << g0;
            FTP(kk * 4 + 1);
            const uint32_t fb = sb + SM_BAR + (B_FULL + g0) * 8;
            mbar_expect_tx(fb, 3 * GR);
            tma2d(sb + g0 * GR, &p.c, kb * 64, (2 * idx + rank) * 128, fb);
            tma3d_mc(sb + (g0 + 1 + rank) * GR, rank ? &p.wuv : &p.wuk, 0, kb * 64, head * 2, fb);
            if (kk == 4) { prefetch_tm(&p.x); prefetch_tm(&p.wq); }
          }
          const int head = hp + rank;
#pragma unroll 1
          for (int kb = 0; kb < 16; kb++) {
            const int g0 = 2 + 3 * (kb & 3);
            FTP(64 + kb * 4);
            acquire(g0); pe ^= 6u << g0;
            FTP(64 + kb * 4 + 1);
            const uint32_t fb = sb + SM_BAR + (B_FULL + g0) * 8;
            mbar_expect_tx(fb, 3 * GR);
            tma2d_mc(sb + (g0 + rank) * GR, &p.x, kb * 64, (rank ? 15 - idx : idx) * 128, fb);
            tma3d(sb + (g0 + 2) * GR, &p.wq, 0, kb * 64, head * 2, fb);
          }
          flag_wait(FLAG(F_KV + rnd * 8 + grp), 32);
          fence_async_all();
          acquire(2); pe ^= 8u;
          int g0 = 6;
#pragma unroll 1
          for (int f = 0; f < 34; f++) {
            const bool isk = (f == 0) || ((f & 1) && f < 33);
            const int it = (f == 0) ? 0 : (f == 33) ? 16 : isk ? (f + 1) >> 1 : (f >> 1) - 1;
            const int blk = it == 0 ? idx : it <= idx ? it - 1 : it < 16 ? 15 - it : 15 - idx;
            acquire(g0); acquire(g0 + 1);
            const uint32_t fb = sb + SM_BAR + (B_FULL + g0) * 8;
            mbar_expect_tx(fb, 2 * GR);
            bulk_g2s(sb + g0 * GR, (isk ? g_kimg : g_vimg) + (size_t)(head * 16 + blk) * 32768, 2 * GR, fb);
            g0 = g0 == 12 ? 4 : g0 + 2;
            if (rnd == 0) {
              if (f == 20 || f == 22) pf3d(rank ? &p.wuv : &p.wuk, 0, idx * 64, (hp + 16 + (f == 22)) * 2);
              if (f == 24) pf2d(&p.c, grp * 64, (2 * idx + rank) * 128);
              if (f == 26 || f == 28) pf3d(&p.wq, 0, (idx + 4 * (f - 26)) * 64, (hp + 16 + rank) * 2);
            } else {
              if (f >= 18 && !(f & 1)) pf2d(&p.wo, grp * 128 + rank * 64, (idx + 4 * (f - 18)) * 64);
              if (f == 25) asm volatile("cp.async.bulk.prefetch.L2.global [%0], %1;" ::"l"(p.ssk + (size_t)cch * SEQ), "r"(CN_MAIN * 4096) : "memory");
              if (f == 27) {
                flag_wait(FLAG(F_U + 4), NMAIN);
                asm volatile("cp.async.bulk.prefetch.L2.global [%0], %1;" ::"l"(g_w + (size_t)cch * WSTRIDE), "r"(CN_MAIN * WSTRIDE) : "memory");
              }
            }
          }
        }
        {
          int g = cg0;
#pragma unroll 1
          for (int i = 0, ch = cch; i < cn; i++, ch += cstep) {
            if ((i & 15) == 0) { flag_wait(FLAG(F_U + (spare ? 32 - __clz(ch >> 6) : 4)), NMAIN); fence_async_all(); }
            acquire(g);
            const uint32_t fb = sb + SM_BAR + (B_FULL + g) * 8;
            mbar_expect_tx(fb, WBYTES + 4096);
            bulk_g2s(sb + g * GR, g_w + (size_t)ch * WSTRIDE, WBYTES, fb);
            bulk_g2s(sb + g * GR + WBYTES, p.ssk + (size_t)ch * SEQ, 4096, fb);
            g = g == NGR - 1 ? 0 : g + 1;
          }
        }
        if (!spare) {
          prefetch_tm(&p.y); prefetch_tm(&p.out);
          const int rt = 2 * grp + rank, ct = idx;
          int g0 = P3G;
#pragma unroll 1
          for (int kb = 0; kb < 66; kb++) {
            if (kb == 0 || kb == 32 || kb >= 64) {
              flag_wait(FLAG(kb < 64 ? F_CTX + rt * 2 + (kb >> 5) : kb == 64 ? F_GATE : F_Y + ct), kb < 64 ? 32 : 128);
              fence_async_all();
            }
            acquire(g0); acquire(g0 + 1);
            const uint32_t fb = sb + SM_BAR + (B_FULL + g0) * 8;
            mbar_expect_tx(fb, kb == 65 ? 2 * GR + 512 : 2 * GR);
            if (kb < 64) {
              bulk_g2s(sb + g0 * GR, g_cimg + (size_t)(rt * 64 + kb) * GR, GR, fb);
              tma2d_mc(sb + (g0 + 1) * GR + rank * 8192, &p.wo, ct * 128 + rank * 64, kb * 64, fb);
            } else {
              const CUtensorMap* tm = kb == 64 ? &p.x : &p.y;
              const int c0 = (kb == 64 ? ct : rt) * 128, c1 = (kb == 64 ? rt : ct) * 128;
              tma2d(sb + g0 * GR, tm, c0, c1, fb);
              tma2d(sb + (g0 + 1) * GR, tm, c0 + 64, c1, fb);
              if (kb == 65) bulk_g2s(sb + SM_GATE, g_gate + rt * 128, 512, fb);
            }
            g0 = g0 == 12 ? 0 : g0 + 2;
          }
          if (atomicAdd(FLAG(F_EXIT), 1) == NMAIN - 1) {
#pragma unroll 1
            for (int i = 0; i < F_NUM; i++) *FLAG(i) = 0;
          }
        }
        mbar_arrive(sb + SM_BAR + B_DONE * 8);
      }
    } else if (warp < 3) {
      if (lane == 0) {
        const int w = warp - 1;
        uint32_t p0 = 0;
        int cg = cg0 + w, ch = cch + w * cstep;
#pragma unroll 1
        for (int e = spare ? 12 : 0; e < 12 + (cn + 1 - w) / 2; e++) {
          const int rnd = e >= 6, k = e - 6 * rnd, hp = 16 * rnd + 2 * grp;
          uint8_t* dst;
          unsigned* fl = nullptr;
          int npc = 16384 / ST_PZ, pz = ST_PZ, rel = -1;
          uint32_t src = sb + w * 8192;
          if (k < 4) {
            dst = ((k & 1) ? g_vimg : g_kimg) + (size_t)((hp + (k >> 1)) * 16 + 2 * idx + rank) * 32768 + w * 8192;
            if (k == 3) fl = FLAG(F_KV + rnd * 8 + grp);
          } else if (k < 6) {
            const int rt = k == 4 ? idx : 15 - idx;
            dst = g_cimg + (size_t)(rt * 32 + hp + rank) * 32768 + w * 8192;
            fl = FLAG(F_CTX + rt * 2 + rnd);
            if (k == 4) { src += 2 * GR; rel = 2; } else if (rnd) rel = 0;
          } else {
            dst = reinterpret_cast<uint8_t*>(g_yT + (size_t)ch * SEQ);
            fl = FLAG(F_Y + (ch >> 7));
            src = sb + cg * GR; npc = 1; pz = 4096;
          }
          if (k == 4) mbar_wait(sb + SM_BAR + (B_EV + 2 + w) * 8, rnd);
          else { mbar_wait(sb + SM_BAR + (B_EV + w) * 8, p0); p0 ^= 1; }
          if (w == 0) FTP(k * 4 + 2);
          fence_async_smem();
#pragma unroll 1
          for (int i = 0; i < npc; i++) {
            const uint32_t o = (i * ST_PZ >> 13) * 16384 + ((i * ST_PZ) & 8191);
            asm volatile("cp.async.bulk.global.shared::cta.bulk_group [%0], [%1], %2;" ::"l"(dst + o), "r"(src + o), "r"(pz) : "memory");
            asm volatile("cp.async.bulk.commit_group;\ncp.async.bulk.wait_group %0;" ::"n"(ST_OUT) : "memory");
          }
          asm volatile("cp.async.bulk.wait_group.read 0;" ::: "memory");
          if (w == 0) FTP(k * 4 + 3);
          if (k != 4) mbar_arrive(sb + SM_BAR + (B_EV + 4 + w) * 8);
          if (rel >= 0 || (k >= 6 && (!spare || e < 12 + cn / 2 - NGR / 2))) {
#pragma unroll 1
            for (int i = 0; i < 4; i++) mbar_arrive_cluster(sb + SM_BAR + (B_EMPTY + (k >= 6 ? cg : rel + (i >> 1))) * 8, i & 1);
          }
          if (k >= 6) { cg += 2; if (cg >= NGR) cg -= NGR; ch += 2 * cstep; }
          if (fl) {
            asm volatile("cp.async.bulk.wait_group 0;" ::: "memory");
            fence_release();
            flag_add(fl);
          }
        }
        mbar_arrive(sb + SM_BAR + B_DONE * 8);
      }
    } else {
      if (!spare) {
        const int s0 = lb * 16;
#pragma unroll 1
        for (int cg = 0; cg < 16; cg++) {
          const int ch = cg * 64 + 2 * lane;
          const uint32_t* kp = reinterpret_cast<const uint32_t*>(p.ak + (size_t)s0 * DM + ch);
          const uint32_t* vp = reinterpret_cast<const uint32_t*>(p.av + (size_t)s0 * DM + ch);
          if (cg < 15) {
            const __nv_bfloat16* pf = (lane < 16 ? p.ak : p.av) + (size_t)(s0 + (lane & 15)) * DM + cg * 64 + 64;
            asm volatile("prefetch.global.L2 [%0];" ::"l"(pf));
          }
          if (cg == 1) {
#pragma unroll 1
            for (int i = 0; i < 8; i++) asm volatile("prefetch.global.L2 [%0];" ::"l"(p.xp + (size_t)s0 * DM + (i * 32 + lane) * 64));
          }
          const uint4 sw = __ldg(reinterpret_cast<const uint4*>(p.shk + ch * 4));
          uint32_t k3 = 0, k2 = 0, k1 = 0, k0 = 0, up = 0;
          if (lb > 0) { k3 = __ldg(kp - 4 * 512); k2 = __ldg(kp - 3 * 512); k1 = __ldg(kp - 2 * 512); k0 = __ldg(kp - 512); up = __ldg(vp - 512); }
#pragma unroll 1
          for (int hb = 0; hb < 2; hb++) {
            uint32_t kk[8], u[8];
#pragma unroll
            for (int r = 0; r < 8; r++) { kk[r] = __ldg(kp + r * 512); u[r] = __ldg(vp + r * 512); }
            const uint32_t w0 = __byte_perm(sw.x, sw.z, 0x5410), w1 = __byte_perm(sw.x, sw.z, 0x7632);
            const uint32_t w2 = __byte_perm(sw.y, sw.w, 0x5410), w3 = __byte_perm(sw.y, sw.w, 0x7632);
            if (hb == 0) up = hmul2(hadd2(hadd2(hadd2(hmul2(k3, w3), hmul2(k2, w2)), hmul2(k1, w1)), hmul2(k0, w0)), up);
#pragma unroll
            for (int r = 0; r < 8; r++) {
              k3 = k2; k2 = k1; k1 = k0; k0 = kk[r];
              u[r] = hmul2(hadd2(hadd2(hadd2(hmul2(k3, w3), hmul2(k2, w2)), hmul2(k1, w1)), hmul2(k0, w0)), u[r]);
            }
            if (lane == 0) asm volatile("cp.async.bulk.wait_group.read 0;" ::: "memory");
            __syncwarp();
            const uint32_t dst = sb + SM_UST + lane * 32 + ((lane & 4) << 2);
#pragma unroll
            for (int cc = 0; cc < 2; cc++) {
              const uint32_t sel = cc ? 0x7632 : 0x5410;
              asm volatile("st.shared.v4.b32 [%0], {%1,%2,%3,%4};" ::"r"(dst + cc * 1024), "r"(__byte_perm(u[6], u[5], sel)), "r"(__byte_perm(u[4], u[3], sel)),
                           "r"(__byte_perm(u[2], u[1], sel)), "r"(__byte_perm(u[0], up, sel)) : "memory");
              asm volatile("st.shared.v4.b32 [%0], {%1,%2,%3,%4};" ::"r"((dst ^ 16) + cc * 1024), "r"(__byte_perm(u[7], u[6], sel)), "r"(__byte_perm(u[5], u[4], sel)),
                           "r"(__byte_perm(u[3], u[2], sel)), "r"(__byte_perm(u[1], u[0], sel)) : "memory");
            }
            fence_async_smem();
            __syncwarp();
            if (lane == 0) {
              asm volatile("cp.async.bulk.tensor.3d.global.shared::cta.bulk_group [%0, {%2, %3, %4}], [%1];\ncp.async.bulk.commit_group;"
                           ::"l"(&p.w), "r"(sb + SM_UST), "r"(128 + lb * 16 + (hb ^ 1) * 2176), "r"(cg * 32), "r"(0) : "memory");
            }
            up = u[7];
            kp += 8 * 512; vp += 8 * 512;
          }
          if ((cg & (cg + 1)) == 0 && lane == 0) {
            asm volatile("cp.async.bulk.wait_group 0;" ::: "memory");
            fence_release();
            flag_add(FLAG(F_U + 32 - __clz(cg)));
          }
          TSW(10 + cg);
        }
        const uint4* gw = reinterpret_cast<const uint4*>(p.gate_w) + lane;
#pragma unroll 1
        for (int r = 0; r < 16; r += 4) {
          const uint4* xr = reinterpret_cast<const uint4*>(p.xp + (size_t)(s0 + r) * DM) + lane;
          float s[4] = {0.f, 0.f, 0.f, 0.f};
#pragma unroll 1
          for (int i = 0; i < 4; i++) {
            const uint4 b = __ldg(gw + 32 * i);
            uint4 a[4];
#pragma unroll
            for (int j = 0; j < 4; j++) a[j] = __ldg(xr + 32 * i + j * 128);
#pragma unroll
            for (int j = 0; j < 4; j++) {
              const uint32_t m0 = hmul2(a[j].x, b.x), m1 = hmul2(a[j].y, b.y), m2 = hmul2(a[j].z, b.z), m3 = hmul2(a[j].w, b.w);
              s[j] += ((bf_lo(m0) + bf_hi(m0)) + (bf_lo(m1) + bf_hi(m1))) + ((bf_lo(m2) + bf_hi(m2)) + (bf_lo(m3) + bf_hi(m3)));
            }
          }
          float v = (lane & 1) ? s[1] : s[0], w2 = (lane & 1) ? s[3] : s[2];
          v += __shfl_xor_sync(0xffffffffu, (lane & 1) ? s[0] : s[1], 1);
          w2 += __shfl_xor_sync(0xffffffffu, (lane & 1) ? s[2] : s[3], 1);
          float q = (lane & 2) ? w2 : v;
          q += __shfl_xor_sync(0xffffffffu, (lane & 2) ? v : w2, 2);
#pragma unroll
          for (int o = 4; o < 32; o <<= 1) q += __shfl_xor_sync(0xffffffffu, q, o);
          if (lane < 4) g_gate[s0 + r + lane] = rcp(1.f + __expf(-q));
        }
        fence_release();
        __syncwarp();
        if (lane == 0) flag_add(FLAG(F_GATE));
        TSW(9);
      }
      if (lane == 0) {
        unsigned long long t0, t1;
        asm volatile("mov.u64 %0, %globaltimer;" : "=l"(t0));
        while (!mbar_try(sb + SM_BAR + B_DONE * 8, 0)) {
          asm volatile("mov.u64 %0, %globaltimer;" : "=l"(t1));
          if (t1 - t0 > 2000000000ull) __trap();
        }
      }
    }
    __syncwarp();
    cluster_wait();
  } else {
    asm volatile("setmaxnreg.inc.sync.aligned.u32 232;");
    Cons c;
    c.sb = sb; c.pf = 0; c.rank = rank; c.wg = wgi - 1; c.tid = threadIdx.x & 127;
    const int lane = threadIdx.x & 31, t = lane & 3;
    const int row = c.wg * 64 + (warp & 3) * 16 + (lane >> 2);
    const uint32_t dkk = desc_k(sb), dk0 = dkk + c.wg * 512, dm0 = desc_mn<8192>(sb), dv0 = desc_mn<16384>(sb);
    if (c.wg == 1) bar_arrive(1, 256);
    uint32_t q2par = 1;

    c.pfree = 1;
    const uint32_t stg = sb + (c.wg * 64 + (warp & 3) * 16 + ((lane >> 3) & 1) * 8 + (lane & 7)) * 128 + (((lane >> 4) ^ (lane & 7)) << 4);

#pragma unroll 1
    for (int rnd = 0; rnd < (spare ? 0 : 2); rnd++) {
      uint32_t pv[32];
      FTM(rnd * 8);
      c.wait_full(2);
      FTM(rnd * 8 + 1);
#pragma unroll
      for (int tile = 0; tile < 2; tile++) {
        float acc[128];
        {
          FTG(tile * 32); FTG(tile * 32 + 1);
          const uint32_t a = dk0 + 2 * DG, b = dm0 + 3 * DG;
          c.turn_begin();
          FTG(tile * 32 + 2);
          wg_fence();
          mma_ss_n256_init<1>(acc, a, b);
#pragma unroll
          for (int k = 1; k < 4; k++) mma_ss_n256<1>(acc, a + k * 2, b + k * 128);
          wg_commit();
          c.turn_end();
          FTG(tile * 32 + 3);
        }
#pragma unroll 1
        for (int kb = 1; kb < 8; kb++) {
          const int g0 = 2 + 3 * (kb & 3);
          const uint32_t a = dk0 + g0 * DG, b = dm0 + (g0 + 1) * DG;
          FTG(tile * 32 + kb * 4);
          wg_wait<0>();
          c.release(2 + 3 * ((kb - 1) & 3), 3, true);
          FTG(tile * 32 + kb * 4 + 1);
          c.wait_full(g0);
          c.turn_begin();
          FTG(tile * 32 + kb * 4 + 2);
          wg_fence();
#pragma unroll
          for (int k = 0; k < 4; k++) mma_ss_n256<1>(acc, a + k * 2, b + k * 128);
          wg_commit();
          c.turn_end();
          FTG(tile * 32 + kb * 4 + 3);
          if (tile == 1 && kb == 4) { c.wait_stage_free(); stsm_frag(pv, stg); c.staged(0); }
        }
        c.wait_stage_free();
        const bool nxt = c.try_full(2);
        wg_wait<0>();
        reg_fence(acc);
        c.release(11, 3, true);
        pack_frag<0>(acc, pv);
        stsm_frag(pv, stg);
        c.staged(0);
        pack_frag<64>(acc, pv);
        pin32(pv, sb);
        if (!nxt) mbar_wait(sb + SM_BAR + (B_FULL + 2) * 8, (c.pf >> 2) & 1);
        c.pf ^= 4;
      }
      TS(1 + rnd * 3);
      FTM(rnd * 8 + 2);
      {
        float qa[64], qb[64];
        {
          FTG(64); FTG(65);
          const uint32_t a = dk0 + 2 * DG, b = dm0 + 4 * DG;
          c.turn_begin();
          FTG(66);
          wg_fence();
          mma_ss_n128_init<1>(qa, a, b);
          mma_ss_n128_init<1>(qb, a + DG, b);
#pragma unroll
          for (int k = 1; k < 4; k++) {
            mma_ss_n128<1>(qa, a + k * 2, b + k * 128);
            mma_ss_n128<1>(qb, a + DG + k * 2, b + k * 128);
          }
          wg_commit();
          c.turn_end();
          FTG(67);
        }
#pragma unroll 1
        for (int kb = 1; kb < 16; kb++) {
          const int g0 = 2 + 3 * (kb & 3);
          const uint32_t a = dk0 + g0 * DG, b = dm0 + (g0 + 2) * DG;
          FTG(64 + kb * 4);
          wg_wait<0>();
          c.release(2 + 3 * ((kb - 1) & 3), 3, true);
          FTG(65 + kb * 4);
          c.wait_full(g0);
          c.turn_begin();
          FTG(66 + kb * 4);
          wg_fence();
#pragma unroll
          for (int k = 0; k < 4; k++) {
            mma_ss_n128<1>(qa, a + k * 2, b + k * 128);
            mma_ss_n128<1>(qb, a + DG + k * 2, b + k * 128);
          }
          wg_commit();
          c.turn_end();
          FTG(67 + kb * 4);
          if (kb == QFLUSH) { c.wait_stage_free(); stsm_frag(pv, stg); c.staged(0); }
        }
        c.wait_stage_free();
        mbar_wait(sb + SM_BAR + (B_EMPTY + 2) * 8, q2par);
        mbar_wait(sb + SM_BAR + (B_EMPTY + 3) * 8, q2par);
        q2par ^= 1;
        FTM(rnd * 8 + 3);
        wg_wait<0>();
        reg_fence(qa); reg_fence(qb);
        c.release(11, 3, true);
        pack_frag<0>(qa, pv);
        stsm_frag(pv, stg + 2 * GR);
        pack_frag<0>(qb, pv);
        stsm_frag(pv, stg);
        c.wait_full(6);
        fence_async_smem();
        bar_sync(3 + c.wg, 128);
      }
      TS(2 + rnd * 3);
      FTM(rnd * 8 + 4);
      {
        const int nA = idx + 1;
        float O[64];
        uint32_t P[32];
        SoftState z;
        const int dmask = (row & 63) - 2 * t;
        if (c.wg == 0) attn_head<32>(c, O, P, z, dk0 + 2 * DG, dkk, dmask);
        else attn_head<64>(c, O, P, z, dk0 + 2 * DG, dkk, dmask);
#pragma unroll
        for (int i = 0; i < 64; i++) O[i] = 0.f;
        c.wait_full(8);
        c.wait_full(10);
        FTM(rnd * 8 + 5);
        int gk = 8, gv = 10;
#pragma unroll 1
        for (int it = 1; it < 16 + c.wg; it++) {
          float S[64];
          FTA(it * 7 + 0);
          c.turn_begin();
          FTA(it * 7 + 2);
          wg_fence();
          issue_qk(S, dk0 + (it < nA ? 2 * DG : 0), dkk + gk * DG);
          wg_commit();
          issue_pv<8>(O, P, dv0 + gv * DG, it != nA + 1);
          c.turn_end();
          FTA(it * 7 + 3);
          wg_wait<4>();
          reg_fence(S);
          FTA(it * 7 + 4);
          c.release(gk, 2, true);
          float i0, i1;
          if (it == nA || it == 16) {
            if (it == 16) mask_diag(S, dmask);
            else {
              i0 = rcp(quad_sum(z.l0)); i1 = rcp(quad_sum(z.l1));
              soft_start(S, z);
            }
          }
          float s0, s1;
          const int gvo = gv;
          gk = gv == 12 ? 4 : gv + 2;
          gv = it == 16 ? gk : gk == 12 ? 4 : gk + 2;
#pragma unroll 1
          for (int pass = 0;; pass++) {
            float e[16];
            s0 = 0.f; s1 = 0.f;
            exp_quarter<0>(S, e, z, s0, s1); pin(s1, sb); wg_wait<3>(); reg_fence_part<0, 8>(P); pack_quarter<0>(e, P);
            exp_quarter<1>(S, e, z, s0, s1); pin(s1, sb); wg_wait<2>(); reg_fence_part<8, 8>(P); pack_quarter<1>(e, P);
            exp_quarter<2>(S, e, z, s0, s1); pin(s1, sb); wg_wait<1>(); reg_fence_part<16, 8>(P); pack_quarter<2>(e, P);
            exp_quarter<3>(S, e, z, s0, s1); pin(s1, sb); wg_wait<0>(); reg_fence_part<24, 8>(P); reg_fence(O);
            c.release(gvo, pass ? 0 : 2, true);
            const bool ok = c.try_full(gk) & c.try_full(gv);
            pack_quarter<3>(e, P);
            FTA(it * 7 + 5);
            if (!__any_sync(0xffffffffu, soft_bad(s0, s1) || !ok || it == nA) || pass) break;
            if (it == nA) {
              uint32_t pk[32];
              pack_frag_scaled(O, pk, i0, i1);
              stsm_frag(pk, stg + 2 * GR);
              c.staged(1);
            }
            mbar_wait(sb + SM_BAR + (B_FULL + gk) * 8, (c.pf >> gk) & 1);
            mbar_wait(sb + SM_BAR + (B_FULL + gv) * 8, (c.pf >> gv) & 1);
            if (!__any_sync(0xffffffffu, soft_bad(s0, s1))) break;
            soft_fix<true>(S, O, z);
          }
          c.pf ^= (1u << gk) | (1u << gv);
          z.l0 += s0; z.l1 += s1;
          FTA(it * 7 + 6);
        }
        FTM(rnd * 8 + 6);
        if (c.wg == 0) {
          attn_tail32(c, O, P, z, dk0, dkk, dv0, dmask);
          attn_last_pv<4>(c, O, P, z, dv0);
        } else attn_last_pv<8>(c, O, P, z, dv0);
        c.release(12, 2, true);
        pack_frag_scaled(O, P, z.l0, z.l1);
        stsm_frag(P, stg);
        c.staged(0);
        FTM(rnd * 8 + 7);
      }
      TS(3 + rnd * 3);
    }
    conv_tasks(c, p, (cn + 1 - c.wg) / 2, ((cn - 1) & 1) == c.wg, cg0 + c.wg, cch + c.wg * cstep, 2 * cstep, dkk, warp & 3, lane);
    TS(7);
    if (c.wg == 1) c.pf ^= 0x54;
    if (!spare) {
      const int rt = 2 * grp + rank, ct = idx;
      float acc[64];
      int g0 = P3G + 2, pg = P3G;
      {
        FTO(0);
        c.wait_full(P3G);
        FTO(1);
        const uint32_t a = dk0 + P3G * DG, b = dm0 + (P3G + 1) * DG;
        wg_fence();
        mma_ss_n128_init<1>(acc, a, b);
#pragma unroll
        for (int k = 1; k < 4; k++) mma_ss_n128<1>(acc, a + k * 2, b + k * 128);
        wg_commit();
      }
#pragma unroll 1
      for (int kb = 1; kb < 64; kb++) {
        FTO(kb * 2);
        c.wait_full(g0);
        FTO(kb * 2 + 1);
        const uint32_t a = dk0 + g0 * DG, b = dm0 + (g0 + 1) * DG;
        wg_fence();
#pragma unroll
        for (int k = 0; k < 4; k++) mma_ss_n128<1>(acc, a + k * 2, b + k * 128);
        wg_commit();
        wg_wait<1>();
        c.release(pg, kb <= 59 ? 2 : 0, true);
        pg = g0;
        g0 = g0 == 12 ? 0 : g0 + 2;
      }
      cluster_arrive();
      c.wait_full(P3X);
      c.wait_full(P3Y);
      const float g0f = __uint_as_float(lds32(sb + SM_GATE + row * 4)), g1f = __uint_as_float(lds32(sb + SM_GATE + row * 4 + 32));
      const uint32_t gp0 = pack_bf16(g0f, g0f), gp1 = pack_bf16(g1f, g1f);
      const float h0 = 1.f - g0f, h1 = 1.f - g1f;
      const int w = warp & 3;
      const uint32_t xa = stg + P3X * GR;
      const uint32_t ya = sb + P3Y * GR + c.wg * 16384 + ((lane >> 4) * 8 + (lane & 7)) * 128 + (((2 * w + ((lane >> 3) & 1)) ^ (lane & 7)) << 4);
      uint32_t xy[32];
#pragma unroll
      for (int jj = 0; jj < 8; jj++) {
        uint32_t x[4], y[4];
        asm volatile("ldmatrix.sync.aligned.m8n8.x4.shared.b16 {%0,%1,%2,%3}, [%4];" : "=r"(x[0]), "=r"(x[1]), "=r"(x[2]), "=r"(x[3]) : "r"((xa ^ ((jj & 3) << 5)) + (jj >> 2) * 16384) : "memory");
        asm volatile("ldmatrix.sync.aligned.m8n8.x4.trans.shared.b16 {%0,%1,%2,%3}, [%4];" : "=r"(y[0]), "=r"(y[1]), "=r"(y[2]), "=r"(y[3]) : "r"(ya + jj * 2048) : "memory");
#pragma unroll
        for (int i = 0; i < 4; i++) xy[4 * jj + i] = hmul2(x[i], y[i]);
      }
      wg_wait<0>();
      reg_fence(acc);
      TS(8);
      FTM(16);
#pragma unroll
      for (int i = 0; i < 32; i++) {
        const float h = (i & 1) ? h1 : h0;
        xy[i] = hfma2((i & 1) ? gp1 : gp0, xy[i], pack_bf16(acc[2 * i] * h, acc[2 * i + 1] * h));
      }
      stsm_frag(xy, xa);
      FTM(19);
      fence_async_smem();
      __syncwarp();
      FTM(20);
      if (lane == 0) {
        const int r0 = c.wg * 64 + w * 16;
        tma2d_store(&p.out, sb + P3X * GR + r0 * 128, ct * 128, rt * 128 + r0);
        tma2d_store(&p.out, sb + (P3X + 1) * GR + r0 * 128, ct * 128 + 64, rt * 128 + r0);
        asm volatile("cp.async.bulk.commit_group;\ncp.async.bulk.wait_group.read 0;" ::: "memory");
      }
      FTM(21);
    } else cluster_arrive();
    if (lane == 0) mbar_arrive(sb + SM_BAR + B_DONE * 8);
    __syncwarp();
    TS(9);
    cluster_wait();
  }
}

typedef CUresult (*EncFn)(CUtensorMap*, CUtensorMapDataType, cuuint32_t, void*, const cuuint64_t*, const cuuint64_t*, const cuuint32_t*,
                          const cuuint32_t*, CUtensorMapInterleave, CUtensorMapSwizzle, CUtensorMapL2promotion, CUtensorMapFloatOOBfill);

void enc2d(EncFn enc, CUtensorMap* tm, const void* base, uint64_t cols, uint64_t rows, uint32_t bc, uint32_t br) {
  cuuint64_t dims[2] = {cols, rows}; cuuint64_t strides[1] = {cols * 2}; cuuint32_t box[2] = {bc, br}; cuuint32_t es[2] = {1, 1};
  enc(tm, CU_TENSOR_MAP_DATA_TYPE_BFLOAT16, 2, const_cast<void*>(base), dims, strides, box, es, CU_TENSOR_MAP_INTERLEAVE_NONE,
      CU_TENSOR_MAP_SWIZZLE_128B, CU_TENSOR_MAP_L2_PROMOTION_L2_256B, CU_TENSOR_MAP_FLOAT_OOB_FILL_NONE);
}
void enc3d(EncFn enc, CUtensorMap* tm, const void* base, uint64_t K, uint64_t N) {
  cuuint64_t dims[3] = {64, K, N / 64}; cuuint64_t strides[2] = {N * 2, 128}; cuuint32_t box[3] = {64, 64, 2}; cuuint32_t es[3] = {1, 1, 1};
  enc(tm, CU_TENSOR_MAP_DATA_TYPE_BFLOAT16, 3, const_cast<void*>(base), dims, strides, box, es, CU_TENSOR_MAP_INTERLEAVE_NONE,
      CU_TENSOR_MAP_SWIZZLE_128B, CU_TENSOR_MAP_L2_PROMOTION_L2_256B, CU_TENSOR_MAP_FLOAT_OOB_FILL_NONE);
}

}

extern "C" void kernel_launch(void* const* d_in, const int* in_sizes, int n_in, void* d_out, int out_size) {
  (void)in_sizes; (void)n_in; (void)out_size;
  typedef const __nv_bfloat16* BP;
  BP xq = (BP)d_in[0], ak = (BP)d_in[1], av = (BP)d_in[2], shk = (BP)d_in[3], ssk = (BP)d_in[4], ssd = (BP)d_in[5];
  BP ckv = (BP)d_in[7], wq = (BP)d_in[8], wuk = (BP)d_in[9], wuv = (BP)d_in[10], wo = (BP)d_in[11], gw = (BP)d_in[12];

  static EncFn enc = nullptr;
  if (!enc) {
    cudaDriverEntryPointQueryResult qr;
    cudaGetDriverEntryPoint("cuTensorMapEncodeTiled", (void**)&enc, cudaEnableDefault, &qr);
    cudaFuncSetAttribute(mega_kernel, cudaFuncAttributeMaxDynamicSharedMemorySize, SMEM_BYTES);
  }
  Params p;
  void* yT = nullptr;
  cudaGetSymbolAddress(&yT, g_yT);
  enc2d(enc, &p.x, xq, DM, SEQ, 64, 128);
  enc2d(enc, &p.c, ckv, DC, SEQ, 64, 128);
  enc3d(enc, &p.wq, wq, DM, NH * HD);
  enc3d(enc, &p.wuk, wuk, DC, NH * HD);
  enc3d(enc, &p.wuv, wuv, DC, NH * HD);
  enc2d(enc, &p.wo, wo, DM, NH * HD, 64, 64);
  enc2d(enc, &p.y, yT, SEQ, DM, 64, 128);
  enc2d(enc, &p.out, d_out, DM, SEQ, 64, 16);
  {
    void* wp = nullptr;
    cudaGetSymbolAddress(&wp, g_w);
    cuuint64_t dims[3] = {WSTRIDE / 2, DM / 2, 2}; cuuint64_t strides[2] = {2 * WSTRIDE, WSTRIDE}; cuuint32_t box[3] = {16, 32, 2}; cuuint32_t es[3] = {1, 1, 1};
    enc(&p.w, CU_TENSOR_MAP_DATA_TYPE_BFLOAT16, 3, wp, dims, strides, box, es, CU_TENSOR_MAP_INTERLEAVE_NONE,
        CU_TENSOR_MAP_SWIZZLE_32B, CU_TENSOR_MAP_L2_PROMOTION_NONE, CU_TENSOR_MAP_FLOAT_OOB_FILL_NONE);
  }
  p.xp = xq; p.gate_w = gw; p.ak = ak; p.av = av; p.shk = shk; p.ssk = ssk; p.ssd = ssd;

  mega_kernel<<<132, NTHREADS, SMEM_BYTES>>>(p);
}
```

```cpp
#include <cuda_runtime.h>
#include <cuda.h>
#include <cuda_bf16.h>
#include <stdint.h>

namespace {

constexpr int SEQ = 2048, DM = 1024, DC = 512, NH = 32, HD = 128;
constexpr int GR = 16384;
constexpr int NGR = 14;
constexpr int SM_BAR = NGR * GR;
constexpr int SM_GATE = SM_BAR + 512;
constexpr int SM_UST = SM_GATE + 512;
constexpr int SMEM_BYTES = SM_UST + 2048;
constexpr int NTHREADS = 384;
#define SM_LIMIT 1048576.f
constexpr int CN_MAIN = 5, CN_SPARE = 96;
constexpr int P3G = 6, P3X = 10, P3Y = 12;
constexpr int NMAIN = 128;

constexpr int B_FULL = 0, B_EMPTY = 14, B_EV = 28, B_DONE = 34;

__device__ __align__(1024) uint8_t g_kv[2 * 16 * 16 * 32768];
__device__ __align__(1024) uint8_t g_cimg[16 * NH * 32768];
__device__ __align__(1024) __nv_bfloat16 g_yT[DM * SEQ];
__device__ __align__(1024) float g_gate[SEQ];
constexpr int WSTRIDE = 8832, WBYTES = 8736;
__device__ __align__(1024) uint8_t g_w[DM * WSTRIDE];
__device__ unsigned g_flags[128 * 8];
constexpr int F_KV = 0, F_CTX = 16, F_U = 48, F_AD = 56, F_Y = 64, F_GATE = 72, F_EXIT = 73;
#define FLAG(i) (&g_flags[(i) * 8])

#define TS(slot)
#define TSW(slot)
#define FTX(i, off)
#define FTDUMP()

#define ST_OUT 1
#define QFLUSH 4
#define POL_W EV_FIRST
#define POL_WO EV_FIRST
#define POL_KV EV_NORMAL
#define POL_C EV_FIRST
#define POL_CTX EV_FIRST
#define HALFPV 0
#define FINE_MODE 0
#define FINE_RND 1
#define FTA(i) do { if (FINE_MODE == 0) FTX(i, rnd ^ FINE_RND); } while (0)
#define FTG(i) do { if (FINE_MODE == 1) FTX(i, rnd ^ FINE_RND); } while (0)
#define FTM(i) do { if (FINE_MODE == 4) FTX(i, 0); } while (0)
#define FTC(k) do { if (FINE_MODE == 5) FTX((i & 7) * 8 + (k), (i >> 3) ^ FINE_RND); } while (0)
#define FTO(i) do { if (FINE_MODE == 2) FTX(i, 0); } while (0)

__device__ __forceinline__ uint32_t smem_u32(const void* p) { return (uint32_t)__cvta_generic_to_shared(p); }
__device__ __forceinline__ void mbar_init(uint32_t bar, int cnt) { asm volatile("mbarrier.init.shared::cta.b64 [%0], %1;" ::"r"(bar), "r"(cnt) : "memory"); }
__device__ __forceinline__ void mbar_expect_tx(uint32_t bar, uint32_t bytes) { asm volatile("mbarrier.arrive.expect_tx.shared::cta.b64 _, [%0], %1;" ::"r"(bar), "r"(bytes) : "memory"); }
__device__ __forceinline__ void mbar_arrive(uint32_t bar) { asm volatile("mbarrier.arrive.shared::cta.b64 _, [%0];" ::"r"(bar) : "memory"); }
__device__ __forceinline__ void mbar_arrive_cluster(uint32_t bar, uint32_t cta) {
  asm volatile("{\n.reg .b32 r;\nmapa.shared::cluster.u32 r, %0, %1;\nmbarrier.arrive.shared::cluster.b64 _, [r];\n}\n" ::"r"(bar), "r"(cta) : "memory");
}
__device__ __forceinline__ bool mbar_try(uint32_t bar, uint32_t parity) {
  uint32_t ok;
  asm volatile("{\n.reg .pred p;\nmbarrier.try_wait.parity.shared::cta.b64 p, [%1], %2, 20000;\nselp.u32 %0, 1, 0, p;\n}\n" : "=r"(ok) : "r"(bar), "r"(parity) : "memory");
  return ok;
}
__device__ __forceinline__ bool mbar_test(uint32_t bar, uint32_t parity) {
  uint32_t ok;
  asm volatile("{\n.reg .pred p;\nmbarrier.test_wait.parity.shared::cta.b64 p, [%1], %2;\nselp.u32 %0, 1, 0, p;\n}\n" : "=r"(ok) : "r"(bar), "r"(parity) : "memory");
  return ok;
}
__device__ __forceinline__ void mbar_wait(uint32_t bar, uint32_t parity) {
  asm volatile("{\n.reg .pred p;\nWAIT_LOOP:\nbar.warp.sync -1;\nmbarrier.try_wait.parity.shared::cta.b64 p, [%0], %1;\n@!p bra WAIT_LOOP;\n}\n" ::"r"(bar), "r"(parity) : "memory");
}
__device__ __forceinline__ void mbar_wait1(uint32_t bar, uint32_t parity) {
  asm volatile("{\n.reg .pred p;\nWAIT_LOOP:\nbar.warp.sync -1;\nmbarrier.try_wait.parity.shared::cta.b64 p, [%0], %1, 4000;\n@!p bra WAIT_LOOP;\n}\n" ::"r"(bar), "r"(parity) : "memory");
}
constexpr uint64_t EV_NORMAL = 0x1000000000000000ull, EV_FIRST = 0x12F0000000000000ull;
__device__ __forceinline__ uint32_t ldg_stream(const uint32_t* p) {
  uint32_t r; asm volatile("ld.global.nc.L1::no_allocate.L2::cache_hint.b32 %0, [%1], %2;" : "=r"(r) : "l"(p), "l"(EV_FIRST)); return r;
}
__device__ __forceinline__ void tma2d(uint32_t dst, const CUtensorMap* tm, int c0, int c1, uint32_t bar, uint64_t pol) {
  asm volatile("cp.async.bulk.tensor.2d.shared::cluster.global.mbarrier::complete_tx::bytes.L2::cache_hint [%0], [%1, {%3, %4}], [%2], %5;"
               ::"r"(dst), "l"(tm), "r"(bar), "r"(c0), "r"(c1), "l"(pol) : "memory");
}
__device__ __forceinline__ void tma2d_mc(uint32_t dst, const CUtensorMap* tm, int c0, int c1, uint32_t bar, uint64_t pol) {
  asm volatile("cp.async.bulk.tensor.2d.shared::cluster.global.mbarrier::complete_tx::bytes.multicast::cluster.L2::cache_hint [%0], [%1, {%3, %4}], [%2], %5, %6;"
               ::"r"(dst), "l"(tm), "r"(bar), "r"(c0), "r"(c1), "h"((uint16_t)3), "l"(pol) : "memory");
}
__device__ __forceinline__ void tma3d(uint32_t dst, const CUtensorMap* tm, int c0, int c1, int c2, uint32_t bar, uint64_t pol) {
  asm volatile("cp.async.bulk.tensor.3d.shared::cluster.global.mbarrier::complete_tx::bytes.L2::cache_hint [%0], [%1, {%3, %4, %5}], [%2], %6;"
               ::"r"(dst), "l"(tm), "r"(bar), "r"(c0), "r"(c1), "r"(c2), "l"(pol) : "memory");
}
__device__ __forceinline__ void tma3d_mc(uint32_t dst, const CUtensorMap* tm, int c0, int c1, int c2, uint32_t bar, uint64_t pol) {
  asm volatile("cp.async.bulk.tensor.3d.shared::cluster.global.mbarrier::complete_tx::bytes.multicast::cluster.L2::cache_hint [%0], [%1, {%3, %4, %5}], [%2], %6, %7;"
               ::"r"(dst), "l"(tm), "r"(bar), "r"(c0), "r"(c1), "r"(c2), "h"((uint16_t)3), "l"(pol) : "memory");
}
__device__ __forceinline__ void bulk_g2s(uint32_t dst, const void* src, uint32_t bytes, uint32_t bar, uint64_t pol) {
  asm volatile("cp.async.bulk.shared::cluster.global.mbarrier::complete_tx::bytes.L2::cache_hint [%0], [%1], %2, [%3], %4;"
               ::"r"(dst), "l"(src), "r"(bytes), "r"(bar), "l"(pol) : "memory");
}
__device__ __forceinline__ void tma2d_store(const CUtensorMap* tm, uint32_t src, int c0, int c1) {
  asm volatile("cp.async.bulk.tensor.2d.global.shared::cta.bulk_group [%0, {%2, %3}], [%1];" ::"l"(tm), "r"(src), "r"(c0), "r"(c1) : "memory");
}
__device__ __forceinline__ void prefetch_tm(const CUtensorMap* tm) { asm volatile("prefetch.tensormap [%0];" ::"l"(tm) : "memory"); }
__device__ __forceinline__ void wg_fence() { asm volatile("wgmma.fence.sync.aligned;" ::: "memory"); }
__device__ __forceinline__ void wg_commit() { asm volatile("wgmma.commit_group.sync.aligned;" ::: "memory"); }
template <int N> __device__ __forceinline__ void wg_wait() { asm volatile("wgmma.wait_group.sync.aligned %0;" ::"n"(N) : "memory"); }
__device__ __forceinline__ void bar_sync(int id, int n) { asm volatile("bar.sync %0, %1;" ::"r"(id), "r"(n) : "memory"); }
__device__ __forceinline__ void bar_arrive(int id, int n) { asm volatile("bar.arrive %0, %1;" ::"r"(id), "r"(n) : "memory"); }
__device__ __forceinline__ void fence_async_smem() { asm volatile("fence.proxy.async.shared::cta;" ::: "memory"); }
__device__ __forceinline__ void fence_async_all() { asm volatile("fence.proxy.async.global;" ::: "memory"); }
__device__ __forceinline__ uint32_t pack_bf16(float lo, float hi) { uint32_t r; asm("cvt.rn.bf16x2.f32 %0, %1, %2;" : "=r"(r) : "f"(hi), "f"(lo)); return r; }
__device__ __forceinline__ float ex2(float x) { float r; asm("ex2.approx.ftz.f32 %0, %1;" : "=f"(r) : "f"(x)); return r; }
__device__ __forceinline__ float rcp(float x) { float r; asm("rcp.approx.ftz.f32 %0, %1;" : "=f"(r) : "f"(x)); return r; }
__device__ __forceinline__ void flag_wait(const unsigned* f, unsigned target) {
  unsigned v;
  do { asm volatile("ld.acquire.gpu.global.u32 %0, [%1];" : "=r"(v) : "l"(f) : "memory"); } while (__any_sync(0xffffffffu, v < target));
}
__device__ __forceinline__ bool elect() {
  uint32_t r;
  asm volatile("{\n.reg .pred p;\nelect.sync _|p, -1;\nselp.u32 %0, 1, 0, p;\n}\n" : "=r"(r));
  return r;
}
__device__ __forceinline__ void fence_release() { asm volatile("fence.release.gpu;" ::: "memory"); }
__device__ __forceinline__ void flag_add(unsigned* f) { asm volatile("red.relaxed.gpu.global.add.u32 [%0], 1;" ::"l"(f) : "memory"); }
__device__ __forceinline__ void cluster_arrive() { asm volatile("barrier.cluster.arrive.relaxed.aligned;" ::: "memory"); }
__device__ __forceinline__ void cluster_wait() { asm volatile("barrier.cluster.wait.aligned;" ::: "memory"); }
__device__ __forceinline__ uint32_t hmul2(uint32_t a, uint32_t b) { uint32_t r; asm("mul.rn.bf16x2 %0, %1, %2;" : "=r"(r) : "r"(a), "r"(b)); return r; }
__device__ __forceinline__ uint32_t hadd2(uint32_t a, uint32_t b) { uint32_t r; asm("add.rn.bf16x2 %0, %1, %2;" : "=r"(r) : "r"(a), "r"(b)); return r; }
__device__ __forceinline__ uint32_t hfma2(uint32_t a, uint32_t b, uint32_t c) { uint32_t r; asm("fma.rn.bf16x2 %0, %1, %2, %3;" : "=r"(r) : "r"(a), "r"(b), "r"(c)); return r; }
__device__ __forceinline__ uint32_t lds32(uint32_t a) { uint32_t r; asm volatile("ld.shared.b32 %0, [%1];" : "=r"(r) : "r"(a) : "memory"); return r; }
__device__ __forceinline__ uint4 lds128(uint32_t a) { uint4 r; asm volatile("ld.shared.v4.b32 {%0,%1,%2,%3}, [%4];" : "=r"(r.x), "=r"(r.y), "=r"(r.z), "=r"(r.w) : "r"(a) : "memory"); return r; }
__device__ __forceinline__ uint32_t desc_k(uint32_t addr) { return ((addr & 0x3FFFF) >> 4) | (1u << 16); }
template <int LBO> __device__ __forceinline__ uint32_t desc_mn(uint32_t addr) { return ((addr & 0x3FFFF) >> 4) | ((uint32_t)(LBO >> 4) << 16); }
#define DHI "0x40000040"

#define R8(d, o) "+f"(d[o]), "+f"(d[o + 1]), "+f"(d[o + 2]), "+f"(d[o + 3]), "+f"(d[o + 4]), "+f"(d[o + 5]), "+f"(d[o + 6]), "+f"(d[o + 7])
#define R32(d, o) R8(d, o), R8(d, o + 8), R8(d, o + 16), R8(d, o + 24)
#define R64(d, o) R32(d, o), R32(d, o + 32)
#define L64 "%0,%1,%2,%3,%4,%5,%6,%7,%8,%9,%10,%11,%12,%13,%14,%15,%16,%17,%18,%19,%20,%21,%22,%23,%24,%25,%26,%27,%28,%29,%30,%31," \
            "%32,%33,%34,%35,%36,%37,%38,%39,%40,%41,%42,%43,%44,%45,%46,%47,%48,%49,%50,%51,%52,%53,%54,%55,%56,%57,%58,%59,%60,%61,%62,%63"
#define L128 L64 ",%64,%65,%66,%67,%68,%69,%70,%71,%72,%73,%74,%75,%76,%77,%78,%79,%80,%81,%82,%83,%84,%85,%86,%87,%88,%89,%90,%91,%92,%93,%94,%95," \
            "%96,%97,%98,%99,%100,%101,%102,%103,%104,%105,%106,%107,%108,%109,%110,%111,%112,%113,%114,%115,%116,%117,%118,%119,%120,%121,%122,%123,%124,%125,%126,%127"

template <int TB> __device__ __forceinline__ void mma_ss_n128(float (&d)[64], uint32_t da, uint32_t db) {
  asm volatile("{\n.reg .b64 da, db;\nmov.b64 da, {%64, " DHI "};\nmov.b64 db, {%65, " DHI "};\n"
               "wgmma.mma_async.sync.aligned.m64n128k16.f32.bf16.bf16 {" L64 "}, da, db, 1, 1, 1, 0, %66;\n}\n"
               : R64(d, 0) : "r"(da), "r"(db), "n"(TB));
}
template <int TB> __device__ __forceinline__ void mma_rs_n128(float (&d)[64], uint32_t a0, uint32_t a1, uint32_t a2, uint32_t a3, uint32_t db, int sd) {
  asm volatile("{\n.reg .pred p;\n.reg .b64 db;\nsetp.ne.b32 p, %69, 0;\nmov.b64 db, {%68, " DHI "};\n"
               "wgmma.mma_async.sync.aligned.m64n128k16.f32.bf16.bf16 {" L64 "}, {%64,%65,%66,%67}, db, p, 1, 1, %70;\n}\n"
               : R64(d, 0) : "r"(a0), "r"(a1), "r"(a2), "r"(a3), "r"(db), "r"(sd), "n"(TB));
}
template <int TB> __device__ __forceinline__ void mma_ss_n256(float (&d)[128], uint32_t da, uint32_t db) {
  asm volatile("{\n.reg .b64 da, db;\nmov.b64 da, {%128, " DHI "};\nmov.b64 db, {%129, " DHI "};\n"
               "wgmma.mma_async.sync.aligned.m64n256k16.f32.bf16.bf16 {" L128 "}, da, db, 1, 1, 1, 0, %130;\n}\n"
               : R64(d, 0), R64(d, 64) : "r"(da), "r"(db), "n"(TB));
}
#define W8(d, o) "=f"(d[o]), "=f"(d[o + 1]), "=f"(d[o + 2]), "=f"(d[o + 3]), "=f"(d[o + 4]), "=f"(d[o + 5]), "=f"(d[o + 6]), "=f"(d[o + 7])
#define W32(d, o) W8(d, o), W8(d, o + 8), W8(d, o + 16), W8(d, o + 24)
#define W64(d, o) W32(d, o), W32(d, o + 32)
template <int TB> __device__ __forceinline__ void mma_ss_n128_init(float (&d)[64], uint32_t da, uint32_t db) {
  asm volatile("{\n.reg .b64 da, db;\nmov.b64 da, {%64, " DHI "};\nmov.b64 db, {%65, " DHI "};\n"
               "wgmma.mma_async.sync.aligned.m64n128k16.f32.bf16.bf16 {" L64 "}, da, db, 0, 1, 1, 0, %66;\n}\n"
               : W64(d, 0) : "r"(da), "r"(db), "n"(TB));
}
template <int TB> __device__ __forceinline__ void mma_ss_n256_init(float (&d)[128], uint32_t da, uint32_t db) {
  asm volatile("{\n.reg .b64 da, db;\nmov.b64 da, {%128, " DHI "};\nmov.b64 db, {%129, " DHI "};\n"
               "wgmma.mma_async.sync.aligned.m64n256k16.f32.bf16.bf16 {" L128 "}, da, db, 0, 1, 1, 0, %130;\n}\n"
               : W64(d, 0), W64(d, 64) : "r"(da), "r"(db), "n"(TB));
}
#define L32 "%0,%1,%2,%3,%4,%5,%6,%7,%8,%9,%10,%11,%12,%13,%14,%15,%16,%17,%18,%19,%20,%21,%22,%23,%24,%25,%26,%27,%28,%29,%30,%31"
__device__ __forceinline__ void mma_ss_n64(float (&d)[32], uint32_t da, uint32_t db) {
  asm volatile("{\n.reg .b64 da, db;\nmov.b64 da, {%32, " DHI "};\nmov.b64 db, {%33, " DHI "};\n"
               "wgmma.mma_async.sync.aligned.m64n64k16.f32.bf16.bf16 {" L32 "}, da, db, 1, 1, 1, 0, 0;\n}\n"
               : R32(d, 0) : "r"(da), "r"(db));
}
__device__ __forceinline__ void mma_ss_n64_init(float (&d)[32], uint32_t da, uint32_t db) {
  asm volatile("{\n.reg .b64 da, db;\nmov.b64 da, {%32, " DHI "};\nmov.b64 db, {%33, " DHI "};\n"
               "wgmma.mma_async.sync.aligned.m64n64k16.f32.bf16.bf16 {" L32 "}, da, db, 0, 1, 1, 0, 0;\n}\n"
               : W32(d, 0) : "r"(da), "r"(db));
}
#define L16 "%0,%1,%2,%3,%4,%5,%6,%7,%8,%9,%10,%11,%12,%13,%14,%15"
__device__ __forceinline__ void mma_rs_n32(float (&d)[16], uint32_t a0, uint32_t a1, uint32_t a2, uint32_t a3, uint32_t db) {
  asm volatile("{\n.reg .b64 db;\nmov.b64 db, {%20, 0x00000008};\n"
               "wgmma.mma_async.sync.aligned.m64n32k16.f32.bf16.bf16 {" L16 "}, {%16,%17,%18,%19}, db, 1, 1, 1, 0;\n}\n"
               : R8(d, 0), R8(d, 8) : "r"(a0), "r"(a1), "r"(a2), "r"(a3), "r"(db));
}
__device__ __forceinline__ void mma_rs_n32_init(float (&d)[16], uint32_t a0, uint32_t a1, uint32_t a2, uint32_t a3, uint32_t db) {
  asm volatile("{\n.reg .b64 db;\nmov.b64 db, {%20, 0x00000008};\n"
               "wgmma.mma_async.sync.aligned.m64n32k16.f32.bf16.bf16 {" L16 "}, {%16,%17,%18,%19}, db, 0, 1, 1, 0;\n}\n"
               : W8(d, 0), W8(d, 8) : "r"(a0), "r"(a1), "r"(a2), "r"(a3), "r"(db));
}
__device__ __forceinline__ void mma_ss_n8(float (&d)[4], uint32_t da, uint32_t db) {
  asm volatile("{\n.reg .b64 da, db;\nmov.b64 da, {%4, " DHI "};\nmov.b64 db, {%5, 0x00000008};\n"
               "wgmma.mma_async.sync.aligned.m64n8k16.f32.bf16.bf16 {%0,%1,%2,%3}, da, db, 1, 1, 1, 0, 0;\n}\n"
               : "+f"(d[0]), "+f"(d[1]), "+f"(d[2]), "+f"(d[3]) : "r"(da), "r"(db));
}
template <int N> __device__ __forceinline__ void reg_fence(float (&d)[N]) {
#pragma unroll
  for (int i = 0; i < N; i++) asm volatile("" : "+f"(d[i])::"memory");
}
template <int N> __device__ __forceinline__ void reg_fence(uint32_t (&d)[N]) {
#pragma unroll
  for (int i = 0; i < N; i++) asm volatile("" : "+r"(d[i])::"memory");
}

struct __align__(64) Params {
  CUtensorMap x, c, wq, wuk, wuv, wo, y, out, w;
  const __nv_bfloat16* xp;
  const __nv_bfloat16* gate_w;
  const __nv_bfloat16 *ak, *av, *shk, *ssk, *ssd;
  int zero;
};

template <int O, int N, int M> __device__ __forceinline__ void pack_frag(const float (&acc)[N], uint32_t (&pk)[M]) {
#pragma unroll
  for (int i = 0; i < 32; i++) pk[i] = pack_bf16(acc[O + 2 * i], acc[O + 2 * i + 1]);
}
__device__ __forceinline__ void pack_frag_scaled(const float (&acc)[64], uint32_t (&pk)[32], float s0, float s1) {
#pragma unroll
  for (int i = 0; i < 32; i++) { const float s = (i & 1) ? s1 : s0; pk[i] = pack_bf16(acc[2 * i] * s, acc[2 * i + 1] * s); }
}
template <int J0 = 0, int J1 = 8, int M> __device__ __forceinline__ void stsm_frag(const uint32_t (&pk)[M], uint32_t a) {
#pragma unroll
  for (int jj = J0; jj < J1; jj++)
    asm volatile("stmatrix.sync.aligned.m8n8.x4.shared.b16 [%0], {%1,%2,%3,%4};" ::"r"((a ^ ((jj & 3) << 5)) + (jj >> 2) * 16384),
                 "r"(pk[4 * jj]), "r"(pk[4 * jj + 1]), "r"(pk[4 * jj + 2]), "r"(pk[4 * jj + 3]) : "memory");
}

struct Cons {
  uint32_t sb;
  uint32_t pf;
  uint32_t rank;
  int wg, tid;
  __device__ __forceinline__ void wait_full(int g) { mbar_wait(sb + SM_BAR + (B_FULL + g) * 8, (pf >> g) & 1); pf ^= 1u << g; }
  __device__ __forceinline__ void release(int g, int n, bool cross) {
    if (tid < 2 * n) mbar_arrive_cluster(sb + SM_BAR + (B_EMPTY + g + (tid >> 1)) * 8, cross ? (uint32_t)(tid & 1) : rank);
  }
  __device__ __forceinline__ void turn_begin() { bar_sync(1 + wg, 256); }
  __device__ __forceinline__ void turn_end() { bar_arrive(2 - wg, 256); }
  __device__ __forceinline__ void staged(int e) { __syncwarp(); if ((tid & 31) == 0) mbar_arrive(sb + SM_BAR + (B_EV + 2 * e + wg) * 8); }
  int zero;
  uint32_t pfree;
  __device__ __forceinline__ void wait_stage_free() { mbar_wait(sb + SM_BAR + (B_EV + 4 + wg) * 8, pfree); pfree ^= 1; }
  __device__ __forceinline__ bool try_full(int g) { return mbar_test(sb + SM_BAR + (B_FULL + g) * 8, (pf >> g) & 1); }
};

constexpr float SM_C = 0.08838834764831845f * 1.4426950408889634f;
struct SoftState { float m0, m1, n0, n1, l0, l1; };
template <int Q, int N> __device__ __forceinline__ void exp_quarter(const float (&S)[N], float (&e)[16], const SoftState& z, float& s0, float& s1) {
#pragma unroll
  for (int i = 0; i < 16; i++) e[i] = ex2(fmaf(S[16 * Q + i], SM_C, (i & 2) ? z.n1 : z.n0));
#pragma unroll
  for (int i = 0; i < 16; i += 4) { s0 += e[i]; s1 += e[i + 2]; s0 += e[i + 1]; s1 += e[i + 3]; }
}
template <int Q> __device__ __forceinline__ void pack_quarter(const float (&e)[16], uint32_t (&P)[32]) {
#pragma unroll
  for (int i = 0; i < 8; i++) P[8 * Q + i] = pack_bf16(e[2 * i], e[2 * i + 1]);
}
template <int NV, int N> __device__ __forceinline__ void update_max(const float (&S)[N], SoftState& z, float& sc0, float& sc1) {
  float a0 = fmaxf(S[0], S[1]), a1 = fmaxf(S[2], S[3]), b0 = fmaxf(S[4], S[5]), b1 = fmaxf(S[6], S[7]);
#pragma unroll
  for (int j = 2; j < NV / 4; j += 2) {
    a0 = fmaxf(a0, fmaxf(S[4 * j], S[4 * j + 1]));
    a1 = fmaxf(a1, fmaxf(S[4 * j + 2], S[4 * j + 3]));
    b0 = fmaxf(b0, fmaxf(S[4 * j + 4], S[4 * j + 5]));
    b1 = fmaxf(b1, fmaxf(S[4 * j + 6], S[4 * j + 7]));
  }
  a0 = fmaxf(a0, b0); a1 = fmaxf(a1, b1);
  a0 = fmaxf(a0, __shfl_xor_sync(0xffffffffu, a0, 1)); a1 = fmaxf(a1, __shfl_xor_sync(0xffffffffu, a1, 1));
  a0 = fmaxf(a0, __shfl_xor_sync(0xffffffffu, a0, 2)); a1 = fmaxf(a1, __shfl_xor_sync(0xffffffffu, a1, 2));
  a0 = fmaxf(a0, z.m0); a1 = fmaxf(a1, z.m1);
  sc0 = ex2((z.m0 - a0) * SM_C); sc1 = ex2((z.m1 - a1) * SM_C);
  z.m0 = a0; z.m1 = a1;
  z.n0 = -a0 * SM_C; z.n1 = -a1 * SM_C;
}
template <int N> __device__ __forceinline__ void soft_start(const float (&S)[N], SoftState& z) {
  z.m0 = z.m1 = -INFINITY; z.l0 = z.l1 = 0.f;
  float sc0, sc1;
  update_max<8>(S, z, sc0, sc1);
}
template <int N> __device__ __forceinline__ void exp_all(const float (&S)[N], uint32_t (&P)[32], const SoftState& z, float& s0, float& s1) {
  float e[16];
  exp_quarter<0>(S, e, z, s0, s1); pack_quarter<0>(e, P);
  exp_quarter<1>(S, e, z, s0, s1); pack_quarter<1>(e, P);
  if (N == 64) {
    exp_quarter<N == 64 ? 2 : 0>(S, e, z, s0, s1); pack_quarter<2>(e, P);
    exp_quarter<N == 64 ? 3 : 0>(S, e, z, s0, s1); pack_quarter<3>(e, P);
  }
}
template <bool HAS_O, int N> __device__ __forceinline__ void soft_fix(const float (&S)[N], float (&O)[64], SoftState& z) {
  float sc0, sc1;
  update_max<N>(S, z, sc0, sc1);
  if (HAS_O) {
    z.l0 *= sc0; z.l1 *= sc1;
#pragma unroll
    for (int j = 0; j < 16; j++) { O[4 * j] *= sc0; O[4 * j + 1] *= sc0; O[4 * j + 2] *= sc1; O[4 * j + 3] *= sc1; }
  }
}
__device__ __forceinline__ bool soft_bad(float s0, float s1) { return s0 + s1 > SM_LIMIT; }
__device__ __forceinline__ void pin(float a, uint32_t never_zero) {
  asm volatile("{\n.reg .pred p;\nsetp.eq.u32 p, %1, 0;\n@p st.shared.f32 [%1], %0;\n}\n" ::"f"(a), "r"(never_zero) : "memory");
}
template <int M> __device__ __forceinline__ void pin32(const uint32_t (&v)[M], uint32_t never_zero) {
#pragma unroll
  for (int i = 0; i < 32; i += 4)
    asm volatile("{\n.reg .pred p;\nsetp.eq.u32 p, %4, 0;\n@p st.shared.v4.b32 [%4], {%0,%1,%2,%3};\n}\n" ::"r"(v[i]), "r"(v[i + 1]), "r"(v[i + 2]), "r"(v[i + 3]), "r"(never_zero) : "memory");
}
template <int O, int N> __device__ __forceinline__ void reg_fence_part(uint32_t (&d)[32]) {
#pragma unroll
  for (int i = O; i < O + N; i++) asm volatile("" : "+r"(d[i])::"memory");
}
template <int N> __device__ __forceinline__ void mask_diag(float (&S)[N], int d) {
#pragma unroll
  for (int j = 0; j < 8; j++) {
    if (8 * j > d) S[N - 32 + 4 * j] = -INFINITY;
    if (8 * j + 1 > d) S[N - 32 + 4 * j + 1] = -INFINITY;
    if (8 * j > d + 8) S[N - 32 + 4 * j + 2] = -INFINITY;
    if (8 * j + 1 > d + 8) S[N - 32 + 4 * j + 3] = -INFINITY;
  }
}
__device__ __forceinline__ float quad_sum(float v) {
  v += __shfl_xor_sync(0xffffffffu, v, 1);
  v += __shfl_xor_sync(0xffffffffu, v, 2);
  return v;
}
__device__ __forceinline__ void issue_qk(float (&S)[64], uint32_t dq, uint32_t dk) {
  mma_ss_n128_init<0>(S, dq, dk);
#pragma unroll
  for (int s = 1; s < 8; s++) mma_ss_n128<0>(S, dq + (s >> 2) * 1024 + (s & 3) * 2, dk + (s >> 2) * 1024 + (s & 3) * 2);
}
__device__ __forceinline__ void issue_qk(float (&S)[32], uint32_t dq, uint32_t dk) {
  mma_ss_n64_init(S, dq, dk);
#pragma unroll
  for (int s = 1; s < 8; s++) mma_ss_n64(S, dq + (s >> 2) * 1024 + (s & 3) * 2, dk + (s >> 2) * 1024 + (s & 3) * 2);
}
template <int H> __device__ __forceinline__ void issue_pv(float (&O)[64], const uint32_t (&P)[32], uint32_t dv, int acc, bool on) {
  if (on) {
#pragma unroll
    for (int s = 4 * H; s < 4 * H + 4; s++) {
      mma_rs_n128<1>(O, P[4 * s], P[4 * s + 1], P[4 * s + 2], P[4 * s + 3], dv + s * 128, s != 0 ? 1 : acc);
      if (s & 1) wg_commit();
    }
  } else { wg_commit(); wg_commit(); }
}
constexpr uint32_t DG = GR >> 4;
__device__ __forceinline__ void stage_q2(Cons& c, const float (&O)[64], uint32_t (&P)[32], uint32_t stg) {
  wg_commit(); wg_commit(); wg_commit(); wg_commit();
  c.turn_end();
  pack_frag<0>(O, P);
  stsm_frag(P, stg);
  fence_async_smem();
#pragma unroll
  for (int i = 16; i < 32; i++) P[i] = 0;
}
__device__ __forceinline__ void attn_half(Cons& c, float (&O)[64], uint32_t (&P)[32], SoftState& z, uint32_t dk0, uint32_t dkk, uint32_t dv0, int dmask, int last, uint32_t stg) {
  float S[32];
  c.turn_begin();
  wg_fence();
  issue_qk(S, dk0 + (last ? 0 : 2 * DG), dkk + (last ? 8 : 4) * DG);
  wg_commit();
  if (last) {
    issue_pv<0>(O, P, dv0 + 10 * DG, 1, true);
    issue_pv<1>(O, P, dv0 + 10 * DG, 1, true);
    c.turn_end();
  } else stage_q2(c, O, P, stg);
  wg_wait<4>();
  reg_fence(S);
  c.release(last ? 8 : 4, 2, true);
  mask_diag(S, dmask);
  if (!last) soft_start(S, z);
  float s0, s1;
#pragma unroll 1
  for (;;) {
    float e[16];
    s0 = 0.f; s1 = 0.f;
    exp_quarter<0>(S, e, z, s0, s1); pin(s1, c.sb); wg_wait<3>(); reg_fence_part<0, 8>(P); pack_quarter<0>(e, P);
    exp_quarter<1>(S, e, z, s0, s1); pin(s1, c.sb); wg_wait<0>(); reg_fence_part<8, 24>(P); reg_fence(O); pack_quarter<1>(e, P);
    if (!__any_sync(0xffffffffu, soft_bad(s0, s1))) break;
    soft_fix<true>(S, O, z);
  }
  z.l0 += s0; z.l1 += s1;
  c.release(10, last ? 2 : 0, true);
  c.wait_full(last ? 12 : 6);
  if (!last) c.wait_full(8);
}

__device__ __forceinline__ int conv_next(int g, bool spare) { return spare ? (g >= NGR - 2 ? g - (NGR - 4) : g + 2) : g ^ 6; }
__device__ __forceinline__ void conv_final(uint32_t rb, uint32_t yb, const uint4& u, uint32_t dd, bool on) {
  const uint4 q0 = lds128(rb), q1 = lds128(rb + 4096), q2 = lds128(rb + 8192), q3 = lds128(rb + 12288);
  auto fin = [&](uint32_t x0, uint32_t x1, uint32_t x2, uint32_t x3, uint32_t uu) {
    return hfma2(dd, __byte_perm(uu, uu, 0x1032), hadd2(hadd2(x0, x1), hadd2(x2, x3)));
  };
  asm volatile("{\n.reg .pred p;\nsetp.ne.b32 p, %5, 0;\n@p st.shared.v4.b32 [%0], {%1,%2,%3,%4};\n}\n" ::"r"(yb), "r"(fin(q0.x, q1.x, q2.x, q3.x, u.w)),
               "r"(fin(q0.y, q1.y, q2.y, q3.y, u.z)), "r"(fin(q0.z, q1.z, q2.z, q3.z, u.y)), "r"(fin(q0.w, q1.w, q2.w, q3.w, u.x)), "r"((int)on) : "memory");
}
__device__ __forceinline__ void conv_tasks(Cons& c, const Params& p, int ntask, bool last, bool spare, int ch, int chstep, uint32_t dkk, int w, int lane) {
  const uint32_t sb = c.sb;
  int g = 4 + c.wg;
  uint4 u0 = make_uint4(0, 0, 0, 0), u1 = u0;
  uint32_t dd = 0, rb = sb + g * GR;
  const uint32_t yb = sb + c.wg * 8192 + c.tid * 16;
  c.wait_full(g);
#pragma unroll 1
  for (int i = 0; i < ntask; i++) {
    const uint32_t base = sb + g * GR;
    FTC(0);
    uint32_t a[64];
    const uint32_t hb = base + WBYTES - 28 + (8 * w + (lane >> 2) + (lane & 3)) * 4;
    auto lda = [&](int s) {
      a[4 * s] = lds32(hb + s * 256); a[4 * s + 1] = lds32(hb + s * 256 + 128);
      a[4 * s + 2] = lds32(hb + s * 256 + 16); a[4 * s + 3] = lds32(hb + s * 256 + 144);
    };
    lda(0); lda(15); lda(1); lda(14);
    float acc[8][16];
    const uint32_t db = dkk + ((4352 / 16 - 1) << 16) + g * DG + 16;
    FTC(2);
    c.turn_begin();
    FTC(3);
#pragma unroll
    for (int k = 0; k < 8; k++) {
      if (k < 7) wg_fence();
      if (k == 7 && !(last && i == ntask - 1)) c.turn_end();
#pragma unroll
      for (int J = 7; J >= (k >> 1); J--) {
        if (k == 0) mma_rs_n32_init(acc[J], a[0], a[1], a[2], a[3], db + J * 32);
        else mma_rs_n32(acc[J], a[4 * k], a[4 * k + 1], a[4 * k + 2], a[4 * k + 3], db + (2 * J - k) * 16);
      }
      const int s = 15 - k;
#pragma unroll
      for (int J = 7; J >= (s >> 1); J--) mma_rs_n32(acc[J], a[4 * s], a[4 * s + 1], a[4 * s + 2], a[4 * s + 3], db + (2 * J - s) * 16);
      if (k < 6) { lda(k + 2); lda(13 - k); }
      if (k == 0) conv_final(rb, yb, u0, dd, i > 0);
      if (k == 1) {
        conv_final(rb + 2048, yb + 2048, u1, dd, i > 0);
        __syncwarp();
        if (lane == 0 && i > 0) mbar_arrive(sb + SM_BAR + (B_EV + c.wg) * 8);
      }
      if (k == 6) {
        const uint32_t ub = base + 256 + 16 + (c.tid >> 1) * 32 + ((c.tid & 1) ^ 1) * 4352;
        u0 = lds128(ub); u1 = lds128(ub + 2048);
        dd = __bfloat16_as_ushort(p.ssd[ch]) * 0x10001u;
      }
    }
    wg_commit();
    FTC(4);
    g = conv_next(g, spare);
    ch += chstep;
    rb = base + c.tid * 16;
    if (i + 1 < ntask) c.wait_full(g);
    wg_wait<0>();
#pragma unroll
    for (int J = 0; J < 8; J++) reg_fence(acc[J]);
    reg_fence(a);
    bar_sync(3 + c.wg, 128);
    FTC(5);
    const int tw = (lane & 3) + w;
    const uint32_t xb = base + w * 4096 + tw * 32 + (lane >> 2) * 4;
#pragma unroll
    for (int j = 0; j < 32; j++) {
      float v0 = acc[j >> 2][(j & 3) * 4], v1 = acc[j >> 2][(j & 3) * 4 + 1];
      if (j > 0) { v0 += acc[(j - 1) >> 2][((j - 1) & 3) * 4 + 2]; v1 += acc[(j - 1) >> 2][((j - 1) & 3) * 4 + 3]; }
      uint32_t v = pack_bf16(v0, v1), ad = xb + j * 128;
      if (j == 31 && tw >= 4) { v = 0; ad -= 4096; }
      asm volatile("st.shared.b32 [%0], %1;" ::"r"(ad), "r"(v) : "memory");
    }
    c.wait_stage_free();
    bar_sync(3 + c.wg, 128);
    FTC(6);
  }
  conv_final(rb, yb, u0, dd, true);
  conv_final(rb + 2048, yb + 2048, u1, dd, true);
  c.staged(0);
}

__global__ void __cluster_dims__(2, 1, 1) __launch_bounds__(NTHREADS, 1) mega_kernel(const __grid_constant__ Params p) {
  extern __shared__ __align__(1024) uint8_t smem_raw[];
  const uint32_t sb = smem_u32(smem_raw);
  const int wgi = __shfl_sync(0xffffffffu, threadIdx.x >> 7, 0);
  const int warp = __shfl_sync(0xffffffffu, threadIdx.x >> 5, 0);
  const uint32_t rank = blockIdx.x & 1;
  int grp, idx;
  {
    uint32_t smid; asm volatile("mov.u32 %0, %smid;" : "=r"(smid));
    const int tp = smid >> 1;
    if (tp < 32) { grp = tp & 7; idx = tp >> 3; }
    else if (tp < 60) { grp = 1 + (tp - 32) % 7; idx = 4 + (tp - 32) / 7; }
    else if (tp < 62) { grp = 8; idx = tp - 60; }
    else { grp = 0; idx = tp - 58; }
  }
  const int lb = (grp * 8 + idx) * 2 + rank;
  const bool spare = grp == 8;
  const int cn = spare ? CN_SPARE : CN_MAIN, cch = spare ? lb - NMAIN : 4 * CN_SPARE + CN_MAIN * lb, cstep = spare ? 4 : 1;

  if (threadIdx.x == 0) {
    prefetch_tm(&p.c); prefetch_tm(rank ? &p.wuv : &p.wuk);
#pragma unroll 1
    for (int i = 0; i < 2 * NGR + 6; i++) mbar_init(sb + SM_BAR + i * 8, i < NGR || i >= 2 * NGR + 4 ? 1 : 4);
    mbar_init(sb + SM_BAR + B_DONE * 8, 11);
    asm volatile("fence.mbarrier_init.release.cluster;" ::: "memory");
  }
  cluster_arrive();
  cluster_wait();
  TS(0);

  if (wgi == 0) {
    asm volatile("setmaxnreg.dec.sync.aligned.u32 40;");
    const int lane = threadIdx.x & 31;
    cluster_arrive();
    if (warp == 3) {
      if (!spare) {
        const int s0 = lb * 16;
#pragma unroll 1
        for (int cg = 0; cg < 16; cg++) {
          const int ch = cg * 64 + 2 * lane;
          const uint32_t* kp = reinterpret_cast<const uint32_t*>(p.ak + (size_t)s0 * DM + ch);
          const uint32_t* vp = reinterpret_cast<const uint32_t*>(p.av + (size_t)s0 * DM + ch);
          const uint4 sw = __ldg(reinterpret_cast<const uint4*>(p.shk + ch * 4));
          uint32_t k3 = 0, k2 = 0, k1 = 0, k0 = 0, up = 0;
          if (lb > 0) { k3 = ldg_stream(kp - 4 * 512); k2 = ldg_stream(kp - 3 * 512); k1 = ldg_stream(kp - 2 * 512); k0 = ldg_stream(kp - 512); up = ldg_stream(vp - 512); }
          const uint32_t w0 = __byte_perm(sw.x, sw.z, 0x5410), w1 = __byte_perm(sw.x, sw.z, 0x7632);
          const uint32_t w2 = __byte_perm(sw.y, sw.w, 0x5410), w3 = __byte_perm(sw.y, sw.w, 0x7632);
          up = hmul2(hfma2(k0, w0, hfma2(k1, w1, hfma2(k2, w2, hmul2(k3, w3)))), up);
#pragma unroll 1
          for (int hb = 0; hb < 2; hb++) {
            uint32_t kk[8], u[8];
#pragma unroll
            for (int r = 0; r < 8; r++) { kk[r] = ldg_stream(kp + r * 512); u[r] = ldg_stream(vp + r * 512); }
#pragma unroll
            for (int r = 0; r < 8; r++) {
              k3 = k2; k2 = k1; k1 = k0; k0 = kk[r];
              u[r] = hmul2(hfma2(k0, w0, hfma2(k1, w1, hfma2(k2, w2, hmul2(k3, w3)))), u[r]);
            }
            if (lane == 0) asm volatile("cp.async.bulk.wait_group.read 0;" ::: "memory");
            __syncwarp();
            const uint32_t dst = sb + SM_UST + lane * 32 + ((lane & 4) << 2);
#pragma unroll
            for (int cc = 0; cc < 2; cc++) {
              const uint32_t sel = cc ? 0x7632 : 0x5410;
              asm volatile("st.shared.v4.b32 [%0], {%1,%2,%3,%4};" ::"r"(dst + cc * 1024), "r"(__byte_perm(u[6], u[5], sel)), "r"(__byte_perm(u[4], u[3], sel)),
                           "r"(__byte_perm(u[2], u[1], sel)), "r"(__byte_perm(u[0], up, sel)) : "memory");
              asm volatile("st.shared.v4.b32 [%0], {%1,%2,%3,%4};" ::"r"((dst ^ 16) + cc * 1024), "r"(__byte_perm(u[7], u[6], sel)), "r"(__byte_perm(u[5], u[4], sel)),
                           "r"(__byte_perm(u[3], u[2], sel)), "r"(__byte_perm(u[1], u[0], sel)) : "memory");
            }
            fence_async_smem();
            __syncwarp();
            if (lane == 0) {
              asm volatile("cp.async.bulk.tensor.3d.global.shared::cta.bulk_group [%0, {%2, %3, %4}], [%1];\ncp.async.bulk.commit_group;"
                           ::"l"(&p.w), "r"(sb + SM_UST), "r"(128 + lb * 16 + (hb ^ 1) * 2176), "r"(cg * 32), "r"(0) : "memory");
            }
            up = u[7];
            kp += 8 * 512; vp += 8 * 512;
          }
          if ((cg & (cg + 1)) == 0 && lane == 0) {
            asm volatile("cp.async.bulk.wait_group 0;" ::: "memory");
            fence_release();
            flag_add(FLAG(F_U + 32 - __clz(cg)));
          }
          TSW(10 + cg);
        }
      }
      if (lane == 0) {
        unsigned long long t0, t1;
        asm volatile("mov.u64 %0, %globaltimer;" : "=l"(t0));
        while (!mbar_try(sb + SM_BAR + B_DONE * 8, 0)) {
          asm volatile("mov.u64 %0, %globaltimer;" : "=l"(t1));
          if (t1 - t0 > 2000000000ull) __trap();
        }
      }
    } else if (warp != 0) {
      const int w = warp - 1, ne = 12 + (cn + 1 - w) / 2;
      uint32_t p0 = 0;
      int cg = 4 + w, ch = cch + w * cstep;
#pragma unroll 1
      for (int e = spare ? 12 : 0; e < ne; e++) {
        const int rnd = e >= 6, k = e - 6 * rnd, rt = k == 4 ? idx : 15 - idx;
        uint8_t* dst = k < 4 ? g_kv + (size_t)(((k & 1) * 16 + 2 * grp + (k >> 1)) * 16 + 2 * idx + rank) * 32768 + w * 8192
                     : k < 6 ? g_cimg + (size_t)(rt * 32 + 16 * rnd + 2 * grp + rank) * 32768 + w * 8192
                             : reinterpret_cast<uint8_t*>(g_yT + (size_t)ch * SEQ);
        const uint32_t src = sb + w * 8192 + (k == 4 ? 2 * GR : 0);
        if (e == 6) flag_wait(FLAG(F_AD + grp), 32);
        mbar_wait1(sb + SM_BAR + (B_EV + (k == 4 ? 2 : 0) + w) * 8, k == 4 ? rnd : p0);
        if (k != 4) p0 ^= 1;
        if (lane < 4 && k >= 6 && (!spare || e < ne - 6)) mbar_arrive_cluster(sb + SM_BAR + (B_EMPTY + cg) * 8, lane & 1);
        fence_async_smem();
        if (elect()) {
#pragma unroll 1
          for (int i = 0; i < (k >= 6 ? 1 : 8); i++) {
            const uint32_t o = (i >> 2) * 16384 + (i & 3) * 2048;
            asm volatile("cp.async.bulk.global.shared::cta.bulk_group [%0], [%1], %2;" ::"l"(dst + o), "r"(src + o), "r"(k >= 6 ? 4096 : 2048) : "memory");
            asm volatile("cp.async.bulk.commit_group;\ncp.async.bulk.wait_group.read %0;" ::"n"(ST_OUT) : "memory");
          }
          asm volatile("cp.async.bulk.wait_group 0;" ::: "memory");
          if (k != 4) mbar_arrive(sb + SM_BAR + (B_EV + 4 + w) * 8);
        }
        __syncwarp();
        if (lane < 4 && (k == 4 || (e == ne - 1 && !spare)))
          mbar_arrive_cluster(sb + SM_BAR + (B_EMPTY + (k == 4 ? 2 : 0) + (lane >> 1)) * 8, lane & 1);
        if (k >= 3) {
          fence_release();
          if (lane == 0 || (lane == 1 && e == 5))
            flag_add(FLAG(lane ? F_AD + grp : k == 3 ? F_KV + rnd * 8 + grp : k < 6 ? F_CTX + rt * 2 + rnd : F_Y + (ch >> 7)));
        }
        if (k >= 6) { cg = conv_next(cg, spare); ch += 2 * cstep; }
      }
      if (lane == 0) mbar_arrive(sb + SM_BAR + B_DONE * 8);
    } else {
      uint32_t pe = 0x3FFC;
      auto acquire = [&](int g) { mbar_wait1(sb + SM_BAR + (B_EMPTY + g) * 8, (pe >> g) & 1); pe ^= 1u << g; };
#pragma unroll 1
      for (int rnd = 0; rnd < (spare ? 0 : 2); rnd++) {
        const int hp = 16 * rnd + 2 * grp, head = hp + rank;
#pragma unroll 1
        for (int kk = 0; kk < 32; kk++) {
          const int g0 = 2 + 3 * (kk & 3);
          acquire(g0);
          if (kk < 4) { acquire(g0 + 1); acquire(g0 + 2); } else pe ^= 6u << g0;
          if (elect()) {
            const uint32_t fb = sb + SM_BAR + (B_FULL + g0) * 8;
            mbar_expect_tx(fb, 3 * GR);
            if (kk < 16) {
              tma2d(sb + g0 * GR, &p.c, (kk & 7) * 64, (2 * idx + rank) * 128, fb, EV_NORMAL);
              tma3d_mc(sb + (g0 + 1 + rank) * GR, rank ? &p.wuv : &p.wuk, 0, (kk & 7) * 64, (hp + (kk >> 3)) * 2, fb, POL_W);
            } else {
              tma2d_mc(sb + (g0 + rank) * GR, &p.x, (kk - 16) * 64, (rank ? 15 - idx : idx) * 128, fb, EV_NORMAL);
              tma3d(sb + (g0 + 2) * GR, &p.wq, 0, (kk - 16) * 64, head * 2, fb, POL_W);
            }
            if (kk == 3) { prefetch_tm(&p.x); prefetch_tm(&p.wq); }
          }
        }
        flag_wait(FLAG(F_KV + rnd * 8 + grp), 32);
        fence_async_all();
        acquire(2); pe ^= 8u;
        int g0 = 4;
#pragma unroll 1
        for (int f = 0; f < 34; f++) {
          const bool isk = (f == 0) || ((f & 1) && f < 33);
          const int it = (f == 0) ? 0 : (f == 33) ? 16 : isk ? (f + 1) >> 1 : (f >> 1) - 1;
          const int blk = it == 0 ? idx : it <= idx ? it - 1 : it < 16 ? 15 - it : 15 - idx;
          acquire(g0);
          if (f < 8) acquire(g0 + 1); else pe ^= 2u << g0;
          if (elect()) {
            const uint32_t fb = sb + SM_BAR + (B_FULL + g0) * 8;
            mbar_expect_tx(fb, 2 * GR);
            bulk_g2s(sb + g0 * GR, g_kv + (size_t)(((isk ? 0 : 16) + (head & 15)) * 16 + blk) * 32768, 2 * GR, fb, POL_KV);
          }
          g0 = f == 2 ? 12 : g0 == 12 ? 4 : g0 + 2;
        }
      }
      if (spare) {
#pragma unroll 1
        for (int i = -1, g = 1; i < 64; i++) {
          if (i >= 0) acquire(g);
          if (elect()) {
            const uint32_t fb = sb + SM_BAR + (B_FULL + g) * 8;
            mbar_expect_tx(fb, i < 0 ? 2048 : GR);
            if (i < 0) bulk_g2s(sb + GR, p.gate_w, 2048, fb, EV_NORMAL);
            else tma2d(sb + g * GR, &p.x, (i & 15) * 64, (lb - NMAIN) * 512 + (i >> 4) * 128, fb, EV_NORMAL);
          }
          g = g == NGR - 1 ? 2 : g + 1;
        }
      }
      auto conv_fill = [&](int g, int ch) {
        acquire(g);
        if (elect()) {
          const uint32_t fb = sb + SM_BAR + (B_FULL + g) * 8;
          mbar_expect_tx(fb, WBYTES + 4096);
          bulk_g2s(sb + g * GR, g_w + (size_t)ch * WSTRIDE, WBYTES, fb, POL_C);
          bulk_g2s(sb + g * GR + WBYTES, p.ssk + (size_t)ch * SEQ, 4096, fb, POL_C);
        }
      };
#pragma unroll 1
      for (int i = 0, g = 4; i < cn; i++) {
        if ((i & 15) == 0) { flag_wait(FLAG(F_U + (spare ? 32 - __clz(i >> 4) : 4)), NMAIN); fence_async_all(); }
        conv_fill(g + (i & 1), cch + i * cstep);
        if (i & 1) g = conv_next(g, spare);
      }
      if (!spare) {
        const int rt = 2 * grp + rank, ct = idx;
        int g0 = P3G;
#pragma unroll 1
        for (int kb = 0; kb < 66; kb++) {
          if (kb == 0 || kb == 32 || kb >= 64) {
            flag_wait(FLAG(kb < 64 ? F_CTX + rt * 2 + (kb >> 5) : kb == 64 ? F_GATE : F_Y + ct), kb <= 64 ? 32 : 128);
            fence_async_all();
          }
          acquire(g0);
          if (kb < 11) acquire(g0 + 1);
          if (elect()) {
            const uint32_t fb = sb + SM_BAR + (B_FULL + g0) * 8;
            mbar_expect_tx(fb, kb == 64 ? 2 * GR + 512 : 2 * GR);
            if (kb <= 64) bulk_g2s(kb < 64 ? sb + g0 * GR : sb + SM_GATE, kb < 64 ? (const void*)(g_cimg + (size_t)(rt * 64 + kb) * GR) : (const void*)(g_gate + rt * 128), kb < 64 ? GR : 512, fb, POL_CTX);
            if (kb < 64) {
              tma2d_mc(sb + (g0 + 1) * GR + rank * 8192, &p.wo, ct * 128 + rank * 64, kb * 64, fb, POL_WO);
              if (kb == 40) { prefetch_tm(&p.y); prefetch_tm(&p.out); }
            } else {
              const CUtensorMap* tm = kb == 64 ? &p.x : &p.y;
              const int c0 = (kb == 64 ? ct : rt) * 128, c1 = (kb == 64 ? rt : ct) * 128;
              tma2d(sb + g0 * GR, tm, c0, c1, fb, EV_NORMAL);
              tma2d(sb + (g0 + 1) * GR, tm, c0 + 64, c1, fb, EV_NORMAL);
            }
          }
          g0 = g0 == 12 ? (kb == 3 ? 2 : 0) : g0 + 2;
        }
        unsigned n = 0;
        if (lane == 0) n = atomicAdd(FLAG(F_EXIT), 1);
        if (__shfl_sync(0xffffffffu, n, 0) == NMAIN - 1) { *FLAG(lane) = 0; *FLAG(lane + 32) = 0; *FLAG(lane + 64) = 0; }
      }
      if (lane == 0) mbar_arrive(sb + SM_BAR + B_DONE * 8);
    }
    __syncwarp();
    cluster_wait();
  } else {
    asm volatile("setmaxnreg.inc.sync.aligned.u32 232;");
    Cons c;
    c.sb = sb; c.pf = 0; c.rank = rank; c.wg = wgi - 1; c.tid = threadIdx.x & 127;
    const int lane = threadIdx.x & 31, t = lane & 3;
    const int row = c.wg * 64 + (warp & 3) * 16 + (lane >> 2);
    const uint32_t dkk = desc_k(sb), dk0 = dkk + c.wg * 512, dm0 = desc_mn<8192>(sb), dv0 = desc_mn<16384>(sb);
    if (c.wg == 1) bar_arrive(1, 256);
    c.pfree = 1;
    c.zero = p.zero;
    const uint32_t stg = sb + (c.wg * 64 + (warp & 3) * 16 + ((lane >> 3) & 1) * 8 + (lane & 7)) * 128 + (((lane >> 4) ^ (lane & 7)) << 4);

    if (spare) {
      c.wait_full(1);
      int g = 2;
#pragma unroll 1
      for (int r = 0; r < 4; r++) {
        float d[4] = {0.f, 0.f, 0.f, 0.f};
#pragma unroll 1
        for (int kb = 0; kb < 16; kb++) {
          c.wait_full(g);
          wg_fence();
#pragma unroll
          for (int k = 0; k < 4; k++) mma_ss_n8(d, dk0 + g * DG + k * 2, dkk + DG + kb * 8 + k * 2);
          wg_commit();
          wg_wait<0>();
          c.release(g, 1, true);
          g = g == NGR - 1 ? 2 : g + 1;
        }
        reg_fence(d);
        if (t == 0) {
          float* gp = g_gate + (lb - NMAIN) * 512 + r * 128 + row;
          gp[0] = rcp(1.f + ex2(-1.4426950408889634f * d[0])); gp[8] = rcp(1.f + ex2(-1.4426950408889634f * d[2]));
        }
      }
      fence_release();
      __syncwarp();
      if (lane == 0) flag_add(FLAG(F_GATE));
      TS(1);
    }
    uint32_t pv[32];
#pragma unroll
    for (int i = 0; i < 32; i++) pv[i] = 0;
#pragma unroll 1
    for (int rnd = 0; rnd < (spare ? 0 : 2); rnd++) {
      float O[64];
      FTM(rnd * 8);
      c.wait_full(2);
      FTM(rnd * 8 + 1);
#pragma unroll 1
      for (int tile = c.zero; tile < 2; tile++) {
        float acc[128];
        {
          FTG(tile * 32); FTG(tile * 32 + 1);
          const uint32_t a = dk0 + 2 * DG, b = dm0 + 3 * DG;
          c.turn_begin();
          FTG(tile * 32 + 2);
          wg_fence();
          mma_ss_n256_init<1>(acc, a, b);
#pragma unroll
          for (int k = 1; k < 4; k++) mma_ss_n256<1>(acc, a + k * 2, b + k * 128);
          wg_commit();
          FTG(tile * 32 + 3);
        }
#pragma unroll 1
        for (int kb = 1; kb < 8; kb++) {
          const int g0 = 2 + 3 * (kb & 3);
          const uint32_t a = dk0 + g0 * DG, b = dm0 + (g0 + 1) * DG;
          const bool second = kb == 1 || kb == 7;
          FTG(tile * 32 + kb * 4);
          if (!second) { wg_wait<0>(); c.release(2 + 3 * ((kb - 1) & 3), 3, true); }
          FTG(tile * 32 + kb * 4 + 1);
          c.wait_full(g0);
          if (!second) c.turn_begin();
          FTG(tile * 32 + kb * 4 + 2);
          wg_fence();
#pragma unroll
          for (int k = 0; k < 4; k++) mma_ss_n256<1>(acc, a + k * 2, b + k * 128);
          wg_commit();
          if (kb != 6) c.turn_end();
          if (second) { wg_wait<1>(); c.release(2 + 3 * ((kb - 1) & 3), 3, true); }
          FTG(tile * 32 + kb * 4 + 3);
          if (tile == 1 && kb == 3) { c.wait_stage_free(); stsm_frag<0, 4>(pv, stg); }
          if (tile == 1 && kb == 4) { stsm_frag<4, 8>(pv, stg); c.staged(0); }
        }
        c.wait_stage_free();
        const bool nxt = c.try_full(2);
        wg_wait<0>();
        reg_fence(acc);
        c.release(11, 3, true);
        pack_frag<0>(acc, pv);
        stsm_frag(pv, stg);
        c.staged(0);
        pack_frag<64>(acc, pv);
        pin32(pv, sb);
        if (!nxt) mbar_wait(sb + SM_BAR + (B_FULL + 2) * 8, (c.pf >> 2) & 1);
        c.pf ^= 4;
      }
      TS(1 + rnd * 3);
      FTM(rnd * 8 + 2);
      {
        float qa[64];
        float (&qb)[64] = O;
        {
          FTG(64); FTG(65);
          const uint32_t a = dk0 + 2 * DG, b = dm0 + 4 * DG;
          c.turn_begin();
          FTG(66);
          wg_fence();
          mma_ss_n128_init<1>(qa, a, b);
          mma_ss_n128_init<1>(qb, a + DG, b);
#pragma unroll
          for (int k = 1; k < 4; k++) {
            mma_ss_n128<1>(qa, a + k * 2, b + k * 128);
            mma_ss_n128<1>(qb, a + DG + k * 2, b + k * 128);
          }
          wg_commit();
          FTG(67);
        }
#pragma unroll 1
        for (int kb = 1; kb < 16; kb++) {
          const int g0 = 2 + 3 * (kb & 3);
          const uint32_t a = dk0 + g0 * DG, b = dm0 + (g0 + 2) * DG;
          const bool second = kb == 1 || kb == 15;
          FTG(64 + kb * 4);
          if (!second) { wg_wait<0>(); c.release(2 + 3 * ((kb - 1) & 3), 3, true); }
          FTG(65 + kb * 4);
          c.wait_full(g0);
          if (!second) c.turn_begin();
          FTG(66 + kb * 4);
          wg_fence();
#pragma unroll
          for (int k = 0; k < 4; k++) {
            mma_ss_n128<1>(qa, a + k * 2, b + k * 128);
            mma_ss_n128<1>(qb, a + DG + k * 2, b + k * 128);
          }
          wg_commit();
          if (kb != 14) c.turn_end();
          if (second) { wg_wait<1>(); c.release(2 + 3 * ((kb - 1) & 3), 3, true); }
          FTG(67 + kb * 4);
          if (kb == QFLUSH) { c.wait_stage_free(); stsm_frag<0, 4>(pv, stg); }
          if (kb == QFLUSH + 1) { stsm_frag<4, 8>(pv, stg); c.staged(0); }
        }
        c.wait_stage_free();
        mbar_wait(sb + SM_BAR + (B_EMPTY + 2) * 8, rnd ^ 1);
        c.wait_full(4);
        FTM(rnd * 8 + 3);
        wg_wait<0>();
        reg_fence(qa); reg_fence(qb);
        c.release(11, 3, true);
        pack_frag<0>(qa, pv);
        stsm_frag(pv, stg + 2 * GR);
        fence_async_smem();
      }
      TS(2 + rnd * 3);
      FTM(rnd * 8 + 4);
      {
        const int nA = idx + 1;
        uint32_t (&P)[32] = pv;
        SoftState z;
        const int dmask = (row & 63) - 2 * t;
        z.m0 = z.m1 = z.n0 = z.n1 = z.l0 = z.l1 = 0.f;
#pragma unroll 1
        for (int seg = c.zero;; seg++) {
        if (c.wg == 0) attn_half(c, O, P, z, dk0, dkk, dv0, dmask, seg, stg);
        if (seg) break;
        FTM(rnd * 8 + 5);
        int gk = c.wg ? 4 : 6, gv = c.wg ? 4 : 8;
#pragma unroll 1
        for (int it = 1 - c.wg; it < 16 + c.wg; it++) {
          float S[64];
          FTA(it * 7 + 0);
          c.turn_begin();
          FTA(it * 7 + 2);
          wg_fence();
          issue_qk(S, dk0 + (it < nA ? 2 * DG : 0), dkk + gk * DG);
          wg_commit();
          if (it) {
            issue_pv<0>(O, P, dv0 + gv * DG, it != nA + 1 && it != 1, true);
            issue_pv<1>(O, P, dv0 + gv * DG, 1, HALFPV ? it + c.wg > 1 : true);
            c.turn_end();
          } else stage_q2(c, O, P, stg);
          FTA(it * 7 + 3);
          wg_wait<4>();
          reg_fence(S);
          FTA(it * 7 + 4);
          c.release(gk, 2, true);
          float i0, i1;
          if (it == nA || (it & 15) == 0) {
            if (it != nA) mask_diag(S, dmask);
            if (it != 16) {
              i0 = rcp(quad_sum(z.l0)); i1 = rcp(quad_sum(z.l1));
              soft_start(S, z);
            }
          }
          float s0, s1;
          const int gvo = gv;
          gk = it == 1 ? 12 : gv == 12 ? 4 : gv + 2;
          gv = it == 16 ? gk : gk == 12 ? 4 : gk + 2;
#pragma unroll 1
          for (int pass = 0;; pass++) {
            float e[16];
            s0 = 0.f; s1 = 0.f;
            exp_quarter<0>(S, e, z, s0, s1); pin(s1, sb); wg_wait<3>(); reg_fence_part<0, 8>(P); pack_quarter<0>(e, P);
            exp_quarter<1>(S, e, z, s0, s1); pin(s1, sb); wg_wait<2>(); reg_fence_part<8, 8>(P); pack_quarter<1>(e, P);
            exp_quarter<2>(S, e, z, s0, s1); pin(s1, sb); wg_wait<1>(); reg_fence_part<16, 8>(P); pack_quarter<2>(e, P);
            exp_quarter<3>(S, e, z, s0, s1); pin(s1, sb); wg_wait<0>(); reg_fence_part<24, 8>(P); reg_fence(O);
            c.release(gvo, pass || !it ? 0 : 2, true);
            const bool ok = c.try_full(gk) & c.try_full(gv);
            pack_quarter<3>(e, P);
            FTA(it * 7 + 5);
            if (!__any_sync(0xffffffffu, soft_bad(s0, s1) || !ok || it == nA) || pass) break;
            if (it == nA) {
              uint32_t pk[32];
              pack_frag_scaled(O, pk, i0, i1);
              stsm_frag(pk, stg + 2 * GR);
              c.staged(1);
            }
            mbar_wait(sb + SM_BAR + (B_FULL + gk) * 8, (c.pf >> gk) & 1);
            mbar_wait(sb + SM_BAR + (B_FULL + gv) * 8, (c.pf >> gv) & 1);
            if (!__any_sync(0xffffffffu, soft_bad(s0, s1))) break;
            soft_fix<true>(S, O, z);
          }
          c.pf ^= (1u << gk) | (1u << gv);
          z.l0 += s0; z.l1 += s1;
          FTA(it * 7 + 6);
        }
        FTM(rnd * 8 + 6);
        }
        c.turn_begin();
        wg_fence();
        issue_pv<0>(O, P, dv0 + 12 * DG, 1, true);
        issue_pv<1>(O, P, dv0 + 12 * DG, 1, c.wg);
        c.turn_end();
        z.l0 = rcp(quad_sum(z.l0)); z.l1 = rcp(quad_sum(z.l1));
        wg_wait<0>();
        reg_fence(O); reg_fence(P);
        c.release(12, 2, true);
        pack_frag_scaled(O, P, z.l0, z.l1);
        stsm_frag(P, stg);
        c.staged(0);
        FTM(rnd * 8 + 7);
      }
      TS(3 + rnd * 3);
    }
    conv_tasks(c, p, (cn + 1 - c.wg) / 2, ((cn - 1) & 1) == c.wg, spare, cch + c.wg * cstep, 2 * cstep, dkk, warp & 3, lane);
    if (c.wg == 1) c.pf ^= 0x4;
    TS(7);
    if (!spare) {
      const int rt = 2 * grp + rank, ct = idx;
      float acc[64];
      int g0 = P3G + 2, pg = P3G;
      {
        FTO(0);
        c.wait_full(P3G);
        FTO(1);
        const uint32_t a = dk0 + P3G * DG, b = dm0 + (P3G + 1) * DG;
        wg_fence();
        mma_ss_n128_init<1>(acc, a, b);
#pragma unroll
        for (int k = 1; k < 4; k++) mma_ss_n128<1>(acc, a + k * 2, b + k * 128);
        wg_commit();
      }
#pragma unroll 1
      for (int kb = 1; kb < 64; kb++) {
        FTO(kb * 2);
        c.wait_full(g0);
        FTO(kb * 2 + 1);
        const uint32_t a = dk0 + g0 * DG, b = dm0 + (g0 + 1) * DG;
        wg_fence();
#pragma unroll
        for (int k = 0; k < 4; k++) mma_ss_n128<1>(acc, a + k * 2, b + k * 128);
        wg_commit();
        wg_wait<1>();
        c.release(pg, kb <= 59 ? 2 : 0, true);
        if (kb == 40) FTDUMP();
        pg = g0;
        g0 = g0 == 12 ? (kb == 3 ? 2 : 0) : g0 + 2;
      }
      cluster_arrive();
      c.wait_full(P3X);
      c.wait_full(P3Y);
      const float g0f = __uint_as_float(lds32(sb + SM_GATE + row * 4)), g1f = __uint_as_float(lds32(sb + SM_GATE + row * 4 + 32));
      const uint32_t gp0 = pack_bf16(g0f, g0f), gp1 = pack_bf16(g1f, g1f);
      const float h0 = 1.f - g0f, h1 = 1.f - g1f;
      const int w = warp & 3;
      const uint32_t xa = stg + P3X * GR;
      const uint32_t ya = sb + P3Y * GR + c.wg * 16384 + ((lane >> 4) * 8 + (lane & 7)) * 128 + (((2 * w + ((lane >> 3) & 1)) ^ (lane & 7)) << 4);
      uint32_t xy[32];
#pragma unroll
      for (int jj = 0; jj < 8; jj++) {
        uint32_t x[4], y[4];
        asm volatile("ldmatrix.sync.aligned.m8n8.x4.shared.b16 {%0,%1,%2,%3}, [%4];" : "=r"(x[0]), "=r"(x[1]), "=r"(x[2]), "=r"(x[3]) : "r"((xa ^ ((jj & 3) << 5)) + (jj >> 2) * 16384) : "memory");
        asm volatile("ldmatrix.sync.aligned.m8n8.x4.trans.shared.b16 {%0,%1,%2,%3}, [%4];" : "=r"(y[0]), "=r"(y[1]), "=r"(y[2]), "=r"(y[3]) : "r"(ya + jj * 2048) : "memory");
#pragma unroll
        for (int i = 0; i < 4; i++) xy[4 * jj + i] = hmul2(x[i], y[i]);
      }
      wg_wait<0>();
      reg_fence(acc);
      TS(8);
#pragma unroll
      for (int i = 0; i < 32; i++) {
        const float h = (i & 1) ? h1 : h0;
        xy[i] = hfma2((i & 1) ? gp1 : gp0, xy[i], pack_bf16(acc[2 * i] * h, acc[2 * i + 1] * h));
      }
      stsm_frag(xy, xa);
      fence_async_smem();
      __syncwarp();
      if (lane == 0) {
        const int r0 = c.wg * 64 + w * 16;
        tma2d_store(&p.out, sb + P3X * GR + r0 * 128, ct * 128, rt * 128 + r0);
        tma2d_store(&p.out, sb + (P3X + 1) * GR + r0 * 128, ct * 128 + 64, rt * 128 + r0);
        asm volatile("cp.async.bulk.commit_group;\ncp.async.bulk.wait_group.read 0;" ::: "memory");
      }
    } else { FTDUMP(); cluster_arrive(); }
    if (lane == 0) mbar_arrive(sb + SM_BAR + B_DONE * 8);
    __syncwarp();
    TS(9);
    cluster_wait();
  }
}

typedef CUresult (*EncFn)(CUtensorMap*, CUtensorMapDataType, cuuint32_t, void*, const cuuint64_t*, const cuuint64_t*, const cuuint32_t*,
                          const cuuint32_t*, CUtensorMapInterleave, CUtensorMapSwizzle, CUtensorMapL2promotion, CUtensorMapFloatOOBfill);

void enc2d(EncFn enc, CUtensorMap* tm, const void* base, uint64_t cols, uint64_t rows, uint32_t bc, uint32_t br) {
  cuuint64_t dims[2] = {cols, rows}; cuuint64_t strides[1] = {cols * 2}; cuuint32_t box[2] = {bc, br}; cuuint32_t es[2] = {1, 1};
  enc(tm, CU_TENSOR_MAP_DATA_TYPE_BFLOAT16, 2, const_cast<void*>(base), dims, strides, box, es, CU_TENSOR_MAP_INTERLEAVE_NONE,
      CU_TENSOR_MAP_SWIZZLE_128B, CU_TENSOR_MAP_L2_PROMOTION_L2_256B, CU_TENSOR_MAP_FLOAT_OOB_FILL_NONE);
}
void enc3d(EncFn enc, CUtensorMap* tm, const void* base, uint64_t K, uint64_t N) {
  cuuint64_t dims[3] = {64, K, N / 64}; cuuint64_t strides[2] = {N * 2, 128}; cuuint32_t box[3] = {64, 64, 2}; cuuint32_t es[3] = {1, 1, 1};
  enc(tm, CU_TENSOR_MAP_DATA_TYPE_BFLOAT16, 3, const_cast<void*>(base), dims, strides, box, es, CU_TENSOR_MAP_INTERLEAVE_NONE,
      CU_TENSOR_MAP_SWIZZLE_128B, CU_TENSOR_MAP_L2_PROMOTION_L2_256B, CU_TENSOR_MAP_FLOAT_OOB_FILL_NONE);
}

}

extern "C" void kernel_launch(void* const* d_in, const int* in_sizes, int n_in, void* d_out, int out_size) {
  (void)in_sizes; (void)n_in; (void)out_size;
  typedef const __nv_bfloat16* BP;
  BP xq = (BP)d_in[0], ak = (BP)d_in[1], av = (BP)d_in[2], shk = (BP)d_in[3], ssk = (BP)d_in[4], ssd = (BP)d_in[5];
  BP ckv = (BP)d_in[7], wq = (BP)d_in[8], wuk = (BP)d_in[9], wuv = (BP)d_in[10], wo = (BP)d_in[11], gw = (BP)d_in[12];

  static EncFn enc = nullptr;
  if (!enc) {
    cudaDriverEntryPointQueryResult qr;
    cudaGetDriverEntryPoint("cuTensorMapEncodeTiled", (void**)&enc, cudaEnableDefault, &qr);
    cudaFuncSetAttribute(mega_kernel, cudaFuncAttributeMaxDynamicSharedMemorySize, SMEM_BYTES);
  }
  Params p;
  void* yT = nullptr;
  cudaGetSymbolAddress(&yT, g_yT);
  enc2d(enc, &p.x, xq, DM, SEQ, 64, 128);
  enc2d(enc, &p.c, ckv, DC, SEQ, 64, 128);
  enc3d(enc, &p.wq, wq, DM, NH * HD);
  enc3d(enc, &p.wuk, wuk, DC, NH * HD);
  enc3d(enc, &p.wuv, wuv, DC, NH * HD);
  enc2d(enc, &p.wo, wo, DM, NH * HD, 64, 64);
  enc2d(enc, &p.y, yT, SEQ, DM, 64, 128);
  enc2d(enc, &p.out, d_out, DM, SEQ, 64, 16);
  {
    void* wp = nullptr;
    cudaGetSymbolAddress(&wp, g_w);
    cuuint64_t dims[3] = {WSTRIDE / 2, DM / 2, 2}; cuuint64_t strides[2] = {2 * WSTRIDE, WSTRIDE}; cuuint32_t box[3] = {16, 32, 2}; cuuint32_t es[3] = {1, 1, 1};
    enc(&p.w, CU_TENSOR_MAP_DATA_TYPE_BFLOAT16, 3, wp, dims, strides, box, es, CU_TENSOR_MAP_INTERLEAVE_NONE,
        CU_TENSOR_MAP_SWIZZLE_32B, CU_TENSOR_MAP_L2_PROMOTION_NONE, CU_TENSOR_MAP_FLOAT_OOB_FILL_NONE);
  }
  p.zero = 0;
  p.xp = xq; p.gate_w = gw; p.ak = ak; p.av = av; p.shk = shk; p.ssk = ssk; p.ssd = ssd;

  mega_kernel<<<132, NTHREADS, SMEM_BYTES>>>(p);
}
```

```cpp
#include <cuda_runtime.h>
#include <cuda.h>
#include <cuda_bf16.h>
#include <stdint.h>

namespace {

constexpr int SEQ = 2048, DM = 1024, DC = 512, NH = 32, HD = 128;
constexpr int GR = 16384;
constexpr int NGR = 14;
constexpr int SM_BAR = NGR * GR;
constexpr int SM_GATE = SM_BAR + 512;
constexpr int SM_UST = SM_GATE + 512;
constexpr int SMEM_BYTES = SM_UST + 2048;
constexpr int NTHREADS = 384;
#define SM_LIMIT 1048576.f
constexpr int CN_MAIN = 5, CN_SPARE = 96;
constexpr int P3G = 6, P3X = 10, P3Y = 12;
constexpr int NMAIN = 128;

constexpr int B_FULL = 0, B_EMPTY = 14, B_EV = 28, B_DONE = 34;

__device__ __align__(1024) uint8_t g_kv[2 * 16 * 16 * 32768];
__device__ __align__(1024) uint8_t g_cimg[16 * NH * 32768];
__device__ __align__(1024) __nv_bfloat16 g_yT[DM * SEQ];
__device__ __align__(1024) float g_gate[SEQ];
constexpr int WSTRIDE = 8832, WBYTES = 8736;
__device__ __align__(1024) uint8_t g_w[DM * WSTRIDE];
__device__ unsigned g_flags[128 * 8];
constexpr int F_KV = 0, F_CTX = 16, F_U = 48, F_AD = 56, F_Y = 64, F_GATE = 72, F_EXIT = 73;
#define FLAG(i) (&g_flags[(i) * 8])

#define TS(slot)
#define TSW(slot)
#define FTX(i, off)
#define FTDUMP()

#define ST_OUT 1
#define QFLUSH 4
#define POL_W EV_FIRST
#define POL_WO EV_FIRST
#define POL_KV EV_NORMAL
#define POL_C EV_FIRST
#define POL_CTX EV_FIRST
#define HALFPV 0
#define PWAIT mbar_wait1
#define FINE_MODE 0
#define FINE_RND 1
#define FTA(i) do { if (FINE_MODE == 0) FTX(i, rnd ^ FINE_RND); } while (0)
#define FTG(i) do { if (FINE_MODE == 1) FTX(i, rnd ^ FINE_RND); } while (0)
#define FTM(i) do { if (FINE_MODE == 4) FTX(i, 0); } while (0)
#define FTC(k) do { if (FINE_MODE == 5) FTX((i & 7) * 8 + (k), (i >> 3) ^ FINE_RND); } while (0)
#define FTO(i) do { if (FINE_MODE == 2) FTX(i, 0); } while (0)

__device__ __forceinline__ uint32_t smem_u32(const void* p) { return (uint32_t)__cvta_generic_to_shared(p); }
__device__ __forceinline__ void mbar_init(uint32_t bar, int cnt) { asm volatile("mbarrier.init.shared::cta.b64 [%0], %1;" ::"r"(bar), "r"(cnt) : "memory"); }
__device__ __forceinline__ void mbar_expect_tx(uint32_t bar, uint32_t bytes) { asm volatile("mbarrier.arrive.expect_tx.shared::cta.b64 _, [%0], %1;" ::"r"(bar), "r"(bytes) : "memory"); }
__device__ __forceinline__ void mbar_arrive(uint32_t bar) { asm volatile("mbarrier.arrive.shared::cta.b64 _, [%0];" ::"r"(bar) : "memory"); }
__device__ __forceinline__ void mbar_arrive_cluster(uint32_t bar, uint32_t cta) {
  asm volatile("{\n.reg .b32 r;\nmapa.shared::cluster.u32 r, %0, %1;\nmbarrier.arrive.shared::cluster.b64 _, [r];\n}\n" ::"r"(bar), "r"(cta) : "memory");
}
__device__ __forceinline__ bool mbar_try(uint32_t bar, uint32_t parity) {
  uint32_t ok;
  asm volatile("{\n.reg .pred p;\nmbarrier.try_wait.parity.shared::cta.b64 p, [%1], %2, 20000;\nselp.u32 %0, 1, 0, p;\n}\n" : "=r"(ok) : "r"(bar), "r"(parity) : "memory");
  return ok;
}
__device__ __forceinline__ bool mbar_test(uint32_t bar, uint32_t parity) {
  uint32_t ok;
  asm volatile("{\n.reg .pred p;\nmbarrier.test_wait.parity.shared::cta.b64 p, [%1], %2;\nselp.u32 %0, 1, 0, p;\n}\n" : "=r"(ok) : "r"(bar), "r"(parity) : "memory");
  return ok;
}
__device__ __forceinline__ void mbar_wait(uint32_t bar, uint32_t parity) {
  asm volatile("{\n.reg .pred p;\nWAIT_LOOP:\nbar.warp.sync -1;\nmbarrier.try_wait.parity.shared::cta.b64 p, [%0], %1;\n@!p bra WAIT_LOOP;\n}\n" ::"r"(bar), "r"(parity) : "memory");
}
__device__ __forceinline__ void mbar_wait1(uint32_t bar, uint32_t parity) {
  asm volatile("{\n.reg .pred p;\nWAIT_LOOP:\nbar.warp.sync -1;\nmbarrier.try_wait.parity.shared::cta.b64 p, [%0], %1, 4000;\n@!p bra WAIT_LOOP;\n}\n" ::"r"(bar), "r"(parity) : "memory");
}
constexpr uint64_t EV_NORMAL = 0x1000000000000000ull, EV_FIRST = 0x12F0000000000000ull;
__device__ __forceinline__ uint32_t ldg_stream(const uint32_t* p) {
  uint32_t r; asm volatile("ld.global.nc.L1::no_allocate.L2::cache_hint.b32 %0, [%1], %2;" : "=r"(r) : "l"(p), "l"(EV_FIRST)); return r;
}
__device__ __forceinline__ void tma2d(uint32_t dst, const CUtensorMap* tm, int c0, int c1, uint32_t bar, uint64_t pol) {
  asm volatile("cp.async.bulk.tensor.2d.shared::cluster.global.mbarrier::complete_tx::bytes.L2::cache_hint [%0], [%1, {%3, %4}], [%2], %5;"
               ::"r"(dst), "l"(tm), "r"(bar), "r"(c0), "r"(c1), "l"(pol) : "memory");
}
__device__ __forceinline__ void tma2d_mc(uint32_t dst, const CUtensorMap* tm, int c0, int c1, uint32_t bar, uint64_t pol) {
  asm volatile("cp.async.bulk.tensor.2d.shared::cluster.global.mbarrier::complete_tx::bytes.multicast::cluster.L2::cache_hint [%0], [%1, {%3, %4}], [%2], %5, %6;"
               ::"r"(dst), "l"(tm), "r"(bar), "r"(c0), "r"(c1), "h"((uint16_t)3), "l"(pol) : "memory");
}
__device__ __forceinline__ void tma3d(uint32_t dst, const CUtensorMap* tm, int c0, int c1, int c2, uint32_t bar, uint64_t pol) {
  asm volatile("cp.async.bulk.tensor.3d.shared::cluster.global.mbarrier::complete_tx::bytes.L2::cache_hint [%0], [%1, {%3, %4, %5}], [%2], %6;"
               ::"r"(dst), "l"(tm), "r"(bar), "r"(c0), "r"(c1), "r"(c2), "l"(pol) : "memory");
}
__device__ __forceinline__ void tma3d_mc(uint32_t dst, const CUtensorMap* tm, int c0, int c1, int c2, uint32_t bar, uint64_t pol) {
  asm volatile("cp.async.bulk.tensor.3d.shared::cluster.global.mbarrier::complete_tx::bytes.multicast::cluster.L2::cache_hint [%0], [%1, {%3, %4, %5}], [%2], %6, %7;"
               ::"r"(dst), "l"(tm), "r"(bar), "r"(c0), "r"(c1), "r"(c2), "h"((uint16_t)3), "l"(pol) : "memory");
}
__device__ __forceinline__ void bulk_g2s(uint32_t dst, const void* src, uint32_t bytes, uint32_t bar, uint64_t pol) {
  asm volatile("cp.async.bulk.shared::cluster.global.mbarrier::complete_tx::bytes.L2::cache_hint [%0], [%1], %2, [%3], %4;"
               ::"r"(dst), "l"(src), "r"(bytes), "r"(bar), "l"(pol) : "memory");
}
__device__ __forceinline__ void tma2d_store(const CUtensorMap* tm, uint32_t src, int c0, int c1) {
  asm volatile("cp.async.bulk.tensor.2d.global.shared::cta.bulk_group [%0, {%2, %3}], [%1];" ::"l"(tm), "r"(src), "r"(c0), "r"(c1) : "memory");
}
__device__ __forceinline__ void prefetch_tm(const CUtensorMap* tm) { asm volatile("prefetch.tensormap [%0];" ::"l"(tm) : "memory"); }
__device__ __forceinline__ void wg_fence() { asm volatile("wgmma.fence.sync.aligned;" ::: "memory"); }
__device__ __forceinline__ void wg_commit() { asm volatile("wgmma.commit_group.sync.aligned;" ::: "memory"); }
template <int N> __device__ __forceinline__ void wg_wait() { asm volatile("wgmma.wait_group.sync.aligned %0;" ::"n"(N) : "memory"); }
__device__ __forceinline__ void bar_sync(int id, int n) { asm volatile("bar.sync %0, %1;" ::"r"(id), "r"(n) : "memory"); }
__device__ __forceinline__ void bar_arrive(int id, int n) { asm volatile("bar.arrive %0, %1;" ::"r"(id), "r"(n) : "memory"); }
__device__ __forceinline__ void fence_async_smem() { asm volatile("fence.proxy.async.shared::cta;" ::: "memory"); }
__device__ __forceinline__ void fence_async_all() { asm volatile("fence.proxy.async.global;" ::: "memory"); }
__device__ __forceinline__ uint32_t pack_bf16(float lo, float hi) { uint32_t r; asm("cvt.rn.bf16x2.f32 %0, %1, %2;" : "=r"(r) : "f"(hi), "f"(lo)); return r; }
__device__ __forceinline__ float ex2(float x) { float r; asm("ex2.approx.ftz.f32 %0, %1;" : "=f"(r) : "f"(x)); return r; }
__device__ __forceinline__ float rcp(float x) { float r; asm("rcp.approx.ftz.f32 %0, %1;" : "=f"(r) : "f"(x)); return r; }
__device__ __forceinline__ void flag_wait(const unsigned* f, unsigned target) {
  unsigned v;
  do { asm volatile("ld.acquire.gpu.global.u32 %0, [%1];" : "=r"(v) : "l"(f) : "memory"); } while (__any_sync(0xffffffffu, v < target));
}
__device__ __forceinline__ bool elect() {
  uint32_t r;
  asm volatile("{\n.reg .pred p;\nelect.sync _|p, -1;\nselp.u32 %0, 1, 0, p;\n}\n" : "=r"(r));
  return r;
}
__device__ __forceinline__ void fence_release() { asm volatile("fence.release.gpu;" ::: "memory"); }
__device__ __forceinline__ void flag_add(unsigned* f) { asm volatile("red.relaxed.gpu.global.add.u32 [%0], 1;" ::"l"(f) : "memory"); }
__device__ __forceinline__ void cluster_arrive() { asm volatile("barrier.cluster.arrive.relaxed.aligned;" ::: "memory"); }
__device__ __forceinline__ void cluster_wait() { asm volatile("barrier.cluster.wait.aligned;" ::: "memory"); }
__device__ __forceinline__ uint32_t hmul2(uint32_t a, uint32_t b) { uint32_t r; asm("mul.rn.bf16x2 %0, %1, %2;" : "=r"(r) : "r"(a), "r"(b)); return r; }
__device__ __forceinline__ uint32_t hadd2(uint32_t a, uint32_t b) { uint32_t r; asm("add.rn.bf16x2 %0, %1, %2;" : "=r"(r) : "r"(a), "r"(b)); return r; }
__device__ __forceinline__ uint32_t hfma2(uint32_t a, uint32_t b, uint32_t c) { uint32_t r; asm("fma.rn.bf16x2 %0, %1, %2, %3;" : "=r"(r) : "r"(a), "r"(b), "r"(c)); return r; }
__device__ __forceinline__ uint32_t lds32(uint32_t a) { uint32_t r; asm volatile("ld.shared.b32 %0, [%1];" : "=r"(r) : "r"(a) : "memory"); return r; }
__device__ __forceinline__ uint4 lds128(uint32_t a) { uint4 r; asm volatile("ld.shared.v4.b32 {%0,%1,%2,%3}, [%4];" : "=r"(r.x), "=r"(r.y), "=r"(r.z), "=r"(r.w) : "r"(a) : "memory"); return r; }
__device__ __forceinline__ uint32_t desc_k(uint32_t addr) { return ((addr & 0x3FFFF) >> 4) | (1u << 16); }
template <int LBO> __device__ __forceinline__ uint32_t desc_mn(uint32_t addr) { return ((addr & 0x3FFFF) >> 4) | ((uint32_t)(LBO >> 4) << 16); }
#define DHI "0x40000040"

#define R8(d, o) "+f"(d[o]), "+f"(d[o + 1]), "+f"(d[o + 2]), "+f"(d[o + 3]), "+f"(d[o + 4]), "+f"(d[o + 5]), "+f"(d[o + 6]), "+f"(d[o + 7])
#define R32(d, o) R8(d, o), R8(d, o + 8), R8(d, o + 16), R8(d, o + 24)
#define R64(d, o) R32(d, o), R32(d, o + 32)
#define L64 "%0,%1,%2,%3,%4,%5,%6,%7,%8,%9,%10,%11,%12,%13,%14,%15,%16,%17,%18,%19,%20,%21,%22,%23,%24,%25,%26,%27,%28,%29,%30,%31," \
            "%32,%33,%34,%35,%36,%37,%38,%39,%40,%41,%42,%43,%44,%45,%46,%47,%48,%49,%50,%51,%52,%53,%54,%55,%56,%57,%58,%59,%60,%61,%62,%63"
#define L128 L64 ",%64,%65,%66,%67,%68,%69,%70,%71,%72,%73,%74,%75,%76,%77,%78,%79,%80,%81,%82,%83,%84,%85,%86,%87,%88,%89,%90,%91,%92,%93,%94,%95," \
            "%96,%97,%98,%99,%100,%101,%102,%103,%104,%105,%106,%107,%108,%109,%110,%111,%112,%113,%114,%115,%116,%117,%118,%119,%120,%121,%122,%123,%124,%125,%126,%127"

template <int TB> __device__ __forceinline__ void mma_ss_n128(float (&d)[64], uint32_t da, uint32_t db) {
  asm volatile("{\n.reg .b64 da, db;\nmov.b64 da, {%64, " DHI "};\nmov.b64 db, {%65, " DHI "};\n"
               "wgmma.mma_async.sync.aligned.m64n128k16.f32.bf16.bf16 {" L64 "}, da, db, 1, 1, 1, 0, %66;\n}\n"
               : R64(d, 0) : "r"(da), "r"(db), "n"(TB));
}
template <int TB> __device__ __forceinline__ void mma_rs_n128(float (&d)[64], uint32_t a0, uint32_t a1, uint32_t a2, uint32_t a3, uint32_t db, int sd) {
  asm volatile("{\n.reg .pred p;\n.reg .b64 db;\nsetp.ne.b32 p, %69, 0;\nmov.b64 db, {%68, " DHI "};\n"
               "wgmma.mma_async.sync.aligned.m64n128k16.f32.bf16.bf16 {" L64 "}, {%64,%65,%66,%67}, db, p, 1, 1, %70;\n}\n"
               : R64(d, 0) : "r"(a0), "r"(a1), "r"(a2), "r"(a3), "r"(db), "r"(sd), "n"(TB));
}
template <int TB> __device__ __forceinline__ void mma_ss_n256(float (&d)[128], uint32_t da, uint32_t db) {
  asm volatile("{\n.reg .b64 da, db;\nmov.b64 da, {%128, " DHI "};\nmov.b64 db, {%129, " DHI "};\n"
               "wgmma.mma_async.sync.aligned.m64n256k16.f32.bf16.bf16 {" L128 "}, da, db, 1, 1, 1, 0, %130;\n}\n"
               : R64(d, 0), R64(d, 64) : "r"(da), "r"(db), "n"(TB));
}
#define W8(d, o) "=f"(d[o]), "=f"(d[o + 1]), "=f"(d[o + 2]), "=f"(d[o + 3]), "=f"(d[o + 4]), "=f"(d[o + 5]), "=f"(d[o + 6]), "=f"(d[o + 7])
#define W32(d, o) W8(d, o), W8(d, o + 8), W8(d, o + 16), W8(d, o + 24)
#define W64(d, o) W32(d, o), W32(d, o + 32)
template <int TB> __device__ __forceinline__ void mma_ss_n128_init(float (&d)[64], uint32_t da, uint32_t db) {
  asm volatile("{\n.reg .b64 da, db;\nmov.b64 da, {%64, " DHI "};\nmov.b64 db, {%65, " DHI "};\n"
               "wgmma.mma_async.sync.aligned.m64n128k16.f32.bf16.bf16 {" L64 "}, da, db, 0, 1, 1, 0, %66;\n}\n"
               : W64(d, 0) : "r"(da), "r"(db), "n"(TB));
}
template <int TB> __device__ __forceinline__ void mma_ss_n256_init(float (&d)[128], uint32_t da, uint32_t db) {
  asm volatile("{\n.reg .b64 da, db;\nmov.b64 da, {%128, " DHI "};\nmov.b64 db, {%129, " DHI "};\n"
               "wgmma.mma_async.sync.aligned.m64n256k16.f32.bf16.bf16 {" L128 "}, da, db, 0, 1, 1, 0, %130;\n}\n"
               : W64(d, 0), W64(d, 64) : "r"(da), "r"(db), "n"(TB));
}
#define L32 "%0,%1,%2,%3,%4,%5,%6,%7,%8,%9,%10,%11,%12,%13,%14,%15,%16,%17,%18,%19,%20,%21,%22,%23,%24,%25,%26,%27,%28,%29,%30,%31"
__device__ __forceinline__ void mma_ss_n64(float (&d)[32], uint32_t da, uint32_t db) {
  asm volatile("{\n.reg .b64 da, db;\nmov.b64 da, {%32, " DHI "};\nmov.b64 db, {%33, " DHI "};\n"
               "wgmma.mma_async.sync.aligned.m64n64k16.f32.bf16.bf16 {" L32 "}, da, db, 1, 1, 1, 0, 0;\n}\n"
               : R32(d, 0) : "r"(da), "r"(db));
}
__device__ __forceinline__ void mma_ss_n64_init(float (&d)[32], uint32_t da, uint32_t db) {
  asm volatile("{\n.reg .b64 da, db;\nmov.b64 da, {%32, " DHI "};\nmov.b64 db, {%33, " DHI "};\n"
               "wgmma.mma_async.sync.aligned.m64n64k16.f32.bf16.bf16 {" L32 "}, da, db, 0, 1, 1, 0, 0;\n}\n"
               : W32(d, 0) : "r"(da), "r"(db));
}
#define L16 "%0,%1,%2,%3,%4,%5,%6,%7,%8,%9,%10,%11,%12,%13,%14,%15"
__device__ __forceinline__ void mma_rs_n32(float (&d)[16], uint32_t a0, uint32_t a1, uint32_t a2, uint32_t a3, uint32_t db) {
  asm volatile("{\n.reg .b64 db;\nmov.b64 db, {%20, 0x00000008};\n"
               "wgmma.mma_async.sync.aligned.m64n32k16.f32.bf16.bf16 {" L16 "}, {%16,%17,%18,%19}, db, 1, 1, 1, 0;\n}\n"
               : R8(d, 0), R8(d, 8) : "r"(a0), "r"(a1), "r"(a2), "r"(a3), "r"(db));
}
__device__ __forceinline__ void mma_rs_n32_init(float (&d)[16], uint32_t a0, uint32_t a1, uint32_t a2, uint32_t a3, uint32_t db) {
  asm volatile("{\n.reg .b64 db;\nmov.b64 db, {%20, 0x00000008};\n"
               "wgmma.mma_async.sync.aligned.m64n32k16.f32.bf16.bf16 {" L16 "}, {%16,%17,%18,%19}, db, 0, 1, 1, 0;\n}\n"
               : W8(d, 0), W8(d, 8) : "r"(a0), "r"(a1), "r"(a2), "r"(a3), "r"(db));
}
__device__ __forceinline__ void mma_ss_n8(float (&d)[4], uint32_t da, uint32_t db) {
  asm volatile("{\n.reg .b64 da, db;\nmov.b64 da, {%4, " DHI "};\nmov.b64 db, {%5, 0x00000008};\n"
               "wgmma.mma_async.sync.aligned.m64n8k16.f32.bf16.bf16 {%0,%1,%2,%3}, da, db, 1, 1, 1, 0, 0;\n}\n"
               : "+f"(d[0]), "+f"(d[1]), "+f"(d[2]), "+f"(d[3]) : "r"(da), "r"(db));
}
template <int N> __device__ __forceinline__ void reg_fence(float (&d)[N]) {
#pragma unroll
  for (int i = 0; i < N; i++) asm volatile("" : "+f"(d[i])::"memory");
}
template <int N> __device__ __forceinline__ void reg_fence(uint32_t (&d)[N]) {
#pragma unroll
  for (int i = 0; i < N; i++) asm volatile("" : "+r"(d[i])::"memory");
}

struct __align__(64) Params {
  CUtensorMap x, c, wq, wuk, wuv, wo, y, out, w;
  const __nv_bfloat16* xp;
  const __nv_bfloat16* gate_w;
  const __nv_bfloat16 *ak, *av, *shk, *ssk, *ssd;
  int zero;
};

template <int O, int N, int M> __device__ __forceinline__ void pack_frag(const float (&acc)[N], uint32_t (&pk)[M]) {
#pragma unroll
  for (int i = 0; i < 32; i++) pk[i] = pack_bf16(acc[O + 2 * i], acc[O + 2 * i + 1]);
}
__device__ __forceinline__ void pack_frag_scaled(const float (&acc)[64], uint32_t (&pk)[32], float s0, float s1) {
#pragma unroll
  for (int i = 0; i < 32; i++) { const float s = (i & 1) ? s1 : s0; pk[i] = pack_bf16(acc[2 * i] * s, acc[2 * i + 1] * s); }
}
template <int J0 = 0, int J1 = 8, int M> __device__ __forceinline__ void stsm_frag(const uint32_t (&pk)[M], uint32_t a) {
#pragma unroll
  for (int jj = J0; jj < J1; jj++)
    asm volatile("stmatrix.sync.aligned.m8n8.x4.shared.b16 [%0], {%1,%2,%3,%4};" ::"r"((a ^ ((jj & 3) << 5)) + (jj >> 2) * 16384),
                 "r"(pk[4 * jj]), "r"(pk[4 * jj + 1]), "r"(pk[4 * jj + 2]), "r"(pk[4 * jj + 3]) : "memory");
}

struct Cons {
  uint32_t sb;
  uint32_t pf;
  int wg, tid;
  __device__ __forceinline__ void wait_full(int g) { mbar_wait(sb + SM_BAR + (B_FULL + g) * 8, (pf >> g) & 1); pf ^= 1u << g; }
  uint32_t relb;
  __device__ __forceinline__ void release(int g, int n) {
    if (tid < 2 * n) asm volatile("mbarrier.arrive.shared::cluster.b64 _, [%0];" ::"r"(relb + g * 8) : "memory");
  }
  __device__ __forceinline__ void turn_begin() { bar_sync(1 + wg, 256); }
  __device__ __forceinline__ void turn_end() { bar_arrive(2 - wg, 256); }
  __device__ __forceinline__ void staged(int e) { __syncwarp(); if ((tid & 31) == 0) mbar_arrive(sb + SM_BAR + (B_EV + 2 * e + wg) * 8); }
  int zero;
  uint32_t pfree;
  __device__ __forceinline__ void wait_stage_free() { mbar_wait(sb + SM_BAR + (B_EV + 4 + wg) * 8, pfree); pfree ^= 1; }
  __device__ __forceinline__ bool try_full(int g) { return mbar_test(sb + SM_BAR + (B_FULL + g) * 8, (pf >> g) & 1); }
};

constexpr float SM_C = 0.08838834764831845f * 1.4426950408889634f;
struct SoftState { float m0, m1, n0, n1, l0, l1; };
template <int Q, int N> __device__ __forceinline__ void exp_quarter(const float (&S)[N], float (&e)[16], const SoftState& z, float& s0, float& s1) {
#pragma unroll
  for (int i = 0; i < 16; i++) e[i] = ex2(fmaf(S[16 * Q + i], SM_C, (i & 2) ? z.n1 : z.n0));
#pragma unroll
  for (int i = 0; i < 16; i += 4) { s0 += e[i]; s1 += e[i + 2]; s0 += e[i + 1]; s1 += e[i + 3]; }
}
template <int Q> __device__ __forceinline__ void pack_quarter(const float (&e)[16], uint32_t (&P)[32]) {
#pragma unroll
  for (int i = 0; i < 8; i++) P[8 * Q + i] = pack_bf16(e[2 * i], e[2 * i + 1]);
}
template <int NV, int N> __device__ __forceinline__ void update_max(const float (&S)[N], SoftState& z, float& sc0, float& sc1) {
  float a0 = fmaxf(S[0], S[1]), a1 = fmaxf(S[2], S[3]), b0 = fmaxf(S[4], S[5]), b1 = fmaxf(S[6], S[7]);
#pragma unroll
  for (int j = 2; j < NV / 4; j += 2) {
    a0 = fmaxf(a0, fmaxf(S[4 * j], S[4 * j + 1]));
    a1 = fmaxf(a1, fmaxf(S[4 * j + 2], S[4 * j + 3]));
    b0 = fmaxf(b0, fmaxf(S[4 * j + 4], S[4 * j + 5]));
    b1 = fmaxf(b1, fmaxf(S[4 * j + 6], S[4 * j + 7]));
  }
  a0 = fmaxf(a0, b0); a1 = fmaxf(a1, b1);
  a0 = fmaxf(a0, __shfl_xor_sync(0xffffffffu, a0, 1)); a1 = fmaxf(a1, __shfl_xor_sync(0xffffffffu, a1, 1));
  a0 = fmaxf(a0, __shfl_xor_sync(0xffffffffu, a0, 2)); a1 = fmaxf(a1, __shfl_xor_sync(0xffffffffu, a1, 2));
  a0 = fmaxf(a0, z.m0); a1 = fmaxf(a1, z.m1);
  sc0 = ex2((z.m0 - a0) * SM_C); sc1 = ex2((z.m1 - a1) * SM_C);
  z.m0 = a0; z.m1 = a1;
  z.n0 = -a0 * SM_C; z.n1 = -a1 * SM_C;
}
template <int N> __device__ __forceinline__ void soft_start(const float (&S)[N], SoftState& z) {
  z.m0 = z.m1 = -INFINITY; z.l0 = z.l1 = 0.f;
  float sc0, sc1;
  update_max<8>(S, z, sc0, sc1);
}
template <int N> __device__ __forceinline__ void exp_all(const float (&S)[N], uint32_t (&P)[32], const SoftState& z, float& s0, float& s1) {
  float e[16];
  exp_quarter<0>(S, e, z, s0, s1); pack_quarter<0>(e, P);
  exp_quarter<1>(S, e, z, s0, s1); pack_quarter<1>(e, P);
  if (N == 64) {
    exp_quarter<N == 64 ? 2 : 0>(S, e, z, s0, s1); pack_quarter<2>(e, P);
    exp_quarter<N == 64 ? 3 : 0>(S, e, z, s0, s1); pack_quarter<3>(e, P);
  }
}
template <bool HAS_O, int N> __device__ __forceinline__ void soft_fix(const float (&S)[N], float (&O)[64], SoftState& z) {
  float sc0, sc1;
  update_max<N>(S, z, sc0, sc1);
  if (HAS_O) {
    z.l0 *= sc0; z.l1 *= sc1;
#pragma unroll
    for (int j = 0; j < 16; j++) { O[4 * j] *= sc0; O[4 * j + 1] *= sc0; O[4 * j + 2] *= sc1; O[4 * j + 3] *= sc1; }
  }
}
__device__ __forceinline__ bool soft_bad(float s0, float s1) { return s0 + s1 > SM_LIMIT; }
__device__ __forceinline__ void pin(float a, uint32_t never_zero) {
  asm volatile("{\n.reg .pred p;\nsetp.eq.u32 p, %1, 0;\n@p st.shared.f32 [%1], %0;\n}\n" ::"f"(a), "r"(never_zero) : "memory");
}
template <int M> __device__ __forceinline__ void pin32(const uint32_t (&v)[M], uint32_t never_zero) {
#pragma unroll
  for (int i = 0; i < 32; i += 4)
    asm volatile("{\n.reg .pred p;\nsetp.eq.u32 p, %4, 0;\n@p st.shared.v4.b32 [%4], {%0,%1,%2,%3};\n}\n" ::"r"(v[i]), "r"(v[i + 1]), "r"(v[i + 2]), "r"(v[i + 3]), "r"(never_zero) : "memory");
}
template <int O, int N> __device__ __forceinline__ void reg_fence_part(uint32_t (&d)[32]) {
#pragma unroll
  for (int i = O; i < O + N; i++) asm volatile("" : "+r"(d[i])::"memory");
}
template <int N> __device__ __forceinline__ void mask_diag(float (&S)[N], int d) {
#pragma unroll
  for (int j = 0; j < 8; j++) {
    if (8 * j > d) S[N - 32 + 4 * j] = -INFINITY;
    if (8 * j + 1 > d) S[N - 32 + 4 * j + 1] = -INFINITY;
    if (8 * j > d + 8) S[N - 32 + 4 * j + 2] = -INFINITY;
    if (8 * j + 1 > d + 8) S[N - 32 + 4 * j + 3] = -INFINITY;
  }
}
__device__ __forceinline__ float quad_sum(float v) {
  v += __shfl_xor_sync(0xffffffffu, v, 1);
  v += __shfl_xor_sync(0xffffffffu, v, 2);
  return v;
}
__device__ __forceinline__ void issue_qk(float (&S)[64], uint32_t dq, uint32_t dk) {
  mma_ss_n128_init<0>(S, dq, dk);
#pragma unroll
  for (int s = 1; s < 8; s++) mma_ss_n128<0>(S, dq + (s >> 2) * 1024 + (s & 3) * 2, dk + (s >> 2) * 1024 + (s & 3) * 2);
}
__device__ __forceinline__ void issue_qk(float (&S)[32], uint32_t dq, uint32_t dk) {
  mma_ss_n64_init(S, dq, dk);
#pragma unroll
  for (int s = 1; s < 8; s++) mma_ss_n64(S, dq + (s >> 2) * 1024 + (s & 3) * 2, dk + (s >> 2) * 1024 + (s & 3) * 2);
}
template <int H> __device__ __forceinline__ void issue_pv(float (&O)[64], const uint32_t (&P)[32], uint32_t dv, int acc, bool on) {
  if (on) {
#pragma unroll
    for (int s = 4 * H; s < 4 * H + 4; s++) {
      mma_rs_n128<1>(O, P[4 * s], P[4 * s + 1], P[4 * s + 2], P[4 * s + 3], dv + s * 128, s != 0 ? 1 : acc);
      if (s & 1) wg_commit();
    }
  } else { wg_commit(); wg_commit(); }
}
constexpr uint32_t DG = GR >> 4;
__device__ __forceinline__ void stage_q2(Cons& c, const float (&O)[64], uint32_t (&P)[32], uint32_t stg) {
  wg_commit(); wg_commit(); wg_commit(); wg_commit();
  c.turn_end();
  pack_frag<0>(O, P);
  stsm_frag(P, stg);
  fence_async_smem();
#pragma unroll
  for (int i = 16; i < 32; i++) P[i] = 0;
}
__device__ __forceinline__ void attn_half(Cons& c, float (&O)[64], uint32_t (&P)[32], SoftState& z, uint32_t dk0, uint32_t dkk, uint32_t dv0, int dmask, int last, uint32_t stg) {
  float S[32];
  c.turn_begin();
  wg_fence();
  issue_qk(S, dk0 + (last ? 0 : 2 * DG), dkk + (last ? 8 : 4) * DG);
  wg_commit();
  if (last) {
    issue_pv<0>(O, P, dv0 + 10 * DG, 1, true);
    issue_pv<1>(O, P, dv0 + 10 * DG, 1, true);
    c.turn_end();
  } else stage_q2(c, O, P, stg);
  wg_wait<4>();
  reg_fence(S);
  c.release(last ? 8 : 4, 2);
  mask_diag(S, dmask);
  if (!last) soft_start(S, z);
  float s0, s1;
#pragma unroll 1
  for (;;) {
    float e[16];
    s0 = 0.f; s1 = 0.f;
    exp_quarter<0>(S, e, z, s0, s1); pin(s1, c.sb); wg_wait<3>(); reg_fence_part<0, 8>(P); pack_quarter<0>(e, P);
    exp_quarter<1>(S, e, z, s0, s1); pin(s1, c.sb); wg_wait<0>(); reg_fence_part<8, 24>(P); reg_fence(O); pack_quarter<1>(e, P);
    if (!__any_sync(0xffffffffu, soft_bad(s0, s1))) break;
    soft_fix<true>(S, O, z);
  }
  z.l0 += s0; z.l1 += s1;
  c.release(10, last ? 2 : 0);
  c.wait_full(last ? 12 : 6);
  if (!last) c.wait_full(8);
}

__device__ __forceinline__ int conv_next(int g, bool spare) { return spare ? (g >= NGR - 2 ? g - (NGR - 4) : g + 2) : g ^ 6; }
__device__ __forceinline__ void conv_final(uint32_t rb, uint32_t yb, const uint4& u, uint32_t dd, bool on) {
  const uint4 q0 = lds128(rb), q1 = lds128(rb + 4096), q2 = lds128(rb + 8192), q3 = lds128(rb + 12288);
  auto fin = [&](uint32_t x0, uint32_t x1, uint32_t x2, uint32_t x3, uint32_t uu) {
    return hfma2(dd, __byte_perm(uu, uu, 0x1032), hadd2(hadd2(x0, x1), hadd2(x2, x3)));
  };
  asm volatile("{\n.reg .pred p;\nsetp.ne.b32 p, %5, 0;\n@p st.shared.v4.b32 [%0], {%1,%2,%3,%4};\n}\n" ::"r"(yb), "r"(fin(q0.x, q1.x, q2.x, q3.x, u.w)),
               "r"(fin(q0.y, q1.y, q2.y, q3.y, u.z)), "r"(fin(q0.z, q1.z, q2.z, q3.z, u.y)), "r"(fin(q0.w, q1.w, q2.w, q3.w, u.x)), "r"((int)on) : "memory");
}
__device__ __forceinline__ void conv_tasks(Cons& c, const Params& p, int ntask, bool last, bool spare, int ch, int chstep, uint32_t dkk, int w, int lane) {
  const uint32_t sb = c.sb;
  int g = 4 + c.wg;
  uint4 u0 = make_uint4(0, 0, 0, 0), u1 = u0;
  uint32_t dd = 0, rb = sb + g * GR;
  const uint32_t yb = sb + c.wg * 8192 + c.tid * 16;
  c.wait_full(g);
#pragma unroll 1
  for (int i = 0; i < ntask; i++) {
    const uint32_t base = sb + g * GR;
    FTC(0);
    uint32_t a[64];
    const uint32_t hb = base + WBYTES - 28 + (8 * w + (lane >> 2) + (lane & 3)) * 4;
    auto lda = [&](int s) {
      a[4 * s] = lds32(hb + s * 256); a[4 * s + 1] = lds32(hb + s * 256 + 128);
      a[4 * s + 2] = lds32(hb + s * 256 + 16); a[4 * s + 3] = lds32(hb + s * 256 + 144);
    };
    lda(0); lda(15); lda(1); lda(14);
    float acc[8][16];
    const uint32_t db = dkk + ((4352 / 16 - 1) << 16) + g * DG + 16;
    FTC(2);
    c.turn_begin();
    FTC(3);
#pragma unroll
    for (int k = 0; k < 8; k++) {
      if (k < 7) wg_fence();
      if (k == 7 && !(last && i == ntask - 1)) c.turn_end();
#pragma unroll
      for (int J = 7; J >= (k >> 1); J--) {
        if (k == 0) mma_rs_n32_init(acc[J], a[0], a[1], a[2], a[3], db + J * 32);
        else mma_rs_n32(acc[J], a[4 * k], a[4 * k + 1], a[4 * k + 2], a[4 * k + 3], db + (2 * J - k) * 16);
      }
      const int s = 15 - k;
#pragma unroll
      for (int J = 7; J >= (s >> 1); J--) mma_rs_n32(acc[J], a[4 * s], a[4 * s + 1], a[4 * s + 2], a[4 * s + 3], db + (2 * J - s) * 16);
      if (k < 6) { lda(k + 2); lda(13 - k); }
      if (k == 0) conv_final(rb, yb, u0, dd, i > 0);
      if (k == 1) {
        conv_final(rb + 2048, yb + 2048, u1, dd, i > 0);
        __syncwarp();
        if (lane == 0 && i > 0) mbar_arrive(sb + SM_BAR + (B_EV + c.wg) * 8);
      }
      if (k == 6) {
        const uint32_t ub = base + 256 + 16 + (c.tid >> 1) * 32 + ((c.tid & 1) ^ 1) * 4352;
        u0 = lds128(ub); u1 = lds128(ub + 2048);
        dd = __bfloat16_as_ushort(p.ssd[ch]) * 0x10001u;
      }
    }
    wg_commit();
    FTC(4);
    g = conv_next(g, spare);
    ch += chstep;
    rb = base + c.tid * 16;
    if (i + 1 < ntask) c.wait_full(g);
    wg_wait<0>();
#pragma unroll
    for (int J = 0; J < 8; J++) reg_fence(acc[J]);
    reg_fence(a);
    bar_sync(3 + c.wg, 128);
    FTC(5);
    const int tw = (lane & 3) + w;
    const uint32_t xb = base + w * 4096 + tw * 32 + (lane >> 2) * 4;
#pragma unroll
    for (int j = 0; j < 32; j++) {
      float v0 = acc[j >> 2][(j & 3) * 4], v1 = acc[j >> 2][(j & 3) * 4 + 1];
      if (j > 0) { v0 += acc[(j - 1) >> 2][((j - 1) & 3) * 4 + 2]; v1 += acc[(j - 1) >> 2][((j - 1) & 3) * 4 + 3]; }
      uint32_t v = pack_bf16(v0, v1), ad = xb + j * 128;
      if (j == 31 && tw >= 4) { v = 0; ad -= 4096; }
      asm volatile("st.shared.b32 [%0], %1;" ::"r"(ad), "r"(v) : "memory");
    }
    c.wait_stage_free();
    bar_sync(3 + c.wg, 128);
    FTC(6);
  }
  conv_final(rb, yb, u0, dd, true);
  conv_final(rb + 2048, yb + 2048, u1, dd, true);
  c.staged(0);
}

__global__ void __cluster_dims__(2, 1, 1) __launch_bounds__(NTHREADS, 1) mega_kernel(const __grid_constant__ Params p) {
  extern __shared__ __align__(1024) uint8_t smem_raw[];
  const uint32_t sb = smem_u32(smem_raw);
  const int wgi = __shfl_sync(0xffffffffu, threadIdx.x >> 7, 0);
  const int warp = __shfl_sync(0xffffffffu, threadIdx.x >> 5, 0);
  const uint32_t rank = blockIdx.x & 1;
  int grp, idx;
  {
    uint32_t smid; asm volatile("mov.u32 %0, %smid;" : "=r"(smid));
    const int tp = smid >> 1;
    if (tp < 32) { grp = tp & 7; idx = tp >> 3; }
    else if (tp < 60) { grp = 1 + (tp - 32) % 7; idx = 4 + (tp - 32) / 7; }
    else if (tp < 62) { grp = 8; idx = tp - 60; }
    else { grp = 0; idx = tp - 58; }
  }
  const int lb = (grp * 8 + idx) * 2 + rank;
  const bool spare = grp == 8;
  const int cn = spare ? CN_SPARE : CN_MAIN, cch = spare ? lb - NMAIN : 4 * CN_SPARE + CN_MAIN * lb, cstep = spare ? 4 : 1;

  if (threadIdx.x == 0) {
    prefetch_tm(&p.c); prefetch_tm(rank ? &p.wuv : &p.wuk);
#pragma unroll 1
    for (int i = 0; i < 2 * NGR + 6; i++) mbar_init(sb + SM_BAR + i * 8, i < NGR || i >= 2 * NGR + 4 ? 1 : 4);
    mbar_init(sb + SM_BAR + B_DONE * 8, 11);
    asm volatile("fence.mbarrier_init.release.cluster;" ::: "memory");
  }
  cluster_arrive();
  cluster_wait();
  TS(0);

  if (wgi == 0) {
    asm volatile("setmaxnreg.dec.sync.aligned.u32 40;");
    const int lane = threadIdx.x & 31;
    cluster_arrive();
    if (warp == 3) {
      if (!spare) {
        const int s0 = lb * 16;
#pragma unroll 1
        for (int cg = 0; cg < 16; cg++) {
          const int ch = cg * 64 + 2 * lane;
          const uint32_t* kp = reinterpret_cast<const uint32_t*>(p.ak + (size_t)s0 * DM + ch);
          const uint32_t* vp = reinterpret_cast<const uint32_t*>(p.av + (size_t)s0 * DM + ch);
          const uint4 sw = __ldg(reinterpret_cast<const uint4*>(p.shk + ch * 4));
          uint32_t k3 = 0, k2 = 0, k1 = 0, k0 = 0, up = 0;
          if (lb > 0) { k3 = ldg_stream(kp - 4 * 512); k2 = ldg_stream(kp - 3 * 512); k1 = ldg_stream(kp - 2 * 512); k0 = ldg_stream(kp - 512); up = ldg_stream(vp - 512); }
          const uint32_t w0 = __byte_perm(sw.x, sw.z, 0x5410), w1 = __byte_perm(sw.x, sw.z, 0x7632);
          const uint32_t w2 = __byte_perm(sw.y, sw.w, 0x5410), w3 = __byte_perm(sw.y, sw.w, 0x7632);
          up = hmul2(hfma2(k0, w0, hfma2(k1, w1, hfma2(k2, w2, hmul2(k3, w3)))), up);
#pragma unroll 1
          for (int hb = 0; hb < 2; hb++) {
            uint32_t kk[8], u[8];
#pragma unroll
            for (int r = 0; r < 8; r++) { kk[r] = ldg_stream(kp + r * 512); u[r] = ldg_stream(vp + r * 512); }
#pragma unroll
            for (int r = 0; r < 8; r++) {
              k3 = k2; k2 = k1; k1 = k0; k0 = kk[r];
              u[r] = hmul2(hfma2(k0, w0, hfma2(k1, w1, hfma2(k2, w2, hmul2(k3, w3)))), u[r]);
            }
            if (lane == 0) asm volatile("cp.async.bulk.wait_group.read 0;" ::: "memory");
            __syncwarp();
            const uint32_t dst = sb + SM_UST + lane * 32 + ((lane & 4) << 2);
#pragma unroll
            for (int cc = 0; cc < 2; cc++) {
              const uint32_t sel = cc ? 0x7632 : 0x5410;
              asm volatile("st.shared.v4.b32 [%0], {%1,%2,%3,%4};" ::"r"(dst + cc * 1024), "r"(__byte_perm(u[6], u[5], sel)), "r"(__byte_perm(u[4], u[3], sel)),
                           "r"(__byte_perm(u[2], u[1], sel)), "r"(__byte_perm(u[0], up, sel)) : "memory");
              asm volatile("st.shared.v4.b32 [%0], {%1,%2,%3,%4};" ::"r"((dst ^ 16) + cc * 1024), "r"(__byte_perm(u[7], u[6], sel)), "r"(__byte_perm(u[5], u[4], sel)),
                           "r"(__byte_perm(u[3], u[2], sel)), "r"(__byte_perm(u[1], u[0], sel)) : "memory");
            }
            fence_async_smem();
            __syncwarp();
            if (lane == 0) {
              asm volatile("cp.async.bulk.tensor.3d.global.shared::cta.bulk_group [%0, {%2, %3, %4}], [%1];\ncp.async.bulk.commit_group;"
                           ::"l"(&p.w), "r"(sb + SM_UST), "r"(128 + lb * 16 + (hb ^ 1) * 2176), "r"(cg * 32), "r"(0) : "memory");
            }
            up = u[7];
            kp += 8 * 512; vp += 8 * 512;
          }
          if ((cg & (cg + 1)) == 0 && lane == 0) {
            asm volatile("cp.async.bulk.wait_group 0;" ::: "memory");
            fence_release();
            flag_add(FLAG(F_U + 32 - __clz(cg)));
          }
          TSW(10 + cg);
        }
      }
      if (lane == 0) {
        unsigned long long t0, t1;
        asm volatile("mov.u64 %0, %globaltimer;" : "=l"(t0));
        while (!mbar_try(sb + SM_BAR + B_DONE * 8, 0)) {
          asm volatile("mov.u64 %0, %globaltimer;" : "=l"(t1));
          if (t1 - t0 > 2000000000ull) __trap();
        }
      }
    } else if (warp != 0) {
      const int w = warp - 1, ne = 12 + (cn + 1 - w) / 2;
      uint32_t p0 = 0;
      int cg = 4 + w, ch = cch + w * cstep;
#pragma unroll 1
      for (int e = spare ? 12 : 0; e < ne; e++) {
        const int rnd = e >= 6, k = e - 6 * rnd, rt = k == 4 ? idx : 15 - idx;
        uint8_t* dst = k < 4 ? g_kv + (size_t)(((k & 1) * 16 + 2 * grp + (k >> 1)) * 16 + 2 * idx + rank) * 32768 + w * 8192
                     : k < 6 ? g_cimg + (size_t)(rt * 32 + 16 * rnd + 2 * grp + rank) * 32768 + w * 8192
                             : reinterpret_cast<uint8_t*>(g_yT + (size_t)ch * SEQ);
        const uint32_t src = sb + w * 8192 + (k == 4 ? 2 * GR : 0);
        if (e == 6) flag_wait(FLAG(F_AD + grp), 32);
        mbar_wait1(sb + SM_BAR + (B_EV + (k == 4 ? 2 : 0) + w) * 8, k == 4 ? rnd : p0);
        if (k != 4) p0 ^= 1;
        if (lane < 4 && k >= 6 && (!spare || e < ne - 6)) mbar_arrive_cluster(sb + SM_BAR + (B_EMPTY + cg) * 8, lane & 1);
        fence_async_smem();
        if (elect()) {
#pragma unroll 1
          for (int i = 0; i < (k >= 6 ? 1 : 8); i++) {
            const uint32_t o = (i >> 2) * 16384 + (i & 3) * 2048;
            asm volatile("cp.async.bulk.global.shared::cta.bulk_group [%0], [%1], %2;" ::"l"(dst + o), "r"(src + o), "r"(k >= 6 ? 4096 : 2048) : "memory");
            asm volatile("cp.async.bulk.commit_group;\ncp.async.bulk.wait_group.read %0;" ::"n"(ST_OUT) : "memory");
          }
          asm volatile("cp.async.bulk.wait_group 0;" ::: "memory");
          if (k != 4) mbar_arrive(sb + SM_BAR + (B_EV + 4 + w) * 8);
        }
        __syncwarp();
        if (lane < 4 && (k == 4 || (e == ne - 1 && !spare)))
          mbar_arrive_cluster(sb + SM_BAR + (B_EMPTY + (k == 4 ? 2 : 0) + (lane >> 1)) * 8, lane & 1);
        if (k >= 3) {
          fence_release();
          if (lane == 0 || (lane == 1 && e == 5))
            flag_add(FLAG(lane ? F_AD + grp : k == 3 ? F_KV + rnd * 8 + grp : k < 6 ? F_CTX + rt * 2 + rnd : F_Y + (ch >> 7)));
        }
        if (k >= 6) { cg = conv_next(cg, spare); ch += 2 * cstep; }
      }
      if (lane == 0) mbar_arrive(sb + SM_BAR + B_DONE * 8);
    } else {
      uint32_t pe = 0x3FFC;
      auto acquire = [&](int g) { PWAIT(sb + SM_BAR + (B_EMPTY + g) * 8, (pe >> g) & 1); pe ^= 1u << g; };
#pragma unroll 1
      for (int rnd = 0; rnd < (spare ? 0 : 2); rnd++) {
        const int hp = 16 * rnd + 2 * grp, head = hp + rank;
#pragma unroll 1
        for (int kk = 0; kk < 32; kk++) {
          const int g0 = 2 + 3 * (kk & 3);
          acquire(g0);
          if (kk < 4) { acquire(g0 + 1); acquire(g0 + 2); } else pe ^= 6u << g0;
          if (elect()) {
            const uint32_t fb = sb + SM_BAR + (B_FULL + g0) * 8;
            mbar_expect_tx(fb, 3 * GR);
            if (kk < 16) {
              tma2d(sb + g0 * GR, &p.c, (kk & 7) * 64, (2 * idx + rank) * 128, fb, EV_NORMAL);
              tma3d_mc(sb + (g0 + 1 + rank) * GR, rank ? &p.wuv : &p.wuk, 0, (kk & 7) * 64, (hp + (kk >> 3)) * 2, fb, POL_W);
            } else {
              tma2d_mc(sb + (g0 + rank) * GR, &p.x, (kk - 16) * 64, (rank ? 15 - idx : idx) * 128, fb, EV_NORMAL);
              tma3d(sb + (g0 + 2) * GR, &p.wq, 0, (kk - 16) * 64, head * 2, fb, POL_W);
            }
            if (kk == 3) { prefetch_tm(&p.x); prefetch_tm(&p.wq); }
          }
        }
        flag_wait(FLAG(F_KV + rnd * 8 + grp), 32);
        fence_async_all();
        acquire(2); pe ^= 8u;
        int g0 = 4;
#pragma unroll 1
        for (int f = 0; f < 34; f++) {
          const bool isk = (f == 0) || ((f & 1) && f < 33);
          const int it = (f == 0) ? 0 : (f == 33) ? 16 : isk ? (f + 1) >> 1 : (f >> 1) - 1;
          const int blk = it == 0 ? idx : it <= idx ? it - 1 : it < 16 ? 15 - it : 15 - idx;
          acquire(g0);
          if (f < 8) acquire(g0 + 1); else pe ^= 2u << g0;
          if (elect()) {
            const uint32_t fb = sb + SM_BAR + (B_FULL + g0) * 8;
            mbar_expect_tx(fb, 2 * GR);
            bulk_g2s(sb + g0 * GR, g_kv + (size_t)(((isk ? 0 : 16) + (head & 15)) * 16 + blk) * 32768, 2 * GR, fb, POL_KV);
          }
          g0 = f == 2 ? 12 : g0 == 12 ? 4 : g0 + 2;
        }
      }
      if (spare) {
#pragma unroll 1
        for (int i = -1, g = 1; i < 64; i++) {
          if (i >= 0) acquire(g);
          if (elect()) {
            const uint32_t fb = sb + SM_BAR + (B_FULL + g) * 8;
            mbar_expect_tx(fb, i < 0 ? 2048 : GR);
            if (i < 0) bulk_g2s(sb + GR, p.gate_w, 2048, fb, EV_NORMAL);
            else tma2d(sb + g * GR, &p.x, (i & 15) * 64, (lb - NMAIN) * 512 + (i >> 4) * 128, fb, EV_NORMAL);
          }
          g = g == NGR - 1 ? 2 : g + 1;
        }
      }
      auto conv_fill = [&](int g, int ch) {
        acquire(g);
        if (elect()) {
          const uint32_t fb = sb + SM_BAR + (B_FULL + g) * 8;
          mbar_expect_tx(fb, WBYTES + 4096);
          bulk_g2s(sb + g * GR, g_w + (size_t)ch * WSTRIDE, WBYTES, fb, POL_C);
          bulk_g2s(sb + g * GR + WBYTES, p.ssk + (size_t)ch * SEQ, 4096, fb, POL_C);
        }
      };
#pragma unroll 1
      for (int i = 0, g = 4; i < cn; i++) {
        if ((i & 15) == 0) { flag_wait(FLAG(F_U + (spare ? 32 - __clz(i >> 4) : 4)), NMAIN); fence_async_all(); }
        conv_fill(g + (i & 1), cch + i * cstep);
        if (i & 1) g = conv_next(g, spare);
      }
      if (!spare) {
        const int rt = 2 * grp + rank, ct = idx;
        int g0 = P3G;
#pragma unroll 1
        for (int kb = 0; kb < 66; kb++) {
          if (kb == 0 || kb == 32 || kb >= 64) {
            flag_wait(FLAG(kb < 64 ? F_CTX + rt * 2 + (kb >> 5) : kb == 64 ? F_GATE : F_Y + ct), kb <= 64 ? 32 : 128);
            fence_async_all();
          }
          acquire(g0);
          if (kb < 11) acquire(g0 + 1);
          if (elect()) {
            const uint32_t fb = sb + SM_BAR + (B_FULL + g0) * 8;
            mbar_expect_tx(fb, kb == 64 ? 2 * GR + 512 : 2 * GR);
            if (kb <= 64) bulk_g2s(kb < 64 ? sb + g0 * GR : sb + SM_GATE, kb < 64 ? (const void*)(g_cimg + (size_t)(rt * 64 + kb) * GR) : (const void*)(g_gate + rt * 128), kb < 64 ? GR : 512, fb, POL_CTX);
            if (kb < 64) {
              tma2d_mc(sb + (g0 + 1) * GR + rank * 8192, &p.wo, ct * 128 + rank * 64, kb * 64, fb, POL_WO);
              if (kb == 40) { prefetch_tm(&p.y); prefetch_tm(&p.out); }
            } else {
              const CUtensorMap* tm = kb == 64 ? &p.x : &p.y;
              const int c0 = (kb == 64 ? ct : rt) * 128, c1 = (kb == 64 ? rt : ct) * 128;
              tma2d(sb + g0 * GR, tm, c0, c1, fb, EV_NORMAL);
              tma2d(sb + (g0 + 1) * GR, tm, c0 + 64, c1, fb, EV_NORMAL);
            }
          }
          g0 = g0 == 12 ? (kb == 3 ? 2 : 0) : g0 + 2;
        }
        unsigned n = 0;
        if (lane == 0) n = atomicAdd(FLAG(F_EXIT), 1);
        if (__shfl_sync(0xffffffffu, n, 0) == NMAIN - 1) { *FLAG(lane) = 0; *FLAG(lane + 32) = 0; *FLAG(lane + 64) = 0; }
      }
      if (lane == 0) mbar_arrive(sb + SM_BAR + B_DONE * 8);
    }
    __syncwarp();
    cluster_wait();
  } else {
    asm volatile("setmaxnreg.inc.sync.aligned.u32 232;");
    Cons c;
    c.sb = sb; c.pf = 0; c.wg = wgi - 1; c.tid = threadIdx.x & 127;
    const int lane = threadIdx.x & 31, t = lane & 3;
    const int row = c.wg * 64 + (warp & 3) * 16 + (lane >> 2);
    const uint32_t dkk = desc_k(sb), dk0 = dkk + c.wg * 512, dm0 = desc_mn<8192>(sb), dv0 = desc_mn<16384>(sb);
    if (c.wg == 1) bar_arrive(1, 256);
    c.pfree = 1;
    asm("mapa.shared::cluster.u32 %0, %1, %2;" : "=r"(c.relb) : "r"(sb + SM_BAR + (B_EMPTY + (c.tid >> 1)) * 8), "r"(c.tid & 1));
    c.zero = p.zero;
    const uint32_t stg = sb + (c.wg * 64 + (warp & 3) * 16 + ((lane >> 3) & 1) * 8 + (lane & 7)) * 128 + (((lane >> 4) ^ (lane & 7)) << 4);

    if (spare) {
      c.wait_full(1);
      int g = 2;
#pragma unroll 1
      for (int r = 0; r < 4; r++) {
        float d[4] = {0.f, 0.f, 0.f, 0.f};
#pragma unroll 1
        for (int kb = 0; kb < 16; kb++) {
          c.wait_full(g);
          wg_fence();
#pragma unroll
          for (int k = 0; k < 4; k++) mma_ss_n8(d, dk0 + g * DG + k * 2, dkk + DG + kb * 8 + k * 2);
          wg_commit();
          wg_wait<0>();
          c.release(g, 1);
          g = g == NGR - 1 ? 2 : g + 1;
        }
        reg_fence(d);
        if (t == 0) {
          float* gp = g_gate + (lb - NMAIN) * 512 + r * 128 + row;
          gp[0] = rcp(1.f + ex2(-1.4426950408889634f * d[0])); gp[8] = rcp(1.f + ex2(-1.4426950408889634f * d[2]));
        }
      }
      fence_release();
      __syncwarp();
      if (lane == 0) flag_add(FLAG(F_GATE));
      TS(1);
    }
    uint32_t pv[32];
#pragma unroll
    for (int i = 0; i < 32; i++) pv[i] = 0;
#pragma unroll 1
    for (int rnd = 0; rnd < (spare ? 0 : 2); rnd++) {
      float O[64];
      FTM(rnd * 8);
      c.wait_full(2);
      FTM(rnd * 8 + 1);
#pragma unroll 1
      for (int tile = c.zero; tile < 2; tile++) {
        float acc[128];
        {
          FTG(tile * 32); FTG(tile * 32 + 1);
          const uint32_t a = dk0 + 2 * DG, b = dm0 + 3 * DG;
          c.turn_begin();
          FTG(tile * 32 + 2);
          wg_fence();
          mma_ss_n256_init<1>(acc, a, b);
#pragma unroll
          for (int k = 1; k < 4; k++) mma_ss_n256<1>(acc, a + k * 2, b + k * 128);
          wg_commit();
          FTG(tile * 32 + 3);
        }
#pragma unroll 1
        for (int kb = 1; kb < 8; kb++) {
          const int g0 = 2 + 3 * (kb & 3);
          const uint32_t a = dk0 + g0 * DG, b = dm0 + (g0 + 1) * DG;
          const bool second = kb == 1 || kb == 7;
          FTG(tile * 32 + kb * 4);
          if (!second) { wg_wait<0>(); c.release(2 + 3 * ((kb - 1) & 3), 3); }
          FTG(tile * 32 + kb * 4 + 1);
          c.wait_full(g0);
          if (!second) c.turn_begin();
          FTG(tile * 32 + kb * 4 + 2);
          wg_fence();
#pragma unroll
          for (int k = 0; k < 4; k++) mma_ss_n256<1>(acc, a + k * 2, b + k * 128);
          wg_commit();
          if (kb != 6) c.turn_end();
          if (second) { wg_wait<1>(); c.release(2 + 3 * ((kb - 1) & 3), 3); }
          FTG(tile * 32 + kb * 4 + 3);
          if (tile == 1 && kb == 3) { c.wait_stage_free(); stsm_frag<0, 4>(pv, stg); }
          if (tile == 1 && kb == 4) { stsm_frag<4, 8>(pv, stg); c.staged(0); }
        }
        c.wait_stage_free();
        const bool nxt = c.try_full(2);
        wg_wait<0>();
        reg_fence(acc);
        c.release(11, 3);
        pack_frag<0>(acc, pv);
        stsm_frag(pv, stg);
        c.staged(0);
        pack_frag<64>(acc, pv);
        pin32(pv, sb);
        if (!nxt) mbar_wait(sb + SM_BAR + (B_FULL + 2) * 8, (c.pf >> 2) & 1);
        c.pf ^= 4;
      }
      TS(1 + rnd * 3);
      FTM(rnd * 8 + 2);
      {
        float qa[64];
        float (&qb)[64] = O;
        {
          FTG(64); FTG(65);
          const uint32_t a = dk0 + 2 * DG, b = dm0 + 4 * DG;
          c.turn_begin();
          FTG(66);
          wg_fence();
          mma_ss_n128_init<1>(qa, a, b);
          mma_ss_n128_init<1>(qb, a + DG, b);
#pragma unroll
          for (int k = 1; k < 4; k++) {
            mma_ss_n128<1>(qa, a + k * 2, b + k * 128);
            mma_ss_n128<1>(qb, a + DG + k * 2, b + k * 128);
          }
          wg_commit();
          FTG(67);
        }
#pragma unroll 1
        for (int kb = 1; kb < 16; kb++) {
          const int g0 = 2 + 3 * (kb & 3);
          const uint32_t a = dk0 + g0 * DG, b = dm0 + (g0 + 2) * DG;
          const bool second = kb == 1 || kb == 15;
          FTG(64 + kb * 4);
          if (!second) { wg_wait<0>(); c.release(2 + 3 * ((kb - 1) & 3), 3); }
          FTG(65 + kb * 4);
          c.wait_full(g0);
          if (!second) c.turn_begin();
          FTG(66 + kb * 4);
          wg_fence();
#pragma unroll
          for (int k = 0; k < 4; k++) {
            mma_ss_n128<1>(qa, a + k * 2, b + k * 128);
            mma_ss_n128<1>(qb, a + DG + k * 2, b + k * 128);
          }
          wg_commit();
          if (kb != 14) c.turn_end();
          if (second) { wg_wait<1>(); c.release(2 + 3 * ((kb - 1) & 3), 3); }
          FTG(67 + kb * 4);
          if (kb == QFLUSH) { c.wait_stage_free(); stsm_frag<0, 4>(pv, stg); }
          if (kb == QFLUSH + 1) { stsm_frag<4, 8>(pv, stg); c.staged(0); }
        }
        c.wait_stage_free();
        mbar_wait(sb + SM_BAR + (B_EMPTY + 2) * 8, rnd ^ 1);
        c.wait_full(4);
        FTM(rnd * 8 + 3);
        wg_wait<0>();
        reg_fence(qa); reg_fence(qb);
        c.release(11, 3);
        pack_frag<0>(qa, pv);
        stsm_frag(pv, stg + 2 * GR);
        fence_async_smem();
      }
      TS(2 + rnd * 3);
      FTM(rnd * 8 + 4);
      {
        const int nA = idx + 1;
        uint32_t (&P)[32] = pv;
        SoftState z;
        const int dmask = (row & 63) - 2 * t;
        z.m0 = z.m1 = z.n0 = z.n1 = z.l0 = z.l1 = 0.f;
#pragma unroll 1
        for (int seg = c.zero;; seg++) {
        if (c.wg == 0) attn_half(c, O, P, z, dk0, dkk, dv0, dmask, seg, stg);
        if (seg) break;
        FTM(rnd * 8 + 5);
        int gk = c.wg ? 4 : 6, gv = c.wg ? 4 : 8;
#pragma unroll 1
        for (int it = 1 - c.wg; it < 16 + c.wg; it++) {
          float S[64];
          FTA(it * 7 + 0);
          c.turn_begin();
          FTA(it * 7 + 2);
          wg_fence();
          issue_qk(S, dk0 + (it < nA ? 2 * DG : 0), dkk + gk * DG);
          wg_commit();
          if (it) {
            issue_pv<0>(O, P, dv0 + gv * DG, it != nA + 1 && it != 1, true);
            issue_pv<1>(O, P, dv0 + gv * DG, 1, HALFPV ? it + c.wg > 1 : true);
            c.turn_end();
          } else stage_q2(c, O, P, stg);
          FTA(it * 7 + 3);
          wg_wait<4>();
          reg_fence(S);
          FTA(it * 7 + 4);
          c.release(gk, 2);
          float i0, i1;
          if (it == nA || (it & 15) == 0) {
            if (it != nA) mask_diag(S, dmask);
            if (it != 16) {
              i0 = rcp(quad_sum(z.l0)); i1 = rcp(quad_sum(z.l1));
              soft_start(S, z);
            }
          }
          float s0, s1;
          const int gvo = gv;
          gk = it == 1 ? 12 : gv == 12 ? 4 : gv + 2;
          gv = it == 16 ? gk : gk == 12 ? 4 : gk + 2;
#pragma unroll 1
          for (int pass = 0;; pass++) {
            float e[16];
            s0 = 0.f; s1 = 0.f;
            exp_quarter<0>(S, e, z, s0, s1); pin(s1, sb); wg_wait<3>(); reg_fence_part<0, 8>(P); pack_quarter<0>(e, P);
            exp_quarter<1>(S, e, z, s0, s1); pin(s1, sb); wg_wait<2>(); reg_fence_part<8, 8>(P); pack_quarter<1>(e, P);
            exp_quarter<2>(S, e, z, s0, s1); pin(s1, sb); wg_wait<1>(); reg_fence_part<16, 8>(P); pack_quarter<2>(e, P);
            exp_quarter<3>(S, e, z, s0, s1); pin(s1, sb); wg_wait<0>(); reg_fence_part<24, 8>(P); reg_fence(O);
            c.release(gvo, pass || !it ? 0 : 2);
            const bool ok = c.try_full(gk) & c.try_full(gv);
            pack_quarter<3>(e, P);
            FTA(it * 7 + 5);
            if (!__any_sync(0xffffffffu, soft_bad(s0, s1) || !ok || it == nA) || pass) break;
            if (it == nA) {
              uint32_t pk[32];
              pack_frag_scaled(O, pk, i0, i1);
              stsm_frag(pk, stg + 2 * GR);
              c.staged(1);
            }
            mbar_wait(sb + SM_BAR + (B_FULL + gk) * 8, (c.pf >> gk) & 1);
            mbar_wait(sb + SM_BAR + (B_FULL + gv) * 8, (c.pf >> gv) & 1);
            if (!__any_sync(0xffffffffu, soft_bad(s0, s1))) break;
            soft_fix<true>(S, O, z);
          }
          c.pf ^= (1u << gk) | (1u << gv);
          z.l0 += s0; z.l1 += s1;
          FTA(it * 7 + 6);
        }
        FTM(rnd * 8 + 6);
        }
        c.turn_begin();
        wg_fence();
        issue_pv<0>(O, P, dv0 + 12 * DG, 1, true);
        issue_pv<1>(O, P, dv0 + 12 * DG, 1, c.wg);
        c.turn_end();
        z.l0 = rcp(quad_sum(z.l0)); z.l1 = rcp(quad_sum(z.l1));
        wg_wait<0>();
        reg_fence(O); reg_fence(P);
        c.release(12, 2);
        pack_frag_scaled(O, P, z.l0, z.l1);
        stsm_frag(P, stg);
        c.staged(0);
        FTM(rnd * 8 + 7);
      }
      TS(3 + rnd * 3);
    }
    conv_tasks(c, p, (cn + 1 - c.wg) / 2, ((cn - 1) & 1) == c.wg, spare, cch + c.wg * cstep, 2 * cstep, dkk, warp & 3, lane);
    if (c.wg == 1) c.pf ^= 0x4;
    TS(7);
    if (!spare) {
      const int rt = 2 * grp + rank, ct = idx;
      float acc[64];
      int g0 = P3G + 2, pg = P3G;
      {
        FTO(0);
        c.wait_full(P3G);
        FTO(1);
        const uint32_t a = dk0 + P3G * DG, b = dm0 + (P3G + 1) * DG;
        wg_fence();
        mma_ss_n128_init<1>(acc, a, b);
#pragma unroll
        for (int k = 1; k < 4; k++) mma_ss_n128<1>(acc, a + k * 2, b + k * 128);
        wg_commit();
      }
#pragma unroll 1
      for (int kb = 1; kb < 64; kb++) {
        FTO(kb * 2);
        c.wait_full(g0);
        FTO(kb * 2 + 1);
        const uint32_t a = dk0 + g0 * DG, b = dm0 + (g0 + 1) * DG;
        wg_fence();
#pragma unroll
        for (int k = 0; k < 4; k++) mma_ss_n128<1>(acc, a + k * 2, b + k * 128);
        wg_commit();
        wg_wait<1>();
        c.release(pg, kb <= 59 ? 2 : 0);
        if (kb == 40) FTDUMP();
        pg = g0;
        g0 = g0 == 12 ? (kb == 3 ? 2 : 0) : g0 + 2;
      }
      cluster_arrive();
      c.wait_full(P3X);
      c.wait_full(P3Y);
      const float g0f = __uint_as_float(lds32(sb + SM_GATE + row * 4)), g1f = __uint_as_float(lds32(sb + SM_GATE + row * 4 + 32));
      const uint32_t gp0 = pack_bf16(g0f, g0f), gp1 = pack_bf16(g1f, g1f);
      const float h0 = 1.f - g0f, h1 = 1.f - g1f;
      const int w = warp & 3;
      const uint32_t xa = stg + P3X * GR;
      const uint32_t ya = sb + P3Y * GR + c.wg * 16384 + ((lane >> 4) * 8 + (lane & 7)) * 128 + (((2 * w + ((lane >> 3) & 1)) ^ (lane & 7)) << 4);
      uint32_t xy[32];
#pragma unroll
      for (int jj = 0; jj < 8; jj++) {
        uint32_t x[4], y[4];
        asm volatile("ldmatrix.sync.aligned.m8n8.x4.shared.b16 {%0,%1,%2,%3}, [%4];" : "=r"(x[0]), "=r"(x[1]), "=r"(x[2]), "=r"(x[3]) : "r"((xa ^ ((jj & 3) << 5)) + (jj >> 2) * 16384) : "memory");
        asm volatile("ldmatrix.sync.aligned.m8n8.x4.trans.shared.b16 {%0,%1,%2,%3}, [%4];" : "=r"(y[0]), "=r"(y[1]), "=r"(y[2]), "=r"(y[3]) : "r"(ya + jj * 2048) : "memory");
#pragma unroll
        for (int i = 0; i < 4; i++) xy[4 * jj + i] = hmul2(x[i], y[i]);
      }
      wg_wait<0>();
      reg_fence(acc);
      TS(8);
#pragma unroll
      for (int i = 0; i < 32; i++) {
        const float h = (i & 1) ? h1 : h0;
        xy[i] = hfma2((i & 1) ? gp1 : gp0, xy[i], pack_bf16(acc[2 * i] * h, acc[2 * i + 1] * h));
      }
      stsm_frag(xy, xa);
      fence_async_smem();
      __syncwarp();
      if (lane == 0) {
        const int r0 = c.wg * 64 + w * 16;
        tma2d_store(&p.out, sb + P3X * GR + r0 * 128, ct * 128, rt * 128 + r0);
        tma2d_store(&p.out, sb + (P3X + 1) * GR + r0 * 128, ct * 128 + 64, rt * 128 + r0);
        asm volatile("cp.async.bulk.commit_group;\ncp.async.bulk.wait_group.read 0;" ::: "memory");
      }
    } else { FTDUMP(); cluster_arrive(); }
    if (lane == 0) mbar_arrive(sb + SM_BAR + B_DONE * 8);
    __syncwarp();
    TS(9);
    cluster_wait();
  }
}

typedef CUresult (*EncFn)(CUtensorMap*, CUtensorMapDataType, cuuint32_t, void*, const cuuint64_t*, const cuuint64_t*, const cuuint32_t*,
                          const cuuint32_t*, CUtensorMapInterleave, CUtensorMapSwizzle, CUtensorMapL2promotion, CUtensorMapFloatOOBfill);

void enc2d(EncFn enc, CUtensorMap* tm, const void* base, uint64_t cols, uint64_t rows, uint32_t bc, uint32_t br) {
  cuuint64_t dims[2] = {cols, rows}; cuuint64_t strides[1] = {cols * 2}; cuuint32_t box[2] = {bc, br}; cuuint32_t es[2] = {1, 1};
  enc(tm, CU_TENSOR_MAP_DATA_TYPE_BFLOAT16, 2, const_cast<void*>(base), dims, strides, box, es, CU_TENSOR_MAP_INTERLEAVE_NONE,
      CU_TENSOR_MAP_SWIZZLE_128B, CU_TENSOR_MAP_L2_PROMOTION_L2_256B, CU_TENSOR_MAP_FLOAT_OOB_FILL_NONE);
}
void enc3d(EncFn enc, CUtensorMap* tm, const void* base, uint64_t K, uint64_t N) {
  cuuint64_t dims[3] = {64, K, N / 64}; cuuint64_t strides[2] = {N * 2, 128}; cuuint32_t box[3] = {64, 64, 2}; cuuint32_t es[3] = {1, 1, 1};
  enc(tm, CU_TENSOR_MAP_DATA_TYPE_BFLOAT16, 3, const_cast<void*>(base), dims, strides, box, es, CU_TENSOR_MAP_INTERLEAVE_NONE,
      CU_TENSOR_MAP_SWIZZLE_128B, CU_TENSOR_MAP_L2_PROMOTION_L2_256B, CU_TENSOR_MAP_FLOAT_OOB_FILL_NONE);
}

}

extern "C" void kernel_launch(void* const* d_in, const int* in_sizes, int n_in, void* d_out, int out_size) {
  (void)in_sizes; (void)n_in; (void)out_size;
  typedef const __nv_bfloat16* BP;
  BP xq = (BP)d_in[0], ak = (BP)d_in[1], av = (BP)d_in[2], shk = (BP)d_in[3], ssk = (BP)d_in[4], ssd = (BP)d_in[5];
  BP ckv = (BP)d_in[7], wq = (BP)d_in[8], wuk = (BP)d_in[9], wuv = (BP)d_in[10], wo = (BP)d_in[11], gw = (BP)d_in[12];

  static EncFn enc = nullptr;
  if (!enc) {
    cudaDriverEntryPointQueryResult qr;
    cudaGetDriverEntryPoint("cuTensorMapEncodeTiled", (void**)&enc, cudaEnableDefault, &qr);
    cudaFuncSetAttribute(mega_kernel, cudaFuncAttributeMaxDynamicSharedMemorySize, SMEM_BYTES);
  }
  Params p;
  void* yT = nullptr;
  cudaGetSymbolAddress(&yT, g_yT);
  enc2d(enc, &p.x, xq, DM, SEQ, 64, 128);
  enc2d(enc, &p.c, ckv, DC, SEQ, 64, 128);
  enc3d(enc, &p.wq, wq, DM, NH * HD);
  enc3d(enc, &p.wuk, wuk, DC, NH * HD);
  enc3d(enc, &p.wuv, wuv, DC, NH * HD);
  enc2d(enc, &p.wo, wo, DM, NH * HD, 64, 64);
  enc2d(enc, &p.y, yT, SEQ, DM, 64, 128);
  enc2d(enc, &p.out, d_out, DM, SEQ, 64, 16);
  {
    void* wp = nullptr;
    cudaGetSymbolAddress(&wp, g_w);
    cuuint64_t dims[3] = {WSTRIDE / 2, DM / 2, 2}; cuuint64_t strides[2] = {2 * WSTRIDE, WSTRIDE}; cuuint32_t box[3] = {16, 32, 2}; cuuint32_t es[3] = {1, 1, 1};
    enc(&p.w, CU_TENSOR_MAP_DATA_TYPE_BFLOAT16, 3, wp, dims, strides, box, es, CU_TENSOR_MAP_INTERLEAVE_NONE,
        CU_TENSOR_MAP_SWIZZLE_32B, CU_TENSOR_MAP_L2_PROMOTION_NONE, CU_TENSOR_MAP_FLOAT_OOB_FILL_NONE);
  }
  p.zero = 0;
  p.xp = xq; p.gate_w = gw; p.ak = ak; p.av = av; p.shk = shk; p.ssk = ssk; p.ssd = ssd;

  mega_kernel<<<132, NTHREADS, SMEM_BYTES>>>(p);
}
```

```cpp
#include <cuda_runtime.h>
#include <cuda.h>
#include <cuda_bf16.h>
#include <stdint.h>

namespace {

constexpr int SEQ = 2048, DM = 1024, DC = 512, NH = 32, HD = 128;
constexpr int GR = 16384;
constexpr int NGR = 14;
constexpr int SM_BAR = NGR * GR;
constexpr int SM_GATE = SM_BAR + 512;
constexpr int SM_UST = SM_GATE + 512;
constexpr int SMEM_BYTES = SM_UST + 2048;
constexpr int NTHREADS = 384;
#define SM_LIMIT 1.0995116e12f
#define SM_LOW 9.094947e-13f
constexpr int CN_MAIN = 5, CN_SPARE = 96;
constexpr int P3G = 6, P3X = 10, P3Y = 12;
constexpr int NMAIN = 128;

constexpr int B_FULL = 0, B_EMPTY = 14, B_EV = 28, B_DONE = 34;

__device__ __align__(1024) uint8_t g_kv[2 * 16 * 16 * 32768];
__device__ __align__(1024) uint8_t g_cimg[16 * NH * 32768];
__device__ __align__(1024) __nv_bfloat16 g_yT[DM * SEQ];
__device__ __align__(1024) float g_gate[SEQ];
constexpr int WSTRIDE = 8832, WBYTES = 8736;
__device__ __align__(1024) uint8_t g_w[DM * WSTRIDE];
__device__ unsigned g_flags[128 * 8];
constexpr int F_KV = 0, F_CTX = 16, F_U = 48, F_AD = 56, F_Y = 64, F_GATE = 72, F_EXIT = 73;
#define FLAG(i) (&g_flags[(i) * 8])

#define TS(slot)
#define TSW(slot)
#define FTX(i, off)
#define FTDUMP()

#define ST_OUT 0
#define QFLUSH 4
#define POL_W EV_NORMAL
#define POL_WO EV_FIRST
#define POL_KV EV_NORMAL
#define POL_C EV_FIRST
#define POL_CTX EV_FIRST
#define HALFPV 0
#define PWAIT mbar_wait1
#define PRE_SLEEP 1500
#define EXPV 1
#define START_PF 1
#define SUMV 0
#define ROT 8
#define FINE_MODE 0
#define FINE_RND 1
#define FTA(i) do { if (FINE_MODE == 0) FTX(i, rnd ^ FINE_RND); } while (0)
#define FTG(i) do { if (FINE_MODE == 1) FTX(i, rnd ^ FINE_RND); } while (0)
#define FTM(i) do { if (FINE_MODE == 4) FTX(i, 0); } while (0)
#define FTC(k) do { if (FINE_MODE == 5) FTX((i & 7) * 8 + (k), (i >> 3) ^ FINE_RND); } while (0)
#define FTO(i) do { if (FINE_MODE == 2) FTX(i, 0); } while (0)

__device__ __forceinline__ uint32_t smem_u32(const void* p) { return (uint32_t)__cvta_generic_to_shared(p); }
__device__ __forceinline__ void mbar_init(uint32_t bar, int cnt) { asm volatile("mbarrier.init.shared::cta.b64 [%0], %1;" ::"r"(bar), "r"(cnt) : "memory"); }
__device__ __forceinline__ void mbar_expect_tx(uint32_t bar, uint32_t bytes) { asm volatile("mbarrier.arrive.expect_tx.shared::cta.b64 _, [%0], %1;" ::"r"(bar), "r"(bytes) : "memory"); }
__device__ __forceinline__ void mbar_arrive(uint32_t bar) { asm volatile("mbarrier.arrive.shared::cta.b64 _, [%0];" ::"r"(bar) : "memory"); }
__device__ __forceinline__ void mbar_arrive_cluster(uint32_t bar, uint32_t cta) {
  asm volatile("{\n.reg .b32 r;\nmapa.shared::cluster.u32 r, %0, %1;\nmbarrier.arrive.shared::cluster.b64 _, [r];\n}\n" ::"r"(bar), "r"(cta) : "memory");
}
__device__ __forceinline__ bool mbar_try(uint32_t bar, uint32_t parity) {
  uint32_t ok;
  asm volatile("{\n.reg .pred p;\nmbarrier.try_wait.parity.shared::cta.b64 p, [%1], %2, 20000;\nselp.u32 %0, 1, 0, p;\n}\n" : "=r"(ok) : "r"(bar), "r"(parity) : "memory");
  return ok;
}
__device__ __forceinline__ bool mbar_test(uint32_t bar, uint32_t parity) {
  uint32_t ok;
  asm volatile("{\n.reg .pred p;\nmbarrier.test_wait.parity.shared::cta.b64 p, [%1], %2;\nselp.u32 %0, 1, 0, p;\n}\n" : "=r"(ok) : "r"(bar), "r"(parity) : "memory");
  return ok;
}
__device__ __forceinline__ void mbar_wait(uint32_t bar, uint32_t parity) {
  asm volatile("{\n.reg .pred p;\nWAIT_LOOP:\nbar.warp.sync -1;\nmbarrier.try_wait.parity.shared::cta.b64 p, [%0], %1;\n@!p bra WAIT_LOOP;\n}\n" ::"r"(bar), "r"(parity) : "memory");
}
__device__ __forceinline__ void mbar_wait1(uint32_t bar, uint32_t parity) {
  asm volatile("{\n.reg .pred p;\nWAIT_LOOP:\nbar.warp.sync -1;\nmbarrier.try_wait.parity.shared::cta.b64 p, [%0], %1, 4000;\n@!p bra WAIT_LOOP;\n}\n" ::"r"(bar), "r"(parity) : "memory");
}
constexpr uint64_t EV_NORMAL = 0x1000000000000000ull, EV_FIRST = 0x12F0000000000000ull;
__device__ __forceinline__ uint32_t ldg_stream(const uint32_t* p) {
  uint32_t r; asm volatile("ld.global.nc.L1::no_allocate.L2::cache_hint.b32 %0, [%1], %2;" : "=r"(r) : "l"(p), "l"(EV_FIRST)); return r;
}
__device__ __forceinline__ void tma2d(uint32_t dst, const CUtensorMap* tm, int c0, int c1, uint32_t bar, uint64_t pol) {
  asm volatile("cp.async.bulk.tensor.2d.shared::cluster.global.mbarrier::complete_tx::bytes.L2::cache_hint [%0], [%1, {%3, %4}], [%2], %5;"
               ::"r"(dst), "l"(tm), "r"(bar), "r"(c0), "r"(c1), "l"(pol) : "memory");
}
__device__ __forceinline__ void tma2d_mc(uint32_t dst, const CUtensorMap* tm, int c0, int c1, uint32_t bar, uint64_t pol) {
  asm volatile("cp.async.bulk.tensor.2d.shared::cluster.global.mbarrier::complete_tx::bytes.multicast::cluster.L2::cache_hint [%0], [%1, {%3, %4}], [%2], %5, %6;"
               ::"r"(dst), "l"(tm), "r"(bar), "r"(c0), "r"(c1), "h"((uint16_t)3), "l"(pol) : "memory");
}
__device__ __forceinline__ void tma3d(uint32_t dst, const CUtensorMap* tm, int c0, int c1, int c2, uint32_t bar, uint64_t pol) {
  asm volatile("cp.async.bulk.tensor.3d.shared::cluster.global.mbarrier::complete_tx::bytes.L2::cache_hint [%0], [%1, {%3, %4, %5}], [%2], %6;"
               ::"r"(dst), "l"(tm), "r"(bar), "r"(c0), "r"(c1), "r"(c2), "l"(pol) : "memory");
}
__device__ __forceinline__ void tma3d_mc(uint32_t dst, const CUtensorMap* tm, int c0, int c1, int c2, uint32_t bar, uint64_t pol) {
  asm volatile("cp.async.bulk.tensor.3d.shared::cluster.global.mbarrier::complete_tx::bytes.multicast::cluster.L2::cache_hint [%0], [%1, {%3, %4, %5}], [%2], %6, %7;"
               ::"r"(dst), "l"(tm), "r"(bar), "r"(c0), "r"(c1), "r"(c2), "h"((uint16_t)3), "l"(pol) : "memory");
}
__device__ __forceinline__ void bulk_g2s(uint32_t dst, const void* src, uint32_t bytes, uint32_t bar, uint64_t pol) {
  asm volatile("cp.async.bulk.shared::cluster.global.mbarrier::complete_tx::bytes.L2::cache_hint [%0], [%1], %2, [%3], %4;"
               ::"r"(dst), "l"(src), "r"(bytes), "r"(bar), "l"(pol) : "memory");
}
__device__ __forceinline__ void tma2d_store(const CUtensorMap* tm, uint32_t src, int c0, int c1) {
  asm volatile("cp.async.bulk.tensor.2d.global.shared::cta.bulk_group [%0, {%2, %3}], [%1];" ::"l"(tm), "r"(src), "r"(c0), "r"(c1) : "memory");
}
__device__ __forceinline__ void prefetch_tm(const CUtensorMap* tm) { asm volatile("prefetch.tensormap [%0];" ::"l"(tm) : "memory"); }
__device__ __forceinline__ void wg_fence() { asm volatile("wgmma.fence.sync.aligned;" ::: "memory"); }
__device__ __forceinline__ void wg_commit() { asm volatile("wgmma.commit_group.sync.aligned;" ::: "memory"); }
template <int N> __device__ __forceinline__ void wg_wait() { asm volatile("wgmma.wait_group.sync.aligned %0;" ::"n"(N) : "memory"); }
__device__ __forceinline__ void bar_sync(int id, int n) { asm volatile("bar.sync %0, %1;" ::"r"(id), "r"(n) : "memory"); }
__device__ __forceinline__ void bar_arrive(int id, int n) { asm volatile("bar.arrive %0, %1;" ::"r"(id), "r"(n) : "memory"); }
__device__ __forceinline__ void fence_async_smem() { asm volatile("fence.proxy.async.shared::cta;" ::: "memory"); }
__device__ __forceinline__ void fence_async_all() { asm volatile("fence.proxy.async.global;" ::: "memory"); }
__device__ __forceinline__ uint32_t pack_bf16(float lo, float hi) { uint32_t r; asm("cvt.rn.bf16x2.f32 %0, %1, %2;" : "=r"(r) : "f"(hi), "f"(lo)); return r; }
__device__ __forceinline__ float ex2(float x) { float r; asm("ex2.approx.ftz.f32 %0, %1;" : "=f"(r) : "f"(x)); return r; }
__device__ __forceinline__ float rcp(float x) { float r; asm("rcp.approx.ftz.f32 %0, %1;" : "=f"(r) : "f"(x)); return r; }
__device__ __forceinline__ void flag_wait(const unsigned* f, unsigned target) {
  unsigned v;
  do { asm volatile("ld.acquire.gpu.global.u32 %0, [%1];" : "=r"(v) : "l"(f) : "memory"); } while (__any_sync(0xffffffffu, v < target));
}
__device__ __forceinline__ bool elect() {
  uint32_t r;
  asm volatile("{\n.reg .pred p;\nelect.sync _|p, -1;\nselp.u32 %0, 1, 0, p;\n}\n" : "=r"(r));
  return r;
}
__device__ __forceinline__ void fence_release() { asm volatile("fence.release.gpu;" ::: "memory"); }
__device__ __forceinline__ void flag_add(unsigned* f) { asm volatile("red.relaxed.gpu.global.add.u32 [%0], 1;" ::"l"(f) : "memory"); }
__device__ __forceinline__ void cluster_arrive() { asm volatile("barrier.cluster.arrive.relaxed.aligned;" ::: "memory"); }
__device__ __forceinline__ void cluster_wait() { asm volatile("barrier.cluster.wait.aligned;" ::: "memory"); }
__device__ __forceinline__ uint32_t hmul2(uint32_t a, uint32_t b) { uint32_t r; asm("mul.rn.bf16x2 %0, %1, %2;" : "=r"(r) : "r"(a), "r"(b)); return r; }
__device__ __forceinline__ uint32_t hadd2(uint32_t a, uint32_t b) { uint32_t r; asm("add.rn.bf16x2 %0, %1, %2;" : "=r"(r) : "r"(a), "r"(b)); return r; }
__device__ __forceinline__ uint32_t hfma2(uint32_t a, uint32_t b, uint32_t c) { uint32_t r; asm("fma.rn.bf16x2 %0, %1, %2, %3;" : "=r"(r) : "r"(a), "r"(b), "r"(c)); return r; }
__device__ __forceinline__ uint32_t lds32(uint32_t a) { uint32_t r; asm volatile("ld.shared.b32 %0, [%1];" : "=r"(r) : "r"(a) : "memory"); return r; }
__device__ __forceinline__ uint4 lds128(uint32_t a) { uint4 r; asm volatile("ld.shared.v4.b32 {%0,%1,%2,%3}, [%4];" : "=r"(r.x), "=r"(r.y), "=r"(r.z), "=r"(r.w) : "r"(a) : "memory"); return r; }
__device__ __forceinline__ uint32_t desc_k(uint32_t addr) { return ((addr & 0x3FFFF) >> 4) | (1u << 16); }
template <int LBO> __device__ __forceinline__ uint32_t desc_mn(uint32_t addr) { return ((addr & 0x3FFFF) >> 4) | ((uint32_t)(LBO >> 4) << 16); }
#define DHI "0x40000040"

#define R8(d, o) "+f"(d[o]), "+f"(d[o + 1]), "+f"(d[o + 2]), "+f"(d[o + 3]), "+f"(d[o + 4]), "+f"(d[o + 5]), "+f"(d[o + 6]), "+f"(d[o + 7])
#define R32(d, o) R8(d, o), R8(d, o + 8), R8(d, o + 16), R8(d, o + 24)
#define R64(d, o) R32(d, o), R32(d, o + 32)
#define L64 "%0,%1,%2,%3,%4,%5,%6,%7,%8,%9,%10,%11,%12,%13,%14,%15,%16,%17,%18,%19,%20,%21,%22,%23,%24,%25,%26,%27,%28,%29,%30,%31," \
            "%32,%33,%34,%35,%36,%37,%38,%39,%40,%41,%42,%43,%44,%45,%46,%47,%48,%49,%50,%51,%52,%53,%54,%55,%56,%57,%58,%59,%60,%61,%62,%63"
#define L128 L64 ",%64,%65,%66,%67,%68,%69,%70,%71,%72,%73,%74,%75,%76,%77,%78,%79,%80,%81,%82,%83,%84,%85,%86,%87,%88,%89,%90,%91,%92,%93,%94,%95," \
            "%96,%97,%98,%99,%100,%101,%102,%103,%104,%105,%106,%107,%108,%109,%110,%111,%112,%113,%114,%115,%116,%117,%118,%119,%120,%121,%122,%123,%124,%125,%126,%127"

template <int TB> __device__ __forceinline__ void mma_ss_n128(float (&d)[64], uint32_t da, uint32_t db) {
  asm volatile("{\n.reg .b64 da, db;\nmov.b64 da, {%64, " DHI "};\nmov.b64 db, {%65, " DHI "};\n"
               "wgmma.mma_async.sync.aligned.m64n128k16.f32.bf16.bf16 {" L64 "}, da, db, 1, 1, 1, 0, %66;\n}\n"
               : R64(d, 0) : "r"(da), "r"(db), "n"(TB));
}
template <int TB> __device__ __forceinline__ void mma_rs_n128(float (&d)[64], uint32_t a0, uint32_t a1, uint32_t a2, uint32_t a3, uint32_t db, int sd) {
  asm volatile("{\n.reg .pred p;\n.reg .b64 db;\nsetp.ne.b32 p, %69, 0;\nmov.b64 db, {%68, " DHI "};\n"
               "wgmma.mma_async.sync.aligned.m64n128k16.f32.bf16.bf16 {" L64 "}, {%64,%65,%66,%67}, db, p, 1, 1, %70;\n}\n"
               : R64(d, 0) : "r"(a0), "r"(a1), "r"(a2), "r"(a3), "r"(db), "r"(sd), "n"(TB));
}
template <int TB> __device__ __forceinline__ void mma_ss_n256(float (&d)[128], uint32_t da, uint32_t db) {
  asm volatile("{\n.reg .b64 da, db;\nmov.b64 da, {%128, " DHI "};\nmov.b64 db, {%129, " DHI "};\n"
               "wgmma.mma_async.sync.aligned.m64n256k16.f32.bf16.bf16 {" L128 "}, da, db, 1, 1, 1, 0, %130;\n}\n"
               : R64(d, 0), R64(d, 64) : "r"(da), "r"(db), "n"(TB));
}
#define W8(d, o) "=f"(d[o]), "=f"(d[o + 1]), "=f"(d[o + 2]), "=f"(d[o + 3]), "=f"(d[o + 4]), "=f"(d[o + 5]), "=f"(d[o + 6]), "=f"(d[o + 7])
#define W32(d, o) W8(d, o), W8(d, o + 8), W8(d, o + 16), W8(d, o + 24)
#define W64(d, o) W32(d, o), W32(d, o + 32)
template <int TB> __device__ __forceinline__ void mma_ss_n128_init(float (&d)[64], uint32_t da, uint32_t db) {
  asm volatile("{\n.reg .b64 da, db;\nmov.b64 da, {%64, " DHI "};\nmov.b64 db, {%65, " DHI "};\n"
               "wgmma.mma_async.sync.aligned.m64n128k16.f32.bf16.bf16 {" L64 "}, da, db, 0, 1, 1, 0, %66;\n}\n"
               : W64(d, 0) : "r"(da), "r"(db), "n"(TB));
}
template <int TB> __device__ __forceinline__ void mma_ss_n256_init(float (&d)[128], uint32_t da, uint32_t db) {
  asm volatile("{\n.reg .b64 da, db;\nmov.b64 da, {%128, " DHI "};\nmov.b64 db, {%129, " DHI "};\n"
               "wgmma.mma_async.sync.aligned.m64n256k16.f32.bf16.bf16 {" L128 "}, da, db, 0, 1, 1, 0, %130;\n}\n"
               : W64(d, 0), W64(d, 64) : "r"(da), "r"(db), "n"(TB));
}
#define L32 "%0,%1,%2,%3,%4,%5,%6,%7,%8,%9,%10,%11,%12,%13,%14,%15,%16,%17,%18,%19,%20,%21,%22,%23,%24,%25,%26,%27,%28,%29,%30,%31"
__device__ __forceinline__ void mma_ss_n64(float (&d)[32], uint32_t da, uint32_t db) {
  asm volatile("{\n.reg .b64 da, db;\nmov.b64 da, {%32, " DHI "};\nmov.b64 db, {%33, " DHI "};\n"
               "wgmma.mma_async.sync.aligned.m64n64k16.f32.bf16.bf16 {" L32 "}, da, db, 1, 1, 1, 0, 0;\n}\n"
               : R32(d, 0) : "r"(da), "r"(db));
}
__device__ __forceinline__ void mma_ss_n64_init(float (&d)[32], uint32_t da, uint32_t db) {
  asm volatile("{\n.reg .b64 da, db;\nmov.b64 da, {%32, " DHI "};\nmov.b64 db, {%33, " DHI "};\n"
               "wgmma.mma_async.sync.aligned.m64n64k16.f32.bf16.bf16 {" L32 "}, da, db, 0, 1, 1, 0, 0;\n}\n"
               : W32(d, 0) : "r"(da), "r"(db));
}
#define L16 "%0,%1,%2,%3,%4,%5,%6,%7,%8,%9,%10,%11,%12,%13,%14,%15"
__device__ __forceinline__ void mma_rs_n32(float (&d)[16], uint32_t a0, uint32_t a1, uint32_t a2, uint32_t a3, uint32_t db) {
  asm volatile("{\n.reg .b64 db;\nmov.b64 db, {%20, 0x00000008};\n"
               "wgmma.mma_async.sync.aligned.m64n32k16.f32.bf16.bf16 {" L16 "}, {%16,%17,%18,%19}, db, 1, 1, 1, 0;\n}\n"
               : R8(d, 0), R8(d, 8) : "r"(a0), "r"(a1), "r"(a2), "r"(a3), "r"(db));
}
__device__ __forceinline__ void mma_rs_n32_init(float (&d)[16], uint32_t a0, uint32_t a1, uint32_t a2, uint32_t a3, uint32_t db) {
  asm volatile("{\n.reg .b64 db;\nmov.b64 db, {%20, 0x00000008};\n"
               "wgmma.mma_async.sync.aligned.m64n32k16.f32.bf16.bf16 {" L16 "}, {%16,%17,%18,%19}, db, 0, 1, 1, 0;\n}\n"
               : W8(d, 0), W8(d, 8) : "r"(a0), "r"(a1), "r"(a2), "r"(a3), "r"(db));
}
__device__ __forceinline__ void mma_ss_n8(float (&d)[4], uint32_t da, uint32_t db) {
  asm volatile("{\n.reg .b64 da, db;\nmov.b64 da, {%4, " DHI "};\nmov.b64 db, {%5, 0x00000008};\n"
               "wgmma.mma_async.sync.aligned.m64n8k16.f32.bf16.bf16 {%0,%1,%2,%3}, da, db, 1, 1, 1, 0, 0;\n}\n"
               : "+f"(d[0]), "+f"(d[1]), "+f"(d[2]), "+f"(d[3]) : "r"(da), "r"(db));
}
template <int N> __device__ __forceinline__ void reg_fence(float (&d)[N]) {
#pragma unroll
  for (int i = 0; i < N; i++) asm volatile("" : "+f"(d[i])::"memory");
}
template <int N> __device__ __forceinline__ void reg_fence(uint32_t (&d)[N]) {
#pragma unroll
  for (int i = 0; i < N; i++) asm volatile("" : "+r"(d[i])::"memory");
}

struct __align__(64) Params {
  CUtensorMap x, c, wq, wuk, wuv, wo, y, out, w;
  const __nv_bfloat16* xp;
  const __nv_bfloat16* gate_w;
  const __nv_bfloat16 *ak, *av, *shk, *ssk, *ssd, *cp, *wukp, *wuvp;
  int zero;
};

template <int O, int N, int M> __device__ __forceinline__ void pack_frag(const float (&acc)[N], uint32_t (&pk)[M]) {
#pragma unroll
  for (int i = 0; i < 32; i++) pk[i] = pack_bf16(acc[O + 2 * i], acc[O + 2 * i + 1]);
}
template <int N> __device__ __forceinline__ void pack_frag_scaled(const float (&acc)[N], uint32_t (&pk)[32], float s0, float s1) {
#pragma unroll
  for (int i = 0; i < 32; i++) { const float s = (i & 1) ? s1 : s0; pk[i] = pack_bf16(acc[2 * i] * s, acc[2 * i + 1] * s); }
}
template <int J0 = 0, int J1 = 8, int M> __device__ __forceinline__ void stsm_frag(const uint32_t (&pk)[M], uint32_t a) {
#pragma unroll
  for (int jj = J0; jj < J1; jj++)
    asm volatile("stmatrix.sync.aligned.m8n8.x4.shared.b16 [%0], {%1,%2,%3,%4};" ::"r"((a ^ ((jj & 3) << 5)) + (jj >> 2) * 16384),
                 "r"(pk[4 * jj]), "r"(pk[4 * jj + 1]), "r"(pk[4 * jj + 2]), "r"(pk[4 * jj + 3]) : "memory");
}

struct Cons {
  uint32_t sb;
  uint32_t pf;
  int wg, tid;
  __device__ __forceinline__ void wait_full(int g) { mbar_wait(sb + SM_BAR + (B_FULL + g) * 8, (pf >> g) & 1); pf ^= 1u << g; }
  uint32_t relb;
  __device__ __forceinline__ void release(int g, int n) {
    if (tid < 2 * n) asm volatile("mbarrier.arrive.shared::cluster.b64 _, [%0];" ::"r"(relb + g * 8) : "memory");
  }
  __device__ __forceinline__ void turn_begin() { bar_sync(1 + wg, 256); }
  __device__ __forceinline__ void turn_end() { bar_arrive(2 - wg, 256); }
  __device__ __forceinline__ void staged(int e) { __syncwarp(); if ((tid & 31) == 0) mbar_arrive(sb + SM_BAR + (B_EV + 2 * e + wg) * 8); }
  int zero;
  uint32_t pfree;
  __device__ __forceinline__ void wait_stage_free() { mbar_wait(sb + SM_BAR + (B_EV + 4 + wg) * 8, pfree); pfree ^= 1; }
  __device__ __forceinline__ bool try_full(int g) { return mbar_test(sb + SM_BAR + (B_FULL + g) * 8, (pf >> g) & 1); }
};

constexpr float SM_C = 0.08838834764831845f * 1.4426950408889634f;
struct SoftState { float m0, m1, l0, l1; int shifted; float t[ROT]; };
__device__ __forceinline__ void ex2_rot(float& t, float s, uint32_t never_zero) {
  asm("{\n.reg .pred p;\nsetp.ne.u32 p, %2, 0;\n@p ex2.approx.ftz.f32 %0, %1;\n}\n" : "+f"(t) : "f"(s), "r"(never_zero));
}
template <int I0, int I1, int N> __device__ __forceinline__ void exp_pairs(const float (&S)[N], uint32_t (&P)[32], SoftState& z, float& s0, float& s1, uint32_t nz) {
#pragma unroll
  for (int i = I0; i < I1; i++) {
    float& a = z.t[(2 * i) % ROT];
    float& b = z.t[(2 * i + 1) % ROT];
    ex2_rot(a, S[2 * i], nz); ex2_rot(b, S[2 * i + 1], nz);
    if (SUMV == 0) { if (i & 1) { s1 += a; s1 += b; } else { s0 += a; s0 += b; } }
    else { if (i & 1) s1 += a + b; else s0 += a + b; }
    P[i] = pack_bf16(a, b);
  }
}
template <int N> __device__ __forceinline__ void shift_scores(float (&S)[N], float d0, float d1) {
#pragma unroll
  for (int i = 0; i < N; i++) S[i] -= (i & 2) ? d1 : d0;
}
__device__ __forceinline__ bool soft_high(float s0, float s1) { return s0 + s1 > SM_LIMIT; }
__device__ __forceinline__ bool soft_unsafe(float s0, float s1, bool first) {
  uint32_t b0 = __ballot_sync(0xffffffffu, s0 >= SM_LOW), b1 = __ballot_sync(0xffffffffu, s1 >= SM_LOW);
  b0 |= b0 >> 1; b0 |= b0 >> 2; b1 |= b1 >> 1; b1 |= b1 >> 2;
  return __any_sync(0xffffffffu, soft_high(s0, s1)) || (first && (b0 & b1 & 0x11111111u) != 0x11111111u);
}
template <int N> __device__ __forceinline__ void soft_fix(const float (&S)[N], float (&O)[64], SoftState& z, bool first, float& d0, float& d1) {
  d0 = d1 = first ? -INFINITY : 0.f;
#pragma unroll
  for (int j = 0; j < N / 4; j++) { d0 = fmaxf(d0, fmaxf(S[4 * j], S[4 * j + 1])); d1 = fmaxf(d1, fmaxf(S[4 * j + 2], S[4 * j + 3])); }
  d0 = fmaxf(d0, __shfl_xor_sync(0xffffffffu, d0, 1)); d1 = fmaxf(d1, __shfl_xor_sync(0xffffffffu, d1, 1));
  d0 = fmaxf(d0, __shfl_xor_sync(0xffffffffu, d0, 2)); d1 = fmaxf(d1, __shfl_xor_sync(0xffffffffu, d1, 2));
  const float sc0 = ex2(-fmaxf(d0, 0.f)), sc1 = ex2(-fmaxf(d1, 0.f));
  z.m0 += d0; z.m1 += d1; z.l0 *= sc0; z.l1 *= sc1; z.shifted = 1;
#pragma unroll
  for (int j = 0; j < 16; j++) { O[4 * j] *= sc0; O[4 * j + 1] *= sc0; O[4 * j + 2] *= sc1; O[4 * j + 3] *= sc1; }
}
__device__ __forceinline__ void pin(float a, uint32_t never_zero) {
  asm volatile("{\n.reg .pred p;\nsetp.eq.u32 p, %1, 0;\n@p st.shared.f32 [%1], %0;\n}\n" ::"f"(a), "r"(never_zero) : "memory");
}
template <int M> __device__ __forceinline__ void pin32(const uint32_t (&v)[M], uint32_t never_zero) {
#pragma unroll
  for (int i = 0; i < 32; i += 4)
    asm volatile("{\n.reg .pred p;\nsetp.eq.u32 p, %4, 0;\n@p st.shared.v4.b32 [%4], {%0,%1,%2,%3};\n}\n" ::"r"(v[i]), "r"(v[i + 1]), "r"(v[i + 2]), "r"(v[i + 3]), "r"(never_zero) : "memory");
}
template <int O, int N> __device__ __forceinline__ void reg_fence_part(uint32_t (&d)[32]) {
#pragma unroll
  for (int i = O; i < O + N; i++) asm volatile("" : "+r"(d[i])::"memory");
}
template <int N> __device__ __forceinline__ void mask_diag(float (&S)[N], int d) {
#pragma unroll
  for (int j = 0; j < 8; j++) {
    if (8 * j > d) S[N - 32 + 4 * j] = -INFINITY;
    if (8 * j + 1 > d) S[N - 32 + 4 * j + 1] = -INFINITY;
    if (8 * j > d + 8) S[N - 32 + 4 * j + 2] = -INFINITY;
    if (8 * j + 1 > d + 8) S[N - 32 + 4 * j + 3] = -INFINITY;
  }
}
__device__ __forceinline__ float quad_sum(float v) {
  v += __shfl_xor_sync(0xffffffffu, v, 1);
  v += __shfl_xor_sync(0xffffffffu, v, 2);
  return v;
}
__device__ __forceinline__ void issue_qk(float (&S)[64], uint32_t dq, uint32_t dk) {
  mma_ss_n128_init<0>(S, dq, dk);
#pragma unroll
  for (int s = 1; s < 8; s++) mma_ss_n128<0>(S, dq + (s >> 2) * 1024 + (s & 3) * 2, dk + (s >> 2) * 1024 + (s & 3) * 2);
}
__device__ __forceinline__ void issue_qk(float (&S)[32], uint32_t dq, uint32_t dk) {
  mma_ss_n64_init(S, dq, dk);
#pragma unroll
  for (int s = 1; s < 8; s++) mma_ss_n64(S, dq + (s >> 2) * 1024 + (s & 3) * 2, dk + (s >> 2) * 1024 + (s & 3) * 2);
}
template <int H> __device__ __forceinline__ void issue_pv(float (&O)[64], const uint32_t (&P)[32], uint32_t dv, int acc, bool on) {
  if (on) {
#pragma unroll
    for (int s = 4 * H; s < 4 * H + 4; s++) {
      mma_rs_n128<1>(O, P[4 * s], P[4 * s + 1], P[4 * s + 2], P[4 * s + 3], dv + s * 128, s != 0 ? 1 : acc);
      if (s & 1) wg_commit();
    }
  } else { wg_commit(); wg_commit(); }
}
constexpr uint32_t DG = GR >> 4;
__device__ __forceinline__ void stage_q2(Cons& c, const float (&O)[64], uint32_t (&P)[32], uint32_t stg) {
  wg_commit(); wg_commit(); wg_commit(); wg_commit();
  c.turn_end();
  pack_frag<0>(O, P);
  stsm_frag(P, stg);
  fence_async_smem();
#pragma unroll
  for (int i = 16; i < 32; i++) P[i] = 0;
}
__device__ __forceinline__ void attn_half(Cons& c, float (&O)[64], uint32_t (&P)[32], SoftState& z, uint32_t dk0, uint32_t dkk, uint32_t dv0, int dmask, int last, uint32_t stg) {
  float S[32];
  c.turn_begin();
  wg_fence();
  issue_qk(S, dk0 + (last ? 0 : 2 * DG), dkk + (last ? 8 : 4) * DG);
  wg_commit();
  if (last) {
    issue_pv<0>(O, P, dv0 + 10 * DG, 1, true);
    issue_pv<1>(O, P, dv0 + 10 * DG, 1, true);
    c.turn_end();
  } else stage_q2(c, O, P, stg);
  wg_wait<4>();
  reg_fence(S);
  c.release(last ? 8 : 4, 2);
  mask_diag(S, dmask);
  float s0, s1, d0 = z.m0, d1 = z.m1;
#pragma unroll 1
  for (int pass = 0;; pass++) {
    if (z.shifted) shift_scores(S, d0, d1);
    s0 = 0.f; s1 = 0.f;
    wg_wait<3>(); reg_fence_part<0, 8>(P);
    exp_pairs<0, 8>(S, P, z, s0, s1, c.sb);
    pin(s1, c.sb); wg_wait<2>(); reg_fence_part<8, 8>(P);
    exp_pairs<8, 16>(S, P, z, s0, s1, c.sb);
    pin(s1, c.sb); wg_wait<0>(); reg_fence_part<16, 16>(P); reg_fence(O);
    if (!soft_unsafe(s0, s1, !last) || pass) break;
    soft_fix(S, O, z, !last, d0, d1);
  }
  z.l0 += s0; z.l1 += s1;
  c.release(10, last ? 2 : 0);
  c.wait_full(last ? 12 : 6);
  if (!last) c.wait_full(8);
}

__device__ __forceinline__ int conv_next(int g, bool spare) { return spare ? (g >= NGR - 2 ? g - (NGR - 4) : g + 2) : g ^ 6; }
__device__ __forceinline__ void conv_final(uint32_t rb, uint32_t yb, const uint4& u, uint32_t dd, bool on) {
  const uint4 q0 = lds128(rb), q1 = lds128(rb + 4096), q2 = lds128(rb + 8192), q3 = lds128(rb + 12288);
  auto fin = [&](uint32_t x0, uint32_t x1, uint32_t x2, uint32_t x3, uint32_t uu) {
    return hfma2(dd, __byte_perm(uu, uu, 0x1032), hadd2(hadd2(x0, x1), hadd2(x2, x3)));
  };
  asm volatile("{\n.reg .pred p;\nsetp.ne.b32 p, %5, 0;\n@p st.shared.v4.b32 [%0], {%1,%2,%3,%4};\n}\n" ::"r"(yb), "r"(fin(q0.x, q1.x, q2.x, q3.x, u.w)),
               "r"(fin(q0.y, q1.y, q2.y, q3.y, u.z)), "r"(fin(q0.z, q1.z, q2.z, q3.z, u.y)), "r"(fin(q0.w, q1.w, q2.w, q3.w, u.x)), "r"((int)on) : "memory");
}
__device__ __forceinline__ void conv_tasks(Cons& c, const Params& p, int ntask, bool last, bool spare, int ch, int chstep, uint32_t dkk, int w, int lane) {
  const uint32_t sb = c.sb;
  int g = 4 + c.wg;
  uint4 u0 = make_uint4(0, 0, 0, 0), u1 = u0;
  uint32_t dd = 0, rb = sb + g * GR;
  const uint32_t yb = sb + c.wg * 8192 + c.tid * 16;
  c.wait_full(g);
#pragma unroll 1
  for (int i = 0; i < ntask; i++) {
    const uint32_t base = sb + g * GR;
    FTC(0);
    uint32_t a[64];
    const uint32_t hb = base + WBYTES - 28 + (8 * w + (lane >> 2) + (lane & 3)) * 4;
    auto lda = [&](int s) {
      a[4 * s] = lds32(hb + s * 256); a[4 * s + 1] = lds32(hb + s * 256 + 128);
      a[4 * s + 2] = lds32(hb + s * 256 + 16); a[4 * s + 3] = lds32(hb + s * 256 + 144);
    };
    lda(0); lda(15); lda(1); lda(14);
    float acc[8][16];
    const uint32_t db = dkk + ((4352 / 16 - 1) << 16) + g * DG + 16;
    FTC(2);
    c.turn_begin();
    FTC(3);
#pragma unroll
    for (int k = 0; k < 8; k++) {
      if (k < 7) wg_fence();
      if (k == 7 && !(last && i == ntask - 1)) c.turn_end();
#pragma unroll
      for (int J = 7; J >= (k >> 1); J--) {
        if (k == 0) mma_rs_n32_init(acc[J], a[0], a[1], a[2], a[3], db + J * 32);
        else mma_rs_n32(acc[J], a[4 * k], a[4 * k + 1], a[4 * k + 2], a[4 * k + 3], db + (2 * J - k) * 16);
      }
      const int s = 15 - k;
#pragma unroll
      for (int J = 7; J >= (s >> 1); J--) mma_rs_n32(acc[J], a[4 * s], a[4 * s + 1], a[4 * s + 2], a[4 * s + 3], db + (2 * J - s) * 16);
      if (k < 6) { lda(k + 2); lda(13 - k); }
      if (k == 0) conv_final(rb, yb, u0, dd, i > 0);
      if (k == 1) {
        conv_final(rb + 2048, yb + 2048, u1, dd, i > 0);
        __syncwarp();
        if (lane == 0 && i > 0) mbar_arrive(sb + SM_BAR + (B_EV + c.wg) * 8);
      }
      if (k == 6) {
        const uint32_t ub = base + 256 + 16 + (c.tid >> 1) * 32 + ((c.tid & 1) ^ 1) * 4352;
        u0 = lds128(ub); u1 = lds128(ub + 2048);
        dd = __bfloat16_as_ushort(p.ssd[ch]) * 0x10001u;
      }
    }
    wg_commit();
    FTC(4);
    g = conv_next(g, spare);
    ch += chstep;
    rb = base + c.tid * 16;
    if (i + 1 < ntask) c.wait_full(g);
    wg_wait<0>();
#pragma unroll
    for (int J = 0; J < 8; J++) reg_fence(acc[J]);
    reg_fence(a);
    bar_sync(3 + c.wg, 128);
    FTC(5);
    const int tw = (lane & 3) + w;
    const uint32_t xb = base + w * 4096 + tw * 32 + (lane >> 2) * 4;
#pragma unroll
    for (int j = 0; j < 32; j++) {
      float v0 = acc[j >> 2][(j & 3) * 4], v1 = acc[j >> 2][(j & 3) * 4 + 1];
      if (j > 0) { v0 += acc[(j - 1) >> 2][((j - 1) & 3) * 4 + 2]; v1 += acc[(j - 1) >> 2][((j - 1) & 3) * 4 + 3]; }
      uint32_t v = pack_bf16(v0, v1), ad = xb + j * 128;
      if (j == 31 && tw >= 4) { v = 0; ad -= 4096; }
      asm volatile("st.shared.b32 [%0], %1;" ::"r"(ad), "r"(v) : "memory");
    }
    c.wait_stage_free();
    bar_sync(3 + c.wg, 128);
    FTC(6);
  }
  conv_final(rb, yb, u0, dd, true);
  conv_final(rb + 2048, yb + 2048, u1, dd, true);
  c.staged(0);
}

__global__ void __cluster_dims__(2, 1, 1) __launch_bounds__(NTHREADS, 1) mega_kernel(const __grid_constant__ Params p) {
  extern __shared__ __align__(1024) uint8_t smem_raw[];
  const uint32_t sb = smem_u32(smem_raw);
  const int wgi = __shfl_sync(0xffffffffu, threadIdx.x >> 7, 0);
  const int warp = __shfl_sync(0xffffffffu, threadIdx.x >> 5, 0);
  const uint32_t rank = blockIdx.x & 1;
  int grp, idx;
  {
    uint32_t smid; asm volatile("mov.u32 %0, %smid;" : "=r"(smid));
    const int tp = smid >> 1;
    if (tp < 32) { grp = tp & 7; idx = tp >> 3; }
    else if (tp < 60) { grp = 1 + (tp - 32) % 7; idx = 4 + (tp - 32) / 7; }
    else if (tp < 62) { grp = 8; idx = tp - 60; }
    else { grp = 0; idx = tp - 58; }
  }
  const int lb = (grp * 8 + idx) * 2 + rank;
  const bool spare = grp == 8;
  const int cn = spare ? CN_SPARE : CN_MAIN, cch = spare ? lb - NMAIN : 4 * CN_SPARE + CN_MAIN * lb, cstep = spare ? 4 : 1;

  if (threadIdx.x == 64) { prefetch_tm(&p.c); prefetch_tm(rank ? &p.wuv : &p.wuk); }
  if (threadIdx.x <= B_DONE) {
    const int i = threadIdx.x;
    mbar_init(sb + SM_BAR + i * 8, i == B_DONE ? 11 : i < NGR || i >= 2 * NGR + 4 ? 1 : 4);
    asm volatile("fence.mbarrier_init.release.cluster;" ::: "memory");
  }
  if (START_PF && wgi && !spare) {
    const int j = threadIdx.x & 127;
#pragma unroll
    for (int kb = 0; kb < START_PF; kb++)
      asm volatile("prefetch.global.L2 [%0];" ::"l"(wgi == 1 ? p.cp + (size_t)((2 * idx + rank) * 128 + j) * DC + kb * 64
                                                             : (rank ? p.wuvp : p.wukp) + (size_t)(kb * 64 + (j >> 1)) * (NH * HD) + 2 * grp * HD + (j & 1) * 64));
  }
  cluster_arrive();
  cluster_wait();
  TS(0);

  if (wgi == 0) {
    asm volatile("setmaxnreg.dec.sync.aligned.u32 40;");
    const int lane = threadIdx.x & 31;
    cluster_arrive();
    if (warp == 3) {
      if (!spare) {
        const int s0 = lb * 16;
#pragma unroll 1
        for (int cg = 0; cg < 16; cg++) {
          __nanosleep(PRE_SLEEP);
          const int ch = cg * 64 + 2 * lane;
          const uint32_t* kp = reinterpret_cast<const uint32_t*>(p.ak + (size_t)s0 * DM + ch);
          const uint32_t* vp = reinterpret_cast<const uint32_t*>(p.av + (size_t)s0 * DM + ch);
          const uint4 sw = __ldg(reinterpret_cast<const uint4*>(p.shk + ch * 4));
          uint32_t k3 = 0, k2 = 0, k1 = 0, k0 = 0, up = 0;
          if (lb > 0) { k3 = ldg_stream(kp - 4 * 512); k2 = ldg_stream(kp - 3 * 512); k1 = ldg_stream(kp - 2 * 512); k0 = ldg_stream(kp - 512); up = ldg_stream(vp - 512); }
          const uint32_t w0 = __byte_perm(sw.x, sw.z, 0x5410), w1 = __byte_perm(sw.x, sw.z, 0x7632);
          const uint32_t w2 = __byte_perm(sw.y, sw.w, 0x5410), w3 = __byte_perm(sw.y, sw.w, 0x7632);
          up = hmul2(hfma2(k0, w0, hfma2(k1, w1, hfma2(k2, w2, hmul2(k3, w3)))), up);
#pragma unroll 1
          for (int hb = 0; hb < 2; hb++) {
            uint32_t kk[8], u[8];
#pragma unroll
            for (int r = 0; r < 8; r++) { kk[r] = ldg_stream(kp + r * 512); u[r] = ldg_stream(vp + r * 512); }
#pragma unroll
            for (int r = 0; r < 8; r++) {
              k3 = k2; k2 = k1; k1 = k0; k0 = kk[r];
              u[r] = hmul2(hfma2(k0, w0, hfma2(k1, w1, hfma2(k2, w2, hmul2(k3, w3)))), u[r]);
            }
            if (lane == 0) asm volatile("cp.async.bulk.wait_group.read 0;" ::: "memory");
            __syncwarp();
            const uint32_t dst = sb + SM_UST + lane * 32 + ((lane & 4) << 2);
#pragma unroll
            for (int cc = 0; cc < 2; cc++) {
              const uint32_t sel = cc ? 0x7632 : 0x5410;
              asm volatile("st.shared.v4.b32 [%0], {%1,%2,%3,%4};" ::"r"(dst + cc * 1024), "r"(__byte_perm(u[6], u[5], sel)), "r"(__byte_perm(u[4], u[3], sel)),
                           "r"(__byte_perm(u[2], u[1], sel)), "r"(__byte_perm(u[0], up, sel)) : "memory");
              asm volatile("st.shared.v4.b32 [%0], {%1,%2,%3,%4};" ::"r"((dst ^ 16) + cc * 1024), "r"(__byte_perm(u[7], u[6], sel)), "r"(__byte_perm(u[5], u[4], sel)),
                           "r"(__byte_perm(u[3], u[2], sel)), "r"(__byte_perm(u[1], u[0], sel)) : "memory");
            }
            fence_async_smem();
            __syncwarp();
            if (lane == 0) {
              asm volatile("cp.async.bulk.tensor.3d.global.shared::cta.bulk_group [%0, {%2, %3, %4}], [%1];\ncp.async.bulk.commit_group;"
                           ::"l"(&p.w), "r"(sb + SM_UST), "r"(128 + lb * 16 + (hb ^ 1) * 2176), "r"(cg * 32), "r"(0) : "memory");
            }
            up = u[7];
            kp += 8 * 512; vp += 8 * 512;
          }
          if ((cg & (cg + 1)) == 0 && lane == 0) {
            asm volatile("cp.async.bulk.wait_group 0;" ::: "memory");
            fence_release();
            flag_add(FLAG(F_U + 32 - __clz(cg)));
          }
          TSW(10 + cg);
        }
      }
      if (lane == 0) {
        unsigned long long t0, t1;
        asm volatile("mov.u64 %0, %globaltimer;" : "=l"(t0));
        while (!mbar_try(sb + SM_BAR + B_DONE * 8, 0)) {
          asm volatile("mov.u64 %0, %globaltimer;" : "=l"(t1));
          if (t1 - t0 > 2000000000ull) __trap();
        }
      }
    } else if (warp != 0) {
      const int w = warp - 1, ne = 12 + (cn + 1 - w) / 2;
      uint32_t p0 = 0;
      int cg = 4 + w, ch = cch + w * cstep;
#pragma unroll 1
      for (int e = spare ? 12 : 0; e < ne; e++) {
        const int rnd = e >= 6, k = e - 6 * rnd, rt = k == 4 ? idx : 15 - idx;
        uint8_t* dst = k < 4 ? g_kv + (size_t)(((k & 1) * 16 + 2 * grp + (k >> 1)) * 16 + 2 * idx + rank) * 32768 + w * 8192
                     : k < 6 ? g_cimg + (size_t)(rt * 32 + 16 * rnd + 2 * grp + rank) * 32768 + w * 8192
                             : reinterpret_cast<uint8_t*>(g_yT + (size_t)ch * SEQ);
        const uint32_t src = sb + w * 8192 + (k == 4 ? 2 * GR : 0);
        if (e == 6) flag_wait(FLAG(F_AD + grp), 32);
        mbar_wait1(sb + SM_BAR + (B_EV + (k == 4 ? 2 : 0) + w) * 8, k == 4 ? rnd : p0);
        if (k != 4) p0 ^= 1;
        if (lane < 4 && k >= 6 && (!spare || e < ne - 6)) mbar_arrive_cluster(sb + SM_BAR + (B_EMPTY + cg) * 8, lane & 1);
        fence_async_smem();
        if (elect()) {
#pragma unroll 1
          for (int i = 0; i < (k >= 6 ? 1 : 8); i++) {
            const uint32_t o = (i >> 2) * 16384 + (i & 3) * 2048;
            asm volatile("cp.async.bulk.global.shared::cta.bulk_group [%0], [%1], %2;" ::"l"(dst + o), "r"(src + o), "r"(k >= 6 ? 4096 : 2048) : "memory");
            asm volatile("cp.async.bulk.commit_group;\ncp.async.bulk.wait_group.read %0;" ::"n"(ST_OUT) : "memory");
          }
          asm volatile("cp.async.bulk.wait_group 0;" ::: "memory");
          if (k != 4) mbar_arrive(sb + SM_BAR + (B_EV + 4 + w) * 8);
        }
        __syncwarp();
        if (lane < 4 && (k == 4 || (e == ne - 1 && !spare)))
          mbar_arrive_cluster(sb + SM_BAR + (B_EMPTY + (k == 4 ? 2 : 0) + (lane >> 1)) * 8, lane & 1);
        if (k >= 3) {
          fence_release();
          if (lane == 0 || (lane == 1 && e == 5))
            flag_add(FLAG(lane ? F_AD + grp : k == 3 ? F_KV + rnd * 8 + grp : k < 6 ? F_CTX + rt * 2 + rnd : F_Y + (ch >> 7)));
        }
        if (k >= 6) { cg = conv_next(cg, spare); ch += 2 * cstep; }
      }
      if (lane == 0) mbar_arrive(sb + SM_BAR + B_DONE * 8);
    } else {
      uint32_t pe = 0x3FFC;
      auto acquire = [&](int g) { PWAIT(sb + SM_BAR + (B_EMPTY + g) * 8, (pe >> g) & 1); pe ^= 1u << g; };
#pragma unroll 1
      for (int rnd = 0; rnd < (spare ? 0 : 2); rnd++) {
        const int hp = 16 * rnd + 2 * grp, head = hp + rank;
#pragma unroll 1
        for (int kk = 0; kk < 32; kk++) {
          const int g0 = 2 + 3 * (kk & 3);
          acquire(g0);
          if (kk < 4) { acquire(g0 + 1); acquire(g0 + 2); } else pe ^= 6u << g0;
          if (elect()) {
            const uint32_t fb = sb + SM_BAR + (B_FULL + g0) * 8;
            mbar_expect_tx(fb, 3 * GR);
            if (kk < 16) {
              tma2d(sb + g0 * GR, &p.c, (kk & 7) * 64, (2 * idx + rank) * 128, fb, EV_NORMAL);
              tma3d_mc(sb + (g0 + 1 + rank) * GR, rank ? &p.wuv : &p.wuk, 0, (kk & 7) * 64, (hp + (kk >> 3)) * 2, fb, POL_W);
            } else {
              tma2d_mc(sb + (g0 + rank) * GR, &p.x, (kk - 16) * 64, (rank ? 15 - idx : idx) * 128, fb, EV_NORMAL);
              tma3d(sb + (g0 + 2) * GR, &p.wq, 0, (kk - 16) * 64, head * 2, fb, POL_W);
            }
            if (kk == 3) { prefetch_tm(&p.x); prefetch_tm(&p.wq); }
          }
        }
        flag_wait(FLAG(F_KV + rnd * 8 + grp), 32);
        fence_async_all();
        acquire(2); pe ^= 8u;
        int g0 = 4;
#pragma unroll 1
        for (int f = 0; f < 34; f++) {
          const bool isk = (f == 0) || ((f & 1) && f < 33);
          const int it = (f == 0) ? 0 : (f == 33) ? 16 : isk ? (f + 1) >> 1 : (f >> 1) - 1;
          const int blk = it == 0 ? idx : it <= idx ? it - 1 : it < 16 ? 15 - it : 15 - idx;
          acquire(g0);
          if (f < 8) acquire(g0 + 1); else pe ^= 2u << g0;
          if (elect()) {
            const uint32_t fb = sb + SM_BAR + (B_FULL + g0) * 8;
            mbar_expect_tx(fb, 2 * GR);
            bulk_g2s(sb + g0 * GR, g_kv + (size_t)(((isk ? 0 : 16) + (head & 15)) * 16 + blk) * 32768, 2 * GR, fb, POL_KV);
          }
          g0 = f == 2 ? 12 : g0 == 12 ? 4 : g0 + 2;
        }
      }
      if (spare) {
#pragma unroll 1
        for (int i = -1, g = 1; i < 64; i++) {
          if (i >= 0) acquire(g);
          if (elect()) {
            const uint32_t fb = sb + SM_BAR + (B_FULL + g) * 8;
            mbar_expect_tx(fb, i < 0 ? 2048 : GR);
            if (i < 0) bulk_g2s(sb + GR, p.gate_w, 2048, fb, EV_NORMAL);
            else tma2d(sb + g * GR, &p.x, (i & 15) * 64, (lb - NMAIN) * 512 + (i >> 4) * 128, fb, EV_NORMAL);
          }
          g = g == NGR - 1 ? 2 : g + 1;
        }
      }
      auto conv_fill = [&](int g, int ch) {
        acquire(g);
        if (elect()) {
          const uint32_t fb = sb + SM_BAR + (B_FULL + g) * 8;
          mbar_expect_tx(fb, WBYTES + 4096);
          bulk_g2s(sb + g * GR, g_w + (size_t)ch * WSTRIDE, WBYTES, fb, POL_C);
          bulk_g2s(sb + g * GR + WBYTES, p.ssk + (size_t)ch * SEQ, 4096, fb, POL_C);
        }
      };
#pragma unroll 1
      for (int i = 0, g = 4; i < cn; i++) {
        if ((i & 15) == 0) { flag_wait(FLAG(F_U + (spare ? 32 - __clz(i >> 4) : 4)), NMAIN); fence_async_all(); }
        conv_fill(g + (i & 1), cch + i * cstep);
        if (i & 1) g = conv_next(g, spare);
      }
      if (!spare) {
        const int rt = 2 * grp + rank, ct = idx;
        int g0 = P3G;
#pragma unroll 1
        for (int kb = 0; kb < 66; kb++) {
          if (kb == 0 || kb == 32 || kb >= 64) {
            flag_wait(FLAG(kb < 64 ? F_CTX + rt * 2 + (kb >> 5) : kb == 64 ? F_GATE : F_Y + ct), kb <= 64 ? 32 : 128);
            fence_async_all();
          }
          acquire(g0);
          if (kb < 11) acquire(g0 + 1);
          if (elect()) {
            const uint32_t fb = sb + SM_BAR + (B_FULL + g0) * 8;
            mbar_expect_tx(fb, kb == 64 ? 2 * GR + 512 : 2 * GR);
            if (kb <= 64) bulk_g2s(kb < 64 ? sb + g0 * GR : sb + SM_GATE, kb < 64 ? (const void*)(g_cimg + (size_t)(rt * 64 + kb) * GR) : (const void*)(g_gate + rt * 128), kb < 64 ? GR : 512, fb, POL_CTX);
            if (kb < 64) {
              tma2d_mc(sb + (g0 + 1) * GR + rank * 8192, &p.wo, ct * 128 + rank * 64, kb * 64, fb, POL_WO);
              if (kb == 40) { prefetch_tm(&p.y); prefetch_tm(&p.out); }
            } else {
              const CUtensorMap* tm = kb == 64 ? &p.x : &p.y;
              const int c0 = (kb == 64 ? ct : rt) * 128, c1 = (kb == 64 ? rt : ct) * 128;
              tma2d(sb + g0 * GR, tm, c0, c1, fb, EV_NORMAL);
              tma2d(sb + (g0 + 1) * GR, tm, c0 + 64, c1, fb, EV_NORMAL);
            }
          }
          g0 = g0 == 12 ? (kb == 3 ? 2 : 0) : g0 + 2;
        }
        unsigned n = 0;
        if (lane == 0) n = atomicAdd(FLAG(F_EXIT), 1);
        if (__shfl_sync(0xffffffffu, n, 0) == NMAIN - 1) { *FLAG(lane) = 0; *FLAG(lane + 32) = 0; *FLAG(lane + 64) = 0; }
      }
      if (lane == 0) mbar_arrive(sb + SM_BAR + B_DONE * 8);
    }
    __syncwarp();
    cluster_wait();
  } else {
    asm volatile("setmaxnreg.inc.sync.aligned.u32 232;");
    Cons c;
    c.sb = sb; c.pf = 0; c.wg = wgi - 1; c.tid = threadIdx.x & 127;
    const int lane = threadIdx.x & 31, t = lane & 3;
    const int row = c.wg * 64 + (warp & 3) * 16 + (lane >> 2);
    const uint32_t dkk = desc_k(sb), dk0 = dkk + c.wg * 512, dm0 = desc_mn<8192>(sb), dv0 = desc_mn<16384>(sb);
    if (c.wg == 1) bar_arrive(1, 256);
    c.pfree = 1;
    asm("mapa.shared::cluster.u32 %0, %1, %2;" : "=r"(c.relb) : "r"(sb + SM_BAR + (B_EMPTY + (c.tid >> 1)) * 8), "r"(c.tid & 1));
    c.zero = p.zero;
    const uint32_t stg = sb + (c.wg * 64 + (warp & 3) * 16 + ((lane >> 3) & 1) * 8 + (lane & 7)) * 128 + (((lane >> 4) ^ (lane & 7)) << 4);

    if (spare) {
      c.wait_full(1);
      int g = 2;
#pragma unroll 1
      for (int r = 0; r < 4; r++) {
        float d[4] = {0.f, 0.f, 0.f, 0.f};
#pragma unroll 1
        for (int kb = 0; kb < 16; kb++) {
          c.wait_full(g);
          wg_fence();
#pragma unroll
          for (int k = 0; k < 4; k++) mma_ss_n8(d, dk0 + g * DG + k * 2, dkk + DG + kb * 8 + k * 2);
          wg_commit();
          wg_wait<0>();
          c.release(g, 1);
          g = g == NGR - 1 ? 2 : g + 1;
        }
        reg_fence(d);
        if (t == 0) {
          float* gp = g_gate + (lb - NMAIN) * 512 + r * 128 + row;
          gp[0] = rcp(1.f + ex2(-1.4426950408889634f * d[0])); gp[8] = rcp(1.f + ex2(-1.4426950408889634f * d[2]));
        }
      }
      fence_release();
      __syncwarp();
      if (lane == 0) flag_add(FLAG(F_GATE));
      TS(1);
    }
    uint32_t pv[32];
#pragma unroll
    for (int i = 0; i < 32; i++) pv[i] = 0;
#pragma unroll 1
    for (int rnd = 0; rnd < (spare ? 0 : 2); rnd++) {
      float O[64];
      FTM(rnd * 8);
      c.wait_full(2);
      FTM(rnd * 8 + 1);
#pragma unroll 1
      for (int tile = c.zero; tile < 2; tile++) {
        float acc[128];
        {
          FTG(tile * 32); FTG(tile * 32 + 1);
          const uint32_t a = dk0 + 2 * DG, b = dm0 + 3 * DG;
          c.turn_begin();
          FTG(tile * 32 + 2);
          wg_fence();
          mma_ss_n256_init<1>(acc, a, b);
#pragma unroll
          for (int k = 1; k < 4; k++) mma_ss_n256<1>(acc, a + k * 2, b + k * 128);
          wg_commit();
          FTG(tile * 32 + 3);
        }
#pragma unroll 1
        for (int kb = 1; kb < 8; kb++) {
          const int g0 = 2 + 3 * (kb & 3);
          const uint32_t a = dk0 + g0 * DG, b = dm0 + (g0 + 1) * DG;
          const bool second = kb == 1 || kb == 7;
          FTG(tile * 32 + kb * 4);
          if (!second) { wg_wait<0>(); c.release(2 + 3 * ((kb - 1) & 3), 3); }
          FTG(tile * 32 + kb * 4 + 1);
          c.wait_full(g0);
          if (!second) c.turn_begin();
          FTG(tile * 32 + kb * 4 + 2);
          wg_fence();
#pragma unroll
          for (int k = 0; k < 4; k++) mma_ss_n256<1>(acc, a + k * 2, b + k * 128);
          wg_commit();
          if (kb != 6) c.turn_end();
          if (second) { wg_wait<1>(); c.release(2 + 3 * ((kb - 1) & 3), 3); }
          FTG(tile * 32 + kb * 4 + 3);
          if (tile == 1 && kb == 3) { c.wait_stage_free(); stsm_frag<0, 4>(pv, stg); }
          if (tile == 1 && kb == 4) { stsm_frag<4, 8>(pv, stg); c.staged(0); }
        }
        c.wait_stage_free();
        const bool nxt = c.try_full(2);
        wg_wait<0>();
        reg_fence(acc);
        c.release(11, 3);
        pack_frag_scaled(acc, pv, SM_C, SM_C);
        stsm_frag(pv, stg);
        c.staged(0);
        pack_frag<64>(acc, pv);
        pin32(pv, sb);
        if (!nxt) mbar_wait(sb + SM_BAR + (B_FULL + 2) * 8, (c.pf >> 2) & 1);
        c.pf ^= 4;
      }
      TS(1 + rnd * 3);
      FTM(rnd * 8 + 2);
      {
        float qa[64];
        float (&qb)[64] = O;
        {
          FTG(64); FTG(65);
          const uint32_t a = dk0 + 2 * DG, b = dm0 + 4 * DG;
          c.turn_begin();
          FTG(66);
          wg_fence();
          mma_ss_n128_init<1>(qa, a, b);
          mma_ss_n128_init<1>(qb, a + DG, b);
#pragma unroll
          for (int k = 1; k < 4; k++) {
            mma_ss_n128<1>(qa, a + k * 2, b + k * 128);
            mma_ss_n128<1>(qb, a + DG + k * 2, b + k * 128);
          }
          wg_commit();
          FTG(67);
        }
#pragma unroll 1
        for (int kb = 1; kb < 16; kb++) {
          const int g0 = 2 + 3 * (kb & 3);
          const uint32_t a = dk0 + g0 * DG, b = dm0 + (g0 + 2) * DG;
          const bool second = kb == 1 || kb == 15;
          FTG(64 + kb * 4);
          if (!second) { wg_wait<0>(); c.release(2 + 3 * ((kb - 1) & 3), 3); }
          FTG(65 + kb * 4);
          c.wait_full(g0);
          if (!second) c.turn_begin();
          FTG(66 + kb * 4);
          wg_fence();
#pragma unroll
          for (int k = 0; k < 4; k++) {
            mma_ss_n128<1>(qa, a + k * 2, b + k * 128);
            mma_ss_n128<1>(qb, a + DG + k * 2, b + k * 128);
          }
          wg_commit();
          if (kb != 14) c.turn_end();
          if (second) { wg_wait<1>(); c.release(2 + 3 * ((kb - 1) & 3), 3); }
          FTG(67 + kb * 4);
          if (kb == QFLUSH) { c.wait_stage_free(); stsm_frag<0, 4>(pv, stg); }
          if (kb == QFLUSH + 1) { stsm_frag<4, 8>(pv, stg); c.staged(0); }
        }
        c.wait_stage_free();
        mbar_wait(sb + SM_BAR + (B_EMPTY + 2) * 8, rnd ^ 1);
        c.wait_full(4);
        FTM(rnd * 8 + 3);
        wg_wait<0>();
        reg_fence(qa); reg_fence(qb);
        c.release(11, 3);
        pack_frag<0>(qa, pv);
        stsm_frag(pv, stg + 2 * GR);
        fence_async_smem();
      }
      TS(2 + rnd * 3);
      FTM(rnd * 8 + 4);
      {
        const int nA = idx + 1;
        uint32_t (&P)[32] = pv;
        SoftState z;
        const int dmask = (row & 63) - 2 * t;
        z.m0 = z.m1 = z.l0 = z.l1 = 0.f; z.shifted = c.zero;
#pragma unroll
        for (int i = 0; i < ROT; i++) z.t[i] = 0.f;
#pragma unroll 1
        for (int seg = c.zero;; seg++) {
        if (c.wg == 0) attn_half(c, O, P, z, dk0, dkk, dv0, dmask, seg, stg);
        if (seg) break;
        FTM(rnd * 8 + 5);
        int gk = c.wg ? 4 : 6, gv = c.wg ? 4 : 8;
#pragma unroll 1
        for (int it = 1 - c.wg; it < 16 + c.wg; it++) {
          float S[64];
          FTA(it * 7 + 0);
          c.turn_begin();
          FTA(it * 7 + 2);
          wg_fence();
          issue_qk(S, dk0 + (it < nA ? 2 * DG : 0), dkk + gk * DG);
          wg_commit();
          if (it) {
            issue_pv<0>(O, P, dv0 + gv * DG, it != nA + 1 && it != 1, true);
            issue_pv<1>(O, P, dv0 + gv * DG, 1, HALFPV ? it + c.wg > 1 : true);
            c.turn_end();
          } else stage_q2(c, O, P, stg);
          FTA(it * 7 + 3);
          wg_wait<4>();
          reg_fence(S);
          FTA(it * 7 + 4);
          c.release(gk, 2);
          const float lo0 = z.l0, lo1 = z.l1;
          const bool first = it == nA || it == 0;
          if (it == nA) { z.m0 = z.m1 = z.l0 = z.l1 = 0.f; z.shifted = 0; }
          float s0, s1, d0 = z.m0, d1 = z.m1;
          const int gvo = gv;
          gk = it == 1 ? 12 : gv == 12 ? 4 : gv + 2;
          gv = it == 16 ? gk : gk == 12 ? 4 : gk + 2;
#pragma unroll 1
          for (int pass = 0;; pass++) {
            if (z.shifted || (it & 15) == 0) {
              if ((it & 15) == 0) mask_diag(S, dmask);
              if (z.shifted) shift_scores(S, d0, d1);
            }
            s0 = 0.f; s1 = 0.f;
            wg_wait<3>(); reg_fence_part<0, 8>(P);
            exp_pairs<0, 8>(S, P, z, s0, s1, c.sb);
            pin(s1, sb); wg_wait<2>(); reg_fence_part<8, 8>(P);
            exp_pairs<8, 16>(S, P, z, s0, s1, c.sb);
            pin(s1, sb); wg_wait<1>(); reg_fence_part<16, 8>(P);
            exp_pairs<16, 24>(S, P, z, s0, s1, c.sb);
            pin(s1, sb); wg_wait<0>(); reg_fence_part<24, 8>(P); reg_fence(O);
            c.release(gvo, pass || !it ? 0 : 2);
            const bool ok = c.try_full(gk) & c.try_full(gv);
            exp_pairs<24, 32>(S, P, z, s0, s1, c.sb);
            FTA(it * 7 + 5);
            if (!__any_sync(0xffffffffu, soft_high(s0, s1) || !ok || first) || pass) break;
            if (it == nA) {
              uint32_t pk[32];
              pack_frag_scaled(O, pk, rcp(quad_sum(lo0)), rcp(quad_sum(lo1)));
              stsm_frag(pk, stg + 2 * GR);
              c.staged(1);
            }
            mbar_wait(sb + SM_BAR + (B_FULL + gk) * 8, (c.pf >> gk) & 1);
            mbar_wait(sb + SM_BAR + (B_FULL + gv) * 8, (c.pf >> gv) & 1);
            if (!soft_unsafe(s0, s1, first)) break;
            soft_fix(S, O, z, first, d0, d1);
          }
          c.pf ^= (1u << gk) | (1u << gv);
          z.l0 += s0; z.l1 += s1;
          FTA(it * 7 + 6);
        }
        FTM(rnd * 8 + 6);
        }
        c.turn_begin();
        wg_fence();
        issue_pv<0>(O, P, dv0 + 12 * DG, 1, true);
        issue_pv<1>(O, P, dv0 + 12 * DG, 1, c.wg);
        c.turn_end();
        z.l0 = rcp(quad_sum(z.l0)); z.l1 = rcp(quad_sum(z.l1));
        wg_wait<0>();
        reg_fence(O); reg_fence(P);
        c.release(12, 2);
        pack_frag_scaled(O, P, z.l0, z.l1);
        stsm_frag(P, stg);
        c.staged(0);
        FTM(rnd * 8 + 7);
      }
      TS(3 + rnd * 3);
    }
    conv_tasks(c, p, (cn + 1 - c.wg) / 2, ((cn - 1) & 1) == c.wg, spare, cch + c.wg * cstep, 2 * cstep, dkk, warp & 3, lane);
    if (c.wg == 1) c.pf ^= 0x4;
    TS(7);
    if (!spare) {
      const int rt = 2 * grp + rank, ct = idx;
      float acc[64];
      int g0 = P3G + 2, pg = P3G;
      {
        FTO(0);
        c.wait_full(P3G);
        FTO(1);
        const uint32_t a = dk0 + P3G * DG, b = dm0 + (P3G + 1) * DG;
        wg_fence();
        mma_ss_n128_init<1>(acc, a, b);
#pragma unroll
        for (int k = 1; k < 4; k++) mma_ss_n128<1>(acc, a + k * 2, b + k * 128);
        wg_commit();
      }
#pragma unroll 1
      for (int kb = 1; kb < 64; kb++) {
        FTO(kb * 2);
        c.wait_full(g0);
        FTO(kb * 2 + 1);
        const uint32_t a = dk0 + g0 * DG, b = dm0 + (g0 + 1) * DG;
        wg_fence();
#pragma unroll
        for (int k = 0; k < 4; k++) mma_ss_n128<1>(acc, a + k * 2, b + k * 128);
        wg_commit();
        wg_wait<1>();
        c.release(pg, kb <= 59 ? 2 : 0);
        if (kb == 40) FTDUMP();
        pg = g0;
        g0 = g0 == 12 ? (kb == 3 ? 2 : 0) : g0 + 2;
      }
      cluster_arrive();
      c.wait_full(P3X);
      c.wait_full(P3Y);
      const float g0f = __uint_as_float(lds32(sb + SM_GATE + row * 4)), g1f = __uint_as_float(lds32(sb + SM_GATE + row * 4 + 32));
      const uint32_t gp0 = pack_bf16(g0f, g0f), gp1 = pack_bf16(g1f, g1f);
      const float h0 = 1.f - g0f, h1 = 1.f - g1f;
      const int w = warp & 3;
      const uint32_t xa = stg + P3X * GR;
      const uint32_t ya = sb + P3Y * GR + c.wg * 16384 + ((lane >> 4) * 8 + (lane & 7)) * 128 + (((2 * w + ((lane >> 3) & 1)) ^ (lane & 7)) << 4);
      uint32_t xy[32];
#pragma unroll
      for (int jj = 0; jj < 8; jj++) {
        uint32_t x[4], y[4];
        asm volatile("ldmatrix.sync.aligned.m8n8.x4.shared.b16 {%0,%1,%2,%3}, [%4];" : "=r"(x[0]), "=r"(x[1]), "=r"(x[2]), "=r"(x[3]) : "r"((xa ^ ((jj & 3) << 5)) + (jj >> 2) * 16384) : "memory");
        asm volatile("ldmatrix.sync.aligned.m8n8.x4.trans.shared.b16 {%0,%1,%2,%3}, [%4];" : "=r"(y[0]), "=r"(y[1]), "=r"(y[2]), "=r"(y[3]) : "r"(ya + jj * 2048) : "memory");
#pragma unroll
        for (int i = 0; i < 4; i++) xy[4 * jj + i] = hmul2(x[i], y[i]);
      }
      wg_wait<0>();
      reg_fence(acc);
      TS(8);
#pragma unroll
      for (int i = 0; i < 32; i++) {
        const float h = (i & 1) ? h1 : h0;
        xy[i] = hfma2((i & 1) ? gp1 : gp0, xy[i], pack_bf16(acc[2 * i] * h, acc[2 * i + 1] * h));
      }
      stsm_frag(xy, xa);
      fence_async_smem();
      __syncwarp();
      if (lane == 0) {
        const int r0 = c.wg * 64 + w * 16;
        tma2d_store(&p.out, sb + P3X * GR + r0 * 128, ct * 128, rt * 128 + r0);
        tma2d_store(&p.out, sb + (P3X + 1) * GR + r0 * 128, ct * 128 + 64, rt * 128 + r0);
        asm volatile("cp.async.bulk.commit_group;\ncp.async.bulk.wait_group.read 0;" ::: "memory");
      }
    } else { FTDUMP(); cluster_arrive(); }
    if (lane == 0) mbar_arrive(sb + SM_BAR + B_DONE * 8);
    __syncwarp();
    TS(9);
    cluster_wait();
  }
}

typedef CUresult (*EncFn)(CUtensorMap*, CUtensorMapDataType, cuuint32_t, void*, const cuuint64_t*, const cuuint64_t*, const cuuint32_t*,
                          const cuuint32_t*, CUtensorMapInterleave, CUtensorMapSwizzle, CUtensorMapL2promotion, CUtensorMapFloatOOBfill);

void enc2d(EncFn enc, CUtensorMap* tm, const void* base, uint64_t cols, uint64_t rows, uint32_t bc, uint32_t br) {
  cuuint64_t dims[2] = {cols, rows}; cuuint64_t strides[1] = {cols * 2}; cuuint32_t box[2] = {bc, br}; cuuint32_t es[2] = {1, 1};
  enc(tm, CU_TENSOR_MAP_DATA_TYPE_BFLOAT16, 2, const_cast<void*>(base), dims, strides, box, es, CU_TENSOR_MAP_INTERLEAVE_NONE,
      CU_TENSOR_MAP_SWIZZLE_128B, CU_TENSOR_MAP_L2_PROMOTION_L2_256B, CU_TENSOR_MAP_FLOAT_OOB_FILL_NONE);
}
void enc3d(EncFn enc, CUtensorMap* tm, const void* base, uint64_t K, uint64_t N) {
  cuuint64_t dims[3] = {64, K, N / 64}; cuuint64_t strides[2] = {N * 2, 128}; cuuint32_t box[3] = {64, 64, 2}; cuuint32_t es[3] = {1, 1, 1};
  enc(tm, CU_TENSOR_MAP_DATA_TYPE_BFLOAT16, 3, const_cast<void*>(base), dims, strides, box, es, CU_TENSOR_MAP_INTERLEAVE_NONE,
      CU_TENSOR_MAP_SWIZZLE_128B, CU_TENSOR_MAP_L2_PROMOTION_L2_256B, CU_TENSOR_MAP_FLOAT_OOB_FILL_NONE);
}

}

extern "C" void kernel_launch(void* const* d_in, const int* in_sizes, int n_in, void* d_out, int out_size) {
  (void)in_sizes; (void)n_in; (void)out_size;
  typedef const __nv_bfloat16* BP;
  BP xq = (BP)d_in[0], ak = (BP)d_in[1], av = (BP)d_in[2], shk = (BP)d_in[3], ssk = (BP)d_in[4], ssd = (BP)d_in[5];
  BP ckv = (BP)d_in[7], wq = (BP)d_in[8], wuk = (BP)d_in[9], wuv = (BP)d_in[10], wo = (BP)d_in[11], gw = (BP)d_in[12];

  static EncFn enc = nullptr;
  if (!enc) {
    cudaDriverEntryPointQueryResult qr;
    cudaGetDriverEntryPoint("cuTensorMapEncodeTiled", (void**)&enc, cudaEnableDefault, &qr);
    cudaFuncSetAttribute(mega_kernel, cudaFuncAttributeMaxDynamicSharedMemorySize, SMEM_BYTES);
  }
  Params p;
  void* yT = nullptr;
  cudaGetSymbolAddress(&yT, g_yT);
  enc2d(enc, &p.x, xq, DM, SEQ, 64, 128);
  enc2d(enc, &p.c, ckv, DC, SEQ, 64, 128);
  enc3d(enc, &p.wq, wq, DM, NH * HD);
  enc3d(enc, &p.wuk, wuk, DC, NH * HD);
  enc3d(enc, &p.wuv, wuv, DC, NH * HD);
  enc2d(enc, &p.wo, wo, DM, NH * HD, 64, 64);
  enc2d(enc, &p.y, yT, SEQ, DM, 64, 128);
  enc2d(enc, &p.out, d_out, DM, SEQ, 64, 16);
  {
    void* wp = nullptr;
    cudaGetSymbolAddress(&wp, g_w);
    cuuint64_t dims[3] = {WSTRIDE / 2, DM / 2, 2}; cuuint64_t strides[2] = {2 * WSTRIDE, WSTRIDE}; cuuint32_t box[3] = {16, 32, 2}; cuuint32_t es[3] = {1, 1, 1};
    enc(&p.w, CU_TENSOR_MAP_DATA_TYPE_BFLOAT16, 3, wp, dims, strides, box, es, CU_TENSOR_MAP_INTERLEAVE_NONE,
        CU_TENSOR_MAP_SWIZZLE_32B, CU_TENSOR_MAP_L2_PROMOTION_NONE, CU_TENSOR_MAP_FLOAT_OOB_FILL_NONE);
  }
  p.zero = 0;
  p.cp = ckv; p.wukp = wuk; p.wuvp = wuv;
  p.xp = xq; p.gate_w = gw; p.ak = ak; p.av = av; p.shk = shk; p.ssk = ssk; p.ssd = ssd;

  mega_kernel<<<132, NTHREADS, SMEM_BYTES>>>(p);
}
```

```cpp
#include <cuda_runtime.h>
#include <cuda.h>
#include <cuda_bf16.h>
#include <stdint.h>

namespace {

constexpr int SEQ = 2048, DM = 1024, DC = 512, NH = 32, HD = 128;
constexpr int GR = 16384;
constexpr int NGR = 14;
constexpr int SM_BAR = NGR * GR;
constexpr int SM_GATE = SM_BAR + 512;
constexpr int SM_UST = SM_GATE + 512;
constexpr int SMEM_BYTES = SM_UST + 2048;
constexpr int NTHREADS = 384;
#define SM_LIMIT 1.0995116e12f
#define SM_LOW 9.094947e-13f
constexpr int CN_MAIN = 5, CN_SPARE = 96;
constexpr int P3G = 6, P3X = 10, P3Y = 12;
constexpr int NMAIN = 128;

constexpr int B_FULL = 0, B_EMPTY = 14, B_EV = 28, B_DONE = 34;

__device__ __align__(1024) uint8_t g_kv[2 * 16 * 16 * 32768];
__device__ __align__(1024) uint8_t g_cimg[16 * NH * 32768];
__device__ __align__(1024) __nv_bfloat16 g_yT[DM * SEQ];
__device__ __align__(1024) float g_gate[SEQ];
constexpr int WSTRIDE = 8832, WBYTES = 8736;
__device__ __align__(1024) uint8_t g_w[DM * WSTRIDE];
__device__ unsigned g_flags[128 * 8];
constexpr int F_KV = 0, F_CTX = 16, F_U = 48, F_AD = 56, F_Y = 64, F_GATE = 72, F_EXIT = 73;
#define FLAG(i) (&g_flags[(i) * 8])

#define TS(slot)
#define TSW(slot)
#define FTX(i, off)
#define FTDUMP()

#define ST_OUT 0
#define QFLUSH 4
#define POL_W EV_NORMAL
#define POL_WO EV_FIRST
#define POL_KV EV_NORMAL
#define POL_C EV_FIRST
#define POL_CTX EV_FIRST
#define HALFPV 0
#define PWAIT mbar_wait1
#define PRE_SLEEP 1500
#define EXPV 1
#define START_PF 1
#define SUMV 0
#define ROT 8
#define EARLY_RCP 1
#define FINE_MODE 0
#define FINE_RND 1
#define FTA(i) do { if (FINE_MODE == 0) FTX(i, rnd ^ FINE_RND); } while (0)
#define FTG(i) do { if (FINE_MODE == 1) FTX(i, rnd ^ FINE_RND); } while (0)
#define FTM(i) do { if (FINE_MODE == 4) FTX(i, 0); } while (0)
#define FTC(k) do { if (FINE_MODE == 5) FTX((i & 7) * 8 + (k), (i >> 3) ^ FINE_RND); } while (0)
#define FTO(i) do { if (FINE_MODE == 2) FTX(i, 0); } while (0)

__device__ __forceinline__ uint32_t smem_u32(const void* p) { return (uint32_t)__cvta_generic_to_shared(p); }
__device__ __forceinline__ void mbar_init(uint32_t bar, int cnt) { asm volatile("mbarrier.init.shared::cta.b64 [%0], %1;" ::"r"(bar), "r"(cnt) : "memory"); }
__device__ __forceinline__ void mbar_expect_tx(uint32_t bar, uint32_t bytes) { asm volatile("mbarrier.arrive.expect_tx.shared::cta.b64 _, [%0], %1;" ::"r"(bar), "r"(bytes) : "memory"); }
__device__ __forceinline__ void mbar_arrive(uint32_t bar) { asm volatile("mbarrier.arrive.shared::cta.b64 _, [%0];" ::"r"(bar) : "memory"); }
__device__ __forceinline__ void mbar_arrive_cluster(uint32_t bar, uint32_t cta) {
  asm volatile("{\n.reg .b32 r;\nmapa.shared::cluster.u32 r, %0, %1;\nmbarrier.arrive.shared::cluster.b64 _, [r];\n}\n" ::"r"(bar), "r"(cta) : "memory");
}
__device__ __forceinline__ bool mbar_try(uint32_t bar, uint32_t parity) {
  uint32_t ok;
  asm volatile("{\n.reg .pred p;\nmbarrier.try_wait.parity.shared::cta.b64 p, [%1], %2, 20000;\nselp.u32 %0, 1, 0, p;\n}\n" : "=r"(ok) : "r"(bar), "r"(parity) : "memory");
  return ok;
}
__device__ __forceinline__ bool mbar_test(uint32_t bar, uint32_t parity) {
  uint32_t ok;
  asm volatile("{\n.reg .pred p;\nmbarrier.test_wait.parity.shared::cta.b64 p, [%1], %2;\nselp.u32 %0, 1, 0, p;\n}\n" : "=r"(ok) : "r"(bar), "r"(parity) : "memory");
  return ok;
}
__device__ __forceinline__ void mbar_wait(uint32_t bar, uint32_t parity) {
  asm volatile("{\n.reg .pred p;\nWAIT_LOOP:\nbar.warp.sync -1;\nmbarrier.try_wait.parity.shared::cta.b64 p, [%0], %1;\n@!p bra WAIT_LOOP;\n}\n" ::"r"(bar), "r"(parity) : "memory");
}
__device__ __forceinline__ void mbar_wait1(uint32_t bar, uint32_t parity) {
  asm volatile("{\n.reg .pred p;\nWAIT_LOOP:\nbar.warp.sync -1;\nmbarrier.try_wait.parity.shared::cta.b64 p, [%0], %1, 4000;\n@!p bra WAIT_LOOP;\n}\n" ::"r"(bar), "r"(parity) : "memory");
}
constexpr uint64_t EV_NORMAL = 0x1000000000000000ull, EV_FIRST = 0x12F0000000000000ull;
__device__ __forceinline__ uint32_t ldg_stream(const uint32_t* p) {
  uint32_t r; asm volatile("ld.global.nc.L1::no_allocate.L2::cache_hint.b32 %0, [%1], %2;" : "=r"(r) : "l"(p), "l"(EV_FIRST)); return r;
}
__device__ __forceinline__ void tma2d(uint32_t dst, const CUtensorMap* tm, int c0, int c1, uint32_t bar, uint64_t pol) {
  asm volatile("cp.async.bulk.tensor.2d.shared::cluster.global.mbarrier::complete_tx::bytes.L2::cache_hint [%0], [%1, {%3, %4}], [%2], %5;"
               ::"r"(dst), "l"(tm), "r"(bar), "r"(c0), "r"(c1), "l"(pol) : "memory");
}
__device__ __forceinline__ void tma2d_mc(uint32_t dst, const CUtensorMap* tm, int c0, int c1, uint32_t bar, uint64_t pol) {
  asm volatile("cp.async.bulk.tensor.2d.shared::cluster.global.mbarrier::complete_tx::bytes.multicast::cluster.L2::cache_hint [%0], [%1, {%3, %4}], [%2], %5, %6;"
               ::"r"(dst), "l"(tm), "r"(bar), "r"(c0), "r"(c1), "h"((uint16_t)3), "l"(pol) : "memory");
}
__device__ __forceinline__ void tma3d(uint32_t dst, const CUtensorMap* tm, int c0, int c1, int c2, uint32_t bar, uint64_t pol) {
  asm volatile("cp.async.bulk.tensor.3d.shared::cluster.global.mbarrier::complete_tx::bytes.L2::cache_hint [%0], [%1, {%3, %4, %5}], [%2], %6;"
               ::"r"(dst), "l"(tm), "r"(bar), "r"(c0), "r"(c1), "r"(c2), "l"(pol) : "memory");
}
__device__ __forceinline__ void tma3d_mc(uint32_t dst, const CUtensorMap* tm, int c0, int c1, int c2, uint32_t bar, uint64_t pol) {
  asm volatile("cp.async.bulk.tensor.3d.shared::cluster.global.mbarrier::complete_tx::bytes.multicast::cluster.L2::cache_hint [%0], [%1, {%3, %4, %5}], [%2], %6, %7;"
               ::"r"(dst), "l"(tm), "r"(bar), "r"(c0), "r"(c1), "r"(c2), "h"((uint16_t)3), "l"(pol) : "memory");
}
__device__ __forceinline__ void bulk_g2s(uint32_t dst, const void* src, uint32_t bytes, uint32_t bar, uint64_t pol) {
  asm volatile("cp.async.bulk.shared::cluster.global.mbarrier::complete_tx::bytes.L2::cache_hint [%0], [%1], %2, [%3], %4;"
               ::"r"(dst), "l"(src), "r"(bytes), "r"(bar), "l"(pol) : "memory");
}
__device__ __forceinline__ void tma2d_store(const CUtensorMap* tm, uint32_t src, int c0, int c1) {
  asm volatile("cp.async.bulk.tensor.2d.global.shared::cta.bulk_group [%0, {%2, %3}], [%1];" ::"l"(tm), "r"(src), "r"(c0), "r"(c1) : "memory");
}
__device__ __forceinline__ void prefetch_tm(const CUtensorMap* tm) { asm volatile("prefetch.tensormap [%0];" ::"l"(tm) : "memory"); }
__device__ __forceinline__ void wg_fence() { asm volatile("wgmma.fence.sync.aligned;" ::: "memory"); }
__device__ __forceinline__ void wg_commit() { asm volatile("wgmma.commit_group.sync.aligned;" ::: "memory"); }
template <int N> __device__ __forceinline__ void wg_wait() { asm volatile("wgmma.wait_group.sync.aligned %0;" ::"n"(N) : "memory"); }
__device__ __forceinline__ void bar_sync(int id, int n) { asm volatile("bar.sync %0, %1;" ::"r"(id), "r"(n) : "memory"); }
__device__ __forceinline__ void bar_arrive(int id, int n) { asm volatile("bar.arrive %0, %1;" ::"r"(id), "r"(n) : "memory"); }
__device__ __forceinline__ void fence_async_smem() { asm volatile("fence.proxy.async.shared::cta;" ::: "memory"); }
__device__ __forceinline__ void fence_async_all() { asm volatile("fence.proxy.async.global;" ::: "memory"); }
__device__ __forceinline__ uint32_t pack_bf16(float lo, float hi) { uint32_t r; asm("cvt.rn.bf16x2.f32 %0, %1, %2;" : "=r"(r) : "f"(hi), "f"(lo)); return r; }
__device__ __forceinline__ float ex2(float x) { float r; asm("ex2.approx.ftz.f32 %0, %1;" : "=f"(r) : "f"(x)); return r; }
__device__ __forceinline__ float rcp(float x) { float r; asm("rcp.approx.ftz.f32 %0, %1;" : "=f"(r) : "f"(x)); return r; }
__device__ __forceinline__ void flag_wait(const unsigned* f, unsigned target) {
  unsigned v;
  do { asm volatile("ld.acquire.gpu.global.u32 %0, [%1];" : "=r"(v) : "l"(f) : "memory"); } while (__any_sync(0xffffffffu, v < target));
}
__device__ __forceinline__ bool elect() {
  uint32_t r;
  asm volatile("{\n.reg .pred p;\nelect.sync _|p, -1;\nselp.u32 %0, 1, 0, p;\n}\n" : "=r"(r));
  return r;
}
__device__ __forceinline__ void fence_release() { asm volatile("fence.release.gpu;" ::: "memory"); }
__device__ __forceinline__ void flag_add(unsigned* f) { asm volatile("red.relaxed.gpu.global.add.u32 [%0], 1;" ::"l"(f) : "memory"); }
__device__ __forceinline__ void cluster_arrive() { asm volatile("barrier.cluster.arrive.relaxed.aligned;" ::: "memory"); }
__device__ __forceinline__ void cluster_wait() { asm volatile("barrier.cluster.wait.aligned;" ::: "memory"); }
__device__ __forceinline__ uint32_t hmul2(uint32_t a, uint32_t b) { uint32_t r; asm("mul.rn.bf16x2 %0, %1, %2;" : "=r"(r) : "r"(a), "r"(b)); return r; }
__device__ __forceinline__ uint32_t hadd2(uint32_t a, uint32_t b) { uint32_t r; asm("add.rn.bf16x2 %0, %1, %2;" : "=r"(r) : "r"(a), "r"(b)); return r; }
__device__ __forceinline__ uint32_t hfma2(uint32_t a, uint32_t b, uint32_t c) { uint32_t r; asm("fma.rn.bf16x2 %0, %1, %2, %3;" : "=r"(r) : "r"(a), "r"(b), "r"(c)); return r; }
__device__ __forceinline__ uint32_t lds32(uint32_t a) { uint32_t r; asm volatile("ld.shared.b32 %0, [%1];" : "=r"(r) : "r"(a) : "memory"); return r; }
__device__ __forceinline__ uint4 lds128(uint32_t a) { uint4 r; asm volatile("ld.shared.v4.b32 {%0,%1,%2,%3}, [%4];" : "=r"(r.x), "=r"(r.y), "=r"(r.z), "=r"(r.w) : "r"(a) : "memory"); return r; }
__device__ __forceinline__ uint32_t desc_k(uint32_t addr) { return ((addr & 0x3FFFF) >> 4) | (1u << 16); }
template <int LBO> __device__ __forceinline__ uint32_t desc_mn(uint32_t addr) { return ((addr & 0x3FFFF) >> 4) | ((uint32_t)(LBO >> 4) << 16); }
#define DHI "0x40000040"

#define R8(d, o) "+f"(d[o]), "+f"(d[o + 1]), "+f"(d[o + 2]), "+f"(d[o + 3]), "+f"(d[o + 4]), "+f"(d[o + 5]), "+f"(d[o + 6]), "+f"(d[o + 7])
#define R32(d, o) R8(d, o), R8(d, o + 8), R8(d, o + 16), R8(d, o + 24)
#define R64(d, o) R32(d, o), R32(d, o + 32)
#define L64 "%0,%1,%2,%3,%4,%5,%6,%7,%8,%9,%10,%11,%12,%13,%14,%15,%16,%17,%18,%19,%20,%21,%22,%23,%24,%25,%26,%27,%28,%29,%30,%31," \
            "%32,%33,%34,%35,%36,%37,%38,%39,%40,%41,%42,%43,%44,%45,%46,%47,%48,%49,%50,%51,%52,%53,%54,%55,%56,%57,%58,%59,%60,%61,%62,%63"
#define L128 L64 ",%64,%65,%66,%67,%68,%69,%70,%71,%72,%73,%74,%75,%76,%77,%78,%79,%80,%81,%82,%83,%84,%85,%86,%87,%88,%89,%90,%91,%92,%93,%94,%95," \
            "%96,%97,%98,%99,%100,%101,%102,%103,%104,%105,%106,%107,%108,%109,%110,%111,%112,%113,%114,%115,%116,%117,%118,%119,%120,%121,%122,%123,%124,%125,%126,%127"

template <int TB> __device__ __forceinline__ void mma_ss_n128(float (&d)[64], uint32_t da, uint32_t db) {
  asm volatile("{\n.reg .b64 da, db;\nmov.b64 da, {%64, " DHI "};\nmov.b64 db, {%65, " DHI "};\n"
               "wgmma.mma_async.sync.aligned.m64n128k16.f32.bf16.bf16 {" L64 "}, da, db, 1, 1, 1, 0, %66;\n}\n"
               : R64(d, 0) : "r"(da), "r"(db), "n"(TB));
}
template <int TB> __device__ __forceinline__ void mma_rs_n128(float (&d)[64], uint32_t a0, uint32_t a1, uint32_t a2, uint32_t a3, uint32_t db, int sd) {
  asm volatile("{\n.reg .pred p;\n.reg .b64 db;\nsetp.ne.b32 p, %69, 0;\nmov.b64 db, {%68, " DHI "};\n"
               "wgmma.mma_async.sync.aligned.m64n128k16.f32.bf16.bf16 {" L64 "}, {%64,%65,%66,%67}, db, p, 1, 1, %70;\n}\n"
               : R64(d, 0) : "r"(a0), "r"(a1), "r"(a2), "r"(a3), "r"(db), "r"(sd), "n"(TB));
}
template <int TB> __device__ __forceinline__ void mma_ss_n256(float (&d)[128], uint32_t da, uint32_t db) {
  asm volatile("{\n.reg .b64 da, db;\nmov.b64 da, {%128, " DHI "};\nmov.b64 db, {%129, " DHI "};\n"
               "wgmma.mma_async.sync.aligned.m64n256k16.f32.bf16.bf16 {" L128 "}, da, db, 1, 1, 1, 0, %130;\n}\n"
               : R64(d, 0), R64(d, 64) : "r"(da), "r"(db), "n"(TB));
}
#define W8(d, o) "=f"(d[o]), "=f"(d[o + 1]), "=f"(d[o + 2]), "=f"(d[o + 3]), "=f"(d[o + 4]), "=f"(d[o + 5]), "=f"(d[o + 6]), "=f"(d[o + 7])
#define W32(d, o) W8(d, o), W8(d, o + 8), W8(d, o + 16), W8(d, o + 24)
#define W64(d, o) W32(d, o), W32(d, o + 32)
template <int TB> __device__ __forceinline__ void mma_ss_n128_init(float (&d)[64], uint32_t da, uint32_t db) {
  asm volatile("{\n.reg .b64 da, db;\nmov.b64 da, {%64, " DHI "};\nmov.b64 db, {%65, " DHI "};\n"
               "wgmma.mma_async.sync.aligned.m64n128k16.f32.bf16.bf16 {" L64 "}, da, db, 0, 1, 1, 0, %66;\n}\n"
               : W64(d, 0) : "r"(da), "r"(db), "n"(TB));
}
template <int TB> __device__ __forceinline__ void mma_ss_n256_init(float (&d)[128], uint32_t da, uint32_t db) {
  asm volatile("{\n.reg .b64 da, db;\nmov.b64 da, {%128, " DHI "};\nmov.b64 db, {%129, " DHI "};\n"
               "wgmma.mma_async.sync.aligned.m64n256k16.f32.bf16.bf16 {" L128 "}, da, db, 0, 1, 1, 0, %130;\n}\n"
               : W64(d, 0), W64(d, 64) : "r"(da), "r"(db), "n"(TB));
}
#define L32 "%0,%1,%2,%3,%4,%5,%6,%7,%8,%9,%10,%11,%12,%13,%14,%15,%16,%17,%18,%19,%20,%21,%22,%23,%24,%25,%26,%27,%28,%29,%30,%31"
__device__ __forceinline__ void mma_ss_n64(float (&d)[32], uint32_t da, uint32_t db) {
  asm volatile("{\n.reg .b64 da, db;\nmov.b64 da, {%32, " DHI "};\nmov.b64 db, {%33, " DHI "};\n"
               "wgmma.mma_async.sync.aligned.m64n64k16.f32.bf16.bf16 {" L32 "}, da, db, 1, 1, 1, 0, 0;\n}\n"
               : R32(d, 0) : "r"(da), "r"(db));
}
__device__ __forceinline__ void mma_ss_n64_init(float (&d)[32], uint32_t da, uint32_t db) {
  asm volatile("{\n.reg .b64 da, db;\nmov.b64 da, {%32, " DHI "};\nmov.b64 db, {%33, " DHI "};\n"
               "wgmma.mma_async.sync.aligned.m64n64k16.f32.bf16.bf16 {" L32 "}, da, db, 0, 1, 1, 0, 0;\n}\n"
               : W32(d, 0) : "r"(da), "r"(db));
}
#define L16 "%0,%1,%2,%3,%4,%5,%6,%7,%8,%9,%10,%11,%12,%13,%14,%15"
__device__ __forceinline__ void mma_rs_n32(float (&d)[16], uint32_t a0, uint32_t a1, uint32_t a2, uint32_t a3, uint32_t db) {
  asm volatile("{\n.reg .b64 db;\nmov.b64 db, {%20, 0x00000008};\n"
               "wgmma.mma_async.sync.aligned.m64n32k16.f32.bf16.bf16 {" L16 "}, {%16,%17,%18,%19}, db, 1, 1, 1, 0;\n}\n"
               : R8(d, 0), R8(d, 8) : "r"(a0), "r"(a1), "r"(a2), "r"(a3), "r"(db));
}
__device__ __forceinline__ void mma_rs_n32_init(float (&d)[16], uint32_t a0, uint32_t a1, uint32_t a2, uint32_t a3, uint32_t db) {
  asm volatile("{\n.reg .b64 db;\nmov.b64 db, {%20, 0x00000008};\n"
               "wgmma.mma_async.sync.aligned.m64n32k16.f32.bf16.bf16 {" L16 "}, {%16,%17,%18,%19}, db, 0, 1, 1, 0;\n}\n"
               : W8(d, 0), W8(d, 8) : "r"(a0), "r"(a1), "r"(a2), "r"(a3), "r"(db));
}
__device__ __forceinline__ void mma_ss_n8(float (&d)[4], uint32_t da, uint32_t db) {
  asm volatile("{\n.reg .b64 da, db;\nmov.b64 da, {%4, " DHI "};\nmov.b64 db, {%5, 0x00000008};\n"
               "wgmma.mma_async.sync.aligned.m64n8k16.f32.bf16.bf16 {%0,%1,%2,%3}, da, db, 1, 1, 1, 0, 0;\n}\n"
               : "+f"(d[0]), "+f"(d[1]), "+f"(d[2]), "+f"(d[3]) : "r"(da), "r"(db));
}
template <int N> __device__ __forceinline__ void reg_fence(float (&d)[N]) {
#pragma unroll
  for (int i = 0; i < N; i++) asm volatile("" : "+f"(d[i])::"memory");
}
template <int N> __device__ __forceinline__ void reg_fence(uint32_t (&d)[N]) {
#pragma unroll
  for (int i = 0; i < N; i++) asm volatile("" : "+r"(d[i])::"memory");
}

struct __align__(64) Params {
  CUtensorMap x, c, wq, wuk, wuv, wo, y, out, w;
  const __nv_bfloat16* xp;
  const __nv_bfloat16* gate_w;
  const __nv_bfloat16 *ak, *av, *shk, *ssk, *ssd, *cp, *wukp, *wuvp;
  int zero;
};

template <int O, int N, int M> __device__ __forceinline__ void pack_frag(const float (&acc)[N], uint32_t (&pk)[M]) {
#pragma unroll
  for (int i = 0; i < 32; i++) pk[i] = pack_bf16(acc[O + 2 * i], acc[O + 2 * i + 1]);
}
template <int N> __device__ __forceinline__ void pack_frag_scaled(const float (&acc)[N], uint32_t (&pk)[32], float s0, float s1) {
#pragma unroll
  for (int i = 0; i < 32; i++) { const float s = (i & 1) ? s1 : s0; pk[i] = pack_bf16(acc[2 * i] * s, acc[2 * i + 1] * s); }
}
template <int J0 = 0, int J1 = 8, int M> __device__ __forceinline__ void stsm_frag(const uint32_t (&pk)[M], uint32_t a) {
#pragma unroll
  for (int jj = J0; jj < J1; jj++)
    asm volatile("stmatrix.sync.aligned.m8n8.x4.shared.b16 [%0], {%1,%2,%3,%4};" ::"r"((a ^ ((jj & 3) << 5)) + (jj >> 2) * 16384),
                 "r"(pk[4 * jj]), "r"(pk[4 * jj + 1]), "r"(pk[4 * jj + 2]), "r"(pk[4 * jj + 3]) : "memory");
}

struct Cons {
  uint32_t sb;
  uint32_t pf;
  int wg, tid;
  __device__ __forceinline__ void wait_full(int g) { mbar_wait(sb + SM_BAR + (B_FULL + g) * 8, (pf >> g) & 1); pf ^= 1u << g; }
  uint32_t relb;
  __device__ __forceinline__ void release(int g, int n) {
    if (tid < 2 * n) asm volatile("mbarrier.arrive.shared::cluster.b64 _, [%0];" ::"r"(relb + g * 8) : "memory");
  }
  __device__ __forceinline__ void turn_begin() { bar_sync(1 + wg, 256); }
  __device__ __forceinline__ void turn_end() { bar_arrive(2 - wg, 256); }
  __device__ __forceinline__ void staged(int e) { __syncwarp(); if ((tid & 31) == 0) mbar_arrive(sb + SM_BAR + (B_EV + 2 * e + wg) * 8); }
  int zero;
  uint32_t pfree;
  __device__ __forceinline__ void wait_stage_free() { mbar_wait(sb + SM_BAR + (B_EV + 4 + wg) * 8, pfree); pfree ^= 1; }
  __device__ __forceinline__ bool try_full(int g) { return mbar_test(sb + SM_BAR + (B_FULL + g) * 8, (pf >> g) & 1); }
};

constexpr float SM_C = 0.08838834764831845f * 1.4426950408889634f;
struct SoftState { float m0, m1, l0, l1; int shifted; };
__device__ __forceinline__ void ex2_rot(float& t, float s, uint32_t never_zero) {
  asm("{\n.reg .pred p;\nsetp.ne.u32 p, %2, 0;\n@p ex2.approx.ftz.f32 %0, %1;\n}\n" : "+f"(t) : "f"(s), "r"(never_zero));
}
__device__ __forceinline__ void pin(float a, uint32_t never_zero) {
  asm volatile("{\n.reg .pred p;\nsetp.eq.u32 p, %1, 0;\n@p st.shared.f32 [%1], %0;\n}\n" ::"f"(a), "r"(never_zero) : "memory");
}
template <int O, int N> __device__ __forceinline__ void reg_fence_part(uint32_t (&d)[32]) {
#pragma unroll
  for (int i = O; i < O + N; i++) asm volatile("" : "+r"(d[i])::"memory");
}
template <int Q, int W, int N> __device__ __forceinline__ void exp_quarter(const float (&S)[N], uint32_t (&P)[32], float (&t)[ROT], float& s0, float& s1, uint32_t nz) {
#pragma unroll
  for (int i = 8 * Q; i < 8 * Q + 8; i++) {
    float& a = t[(2 * i) % ROT];
    float& b = t[(2 * i + 1) % ROT];
    if (2 * i < ROT) { a = ex2(S[2 * i]); b = ex2(S[2 * i + 1]); }
    else { ex2_rot(a, S[2 * i], nz); ex2_rot(b, S[2 * i + 1], nz); }
    if (i < 2) { if (i) s1 = a + b; else s0 = a + b; }
    else if (SUMV == 0) { if (i & 1) { s1 += a; s1 += b; } else { s0 += a; s0 += b; } }
    else { if (i & 1) s1 += a + b; else s0 += a + b; }
    if (i == 8 * Q) { pin(EXPV == 1 && Q ? s1 : s0, nz); wg_wait<W>(); reg_fence_part<8 * Q, 8>(P); }
    P[i] = pack_bf16(a, b);
  }
}
template <int N> __device__ __forceinline__ void shift_scores(float (&S)[N], float d0, float d1) {
#pragma unroll
  for (int i = 0; i < N; i++) S[i] -= (i & 2) ? d1 : d0;
}
__device__ __forceinline__ bool soft_high(float s0, float s1, float lim = SM_LIMIT) { return s0 > lim || s1 > lim; }
__device__ __forceinline__ bool soft_unsafe(float s0, float s1, bool first) {
  uint32_t b0 = __ballot_sync(0xffffffffu, s0 >= SM_LOW), b1 = __ballot_sync(0xffffffffu, s1 >= SM_LOW);
  b0 |= b0 >> 1; b0 |= b0 >> 2; b1 |= b1 >> 1; b1 |= b1 >> 2;
  return __any_sync(0xffffffffu, soft_high(s0, s1)) || (first && (b0 & b1 & 0x11111111u) != 0x11111111u);
}
template <int N> __device__ __forceinline__ void soft_fix(const float (&S)[N], float (&O)[64], SoftState& z, bool first, float& d0, float& d1) {
  d0 = d1 = first ? -INFINITY : 0.f;
#pragma unroll
  for (int j = 0; j < N / 4; j++) { d0 = fmaxf(d0, fmaxf(S[4 * j], S[4 * j + 1])); d1 = fmaxf(d1, fmaxf(S[4 * j + 2], S[4 * j + 3])); }
  d0 = fmaxf(d0, __shfl_xor_sync(0xffffffffu, d0, 1)); d1 = fmaxf(d1, __shfl_xor_sync(0xffffffffu, d1, 1));
  d0 = fmaxf(d0, __shfl_xor_sync(0xffffffffu, d0, 2)); d1 = fmaxf(d1, __shfl_xor_sync(0xffffffffu, d1, 2));
  const float sc0 = ex2(-fmaxf(d0, 0.f)), sc1 = ex2(-fmaxf(d1, 0.f));
  z.m0 += d0; z.m1 += d1; z.l0 *= sc0; z.l1 *= sc1; z.shifted = 1;
#pragma unroll
  for (int j = 0; j < 16; j++) { O[4 * j] *= sc0; O[4 * j + 1] *= sc0; O[4 * j + 2] *= sc1; O[4 * j + 3] *= sc1; }
}
template <int M> __device__ __forceinline__ void pin32(const uint32_t (&v)[M], uint32_t never_zero) {
#pragma unroll
  for (int i = 0; i < 32; i += 4)
    asm volatile("{\n.reg .pred p;\nsetp.eq.u32 p, %4, 0;\n@p st.shared.v4.b32 [%4], {%0,%1,%2,%3};\n}\n" ::"r"(v[i]), "r"(v[i + 1]), "r"(v[i + 2]), "r"(v[i + 3]), "r"(never_zero) : "memory");
}
template <int N> __device__ __forceinline__ void mask_diag(float (&S)[N], float nd) {
  asm volatile("" : "+f"(nd));
#pragma unroll
  for (int i = 0; i < 32; i++) {
    const float beyond = __saturatef(nd + (float)(8 * (i >> 2) + (i & 1) - 4 * (i & 2)));
    S[N - 32 + i] = fmaf(beyond, -3.0e38f, S[N - 32 + i]);
  }
}
__device__ __forceinline__ float quad_sum(float v) {
  v += __shfl_xor_sync(0xffffffffu, v, 1);
  v += __shfl_xor_sync(0xffffffffu, v, 2);
  return v;
}
__device__ __forceinline__ void issue_qk(float (&S)[64], uint32_t dq, uint32_t dk) {
  mma_ss_n128_init<0>(S, dq, dk);
#pragma unroll
  for (int s = 1; s < 8; s++) mma_ss_n128<0>(S, dq + (s >> 2) * 1024 + (s & 3) * 2, dk + (s >> 2) * 1024 + (s & 3) * 2);
}
__device__ __forceinline__ void issue_qk(float (&S)[32], uint32_t dq, uint32_t dk) {
  mma_ss_n64_init(S, dq, dk);
#pragma unroll
  for (int s = 1; s < 8; s++) mma_ss_n64(S, dq + (s >> 2) * 1024 + (s & 3) * 2, dk + (s >> 2) * 1024 + (s & 3) * 2);
}
template <int H> __device__ __forceinline__ void issue_pv(float (&O)[64], const uint32_t (&P)[32], uint32_t dv, int acc, bool on) {
  if (on) {
#pragma unroll
    for (int s = 4 * H; s < 4 * H + 4; s++) {
      mma_rs_n128<1>(O, P[4 * s], P[4 * s + 1], P[4 * s + 2], P[4 * s + 3], dv + s * 128, s != 0 ? 1 : acc);
      if (s & 1) wg_commit();
    }
  } else { wg_commit(); wg_commit(); }
}
constexpr uint32_t DG = GR >> 4;
__device__ __forceinline__ void stage_q2(Cons& c, const float (&O)[64], uint32_t (&P)[32], uint32_t stg) {
  wg_commit(); wg_commit(); wg_commit(); wg_commit();
  c.turn_end();
  pack_frag<0>(O, P);
  stsm_frag(P, stg);
  fence_async_smem();
#pragma unroll
  for (int i = 16; i < 32; i++) P[i] = 0;
}
__device__ __forceinline__ void attn_half(Cons& c, float (&O)[64], uint32_t (&P)[32], SoftState& z, uint32_t dk0, uint32_t dkk, uint32_t dv0, float dmask, int last, uint32_t stg) {
  float S[32];
  c.turn_begin();
  wg_fence();
  issue_qk(S, dk0 + (last ? 0 : 2 * DG), dkk + (last ? 8 : 4) * DG);
  wg_commit();
  if (last) {
    issue_pv<0>(O, P, dv0 + 10 * DG, 1, true);
    issue_pv<1>(O, P, dv0 + 10 * DG, 1, true);
    c.turn_end();
  } else stage_q2(c, O, P, stg);
  wg_wait<4>();
  reg_fence(S);
  c.release(last ? 8 : 4, 2);
  mask_diag(S, dmask);
  float s0, s1, d0 = z.m0, d1 = z.m1;
#pragma unroll 1
  for (int pass = 0;; pass++) {
    if (z.shifted) shift_scores(S, d0, d1);
    float tr[ROT];
    exp_quarter<0, 3>(S, P, tr, s0, s1, c.sb);
    exp_quarter<1, 2>(S, P, tr, s0, s1, c.sb);
    pin(s1, c.sb); wg_wait<0>(); reg_fence_part<16, 16>(P); reg_fence(O);
    if (!soft_unsafe(s0, s1, !last) || pass) break;
    soft_fix(S, O, z, !last, d0, d1);
  }
  z.l0 += s0; z.l1 += s1;
  c.release(10, last ? 2 : 0);
  c.wait_full(last ? 12 : 6);
  if (!last) c.wait_full(8);
}

__device__ __forceinline__ int conv_next(int g, bool spare) { return spare ? (g >= NGR - 2 ? g - (NGR - 4) : g + 2) : g ^ 6; }
__device__ __forceinline__ void conv_final(uint32_t rb, uint32_t yb, const uint4& u, uint32_t dd, bool on) {
  const uint4 q0 = lds128(rb), q1 = lds128(rb + 4096), q2 = lds128(rb + 8192), q3 = lds128(rb + 12288);
  auto fin = [&](uint32_t x0, uint32_t x1, uint32_t x2, uint32_t x3, uint32_t uu) {
    return hfma2(dd, __byte_perm(uu, uu, 0x1032), hadd2(hadd2(x0, x1), hadd2(x2, x3)));
  };
  asm volatile("{\n.reg .pred p;\nsetp.ne.b32 p, %5, 0;\n@p st.shared.v4.b32 [%0], {%1,%2,%3,%4};\n}\n" ::"r"(yb), "r"(fin(q0.x, q1.x, q2.x, q3.x, u.w)),
               "r"(fin(q0.y, q1.y, q2.y, q3.y, u.z)), "r"(fin(q0.z, q1.z, q2.z, q3.z, u.y)), "r"(fin(q0.w, q1.w, q2.w, q3.w, u.x)), "r"((int)on) : "memory");
}
__device__ __forceinline__ void conv_tasks(Cons& c, const Params& p, int ntask, bool last, bool spare, int ch, int chstep, uint32_t dkk, int w, int lane) {
  const uint32_t sb = c.sb;
  int g = 4 + c.wg;
  uint4 u0 = make_uint4(0, 0, 0, 0), u1 = u0;
  uint32_t dd = 0, rb = sb + g * GR;
  const uint32_t yb = sb + c.wg * 8192 + c.tid * 16;
  c.wait_full(g);
#pragma unroll 1
  for (int i = 0; i < ntask; i++) {
    const uint32_t base = sb + g * GR;
    FTC(0);
    uint32_t a[64];
    const uint32_t hb = base + WBYTES - 28 + (8 * w + (lane >> 2) + (lane & 3)) * 4;
    auto lda = [&](int s) {
      a[4 * s] = lds32(hb + s * 256); a[4 * s + 1] = lds32(hb + s * 256 + 128);
      a[4 * s + 2] = lds32(hb + s * 256 + 16); a[4 * s + 3] = lds32(hb + s * 256 + 144);
    };
    lda(0); lda(15); lda(1); lda(14);
    float acc[8][16];
    const uint32_t db = dkk + ((4352 / 16 - 1) << 16) + g * DG + 16;
    FTC(2);
    c.turn_begin();
    FTC(3);
#pragma unroll
    for (int k = 0; k < 8; k++) {
      if (k < 7) wg_fence();
      if (k == 7 && !(last && i == ntask - 1)) c.turn_end();
#pragma unroll
      for (int J = 7; J >= (k >> 1); J--) {
        if (k == 0) mma_rs_n32_init(acc[J], a[0], a[1], a[2], a[3], db + J * 32);
        else mma_rs_n32(acc[J], a[4 * k], a[4 * k + 1], a[4 * k + 2], a[4 * k + 3], db + (2 * J - k) * 16);
      }
      const int s = 15 - k;
#pragma unroll
      for (int J = 7; J >= (s >> 1); J--) mma_rs_n32(acc[J], a[4 * s], a[4 * s + 1], a[4 * s + 2], a[4 * s + 3], db + (2 * J - s) * 16);
      if (k < 6) { lda(k + 2); lda(13 - k); }
      if (k == 0) conv_final(rb, yb, u0, dd, i > 0);
      if (k == 1) {
        conv_final(rb + 2048, yb + 2048, u1, dd, i > 0);
        __syncwarp();
        if (lane == 0 && i > 0) mbar_arrive(sb + SM_BAR + (B_EV + c.wg) * 8);
      }
      if (k == 6) {
        const uint32_t ub = base + 256 + 16 + (c.tid >> 1) * 32 + ((c.tid & 1) ^ 1) * 4352;
        u0 = lds128(ub); u1 = lds128(ub + 2048);
        dd = __bfloat16_as_ushort(p.ssd[ch]) * 0x10001u;
      }
    }
    wg_commit();
    FTC(4);
    g = conv_next(g, spare);
    ch += chstep;
    rb = base + c.tid * 16;
    if (i + 1 < ntask) c.wait_full(g);
    wg_wait<0>();
#pragma unroll
    for (int J = 0; J < 8; J++) reg_fence(acc[J]);
    reg_fence(a);
    bar_sync(3 + c.wg, 128);
    FTC(5);
    const int tw = (lane & 3) + w;
    const uint32_t xb = base + w * 4096 + tw * 32 + (lane >> 2) * 4;
#pragma unroll
    for (int j = 0; j < 32; j++) {
      float v0 = acc[j >> 2][(j & 3) * 4], v1 = acc[j >> 2][(j & 3) * 4 + 1];
      if (j > 0) { v0 += acc[(j - 1) >> 2][((j - 1) & 3) * 4 + 2]; v1 += acc[(j - 1) >> 2][((j - 1) & 3) * 4 + 3]; }
      uint32_t v = pack_bf16(v0, v1), ad = xb + j * 128;
      if (j == 31 && tw >= 4) { v = 0; ad -= 4096; }
      asm volatile("st.shared.b32 [%0], %1;" ::"r"(ad), "r"(v) : "memory");
    }
    c.wait_stage_free();
    bar_sync(3 + c.wg, 128);
    FTC(6);
  }
  conv_final(rb, yb, u0, dd, true);
  conv_final(rb + 2048, yb + 2048, u1, dd, true);
  c.staged(0);
}

__global__ void __cluster_dims__(2, 1, 1) __launch_bounds__(NTHREADS, 1) mega_kernel(const __grid_constant__ Params p) {
  extern __shared__ __align__(1024) uint8_t smem_raw[];
  const uint32_t sb = smem_u32(smem_raw);
  const int wgi = __shfl_sync(0xffffffffu, threadIdx.x >> 7, 0);
  const int warp = __shfl_sync(0xffffffffu, threadIdx.x >> 5, 0);
  const uint32_t rank = blockIdx.x & 1;
  int grp, idx;
  {
    uint32_t smid; asm volatile("mov.u32 %0, %smid;" : "=r"(smid));
    const int tp = smid >> 1;
    if (tp < 32) { grp = tp & 7; idx = tp >> 3; }
    else if (tp < 60) { grp = 1 + (tp - 32) % 7; idx = 4 + (tp - 32) / 7; }
    else if (tp < 62) { grp = 8; idx = tp - 60; }
    else { grp = 0; idx = tp - 58; }
  }
  const int lb = (grp * 8 + idx) * 2 + rank;
  const bool spare = grp == 8;
  const int cn = spare ? CN_SPARE : CN_MAIN, cch = spare ? lb - NMAIN : 4 * CN_SPARE + CN_MAIN * lb, cstep = spare ? 4 : 1;

  if (threadIdx.x == 64) { prefetch_tm(&p.c); prefetch_tm(rank ? &p.wuv : &p.wuk); }
  if (threadIdx.x <= B_DONE) {
    const int i = threadIdx.x;
    mbar_init(sb + SM_BAR + i * 8, i == B_DONE ? 11 : i < NGR || i >= 2 * NGR + 4 ? 1 : 4);
    asm volatile("fence.mbarrier_init.release.cluster;" ::: "memory");
  }
  if (START_PF && wgi && !spare) {
    const int j = threadIdx.x & 127;
#pragma unroll
    for (int kb = 0; kb < START_PF; kb++)
      asm volatile("prefetch.global.L2 [%0];" ::"l"(wgi == 1 ? p.cp + (size_t)((2 * idx + rank) * 128 + j) * DC + kb * 64
                                                             : (rank ? p.wuvp : p.wukp) + (size_t)(kb * 64 + (j >> 1)) * (NH * HD) + 2 * grp * HD + (j & 1) * 64));
  }
  cluster_arrive();
  cluster_wait();
  TS(0);

  if (wgi == 0) {
    asm volatile("setmaxnreg.dec.sync.aligned.u32 40;");
    const int lane = threadIdx.x & 31;
    cluster_arrive();
    if (warp == 3) {
      if (!spare) {
        const int s0 = lb * 16;
#pragma unroll 1
        for (int cg = 0; cg < 16; cg++) {
          __nanosleep(PRE_SLEEP);
          const int ch = cg * 64 + 2 * lane;
          const uint32_t* kp = reinterpret_cast<const uint32_t*>(p.ak + (size_t)s0 * DM + ch);
          const uint32_t* vp = reinterpret_cast<const uint32_t*>(p.av + (size_t)s0 * DM + ch);
          const uint4 sw = __ldg(reinterpret_cast<const uint4*>(p.shk + ch * 4));
          uint32_t k3 = 0, k2 = 0, k1 = 0, k0 = 0, up = 0;
          if (lb > 0) { k3 = ldg_stream(kp - 4 * 512); k2 = ldg_stream(kp - 3 * 512); k1 = ldg_stream(kp - 2 * 512); k0 = ldg_stream(kp - 512); up = ldg_stream(vp - 512); }
          const uint32_t w0 = __byte_perm(sw.x, sw.z, 0x5410), w1 = __byte_perm(sw.x, sw.z, 0x7632);
          const uint32_t w2 = __byte_perm(sw.y, sw.w, 0x5410), w3 = __byte_perm(sw.y, sw.w, 0x7632);
          up = hmul2(hfma2(k0, w0, hfma2(k1, w1, hfma2(k2, w2, hmul2(k3, w3)))), up);
#pragma unroll 1
          for (int hb = 0; hb < 2; hb++) {
            uint32_t kk[8], u[8];
#pragma unroll
            for (int r = 0; r < 8; r++) { kk[r] = ldg_stream(kp + r * 512); u[r] = ldg_stream(vp + r * 512); }
#pragma unroll
            for (int r = 0; r < 8; r++) {
              k3 = k2; k2 = k1; k1 = k0; k0 = kk[r];
              u[r] = hmul2(hfma2(k0, w0, hfma2(k1, w1, hfma2(k2, w2, hmul2(k3, w3)))), u[r]);
            }
            if (lane == 0) asm volatile("cp.async.bulk.wait_group.read 0;" ::: "memory");
            __syncwarp();
            const uint32_t dst = sb + SM_UST + lane * 32 + ((lane & 4) << 2);
#pragma unroll
            for (int cc = 0; cc < 2; cc++) {
              const uint32_t sel = cc ? 0x7632 : 0x5410;
              asm volatile("st.shared.v4.b32 [%0], {%1,%2,%3,%4};" ::"r"(dst + cc * 1024), "r"(__byte_perm(u[6], u[5], sel)), "r"(__byte_perm(u[4], u[3], sel)),
                           "r"(__byte_perm(u[2], u[1], sel)), "r"(__byte_perm(u[0], up, sel)) : "memory");
              asm volatile("st.shared.v4.b32 [%0], {%1,%2,%3,%4};" ::"r"((dst ^ 16) + cc * 1024), "r"(__byte_perm(u[7], u[6], sel)), "r"(__byte_perm(u[5], u[4], sel)),
                           "r"(__byte_perm(u[3], u[2], sel)), "r"(__byte_perm(u[1], u[0], sel)) : "memory");
            }
            fence_async_smem();
            __syncwarp();
            if (lane == 0) {
              asm volatile("cp.async.bulk.tensor.3d.global.shared::cta.bulk_group [%0, {%2, %3, %4}], [%1];\ncp.async.bulk.commit_group;"
                           ::"l"(&p.w), "r"(sb + SM_UST), "r"(128 + lb * 16 + (hb ^ 1) * 2176), "r"(cg * 32), "r"(0) : "memory");
            }
            up = u[7];
            kp += 8 * 512; vp += 8 * 512;
          }
          if ((cg & (cg + 1)) == 0 && lane == 0) {
            asm volatile("cp.async.bulk.wait_group 0;" ::: "memory");
            fence_release();
            flag_add(FLAG(F_U + 32 - __clz(cg)));
          }
          TSW(10 + cg);
        }
      }
      if (lane == 0) {
        unsigned long long t0, t1;
        asm volatile("mov.u64 %0, %globaltimer;" : "=l"(t0));
        while (!mbar_try(sb + SM_BAR + B_DONE * 8, 0)) {
          asm volatile("mov.u64 %0, %globaltimer;" : "=l"(t1));
          if (t1 - t0 > 2000000000ull) __trap();
        }
      }
    } else if (warp != 0) {
      const int w = warp - 1, ne = 12 + (cn + 1 - w) / 2;
      uint32_t p0 = 0;
      int cg = 4 + w, ch = cch + w * cstep;
#pragma unroll 1
      for (int e = spare ? 12 : 0; e < ne; e++) {
        const int rnd = e >= 6, k = e - 6 * rnd, rt = k == 4 ? idx : 15 - idx;
        uint8_t* dst = k < 4 ? g_kv + (size_t)(((k & 1) * 16 + 2 * grp + (k >> 1)) * 16 + 2 * idx + rank) * 32768 + w * 8192
                     : k < 6 ? g_cimg + (size_t)(rt * 32 + 16 * rnd + 2 * grp + rank) * 32768 + w * 8192
                             : reinterpret_cast<uint8_t*>(g_yT + (size_t)ch * SEQ);
        const uint32_t src = sb + w * 8192 + (k == 4 ? 2 * GR : 0);
        if (e == 6) flag_wait(FLAG(F_AD + grp), 32);
        mbar_wait1(sb + SM_BAR + (B_EV + (k == 4 ? 2 : 0) + w) * 8, k == 4 ? rnd : p0);
        if (k != 4) p0 ^= 1;
        if (lane < 4 && k >= 6 && (!spare || e < ne - 6)) mbar_arrive_cluster(sb + SM_BAR + (B_EMPTY + cg) * 8, lane & 1);
        fence_async_smem();
        if (elect()) {
#pragma unroll 1
          for (int i = 0; i < (k >= 6 ? 1 : 8); i++) {
            const uint32_t o = (i >> 2) * 16384 + (i & 3) * 2048;
            asm volatile("cp.async.bulk.global.shared::cta.bulk_group [%0], [%1], %2;" ::"l"(dst + o), "r"(src + o), "r"(k >= 6 ? 4096 : 2048) : "memory");
            asm volatile("cp.async.bulk.commit_group;\ncp.async.bulk.wait_group.read %0;" ::"n"(ST_OUT) : "memory");
          }
          asm volatile("cp.async.bulk.wait_group 0;" ::: "memory");
          if (k != 4) mbar_arrive(sb + SM_BAR + (B_EV + 4 + w) * 8);
        }
        __syncwarp();
        if (lane < 4 && (k == 4 || (e == ne - 1 && !spare)))
          mbar_arrive_cluster(sb + SM_BAR + (B_EMPTY + (k == 4 ? 2 : 0) + (lane >> 1)) * 8, lane & 1);
        if (k >= 3) {
          fence_release();
          if (lane == 0 || (lane == 1 && e == 5))
            flag_add(FLAG(lane ? F_AD + grp : k == 3 ? F_KV + rnd * 8 + grp : k < 6 ? F_CTX + rt * 2 + rnd : F_Y + (ch >> 7)));
        }
        if (k >= 6) { cg = conv_next(cg, spare); ch += 2 * cstep; }
      }
      if (lane == 0) mbar_arrive(sb + SM_BAR + B_DONE * 8);
    } else {
      uint32_t pe = 0x3FFC;
      auto acquire = [&](int g) { PWAIT(sb + SM_BAR + (B_EMPTY + g) * 8, (pe >> g) & 1); pe ^= 1u << g; };
#pragma unroll 1
      for (int rnd = 0; rnd < (spare ? 0 : 2); rnd++) {
        const int hp = 16 * rnd + 2 * grp, head = hp + rank;
#pragma unroll 1
        for (int kk = 0; kk < 32; kk++) {
          const int g0 = 2 + 3 * (kk & 3);
          acquire(g0);
          if (kk < 4) { acquire(g0 + 1); acquire(g0 + 2); } else pe ^= 6u << g0;
          if (elect()) {
            const uint32_t fb = sb + SM_BAR + (B_FULL + g0) * 8;
            mbar_expect_tx(fb, 3 * GR);
            if (kk < 16) {
              tma2d(sb + g0 * GR, &p.c, (kk & 7) * 64, (2 * idx + rank) * 128, fb, EV_NORMAL);
              tma3d_mc(sb + (g0 + 1 + rank) * GR, rank ? &p.wuv : &p.wuk, 0, (kk & 7) * 64, (hp + (kk >> 3)) * 2, fb, POL_W);
            } else {
              tma2d_mc(sb + (g0 + rank) * GR, &p.x, (kk - 16) * 64, (rank ? 15 - idx : idx) * 128, fb, EV_NORMAL);
              tma3d(sb + (g0 + 2) * GR, &p.wq, 0, (kk - 16) * 64, head * 2, fb, POL_W);
            }
            if (kk == 3) { prefetch_tm(&p.x); prefetch_tm(&p.wq); }
          }
        }
        flag_wait(FLAG(F_KV + rnd * 8 + grp), 32);
        fence_async_all();
        acquire(2); pe ^= 8u;
        int g0 = 4;
#pragma unroll 1
        for (int f = 0; f < 34; f++) {
          const bool isk = (f == 0) || ((f & 1) && f < 33);
          const int it = (f == 0) ? 0 : (f == 33) ? 16 : isk ? (f + 1) >> 1 : (f >> 1) - 1;
          const int blk = it == 0 ? idx : it <= idx ? it - 1 : it < 16 ? 15 - it : 15 - idx;
          acquire(g0);
          if (f < 5) acquire(g0 + 1); else pe ^= 2u << g0;
          if (elect()) {
            const uint32_t fb = sb + SM_BAR + (B_FULL + g0) * 8;
            mbar_expect_tx(fb, 2 * GR);
            bulk_g2s(sb + g0 * GR, g_kv + (size_t)(((isk ? 0 : 16) + (head & 15)) * 16 + blk) * 32768, 2 * GR, fb, POL_KV);
          }
          g0 = f == 12 ? 12 : g0 == 12 ? 4 : g0 + 2;
        }
      }
      if (spare) {
#pragma unroll 1
        for (int i = 0, g = 2; i < 32; i++) {
          acquire(g); pe ^= 2u << g;
          if (elect()) {
            const uint32_t fb = sb + SM_BAR + (B_FULL + g) * 8;
            if (i == 0) { mbar_expect_tx(fb - 8, 2048); bulk_g2s(sb + GR, p.gate_w, 2048, fb - 8, EV_NORMAL); }
            mbar_expect_tx(fb, 2 * GR);
            tma2d(sb + g * GR, &p.x, (i & 7) * 128, (lb - NMAIN) * 512 + (i >> 3) * 128, fb, EV_NORMAL);
            tma2d(sb + (g + 1) * GR, &p.x, (i & 7) * 128 + 64, (lb - NMAIN) * 512 + (i >> 3) * 128, fb, EV_NORMAL);
          }
          g = g == NGR - 2 ? 2 : g + 2;
        }
      }
      auto conv_fill = [&](int g, int ch) {
        acquire(g);
        if (elect()) {
          const uint32_t fb = sb + SM_BAR + (B_FULL + g) * 8;
          mbar_expect_tx(fb, WBYTES + 4096);
          bulk_g2s(sb + g * GR, g_w + (size_t)ch * WSTRIDE, WBYTES, fb, POL_C);
          bulk_g2s(sb + g * GR + WBYTES, p.ssk + (size_t)ch * SEQ, 4096, fb, POL_C);
        }
      };
#pragma unroll 1
      for (int i = 0, g = 4; i < cn; i++) {
        if ((i & 15) == 0) { flag_wait(FLAG(F_U + (spare ? 32 - __clz(i >> 4) : 4)), NMAIN); fence_async_all(); }
        conv_fill(g + (i & 1), cch + i * cstep);
        if (i & 1) g = conv_next(g, spare);
      }
      if (!spare) {
        const int rt = 2 * grp + rank, ct = idx;
        int g0 = P3G;
#pragma unroll 1
        for (int kb = 0; kb < 66; kb++) {
          if (kb == 0 || kb == 32 || kb >= 64) {
            flag_wait(FLAG(kb < 64 ? F_CTX + rt * 2 + (kb >> 5) : kb == 64 ? F_GATE : F_Y + ct), kb <= 64 ? 32 : 128);
            fence_async_all();
          }
          acquire(g0);
          if (kb < 11) acquire(g0 + 1);
          if (elect()) {
            const uint32_t fb = sb + SM_BAR + (B_FULL + g0) * 8;
            mbar_expect_tx(fb, kb == 64 ? 2 * GR + 512 : 2 * GR);
            if (kb <= 64) bulk_g2s(kb < 64 ? sb + g0 * GR : sb + SM_GATE, kb < 64 ? (const void*)(g_cimg + (size_t)(rt * 64 + kb) * GR) : (const void*)(g_gate + rt * 128), kb < 64 ? GR : 512, fb, POL_CTX);
            if (kb < 64) {
              tma2d_mc(sb + (g0 + 1) * GR + rank * 8192, &p.wo, ct * 128 + rank * 64, kb * 64, fb, POL_WO);
              if (kb == 40) { prefetch_tm(&p.y); prefetch_tm(&p.out); }
            } else {
              const CUtensorMap* tm = kb == 64 ? &p.x : &p.y;
              const int c0 = (kb == 64 ? ct : rt) * 128, c1 = (kb == 64 ? rt : ct) * 128;
              tma2d(sb + g0 * GR, tm, c0, c1, fb, EV_NORMAL);
              tma2d(sb + (g0 + 1) * GR, tm, c0 + 64, c1, fb, EV_NORMAL);
            }
          }
          g0 = g0 == 12 ? (kb == 3 ? 2 : 0) : g0 + 2;
        }
        unsigned n = 0;
        if (lane == 0) n = atomicAdd(FLAG(F_EXIT), 1);
        if (__shfl_sync(0xffffffffu, n, 0) == NMAIN - 1) { *FLAG(lane) = 0; *FLAG(lane + 32) = 0; *FLAG(lane + 64) = 0; }
      }
      if (lane == 0) mbar_arrive(sb + SM_BAR + B_DONE * 8);
    }
    __syncwarp();
    cluster_wait();
  } else {
    asm volatile("setmaxnreg.inc.sync.aligned.u32 232;");
    Cons c;
    c.sb = sb; c.pf = 0; c.wg = wgi - 1; c.tid = threadIdx.x & 127;
    const int lane = threadIdx.x & 31, t = lane & 3;
    const int row = c.wg * 64 + (warp & 3) * 16 + (lane >> 2);
    const uint32_t dkk = desc_k(sb), dk0 = dkk + c.wg * 512, dm0 = desc_mn<8192>(sb), dv0 = desc_mn<16384>(sb);
    if (c.wg == 1) bar_arrive(1, 256);
    c.pfree = 1;
    asm("mapa.shared::cluster.u32 %0, %1, %2;" : "=r"(c.relb) : "r"(sb + SM_BAR + (B_EMPTY + (c.tid >> 1)) * 8), "r"(c.tid & 1));
    c.zero = p.zero;
    const uint32_t stg = sb + (c.wg * 64 + (warp & 3) * 16 + ((lane >> 3) & 1) * 8 + (lane & 7)) * 128 + (((lane >> 4) ^ (lane & 7)) << 4);

    if (spare) {
      c.wait_full(1);
      int g = 2;
#pragma unroll 1
      for (int r = 0; r < 4; r++) {
        float d[4] = {0.f, 0.f, 0.f, 0.f}, e[4] = {0.f, 0.f, 0.f, 0.f};
#pragma unroll 1
        for (int kb = 0; kb < 16; kb += 2) {
          c.wait_full(g);
          wg_fence();
#pragma unroll
          for (int k = 0; k < 4; k++) {
            mma_ss_n8(d, dk0 + g * DG + k * 2, dkk + DG + kb * 8 + k * 2);
            mma_ss_n8(e, dk0 + (g + 1) * DG + k * 2, dkk + DG + kb * 8 + 8 + k * 2);
          }
          wg_commit();
          wg_wait<0>();
          c.release(g, 2);
          g = g == NGR - 2 ? 2 : g + 2;
        }
        reg_fence(d); reg_fence(e);
        d[0] += e[0]; d[2] += e[2];
        if (t == 0) {
          float* gp = g_gate + (lb - NMAIN) * 512 + r * 128 + row;
          gp[0] = rcp(1.f + ex2(-1.4426950408889634f * d[0])); gp[8] = rcp(1.f + ex2(-1.4426950408889634f * d[2]));
        }
      }
      fence_release();
      __syncwarp();
      if (lane == 0) flag_add(FLAG(F_GATE));
      TS(1);
    }
    const float dmask = (float)(2 * t - (row & 63));
    uint32_t pv[32];
#pragma unroll
    for (int i = 0; i < 32; i++) pv[i] = 0;
#pragma unroll 1
    for (int rnd = 0; rnd < (spare ? 0 : 2); rnd++) {
      float O[64];
      FTM(rnd * 8);
      c.wait_full(2);
      FTM(rnd * 8 + 1);
#pragma unroll 1
      for (int tile = c.zero; tile < 2; tile++) {
        float acc[128];
        {
          FTG(tile * 32); FTG(tile * 32 + 1);
          const uint32_t a = dk0 + 2 * DG, b = dm0 + 3 * DG;
          c.turn_begin();
          FTG(tile * 32 + 2);
          wg_fence();
          mma_ss_n256_init<1>(acc, a, b);
#pragma unroll
          for (int k = 1; k < 4; k++) mma_ss_n256<1>(acc, a + k * 2, b + k * 128);
          wg_commit();
          FTG(tile * 32 + 3);
        }
#pragma unroll 1
        for (int kb = 1; kb < 8; kb++) {
          const int g0 = 2 + 3 * (kb & 3);
          const uint32_t a = dk0 + g0 * DG, b = dm0 + (g0 + 1) * DG;
          const bool second = kb == 1 || kb == 7;
          FTG(tile * 32 + kb * 4);
          if (!second) { wg_wait<0>(); c.release(2 + 3 * ((kb - 1) & 3), 3); }
          FTG(tile * 32 + kb * 4 + 1);
          c.wait_full(g0);
          if (!second) c.turn_begin();
          FTG(tile * 32 + kb * 4 + 2);
          wg_fence();
#pragma unroll
          for (int k = 0; k < 4; k++) mma_ss_n256<1>(acc, a + k * 2, b + k * 128);
          wg_commit();
          if (kb != 6) c.turn_end();
          if (second) { wg_wait<1>(); c.release(2 + 3 * ((kb - 1) & 3), 3); }
          FTG(tile * 32 + kb * 4 + 3);
          if (tile == 1 && kb == 3) { c.wait_stage_free(); stsm_frag<0, 4>(pv, stg); }
          if (tile == 1 && kb == 4) { stsm_frag<4, 8>(pv, stg); c.staged(0); }
        }
        c.wait_stage_free();
        const bool nxt = c.try_full(2);
        wg_wait<0>();
        reg_fence(acc);
        c.release(11, 3);
        pack_frag_scaled(acc, pv, SM_C, SM_C);
        stsm_frag(pv, stg);
        c.staged(0);
        pack_frag<64>(acc, pv);
        pin32(pv, sb);
        if (!nxt) mbar_wait(sb + SM_BAR + (B_FULL + 2) * 8, (c.pf >> 2) & 1);
        c.pf ^= 4;
      }
      TS(1 + rnd * 3);
      FTM(rnd * 8 + 2);
      {
        float qa[64];
        float (&qb)[64] = O;
        {
          FTG(64); FTG(65);
          const uint32_t a = dk0 + 2 * DG, b = dm0 + 4 * DG;
          c.turn_begin();
          FTG(66);
          wg_fence();
          mma_ss_n128_init<1>(qa, a, b);
          mma_ss_n128_init<1>(qb, a + DG, b);
#pragma unroll
          for (int k = 1; k < 4; k++) {
            mma_ss_n128<1>(qa, a + k * 2, b + k * 128);
            mma_ss_n128<1>(qb, a + DG + k * 2, b + k * 128);
          }
          wg_commit();
          FTG(67);
        }
#pragma unroll 1
        for (int kb = 1; kb < 16; kb++) {
          const int g0 = 2 + 3 * (kb & 3);
          const uint32_t a = dk0 + g0 * DG, b = dm0 + (g0 + 2) * DG;
          const bool second = kb == 1 || kb == 15;
          FTG(64 + kb * 4);
          if (!second) { wg_wait<0>(); c.release(2 + 3 * ((kb - 1) & 3), 3); }
          FTG(65 + kb * 4);
          c.wait_full(g0);
          if (!second) c.turn_begin();
          FTG(66 + kb * 4);
          wg_fence();
#pragma unroll
          for (int k = 0; k < 4; k++) {
            mma_ss_n128<1>(qa, a + k * 2, b + k * 128);
            mma_ss_n128<1>(qb, a + DG + k * 2, b + k * 128);
          }
          wg_commit();
          if (kb != 14) c.turn_end();
          if (second) { wg_wait<1>(); c.release(2 + 3 * ((kb - 1) & 3), 3); }
          FTG(67 + kb * 4);
          if (kb == QFLUSH) { c.wait_stage_free(); stsm_frag<0, 4>(pv, stg); }
          if (kb == QFLUSH + 1) { stsm_frag<4, 8>(pv, stg); c.staged(0); }
        }
        c.wait_stage_free();
        mbar_wait(sb + SM_BAR + (B_EMPTY + 2) * 8, rnd ^ 1);
        c.wait_full(4);
        FTM(rnd * 8 + 3);
        wg_wait<0>();
        reg_fence(qa); reg_fence(qb);
        c.release(11, 3);
        pack_frag<0>(qa, pv);
        stsm_frag(pv, stg + 2 * GR);
        fence_async_smem();
      }
      TS(2 + rnd * 3);
      FTM(rnd * 8 + 4);
      {
        const int nA = idx + 1;
        uint32_t (&P)[32] = pv;
        SoftState z;
        z.m0 = z.m1 = z.l0 = z.l1 = 0.f; z.shifted = c.zero;
#pragma unroll 1
        for (int seg = c.zero;; seg++) {
        if (c.wg == 0) attn_half(c, O, P, z, dk0, dkk, dv0, dmask, seg, stg);
        if (seg) break;
        FTM(rnd * 8 + 5);
        int gk = c.wg ? 4 : 6, gv = c.wg ? 4 : 8;
        uint32_t dq = dk0 + (1 - c.wg < nA ? 2 * DG : 0), dk = dkk + gk * DG;
#pragma unroll 1
        for (int it = 1 - c.wg; it < 16 + c.wg; it++) {
          float S[64];
          FTA(it * 7 + 0);
          c.turn_begin();
          FTA(it * 7 + 2);
          wg_fence();
          issue_qk(S, dq, dk);
          wg_commit();
          const uint32_t dv = dv0 + gv * DG;
          uint32_t relk = c.relb + gk * 8, relv = c.relb + gv * 8;
          gk = it == 6 ? 12 : gv == 12 ? 4 : gv + 2;
          gv = it == 16 ? gk : gk == 12 ? 4 : gk + 2;
          uint32_t fk = sb + SM_BAR + (B_FULL + gk) * 8, fv = sb + SM_BAR + (B_FULL + gv) * 8, park = (c.pf >> gk) & 1, parv = (c.pf >> gv) & 1;
          c.pf ^= (1u << gk) | (1u << gv);
          dq = dk0 + (it + 1 < nA ? 2 * DG : 0); dk = dkk + gk * DG;
          float lo0 = z.l0, lo1 = z.l1;
          const bool first = it == nA || it == 0;
          if (it == nA) {
            if (EARLY_RCP) { lo0 = rcp(quad_sum(lo0)); lo1 = rcp(quad_sum(lo1)); }
            z.m0 = z.m1 = z.l0 = z.l1 = 0.f; z.shifted = 0;
          }
          float s0, s1, d0 = z.m0, d1 = z.m1;
          int pre = z.shifted || (it & 15) == 0;
          float lim = first ? -1.f : SM_LIMIT;
          asm volatile("" : "+r"(relk), "+r"(relv), "+r"(fk), "+r"(fv), "+r"(park), "+r"(parv), "+r"(dq), "+r"(dk), "+r"(pre), "+f"(lim), "+f"(d0), "+f"(d1), "+f"(z.l0), "+f"(z.l1));
          if (it) {
            issue_pv<0>(O, P, dv, it != nA + 1 && it != 1, true);
            issue_pv<1>(O, P, dv, 1, HALFPV ? it + c.wg > 1 : true);
            c.turn_end();
          } else stage_q2(c, O, P, stg);
          FTA(it * 7 + 3);
          wg_wait<4>();
          reg_fence(S);
          FTA(it * 7 + 4);
          if (c.tid < 4) asm volatile("mbarrier.arrive.shared::cluster.b64 _, [%0];" ::"r"(relk) : "memory");
#pragma unroll 1
          for (int pass = 0;; pass++) {
            if (pre) {
              if ((it & 15) == 0) mask_diag(S, dmask);
              if (z.shifted) shift_scores(S, d0, d1);
            }
            float tr[ROT];
            exp_quarter<0, 3>(S, P, tr, s0, s1, sb);
            exp_quarter<1, 2>(S, P, tr, s0, s1, sb);
            exp_quarter<2, 1>(S, P, tr, s0, s1, sb);
            exp_quarter<3, 0>(S, P, tr, s0, s1, sb);
            reg_fence(O);
            if (c.tid < (pass || !it ? 0 : 4)) asm volatile("mbarrier.arrive.shared::cluster.b64 _, [%0];" ::"r"(relv) : "memory");
            const bool ok = mbar_test(fk, park) & mbar_test(fv, parv);
            if (!ok) lim = -1.f;
            FTA(it * 7 + 5);
            if (!__any_sync(0xffffffffu, !(s0 <= lim && s1 <= lim))) break;
            if (pass) break;
            if (it == nA) {
              uint32_t pk[32];
              if (!EARLY_RCP) { lo0 = rcp(quad_sum(lo0)); lo1 = rcp(quad_sum(lo1)); }
              pack_frag_scaled(O, pk, lo0, lo1);
              stsm_frag(pk, stg + 2 * GR);
              c.staged(1);
            }
            mbar_wait(fk, park);
            mbar_wait(fv, parv);
            if (!soft_unsafe(s0, s1, first)) break;
            soft_fix(S, O, z, first, d0, d1);
            pre = 1;
          }
          z.l0 += s0; z.l1 += s1;
          FTA(it * 7 + 6);
        }
        FTM(rnd * 8 + 6);
        }
        c.turn_begin();
        wg_fence();
        issue_pv<0>(O, P, dv0 + 12 * DG, 1, true);
        issue_pv<1>(O, P, dv0 + 12 * DG, 1, c.wg);
        c.turn_end();
        z.l0 = rcp(quad_sum(z.l0)); z.l1 = rcp(quad_sum(z.l1));
        wg_wait<0>();
        reg_fence(O); reg_fence(P);
        c.release(12, 2);
        pack_frag_scaled(O, P, z.l0, z.l1);
        stsm_frag(P, stg);
        c.staged(0);
        FTM(rnd * 8 + 7);
      }
      TS(3 + rnd * 3);
    }
    conv_tasks(c, p, (cn + 1 - c.wg) / 2, ((cn - 1) & 1) == c.wg, spare, cch + c.wg * cstep, 2 * cstep, dkk, warp & 3, lane);
    if (c.wg == 1) c.pf ^= 0x4;
    TS(7);
    if (!spare) {
      const int rt = 2 * grp + rank, ct = idx;
      float acc[64];
      int g0 = P3G + 2, pg = P3G;
      {
        FTO(0);
        c.wait_full(P3G);
        FTO(1);
        const uint32_t a = dk0 + P3G * DG, b = dm0 + (P3G + 1) * DG;
        wg_fence();
        mma_ss_n128_init<1>(acc, a, b);
#pragma unroll
        for (int k = 1; k < 4; k++) mma_ss_n128<1>(acc, a + k * 2, b + k * 128);
        wg_commit();
      }
#pragma unroll 1
      for (int kb = 1; kb < 64; kb++) {
        FTO(kb * 2);
        c.wait_full(g0);
        FTO(kb * 2 + 1);
        const uint32_t a = dk0 + g0 * DG, b = dm0 + (g0 + 1) * DG;
        wg_fence();
#pragma unroll
        for (int k = 0; k < 4; k++) mma_ss_n128<1>(acc, a + k * 2, b + k * 128);
        wg_commit();
        wg_wait<1>();
        c.release(pg, kb <= 59 ? 2 : 0);
        if (kb == 40) FTDUMP();
        pg = g0;
        g0 = g0 == 12 ? (kb == 3 ? 2 : 0) : g0 + 2;
      }
      cluster_arrive();
      c.wait_full(P3X);
      c.wait_full(P3Y);
      const float g0f = __uint_as_float(lds32(sb + SM_GATE + row * 4)), g1f = __uint_as_float(lds32(sb + SM_GATE + row * 4 + 32));
      const uint32_t gp0 = pack_bf16(g0f, g0f), gp1 = pack_bf16(g1f, g1f);
      const float h0 = 1.f - g0f, h1 = 1.f - g1f;
      const int w = warp & 3;
      const uint32_t xa = stg + P3X * GR;
      const uint32_t ya = sb + P3Y * GR + c.wg * 16384 + ((lane >> 4) * 8 + (lane & 7)) * 128 + (((2 * w + ((lane >> 3) & 1)) ^ (lane & 7)) << 4);
      uint32_t xy[32];
#pragma unroll
      for (int jj = 0; jj < 8; jj++) {
        uint32_t x[4], y[4];
        asm volatile("ldmatrix.sync.aligned.m8n8.x4.shared.b16 {%0,%1,%2,%3}, [%4];" : "=r"(x[0]), "=r"(x[1]), "=r"(x[2]), "=r"(x[3]) : "r"((xa ^ ((jj & 3) << 5)) + (jj >> 2) * 16384) : "memory");
        asm volatile("ldmatrix.sync.aligned.m8n8.x4.trans.shared.b16 {%0,%1,%2,%3}, [%4];" : "=r"(y[0]), "=r"(y[1]), "=r"(y[2]), "=r"(y[3]) : "r"(ya + jj * 2048) : "memory");
#pragma unroll
        for (int i = 0; i < 4; i++) xy[4 * jj + i] = hmul2(x[i], y[i]);
      }
      wg_wait<0>();
      reg_fence(acc);
      TS(8);
#pragma unroll
      for (int i = 0; i < 32; i++) {
        const float h = (i & 1) ? h1 : h0;
        xy[i] = hfma2((i & 1) ? gp1 : gp0, xy[i], pack_bf16(acc[2 * i] * h, acc[2 * i + 1] * h));
      }
      stsm_frag(xy, xa);
      fence_async_smem();
      __syncwarp();
      if (lane == 0) {
        const int r0 = c.wg * 64 + w * 16;
        tma2d_store(&p.out, sb + P3X * GR + r0 * 128, ct * 128, rt * 128 + r0);
        tma2d_store(&p.out, sb + (P3X + 1) * GR + r0 * 128, ct * 128 + 64, rt * 128 + r0);
        asm volatile("cp.async.bulk.commit_group;\ncp.async.bulk.wait_group.read 0;" ::: "memory");
      }
    } else { FTDUMP(); cluster_arrive(); }
    if (lane == 0) mbar_arrive(sb + SM_BAR + B_DONE * 8);
    __syncwarp();
    TS(9);
    cluster_wait();
  }
}

typedef CUresult (*EncFn)(CUtensorMap*, CUtensorMapDataType, cuuint32_t, void*, const cuuint64_t*, const cuuint64_t*, const cuuint32_t*,
                          const cuuint32_t*, CUtensorMapInterleave, CUtensorMapSwizzle, CUtensorMapL2promotion, CUtensorMapFloatOOBfill);

void enc2d(EncFn enc, CUtensorMap* tm, const void* base, uint64_t cols, uint64_t rows, uint32_t bc, uint32_t br) {
  cuuint64_t dims[2] = {cols, rows}; cuuint64_t strides[1] = {cols * 2}; cuuint32_t box[2] = {bc, br}; cuuint32_t es[2] = {1, 1};
  enc(tm, CU_TENSOR_MAP_DATA_TYPE_BFLOAT16, 2, const_cast<void*>(base), dims, strides, box, es, CU_TENSOR_MAP_INTERLEAVE_NONE,
      CU_TENSOR_MAP_SWIZZLE_128B, CU_TENSOR_MAP_L2_PROMOTION_L2_256B, CU_TENSOR_MAP_FLOAT_OOB_FILL_NONE);
}
void enc3d(EncFn enc, CUtensorMap* tm, const void* base, uint64_t K, uint64_t N) {
  cuuint64_t dims[3] = {64, K, N / 64}; cuuint64_t strides[2] = {N * 2, 128}; cuuint32_t box[3] = {64, 64, 2}; cuuint32_t es[3] = {1, 1, 1};
  enc(tm, CU_TENSOR_MAP_DATA_TYPE_BFLOAT16, 3, const_cast<void*>(base), dims, strides, box, es, CU_TENSOR_MAP_INTERLEAVE_NONE,
      CU_TENSOR_MAP_SWIZZLE_128B, CU_TENSOR_MAP_L2_PROMOTION_L2_256B, CU_TENSOR_MAP_FLOAT_OOB_FILL_NONE);
}

}

extern "C" void kernel_launch(void* const* d_in, const int* in_sizes, int n_in, void* d_out, int out_size) {
  (void)in_sizes; (void)n_in; (void)out_size;
  typedef const __nv_bfloat16* BP;
  BP xq = (BP)d_in[0], ak = (BP)d_in[1], av = (BP)d_in[2], shk = (BP)d_in[3], ssk = (BP)d_in[4], ssd = (BP)d_in[5];
  BP ckv = (BP)d_in[7], wq = (BP)d_in[8], wuk = (BP)d_in[9], wuv = (BP)d_in[10], wo = (BP)d_in[11], gw = (BP)d_in[12];

  static EncFn enc = nullptr;
  if (!enc) {
    cudaDriverEntryPointQueryResult qr;
    cudaGetDriverEntryPoint("cuTensorMapEncodeTiled", (void**)&enc, cudaEnableDefault, &qr);
    cudaFuncSetAttribute(mega_kernel, cudaFuncAttributeMaxDynamicSharedMemorySize, SMEM_BYTES);
  }
  Params p;
  void* yT = nullptr;
  cudaGetSymbolAddress(&yT, g_yT);
  enc2d(enc, &p.x, xq, DM, SEQ, 64, 128);
  enc2d(enc, &p.c, ckv, DC, SEQ, 64, 128);
  enc3d(enc, &p.wq, wq, DM, NH * HD);
  enc3d(enc, &p.wuk, wuk, DC, NH * HD);
  enc3d(enc, &p.wuv, wuv, DC, NH * HD);
  enc2d(enc, &p.wo, wo, DM, NH * HD, 64, 64);
  enc2d(enc, &p.y, yT, SEQ, DM, 64, 128);
  enc2d(enc, &p.out, d_out, DM, SEQ, 64, 16);
  {
    void* wp = nullptr;
    cudaGetSymbolAddress(&wp, g_w);
    cuuint64_t dims[3] = {WSTRIDE / 2, DM / 2, 2}; cuuint64_t strides[2] = {2 * WSTRIDE, WSTRIDE}; cuuint32_t box[3] = {16, 32, 2}; cuuint32_t es[3] = {1, 1, 1};
    enc(&p.w, CU_TENSOR_MAP_DATA_TYPE_BFLOAT16, 3, wp, dims, strides, box, es, CU_TENSOR_MAP_INTERLEAVE_NONE,
        CU_TENSOR_MAP_SWIZZLE_32B, CU_TENSOR_MAP_L2_PROMOTION_NONE, CU_TENSOR_MAP_FLOAT_OOB_FILL_NONE);
  }
  p.zero = 0;
  p.cp = ckv; p.wukp = wuk; p.wuvp = wuv;
  p.xp = xq; p.gate_w = gw; p.ak = ak; p.av = av; p.shk = shk; p.ssk = ssk; p.ssd = ssd;

  mega_kernel<<<132, NTHREADS, SMEM_BYTES>>>(p);
}
```

```cpp
#include <cuda_runtime.h>
#include <cuda.h>
#include <cuda_bf16.h>
#include <stdint.h>

namespace {

constexpr int SEQ = 2048, DM = 1024, DC = 512, NH = 32, HD = 128;
constexpr int GR = 16384;
constexpr int NGR = 14;
constexpr int SM_BAR = NGR * GR;
constexpr int SM_GATE = SM_BAR + 512;
constexpr int SM_UST = SM_GATE + 512;
constexpr int SMEM_BYTES = SM_UST + 2048;
constexpr int NTHREADS = 384;
#define SM_LIMIT 1.0995116e12f
#define SM_LOW 9.094947e-13f
constexpr int CN_MAIN = 5, CN_SPARE = 96;
constexpr int P3G = 6, P3X = 10, P3Y = 12;
constexpr int NMAIN = 128;

constexpr int B_FULL = 0, B_EMPTY = 14, B_EV = 28, B_DONE = 34;

__device__ __align__(1024) uint8_t g_kv[2 * 16 * 16 * 32768];
__device__ __align__(1024) uint8_t g_cimg[16 * NH * 32768];
__device__ __align__(1024) __nv_bfloat16 g_yT[DM * SEQ];
__device__ __align__(1024) float g_gate[SEQ];
constexpr int WSTRIDE = 8832, WBYTES = 8736;
__device__ __align__(1024) uint8_t g_w[DM * WSTRIDE];
__device__ unsigned g_flags[128 * 8];
constexpr int F_KV = 0, F_CTX = 16, F_U = 48, F_AD = 56, F_Y = 64, F_GATE = 72, F_EXIT = 73;
#define FLAG(i) (&g_flags[(i) * 8])

#define TS(slot)
#define TSW(slot)
#define FTX(i, off)
#define FTDUMP()

#define ST_OUT 0
#define QFLUSH 4
#define POL_W EV_NORMAL
#define POL_WO EV_FIRST
#define POL_KV EV_NORMAL
#define POL_C EV_FIRST
#define POL_CTX EV_FIRST
#define HALFPV 0
#define PWAIT mbar_wait1
#define PRE_SLEEP 1500
#define EXPV 1
#define START_PF 1
#define SUMV 0
#define ROT 8
#define EARLY_RCP 1
#define FINE_MODE 0
#define FINE_RND 1
#define FTA(i) do { if (FINE_MODE == 0) FTX(i, rnd ^ FINE_RND); } while (0)
#define FTG(i) do { if (FINE_MODE == 1) FTX(i, rnd ^ FINE_RND); } while (0)
#define FTM(i) do { if (FINE_MODE == 4) FTX(i, 0); } while (0)
#define FTC(k) do { if (FINE_MODE == 5) FTX((i & 7) * 8 + (k), (i >> 3) ^ FINE_RND); } while (0)
#define FTH(i, off) do { if (FINE_MODE == 6) FTX(i, (c.rnd ^ FINE_RND) | (off)); } while (0)
#define FTO(i) do { if (FINE_MODE == 2) FTX(i, 0); } while (0)

__device__ __forceinline__ uint32_t smem_u32(const void* p) { return (uint32_t)__cvta_generic_to_shared(p); }
__device__ __forceinline__ void mbar_init(uint32_t bar, int cnt) { asm volatile("mbarrier.init.shared::cta.b64 [%0], %1;" ::"r"(bar), "r"(cnt) : "memory"); }
__device__ __forceinline__ void mbar_expect_tx(uint32_t bar, uint32_t bytes) { asm volatile("mbarrier.arrive.expect_tx.shared::cta.b64 _, [%0], %1;" ::"r"(bar), "r"(bytes) : "memory"); }
__device__ __forceinline__ void mbar_arrive(uint32_t bar) { asm volatile("mbarrier.arrive.shared::cta.b64 _, [%0];" ::"r"(bar) : "memory"); }
__device__ __forceinline__ void mbar_arrive_cluster(uint32_t bar, uint32_t cta) {
  asm volatile("{\n.reg .b32 r;\nmapa.shared::cluster.u32 r, %0, %1;\nmbarrier.arrive.shared::cluster.b64 _, [r];\n}\n" ::"r"(bar), "r"(cta) : "memory");
}
__device__ __forceinline__ bool mbar_try(uint32_t bar, uint32_t parity) {
  uint32_t ok;
  asm volatile("{\n.reg .pred p;\nmbarrier.try_wait.parity.shared::cta.b64 p, [%1], %2, 20000;\nselp.u32 %0, 1, 0, p;\n}\n" : "=r"(ok) : "r"(bar), "r"(parity) : "memory");
  return ok;
}
__device__ __forceinline__ bool mbar_test(uint32_t bar, uint32_t parity) {
  uint32_t ok;
  asm volatile("{\n.reg .pred p;\nmbarrier.test_wait.parity.shared::cta.b64 p, [%1], %2;\nselp.u32 %0, 1, 0, p;\n}\n" : "=r"(ok) : "r"(bar), "r"(parity) : "memory");
  return ok;
}
__device__ __forceinline__ void mbar_wait(uint32_t bar, uint32_t parity) {
  asm volatile("{\n.reg .pred p;\nWAIT_LOOP:\nbar.warp.sync -1;\nmbarrier.try_wait.parity.shared::cta.b64 p, [%0], %1;\n@!p bra WAIT_LOOP;\n}\n" ::"r"(bar), "r"(parity) : "memory");
}
__device__ __forceinline__ void mbar_wait1(uint32_t bar, uint32_t parity) {
  asm volatile("{\n.reg .pred p;\nWAIT_LOOP:\nbar.warp.sync -1;\nmbarrier.try_wait.parity.shared::cta.b64 p, [%0], %1, 4000;\n@!p bra WAIT_LOOP;\n}\n" ::"r"(bar), "r"(parity) : "memory");
}
constexpr uint64_t EV_NORMAL = 0x1000000000000000ull, EV_FIRST = 0x12F0000000000000ull;
__device__ __forceinline__ uint32_t ldg_stream(const uint32_t* p) {
  uint32_t r; asm volatile("ld.global.nc.L1::no_allocate.L2::cache_hint.b32 %0, [%1], %2;" : "=r"(r) : "l"(p), "l"(EV_FIRST)); return r;
}
__device__ __forceinline__ void tma2d(uint32_t dst, const CUtensorMap* tm, int c0, int c1, uint32_t bar, uint64_t pol) {
  asm volatile("cp.async.bulk.tensor.2d.shared::cluster.global.mbarrier::complete_tx::bytes.L2::cache_hint [%0], [%1, {%3, %4}], [%2], %5;"
               ::"r"(dst), "l"(tm), "r"(bar), "r"(c0), "r"(c1), "l"(pol) : "memory");
}
__device__ __forceinline__ void tma2d_mc(uint32_t dst, const CUtensorMap* tm, int c0, int c1, uint32_t bar, uint64_t pol) {
  asm volatile("cp.async.bulk.tensor.2d.shared::cluster.global.mbarrier::complete_tx::bytes.multicast::cluster.L2::cache_hint [%0], [%1, {%3, %4}], [%2], %5, %6;"
               ::"r"(dst), "l"(tm), "r"(bar), "r"(c0), "r"(c1), "h"((uint16_t)3), "l"(pol) : "memory");
}
__device__ __forceinline__ void tma3d(uint32_t dst, const CUtensorMap* tm, int c0, int c1, int c2, uint32_t bar, uint64_t pol) {
  asm volatile("cp.async.bulk.tensor.3d.shared::cluster.global.mbarrier::complete_tx::bytes.L2::cache_hint [%0], [%1, {%3, %4, %5}], [%2], %6;"
               ::"r"(dst), "l"(tm), "r"(bar), "r"(c0), "r"(c1), "r"(c2), "l"(pol) : "memory");
}
__device__ __forceinline__ void tma3d_mc(uint32_t dst, const CUtensorMap* tm, int c0, int c1, int c2, uint32_t bar, uint64_t pol) {
  asm volatile("cp.async.bulk.tensor.3d.shared::cluster.global.mbarrier::complete_tx::bytes.multicast::cluster.L2::cache_hint [%0], [%1, {%3, %4, %5}], [%2], %6, %7;"
               ::"r"(dst), "l"(tm), "r"(bar), "r"(c0), "r"(c1), "r"(c2), "h"((uint16_t)3), "l"(pol) : "memory");
}
__device__ __forceinline__ void bulk_g2s(uint32_t dst, const void* src, uint32_t bytes, uint32_t bar, uint64_t pol) {
  asm volatile("cp.async.bulk.shared::cluster.global.mbarrier::complete_tx::bytes.L2::cache_hint [%0], [%1], %2, [%3], %4;"
               ::"r"(dst), "l"(src), "r"(bytes), "r"(bar), "l"(pol) : "memory");
}
__device__ __forceinline__ void tma2d_store(const CUtensorMap* tm, uint32_t src, int c0, int c1) {
  asm volatile("cp.async.bulk.tensor.2d.global.shared::cta.bulk_group [%0, {%2, %3}], [%1];" ::"l"(tm), "r"(src), "r"(c0), "r"(c1) : "memory");
}
__device__ __forceinline__ void prefetch_tm(const CUtensorMap* tm) { asm volatile("prefetch.tensormap [%0];" ::"l"(tm) : "memory"); }
__device__ __forceinline__ void wg_fence() { asm volatile("wgmma.fence.sync.aligned;" ::: "memory"); }
__device__ __forceinline__ void wg_commit() { asm volatile("wgmma.commit_group.sync.aligned;" ::: "memory"); }
template <int N> __device__ __forceinline__ void wg_wait() { asm volatile("wgmma.wait_group.sync.aligned %0;" ::"n"(N) : "memory"); }
__device__ __forceinline__ void bar_sync(int id, int n) { asm volatile("bar.sync %0, %1;" ::"r"(id), "r"(n) : "memory"); }
__device__ __forceinline__ void bar_arrive(int id, int n) { asm volatile("bar.arrive %0, %1;" ::"r"(id), "r"(n) : "memory"); }
__device__ __forceinline__ void fence_async_smem() { asm volatile("fence.proxy.async.shared::cta;" ::: "memory"); }
__device__ __forceinline__ void fence_async_all() { asm volatile("fence.proxy.async.global;" ::: "memory"); }
__device__ __forceinline__ uint32_t pack_bf16(float lo, float hi) { uint32_t r; asm("cvt.rn.bf16x2.f32 %0, %1, %2;" : "=r"(r) : "f"(hi), "f"(lo)); return r; }
__device__ __forceinline__ float ex2(float x) { float r; asm("ex2.approx.ftz.f32 %0, %1;" : "=f"(r) : "f"(x)); return r; }
__device__ __forceinline__ float rcp(float x) { float r; asm("rcp.approx.ftz.f32 %0, %1;" : "=f"(r) : "f"(x)); return r; }
__device__ __forceinline__ void flag_wait(const unsigned* f, unsigned target) {
  unsigned v;
  do { asm volatile("ld.acquire.gpu.global.u32 %0, [%1];" : "=r"(v) : "l"(f) : "memory"); } while (__any_sync(0xffffffffu, v < target));
}
__device__ __forceinline__ bool elect() {
  uint32_t r;
  asm volatile("{\n.reg .pred p;\nelect.sync _|p, -1;\nselp.u32 %0, 1, 0, p;\n}\n" : "=r"(r));
  return r;
}
__device__ __forceinline__ void fence_release() { asm volatile("fence.release.gpu;" ::: "memory"); }
__device__ __forceinline__ void flag_add(unsigned* f) { asm volatile("red.relaxed.gpu.global.add.u32 [%0], 1;" ::"l"(f) : "memory"); }
__device__ __forceinline__ void cluster_arrive() { asm volatile("barrier.cluster.arrive.relaxed.aligned;" ::: "memory"); }
__device__ __forceinline__ void cluster_wait() { asm volatile("barrier.cluster.wait.aligned;" ::: "memory"); }
__device__ __forceinline__ uint32_t hmul2(uint32_t a, uint32_t b) { uint32_t r; asm("mul.rn.bf16x2 %0, %1, %2;" : "=r"(r) : "r"(a), "r"(b)); return r; }
__device__ __forceinline__ uint32_t hadd2(uint32_t a, uint32_t b) { uint32_t r; asm("add.rn.bf16x2 %0, %1, %2;" : "=r"(r) : "r"(a), "r"(b)); return r; }
__device__ __forceinline__ uint32_t hfma2(uint32_t a, uint32_t b, uint32_t c) { uint32_t r; asm("fma.rn.bf16x2 %0, %1, %2, %3;" : "=r"(r) : "r"(a), "r"(b), "r"(c)); return r; }
__device__ __forceinline__ uint32_t lds32(uint32_t a) { uint32_t r; asm volatile("ld.shared.b32 %0, [%1];" : "=r"(r) : "r"(a) : "memory"); return r; }
__device__ __forceinline__ uint4 lds128(uint32_t a) { uint4 r; asm volatile("ld.shared.v4.b32 {%0,%1,%2,%3}, [%4];" : "=r"(r.x), "=r"(r.y), "=r"(r.z), "=r"(r.w) : "r"(a) : "memory"); return r; }
__device__ __forceinline__ uint32_t desc_k(uint32_t addr) { return ((addr & 0x3FFFF) >> 4) | (1u << 16); }
template <int LBO> __device__ __forceinline__ uint32_t desc_mn(uint32_t addr) { return ((addr & 0x3FFFF) >> 4) | ((uint32_t)(LBO >> 4) << 16); }
#define DHI "0x40000040"

#define R8(d, o) "+f"(d[o]), "+f"(d[o + 1]), "+f"(d[o + 2]), "+f"(d[o + 3]), "+f"(d[o + 4]), "+f"(d[o + 5]), "+f"(d[o + 6]), "+f"(d[o + 7])
#define R32(d, o) R8(d, o), R8(d, o + 8), R8(d, o + 16), R8(d, o + 24)
#define R64(d, o) R32(d, o), R32(d, o + 32)
#define L64 "%0,%1,%2,%3,%4,%5,%6,%7,%8,%9,%10,%11,%12,%13,%14,%15,%16,%17,%18,%19,%20,%21,%22,%23,%24,%25,%26,%27,%28,%29,%30,%31," \
            "%32,%33,%34,%35,%36,%37,%38,%39,%40,%41,%42,%43,%44,%45,%46,%47,%48,%49,%50,%51,%52,%53,%54,%55,%56,%57,%58,%59,%60,%61,%62,%63"
#define L128 L64 ",%64,%65,%66,%67,%68,%69,%70,%71,%72,%73,%74,%75,%76,%77,%78,%79,%80,%81,%82,%83,%84,%85,%86,%87,%88,%89,%90,%91,%92,%93,%94,%95," \
            "%96,%97,%98,%99,%100,%101,%102,%103,%104,%105,%106,%107,%108,%109,%110,%111,%112,%113,%114,%115,%116,%117,%118,%119,%120,%121,%122,%123,%124,%125,%126,%127"

template <int TB> __device__ __forceinline__ void mma_ss_n128(float (&d)[64], uint32_t da, uint32_t db) {
  asm volatile("{\n.reg .b64 da, db;\nmov.b64 da, {%64, " DHI "};\nmov.b64 db, {%65, " DHI "};\n"
               "wgmma.mma_async.sync.aligned.m64n128k16.f32.bf16.bf16 {" L64 "}, da, db, 1, 1, 1, 0, %66;\n}\n"
               : R64(d, 0) : "r"(da), "r"(db), "n"(TB));
}
template <int TB> __device__ __forceinline__ void mma_rs_n128(float (&d)[64], uint32_t a0, uint32_t a1, uint32_t a2, uint32_t a3, uint32_t db, int sd) {
  asm volatile("{\n.reg .pred p;\n.reg .b64 db;\nsetp.ne.b32 p, %69, 0;\nmov.b64 db, {%68, " DHI "};\n"
               "wgmma.mma_async.sync.aligned.m64n128k16.f32.bf16.bf16 {" L64 "}, {%64,%65,%66,%67}, db, p, 1, 1, %70;\n}\n"
               : R64(d, 0) : "r"(a0), "r"(a1), "r"(a2), "r"(a3), "r"(db), "r"(sd), "n"(TB));
}
template <int TB> __device__ __forceinline__ void mma_ss_n256(float (&d)[128], uint32_t da, uint32_t db) {
  asm volatile("{\n.reg .b64 da, db;\nmov.b64 da, {%128, " DHI "};\nmov.b64 db, {%129, " DHI "};\n"
               "wgmma.mma_async.sync.aligned.m64n256k16.f32.bf16.bf16 {" L128 "}, da, db, 1, 1, 1, 0, %130;\n}\n"
               : R64(d, 0), R64(d, 64) : "r"(da), "r"(db), "n"(TB));
}
#define W8(d, o) "=f"(d[o]), "=f"(d[o + 1]), "=f"(d[o + 2]), "=f"(d[o + 3]), "=f"(d[o + 4]), "=f"(d[o + 5]), "=f"(d[o + 6]), "=f"(d[o + 7])
#define W32(d, o) W8(d, o), W8(d, o + 8), W8(d, o + 16), W8(d, o + 24)
#define W64(d, o) W32(d, o), W32(d, o + 32)
template <int TB> __device__ __forceinline__ void mma_ss_n128_init(float (&d)[64], uint32_t da, uint32_t db) {
  asm volatile("{\n.reg .b64 da, db;\nmov.b64 da, {%64, " DHI "};\nmov.b64 db, {%65, " DHI "};\n"
               "wgmma.mma_async.sync.aligned.m64n128k16.f32.bf16.bf16 {" L64 "}, da, db, 0, 1, 1, 0, %66;\n}\n"
               : W64(d, 0) : "r"(da), "r"(db), "n"(TB));
}
template <int TB> __device__ __forceinline__ void mma_ss_n256_init(float (&d)[128], uint32_t da, uint32_t db) {
  asm volatile("{\n.reg .b64 da, db;\nmov.b64 da, {%128, " DHI "};\nmov.b64 db, {%129, " DHI "};\n"
               "wgmma.mma_async.sync.aligned.m64n256k16.f32.bf16.bf16 {" L128 "}, da, db, 0, 1, 1, 0, %130;\n}\n"
               : W64(d, 0), W64(d, 64) : "r"(da), "r"(db), "n"(TB));
}
#define L32 "%0,%1,%2,%3,%4,%5,%6,%7,%8,%9,%10,%11,%12,%13,%14,%15,%16,%17,%18,%19,%20,%21,%22,%23,%24,%25,%26,%27,%28,%29,%30,%31"
__device__ __forceinline__ void mma_ss_n64(float (&d)[32], uint32_t da, uint32_t db) {
  asm volatile("{\n.reg .b64 da, db;\nmov.b64 da, {%32, " DHI "};\nmov.b64 db, {%33, " DHI "};\n"
               "wgmma.mma_async.sync.aligned.m64n64k16.f32.bf16.bf16 {" L32 "}, da, db, 1, 1, 1, 0, 0;\n}\n"
               : R32(d, 0) : "r"(da), "r"(db));
}
__device__ __forceinline__ void mma_ss_n64_init(float (&d)[32], uint32_t da, uint32_t db) {
  asm volatile("{\n.reg .b64 da, db;\nmov.b64 da, {%32, " DHI "};\nmov.b64 db, {%33, " DHI "};\n"
               "wgmma.mma_async.sync.aligned.m64n64k16.f32.bf16.bf16 {" L32 "}, da, db, 0, 1, 1, 0, 0;\n}\n"
               : W32(d, 0) : "r"(da), "r"(db));
}
#define L16 "%0,%1,%2,%3,%4,%5,%6,%7,%8,%9,%10,%11,%12,%13,%14,%15"
__device__ __forceinline__ void mma_rs_n32(float (&d)[16], uint32_t a0, uint32_t a1, uint32_t a2, uint32_t a3, uint32_t db) {
  asm volatile("{\n.reg .b64 db;\nmov.b64 db, {%20, 0x00000008};\n"
               "wgmma.mma_async.sync.aligned.m64n32k16.f32.bf16.bf16 {" L16 "}, {%16,%17,%18,%19}, db, 1, 1, 1, 0;\n}\n"
               : R8(d, 0), R8(d, 8) : "r"(a0), "r"(a1), "r"(a2), "r"(a3), "r"(db));
}
__device__ __forceinline__ void mma_rs_n32_init(float (&d)[16], uint32_t a0, uint32_t a1, uint32_t a2, uint32_t a3, uint32_t db) {
  asm volatile("{\n.reg .b64 db;\nmov.b64 db, {%20, 0x00000008};\n"
               "wgmma.mma_async.sync.aligned.m64n32k16.f32.bf16.bf16 {" L16 "}, {%16,%17,%18,%19}, db, 0, 1, 1, 0;\n}\n"
               : W8(d, 0), W8(d, 8) : "r"(a0), "r"(a1), "r"(a2), "r"(a3), "r"(db));
}
__device__ __forceinline__ void mma_ss_n8(float (&d)[4], uint32_t da, uint32_t db) {
  asm volatile("{\n.reg .b64 da, db;\nmov.b64 da, {%4, " DHI "};\nmov.b64 db, {%5, 0x00000008};\n"
               "wgmma.mma_async.sync.aligned.m64n8k16.f32.bf16.bf16 {%0,%1,%2,%3}, da, db, 1, 1, 1, 0, 0;\n}\n"
               : "+f"(d[0]), "+f"(d[1]), "+f"(d[2]), "+f"(d[3]) : "r"(da), "r"(db));
}
template <int N> __device__ __forceinline__ void reg_fence(float (&d)[N]) {
#pragma unroll
  for (int i = 0; i < N; i++) asm volatile("" : "+f"(d[i])::"memory");
}
template <int N> __device__ __forceinline__ void reg_fence(uint32_t (&d)[N]) {
#pragma unroll
  for (int i = 0; i < N; i++) asm volatile("" : "+r"(d[i])::"memory");
}

struct __align__(64) Params {
  CUtensorMap x, c, wq, wuk, wuv, wo, y, out, w;
  const __nv_bfloat16* xp;
  const __nv_bfloat16* gate_w;
  const __nv_bfloat16 *ak, *av, *shk, *ssk, *ssd, *cp, *wukp, *wuvp;
  int zero;
};

template <int O, int N, int M> __device__ __forceinline__ void pack_frag(const float (&acc)[N], uint32_t (&pk)[M]) {
#pragma unroll
  for (int i = 0; i < 32; i++) pk[i] = pack_bf16(acc[O + 2 * i], acc[O + 2 * i + 1]);
}
template <int N> __device__ __forceinline__ void pack_frag_scaled(const float (&acc)[N], uint32_t (&pk)[32], float s0, float s1) {
#pragma unroll
  for (int i = 0; i < 32; i++) { const float s = (i & 1) ? s1 : s0; pk[i] = pack_bf16(acc[2 * i] * s, acc[2 * i + 1] * s); }
}
template <int J0 = 0, int J1 = 8, int M> __device__ __forceinline__ void stsm_frag(const uint32_t (&pk)[M], uint32_t a) {
#pragma unroll
  for (int jj = J0; jj < J1; jj++)
    asm volatile("stmatrix.sync.aligned.m8n8.x4.shared.b16 [%0], {%1,%2,%3,%4};" ::"r"((a ^ ((jj & 3) << 5)) + (jj >> 2) * 16384),
                 "r"(pk[4 * jj]), "r"(pk[4 * jj + 1]), "r"(pk[4 * jj + 2]), "r"(pk[4 * jj + 3]) : "memory");
}

struct Cons {
  uint32_t sb;
  uint32_t pf;
  int wg, tid;
  __device__ __forceinline__ void wait_full(int g) { mbar_wait(sb + SM_BAR + (B_FULL + g) * 8, (pf >> g) & 1); pf ^= 1u << g; }
  uint32_t relb;
  __device__ __forceinline__ void release(int g, int n) {
    if (tid < 2 * n) asm volatile("mbarrier.arrive.shared::cluster.b64 _, [%0];" ::"r"(relb + g * 8) : "memory");
  }
  __device__ __forceinline__ void turn_begin() { bar_sync(1 + wg, 256); }
  __device__ __forceinline__ void turn_end() { bar_arrive(2 - wg, 256); }
  __device__ __forceinline__ void staged(int e) { __syncwarp(); if ((tid & 31) == 0) mbar_arrive(sb + SM_BAR + (B_EV + 2 * e + wg) * 8); }
  int zero;
  int rnd;
  uint32_t pfree;
  __device__ __forceinline__ void wait_stage_free() { mbar_wait(sb + SM_BAR + (B_EV + 4 + wg) * 8, pfree); pfree ^= 1; }
  __device__ __forceinline__ bool try_full(int g) { return mbar_test(sb + SM_BAR + (B_FULL + g) * 8, (pf >> g) & 1); }
};

constexpr float SM_C = 0.08838834764831845f * 1.4426950408889634f;
struct SoftState { float m0, m1, l0, l1; int shifted; };
__device__ __forceinline__ void ex2_rot(float& t, float s, uint32_t never_zero) {
  asm("{\n.reg .pred p;\nsetp.ne.u32 p, %2, 0;\n@p ex2.approx.ftz.f32 %0, %1;\n}\n" : "+f"(t) : "f"(s), "r"(never_zero));
}
__device__ __forceinline__ void pin(float a, uint32_t never_zero) {
  asm volatile("{\n.reg .pred p;\nsetp.eq.u32 p, %1, 0;\n@p st.shared.f32 [%1], %0;\n}\n" ::"f"(a), "r"(never_zero) : "memory");
}
template <int O, int N> __device__ __forceinline__ void reg_fence_part(uint32_t (&d)[32]) {
#pragma unroll
  for (int i = O; i < O + N; i++) asm volatile("" : "+r"(d[i])::"memory");
}
template <int Q, int W, int N> __device__ __forceinline__ void exp_quarter(const float (&S)[N], uint32_t (&P)[32], float (&t)[ROT], float& s0, float& s1, uint32_t nz) {
#pragma unroll
  for (int i = 8 * Q; i < 8 * Q + 8; i++) {
    float& a = t[(2 * i) % ROT];
    float& b = t[(2 * i + 1) % ROT];
    if (2 * i < ROT) { a = ex2(S[2 * i]); b = ex2(S[2 * i + 1]); }
    else { ex2_rot(a, S[2 * i], nz); ex2_rot(b, S[2 * i + 1], nz); }
    if (i < 2) { if (i) s1 = a + b; else s0 = a + b; }
    else if (SUMV == 0) { if (i & 1) { s1 += a; s1 += b; } else { s0 += a; s0 += b; } }
    else { if (i & 1) s1 += a + b; else s0 += a + b; }
    if (i == 8 * Q) { pin(EXPV == 1 && Q ? s1 : s0, nz); wg_wait<W>(); reg_fence_part<8 * Q, 8>(P); }
    P[i] = pack_bf16(a, b);
  }
}
template <int N> __device__ __forceinline__ void shift_scores(float (&S)[N], float d0, float d1) {
#pragma unroll
  for (int i = 0; i < N; i++) S[i] -= (i & 2) ? d1 : d0;
}
__device__ __forceinline__ bool soft_high(float s0, float s1, float lim = SM_LIMIT) { return s0 > lim || s1 > lim; }
__device__ __forceinline__ bool soft_unsafe(float s0, float s1, bool first) {
  uint32_t b0 = __ballot_sync(0xffffffffu, s0 >= SM_LOW), b1 = __ballot_sync(0xffffffffu, s1 >= SM_LOW);
  b0 |= b0 >> 1; b0 |= b0 >> 2; b1 |= b1 >> 1; b1 |= b1 >> 2;
  return __any_sync(0xffffffffu, soft_high(s0, s1)) || (first && (b0 & b1 & 0x11111111u) != 0x11111111u);
}
template <int N> __device__ __forceinline__ void soft_fix(const float (&S)[N], float (&O)[64], SoftState& z, bool first, float& d0, float& d1) {
  d0 = d1 = first ? -INFINITY : 0.f;
#pragma unroll
  for (int j = 0; j < N / 4; j++) { d0 = fmaxf(d0, fmaxf(S[4 * j], S[4 * j + 1])); d1 = fmaxf(d1, fmaxf(S[4 * j + 2], S[4 * j + 3])); }
  d0 = fmaxf(d0, __shfl_xor_sync(0xffffffffu, d0, 1)); d1 = fmaxf(d1, __shfl_xor_sync(0xffffffffu, d1, 1));
  d0 = fmaxf(d0, __shfl_xor_sync(0xffffffffu, d0, 2)); d1 = fmaxf(d1, __shfl_xor_sync(0xffffffffu, d1, 2));
  const float sc0 = ex2(-fmaxf(d0, 0.f)), sc1 = ex2(-fmaxf(d1, 0.f));
  z.m0 += d0; z.m1 += d1; z.l0 *= sc0; z.l1 *= sc1; z.shifted = 1;
#pragma unroll
  for (int j = 0; j < 16; j++) { O[4 * j] *= sc0; O[4 * j + 1] *= sc0; O[4 * j + 2] *= sc1; O[4 * j + 3] *= sc1; }
}
template <int M> __device__ __forceinline__ void pin32(const uint32_t (&v)[M], uint32_t never_zero) {
#pragma unroll
  for (int i = 0; i < 32; i += 4)
    asm volatile("{\n.reg .pred p;\nsetp.eq.u32 p, %4, 0;\n@p st.shared.v4.b32 [%4], {%0,%1,%2,%3};\n}\n" ::"r"(v[i]), "r"(v[i + 1]), "r"(v[i + 2]), "r"(v[i + 3]), "r"(never_zero) : "memory");
}
template <int N> __device__ __forceinline__ void mask_diag(float (&S)[N], float nd) {
  asm volatile("" : "+f"(nd));
#pragma unroll
  for (int i = 0; i < 32; i++) {
    const float beyond = __saturatef(nd + (float)(8 * (i >> 2) + (i & 1) - 4 * (i & 2)));
    S[N - 32 + i] = fmaf(beyond, -3.0e38f, S[N - 32 + i]);
  }
}
__device__ __forceinline__ float quad_sum(float v) {
  v += __shfl_xor_sync(0xffffffffu, v, 1);
  v += __shfl_xor_sync(0xffffffffu, v, 2);
  return v;
}
__device__ __forceinline__ void issue_qk(float (&S)[64], uint32_t dq, uint32_t dk) {
  mma_ss_n128_init<0>(S, dq, dk);
#pragma unroll
  for (int s = 1; s < 8; s++) mma_ss_n128<0>(S, dq + (s >> 2) * 1024 + (s & 3) * 2, dk + (s >> 2) * 1024 + (s & 3) * 2);
}
__device__ __forceinline__ void issue_qk(float (&S)[32], uint32_t dq, uint32_t dk) {
  mma_ss_n64_init(S, dq, dk);
#pragma unroll
  for (int s = 1; s < 8; s++) mma_ss_n64(S, dq + (s >> 2) * 1024 + (s & 3) * 2, dk + (s >> 2) * 1024 + (s & 3) * 2);
}
template <int H> __device__ __forceinline__ void issue_pv(float (&O)[64], const uint32_t (&P)[32], uint32_t dv, int acc, bool on) {
  if (on) {
#pragma unroll
    for (int s = 4 * H; s < 4 * H + 4; s++) {
      mma_rs_n128<1>(O, P[4 * s], P[4 * s + 1], P[4 * s + 2], P[4 * s + 3], dv + s * 128, s != 0 ? 1 : acc);
      if (s & 1) wg_commit();
    }
  } else { wg_commit(); wg_commit(); }
}
constexpr uint32_t DG = GR >> 4;
__device__ __forceinline__ void stage_q2(Cons& c, const float (&O)[64], uint32_t (&P)[32], uint32_t stg) {
  wg_commit(); wg_commit(); wg_commit(); wg_commit();
  c.turn_end();
  pack_frag<0>(O, P);
  stsm_frag(P, stg);
  fence_async_smem();
}
__device__ __forceinline__ void attn_half(Cons& c, float (&O)[64], uint32_t (&P)[32], SoftState& z, uint32_t dk0, uint32_t dkk, uint32_t dv0, float dmask, int last) {
  float S[32];
  FTH(8 + last * 32, 0);
  c.turn_begin();
  FTH(9 + last * 32, 0);
  wg_fence();
  issue_qk(S, dk0 + (last ? 0 : 2 * DG), dkk + (last ? 8 : 4) * DG);
  wg_commit();
  issue_pv<0>(O, P, dv0 + 10 * DG, 1, last);
  issue_pv<1>(O, P, dv0 + 10 * DG, 1, last);
  c.turn_end();
  c.wait_full(last ? 12 : 6);
  FTH(10 + last * 32, 0);
  wg_wait<4>();
  reg_fence(S);
  FTH(11 + last * 32, 0);
  c.release(last ? 8 : 4, 2);
  mask_diag(S, dmask);
  float s0, s1, d0 = z.m0, d1 = z.m1;
#pragma unroll 1
  for (int pass = 0;; pass++) {
    if (z.shifted) shift_scores(S, d0, d1);
    float tr[ROT];
    exp_quarter<0, 3>(S, P, tr, s0, s1, c.sb);
    exp_quarter<1, 2>(S, P, tr, s0, s1, c.sb);
    pin(s1, c.sb); wg_wait<0>(); reg_fence_part<16, 16>(P); reg_fence(O);
    if (!soft_unsafe(s0, s1, !last) || pass) break;
    soft_fix(S, O, z, !last, d0, d1);
  }
  FTH(12 + last * 32, 0);
  z.l0 += s0; z.l1 += s1;
  c.release(10, last ? 2 : 0);
  if (!last) c.wait_full(8);
  FTH(13 + last * 32, 0);
}

__device__ __forceinline__ int conv_next(int g, bool spare) { return spare ? (g >= NGR - 2 ? g - (NGR - 4) : g + 2) : g ^ 6; }
__device__ __forceinline__ void conv_final(uint32_t rb, uint32_t yb, const uint4& u, uint32_t dd, bool on) {
  const uint4 q0 = lds128(rb), q1 = lds128(rb + 4096), q2 = lds128(rb + 8192), q3 = lds128(rb + 12288);
  auto fin = [&](uint32_t x0, uint32_t x1, uint32_t x2, uint32_t x3, uint32_t uu) {
    return hfma2(dd, __byte_perm(uu, uu, 0x1032), hadd2(hadd2(x0, x1), hadd2(x2, x3)));
  };
  asm volatile("{\n.reg .pred p;\nsetp.ne.b32 p, %5, 0;\n@p st.shared.v4.b32 [%0], {%1,%2,%3,%4};\n}\n" ::"r"(yb), "r"(fin(q0.x, q1.x, q2.x, q3.x, u.w)),
               "r"(fin(q0.y, q1.y, q2.y, q3.y, u.z)), "r"(fin(q0.z, q1.z, q2.z, q3.z, u.y)), "r"(fin(q0.w, q1.w, q2.w, q3.w, u.x)), "r"((int)on) : "memory");
}
__device__ __forceinline__ void conv_tasks(Cons& c, const Params& p, int ntask, bool last, bool spare, int ch, int chstep, uint32_t dkk, int w, int lane) {
  const uint32_t sb = c.sb;
  int g = 4 + c.wg;
  uint4 u0 = make_uint4(0, 0, 0, 0), u1 = u0;
  uint32_t dd = 0, rb = sb + g * GR;
  const uint32_t yb = sb + c.wg * 8192 + c.tid * 16;
  c.wait_full(g);
#pragma unroll 1
  for (int i = 0; i < ntask; i++) {
    const uint32_t base = sb + g * GR;
    FTC(0);
    uint32_t a[64];
    const uint32_t hb = base + WBYTES - 28 + (8 * w + (lane >> 2) + (lane & 3)) * 4;
    auto lda = [&](int s) {
      a[4 * s] = lds32(hb + s * 256); a[4 * s + 1] = lds32(hb + s * 256 + 128);
      a[4 * s + 2] = lds32(hb + s * 256 + 16); a[4 * s + 3] = lds32(hb + s * 256 + 144);
    };
    lda(0); lda(15); lda(1); lda(14);
    float acc[8][16];
    const uint32_t db = dkk + ((4352 / 16 - 1) << 16) + g * DG + 16;
    FTC(2);
    c.turn_begin();
    FTC(3);
#pragma unroll
    for (int k = 0; k < 8; k++) {
      if (k < 7) wg_fence();
      if (k == 7 && !(last && i == ntask - 1)) c.turn_end();
#pragma unroll
      for (int J = 7; J >= (k >> 1); J--) {
        if (k == 0) mma_rs_n32_init(acc[J], a[0], a[1], a[2], a[3], db + J * 32);
        else mma_rs_n32(acc[J], a[4 * k], a[4 * k + 1], a[4 * k + 2], a[4 * k + 3], db + (2 * J - k) * 16);
      }
      const int s = 15 - k;
#pragma unroll
      for (int J = 7; J >= (s >> 1); J--) mma_rs_n32(acc[J], a[4 * s], a[4 * s + 1], a[4 * s + 2], a[4 * s + 3], db + (2 * J - s) * 16);
      if (k < 6) { lda(k + 2); lda(13 - k); }
      if (k == 0) conv_final(rb, yb, u0, dd, i > 0);
      if (k == 1) {
        conv_final(rb + 2048, yb + 2048, u1, dd, i > 0);
        __syncwarp();
        if (lane == 0 && i > 0) mbar_arrive(sb + SM_BAR + (B_EV + c.wg) * 8);
      }
      if (k == 6) {
        const uint32_t ub = base + 256 + 16 + (c.tid >> 1) * 32 + ((c.tid & 1) ^ 1) * 4352;
        u0 = lds128(ub); u1 = lds128(ub + 2048);
        dd = __bfloat16_as_ushort(p.ssd[ch]) * 0x10001u;
      }
    }
    wg_commit();
    FTC(4);
    g = conv_next(g, spare);
    ch += chstep;
    rb = base + c.tid * 16;
    if (i + 1 < ntask) c.wait_full(g);
    wg_wait<0>();
#pragma unroll
    for (int J = 0; J < 8; J++) reg_fence(acc[J]);
    reg_fence(a);
    bar_sync(3 + c.wg, 128);
    FTC(5);
    const int tw = (lane & 3) + w;
    const uint32_t xb = base + w * 4096 + tw * 32 + (lane >> 2) * 4;
#pragma unroll
    for (int j = 0; j < 32; j++) {
      float v0 = acc[j >> 2][(j & 3) * 4], v1 = acc[j >> 2][(j & 3) * 4 + 1];
      if (j > 0) { v0 += acc[(j - 1) >> 2][((j - 1) & 3) * 4 + 2]; v1 += acc[(j - 1) >> 2][((j - 1) & 3) * 4 + 3]; }
      uint32_t v = pack_bf16(v0, v1), ad = xb + j * 128;
      if (j == 31 && tw >= 4) { v = 0; ad -= 4096; }
      asm volatile("st.shared.b32 [%0], %1;" ::"r"(ad), "r"(v) : "memory");
    }
    c.wait_stage_free();
    bar_sync(3 + c.wg, 128);
    FTC(6);
  }
  conv_final(rb, yb, u0, dd, true);
  conv_final(rb + 2048, yb + 2048, u1, dd, true);
  c.staged(0);
}

__global__ void __cluster_dims__(2, 1, 1) __launch_bounds__(NTHREADS, 1) mega_kernel(const __grid_constant__ Params p) {
  extern __shared__ __align__(1024) uint8_t smem_raw[];
  const uint32_t sb = smem_u32(smem_raw);
  const int wgi = __shfl_sync(0xffffffffu, threadIdx.x >> 7, 0);
  const int warp = __shfl_sync(0xffffffffu, threadIdx.x >> 5, 0);
  const uint32_t rank = blockIdx.x & 1;
  int grp, idx;
  {
    uint32_t smid; asm volatile("mov.u32 %0, %smid;" : "=r"(smid));
    const int tp = smid >> 1;
    if (tp < 32) { grp = tp & 7; idx = tp >> 3; }
    else if (tp < 60) { grp = 1 + (tp - 32) % 7; idx = 4 + (tp - 32) / 7; }
    else if (tp < 62) { grp = 8; idx = tp - 60; }
    else { grp = 0; idx = tp - 58; }
  }
  const int lb = (grp * 8 + idx) * 2 + rank;
  const bool spare = grp == 8;
  const int cn = spare ? CN_SPARE : CN_MAIN, cch = spare ? lb - NMAIN : 4 * CN_SPARE + CN_MAIN * lb, cstep = spare ? 4 : 1;

  if (threadIdx.x == 64) { prefetch_tm(&p.c); prefetch_tm(rank ? &p.wuv : &p.wuk); }
  if (threadIdx.x <= B_DONE) {
    const int i = threadIdx.x;
    mbar_init(sb + SM_BAR + i * 8, i == B_DONE ? 11 : i < NGR || i >= 2 * NGR + 4 ? 1 : 4);
    asm volatile("fence.mbarrier_init.release.cluster;" ::: "memory");
  }
  if (START_PF && wgi && !spare) {
    const int j = threadIdx.x & 127;
#pragma unroll
    for (int kb = 0; kb < START_PF; kb++)
      asm volatile("prefetch.global.L2 [%0];" ::"l"(wgi == 1 ? p.cp + (size_t)((2 * idx + rank) * 128 + j) * DC + kb * 64
                                                             : (rank ? p.wuvp : p.wukp) + (size_t)(kb * 64 + (j >> 1)) * (NH * HD) + 2 * grp * HD + (j & 1) * 64));
  }
  cluster_arrive();
  cluster_wait();
  TS(0);

  if (wgi == 0) {
    asm volatile("setmaxnreg.dec.sync.aligned.u32 40;");
    const int lane = threadIdx.x & 31;
    cluster_arrive();
    if (warp == 3) {
      if (!spare) {
        const int s0 = lb * 16;
#pragma unroll 1
        for (int cg = 0; cg < 16; cg++) {
          __nanosleep(PRE_SLEEP);
          const int ch = cg * 64 + 2 * lane;
          const uint32_t* kp = reinterpret_cast<const uint32_t*>(p.ak + (size_t)s0 * DM + ch);
          const uint32_t* vp = reinterpret_cast<const uint32_t*>(p.av + (size_t)s0 * DM + ch);
          const uint4 sw = __ldg(reinterpret_cast<const uint4*>(p.shk + ch * 4));
          uint32_t k3 = 0, k2 = 0, k1 = 0, k0 = 0, up = 0;
          if (lb > 0) { k3 = ldg_stream(kp - 4 * 512); k2 = ldg_stream(kp - 3 * 512); k1 = ldg_stream(kp - 2 * 512); k0 = ldg_stream(kp - 512); up = ldg_stream(vp - 512); }
          const uint32_t w0 = __byte_perm(sw.x, sw.z, 0x5410), w1 = __byte_perm(sw.x, sw.z, 0x7632);
          const uint32_t w2 = __byte_perm(sw.y, sw.w, 0x5410), w3 = __byte_perm(sw.y, sw.w, 0x7632);
          up = hmul2(hfma2(k0, w0, hfma2(k1, w1, hfma2(k2, w2, hmul2(k3, w3)))), up);
#pragma unroll 1
          for (int hb = 0; hb < 2; hb++) {
            uint32_t kk[8], u[8];
#pragma unroll
            for (int r = 0; r < 8; r++) { kk[r] = ldg_stream(kp + r * 512); u[r] = ldg_stream(vp + r * 512); }
#pragma unroll
            for (int r = 0; r < 8; r++) {
              k3 = k2; k2 = k1; k1 = k0; k0 = kk[r];
              u[r] = hmul2(hfma2(k0, w0, hfma2(k1, w1, hfma2(k2, w2, hmul2(k3, w3)))), u[r]);
            }
            if (lane == 0) asm volatile("cp.async.bulk.wait_group.read 0;" ::: "memory");
            __syncwarp();
            const uint32_t dst = sb + SM_UST + lane * 32 + ((lane & 4) << 2);
#pragma unroll
            for (int cc = 0; cc < 2; cc++) {
              const uint32_t sel = cc ? 0x7632 : 0x5410;
              asm volatile("st.shared.v4.b32 [%0], {%1,%2,%3,%4};" ::"r"(dst + cc * 1024), "r"(__byte_perm(u[6], u[5], sel)), "r"(__byte_perm(u[4], u[3], sel)),
                           "r"(__byte_perm(u[2], u[1], sel)), "r"(__byte_perm(u[0], up, sel)) : "memory");
              asm volatile("st.shared.v4.b32 [%0], {%1,%2,%3,%4};" ::"r"((dst ^ 16) + cc * 1024), "r"(__byte_perm(u[7], u[6], sel)), "r"(__byte_perm(u[5], u[4], sel)),
                           "r"(__byte_perm(u[3], u[2], sel)), "r"(__byte_perm(u[1], u[0], sel)) : "memory");
            }
            fence_async_smem();
            __syncwarp();
            if (lane == 0) {
              asm volatile("cp.async.bulk.tensor.3d.global.shared::cta.bulk_group [%0, {%2, %3, %4}], [%1];\ncp.async.bulk.commit_group;"
                           ::"l"(&p.w), "r"(sb + SM_UST), "r"(128 + lb * 16 + (hb ^ 1) * 2176), "r"(cg * 32), "r"(0) : "memory");
            }
            up = u[7];
            kp += 8 * 512; vp += 8 * 512;
          }
          if ((cg & (cg + 1)) == 0 && lane == 0) {
            asm volatile("cp.async.bulk.wait_group 0;" ::: "memory");
            fence_release();
            flag_add(FLAG(F_U + 32 - __clz(cg)));
          }
          TSW(10 + cg);
        }
      }
      if (lane == 0) {
        unsigned long long t0, t1;
        asm volatile("mov.u64 %0, %globaltimer;" : "=l"(t0));
        while (!mbar_try(sb + SM_BAR + B_DONE * 8, 0)) {
          asm volatile("mov.u64 %0, %globaltimer;" : "=l"(t1));
          if (t1 - t0 > 2000000000ull) __trap();
        }
      }
    } else if (warp != 0) {
      const int w = warp - 1, ne = 12 + (cn + 1 - w) / 2;
      uint32_t p0 = 0;
      int cg = 4 + w, ch = cch + w * cstep;
#pragma unroll 1
      for (int e = spare ? 12 : 0; e < ne; e++) {
        const int rnd = e >= 6, k = e - 6 * rnd, rt = k == 4 ? idx : 15 - idx;
        uint8_t* dst = k < 4 ? g_kv + (size_t)(((k & 1) * 16 + 2 * grp + (k >> 1)) * 16 + 2 * idx + rank) * 32768 + w * 8192
                     : k < 6 ? g_cimg + (size_t)(rt * 32 + 16 * rnd + 2 * grp + rank) * 32768 + (w ^ (k & 1)) * 8192
                             : reinterpret_cast<uint8_t*>(g_yT + (size_t)ch * SEQ);
        const uint32_t src = sb + w * 8192 + (k == 4 ? 2 * GR : 0);
        if (e == 6) flag_wait(FLAG(F_AD + grp), 32);
        mbar_wait1(sb + SM_BAR + (B_EV + (k == 4 ? 2 : 0) + w) * 8, k == 4 ? rnd : p0);
        if (k != 4) p0 ^= 1;
        if (lane < 4 && k >= 6 && (!spare || e < ne - 6)) mbar_arrive_cluster(sb + SM_BAR + (B_EMPTY + cg) * 8, lane & 1);
        fence_async_smem();
        if (elect()) {
#pragma unroll 1
          for (int i = 0; i < (k >= 6 ? 1 : 8); i++) {
            const uint32_t o = (i >> 2) * 16384 + (i & 3) * 2048;
            asm volatile("cp.async.bulk.global.shared::cta.bulk_group [%0], [%1], %2;" ::"l"(dst + o), "r"(src + o), "r"(k >= 6 ? 4096 : 2048) : "memory");
            asm volatile("cp.async.bulk.commit_group;\ncp.async.bulk.wait_group.read %0;" ::"n"(ST_OUT) : "memory");
          }
          asm volatile("cp.async.bulk.wait_group 0;" ::: "memory");
          if (k != 4) mbar_arrive(sb + SM_BAR + (B_EV + 4 + w) * 8);
        }
        __syncwarp();
        if (lane < 4 && (k == 4 || (e == ne - 1 && !spare)))
          mbar_arrive_cluster(sb + SM_BAR + (B_EMPTY + (k == 4 ? 2 : 0) + (lane >> 1)) * 8, lane & 1);
        if (k >= 3) {
          fence_release();
          if (lane == 0 || (lane == 1 && e == 5))
            flag_add(FLAG(lane ? F_AD + grp : k == 3 ? F_KV + rnd * 8 + grp : k < 6 ? F_CTX + rt * 2 + rnd : F_Y + (ch >> 7)));
        }
        if (k >= 6) { cg = conv_next(cg, spare); ch += 2 * cstep; }
      }
      if (lane == 0) mbar_arrive(sb + SM_BAR + B_DONE * 8);
    } else {
      uint32_t pe = 0x3FFC;
      auto acquire = [&](int g) { PWAIT(sb + SM_BAR + (B_EMPTY + g) * 8, (pe >> g) & 1); pe ^= 1u << g; };
#pragma unroll 1
      for (int rnd = 0; rnd < (spare ? 0 : 2); rnd++) {
        const int hp = 16 * rnd + 2 * grp, head = hp + rank;
#pragma unroll 1
        for (int kk = 0; kk < 32; kk++) {
          const int g0 = 2 + 3 * (kk & 3);
          acquire(g0);
          if (kk < 4) { acquire(g0 + 1); acquire(g0 + 2); } else pe ^= 6u << g0;
          if (elect()) {
            const uint32_t fb = sb + SM_BAR + (B_FULL + g0) * 8;
            mbar_expect_tx(fb, 3 * GR);
            if (kk < 16) {
              tma2d(sb + g0 * GR, &p.c, (kk & 7) * 64, (2 * idx + rank) * 128, fb, EV_NORMAL);
              tma3d_mc(sb + (g0 + 1 + rank) * GR, rank ? &p.wuv : &p.wuk, 0, (kk & 7) * 64, (hp + (kk >> 3)) * 2, fb, POL_W);
            } else {
              tma2d_mc(sb + (g0 + rank) * GR, &p.x, (kk - 16) * 64, (rank ? 15 - idx : idx) * 128, fb, EV_NORMAL);
              tma3d(sb + (g0 + 2) * GR, &p.wq, 0, (kk - 16) * 64, head * 2, fb, POL_W);
            }
            if (kk == 3) { prefetch_tm(&p.x); prefetch_tm(&p.wq); }
          }
        }
        flag_wait(FLAG(F_KV + rnd * 8 + grp), 32);
        fence_async_all();
        acquire(2); pe ^= 8u;
        int g0 = 4;
#pragma unroll 1
        for (int f = 0; f < 34; f++) {
          const bool isk = (f == 0) || ((f & 1) && f < 33);
          const int it = (f == 0) ? 0 : (f == 33) ? 16 : isk ? (f + 1) >> 1 : (f >> 1) - 1;
          const int blk = it == 0 ? idx : it <= idx ? it - 1 : it < 16 ? 15 - it : 15 - idx;
          acquire(g0);
          if (f < 5) acquire(g0 + 1); else pe ^= 2u << g0;
          if (elect()) {
            const uint32_t fb = sb + SM_BAR + (B_FULL + g0) * 8;
            mbar_expect_tx(fb, 2 * GR);
            bulk_g2s(sb + g0 * GR, g_kv + (size_t)(((isk ? 0 : 16) + (head & 15)) * 16 + blk) * 32768, 2 * GR, fb, POL_KV);
          }
          g0 = f == 12 ? 12 : g0 == 12 ? 4 : g0 + 2;
        }
      }
      if (spare) {
#pragma unroll 1
        for (int i = 0, g = 2; i < 32; i++) {
          acquire(g); pe ^= 2u << g;
          if (elect()) {
            const uint32_t fb = sb + SM_BAR + (B_FULL + g) * 8;
            if (i == 0) { mbar_expect_tx(fb - 8, 2048); bulk_g2s(sb + GR, p.gate_w, 2048, fb - 8, EV_NORMAL); }
            mbar_expect_tx(fb, 2 * GR);
            tma2d(sb + g * GR, &p.x, (i & 7) * 128, (lb - NMAIN) * 512 + (i >> 3) * 128, fb, EV_NORMAL);
            tma2d(sb + (g + 1) * GR, &p.x, (i & 7) * 128 + 64, (lb - NMAIN) * 512 + (i >> 3) * 128, fb, EV_NORMAL);
          }
          g = g == NGR - 2 ? 2 : g + 2;
        }
      }
      auto conv_fill = [&](int g, int ch) {
        acquire(g);
        if (elect()) {
          const uint32_t fb = sb + SM_BAR + (B_FULL + g) * 8;
          mbar_expect_tx(fb, WBYTES + 4096);
          bulk_g2s(sb + g * GR, g_w + (size_t)ch * WSTRIDE, WBYTES, fb, POL_C);
          bulk_g2s(sb + g * GR + WBYTES, p.ssk + (size_t)ch * SEQ, 4096, fb, POL_C);
        }
      };
#pragma unroll 1
      for (int i = 0, g = 4; i < cn; i++) {
        if ((i & 15) == 0) { flag_wait(FLAG(F_U + (spare ? 32 - __clz(i >> 4) : 4)), NMAIN); fence_async_all(); }
        conv_fill(g + (i & 1), cch + i * cstep);
        if (i & 1) g = conv_next(g, spare);
      }
      if (!spare) {
        const int rt = 2 * grp + rank, ct = idx;
        int g0 = P3G;
#pragma unroll 1
        for (int kb = 0; kb < 66; kb++) {
          if (kb == 0 || kb == 32 || kb >= 64) {
            flag_wait(FLAG(kb < 64 ? F_CTX + rt * 2 + (kb >> 5) : kb == 64 ? F_GATE : F_Y + ct), kb <= 64 ? 32 : 128);
            fence_async_all();
          }
          acquire(g0);
          if (kb < 11) acquire(g0 + 1);
          if (elect()) {
            const uint32_t fb = sb + SM_BAR + (B_FULL + g0) * 8;
            mbar_expect_tx(fb, kb == 64 ? 2 * GR + 512 : 2 * GR);
            if (kb <= 64) bulk_g2s(kb < 64 ? sb + g0 * GR : sb + SM_GATE, kb < 64 ? (const void*)(g_cimg + (size_t)(rt * 64 + kb) * GR) : (const void*)(g_gate + rt * 128), kb < 64 ? GR : 512, fb, POL_CTX);
            if (kb < 64) {
              tma2d_mc(sb + (g0 + 1) * GR + rank * 8192, &p.wo, ct * 128 + rank * 64, kb * 64, fb, POL_WO);
              if (kb == 40) { prefetch_tm(&p.y); prefetch_tm(&p.out); }
            } else {
              const CUtensorMap* tm = kb == 64 ? &p.x : &p.y;
              const int c0 = (kb == 64 ? ct : rt) * 128, c1 = (kb == 64 ? rt : ct) * 128;
              tma2d(sb + g0 * GR, tm, c0, c1, fb, EV_NORMAL);
              tma2d(sb + (g0 + 1) * GR, tm, c0 + 64, c1, fb, EV_NORMAL);
            }
          }
          g0 = g0 == 12 ? (kb == 3 ? 2 : 0) : g0 + 2;
        }
        unsigned n = 0;
        if (lane == 0) n = atomicAdd(FLAG(F_EXIT), 1);
        if (__shfl_sync(0xffffffffu, n, 0) == NMAIN - 1) { *FLAG(lane) = 0; *FLAG(lane + 32) = 0; *FLAG(lane + 64) = 0; }
      }
      if (lane == 0) mbar_arrive(sb + SM_BAR + B_DONE * 8);
    }
    __syncwarp();
    cluster_wait();
  } else {
    asm volatile("setmaxnreg.inc.sync.aligned.u32 232;");
    Cons c;
    c.sb = sb; c.pf = 0; c.wg = wgi - 1; c.tid = threadIdx.x & 127;
    const int lane = threadIdx.x & 31, t = lane & 3;
    const int row = c.wg * 64 + (warp & 3) * 16 + (lane >> 2);
    const uint32_t dkk = desc_k(sb), dk0 = dkk + c.wg * 512, dm0 = desc_mn<8192>(sb), dv0 = desc_mn<16384>(sb);
    const uint32_t dsw = DG + 512 - c.wg * 1024;
    if (c.wg == 1) bar_arrive(1, 256);
    c.pfree = 1;
    asm("mapa.shared::cluster.u32 %0, %1, %2;" : "=r"(c.relb) : "r"(sb + SM_BAR + (B_EMPTY + (c.tid >> 1)) * 8), "r"(c.tid & 1));
    c.zero = p.zero;
    c.rnd = 0;
    const uint32_t stg = sb + (c.wg * 64 + (warp & 3) * 16 + ((lane >> 3) & 1) * 8 + (lane & 7)) * 128 + (((lane >> 4) ^ (lane & 7)) << 4);

    if (spare) {
      c.wait_full(1);
      int g = 2;
#pragma unroll 1
      for (int r = 0; r < 4; r++) {
        float d[4] = {0.f, 0.f, 0.f, 0.f}, e[4] = {0.f, 0.f, 0.f, 0.f};
#pragma unroll 1
        for (int kb = 0; kb < 16; kb += 2) {
          c.wait_full(g);
          wg_fence();
#pragma unroll
          for (int k = 0; k < 4; k++) {
            mma_ss_n8(d, dk0 + g * DG + k * 2, dkk + DG + kb * 8 + k * 2);
            mma_ss_n8(e, dk0 + (g + 1) * DG + k * 2, dkk + DG + kb * 8 + 8 + k * 2);
          }
          wg_commit();
          wg_wait<0>();
          c.release(g, 2);
          g = g == NGR - 2 ? 2 : g + 2;
        }
        reg_fence(d); reg_fence(e);
        d[0] += e[0]; d[2] += e[2];
        if (t == 0) {
          float* gp = g_gate + (lb - NMAIN) * 512 + r * 128 + row;
          gp[0] = rcp(1.f + ex2(-1.4426950408889634f * d[0])); gp[8] = rcp(1.f + ex2(-1.4426950408889634f * d[2]));
        }
      }
      fence_release();
      __syncwarp();
      if (lane == 0) flag_add(FLAG(F_GATE));
      TS(1);
    }
    const float dmask = (float)(2 * t - (row & 63));
    uint32_t pv[32];
#pragma unroll
    for (int i = 0; i < 32; i++) pv[i] = 0;
#pragma unroll 1
    for (int rnd = 0; rnd < (spare ? 0 : 2); rnd++) {
      float O[64];
      FTM(rnd * 8);
      FTH(56, c.rnd == rnd);
      c.wait_full(2);
      FTM(rnd * 8 + 1);
      FTH(57, c.rnd == rnd);
#pragma unroll 1
      for (int tile = c.zero; tile < 2; tile++) {
        float acc[128];
        {
          FTG(tile * 32); FTG(tile * 32 + 1);
          const uint32_t a = dk0 + 2 * DG, b = dm0 + 3 * DG;
          c.turn_begin();
          FTG(tile * 32 + 2);
          FTH(58, c.rnd == rnd);
          wg_fence();
          mma_ss_n256_init<1>(acc, a, b);
#pragma unroll
          for (int k = 1; k < 4; k++) mma_ss_n256<1>(acc, a + k * 2, b + k * 128);
          wg_commit();
          FTG(tile * 32 + 3);
        }
#pragma unroll 1
        for (int kb = 1; kb < 8; kb++) {
          const int g0 = 2 + 3 * (kb & 3);
          const uint32_t a = dk0 + g0 * DG, b = dm0 + (g0 + 1) * DG;
          const bool second = kb == 1 || kb == 7;
          FTG(tile * 32 + kb * 4);
          if (!second) { wg_wait<0>(); c.release(2 + 3 * ((kb - 1) & 3), 3); }
          FTG(tile * 32 + kb * 4 + 1);
          c.wait_full(g0);
          if (!second) c.turn_begin();
          FTG(tile * 32 + kb * 4 + 2);
          wg_fence();
#pragma unroll
          for (int k = 0; k < 4; k++) mma_ss_n256<1>(acc, a + k * 2, b + k * 128);
          wg_commit();
          if (kb != 6) c.turn_end();
          if (second) { wg_wait<1>(); c.release(2 + 3 * ((kb - 1) & 3), 3); }
          FTG(tile * 32 + kb * 4 + 3);
          FTH(58 + kb, c.rnd == rnd || kb > 3);
          if (tile == 1 && kb == 3) { c.wait_stage_free(); stsm_frag<0, 4>(pv, stg); }
          if (tile == 1 && kb == 4) { stsm_frag<4, 8>(pv, stg); c.staged(0); }
        }
        c.rnd = rnd;
        c.wait_stage_free();
        const bool nxt = c.try_full(2);
        wg_wait<0>();
        reg_fence(acc);
        c.release(11, 3);
        pack_frag_scaled(acc, pv, SM_C, SM_C);
        stsm_frag(pv, stg);
        c.staged(0);
        pack_frag<64>(acc, pv);
        pin32(pv, sb);
        if (!nxt) mbar_wait(sb + SM_BAR + (B_FULL + 2) * 8, (c.pf >> 2) & 1);
        c.pf ^= 4;
      }
      TS(1 + rnd * 3);
      FTM(rnd * 8 + 2);
      {
        float qa[64];
        float (&qb)[64] = O;
        {
          FTG(64); FTG(65);
          const uint32_t a = dk0 + 2 * DG, b = dm0 + 4 * DG;
          c.turn_begin();
          FTG(66);
          wg_fence();
          mma_ss_n128_init<1>(qa, a, b);
          mma_ss_n128_init<1>(qb, a + dsw, b);
#pragma unroll
          for (int k = 1; k < 4; k++) {
            mma_ss_n128<1>(qa, a + k * 2, b + k * 128);
            mma_ss_n128<1>(qb, a + dsw + k * 2, b + k * 128);
          }
          wg_commit();
          FTG(67);
        }
#pragma unroll 1
        for (int kb = 1; kb < 16; kb++) {
          const int g0 = 2 + 3 * (kb & 3);
          const uint32_t a = dk0 + g0 * DG, b = dm0 + (g0 + 2) * DG;
          const bool second = kb == 1 || kb == 15;
          FTG(64 + kb * 4);
          if (!second) { wg_wait<0>(); c.release(2 + 3 * ((kb - 1) & 3), 3); }
          FTG(65 + kb * 4);
          c.wait_full(g0);
          if (!second) c.turn_begin();
          FTG(66 + kb * 4);
          FTH(kb - 14, kb < 14);
          wg_fence();
#pragma unroll
          for (int k = 0; k < 4; k++) {
            mma_ss_n128<1>(qa, a + k * 2, b + k * 128);
            mma_ss_n128<1>(qb, a + dsw + k * 2, b + k * 128);
          }
          wg_commit();
          if (kb != 14) c.turn_end();
          if (second) { wg_wait<1>(); c.release(2 + 3 * ((kb - 1) & 3), 3); }
          FTG(67 + kb * 4);
          FTH(2, kb < 15);
          if (kb == QFLUSH) { c.wait_stage_free(); stsm_frag<0, 4>(pv, stg); }
          if (kb == QFLUSH + 1) { stsm_frag<4, 8>(pv, stg); c.staged(0); }
        }
        c.wait_stage_free();
        mbar_wait(sb + SM_BAR + (B_EMPTY + 2) * 8, rnd ^ 1);
        FTM(rnd * 8 + 3);
        FTH(3, 0);
        wg_wait<0>();
        reg_fence(qa); reg_fence(qb);
        FTH(4, 0);
        c.release(11, 3);
        pack_frag<0>(qa, pv);
        stsm_frag(pv, stg + 2 * GR);
        if (c.wg == 0) {
          pack_frag<0>(qb, pv);
          stsm_frag(pv, stg);
#pragma unroll
          for (int i = 16; i < 32; i++) pv[i] = 0;
        }
        fence_async_smem();
        c.wait_full(4);
      }
      TS(2 + rnd * 3);
      FTM(rnd * 8 + 4);
      FTH(5, 0);
      {
        const int nA = idx + 1;
        uint32_t (&P)[32] = pv;
        SoftState z;
        z.m0 = z.m1 = z.l0 = z.l1 = 0.f; z.shifted = c.zero;
#pragma unroll 1
        for (int seg = c.zero;; seg++) {
        if (c.wg == seg) attn_half(c, O, P, z, dk0, dkk, dv0, dmask, seg);
        if (seg) break;
        FTM(rnd * 8 + 5);
        int gk = c.wg ? 4 : 6, gv = c.wg ? 4 : 8;
        uint32_t dq = dk0 + (1 - c.wg < nA ? 2 * DG : 0), dk = dkk + gk * DG;
#pragma unroll 1
        for (int it = 1 - c.wg; it < 17 - c.wg; it++) {
          float S[64];
          FTA(it * 7 + 0); FTH((it < 3 ? 8 + it * 8 : it * 8 - 88) + 0, it >= 3 && it < 15);
          c.turn_begin();
          FTA(it * 7 + 2); FTH((it < 3 ? 8 + it * 8 : it * 8 - 88) + 1, it >= 3 && it < 15);
          wg_fence();
          issue_qk(S, dq, dk);
          wg_commit();
          const uint32_t dv = dv0 + gv * DG;
          uint32_t relk = c.relb + gk * 8, relv = c.relb + gv * 8;
          gk = it == 6 ? 12 : gv == 12 ? 4 : gv + 2;
          gv = it == 16 ? gk : gk == 12 ? 4 : gk + 2;
          uint32_t fk = sb + SM_BAR + (B_FULL + gk) * 8, fv = sb + SM_BAR + (B_FULL + gv) * 8, park = (c.pf >> gk) & 1, parv = (c.pf >> gv) & 1;
          c.pf ^= (1u << gk) | (1u << gv);
          dq = dk0 + (it + 1 < nA ? 2 * DG : 0); dk = dkk + gk * DG;
          float lo0 = z.l0, lo1 = z.l1;
          const bool first = it == nA || it == 0;
          if (it == nA) {
            if (EARLY_RCP) { lo0 = rcp(quad_sum(lo0)); lo1 = rcp(quad_sum(lo1)); }
            z.m0 = z.m1 = z.l0 = z.l1 = 0.f; z.shifted = 0;
          }
          float s0, s1, d0 = z.m0, d1 = z.m1;
          int pre = z.shifted || (it & 15) == 0;
          float lim = first ? -1.f : SM_LIMIT;
          asm volatile("" : "+r"(relk), "+r"(relv), "+r"(fk), "+r"(fv), "+r"(park), "+r"(parv), "+r"(dq), "+r"(dk), "+r"(pre), "+f"(lim), "+f"(d0), "+f"(d1), "+f"(z.l0), "+f"(z.l1));
          if (it) {
            issue_pv<0>(O, P, dv, it != nA + 1 && it != 1, true);
            issue_pv<1>(O, P, dv, 1, HALFPV ? it + c.wg > 1 : true);
            c.turn_end();
          } else stage_q2(c, O, P, stg);
          FTA(it * 7 + 3); FTH((it < 3 ? 8 + it * 8 : it * 8 - 88) + 2, it >= 3 && it < 15);
          wg_wait<4>();
          reg_fence(S);
          FTA(it * 7 + 4); FTH((it < 3 ? 8 + it * 8 : it * 8 - 88) + 3, it >= 3 && it < 15);
          if (c.tid < 4) asm volatile("mbarrier.arrive.shared::cluster.b64 _, [%0];" ::"r"(relk) : "memory");
#pragma unroll 1
          for (int pass = 0;; pass++) {
            if (pre) {
              if ((it & 15) == 0) mask_diag(S, dmask);
              if (z.shifted) shift_scores(S, d0, d1);
            }
            float tr[ROT];
            exp_quarter<0, 3>(S, P, tr, s0, s1, sb);
            exp_quarter<1, 2>(S, P, tr, s0, s1, sb);
            exp_quarter<2, 1>(S, P, tr, s0, s1, sb);
            exp_quarter<3, 0>(S, P, tr, s0, s1, sb);
            reg_fence(O);
            if (c.tid < (pass || !it ? 0 : 4)) asm volatile("mbarrier.arrive.shared::cluster.b64 _, [%0];" ::"r"(relv) : "memory");
            const bool ok = mbar_test(fk, park) & mbar_test(fv, parv);
            if (!ok) lim = -1.f;
            FTA(it * 7 + 5); FTH((it < 3 ? 8 + it * 8 : it * 8 - 88) + 4, it >= 3 && it < 15);
            if (!__any_sync(0xffffffffu, !(s0 <= lim && s1 <= lim))) break;
            if (pass) break;
            if (it == nA) {
              uint32_t pk[32];
              if (!EARLY_RCP) { lo0 = rcp(quad_sum(lo0)); lo1 = rcp(quad_sum(lo1)); }
              pack_frag_scaled(O, pk, lo0, lo1);
              stsm_frag(pk, stg + 2 * GR);
              c.staged(1);
            }
            if (!ok) { mbar_wait(fk, park); mbar_wait(fv, parv); }
            if (!soft_unsafe(s0, s1, first)) break;
            soft_fix(S, O, z, first, d0, d1);
            pre = 1;
          }
          z.l0 += s0; z.l1 += s1;
          FTA(it * 7 + 6); FTH((it < 3 ? 8 + it * 8 : it * 8 - 88) + 5, it >= 3 && it < 15);
        }
        FTM(rnd * 8 + 6);
        }
        FTH(48, 0);
        c.turn_begin();
        FTH(49, 0);
        wg_fence();
        issue_pv<0>(O, P, dv0 + 12 * DG, 1, true);
        issue_pv<1>(O, P, dv0 + 12 * DG, 1, !c.wg);
        c.turn_end();
        z.l0 = rcp(quad_sum(z.l0)); z.l1 = rcp(quad_sum(z.l1));
        wg_wait<0>();
        reg_fence(O); reg_fence(P);
        FTH(50, 0);
        c.release(12, 2);
        pack_frag_scaled(O, P, z.l0, z.l1);
        stsm_frag(P, stg);
        c.staged(0);
        FTM(rnd * 8 + 7);
        FTH(51, 0);
      }
      TS(3 + rnd * 3);
    }
    conv_tasks(c, p, (cn + 1 - c.wg) / 2, ((cn - 1) & 1) == c.wg, spare, cch + c.wg * cstep, 2 * cstep, dkk, warp & 3, lane);
    if (c.wg == 1) c.pf ^= 0x4;
    TS(7);
    if (!spare) {
      const int rt = 2 * grp + rank, ct = idx;
      float acc[64];
      int g0 = P3G + 2, pg = P3G;
      {
        FTO(0);
        c.wait_full(P3G);
        FTO(1);
        const uint32_t a = dk0 + P3G * DG, b = dm0 + (P3G + 1) * DG;
        wg_fence();
        mma_ss_n128_init<1>(acc, a, b);
#pragma unroll
        for (int k = 1; k < 4; k++) mma_ss_n128<1>(acc, a + k * 2, b + k * 128);
        wg_commit();
      }
#pragma unroll 1
      for (int kb = 1; kb < 64; kb++) {
        FTO(kb * 2);
        c.wait_full(g0);
        FTO(kb * 2 + 1);
        const uint32_t a = dk0 + g0 * DG, b = dm0 + (g0 + 1) * DG;
        wg_fence();
#pragma unroll
        for (int k = 0; k < 4; k++) mma_ss_n128<1>(acc, a + k * 2, b + k * 128);
        wg_commit();
        wg_wait<1>();
        c.release(pg, kb <= 59 ? 2 : 0);
        if (kb == 40) FTDUMP();
        pg = g0;
        g0 = g0 == 12 ? (kb == 3 ? 2 : 0) : g0 + 2;
      }
      cluster_arrive();
      c.wait_full(P3X);
      c.wait_full(P3Y);
      const float g0f = __uint_as_float(lds32(sb + SM_GATE + row * 4)), g1f = __uint_as_float(lds32(sb + SM_GATE + row * 4 + 32));
      const uint32_t gp0 = pack_bf16(g0f, g0f), gp1 = pack_bf16(g1f, g1f);
      const float h0 = 1.f - g0f, h1 = 1.f - g1f;
      const int w = warp & 3;
      const uint32_t xa = stg + P3X * GR;
      const uint32_t ya = sb + P3Y * GR + c.wg * 16384 + ((lane >> 4) * 8 + (lane & 7)) * 128 + (((2 * w + ((lane >> 3) & 1)) ^ (lane & 7)) << 4);
      uint32_t xy[32];
#pragma unroll
      for (int jj = 0; jj < 8; jj++) {
        uint32_t x[4], y[4];
        asm volatile("ldmatrix.sync.aligned.m8n8.x4.shared.b16 {%0,%1,%2,%3}, [%4];" : "=r"(x[0]), "=r"(x[1]), "=r"(x[2]), "=r"(x[3]) : "r"((xa ^ ((jj & 3) << 5)) + (jj >> 2) * 16384) : "memory");
        asm volatile("ldmatrix.sync.aligned.m8n8.x4.trans.shared.b16 {%0,%1,%2,%3}, [%4];" : "=r"(y[0]), "=r"(y[1]), "=r"(y[2]), "=r"(y[3]) : "r"(ya + jj * 2048) : "memory");
#pragma unroll
        for (int i = 0; i < 4; i++) xy[4 * jj + i] = hmul2(x[i], y[i]);
      }
      wg_wait<0>();
      reg_fence(acc);
      TS(8);
#pragma unroll
      for (int i = 0; i < 32; i++) {
        const float h = (i & 1) ? h1 : h0;
        xy[i] = hfma2((i & 1) ? gp1 : gp0, xy[i], pack_bf16(acc[2 * i] * h, acc[2 * i + 1] * h));
      }
      stsm_frag(xy, xa);
      fence_async_smem();
      __syncwarp();
      if (lane == 0) {
        const int r0 = c.wg * 64 + w * 16;
        tma2d_store(&p.out, sb + P3X * GR + r0 * 128, ct * 128, rt * 128 + r0);
        tma2d_store(&p.out, sb + (P3X + 1) * GR + r0 * 128, ct * 128 + 64, rt * 128 + r0);
        asm volatile("cp.async.bulk.commit_group;\ncp.async.bulk.wait_group.read 0;" ::: "memory");
      }
    } else { FTDUMP(); cluster_arrive(); }
    if (lane == 0) mbar_arrive(sb + SM_BAR + B_DONE * 8);
    __syncwarp();
    TS(9);
    cluster_wait();
  }
}

typedef CUresult (*EncFn)(CUtensorMap*, CUtensorMapDataType, cuuint32_t, void*, const cuuint64_t*, const cuuint64_t*, const cuuint32_t*,
                          const cuuint32_t*, CUtensorMapInterleave, CUtensorMapSwizzle, CUtensorMapL2promotion, CUtensorMapFloatOOBfill);

void enc2d(EncFn enc, CUtensorMap* tm, const void* base, uint64_t cols, uint64_t rows, uint32_t bc, uint32_t br) {
  cuuint64_t dims[2] = {cols, rows}; cuuint64_t strides[1] = {cols * 2}; cuuint32_t box[2] = {bc, br}; cuuint32_t es[2] = {1, 1};
  enc(tm, CU_TENSOR_MAP_DATA_TYPE_BFLOAT16, 2, const_cast<void*>(base), dims, strides, box, es, CU_TENSOR_MAP_INTERLEAVE_NONE,
      CU_TENSOR_MAP_SWIZZLE_128B, CU_TENSOR_MAP_L2_PROMOTION_L2_256B, CU_TENSOR_MAP_FLOAT_OOB_FILL_NONE);
}
void enc3d(EncFn enc, CUtensorMap* tm, const void* base, uint64_t K, uint64_t N) {
  cuuint64_t dims[3] = {64, K, N / 64}; cuuint64_t strides[2] = {N * 2, 128}; cuuint32_t box[3] = {64, 64, 2}; cuuint32_t es[3] = {1, 1, 1};
  enc(tm, CU_TENSOR_MAP_DATA_TYPE_BFLOAT16, 3, const_cast<void*>(base), dims, strides, box, es, CU_TENSOR_MAP_INTERLEAVE_NONE,
      CU_TENSOR_MAP_SWIZZLE_128B, CU_TENSOR_MAP_L2_PROMOTION_L2_256B, CU_TENSOR_MAP_FLOAT_OOB_FILL_NONE);
}

}

extern "C" void kernel_launch(void* const* d_in, const int* in_sizes, int n_in, void* d_out, int out_size) {
  (void)in_sizes; (void)n_in; (void)out_size;
  typedef const __nv_bfloat16* BP;
  BP xq = (BP)d_in[0], ak = (BP)d_in[1], av = (BP)d_in[2], shk = (BP)d_in[3], ssk = (BP)d_in[4], ssd = (BP)d_in[5];
  BP ckv = (BP)d_in[7], wq = (BP)d_in[8], wuk = (BP)d_in[9], wuv = (BP)d_in[10], wo = (BP)d_in[11], gw = (BP)d_in[12];

  static EncFn enc = nullptr;
  if (!enc) {
    cudaDriverEntryPointQueryResult qr;
    cudaGetDriverEntryPoint("cuTensorMapEncodeTiled", (void**)&enc, cudaEnableDefault, &qr);
    cudaFuncSetAttribute(mega_kernel, cudaFuncAttributeMaxDynamicSharedMemorySize, SMEM_BYTES);
  }
  Params p;
  void* yT = nullptr;
  cudaGetSymbolAddress(&yT, g_yT);
  enc2d(enc, &p.x, xq, DM, SEQ, 64, 128);
  enc2d(enc, &p.c, ckv, DC, SEQ, 64, 128);
  enc3d(enc, &p.wq, wq, DM, NH * HD);
  enc3d(enc, &p.wuk, wuk, DC, NH * HD);
  enc3d(enc, &p.wuv, wuv, DC, NH * HD);
  enc2d(enc, &p.wo, wo, DM, NH * HD, 64, 64);
  enc2d(enc, &p.y, yT, SEQ, DM, 64, 128);
  enc2d(enc, &p.out, d_out, DM, SEQ, 64, 16);
  {
    void* wp = nullptr;
    cudaGetSymbolAddress(&wp, g_w);
    cuuint64_t dims[3] = {WSTRIDE / 2, DM / 2, 2}; cuuint64_t strides[2] = {2 * WSTRIDE, WSTRIDE}; cuuint32_t box[3] = {16, 32, 2}; cuuint32_t es[3] = {1, 1, 1};
    enc(&p.w, CU_TENSOR_MAP_DATA_TYPE_BFLOAT16, 3, wp, dims, strides, box, es, CU_TENSOR_MAP_INTERLEAVE_NONE,
        CU_TENSOR_MAP_SWIZZLE_32B, CU_TENSOR_MAP_L2_PROMOTION_NONE, CU_TENSOR_MAP_FLOAT_OOB_FILL_NONE);
  }
  p.zero = 0;
  p.cp = ckv; p.wukp = wuk; p.wuvp = wuv;
  p.xp = xq; p.gate_w = gw; p.ak = ak; p.av = av; p.shk = shk; p.ssk = ssk; p.ssd = ssd;

  mega_kernel<<<132, NTHREADS, SMEM_BYTES>>>(p);
}
```

```cpp
#include <cuda_runtime.h>
#include <cuda.h>
#include <cuda_bf16.h>
#include <stdint.h>

namespace {

constexpr int SEQ = 2048, DM = 1024, DC = 512, NH = 32, HD = 128;
constexpr int GR = 16384;
constexpr int NGR = 14;
constexpr int SM_BAR = NGR * GR;
constexpr int SM_GATE = SM_BAR + 512;
constexpr int SM_UST = SM_GATE + 512;
constexpr int SMEM_BYTES = SM_UST + 2048;
constexpr int NTHREADS = 384;
#define SM_LIMIT 1.0995116e12f
#define SM_LOW 9.094947e-13f
constexpr int CN_MAIN = 5, CN_SPARE = 96;
constexpr int P3G = 6, P3X = 10, P3Y = 12;
constexpr int NMAIN = 128;

constexpr int B_FULL = 0, B_EMPTY = 14, B_EV = 28, B_DONE = 34;

__device__ __align__(1024) uint8_t g_kv[2 * 16 * 16 * 32768];
__device__ __align__(1024) uint8_t g_cimg[16 * NH * 32768];
__device__ __align__(1024) __nv_bfloat16 g_yT[DM * SEQ];
__device__ __align__(1024) float g_gate[SEQ];
constexpr int WSTRIDE = 8832, WBYTES = 8736;
__device__ __align__(1024) uint8_t g_w[DM * WSTRIDE];
__device__ unsigned g_flags[128 * 8];
constexpr int F_KV = 0, F_CTX = 16, F_U = 48, F_AD = 56, F_Y = 64, F_GATE = 72, F_EXIT = 73;
#define FLAG(i) (&g_flags[(i) * 8])

#define TS(slot)
#define TSW(slot)
#define FTX(i, off)
#define FTDUMP()

#define ST_OUT 0
#define QFLUSH 4
#define POL_W EV_NORMAL
#define POL_WO EV_FIRST
#define POL_KV EV_NORMAL
#define POL_C EV_FIRST
#define POL_CTX EV_FIRST
#define HALFPV 1
#define PWAIT mbar_wait1
#define PRE_SLEEP 1500
#define EXPV 1
#define SUMV 0
#define ROT 8
#define EARLY_RCP 1
#define FINE_MODE 0
#define FINE_RND 1
#define FTA(i) do { if (FINE_MODE == 0) FTX(i, rnd ^ FINE_RND); } while (0)
#define FTG(i) do { if (FINE_MODE == 1) FTX(i, rnd ^ FINE_RND); } while (0)
#define FTM(i) do { if (FINE_MODE == 4) FTX(i, 0); } while (0)
#define FTC(k) do { if (FINE_MODE == 5) FTX((i & 7) * 8 + (k), (i >> 3) ^ FINE_RND); } while (0)
#define FTH(i, off) do { if (FINE_MODE == 6) FTX(i, (c.rnd ^ FINE_RND) | (off)); } while (0)
#define FTO(i) do { if (FINE_MODE == 2) FTX(i, 0); } while (0)

__device__ __forceinline__ uint32_t smem_u32(const void* p) { return (uint32_t)__cvta_generic_to_shared(p); }
__device__ __forceinline__ void mbar_init(uint32_t bar, int cnt) { asm volatile("mbarrier.init.shared::cta.b64 [%0], %1;" ::"r"(bar), "r"(cnt) : "memory"); }
__device__ __forceinline__ void mbar_expect_tx(uint32_t bar, uint32_t bytes) { asm volatile("mbarrier.arrive.expect_tx.shared::cta.b64 _, [%0], %1;" ::"r"(bar), "r"(bytes) : "memory"); }
__device__ __forceinline__ void mbar_arrive(uint32_t bar) { asm volatile("mbarrier.arrive.shared::cta.b64 _, [%0];" ::"r"(bar) : "memory"); }
__device__ __forceinline__ void mbar_arrive_cluster(uint32_t bar, uint32_t cta) {
  asm volatile("{\n.reg .b32 r;\nmapa.shared::cluster.u32 r, %0, %1;\nmbarrier.arrive.shared::cluster.b64 _, [r];\n}\n" ::"r"(bar), "r"(cta) : "memory");
}
__device__ __forceinline__ bool mbar_try(uint32_t bar, uint32_t parity) {
  uint32_t ok;
  asm volatile("{\n.reg .pred p;\nmbarrier.try_wait.parity.shared::cta.b64 p, [%1], %2, 20000;\nselp.u32 %0, 1, 0, p;\n}\n" : "=r"(ok) : "r"(bar), "r"(parity) : "memory");
  return ok;
}
__device__ __forceinline__ bool mbar_test(uint32_t bar, uint32_t parity) {
  uint32_t ok;
  asm volatile("{\n.reg .pred p;\nmbarrier.test_wait.parity.shared::cta.b64 p, [%1], %2;\nselp.u32 %0, 1, 0, p;\n}\n" : "=r"(ok) : "r"(bar), "r"(parity) : "memory");
  return ok;
}
__device__ __forceinline__ void mbar_wait(uint32_t bar, uint32_t parity) {
  asm volatile("{\n.reg .pred p;\nWAIT_LOOP:\nbar.warp.sync -1;\nmbarrier.try_wait.parity.shared::cta.b64 p, [%0], %1;\n@!p bra WAIT_LOOP;\n}\n" ::"r"(bar), "r"(parity) : "memory");
}
__device__ __forceinline__ void mbar_wait1(uint32_t bar, uint32_t parity) {
  asm volatile("{\n.reg .pred p;\nWAIT_LOOP:\nbar.warp.sync -1;\nmbarrier.try_wait.parity.shared::cta.b64 p, [%0], %1, 4000;\n@!p bra WAIT_LOOP;\n}\n" ::"r"(bar), "r"(parity) : "memory");
}
constexpr uint64_t EV_NORMAL = 0x1000000000000000ull, EV_FIRST = 0x12F0000000000000ull;
__device__ __forceinline__ uint32_t ldg_stream(const uint32_t* p) {
  uint32_t r; asm volatile("ld.global.nc.L1::no_allocate.L2::cache_hint.b32 %0, [%1], %2;" : "=r"(r) : "l"(p), "l"(EV_FIRST)); return r;
}
__device__ __forceinline__ void tma2d(uint32_t dst, const CUtensorMap* tm, int c0, int c1, uint32_t bar, uint64_t pol) {
  asm volatile("cp.async.bulk.tensor.2d.shared::cluster.global.mbarrier::complete_tx::bytes.L2::cache_hint [%0], [%1, {%3, %4}], [%2], %5;"
               ::"r"(dst), "l"(tm), "r"(bar), "r"(c0), "r"(c1), "l"(pol) : "memory");
}
__device__ __forceinline__ void tma2d_mc(uint32_t dst, const CUtensorMap* tm, int c0, int c1, uint32_t bar, uint64_t pol) {
  asm volatile("cp.async.bulk.tensor.2d.shared::cluster.global.mbarrier::complete_tx::bytes.multicast::cluster.L2::cache_hint [%0], [%1, {%3, %4}], [%2], %5, %6;"
               ::"r"(dst), "l"(tm), "r"(bar), "r"(c0), "r"(c1), "h"((uint16_t)3), "l"(pol) : "memory");
}
__device__ __forceinline__ void tma3d(uint32_t dst, const CUtensorMap* tm, int c0, int c1, int c2, uint32_t bar, uint64_t pol) {
  asm volatile("cp.async.bulk.tensor.3d.shared::cluster.global.mbarrier::complete_tx::bytes.L2::cache_hint [%0], [%1, {%3, %4, %5}], [%2], %6;"
               ::"r"(dst), "l"(tm), "r"(bar), "r"(c0), "r"(c1), "r"(c2), "l"(pol) : "memory");
}
__device__ __forceinline__ void tma3d_mc(uint32_t dst, const CUtensorMap* tm, int c0, int c1, int c2, uint32_t bar, uint64_t pol) {
  asm volatile("cp.async.bulk.tensor.3d.shared::cluster.global.mbarrier::complete_tx::bytes.multicast::cluster.L2::cache_hint [%0], [%1, {%3, %4, %5}], [%2], %6, %7;"
               ::"r"(dst), "l"(tm), "r"(bar), "r"(c0), "r"(c1), "r"(c2), "h"((uint16_t)3), "l"(pol) : "memory");
}
__device__ __forceinline__ void bulk_g2s(uint32_t dst, const void* src, uint32_t bytes, uint32_t bar, uint64_t pol) {
  asm volatile("cp.async.bulk.shared::cluster.global.mbarrier::complete_tx::bytes.L2::cache_hint [%0], [%1], %2, [%3], %4;"
               ::"r"(dst), "l"(src), "r"(bytes), "r"(bar), "l"(pol) : "memory");
}
__device__ __forceinline__ void tma2d_store(const CUtensorMap* tm, uint32_t src, int c0, int c1) {
  asm volatile("cp.async.bulk.tensor.2d.global.shared::cta.bulk_group [%0, {%2, %3}], [%1];" ::"l"(tm), "r"(src), "r"(c0), "r"(c1) : "memory");
}
__device__ __forceinline__ void prefetch_tm(const CUtensorMap* tm) { asm volatile("prefetch.tensormap [%0];" ::"l"(tm) : "memory"); }
__device__ __forceinline__ void wg_fence() { asm volatile("wgmma.fence.sync.aligned;" ::: "memory"); }
__device__ __forceinline__ void wg_commit() { asm volatile("wgmma.commit_group.sync.aligned;" ::: "memory"); }
template <int N> __device__ __forceinline__ void wg_wait() { asm volatile("wgmma.wait_group.sync.aligned %0;" ::"n"(N) : "memory"); }
__device__ __forceinline__ void bar_sync(int id, int n) { asm volatile("bar.sync %0, %1;" ::"r"(id), "r"(n) : "memory"); }
__device__ __forceinline__ void bar_arrive(int id, int n) { asm volatile("bar.arrive %0, %1;" ::"r"(id), "r"(n) : "memory"); }
__device__ __forceinline__ void fence_async_smem() { asm volatile("fence.proxy.async.shared::cta;" ::: "memory"); }
__device__ __forceinline__ void fence_async_all() { asm volatile("fence.proxy.async.global;" ::: "memory"); }
__device__ __forceinline__ uint32_t pack_bf16(float lo, float hi) { uint32_t r; asm("cvt.rn.bf16x2.f32 %0, %1, %2;" : "=r"(r) : "f"(hi), "f"(lo)); return r; }
__device__ __forceinline__ float ex2(float x) { float r; asm("ex2.approx.ftz.f32 %0, %1;" : "=f"(r) : "f"(x)); return r; }
__device__ __forceinline__ float rcp(float x) { float r; asm("rcp.approx.ftz.f32 %0, %1;" : "=f"(r) : "f"(x)); return r; }
__device__ __forceinline__ void flag_wait(const unsigned* f, unsigned target) {
  unsigned v;
  do { asm volatile("ld.acquire.gpu.global.u32 %0, [%1];" : "=r"(v) : "l"(f) : "memory"); } while (__any_sync(0xffffffffu, v < target));
}
__device__ __forceinline__ bool elect() {
  uint32_t r;
  asm volatile("{\n.reg .pred p;\nelect.sync _|p, -1;\nselp.u32 %0, 1, 0, p;\n}\n" : "=r"(r));
  return r;
}
__device__ __forceinline__ void fence_release() { asm volatile("fence.release.gpu;" ::: "memory"); }
__device__ __forceinline__ void flag_add(unsigned* f) { asm volatile("red.relaxed.gpu.global.add.u32 [%0], 1;" ::"l"(f) : "memory"); }
__device__ __forceinline__ void cluster_arrive() { asm volatile("barrier.cluster.arrive.relaxed.aligned;" ::: "memory"); }
__device__ __forceinline__ void cluster_wait() { asm volatile("barrier.cluster.wait.aligned;" ::: "memory"); }
__device__ __forceinline__ uint32_t hmul2(uint32_t a, uint32_t b) { uint32_t r; asm("mul.rn.bf16x2 %0, %1, %2;" : "=r"(r) : "r"(a), "r"(b)); return r; }
__device__ __forceinline__ uint32_t hadd2(uint32_t a, uint32_t b) { uint32_t r; asm("add.rn.bf16x2 %0, %1, %2;" : "=r"(r) : "r"(a), "r"(b)); return r; }
__device__ __forceinline__ uint32_t hfma2(uint32_t a, uint32_t b, uint32_t c) { uint32_t r; asm("fma.rn.bf16x2 %0, %1, %2, %3;" : "=r"(r) : "r"(a), "r"(b), "r"(c)); return r; }
__device__ __forceinline__ uint32_t lds32(uint32_t a) { uint32_t r; asm volatile("ld.shared.b32 %0, [%1];" : "=r"(r) : "r"(a) : "memory"); return r; }
__device__ __forceinline__ uint4 lds128(uint32_t a) { uint4 r; asm volatile("ld.shared.v4.b32 {%0,%1,%2,%3}, [%4];" : "=r"(r.x), "=r"(r.y), "=r"(r.z), "=r"(r.w) : "r"(a) : "memory"); return r; }
__device__ __forceinline__ uint32_t desc_k(uint32_t addr) { return ((addr & 0x3FFFF) >> 4) | (1u << 16); }
template <int LBO> __device__ __forceinline__ uint32_t desc_mn(uint32_t addr) { return ((addr & 0x3FFFF) >> 4) | ((uint32_t)(LBO >> 4) << 16); }
#define DHI "0x40000040"

#define R8(d, o) "+f"(d[o]), "+f"(d[o + 1]), "+f"(d[o + 2]), "+f"(d[o + 3]), "+f"(d[o + 4]), "+f"(d[o + 5]), "+f"(d[o + 6]), "+f"(d[o + 7])
#define R32(d, o) R8(d, o), R8(d, o + 8), R8(d, o + 16), R8(d, o + 24)
#define R64(d, o) R32(d, o), R32(d, o + 32)
#define L64 "%0,%1,%2,%3,%4,%5,%6,%7,%8,%9,%10,%11,%12,%13,%14,%15,%16,%17,%18,%19,%20,%21,%22,%23,%24,%25,%26,%27,%28,%29,%30,%31," \
            "%32,%33,%34,%35,%36,%37,%38,%39,%40,%41,%42,%43,%44,%45,%46,%47,%48,%49,%50,%51,%52,%53,%54,%55,%56,%57,%58,%59,%60,%61,%62,%63"
#define L128 L64 ",%64,%65,%66,%67,%68,%69,%70,%71,%72,%73,%74,%75,%76,%77,%78,%79,%80,%81,%82,%83,%84,%85,%86,%87,%88,%89,%90,%91,%92,%93,%94,%95," \
            "%96,%97,%98,%99,%100,%101,%102,%103,%104,%105,%106,%107,%108,%109,%110,%111,%112,%113,%114,%115,%116,%117,%118,%119,%120,%121,%122,%123,%124,%125,%126,%127"

template <int TB> __device__ __forceinline__ void mma_ss_n128(float (&d)[64], uint32_t da, uint32_t db) {
  asm volatile("{\n.reg .b64 da, db;\nmov.b64 da, {%64, " DHI "};\nmov.b64 db, {%65, " DHI "};\n"
               "wgmma.mma_async.sync.aligned.m64n128k16.f32.bf16.bf16 {" L64 "}, da, db, 1, 1, 1, 0, %66;\n}\n"
               : R64(d, 0) : "r"(da), "r"(db), "n"(TB));
}
template <int TB> __device__ __forceinline__ void mma_rs_n128(float (&d)[64], uint32_t a0, uint32_t a1, uint32_t a2, uint32_t a3, uint32_t db, int sd) {
  asm volatile("{\n.reg .pred p;\n.reg .b64 db;\nsetp.ne.b32 p, %69, 0;\nmov.b64 db, {%68, " DHI "};\n"
               "wgmma.mma_async.sync.aligned.m64n128k16.f32.bf16.bf16 {" L64 "}, {%64,%65,%66,%67}, db, p, 1, 1, %70;\n}\n"
               : R64(d, 0) : "r"(a0), "r"(a1), "r"(a2), "r"(a3), "r"(db), "r"(sd), "n"(TB));
}
template <int TB> __device__ __forceinline__ void mma_ss_n256(float (&d)[128], uint32_t da, uint32_t db) {
  asm volatile("{\n.reg .b64 da, db;\nmov.b64 da, {%128, " DHI "};\nmov.b64 db, {%129, " DHI "};\n"
               "wgmma.mma_async.sync.aligned.m64n256k16.f32.bf16.bf16 {" L128 "}, da, db, 1, 1, 1, 0, %130;\n}\n"
               : R64(d, 0), R64(d, 64) : "r"(da), "r"(db), "n"(TB));
}
#define W8(d, o) "=f"(d[o]), "=f"(d[o + 1]), "=f"(d[o + 2]), "=f"(d[o + 3]), "=f"(d[o + 4]), "=f"(d[o + 5]), "=f"(d[o + 6]), "=f"(d[o + 7])
#define W32(d, o) W8(d, o), W8(d, o + 8), W8(d, o + 16), W8(d, o + 24)
#define W64(d, o) W32(d, o), W32(d, o + 32)
template <int TB> __device__ __forceinline__ void mma_ss_n128_init(float (&d)[64], uint32_t da, uint32_t db) {
  asm volatile("{\n.reg .b64 da, db;\nmov.b64 da, {%64, " DHI "};\nmov.b64 db, {%65, " DHI "};\n"
               "wgmma.mma_async.sync.aligned.m64n128k16.f32.bf16.bf16 {" L64 "}, da, db, 0, 1, 1, 0, %66;\n}\n"
               : W64(d, 0) : "r"(da), "r"(db), "n"(TB));
}
template <int TB> __device__ __forceinline__ void mma_ss_n256_init(float (&d)[128], uint32_t da, uint32_t db) {
  asm volatile("{\n.reg .b64 da, db;\nmov.b64 da, {%128, " DHI "};\nmov.b64 db, {%129, " DHI "};\n"
               "wgmma.mma_async.sync.aligned.m64n256k16.f32.bf16.bf16 {" L128 "}, da, db, 0, 1, 1, 0, %130;\n}\n"
               : W64(d, 0), W64(d, 64) : "r"(da), "r"(db), "n"(TB));
}
#define L32 "%0,%1,%2,%3,%4,%5,%6,%7,%8,%9,%10,%11,%12,%13,%14,%15,%16,%17,%18,%19,%20,%21,%22,%23,%24,%25,%26,%27,%28,%29,%30,%31"
__device__ __forceinline__ void mma_ss_n64(float (&d)[32], uint32_t da, uint32_t db) {
  asm volatile("{\n.reg .b64 da, db;\nmov.b64 da, {%32, " DHI "};\nmov.b64 db, {%33, " DHI "};\n"
               "wgmma.mma_async.sync.aligned.m64n64k16.f32.bf16.bf16 {" L32 "}, da, db, 1, 1, 1, 0, 0;\n}\n"
               : R32(d, 0) : "r"(da), "r"(db));
}
__device__ __forceinline__ void mma_ss_n64_init(float (&d)[32], uint32_t da, uint32_t db) {
  asm volatile("{\n.reg .b64 da, db;\nmov.b64 da, {%32, " DHI "};\nmov.b64 db, {%33, " DHI "};\n"
               "wgmma.mma_async.sync.aligned.m64n64k16.f32.bf16.bf16 {" L32 "}, da, db, 0, 1, 1, 0, 0;\n}\n"
               : W32(d, 0) : "r"(da), "r"(db));
}
#define L16 "%0,%1,%2,%3,%4,%5,%6,%7,%8,%9,%10,%11,%12,%13,%14,%15"
__device__ __forceinline__ void mma_rs_n32(float (&d)[16], uint32_t a0, uint32_t a1, uint32_t a2, uint32_t a3, uint32_t db) {
  asm volatile("{\n.reg .b64 db;\nmov.b64 db, {%20, 0x00000008};\n"
               "wgmma.mma_async.sync.aligned.m64n32k16.f32.bf16.bf16 {" L16 "}, {%16,%17,%18,%19}, db, 1, 1, 1, 0;\n}\n"
               : R8(d, 0), R8(d, 8) : "r"(a0), "r"(a1), "r"(a2), "r"(a3), "r"(db));
}
__device__ __forceinline__ void mma_rs_n32_init(float (&d)[16], uint32_t a0, uint32_t a1, uint32_t a2, uint32_t a3, uint32_t db) {
  asm volatile("{\n.reg .b64 db;\nmov.b64 db, {%20, 0x00000008};\n"
               "wgmma.mma_async.sync.aligned.m64n32k16.f32.bf16.bf16 {" L16 "}, {%16,%17,%18,%19}, db, 0, 1, 1, 0;\n}\n"
               : W8(d, 0), W8(d, 8) : "r"(a0), "r"(a1), "r"(a2), "r"(a3), "r"(db));
}
__device__ __forceinline__ void mma_ss_n8(float (&d)[4], uint32_t da, uint32_t db) {
  asm volatile("{\n.reg .b64 da, db;\nmov.b64 da, {%4, " DHI "};\nmov.b64 db, {%5, 0x00000008};\n"
               "wgmma.mma_async.sync.aligned.m64n8k16.f32.bf16.bf16 {%0,%1,%2,%3}, da, db, 1, 1, 1, 0, 0;\n}\n"
               : "+f"(d[0]), "+f"(d[1]), "+f"(d[2]), "+f"(d[3]) : "r"(da), "r"(db));
}
template <int N> __device__ __forceinline__ void reg_fence(float (&d)[N]) {
#pragma unroll
  for (int i = 0; i < N; i++) asm volatile("" : "+f"(d[i])::"memory");
}
template <int N> __device__ __forceinline__ void reg_fence(uint32_t (&d)[N]) {
#pragma unroll
  for (int i = 0; i < N; i++) asm volatile("" : "+r"(d[i])::"memory");
}

struct __align__(64) Params {
  CUtensorMap x, c, wq, wuk, wuv, wo, y, out, w;
  const __nv_bfloat16* xp;
  const __nv_bfloat16* gate_w;
  const __nv_bfloat16 *ak, *av, *shk, *ssk, *ssd, *cp, *wukp, *wuvp;
  int zero;
};

template <int O, int N, int M> __device__ __forceinline__ void pack_frag(const float (&acc)[N], uint32_t (&pk)[M]) {
#pragma unroll
  for (int i = 0; i < 32; i++) pk[i] = pack_bf16(acc[O + 2 * i], acc[O + 2 * i + 1]);
}
template <int N> __device__ __forceinline__ void pack_frag_scaled(const float (&acc)[N], uint32_t (&pk)[32], float s0, float s1) {
#pragma unroll
  for (int i = 0; i < 32; i++) { const float s = (i & 1) ? s1 : s0; pk[i] = pack_bf16(acc[2 * i] * s, acc[2 * i + 1] * s); }
}
template <int J0 = 0, int J1 = 8, int M> __device__ __forceinline__ void stsm_frag(const uint32_t (&pk)[M], uint32_t a) {
#pragma unroll
  for (int jj = J0; jj < J1; jj++)
    asm volatile("stmatrix.sync.aligned.m8n8.x4.shared.b16 [%0], {%1,%2,%3,%4};" ::"r"((a ^ ((jj & 3) << 5)) + (jj >> 2) * 16384),
                 "r"(pk[4 * jj]), "r"(pk[4 * jj + 1]), "r"(pk[4 * jj + 2]), "r"(pk[4 * jj + 3]) : "memory");
}

struct Cons {
  uint32_t sb;
  uint32_t pf;
  int wg, tid;
  __device__ __forceinline__ void wait_full(int g) { mbar_wait(sb + SM_BAR + (B_FULL + g) * 8, (pf >> g) & 1); pf ^= 1u << g; }
  uint32_t relb;
  __device__ __forceinline__ void release(int g, int n) {
    if (tid < 2 * n) asm volatile("mbarrier.arrive.shared::cluster.b64 _, [%0];" ::"r"(relb + g * 8) : "memory");
  }
  __device__ __forceinline__ void turn_begin() { bar_sync(1 + wg, 256); }
  __device__ __forceinline__ void turn_end() { bar_arrive(2 - wg, 256); }
  __device__ __forceinline__ void staged(int e) { __syncwarp(); if ((tid & 31) == 0) mbar_arrive(sb + SM_BAR + (B_EV + 2 * e + wg) * 8); }
  int zero;
  int rnd;
  uint32_t pfree;
  __device__ __forceinline__ void wait_stage_free() { mbar_wait(sb + SM_BAR + (B_EV + 4 + wg) * 8, pfree); pfree ^= 1; }
  __device__ __forceinline__ bool try_full(int g) { return mbar_test(sb + SM_BAR + (B_FULL + g) * 8, (pf >> g) & 1); }
};

constexpr float SM_C = 0.08838834764831845f * 1.4426950408889634f;
struct SoftState { float m0, m1, l0, l1; int shifted; };
__device__ __forceinline__ void ex2_rot(float& t, float s, uint32_t never_zero) {
  asm("{\n.reg .pred p;\nsetp.ne.u32 p, %2, 0;\n@p ex2.approx.ftz.f32 %0, %1;\n}\n" : "+f"(t) : "f"(s), "r"(never_zero));
}
__device__ __forceinline__ void pin(float a, uint32_t never_zero) {
  asm volatile("{\n.reg .pred p;\nsetp.eq.u32 p, %1, 0;\n@p st.shared.f32 [%1], %0;\n}\n" ::"f"(a), "r"(never_zero) : "memory");
}
template <int O, int N> __device__ __forceinline__ void reg_fence_part(uint32_t (&d)[32]) {
#pragma unroll
  for (int i = O; i < O + N; i++) asm volatile("" : "+r"(d[i])::"memory");
}
template <int Q, int W, int N> __device__ __forceinline__ void exp_quarter(const float (&S)[N], uint32_t (&P)[32], float (&t)[ROT], float& s0, float& s1, uint32_t nz) {
#pragma unroll
  for (int i = 8 * Q; i < 8 * Q + 8; i++) {
    float& a = t[(2 * i) % ROT];
    float& b = t[(2 * i + 1) % ROT];
    if (2 * i < ROT) { a = ex2(S[2 * i]); b = ex2(S[2 * i + 1]); }
    else { ex2_rot(a, S[2 * i], nz); ex2_rot(b, S[2 * i + 1], nz); }
    if (i < 2) { if (i) s1 = a + b; else s0 = a + b; }
    else if (SUMV == 0) { if (i & 1) { s1 += a; s1 += b; } else { s0 += a; s0 += b; } }
    else { if (i & 1) s1 += a + b; else s0 += a + b; }
    if (i == 8 * Q) { pin(EXPV == 1 && Q ? s1 : s0, nz); wg_wait<W>(); reg_fence_part<8 * Q, 8>(P); }
    P[i] = pack_bf16(a, b);
  }
}
template <int N> __device__ __forceinline__ void shift_scores(float (&S)[N], float d0, float d1) {
#pragma unroll
  for (int i = 0; i < N; i++) S[i] -= (i & 2) ? d1 : d0;
}
__device__ __forceinline__ bool soft_high(float s0, float s1, float lim = SM_LIMIT) { return s0 > lim || s1 > lim; }
__device__ __forceinline__ bool soft_unsafe(float s0, float s1, bool first) {
  uint32_t b0 = __ballot_sync(0xffffffffu, s0 >= SM_LOW), b1 = __ballot_sync(0xffffffffu, s1 >= SM_LOW);
  b0 |= b0 >> 1; b0 |= b0 >> 2; b1 |= b1 >> 1; b1 |= b1 >> 2;
  return __any_sync(0xffffffffu, soft_high(s0, s1)) || (first && (b0 & b1 & 0x11111111u) != 0x11111111u);
}
template <int N> __device__ __forceinline__ void soft_fix(const float (&S)[N], float (&O)[64], SoftState& z, bool first, float& d0, float& d1) {
  d0 = d1 = first ? -INFINITY : 0.f;
#pragma unroll
  for (int j = 0; j < N / 4; j++) { d0 = fmaxf(d0, fmaxf(S[4 * j], S[4 * j + 1])); d1 = fmaxf(d1, fmaxf(S[4 * j + 2], S[4 * j + 3])); }
  d0 = fmaxf(d0, __shfl_xor_sync(0xffffffffu, d0, 1)); d1 = fmaxf(d1, __shfl_xor_sync(0xffffffffu, d1, 1));
  d0 = fmaxf(d0, __shfl_xor_sync(0xffffffffu, d0, 2)); d1 = fmaxf(d1, __shfl_xor_sync(0xffffffffu, d1, 2));
  const float sc0 = ex2(-fmaxf(d0, 0.f)), sc1 = ex2(-fmaxf(d1, 0.f));
  z.m0 += d0; z.m1 += d1; z.l0 *= sc0; z.l1 *= sc1; z.shifted = 1;
#pragma unroll
  for (int j = 0; j < 16; j++) { O[4 * j] *= sc0; O[4 * j + 1] *= sc0; O[4 * j + 2] *= sc1; O[4 * j + 3] *= sc1; }
}
template <int M> __device__ __forceinline__ void pin32(const uint32_t (&v)[M], uint32_t never_zero) {
#pragma unroll
  for (int i = 0; i < 32; i += 4)
    asm volatile("{\n.reg .pred p;\nsetp.eq.u32 p, %4, 0;\n@p st.shared.v4.b32 [%4], {%0,%1,%2,%3};\n}\n" ::"r"(v[i]), "r"(v[i + 1]), "r"(v[i + 2]), "r"(v[i + 3]), "r"(never_zero) : "memory");
}
template <int N> __device__ __forceinline__ void mask_diag(float (&S)[N], float nd) {
  asm volatile("" : "+f"(nd));
#pragma unroll
  for (int i = 0; i < 32; i++) {
    const float beyond = __saturatef(nd + (float)(8 * (i >> 2) + (i & 1) - 4 * (i & 2)));
    S[N - 32 + i] = fmaf(beyond, -3.0e38f, S[N - 32 + i]);
  }
}
__device__ __forceinline__ float quad_sum(float v) {
  v += __shfl_xor_sync(0xffffffffu, v, 1);
  v += __shfl_xor_sync(0xffffffffu, v, 2);
  return v;
}
__device__ __forceinline__ void issue_qk(float (&S)[64], uint32_t dq, uint32_t dk) {
  mma_ss_n128_init<0>(S, dq, dk);
#pragma unroll
  for (int s = 1; s < 8; s++) mma_ss_n128<0>(S, dq + (s >> 2) * 1024 + (s & 3) * 2, dk + (s >> 2) * 1024 + (s & 3) * 2);
}
__device__ __forceinline__ void issue_qk(float (&S)[32], uint32_t dq, uint32_t dk) {
  mma_ss_n64_init(S, dq, dk);
#pragma unroll
  for (int s = 1; s < 8; s++) mma_ss_n64(S, dq + (s >> 2) * 1024 + (s & 3) * 2, dk + (s >> 2) * 1024 + (s & 3) * 2);
}
template <int H> __device__ __forceinline__ void issue_pv(float (&O)[64], const uint32_t (&P)[32], uint32_t dv, int acc, bool on) {
  if (on) {
#pragma unroll
    for (int s = 4 * H; s < 4 * H + 4; s++) {
      mma_rs_n128<1>(O, P[4 * s], P[4 * s + 1], P[4 * s + 2], P[4 * s + 3], dv + s * 128, s != 0 ? 1 : acc);
      if (s & 1) wg_commit();
    }
  } else { wg_commit(); wg_commit(); }
}
constexpr uint32_t DG = GR >> 4;
__device__ __forceinline__ void stage_q2(Cons& c, const float (&O)[64], uint32_t (&P)[32], uint32_t stg) {
  wg_commit(); wg_commit(); wg_commit(); wg_commit();
  c.turn_end();
  pack_frag<0>(O, P);
  stsm_frag(P, stg);
  fence_async_smem();
}
__device__ __forceinline__ void attn_half(Cons& c, float (&O)[64], uint32_t (&P)[32], SoftState& z, uint32_t dk0, uint32_t dkk, uint32_t dv0, float dmask, int last) {
  float S[32];
  FTH(8 + last * 32, 0);
  c.turn_begin();
  FTH(9 + last * 32, 0);
  wg_fence();
  issue_qk(S, dk0 + (last ? 0 : 2 * DG), dkk + (last ? 8 : 4) * DG);
  wg_commit();
  issue_pv<0>(O, P, dv0 + 10 * DG, 1, last);
  issue_pv<1>(O, P, dv0 + 10 * DG, 1, last);
  c.turn_end();
  c.wait_full(last ? 12 : 6);
  FTH(10 + last * 32, 0);
  wg_wait<4>();
  reg_fence(S);
  FTH(11 + last * 32, 0);
  c.release(last ? 8 : 4, 2);
  mask_diag(S, dmask);
  float s0, s1, d0 = z.m0, d1 = z.m1;
#pragma unroll 1
  for (int pass = 0;; pass++) {
    if (z.shifted) shift_scores(S, d0, d1);
    float tr[ROT];
    exp_quarter<0, 3>(S, P, tr, s0, s1, c.sb);
    exp_quarter<1, 2>(S, P, tr, s0, s1, c.sb);
    pin(s1, c.sb); wg_wait<0>(); reg_fence_part<16, 16>(P); reg_fence(O);
    if (!soft_unsafe(s0, s1, !last) || pass) break;
    soft_fix(S, O, z, !last, d0, d1);
  }
  FTH(12 + last * 32, 0);
  z.l0 += s0; z.l1 += s1;
  c.release(10, last ? 2 : 0);
  if (!last) c.wait_full(8);
  FTH(13 + last * 32, 0);
}

__device__ __forceinline__ int conv_next(int g, bool spare) { return spare ? (g >= NGR - 2 ? g - (NGR - 4) : g + 2) : g ^ 6; }
__device__ __forceinline__ void conv_final(uint32_t rb, uint32_t yb, const uint4& u, uint32_t dd, bool on) {
  const uint4 q0 = lds128(rb), q1 = lds128(rb + 4096), q2 = lds128(rb + 8192), q3 = lds128(rb + 12288);
  auto fin = [&](uint32_t x0, uint32_t x1, uint32_t x2, uint32_t x3, uint32_t uu) {
    return hfma2(dd, __byte_perm(uu, uu, 0x1032), hadd2(hadd2(x0, x1), hadd2(x2, x3)));
  };
  asm volatile("{\n.reg .pred p;\nsetp.ne.b32 p, %5, 0;\n@p st.shared.v4.b32 [%0], {%1,%2,%3,%4};\n}\n" ::"r"(yb), "r"(fin(q0.x, q1.x, q2.x, q3.x, u.w)),
               "r"(fin(q0.y, q1.y, q2.y, q3.y, u.z)), "r"(fin(q0.z, q1.z, q2.z, q3.z, u.y)), "r"(fin(q0.w, q1.w, q2.w, q3.w, u.x)), "r"((int)on) : "memory");
}
__device__ __forceinline__ void conv_tasks(Cons& c, const Params& p, int ntask, bool last, bool spare, int ch, int chstep, uint32_t dkk, int w, int lane) {
  const uint32_t sb = c.sb;
  int g = 4 + c.wg;
  uint4 u0 = make_uint4(0, 0, 0, 0), u1 = u0;
  uint32_t dd = 0, rb = sb + g * GR;
  const uint32_t yb = sb + c.wg * 8192 + c.tid * 16;
  c.wait_full(g);
#pragma unroll 1
  for (int i = 0; i < ntask; i++) {
    const uint32_t base = sb + g * GR;
    FTC(0);
    uint32_t a[64];
    const uint32_t hb = base + WBYTES - 28 + (8 * w + (lane >> 2) + (lane & 3)) * 4;
    auto lda = [&](int s) {
      a[4 * s] = lds32(hb + s * 256); a[4 * s + 1] = lds32(hb + s * 256 + 128);
      a[4 * s + 2] = lds32(hb + s * 256 + 16); a[4 * s + 3] = lds32(hb + s * 256 + 144);
    };
    lda(0); lda(15); lda(1); lda(14);
    float acc[8][16];
    const uint32_t db = dkk + ((4352 / 16 - 1) << 16) + g * DG + 16;
    FTC(2);
    c.turn_begin();
    FTC(3);
#pragma unroll
    for (int k = 0; k < 8; k++) {
      if (k < 7) wg_fence();
      if (k == 7 && !(last && i == ntask - 1)) c.turn_end();
#pragma unroll
      for (int J = 7; J >= (k >> 1); J--) {
        if (k == 0) mma_rs_n32_init(acc[J], a[0], a[1], a[2], a[3], db + J * 32);
        else mma_rs_n32(acc[J], a[4 * k], a[4 * k + 1], a[4 * k + 2], a[4 * k + 3], db + (2 * J - k) * 16);
      }
      const int s = 15 - k;
#pragma unroll
      for (int J = 7; J >= (s >> 1); J--) mma_rs_n32(acc[J], a[4 * s], a[4 * s + 1], a[4 * s + 2], a[4 * s + 3], db + (2 * J - s) * 16);
      if (k < 6) { lda(k + 2); lda(13 - k); }
      if (k == 0) conv_final(rb, yb, u0, dd, i > 0);
      if (k == 1) {
        conv_final(rb + 2048, yb + 2048, u1, dd, i > 0);
        __syncwarp();
        if (lane == 0 && i > 0) mbar_arrive(sb + SM_BAR + (B_EV + c.wg) * 8);
      }
      if (k == 6) {
        const uint32_t ub = base + 256 + 16 + (c.tid >> 1) * 32 + ((c.tid & 1) ^ 1) * 4352;
        u0 = lds128(ub); u1 = lds128(ub + 2048);
        dd = __bfloat16_as_ushort(p.ssd[ch]) * 0x10001u;
      }
    }
    wg_commit();
    FTC(4);
    g = conv_next(g, spare);
    ch += chstep;
    rb = base + c.tid * 16;
    if (i + 1 < ntask) c.wait_full(g);
    wg_wait<0>();
#pragma unroll
    for (int J = 0; J < 8; J++) reg_fence(acc[J]);
    reg_fence(a);
    bar_sync(3 + c.wg, 128);
    FTC(5);
    const int tw = (lane & 3) + w;
    const uint32_t xb = base + w * 4096 + tw * 32 + (lane >> 2) * 4;
#pragma unroll
    for (int j = 0; j < 32; j++) {
      float v0 = acc[j >> 2][(j & 3) * 4], v1 = acc[j >> 2][(j & 3) * 4 + 1];
      if (j > 0) { v0 += acc[(j - 1) >> 2][((j - 1) & 3) * 4 + 2]; v1 += acc[(j - 1) >> 2][((j - 1) & 3) * 4 + 3]; }
      uint32_t v = pack_bf16(v0, v1), ad = xb + j * 128;
      if (j == 31 && tw >= 4) { v = 0; ad -= 4096; }
      asm volatile("st.shared.b32 [%0], %1;" ::"r"(ad), "r"(v) : "memory");
    }
    c.wait_stage_free();
    bar_sync(3 + c.wg, 128);
    FTC(6);
  }
  conv_final(rb, yb, u0, dd, true);
  conv_final(rb + 2048, yb + 2048, u1, dd, true);
  c.staged(0);
}

__global__ void __cluster_dims__(2, 1, 1) __launch_bounds__(NTHREADS, 1) mega_kernel(const __grid_constant__ Params p) {
  extern __shared__ __align__(1024) uint8_t smem_raw[];
  const uint32_t sb = smem_u32(smem_raw);
  const int wgi = __shfl_sync(0xffffffffu, threadIdx.x >> 7, 0);
  const int warp = __shfl_sync(0xffffffffu, threadIdx.x >> 5, 0);
  const uint32_t rank = blockIdx.x & 1;
  int grp, idx;
  {
    uint32_t smid; asm volatile("mov.u32 %0, %smid;" : "=r"(smid));
    const int tp = smid >> 1;
    if (tp < 32) { grp = tp & 7; idx = tp >> 3; }
    else if (tp < 60) { grp = 1 + (tp - 32) % 7; idx = 4 + (tp - 32) / 7; }
    else if (tp < 62) { grp = 8; idx = tp - 60; }
    else { grp = 0; idx = tp - 58; }
  }
  const int lb = (grp * 8 + idx) * 2 + rank;
  const bool spare = grp == 8;
  const int cn = spare ? CN_SPARE : CN_MAIN, cch = spare ? lb - NMAIN : 4 * CN_SPARE + CN_MAIN * lb, cstep = spare ? 4 : 1;

  if (threadIdx.x == 64) { prefetch_tm(&p.c); prefetch_tm(rank ? &p.wuv : &p.wuk); }
  if (threadIdx.x <= B_DONE) {
    const int i = threadIdx.x;
    mbar_init(sb + SM_BAR + i * 8, i == B_DONE ? 11 : i < NGR || i >= 2 * NGR + 4 ? 1 : 4);
    asm volatile("fence.mbarrier_init.release.cluster;" ::: "memory");
  }
  if (wgi && !spare) {
    const int j = threadIdx.x & 127;
    const __nv_bfloat16* cb = p.cp + (size_t)(2 * idx + rank) * 128 * DC;
    const __nv_bfloat16* wb = (rank ? p.wuvp : p.wukp) + 2 * grp * HD;
    asm volatile("prefetch.global.L2 [%0];" ::"l"(wgi == 1 ? cb + j * DC : wb + (size_t)(j >> 1) * (NH * HD) + (j & 1) * 64));
  }
  cluster_arrive();
  cluster_wait();
  TS(0);

  if (wgi == 0) {
    asm volatile("setmaxnreg.dec.sync.aligned.u32 40;");
    const int lane = threadIdx.x & 31;
    cluster_arrive();
    if (warp == 3) {
      if (!spare) {
        const int s0 = lb * 16;
#pragma unroll 1
        for (int cg = 0; cg < 16; cg++) {
          __nanosleep(PRE_SLEEP);
          const int ch = cg * 64 + 2 * lane;
          const uint32_t* kp = reinterpret_cast<const uint32_t*>(p.ak + (size_t)s0 * DM + ch);
          const uint32_t* vp = reinterpret_cast<const uint32_t*>(p.av + (size_t)s0 * DM + ch);
          const uint4 sw = __ldg(reinterpret_cast<const uint4*>(p.shk + ch * 4));
          uint32_t k3 = 0, k2 = 0, k1 = 0, k0 = 0, up = 0;
          if (lb > 0) { k3 = ldg_stream(kp - 4 * 512); k2 = ldg_stream(kp - 3 * 512); k1 = ldg_stream(kp - 2 * 512); k0 = ldg_stream(kp - 512); up = ldg_stream(vp - 512); }
          const uint32_t w0 = __byte_perm(sw.x, sw.z, 0x5410), w1 = __byte_perm(sw.x, sw.z, 0x7632);
          const uint32_t w2 = __byte_perm(sw.y, sw.w, 0x5410), w3 = __byte_perm(sw.y, sw.w, 0x7632);
          up = hmul2(hfma2(k0, w0, hfma2(k1, w1, hfma2(k2, w2, hmul2(k3, w3)))), up);
#pragma unroll 1
          for (int hb = 0; hb < 2; hb++) {
            uint32_t kk[8], u[8];
#pragma unroll
            for (int r = 0; r < 8; r++) { kk[r] = ldg_stream(kp + r * 512); u[r] = ldg_stream(vp + r * 512); }
#pragma unroll
            for (int r = 0; r < 8; r++) {
              k3 = k2; k2 = k1; k1 = k0; k0 = kk[r];
              u[r] = hmul2(hfma2(k0, w0, hfma2(k1, w1, hfma2(k2, w2, hmul2(k3, w3)))), u[r]);
            }
            if (lane == 0) asm volatile("cp.async.bulk.wait_group.read 0;" ::: "memory");
            __syncwarp();
            const uint32_t dst = sb + SM_UST + lane * 32 + ((lane & 4) << 2);
#pragma unroll
            for (int cc = 0; cc < 2; cc++) {
              const uint32_t sel = cc ? 0x7632 : 0x5410;
              asm volatile("st.shared.v4.b32 [%0], {%1,%2,%3,%4};" ::"r"(dst + cc * 1024), "r"(__byte_perm(u[6], u[5], sel)), "r"(__byte_perm(u[4], u[3], sel)),
                           "r"(__byte_perm(u[2], u[1], sel)), "r"(__byte_perm(u[0], up, sel)) : "memory");
              asm volatile("st.shared.v4.b32 [%0], {%1,%2,%3,%4};" ::"r"((dst ^ 16) + cc * 1024), "r"(__byte_perm(u[7], u[6], sel)), "r"(__byte_perm(u[5], u[4], sel)),
                           "r"(__byte_perm(u[3], u[2], sel)), "r"(__byte_perm(u[1], u[0], sel)) : "memory");
            }
            fence_async_smem();
            __syncwarp();
            if (lane == 0) {
              asm volatile("cp.async.bulk.tensor.3d.global.shared::cta.bulk_group [%0, {%2, %3, %4}], [%1];\ncp.async.bulk.commit_group;"
                           ::"l"(&p.w), "r"(sb + SM_UST), "r"(128 + lb * 16 + (hb ^ 1) * 2176), "r"(cg * 32), "r"(0) : "memory");
            }
            up = u[7];
            kp += 8 * 512; vp += 8 * 512;
          }
          if ((cg & (cg + 1)) == 0 && lane == 0) {
            asm volatile("cp.async.bulk.wait_group 0;" ::: "memory");
            fence_release();
            flag_add(FLAG(F_U + 32 - __clz(cg)));
          }
          TSW(10 + cg);
        }
      }
      if (lane == 0) {
        unsigned long long t0, t1;
        asm volatile("mov.u64 %0, %globaltimer;" : "=l"(t0));
        while (!mbar_try(sb + SM_BAR + B_DONE * 8, 0)) {
          asm volatile("mov.u64 %0, %globaltimer;" : "=l"(t1));
          if (t1 - t0 > 2000000000ull) __trap();
        }
      }
    } else if (warp != 0) {
      const int w = warp - 1, ne = 12 + (cn + 1 - w) / 2;
      uint32_t p0 = 0;
      int cg = 4 + w, ch = cch + w * cstep;
#pragma unroll 1
      for (int e = spare ? 12 : 0; e < ne; e++) {
        const int rnd = e >= 6, k = e - 6 * rnd, rt = k == 4 ? idx : 15 - idx;
        uint8_t* dst = k < 4 ? g_kv + (size_t)(((k & 1) * 16 + 2 * grp + (k >> 1)) * 16 + 2 * idx + rank) * 32768 + w * 8192
                     : k < 6 ? g_cimg + (size_t)(rt * 32 + 16 * rnd + 2 * grp + rank) * 32768 + (w ^ (k & 1)) * 8192
                             : reinterpret_cast<uint8_t*>(g_yT + (size_t)ch * SEQ);
        const uint32_t src = sb + w * 8192 + (k == 4 ? 2 * GR : 0);
        if (e == 6) flag_wait(FLAG(F_AD + grp), 32);
        mbar_wait1(sb + SM_BAR + (B_EV + (k == 4 ? 2 : 0) + w) * 8, k == 4 ? rnd : p0);
        if (k != 4) p0 ^= 1;
        if (lane < 4 && k >= 6 && (!spare || e < ne - 6)) mbar_arrive_cluster(sb + SM_BAR + (B_EMPTY + cg) * 8, lane & 1);
        fence_async_smem();
        if (elect()) {
#pragma unroll 1
          for (int i = 0; i < (k >= 6 ? 1 : 8); i++) {
            const uint32_t o = (i >> 2) * 16384 + (i & 3) * 2048;
            asm volatile("cp.async.bulk.global.shared::cta.bulk_group [%0], [%1], %2;" ::"l"(dst + o), "r"(src + o), "r"(k >= 6 ? 4096 : 2048) : "memory");
            asm volatile("cp.async.bulk.commit_group;\ncp.async.bulk.wait_group.read %0;" ::"n"(ST_OUT) : "memory");
          }
          asm volatile("cp.async.bulk.wait_group 0;" ::: "memory");
          if (k != 4) mbar_arrive(sb + SM_BAR + (B_EV + 4 + w) * 8);
        }
        __syncwarp();
        if (lane < 4 && (k == 4 || (e == ne - 1 && !spare)))
          mbar_arrive_cluster(sb + SM_BAR + (B_EMPTY + (k == 4 ? 2 : 0) + (lane >> 1)) * 8, lane & 1);
        if (k >= 3) {
          fence_release();
          if (lane == 0 || (lane == 1 && e == 5))
            flag_add(FLAG(lane ? F_AD + grp : k == 3 ? F_KV + rnd * 8 + grp : k < 6 ? F_CTX + rt * 2 + rnd : F_Y + (ch >> 7)));
        }
        if (k >= 6) { cg = conv_next(cg, spare); ch += 2 * cstep; }
      }
      if (lane == 0) mbar_arrive(sb + SM_BAR + B_DONE * 8);
    } else {
      uint32_t pe = 0x3FFC;
      auto acquire = [&](int g) { PWAIT(sb + SM_BAR + (B_EMPTY + g) * 8, (pe >> g) & 1); pe ^= 1u << g; };
#pragma unroll 1
      for (int rnd = 0; rnd < (spare ? 0 : 2); rnd++) {
        const int hp = 16 * rnd + 2 * grp, head = hp + rank;
#pragma unroll 1
        for (int kk = 0; kk < 32; kk++) {
          const int g0 = 2 + 3 * (kk & 3);
          acquire(g0);
          if (kk < 4) { acquire(g0 + 1); acquire(g0 + 2); } else pe ^= 6u << g0;
          if (elect()) {
            const uint32_t fb = sb + SM_BAR + (B_FULL + g0) * 8;
            mbar_expect_tx(fb, 3 * GR);
            if (kk < 16) {
              tma2d(sb + g0 * GR, &p.c, (kk & 7) * 64, (2 * idx + rank) * 128, fb, EV_NORMAL);
              tma3d_mc(sb + (g0 + 1 + rank) * GR, rank ? &p.wuv : &p.wuk, 0, (kk & 7) * 64, (hp + (kk >> 3)) * 2, fb, POL_W);
            } else {
              tma2d_mc(sb + (g0 + rank) * GR, &p.x, (kk - 16) * 64, (rank ? 15 - idx : idx) * 128, fb, EV_NORMAL);
              tma3d(sb + (g0 + 2) * GR, &p.wq, 0, (kk - 16) * 64, head * 2, fb, POL_W);
            }
            if (kk == 3) { prefetch_tm(&p.x); prefetch_tm(&p.wq); }
          }
        }
        flag_wait(FLAG(F_KV + rnd * 8 + grp), 32);
        fence_async_all();
        acquire(2); pe ^= 8u;
        int g0 = 4;
#pragma unroll 1
        for (int f = 0; f < 34; f++) {
          const bool isk = (f == 0) || ((f & 1) && f < 33);
          const int it = (f == 0) ? 0 : (f == 33) ? 16 : isk ? (f + 1) >> 1 : (f >> 1) - 1;
          const int blk = it == 0 ? idx : it <= idx ? it - 1 : it < 16 ? 15 - it : 15 - idx;
          acquire(g0);
          if (f < 5) acquire(g0 + 1); else pe ^= 2u << g0;
          if (elect()) {
            const uint32_t fb = sb + SM_BAR + (B_FULL + g0) * 8;
            const uint32_t nb = 2 * GR;
            mbar_expect_tx(fb, nb);
            bulk_g2s(sb + g0 * GR, g_kv + (size_t)(((isk ? 0 : 16) + (head & 15)) * 16 + blk) * 32768, nb, fb, POL_KV);
          }
          g0 = f == 12 ? 12 : g0 == 12 ? 4 : g0 + 2;
        }
      }
      if (spare) {
#pragma unroll 1
        for (int i = 0, g = 2; i < 32; i++) {
          acquire(g); pe ^= 2u << g;
          if (elect()) {
            const uint32_t fb = sb + SM_BAR + (B_FULL + g) * 8;
            if (i == 0) { mbar_expect_tx(fb - 8, 2048); bulk_g2s(sb + GR, p.gate_w, 2048, fb - 8, EV_NORMAL); }
            mbar_expect_tx(fb, 2 * GR);
            tma2d(sb + g * GR, &p.x, (i & 7) * 128, (lb - NMAIN) * 512 + (i >> 3) * 128, fb, EV_NORMAL);
            tma2d(sb + (g + 1) * GR, &p.x, (i & 7) * 128 + 64, (lb - NMAIN) * 512 + (i >> 3) * 128, fb, EV_NORMAL);
          }
          g = g == NGR - 2 ? 2 : g + 2;
        }
      }
      auto conv_fill = [&](int g, int ch) {
        acquire(g);
        if (elect()) {
          const uint32_t fb = sb + SM_BAR + (B_FULL + g) * 8;
          mbar_expect_tx(fb, WBYTES + 4096);
          bulk_g2s(sb + g * GR, g_w + (size_t)ch * WSTRIDE, WBYTES, fb, POL_C);
          bulk_g2s(sb + g * GR + WBYTES, p.ssk + (size_t)ch * SEQ, 4096, fb, POL_C);
        }
      };
#pragma unroll 1
      for (int i = 0, g = 4; i < cn; i++) {
        if ((i & 15) == 0) { flag_wait(FLAG(F_U + (spare ? 32 - __clz(i >> 4) : 4)), NMAIN); fence_async_all(); }
        conv_fill(g + (i & 1), cch + i * cstep);
        if (i & 1) g = conv_next(g, spare);
      }
      if (!spare) {
        const int rt = 2 * grp + rank, ct = idx;
        int g0 = P3G;
#pragma unroll 1
        for (int kb = 0; kb < 66; kb++) {
          if (kb == 0 || kb == 32 || kb >= 64) {
            flag_wait(FLAG(kb < 64 ? F_CTX + rt * 2 + (kb >> 5) : kb == 64 ? F_GATE : F_Y + ct), kb <= 64 ? 32 : 128);
            fence_async_all();
          }
          acquire(g0);
          if (kb < 11) acquire(g0 + 1);
          if (elect()) {
            const uint32_t fb = sb + SM_BAR + (B_FULL + g0) * 8;
            mbar_expect_tx(fb, kb == 64 ? 2 * GR + 512 : 2 * GR);
            if (kb <= 64) bulk_g2s(kb < 64 ? sb + g0 * GR : sb + SM_GATE, kb < 64 ? (const void*)(g_cimg + (size_t)(rt * 64 + kb) * GR) : (const void*)(g_gate + rt * 128), kb < 64 ? GR : 512, fb, POL_CTX);
            if (kb < 64) {
              tma2d_mc(sb + (g0 + 1) * GR + rank * 8192, &p.wo, ct * 128 + rank * 64, kb * 64, fb, POL_WO);
              if (kb == 40) { prefetch_tm(&p.y); prefetch_tm(&p.out); }
            } else {
              const CUtensorMap* tm = kb == 64 ? &p.x : &p.y;
              const int c0 = (kb == 64 ? ct : rt) * 128, c1 = (kb == 64 ? rt : ct) * 128;
              tma2d(sb + g0 * GR, tm, c0, c1, fb, EV_NORMAL);
              tma2d(sb + (g0 + 1) * GR, tm, c0 + 64, c1, fb, EV_NORMAL);
            }
          }
          g0 = g0 == 12 ? (kb == 3 ? 2 : 0) : g0 + 2;
        }
        unsigned n = 0;
        if (lane == 0) n = atomicAdd(FLAG(F_EXIT), 1);
        if (__shfl_sync(0xffffffffu, n, 0) == NMAIN - 1) { *FLAG(lane) = 0; *FLAG(lane + 32) = 0; *FLAG(lane + 64) = 0; }
      }
      if (lane == 0) mbar_arrive(sb + SM_BAR + B_DONE * 8);
    }
    __syncwarp();
    cluster_wait();
  } else {
    asm volatile("setmaxnreg.inc.sync.aligned.u32 232;");
    Cons c;
    c.sb = sb; c.pf = 0; c.wg = wgi - 1; c.tid = threadIdx.x & 127;
    const int lane = threadIdx.x & 31, t = lane & 3;
    const int row = c.wg * 64 + (warp & 3) * 16 + (lane >> 2);
    const uint32_t dkk = desc_k(sb), dk0 = dkk + c.wg * 512, dm0 = desc_mn<8192>(sb), dv0 = desc_mn<16384>(sb);
    const uint32_t dsw = DG + 512 - c.wg * 1024;
    if (c.wg == 1) bar_arrive(1, 256);
    c.pfree = 1;
    asm("mapa.shared::cluster.u32 %0, %1, %2;" : "=r"(c.relb) : "r"(sb + SM_BAR + (B_EMPTY + (c.tid >> 1)) * 8), "r"(c.tid & 1));
    c.zero = p.zero;
    c.rnd = 0;
    const uint32_t stg = sb + (c.wg * 64 + (warp & 3) * 16 + ((lane >> 3) & 1) * 8 + (lane & 7)) * 128 + (((lane >> 4) ^ (lane & 7)) << 4);

    if (spare) {
      c.wait_full(1);
      int g = 2;
#pragma unroll 1
      for (int r = 0; r < 4; r++) {
        float d[4] = {0.f, 0.f, 0.f, 0.f}, e[4] = {0.f, 0.f, 0.f, 0.f};
#pragma unroll 1
        for (int kb = 0; kb < 16; kb += 2) {
          c.wait_full(g);
          wg_fence();
#pragma unroll
          for (int k = 0; k < 4; k++) {
            mma_ss_n8(d, dk0 + g * DG + k * 2, dkk + DG + kb * 8 + k * 2);
            mma_ss_n8(e, dk0 + (g + 1) * DG + k * 2, dkk + DG + kb * 8 + 8 + k * 2);
          }
          wg_commit();
          wg_wait<0>();
          c.release(g, 2);
          g = g == NGR - 2 ? 2 : g + 2;
        }
        reg_fence(d); reg_fence(e);
        d[0] += e[0]; d[2] += e[2];
        if (t == 0) {
          float* gp = g_gate + (lb - NMAIN) * 512 + r * 128 + row;
          gp[0] = rcp(1.f + ex2(-1.4426950408889634f * d[0])); gp[8] = rcp(1.f + ex2(-1.4426950408889634f * d[2]));
        }
      }
      fence_release();
      __syncwarp();
      if (lane == 0) flag_add(FLAG(F_GATE));
      TS(1);
    }
    const float dmask = (float)(2 * t - (row & 63));
    uint32_t pv[32];
#pragma unroll
    for (int i = 0; i < 32; i++) pv[i] = 0;
#pragma unroll 1
    for (int rnd = 0; rnd < (spare ? 0 : 2); rnd++) {
      float O[64];
      FTM(rnd * 8);
      FTG(0);
      FTH(56, c.rnd == rnd);
      c.wait_full(2);
      FTM(rnd * 8 + 1);
      FTH(57, c.rnd == rnd);
#pragma unroll 1
      for (int tile = c.zero; tile < 2; tile++) {
        float acc[128];
        const bool single = tile == 0;
        {
          FTG(tile * 32 + 1);
          const uint32_t a = dk0 + 2 * DG, b = dm0 + 3 * DG;
          c.turn_begin();
          FTG(tile * 32 + 2);
          FTH(58, c.rnd == rnd);
          wg_fence();
          mma_ss_n256_init<1>(acc, a, b);
#pragma unroll
          for (int k = 1; k < 4; k++) mma_ss_n256<1>(acc, a + k * 2, b + k * 128);
          wg_commit();
          if (single) c.turn_end();
          FTG(tile * 32 + 3);
        }
#pragma unroll 1
        for (int kb = 1; kb < 8; kb++) {
          const int g0 = 2 + 3 * (kb & 3);
          const uint32_t a = dk0 + g0 * DG, b = dm0 + (g0 + 1) * DG;
          const bool second = (kb == 1 && !single) || kb == 7;
          FTG(tile * 32 + kb * 4);
          if (!second) { wg_wait<0>(); c.release(2 + 3 * ((kb - 1) & 3), 3); }
          FTG(tile * 32 + kb * 4 + 1);
          c.wait_full(g0);
          if (!second) c.turn_begin();
          FTG(tile * 32 + kb * 4 + 2);
          wg_fence();
#pragma unroll
          for (int k = 0; k < 4; k++) mma_ss_n256<1>(acc, a + k * 2, b + k * 128);
          wg_commit();
          if (kb != 6) c.turn_end();
          if (second) { wg_wait<1>(); c.release(2 + 3 * ((kb - 1) & 3), 3); }
          FTG(tile * 32 + kb * 4 + 3);
          FTH(58 + kb, c.rnd == rnd || kb > 3);
          if (tile == 1 && kb == 3) { c.wait_stage_free(); stsm_frag<0, 4>(pv, stg); }
          if (tile == 1 && kb == 4) { stsm_frag<4, 8>(pv, stg); c.staged(0); }
        }
        c.rnd = rnd;
        c.wait_stage_free();
        const bool nxt = c.try_full(2);
        wg_wait<0>();
        reg_fence(acc);
        c.release(11, 3);
        pack_frag_scaled(acc, pv, SM_C, SM_C);
        stsm_frag(pv, stg);
        c.staged(0);
        pack_frag<64>(acc, pv);
        pin32(pv, sb);
        FTG(32 + tile * 32);
        if (!nxt) mbar_wait(sb + SM_BAR + (B_FULL + 2) * 8, (c.pf >> 2) & 1);
        c.pf ^= 4;
      }
      TS(1 + rnd * 3);
      FTM(rnd * 8 + 2);
      {
        float qa[64];
        float (&qb)[64] = O;
        {
          FTG(65);
          const uint32_t a = dk0 + 2 * DG, b = dm0 + 4 * DG;
          c.turn_begin();
          FTG(66);
          wg_fence();
          mma_ss_n128_init<1>(qa, a, b);
          mma_ss_n128_init<1>(qb, a + dsw, b);
#pragma unroll
          for (int k = 1; k < 4; k++) {
            mma_ss_n128<1>(qa, a + k * 2, b + k * 128);
            mma_ss_n128<1>(qb, a + dsw + k * 2, b + k * 128);
          }
          wg_commit();
          FTG(67);
        }
#pragma unroll 1
        for (int kb = 1; kb < 16; kb++) {
          const int g0 = 2 + 3 * (kb & 3);
          const uint32_t a = dk0 + g0 * DG, b = dm0 + (g0 + 2) * DG;
          const bool second = kb == 1 || kb == 15;
          FTG(64 + kb * 4);
          if (!second) { wg_wait<0>(); c.release(2 + 3 * ((kb - 1) & 3), 3); }
          FTG(65 + kb * 4);
          c.wait_full(g0);
          if (!second) c.turn_begin();
          FTG(66 + kb * 4);
          FTH(kb - 14, kb < 14);
          wg_fence();
#pragma unroll
          for (int k = 0; k < 4; k++) {
            mma_ss_n128<1>(qa, a + k * 2, b + k * 128);
            mma_ss_n128<1>(qb, a + dsw + k * 2, b + k * 128);
          }
          wg_commit();
          if (kb != 14) c.turn_end();
          if (second) { wg_wait<1>(); c.release(2 + 3 * ((kb - 1) & 3), 3); }
          FTG(67 + kb * 4);
          FTH(2, kb < 15);
          if (kb == QFLUSH) { c.wait_stage_free(); stsm_frag<0, 4>(pv, stg); }
          if (kb == QFLUSH + 1) { stsm_frag<4, 8>(pv, stg); c.staged(0); }
        }
        c.wait_stage_free();
        mbar_wait(sb + SM_BAR + (B_EMPTY + 2) * 8, rnd ^ 1);
        FTM(rnd * 8 + 3);
        FTH(3, 0);
        wg_wait<0>();
        reg_fence(qa); reg_fence(qb);
        FTH(4, 0);
        c.release(11, 3);
        pack_frag<0>(qa, pv);
        stsm_frag(pv, stg + 2 * GR);
        if (c.wg == 0) {
          pack_frag<0>(qb, pv);
          stsm_frag(pv, stg);
#pragma unroll
          for (int i = 16; i < 32; i++) pv[i] = 0;
        }
        fence_async_smem();
        c.wait_full(4);
      }
      TS(2 + rnd * 3);
      FTM(rnd * 8 + 4);
      FTH(5, 0);
      {
        const int nA = idx + 1;
        uint32_t (&P)[32] = pv;
        SoftState z;
        z.m0 = z.m1 = z.l0 = z.l1 = 0.f; z.shifted = c.zero;
#pragma unroll 1
        for (int seg = c.zero;; seg++) {
        if (c.wg == seg) attn_half(c, O, P, z, dk0, dkk, dv0, dmask, seg);
        if (seg) break;
        FTM(rnd * 8 + 5);
        int gk = c.wg ? 4 : 6, gv = c.wg ? 4 : 8;
        uint32_t dq = dk0 + (1 - c.wg < nA ? 2 * DG : 0), dk = dkk + gk * DG;
#pragma unroll 1
        for (int it = 1 - c.wg; it < 17 - c.wg; it++) {
          float S[64];
          FTA(it * 7 + 0); FTH((it < 3 ? 8 + it * 8 : it * 8 - 88) + 0, it >= 3 && it < 15);
          c.turn_begin();
          FTA(it * 7 + 2); FTH((it < 3 ? 8 + it * 8 : it * 8 - 88) + 1, it >= 3 && it < 15);
          wg_fence();
          issue_qk(S, dq, dk);
          wg_commit();
          const uint32_t dv = dv0 + gv * DG;
          uint32_t relk = c.relb + gk * 8, relv = c.relb + gv * 8;
          gk = it == 6 ? 12 : gv == 12 ? 4 : gv + 2;
          gv = it == 16 ? gk : gk == 12 ? 4 : gk + 2;
          uint32_t fk = sb + SM_BAR + (B_FULL + gk) * 8, fv = sb + SM_BAR + (B_FULL + gv) * 8, park = (c.pf >> gk) & 1, parv = (c.pf >> gv) & 1;
          c.pf ^= (1u << gk) | (1u << gv);
          dq = dk0 + (it + 1 < nA ? 2 * DG : 0); dk = dkk + gk * DG;
          float lo0 = z.l0, lo1 = z.l1;
          const bool first = it == nA || it == 0;
          if (it == nA) {
            if (EARLY_RCP) { lo0 = rcp(quad_sum(lo0)); lo1 = rcp(quad_sum(lo1)); }
            z.m0 = z.m1 = z.l0 = z.l1 = 0.f; z.shifted = 0;
          }
          float s0, s1, d0 = z.m0, d1 = z.m1;
          int pre = z.shifted || (it & 15) == 0;
          float lim = first ? -1.f : SM_LIMIT;
          asm volatile("" : "+r"(relk), "+r"(relv), "+r"(fk), "+r"(fv), "+r"(park), "+r"(parv), "+r"(dq), "+r"(dk), "+r"(pre), "+f"(lim), "+f"(d0), "+f"(d1), "+f"(z.l0), "+f"(z.l1));
          if (it) {
            issue_pv<0>(O, P, dv, it != nA + 1 && it != 1, true);
            issue_pv<1>(O, P, dv, 1, HALFPV ? it + c.wg > 1 : true);
            c.turn_end();
          } else stage_q2(c, O, P, stg);
          FTA(it * 7 + 3); FTH((it < 3 ? 8 + it * 8 : it * 8 - 88) + 2, it >= 3 && it < 15);
          wg_wait<4>();
          reg_fence(S);
          FTA(it * 7 + 4); FTH((it < 3 ? 8 + it * 8 : it * 8 - 88) + 3, it >= 3 && it < 15);
          if (c.tid < 4) asm volatile("mbarrier.arrive.shared::cluster.b64 _, [%0];" ::"r"(relk) : "memory");
#pragma unroll 1
          for (int pass = 0;; pass++) {
            if (pre) {
              if ((it & 15) == 0) mask_diag(S, dmask);
              if (z.shifted) shift_scores(S, d0, d1);
            }
            float tr[ROT];
            exp_quarter<0, 3>(S, P, tr, s0, s1, sb);
            exp_quarter<1, 2>(S, P, tr, s0, s1, sb);
            exp_quarter<2, 1>(S, P, tr, s0, s1, sb);
            exp_quarter<3, 0>(S, P, tr, s0, s1, sb);
            reg_fence(O);
            if (c.tid < (pass || !it ? 0 : 4)) asm volatile("mbarrier.arrive.shared::cluster.b64 _, [%0];" ::"r"(relv) : "memory");
            const bool ok = mbar_test(fk, park) & mbar_test(fv, parv);
            if (!ok) lim = -1.f;
            FTA(it * 7 + 5); FTH((it < 3 ? 8 + it * 8 : it * 8 - 88) + 4, it >= 3 && it < 15);
            if (!__any_sync(0xffffffffu, !(s0 <= lim && s1 <= lim))) break;
            if (pass) break;
            if (it == nA) {
              uint32_t pk[32];
              if (!EARLY_RCP) { lo0 = rcp(quad_sum(lo0)); lo1 = rcp(quad_sum(lo1)); }
              pack_frag_scaled(O, pk, lo0, lo1);
              stsm_frag(pk, stg + 2 * GR);
              c.staged(1);
            }
            if (!ok) { mbar_wait(fk, park); mbar_wait(fv, parv); }
            if (!soft_unsafe(s0, s1, first)) break;
            soft_fix(S, O, z, first, d0, d1);
            pre = 1;
          }
          z.l0 += s0; z.l1 += s1;
          FTA(it * 7 + 6); FTH((it < 3 ? 8 + it * 8 : it * 8 - 88) + 5, it >= 3 && it < 15);
        }
        FTM(rnd * 8 + 6);
        }
        FTH(48, 0);
        c.turn_begin();
        FTH(49, 0);
        wg_fence();
        issue_pv<0>(O, P, dv0 + 12 * DG, 1, true);
        issue_pv<1>(O, P, dv0 + 12 * DG, 1, !c.wg);
        c.turn_end();
        z.l0 = rcp(quad_sum(z.l0)); z.l1 = rcp(quad_sum(z.l1));
        wg_wait<0>();
        reg_fence(O); reg_fence(P);
        FTH(50, 0);
        c.release(12, 2);
        pack_frag_scaled(O, P, z.l0, z.l1);
        stsm_frag(P, stg);
        c.staged(0);
        FTM(rnd * 8 + 7);
        FTH(51, 0);
      }
      TS(3 + rnd * 3);
    }
    conv_tasks(c, p, (cn + 1 - c.wg) / 2, ((cn - 1) & 1) == c.wg, spare, cch + c.wg * cstep, 2 * cstep, dkk, warp & 3, lane);
    if (c.wg == 1) c.pf ^= 0x4;
    TS(7);
    if (!spare) {
      const int rt = 2 * grp + rank, ct = idx;
      float acc[64];
      int g0 = P3G + 2, pg = P3G;
      {
        FTO(0);
        c.wait_full(P3G);
        FTO(1);
        const uint32_t a = dk0 + P3G * DG, b = dm0 + (P3G + 1) * DG;
        wg_fence();
        mma_ss_n128_init<1>(acc, a, b);
#pragma unroll
        for (int k = 1; k < 4; k++) mma_ss_n128<1>(acc, a + k * 2, b + k * 128);
        wg_commit();
      }
#pragma unroll 1
      for (int kb = 1; kb < 64; kb++) {
        FTO(kb * 2);
        c.wait_full(g0);
        FTO(kb * 2 + 1);
        const uint32_t a = dk0 + g0 * DG, b = dm0 + (g0 + 1) * DG;
        wg_fence();
#pragma unroll
        for (int k = 0; k < 4; k++) mma_ss_n128<1>(acc, a + k * 2, b + k * 128);
        wg_commit();
        wg_wait<1>();
        c.release(pg, kb <= 59 ? 2 : 0);
        if (kb == 40) FTDUMP();
        pg = g0;
        g0 = g0 == 12 ? (kb == 3 ? 2 : 0) : g0 + 2;
      }
      cluster_arrive();
      c.wait_full(P3X);
      c.wait_full(P3Y);
      const float g0f = __uint_as_float(lds32(sb + SM_GATE + row * 4)), g1f = __uint_as_float(lds32(sb + SM_GATE + row * 4 + 32));
      const uint32_t gp0 = pack_bf16(g0f, g0f), gp1 = pack_bf16(g1f, g1f);
      const float h0 = 1.f - g0f, h1 = 1.f - g1f;
      const int w = warp & 3;
      const uint32_t xa = stg + P3X * GR;
      const uint32_t ya = sb + P3Y * GR + c.wg * 16384 + ((lane >> 4) * 8 + (lane & 7)) * 128 + (((2 * w + ((lane >> 3) & 1)) ^ (lane & 7)) << 4);
      uint32_t xy[32];
#pragma unroll
      for (int jj = 0; jj < 8; jj++) {
        uint32_t x[4], y[4];
        asm volatile("ldmatrix.sync.aligned.m8n8.x4.shared.b16 {%0,%1,%2,%3}, [%4];" : "=r"(x[0]), "=r"(x[1]), "=r"(x[2]), "=r"(x[3]) : "r"((xa ^ ((jj & 3) << 5)) + (jj >> 2) * 16384) : "memory");
        asm volatile("ldmatrix.sync.aligned.m8n8.x4.trans.shared.b16 {%0,%1,%2,%3}, [%4];" : "=r"(y[0]), "=r"(y[1]), "=r"(y[2]), "=r"(y[3]) : "r"(ya + jj * 2048) : "memory");
#pragma unroll
        for (int i = 0; i < 4; i++) xy[4 * jj + i] = hmul2(x[i], y[i]);
      }
      wg_wait<0>();
      reg_fence(acc);
      TS(8);
#pragma unroll
      for (int i = 0; i < 32; i++) {
        const float h = (i & 1) ? h1 : h0;
        xy[i] = hfma2((i & 1) ? gp1 : gp0, xy[i], pack_bf16(acc[2 * i] * h, acc[2 * i + 1] * h));
      }
      stsm_frag(xy, xa);
      fence_async_smem();
      __syncwarp();
      if (lane == 0) {
        const int r0 = c.wg * 64 + w * 16;
        tma2d_store(&p.out, sb + P3X * GR + r0 * 128, ct * 128, rt * 128 + r0);
        tma2d_store(&p.out, sb + (P3X + 1) * GR + r0 * 128, ct * 128 + 64, rt * 128 + r0);
        asm volatile("cp.async.bulk.commit_group;\ncp.async.bulk.wait_group.read 0;" ::: "memory");
      }
    } else { FTDUMP(); cluster_arrive(); }
    if (lane == 0) mbar_arrive(sb + SM_BAR + B_DONE * 8);
    __syncwarp();
    TS(9);
    cluster_wait();
  }
}

typedef CUresult (*EncFn)(CUtensorMap*, CUtensorMapDataType, cuuint32_t, void*, const cuuint64_t*, const cuuint64_t*, const cuuint32_t*,
                          const cuuint32_t*, CUtensorMapInterleave, CUtensorMapSwizzle, CUtensorMapL2promotion, CUtensorMapFloatOOBfill);

void enc2d(EncFn enc, CUtensorMap* tm, const void* base, uint64_t cols, uint64_t rows, uint32_t bc, uint32_t br) {
  cuuint64_t dims[2] = {cols, rows}; cuuint64_t strides[1] = {cols * 2}; cuuint32_t box[2] = {bc, br}; cuuint32_t es[2] = {1, 1};
  enc(tm, CU_TENSOR_MAP_DATA_TYPE_BFLOAT16, 2, const_cast<void*>(base), dims, strides, box, es, CU_TENSOR_MAP_INTERLEAVE_NONE,
      CU_TENSOR_MAP_SWIZZLE_128B, CU_TENSOR_MAP_L2_PROMOTION_L2_256B, CU_TENSOR_MAP_FLOAT_OOB_FILL_NONE);
}
void enc3d(EncFn enc, CUtensorMap* tm, const void* base, uint64_t K, uint64_t N) {
  cuuint64_t dims[3] = {64, K, N / 64}; cuuint64_t strides[2] = {N * 2, 128}; cuuint32_t box[3] = {64, 64, 2}; cuuint32_t es[3] = {1, 1, 1};
  enc(tm, CU_TENSOR_MAP_DATA_TYPE_BFLOAT16, 3, const_cast<void*>(base), dims, strides, box, es, CU_TENSOR_MAP_INTERLEAVE_NONE,
      CU_TENSOR_MAP_SWIZZLE_128B, CU_TENSOR_MAP_L2_PROMOTION_L2_256B, CU_TENSOR_MAP_FLOAT_OOB_FILL_NONE);
}

}

extern "C" void kernel_launch(void* const* d_in, const int* in_sizes, int n_in, void* d_out, int out_size) {
  (void)in_sizes; (void)n_in; (void)out_size;
  typedef const __nv_bfloat16* BP;
  BP xq = (BP)d_in[0], ak = (BP)d_in[1], av = (BP)d_in[2], shk = (BP)d_in[3], ssk = (BP)d_in[4], ssd = (BP)d_in[5];
  BP ckv = (BP)d_in[7], wq = (BP)d_in[8], wuk = (BP)d_in[9], wuv = (BP)d_in[10], wo = (BP)d_in[11], gw = (BP)d_in[12];

  static EncFn enc = nullptr;
  if (!enc) {
    cudaDriverEntryPointQueryResult qr;
    cudaGetDriverEntryPoint("cuTensorMapEncodeTiled", (void**)&enc, cudaEnableDefault, &qr);
    cudaFuncSetAttribute(mega_kernel, cudaFuncAttributeMaxDynamicSharedMemorySize, SMEM_BYTES);
  }
  Params p;
  void* yT = nullptr;
  cudaGetSymbolAddress(&yT, g_yT);
  enc2d(enc, &p.x, xq, DM, SEQ, 64, 128);
  enc2d(enc, &p.c, ckv, DC, SEQ, 64, 128);
  enc3d(enc, &p.wq, wq, DM, NH * HD);
  enc3d(enc, &p.wuk, wuk, DC, NH * HD);
  enc3d(enc, &p.wuv, wuv, DC, NH * HD);
  enc2d(enc, &p.wo, wo, DM, NH * HD, 64, 64);
  enc2d(enc, &p.y, yT, SEQ, DM, 64, 128);
  enc2d(enc, &p.out, d_out, DM, SEQ, 64, 16);
  {
    void* wp = nullptr;
    cudaGetSymbolAddress(&wp, g_w);
    cuuint64_t dims[3] = {WSTRIDE / 2, DM / 2, 2}; cuuint64_t strides[2] = {2 * WSTRIDE, WSTRIDE}; cuuint32_t box[3] = {16, 32, 2}; cuuint32_t es[3] = {1, 1, 1};
    enc(&p.w, CU_TENSOR_MAP_DATA_TYPE_BFLOAT16, 3, wp, dims, strides, box, es, CU_TENSOR_MAP_INTERLEAVE_NONE,
        CU_TENSOR_MAP_SWIZZLE_32B, CU_TENSOR_MAP_L2_PROMOTION_NONE, CU_TENSOR_MAP_FLOAT_OOB_FILL_NONE);
  }
  p.zero = 0;
  p.cp = ckv; p.wukp = wuk; p.wuvp = wuv;
  p.xp = xq; p.gate_w = gw; p.ak = ak; p.av = av; p.shk = shk; p.ssk = ssk; p.ssd = ssd;

  mega_kernel<<<132, NTHREADS, SMEM_BYTES>>>(p);
}
```

```cpp
#include <cuda_runtime.h>
#include <cuda.h>
#include <cuda_bf16.h>
#include <stdint.h>

namespace {

constexpr int SEQ = 2048, DM = 1024, DC = 512, NH = 32, HD = 128;
constexpr int GR = 16384;
constexpr int NGR = 14;
constexpr int SM_BAR = NGR * GR;
constexpr int SM_GATE = SM_BAR + 512;
constexpr int SM_UST = SM_GATE + 512;
constexpr int SMEM_BYTES = SM_UST + 2048;
constexpr int NTHREADS = 384;
#define SM_LIMIT 1.0995116e12f
#define SM_LOW 9.094947e-13f
constexpr int CN_MAIN = 5, CN_SPARE = 96;
constexpr int P3G = 6, P3X = 10, P3Y = 12;
constexpr int NMAIN = 128;

constexpr int B_FULL = 0, B_EMPTY = 14, B_EV = 28, B_SLOT = 34, B_DONE = 35;

__device__ __align__(1024) uint8_t g_kv[2 * 16 * 16 * 32768];
__device__ __align__(1024) uint8_t g_cimg[16 * NH * 32768];
__device__ __align__(1024) __nv_bfloat16 g_yT[DM * SEQ];
__device__ __align__(1024) float g_gate[SEQ];
#define CWIDE 0
constexpr int WZ = CWIDE ? 768 : 256, WPL = WZ + 4096, WBYTES = 2 * WPL + 32, WSTRIDE = 2 * WPL + 128;
__device__ __align__(1024) uint8_t g_w[DM * WSTRIDE];
__device__ unsigned g_flags[128 * 8];
constexpr int F_KV = 0, F_CTX = 16, F_U = 48, F_AD = 56, F_Y = 64, F_GATE = 72, F_EXIT = 73;
constexpr int NSLOT = 66;
__device__ unsigned g_claim[96];
#define FLAG(i) (&g_flags[(i) * 8])

#define TS(slot)
#define TSW(slot)
#define FTX(i, off)
#define FTDUMP()

#define ST_OUT 0
#define QFLUSH 4
#define POL_W EV_NORMAL
#define POL_WO EV_FIRST
#define POL_KV EV_NORMAL
#define POL_C EV_FIRST
#define POL_CTX EV_FIRST
#define HALFPV 1
#define PWAIT mbar_wait1
#define PRE_SLEEP 1500
#define EXPV 1
#define SUMV 0
#define ROT 8
#define EARLY_RCP 1
#define DFOLD 1
#define CLAIM 1
#define START_PF 1
#define FINE_MODE 0
#define FINE_RND 1
#define FTA(i) do { if (FINE_MODE == 0) FTX(i, rnd ^ FINE_RND); } while (0)
#define FTG(i) do { if (FINE_MODE == 1) FTX(i, rnd ^ FINE_RND); } while (0)
#define FTM(i) do { if (FINE_MODE == 4) FTX(i, 0); } while (0)
#define FTC(k) do { if (FINE_MODE == 5) FTX((i & 7) * 8 + (k), (i >> 3) ^ FINE_RND); } while (0)
#define FTH(i, off) do { if (FINE_MODE == 6) FTX(i, (c.rnd ^ FINE_RND) | (off)); } while (0)
#define FTO(i) do { if (FINE_MODE == 2) FTX(i, 0); } while (0)

__device__ __forceinline__ uint32_t smem_u32(const void* p) { return (uint32_t)__cvta_generic_to_shared(p); }
__device__ __forceinline__ void mbar_init(uint32_t bar, int cnt) { asm volatile("mbarrier.init.shared::cta.b64 [%0], %1;" ::"r"(bar), "r"(cnt) : "memory"); }
__device__ __forceinline__ void mbar_expect_tx(uint32_t bar, uint32_t bytes) { asm volatile("mbarrier.arrive.expect_tx.shared::cta.b64 _, [%0], %1;" ::"r"(bar), "r"(bytes) : "memory"); }
__device__ __forceinline__ void mbar_arrive(uint32_t bar) { asm volatile("mbarrier.arrive.shared::cta.b64 _, [%0];" ::"r"(bar) : "memory"); }
__device__ __forceinline__ void mbar_arrive_cluster(uint32_t bar, uint32_t cta) {
  asm volatile("{\n.reg .b32 r;\nmapa.shared::cluster.u32 r, %0, %1;\nmbarrier.arrive.shared::cluster.b64 _, [r];\n}\n" ::"r"(bar), "r"(cta) : "memory");
}
__device__ __forceinline__ bool mbar_try(uint32_t bar, uint32_t parity) {
  uint32_t ok;
  asm volatile("{\n.reg .pred p;\nmbarrier.try_wait.parity.shared::cta.b64 p, [%1], %2, 20000;\nselp.u32 %0, 1, 0, p;\n}\n" : "=r"(ok) : "r"(bar), "r"(parity) : "memory");
  return ok;
}
__device__ __forceinline__ bool mbar_test(uint32_t bar, uint32_t parity) {
  uint32_t ok;
  asm volatile("{\n.reg .pred p;\nmbarrier.test_wait.parity.shared::cta.b64 p, [%1], %2;\nselp.u32 %0, 1, 0, p;\n}\n" : "=r"(ok) : "r"(bar), "r"(parity) : "memory");
  return ok;
}
__device__ __forceinline__ void mbar_wait(uint32_t bar, uint32_t parity) {
  asm volatile("{\n.reg .pred p;\nWAIT_LOOP:\nbar.warp.sync -1;\nmbarrier.try_wait.parity.shared::cta.b64 p, [%0], %1;\n@!p bra WAIT_LOOP;\n}\n" ::"r"(bar), "r"(parity) : "memory");
}
__device__ __forceinline__ void mbar_wait1(uint32_t bar, uint32_t parity) {
  asm volatile("{\n.reg .pred p;\nWAIT_LOOP:\nbar.warp.sync -1;\nmbarrier.try_wait.parity.shared::cta.b64 p, [%0], %1, 4000;\n@!p bra WAIT_LOOP;\n}\n" ::"r"(bar), "r"(parity) : "memory");
}
constexpr uint64_t EV_NORMAL = 0x1000000000000000ull, EV_FIRST = 0x12F0000000000000ull;
__device__ __forceinline__ uint32_t ldg_stream(const uint32_t* p) {
  uint32_t r; asm volatile("ld.global.nc.L1::no_allocate.L2::cache_hint.b32 %0, [%1], %2;" : "=r"(r) : "l"(p), "l"(EV_FIRST)); return r;
}
__device__ __forceinline__ void tma2d(uint32_t dst, const CUtensorMap* tm, int c0, int c1, uint32_t bar, uint64_t pol) {
  asm volatile("cp.async.bulk.tensor.2d.shared::cluster.global.mbarrier::complete_tx::bytes.L2::cache_hint [%0], [%1, {%3, %4}], [%2], %5;"
               ::"r"(dst), "l"(tm), "r"(bar), "r"(c0), "r"(c1), "l"(pol) : "memory");
}
__device__ __forceinline__ void tma2d_mc(uint32_t dst, const CUtensorMap* tm, int c0, int c1, uint32_t bar, uint64_t pol) {
  asm volatile("cp.async.bulk.tensor.2d.shared::cluster.global.mbarrier::complete_tx::bytes.multicast::cluster.L2::cache_hint [%0], [%1, {%3, %4}], [%2], %5, %6;"
               ::"r"(dst), "l"(tm), "r"(bar), "r"(c0), "r"(c1), "h"((uint16_t)3), "l"(pol) : "memory");
}
__device__ __forceinline__ void tma3d(uint32_t dst, const CUtensorMap* tm, int c0, int c1, int c2, uint32_t bar, uint64_t pol) {
  asm volatile("cp.async.bulk.tensor.3d.shared::cluster.global.mbarrier::complete_tx::bytes.L2::cache_hint [%0], [%1, {%3, %4, %5}], [%2], %6;"
               ::"r"(dst), "l"(tm), "r"(bar), "r"(c0), "r"(c1), "r"(c2), "l"(pol) : "memory");
}
__device__ __forceinline__ void tma3d_mc(uint32_t dst, const CUtensorMap* tm, int c0, int c1, int c2, uint32_t bar, uint64_t pol) {
  asm volatile("cp.async.bulk.tensor.3d.shared::cluster.global.mbarrier::complete_tx::bytes.multicast::cluster.L2::cache_hint [%0], [%1, {%3, %4, %5}], [%2], %6, %7;"
               ::"r"(dst), "l"(tm), "r"(bar), "r"(c0), "r"(c1), "r"(c2), "h"((uint16_t)3), "l"(pol) : "memory");
}
__device__ __forceinline__ void bulk_g2s(uint32_t dst, const void* src, uint32_t bytes, uint32_t bar, uint64_t pol) {
  asm volatile("cp.async.bulk.shared::cluster.global.mbarrier::complete_tx::bytes.L2::cache_hint [%0], [%1], %2, [%3], %4;"
               ::"r"(dst), "l"(src), "r"(bytes), "r"(bar), "l"(pol) : "memory");
}
__device__ __forceinline__ void tma2d_store(const CUtensorMap* tm, uint32_t src, int c0, int c1) {
  asm volatile("cp.async.bulk.tensor.2d.global.shared::cta.bulk_group [%0, {%2, %3}], [%1];" ::"l"(tm), "r"(src), "r"(c0), "r"(c1) : "memory");
}
__device__ __forceinline__ void prefetch_tm(const CUtensorMap* tm) { asm volatile("prefetch.tensormap [%0];" ::"l"(tm) : "memory"); }
__device__ __forceinline__ void wg_fence() { asm volatile("wgmma.fence.sync.aligned;" ::: "memory"); }
__device__ __forceinline__ void wg_commit() { asm volatile("wgmma.commit_group.sync.aligned;" ::: "memory"); }
template <int N> __device__ __forceinline__ void wg_wait() { asm volatile("wgmma.wait_group.sync.aligned %0;" ::"n"(N) : "memory"); }
__device__ __forceinline__ void bar_sync(int id, int n) { asm volatile("bar.sync %0, %1;" ::"r"(id), "r"(n) : "memory"); }
__device__ __forceinline__ void bar_arrive(int id, int n) { asm volatile("bar.arrive %0, %1;" ::"r"(id), "r"(n) : "memory"); }
__device__ __forceinline__ void fence_async_smem() { asm volatile("fence.proxy.async.shared::cta;" ::: "memory"); }
__device__ __forceinline__ void fence_async_all() { asm volatile("fence.proxy.async.global;" ::: "memory"); }
__device__ __forceinline__ uint32_t pack_bf16(float lo, float hi) { uint32_t r; asm("cvt.rn.bf16x2.f32 %0, %1, %2;" : "=r"(r) : "f"(hi), "f"(lo)); return r; }
__device__ __forceinline__ float ex2(float x) { float r; asm("ex2.approx.ftz.f32 %0, %1;" : "=f"(r) : "f"(x)); return r; }
__device__ __forceinline__ float rcp(float x) { float r; asm("rcp.approx.ftz.f32 %0, %1;" : "=f"(r) : "f"(x)); return r; }
__device__ __forceinline__ void flag_wait(const unsigned* f, unsigned target) {
  unsigned v;
  do { asm volatile("ld.acquire.gpu.global.u32 %0, [%1];" : "=r"(v) : "l"(f) : "memory"); } while (__any_sync(0xffffffffu, v < target));
}
__device__ __forceinline__ bool elect() {
  uint32_t r;
  asm volatile("{\n.reg .pred p;\nelect.sync _|p, -1;\nselp.u32 %0, 1, 0, p;\n}\n" : "=r"(r));
  return r;
}
__device__ __forceinline__ void fence_release() { asm volatile("fence.release.gpu;" ::: "memory"); }
__device__ __forceinline__ void flag_add(unsigned* f) { asm volatile("red.relaxed.gpu.global.add.u32 [%0], 1;" ::"l"(f) : "memory"); }
__device__ __forceinline__ void cluster_arrive() { asm volatile("barrier.cluster.arrive.relaxed.aligned;" ::: "memory"); }
__device__ __forceinline__ void cluster_wait() { asm volatile("barrier.cluster.wait.aligned;" ::: "memory"); }
__device__ __forceinline__ uint32_t hmul2(uint32_t a, uint32_t b) { uint32_t r; asm("mul.rn.bf16x2 %0, %1, %2;" : "=r"(r) : "r"(a), "r"(b)); return r; }
__device__ __forceinline__ uint32_t hadd2(uint32_t a, uint32_t b) { uint32_t r; asm("add.rn.bf16x2 %0, %1, %2;" : "=r"(r) : "r"(a), "r"(b)); return r; }
__device__ __forceinline__ uint32_t hfma2(uint32_t a, uint32_t b, uint32_t c) { uint32_t r; asm("fma.rn.bf16x2 %0, %1, %2, %3;" : "=r"(r) : "r"(a), "r"(b), "r"(c)); return r; }
__device__ __forceinline__ uint32_t lds32(uint32_t a) { uint32_t r; asm volatile("ld.shared.b32 %0, [%1];" : "=r"(r) : "r"(a) : "memory"); return r; }
__device__ __forceinline__ uint4 lds128(uint32_t a) { uint4 r; asm volatile("ld.shared.v4.b32 {%0,%1,%2,%3}, [%4];" : "=r"(r.x), "=r"(r.y), "=r"(r.z), "=r"(r.w) : "r"(a) : "memory"); return r; }
__device__ __forceinline__ uint32_t desc_k(uint32_t addr) { return ((addr & 0x3FFFF) >> 4) | (1u << 16); }
template <int LBO> __device__ __forceinline__ uint32_t desc_mn(uint32_t addr) { return ((addr & 0x3FFFF) >> 4) | ((uint32_t)(LBO >> 4) << 16); }
#define DHI "0x40000040"

#define R8(d, o) "+f"(d[o]), "+f"(d[o + 1]), "+f"(d[o + 2]), "+f"(d[o + 3]), "+f"(d[o + 4]), "+f"(d[o + 5]), "+f"(d[o + 6]), "+f"(d[o + 7])
#define R32(d, o) R8(d, o), R8(d, o + 8), R8(d, o + 16), R8(d, o + 24)
#define R64(d, o) R32(d, o), R32(d, o + 32)
#define L64 "%0,%1,%2,%3,%4,%5,%6,%7,%8,%9,%10,%11,%12,%13,%14,%15,%16,%17,%18,%19,%20,%21,%22,%23,%24,%25,%26,%27,%28,%29,%30,%31," \
            "%32,%33,%34,%35,%36,%37,%38,%39,%40,%41,%42,%43,%44,%45,%46,%47,%48,%49,%50,%51,%52,%53,%54,%55,%56,%57,%58,%59,%60,%61,%62,%63"
#define L128 L64 ",%64,%65,%66,%67,%68,%69,%70,%71,%72,%73,%74,%75,%76,%77,%78,%79,%80,%81,%82,%83,%84,%85,%86,%87,%88,%89,%90,%91,%92,%93,%94,%95," \
            "%96,%97,%98,%99,%100,%101,%102,%103,%104,%105,%106,%107,%108,%109,%110,%111,%112,%113,%114,%115,%116,%117,%118,%119,%120,%121,%122,%123,%124,%125,%126,%127"

template <int TB> __device__ __forceinline__ void mma_ss_n128(float (&d)[64], uint32_t da, uint32_t db) {
  asm volatile("{\n.reg .b64 da, db;\nmov.b64 da, {%64, " DHI "};\nmov.b64 db, {%65, " DHI "};\n"
               "wgmma.mma_async.sync.aligned.m64n128k16.f32.bf16.bf16 {" L64 "}, da, db, 1, 1, 1, 0, %66;\n}\n"
               : R64(d, 0) : "r"(da), "r"(db), "n"(TB));
}
template <int TB> __device__ __forceinline__ void mma_rs_n128(float (&d)[64], uint32_t a0, uint32_t a1, uint32_t a2, uint32_t a3, uint32_t db, int sd) {
  asm volatile("{\n.reg .pred p;\n.reg .b64 db;\nsetp.ne.b32 p, %69, 0;\nmov.b64 db, {%68, " DHI "};\n"
               "wgmma.mma_async.sync.aligned.m64n128k16.f32.bf16.bf16 {" L64 "}, {%64,%65,%66,%67}, db, p, 1, 1, %70;\n}\n"
               : R64(d, 0) : "r"(a0), "r"(a1), "r"(a2), "r"(a3), "r"(db), "r"(sd), "n"(TB));
}
template <int TB> __device__ __forceinline__ void mma_ss_n256(float (&d)[128], uint32_t da, uint32_t db) {
  asm volatile("{\n.reg .b64 da, db;\nmov.b64 da, {%128, " DHI "};\nmov.b64 db, {%129, " DHI "};\n"
               "wgmma.mma_async.sync.aligned.m64n256k16.f32.bf16.bf16 {" L128 "}, da, db, 1, 1, 1, 0, %130;\n}\n"
               : R64(d, 0), R64(d, 64) : "r"(da), "r"(db), "n"(TB));
}
#define W8(d, o) "=f"(d[o]), "=f"(d[o + 1]), "=f"(d[o + 2]), "=f"(d[o + 3]), "=f"(d[o + 4]), "=f"(d[o + 5]), "=f"(d[o + 6]), "=f"(d[o + 7])
#define W32(d, o) W8(d, o), W8(d, o + 8), W8(d, o + 16), W8(d, o + 24)
#define W64(d, o) W32(d, o), W32(d, o + 32)
template <int TB> __device__ __forceinline__ void mma_ss_n128_init(float (&d)[64], uint32_t da, uint32_t db) {
  asm volatile("{\n.reg .b64 da, db;\nmov.b64 da, {%64, " DHI "};\nmov.b64 db, {%65, " DHI "};\n"
               "wgmma.mma_async.sync.aligned.m64n128k16.f32.bf16.bf16 {" L64 "}, da, db, 0, 1, 1, 0, %66;\n}\n"
               : W64(d, 0) : "r"(da), "r"(db), "n"(TB));
}
template <int TB> __device__ __forceinline__ void mma_ss_n256_init(float (&d)[128], uint32_t da, uint32_t db) {
  asm volatile("{\n.reg .b64 da, db;\nmov.b64 da, {%128, " DHI "};\nmov.b64 db, {%129, " DHI "};\n"
               "wgmma.mma_async.sync.aligned.m64n256k16.f32.bf16.bf16 {" L128 "}, da, db, 0, 1, 1, 0, %130;\n}\n"
               : W64(d, 0), W64(d, 64) : "r"(da), "r"(db), "n"(TB));
}
#define L32 "%0,%1,%2,%3,%4,%5,%6,%7,%8,%9,%10,%11,%12,%13,%14,%15,%16,%17,%18,%19,%20,%21,%22,%23,%24,%25,%26,%27,%28,%29,%30,%31"
__device__ __forceinline__ void mma_ss_n64(float (&d)[32], uint32_t da, uint32_t db) {
  asm volatile("{\n.reg .b64 da, db;\nmov.b64 da, {%32, " DHI "};\nmov.b64 db, {%33, " DHI "};\n"
               "wgmma.mma_async.sync.aligned.m64n64k16.f32.bf16.bf16 {" L32 "}, da, db, 1, 1, 1, 0, 0;\n}\n"
               : R32(d, 0) : "r"(da), "r"(db));
}
__device__ __forceinline__ void mma_ss_n64_init(float (&d)[32], uint32_t da, uint32_t db) {
  asm volatile("{\n.reg .b64 da, db;\nmov.b64 da, {%32, " DHI "};\nmov.b64 db, {%33, " DHI "};\n"
               "wgmma.mma_async.sync.aligned.m64n64k16.f32.bf16.bf16 {" L32 "}, da, db, 0, 1, 1, 0, 0;\n}\n"
               : W32(d, 0) : "r"(da), "r"(db));
}
#define L16 "%0,%1,%2,%3,%4,%5,%6,%7,%8,%9,%10,%11,%12,%13,%14,%15"
template <int O, bool INIT> __device__ __forceinline__ void mma_rs_n32(float (&d)[128], uint32_t a0, uint32_t a1, uint32_t a2, uint32_t a3, uint32_t db) {
  if (INIT) asm volatile("{\n.reg .b64 db;\nmov.b64 db, {%20, 0x00000008};\n"
               "wgmma.mma_async.sync.aligned.m64n32k16.f32.bf16.bf16 {" L16 "}, {%16,%17,%18,%19}, db, 0, 1, 1, 0;\n}\n"
               : W8(d, O), W8(d, O + 8) : "r"(a0), "r"(a1), "r"(a2), "r"(a3), "r"(db));
  else asm volatile("{\n.reg .b64 db;\nmov.b64 db, {%20, 0x00000008};\n"
               "wgmma.mma_async.sync.aligned.m64n32k16.f32.bf16.bf16 {" L16 "}, {%16,%17,%18,%19}, db, 1, 1, 1, 0;\n}\n"
               : R8(d, O), R8(d, O + 8) : "r"(a0), "r"(a1), "r"(a2), "r"(a3), "r"(db));
}
template <int O, bool INIT> __device__ __forceinline__ void mma_rs_n64(float (&d)[128], uint32_t a0, uint32_t a1, uint32_t a2, uint32_t a3, uint32_t db) {
  if (INIT) asm volatile("{\n.reg .b64 db;\nmov.b64 db, {%36, 0x00000008};\n"
               "wgmma.mma_async.sync.aligned.m64n64k16.f32.bf16.bf16 {" L32 "}, {%32,%33,%34,%35}, db, 0, 1, 1, 0;\n}\n"
               : W32(d, O) : "r"(a0), "r"(a1), "r"(a2), "r"(a3), "r"(db));
  else asm volatile("{\n.reg .b64 db;\nmov.b64 db, {%36, 0x00000008};\n"
               "wgmma.mma_async.sync.aligned.m64n64k16.f32.bf16.bf16 {" L32 "}, {%32,%33,%34,%35}, db, 1, 1, 1, 0;\n}\n"
               : R32(d, O) : "r"(a0), "r"(a1), "r"(a2), "r"(a3), "r"(db));
}
template <int S, int J> __device__ __forceinline__ void conv_step(float (&d)[128], const uint32_t (&a)[64], uint32_t db) {
  if constexpr (J >= 0 && J >= (S >> 1)) {
    if constexpr (J >= 8 - 2 * CWIDE) {
      mma_rs_n64<16 * (J - 1), S == 0>(d, a[4 * S], a[4 * S + 1], a[4 * S + 2], a[4 * S + 3], db + (uint32_t)((2 * (J - 1) - S) * 16));
      conv_step<S, J - 2>(d, a, db);
    } else {
      mma_rs_n32<16 * J, S == 0>(d, a[4 * S], a[4 * S + 1], a[4 * S + 2], a[4 * S + 3], db + (uint32_t)((2 * J - S) * 16));
      conv_step<S, J - 1>(d, a, db);
    }
  }
}
__device__ __forceinline__ void mma_ss_n8(float (&d)[4], uint32_t da, uint32_t db) {
  asm volatile("{\n.reg .b64 da, db;\nmov.b64 da, {%4, " DHI "};\nmov.b64 db, {%5, 0x00000008};\n"
               "wgmma.mma_async.sync.aligned.m64n8k16.f32.bf16.bf16 {%0,%1,%2,%3}, da, db, 1, 1, 1, 0, 0;\n}\n"
               : "+f"(d[0]), "+f"(d[1]), "+f"(d[2]), "+f"(d[3]) : "r"(da), "r"(db));
}
template <int N> __device__ __forceinline__ void reg_fence(float (&d)[N]) {
#pragma unroll
  for (int i = 0; i < N; i++) asm volatile("" : "+f"(d[i])::"memory");
}
template <int N> __device__ __forceinline__ void reg_fence(uint32_t (&d)[N]) {
#pragma unroll
  for (int i = 0; i < N; i++) asm volatile("" : "+r"(d[i])::"memory");
}

struct __align__(64) Params {
  CUtensorMap x, c, wq, wuk, wuv, wo, y, out, w;
  const __nv_bfloat16* xp;
  const __nv_bfloat16* gate_w;
  const __nv_bfloat16 *ak, *av, *shk, *ssk, *ssd, *cp, *wukp, *wuvp;
  int zero;
};

template <int O, int N, int M> __device__ __forceinline__ void pack_frag(const float (&acc)[N], uint32_t (&pk)[M]) {
#pragma unroll
  for (int i = 0; i < 32; i++) pk[i] = pack_bf16(acc[O + 2 * i], acc[O + 2 * i + 1]);
}
template <int N> __device__ __forceinline__ void pack_frag_scaled(const float (&acc)[N], uint32_t (&pk)[32], float s0, float s1) {
#pragma unroll
  for (int i = 0; i < 32; i++) { const float s = (i & 1) ? s1 : s0; pk[i] = pack_bf16(acc[2 * i] * s, acc[2 * i + 1] * s); }
}
template <int J0 = 0, int J1 = 8, int M> __device__ __forceinline__ void stsm_frag(const uint32_t (&pk)[M], uint32_t a) {
#pragma unroll
  for (int jj = J0; jj < J1; jj++)
    asm volatile("stmatrix.sync.aligned.m8n8.x4.shared.b16 [%0], {%1,%2,%3,%4};" ::"r"((a ^ ((jj & 3) << 5)) + (jj >> 2) * 16384),
                 "r"(pk[4 * jj]), "r"(pk[4 * jj + 1]), "r"(pk[4 * jj + 2]), "r"(pk[4 * jj + 3]) : "memory");
}

struct Cons {
  uint32_t sb;
  uint32_t pf;
  int wg, tid;
  __device__ __forceinline__ void wait_full(int g) { mbar_wait(sb + SM_BAR + (B_FULL + g) * 8, (pf >> g) & 1); pf ^= 1u << g; }
  uint32_t relb;
  __device__ __forceinline__ void release(int g, int n) {
    if (tid < 2 * n) asm volatile("mbarrier.arrive.shared::cluster.b64 _, [%0];" ::"r"(relb + g * 8) : "memory");
  }
  __device__ __forceinline__ void turn_begin() { bar_sync(1 + wg, 256); }
  __device__ __forceinline__ void turn_end() { bar_arrive(2 - wg, 256); }
  __device__ __forceinline__ void staged(int e) { __syncwarp(); if ((tid & 31) == 0) mbar_arrive(sb + SM_BAR + (B_EV + 2 * e + wg) * 8); }
  int zero;
  int rnd;
  uint32_t pfree;
  __device__ __forceinline__ void wait_stage_free() { mbar_wait(sb + SM_BAR + (B_EV + 4 + wg) * 8, pfree); pfree ^= 1; }
  __device__ __forceinline__ bool try_full(int g) { return mbar_test(sb + SM_BAR + (B_FULL + g) * 8, (pf >> g) & 1); }
};

constexpr float SM_C = 0.08838834764831845f * 1.4426950408889634f;
struct SoftState { float m0, m1, l0, l1; int shifted; };
__device__ __forceinline__ void ex2_rot(float& t, float s, uint32_t never_zero) {
  asm("{\n.reg .pred p;\nsetp.ne.u32 p, %2, 0;\n@p ex2.approx.ftz.f32 %0, %1;\n}\n" : "+f"(t) : "f"(s), "r"(never_zero));
}
__device__ __forceinline__ void pin(float a, uint32_t never_zero) {
  asm volatile("{\n.reg .pred p;\nsetp.eq.u32 p, %1, 0;\n@p st.shared.f32 [%1], %0;\n}\n" ::"f"(a), "r"(never_zero) : "memory");
}
template <int O, int N> __device__ __forceinline__ void reg_fence_part(uint32_t (&d)[32]) {
#pragma unroll
  for (int i = O; i < O + N; i++) asm volatile("" : "+r"(d[i])::"memory");
}
template <int Q, int W, int N> __device__ __forceinline__ void exp_quarter(const float (&S)[N], uint32_t (&P)[32], float (&t)[ROT], float& s0, float& s1, uint32_t nz) {
#pragma unroll
  for (int i = 8 * Q; i < 8 * Q + 8; i++) {
    float& a = t[(2 * i) % ROT];
    float& b = t[(2 * i + 1) % ROT];
    if (2 * i < ROT) { a = ex2(S[2 * i]); b = ex2(S[2 * i + 1]); }
    else { ex2_rot(a, S[2 * i], nz); ex2_rot(b, S[2 * i + 1], nz); }
    if (i < 2) { if (i) s1 = a + b; else s0 = a + b; }
    else if (SUMV == 0) { if (i & 1) { s1 += a; s1 += b; } else { s0 += a; s0 += b; } }
    else { if (i & 1) s1 += a + b; else s0 += a + b; }
    if (i == 8 * Q) { pin(EXPV == 1 && Q ? s1 : s0, nz); wg_wait<W>(); reg_fence_part<8 * Q, 8>(P); }
    P[i] = pack_bf16(a, b);
  }
}
template <int N> __device__ __forceinline__ void shift_scores(float (&S)[N], float d0, float d1) {
#pragma unroll
  for (int i = 0; i < N; i++) S[i] -= (i & 2) ? d1 : d0;
}
__device__ __forceinline__ bool soft_high(float s0, float s1, float lim = SM_LIMIT) { return s0 > lim || s1 > lim; }
__device__ __forceinline__ bool soft_unsafe(float s0, float s1, bool first) {
  uint32_t b0 = __ballot_sync(0xffffffffu, s0 >= SM_LOW), b1 = __ballot_sync(0xffffffffu, s1 >= SM_LOW);
  b0 |= b0 >> 1; b0 |= b0 >> 2; b1 |= b1 >> 1; b1 |= b1 >> 2;
  return __any_sync(0xffffffffu, soft_high(s0, s1)) || (first && (b0 & b1 & 0x11111111u) != 0x11111111u);
}
template <int N> __device__ __forceinline__ void soft_fix(const float (&S)[N], float (&O)[64], SoftState& z, bool first, float& d0, float& d1) {
  d0 = d1 = first ? -INFINITY : 0.f;
#pragma unroll
  for (int j = 0; j < N / 4; j++) { d0 = fmaxf(d0, fmaxf(S[4 * j], S[4 * j + 1])); d1 = fmaxf(d1, fmaxf(S[4 * j + 2], S[4 * j + 3])); }
  d0 = fmaxf(d0, __shfl_xor_sync(0xffffffffu, d0, 1)); d1 = fmaxf(d1, __shfl_xor_sync(0xffffffffu, d1, 1));
  d0 = fmaxf(d0, __shfl_xor_sync(0xffffffffu, d0, 2)); d1 = fmaxf(d1, __shfl_xor_sync(0xffffffffu, d1, 2));
  const float sc0 = ex2(-fmaxf(d0, 0.f)), sc1 = ex2(-fmaxf(d1, 0.f));
  z.m0 += d0; z.m1 += d1; z.l0 *= sc0; z.l1 *= sc1; z.shifted = 1;
#pragma unroll
  for (int j = 0; j < 16; j++) { O[4 * j] *= sc0; O[4 * j + 1] *= sc0; O[4 * j + 2] *= sc1; O[4 * j + 3] *= sc1; }
}
template <int M> __device__ __forceinline__ void pin32(const uint32_t (&v)[M], uint32_t never_zero) {
#pragma unroll
  for (int i = 0; i < 32; i += 4)
    asm volatile("{\n.reg .pred p;\nsetp.eq.u32 p, %4, 0;\n@p st.shared.v4.b32 [%4], {%0,%1,%2,%3};\n}\n" ::"r"(v[i]), "r"(v[i + 1]), "r"(v[i + 2]), "r"(v[i + 3]), "r"(never_zero) : "memory");
}
template <int N> __device__ __forceinline__ void mask_diag(float (&S)[N], float nd) {
  asm volatile("" : "+f"(nd));
#pragma unroll
  for (int i = 0; i < 32; i++) {
    const float beyond = __saturatef(nd + (float)(8 * (i >> 2) + (i & 1) - 4 * (i & 2)));
    S[N - 32 + i] = fmaf(beyond, -3.0e38f, S[N - 32 + i]);
  }
}
__device__ __forceinline__ float quad_sum(float v) {
  v += __shfl_xor_sync(0xffffffffu, v, 1);
  v += __shfl_xor_sync(0xffffffffu, v, 2);
  return v;
}
__device__ __forceinline__ void issue_qk(float (&S)[64], uint32_t dq, uint32_t dk) {
  mma_ss_n128_init<0>(S, dq, dk);
#pragma unroll
  for (int s = 1; s < 8; s++) mma_ss_n128<0>(S, dq + (s >> 2) * 1024 + (s & 3) * 2, dk + (s >> 2) * 1024 + (s & 3) * 2);
}
__device__ __forceinline__ void issue_qk(float (&S)[32], uint32_t dq, uint32_t dk) {
  mma_ss_n64_init(S, dq, dk);
#pragma unroll
  for (int s = 1; s < 8; s++) mma_ss_n64(S, dq + (s >> 2) * 1024 + (s & 3) * 2, dk + (s >> 2) * 1024 + (s & 3) * 2);
}
template <int H> __device__ __forceinline__ void issue_pv(float (&O)[64], const uint32_t (&P)[32], uint32_t dv, int acc, bool on) {
  if (on) {
#pragma unroll
    for (int s = 4 * H; s < 4 * H + 4; s++) {
      mma_rs_n128<1>(O, P[4 * s], P[4 * s + 1], P[4 * s + 2], P[4 * s + 3], dv + s * 128, s != 0 ? 1 : acc);
      if (s & 1) wg_commit();
    }
  } else { wg_commit(); wg_commit(); }
}
constexpr uint32_t DG = GR >> 4;
__device__ __forceinline__ void stage_q2(Cons& c, const float (&O)[64], uint32_t (&P)[32], uint32_t stg) {
  wg_commit(); wg_commit(); wg_commit(); wg_commit();
  c.turn_end();
  pack_frag<0>(O, P);
  stsm_frag(P, stg);
  fence_async_smem();
}
__device__ __forceinline__ void attn_half(Cons& c, float (&O)[64], uint32_t (&P)[32], SoftState& z, uint32_t dk0, uint32_t dkk, uint32_t dv0, float dmask, int last) {
  float S[32];
  FTH(8 + last * 32, 0);
  c.turn_begin();
  FTH(9 + last * 32, 0);
  wg_fence();
  issue_qk(S, dk0 + (last ? 0 : 2 * DG), dkk + (last ? 8 : 4) * DG);
  wg_commit();
  issue_pv<0>(O, P, dv0 + 10 * DG, 1, last);
  issue_pv<1>(O, P, dv0 + 10 * DG, 1, last);
  c.turn_end();
  c.wait_full(last ? 12 : 6);
  FTH(10 + last * 32, 0);
  wg_wait<4>();
  reg_fence(S);
  FTH(11 + last * 32, 0);
  c.release(last ? 8 : 4, 2);
  mask_diag(S, dmask);
  float s0, s1, d0 = z.m0, d1 = z.m1;
#pragma unroll 1
  for (int pass = 0;; pass++) {
    if (z.shifted) shift_scores(S, d0, d1);
    float tr[ROT];
    exp_quarter<0, 3>(S, P, tr, s0, s1, c.sb);
    exp_quarter<1, 2>(S, P, tr, s0, s1, c.sb);
    pin(s1, c.sb); wg_wait<0>(); reg_fence_part<16, 16>(P); reg_fence(O);
    if (!soft_unsafe(s0, s1, !last) || pass) break;
    soft_fix(S, O, z, !last, d0, d1);
  }
  FTH(12 + last * 32, 0);
  z.l0 += s0; z.l1 += s1;
  c.release(10, last ? 2 : 0);
  if (!last) c.wait_full(8);
  FTH(13 + last * 32, 0);
}

template <int V> struct IC { static constexpr int value = V; };
__device__ __forceinline__ int conv_next(int g, bool spare) { return g >= NGR - 2 ? g - (NGR - 4) : !spare && g == 4 ? 1 : g + 2; }
__device__ __forceinline__ void conv_final(uint32_t rb, uint32_t yb, const uint4& u, uint32_t dd, bool on) {
  const uint4 q0 = lds128(rb), q1 = lds128(rb + 4096), q2 = lds128(rb + 8192), q3 = lds128(rb + 12288);
  auto fin = [&](uint32_t x0, uint32_t x1, uint32_t x2, uint32_t x3, uint32_t uu) {
    if (DFOLD) return hadd2(hadd2(x0, x1), hadd2(x2, x3));
    return hfma2(dd, __byte_perm(uu, uu, 0x1032), hadd2(hadd2(x0, x1), hadd2(x2, x3)));
  };
  asm volatile("{\n.reg .pred p;\nsetp.ne.b32 p, %5, 0;\n@p st.shared.v4.b32 [%0], {%1,%2,%3,%4};\n}\n" ::"r"(yb), "r"(fin(q0.x, q1.x, q2.x, q3.x, u.w)),
               "r"(fin(q0.y, q1.y, q2.y, q3.y, u.z)), "r"(fin(q0.z, q1.z, q2.z, q3.z, u.y)), "r"(fin(q0.w, q1.w, q2.w, q3.w, u.x)), "r"((int)on) : "memory");
}
__device__ __forceinline__ void conv_tasks(Cons& c, const Params& p, int ntask, bool last, bool spare, int ch, int chstep, uint32_t dd, uint32_t dkk, int w, int lane) {
  const uint32_t sb = c.sb;
  int g = 2 + c.wg;
  uint4 u0 = make_uint4(0, 0, 0, 0), u1 = u0;
  uint32_t rb = sb + g * GR;
  const uint32_t yb = sb + c.wg * 8192 + c.tid * 16;
  c.wait_full(g);
#pragma unroll 1
  for (int i = 0; i < ntask; i++) {
    const uint32_t base = sb + g * GR;
    FTC(0);
    uint32_t a[64];
    const uint32_t hb = base + WBYTES - 28 + (8 * w + (lane >> 2) + (lane & 3)) * 4;
    auto lda = [&](int s) {
      a[4 * s] = lds32(hb + s * 256); a[4 * s + 1] = lds32(hb + s * 256 + 128);
      a[4 * s + 2] = lds32(hb + s * 256 + 16); a[4 * s + 3] = lds32(hb + s * 256 + 144);
    };
    lda(0); lda(15); lda(1); lda(14);
    if (DFOLD) {
      const int gt = 8 * w + (lane >> 2) + (lane & 3);
      a[0] = hadd2(a[0], gt == 7 ? dd : 0u); a[2] = hadd2(a[2], gt == 3 ? dd : 0u);
    }
    float acc[128];
    const uint32_t db = dkk + ((WPL / 16 - 1) << 16) + g * DG + WZ / 16;
    FTC(2);
    c.turn_begin();
    FTC(3);
    auto pair = [&](auto kc) {
      constexpr int k = decltype(kc)::value;
      if (k < 7) wg_fence();
      if (k == 7 && !(last && i == ntask - 1)) c.turn_end();
      conv_step<k, 7>(acc, a, db);
      conv_step<15 - k, 7>(acc, a, db);
      if (k < 6) { lda(k + 2); lda(13 - k); }
      if (k == 0) conv_final(rb, yb, u0, dd, i > 0);
      if (k == 1) {
        conv_final(rb + 2048, yb + 2048, u1, dd, i > 0);
        __syncwarp();
        if (lane == 0 && i > 0) mbar_arrive(sb + SM_BAR + (B_EV + c.wg) * 8);
      }
      if (DFOLD) { if (k == 6) dd = __bfloat16_as_ushort(p.ssd[(ch + chstep) & (DM - 1)]); }
      else if (k == 6) {
        const uint32_t ub = base + WZ + 16 + (c.tid >> 1) * 32 + ((c.tid & 1) ^ 1) * WPL;
        u0 = lds128(ub); u1 = lds128(ub + 2048);
        dd = __bfloat16_as_ushort(p.ssd[ch]) * 0x10001u;
      }
    };
    pair(IC<0>()); pair(IC<1>()); pair(IC<2>()); pair(IC<3>()); pair(IC<4>()); pair(IC<5>()); pair(IC<6>()); pair(IC<7>());
    wg_commit();
    FTC(4);
    g = conv_next(g, spare);
    ch += chstep;
    rb = base + c.tid * 16;
    wg_wait<0>();
    reg_fence(acc);
    reg_fence(a);
    bar_sync(3 + c.wg, 128);
    FTC(5);
    const int tw = (lane & 3) + w;
    const uint32_t xb = base + w * 4096 + tw * 32 + (lane >> 2) * 4;
#pragma unroll
    for (int j = 0; j < 32; j++) {
      float v0 = acc[4 * j], v1 = acc[4 * j + 1];
      if (j > 0) { v0 += acc[j > 0 ? 4 * j - 2 : 0]; v1 += acc[j > 0 ? 4 * j - 1 : 0]; }
      uint32_t v = pack_bf16(v0, v1), ad = xb + j * 128;
      if (j == 31 && tw >= 4) { v = 0; ad -= 4096; }
      asm volatile("st.shared.b32 [%0], %1;" ::"r"(ad), "r"(v) : "memory");
    }
    c.wait_stage_free();
    if (i + 1 < ntask) c.wait_full(g);
    bar_sync(3 + c.wg, 128);
    FTC(6);
  }
  conv_final(rb, yb, u0, dd, true);
  conv_final(rb + 2048, yb + 2048, u1, dd, true);
  c.staged(0);
}

__global__ void __cluster_dims__(2, 1, 1) __launch_bounds__(NTHREADS, 1) mega_kernel(const __grid_constant__ Params p) {
  extern __shared__ __align__(1024) uint8_t smem_raw[];
  const uint32_t sb = smem_u32(smem_raw);
  const int wgi = __shfl_sync(0xffffffffu, threadIdx.x >> 7, 0);
  const int warp = __shfl_sync(0xffffffffu, threadIdx.x >> 5, 0);
  const uint32_t rank = blockIdx.x & 1;
  int slot;
  {
    uint32_t smid; asm volatile("mov.u32 %0, %smid;" : "=r"(smid));
    const int tp = (smid >> 1) % NSLOT;
    slot = tp < 32 ? (tp & 7) * 8 + (tp >> 3) : tp < 60 ? (1 + (tp - 32) % 7) * 8 + 4 + (tp - 32) / 7 : tp < 62 ? tp + 4 : tp - 58;
  }
  if (elect()) {
    if (warp == 2) { prefetch_tm(&p.c); prefetch_tm(rank ? &p.wuv : &p.wuk); }
#pragma unroll
    for (int k = 0; k < 3; k++) {
      const int i = warp * 3 + k;
      mbar_init(sb + SM_BAR + i * 8, i == B_DONE ? 11 : i < NGR || i >= 2 * NGR + 4 ? 1 : 4);
    }
    if (warp == B_SLOT / 3) mbar_expect_tx(sb + SM_BAR + B_SLOT * 8, 4);
    asm volatile("fence.mbarrier_init.release.cluster;" ::: "memory");
  }
  if (wgi && slot < 64) {
    const int j = threadIdx.x & 127;
    const __nv_bfloat16* cb = p.cp + (size_t)(2 * (slot & 7) + rank) * 128 * DC;
    const __nv_bfloat16* wb = (rank ? p.wuvp : p.wukp) + 2 * (slot >> 3) * HD;
#pragma unroll
    for (int kb = 0; kb < START_PF; kb++)
      asm volatile("prefetch.global.L2 [%0];" ::"l"(wgi == 1 ? cb + j * DC + kb * 64 : wb + (size_t)(kb * 64 + (j >> 1)) * (NH * HD) + (j & 1) * 64));
  }
  __syncwarp();
  cluster_arrive();
  if (CLAIM && threadIdx.x == 96 && rank == 0) {
#pragma unroll 1
    for (int n = 0; n < NSLOT && atomicExch(&g_claim[slot], 1u); n++) slot = slot == NSLOT - 1 ? 0 : slot + 1;
  }
  __syncwarp();
  cluster_wait();
  if (CLAIM) {
    if (threadIdx.x == 96 && rank == 0) {
#pragma unroll
      for (int r = 0; r < 2; r++)
        asm volatile("{\n.reg .b32 a;\nmapa.shared::cluster.u32 a, %0, %1;\nst.async.shared::cluster.mbarrier::complete_tx::bytes.u32 [a + 16], %2, [a];\n}\n"
                     ::"r"(sb + SM_BAR + B_SLOT * 8), "r"(r), "r"(slot) : "memory");
    }
    mbar_wait(sb + SM_BAR + B_SLOT * 8, 0);
    slot = __shfl_sync(0xffffffffu, lds32(sb + SM_BAR + B_SLOT * 8 + 16), 0);
  }
  const int grp = slot >> 3, idx = slot & 7;
  const int lb = slot * 2 + rank;
  const bool spare = grp == 8;
  const int cn = spare ? CN_SPARE : CN_MAIN, cch = spare ? lb - NMAIN : 4 * CN_SPARE + CN_MAIN * lb, cstep = spare ? 4 : 1;
  TS(0);

  if (wgi == 0) {
    asm volatile("setmaxnreg.dec.sync.aligned.u32 40;");
    const int lane = threadIdx.x & 31;
    cluster_arrive();
    if (warp == 3) {
      if (!spare) {
        const int s0 = lb * 16;
#pragma unroll 1
        for (int cg = 0; cg < 16; cg++) {
          __nanosleep(PRE_SLEEP);
          const int ch = cg * 64 + 2 * lane;
          const uint32_t* kp = reinterpret_cast<const uint32_t*>(p.ak + (size_t)s0 * DM + ch);
          const uint32_t* vp = reinterpret_cast<const uint32_t*>(p.av + (size_t)s0 * DM + ch);
          const uint4 sw = __ldg(reinterpret_cast<const uint4*>(p.shk + ch * 4));
          uint32_t k3 = 0, k2 = 0, k1 = 0, k0 = 0, up = 0;
          if (lb > 0) { k3 = ldg_stream(kp - 4 * 512); k2 = ldg_stream(kp - 3 * 512); k1 = ldg_stream(kp - 2 * 512); k0 = ldg_stream(kp - 512); up = ldg_stream(vp - 512); }
          const uint32_t w0 = __byte_perm(sw.x, sw.z, 0x5410), w1 = __byte_perm(sw.x, sw.z, 0x7632);
          const uint32_t w2 = __byte_perm(sw.y, sw.w, 0x5410), w3 = __byte_perm(sw.y, sw.w, 0x7632);
          up = hmul2(hfma2(k0, w0, hfma2(k1, w1, hfma2(k2, w2, hmul2(k3, w3)))), up);
#pragma unroll 1
          for (int hb = 0; hb < 2; hb++) {
            uint32_t kk[8], u[8];
#pragma unroll
            for (int r = 0; r < 8; r++) { kk[r] = ldg_stream(kp + r * 512); u[r] = ldg_stream(vp + r * 512); }
#pragma unroll
            for (int r = 0; r < 8; r++) {
              k3 = k2; k2 = k1; k1 = k0; k0 = kk[r];
              u[r] = hmul2(hfma2(k0, w0, hfma2(k1, w1, hfma2(k2, w2, hmul2(k3, w3)))), u[r]);
            }
            if (lane == 0) asm volatile("cp.async.bulk.wait_group.read 0;" ::: "memory");
            __syncwarp();
            const uint32_t dst = sb + SM_UST + lane * 32 + ((lane & 4) << 2);
#pragma unroll
            for (int cc = 0; cc < 2; cc++) {
              const uint32_t sel = cc ? 0x7632 : 0x5410;
              asm volatile("st.shared.v4.b32 [%0], {%1,%2,%3,%4};" ::"r"(dst + cc * 1024), "r"(__byte_perm(u[6], u[5], sel)), "r"(__byte_perm(u[4], u[3], sel)),
                           "r"(__byte_perm(u[2], u[1], sel)), "r"(__byte_perm(u[0], up, sel)) : "memory");
              asm volatile("st.shared.v4.b32 [%0], {%1,%2,%3,%4};" ::"r"((dst ^ 16) + cc * 1024), "r"(__byte_perm(u[7], u[6], sel)), "r"(__byte_perm(u[5], u[4], sel)),
                           "r"(__byte_perm(u[3], u[2], sel)), "r"(__byte_perm(u[1], u[0], sel)) : "memory");
            }
            fence_async_smem();
            __syncwarp();
            if (lane == 0) {
              asm volatile("cp.async.bulk.tensor.3d.global.shared::cta.bulk_group [%0, {%2, %3, %4}], [%1];\ncp.async.bulk.commit_group;"
                           ::"l"(&p.w), "r"(sb + SM_UST), "r"(WZ / 2 + lb * 16 + (hb ^ 1) * (WPL / 2)), "r"(cg * 32), "r"(0) : "memory");
            }
            up = u[7];
            kp += 8 * 512; vp += 8 * 512;
          }
          if ((cg & (cg + 1)) == 0 && lane == 0) {
            asm volatile("cp.async.bulk.wait_group 0;" ::: "memory");
            fence_release();
            flag_add(FLAG(F_U + 32 - __clz(cg)));
          }
          TSW(10 + cg);
        }
      }
      if (lane == 0) {
        unsigned long long t0, t1;
        asm volatile("mov.u64 %0, %globaltimer;" : "=l"(t0));
        while (!mbar_try(sb + SM_BAR + B_DONE * 8, 0)) {
          asm volatile("mov.u64 %0, %globaltimer;" : "=l"(t1));
          if (t1 - t0 > 2000000000ull) __trap();
        }
      }
    } else if (warp != 0) {
      const int w = warp - 1, ne = 12 + (cn + 1 - w) / 2;
      uint32_t p0 = 0;
      int cg = 2 + w, ch = cch + w * cstep;
#pragma unroll 1
      for (int e = spare ? 12 : 0; e < ne; e++) {
        const int rnd = e >= 6, k = e - 6 * rnd, rt = k == 4 ? idx : 15 - idx;
        uint8_t* dst = k < 4 ? g_kv + (size_t)(((k & 1) * 16 + 2 * grp + (k >> 1)) * 16 + 2 * idx + rank) * 32768 + w * 8192
                     : k < 6 ? g_cimg + (size_t)(rt * 32 + 16 * rnd + 2 * grp + rank) * 32768 + (w ^ (k & 1)) * 8192
                             : reinterpret_cast<uint8_t*>(g_yT + (size_t)ch * SEQ);
        const uint32_t src = sb + w * 8192 + (k == 4 ? 2 * GR : 0);
        if (e == 6) flag_wait(FLAG(F_AD + grp), 32);
        mbar_wait1(sb + SM_BAR + (B_EV + (k == 4 ? 2 : 0) + w) * 8, k == 4 ? rnd : p0);
        if (k != 4) p0 ^= 1;
        if (lane < 4 && k >= 6 && (!spare || e < ne - 6)) mbar_arrive_cluster(sb + SM_BAR + (B_EMPTY + cg) * 8, lane & 1);
        fence_async_smem();
        if (elect()) {
#pragma unroll 1
          for (int i = 0; i < (k >= 6 ? 1 : 8); i++) {
            const uint32_t o = (i >> 2) * 16384 + (i & 3) * 2048;
            asm volatile("cp.async.bulk.global.shared::cta.bulk_group [%0], [%1], %2;" ::"l"(dst + o), "r"(src + o), "r"(k >= 6 ? 4096 : 2048) : "memory");
            asm volatile("cp.async.bulk.commit_group;\ncp.async.bulk.wait_group.read %0;" ::"n"(ST_OUT) : "memory");
          }
          asm volatile("cp.async.bulk.wait_group 0;" ::: "memory");
          if (k != 4) mbar_arrive(sb + SM_BAR + (B_EV + 4 + w) * 8);
        }
        __syncwarp();
        if (lane < (k == 4 ? 4 : e == 11 || (e == ne - 1 && !spare) ? 2 : 0))
          mbar_arrive_cluster(sb + SM_BAR + (B_EMPTY + (k == 4 ? 2 : e == 11) + (lane >> 1)) * 8, lane & 1);
        if (k >= 3) {
          fence_release();
          if (lane == 0 || (lane == 1 && e == 5))
            flag_add(FLAG(lane ? F_AD + grp : k == 3 ? F_KV + rnd * 8 + grp : k < 6 ? F_CTX + rt * 2 + rnd : F_Y + (ch >> 7)));
        }
        if (k >= 6) { cg = conv_next(cg, spare); ch += 2 * cstep; }
      }
      if (lane == 0) mbar_arrive(sb + SM_BAR + B_DONE * 8);
    } else {
      uint32_t pe = 0x3FFC;
      auto acquire = [&](int g) { PWAIT(sb + SM_BAR + (B_EMPTY + g) * 8, (pe >> g) & 1); pe ^= 1u << g; };
#pragma unroll 1
      for (int rnd = 0; rnd < (spare ? 0 : 2); rnd++) {
        const int hp = 16 * rnd + 2 * grp, head = hp + rank;
#pragma unroll 1
        for (int kk = 0; kk < 32; kk++) {
          const int g0 = 2 + 3 * (kk & 3);
          acquire(g0);
          if (kk < 4) { acquire(g0 + 1); acquire(g0 + 2); } else pe ^= 6u << g0;
          if (elect()) {
            const uint32_t fb = sb + SM_BAR + (B_FULL + g0) * 8;
            mbar_expect_tx(fb, 3 * GR);
            if (kk < 16) {
              tma2d(sb + g0 * GR, &p.c, (kk & 7) * 64, (2 * idx + rank) * 128, fb, EV_NORMAL);
              tma3d_mc(sb + (g0 + 1 + rank) * GR, rank ? &p.wuv : &p.wuk, 0, (kk & 7) * 64, (hp + (kk >> 3)) * 2, fb, POL_W);
            } else {
              tma2d_mc(sb + (g0 + rank) * GR, &p.x, (kk - 16) * 64, (rank ? 15 - idx : idx) * 128, fb, EV_NORMAL);
              tma3d(sb + (g0 + 2) * GR, &p.wq, 0, (kk - 16) * 64, head * 2, fb, POL_W);
            }
            if (kk == 3) { prefetch_tm(&p.x); prefetch_tm(&p.wq); }
          }
        }
        flag_wait(FLAG(F_KV + rnd * 8 + grp), 32);
        fence_async_all();
        acquire(2); pe ^= 8u;
        int g0 = 4;
#pragma unroll 1
        for (int f = 0; f < 34; f++) {
          const bool isk = (f == 0) || ((f & 1) && f < 33);
          const int it = (f == 0) ? 0 : (f == 33) ? 16 : isk ? (f + 1) >> 1 : (f >> 1) - 1;
          const int blk = it == 0 ? idx : it <= idx ? it - 1 : it < 16 ? 15 - it : 15 - idx;
          acquire(g0);
          if (f < 5) acquire(g0 + 1); else pe ^= 2u << g0;
          if (elect()) {
            const uint32_t fb = sb + SM_BAR + (B_FULL + g0) * 8;
            mbar_expect_tx(fb, 2 * GR);
            bulk_g2s(sb + g0 * GR, g_kv + (size_t)(((isk ? 0 : 16) + (head & 15)) * 16 + blk) * 32768, 2 * GR, fb, POL_KV);
          }
          g0 = f == 12 ? 12 : g0 == 12 ? 4 : g0 + 2;
        }
      }
      if (spare) {
#pragma unroll 1
        for (int i = 0, g = 2; i < 32; i++) {
          acquire(g); pe ^= 2u << g;
          if (elect()) {
            const uint32_t fb = sb + SM_BAR + (B_FULL + g) * 8;
            if (i == 0) { mbar_expect_tx(fb - 8, 2048); bulk_g2s(sb + GR, p.gate_w, 2048, fb - 8, EV_NORMAL); }
            mbar_expect_tx(fb, 2 * GR);
            tma2d(sb + g * GR, &p.x, (i & 7) * 128, (lb - NMAIN) * 512 + (i >> 3) * 128, fb, EV_NORMAL);
            tma2d(sb + (g + 1) * GR, &p.x, (i & 7) * 128 + 64, (lb - NMAIN) * 512 + (i >> 3) * 128, fb, EV_NORMAL);
          }
          g = g == NGR - 2 ? 2 : g + 2;
        }
      }
      auto conv_fill = [&](int g, int ch) {
        acquire(g);
        if (elect()) {
          const uint32_t fb = sb + SM_BAR + (B_FULL + g) * 8;
          mbar_expect_tx(fb, WBYTES + 4096);
          bulk_g2s(sb + g * GR, g_w + (size_t)ch * WSTRIDE, WBYTES, fb, POL_C);
          bulk_g2s(sb + g * GR + WBYTES, p.ssk + (size_t)ch * SEQ, 4096, fb, POL_C);
        }
      };
#pragma unroll 1
      for (int i = 0, g = 2; i < cn; i++) {
        if ((i & 15) == 0) { flag_wait(FLAG(F_U + (spare ? 32 - __clz(i >> 4) : 4)), NMAIN); fence_async_all(); }
        conv_fill(g + (i & 1), cch + i * cstep);
        if (i & 1) g = conv_next(g, spare);
      }
      if (!spare) {
        const int rt = 2 * grp + rank, ct = idx;
        int g0 = P3G;
#pragma unroll 1
        for (int kb = 0; kb < 66; kb++) {
          if (kb == 0 || kb == 32 || kb >= 64) {
            flag_wait(FLAG(kb < 64 ? F_CTX + rt * 2 + (kb >> 5) : kb == 64 ? F_GATE : F_Y + ct), kb <= 64 ? 32 : 128);
            fence_async_all();
          }
          acquire(g0);
          if (kb < 11) acquire(g0 + 1);
          if (elect()) {
            const uint32_t fb = sb + SM_BAR + (B_FULL + g0) * 8;
            mbar_expect_tx(fb, kb == 64 ? 2 * GR + 512 : 2 * GR);
            if (kb <= 64) bulk_g2s(kb < 64 ? sb + g0 * GR : sb + SM_GATE, kb < 64 ? (const void*)(g_cimg + (size_t)(rt * 64 + kb) * GR) : (const void*)(g_gate + rt * 128), kb < 64 ? GR : 512, fb, POL_CTX);
            if (kb < 64) {
              tma2d_mc(sb + (g0 + 1) * GR + rank * 8192, &p.wo, ct * 128 + rank * 64, kb * 64, fb, POL_WO);
              if (kb == 40) { prefetch_tm(&p.y); prefetch_tm(&p.out); }
            } else {
              const CUtensorMap* tm = kb == 64 ? &p.x : &p.y;
              const int c0 = (kb == 64 ? ct : rt) * 128, c1 = (kb == 64 ? rt : ct) * 128;
              tma2d(sb + g0 * GR, tm, c0, c1, fb, EV_NORMAL);
              tma2d(sb + (g0 + 1) * GR, tm, c0 + 64, c1, fb, EV_NORMAL);
            }
          }
          g0 = g0 == 12 ? (kb == 3 ? 2 : 0) : g0 + 2;
        }
        unsigned n = 0;
        if (lane == 0) n = atomicAdd(FLAG(F_EXIT), 1);
        if (__shfl_sync(0xffffffffu, n, 0) == NMAIN - 1) {
#pragma unroll 1
          for (int i = lane; i < 96; i += 32) { *FLAG(i) = 0; g_claim[i] = 0; }
        }
      }
      if (lane == 0) mbar_arrive(sb + SM_BAR + B_DONE * 8);
    }
    __syncwarp();
    cluster_wait();
  } else {
    asm volatile("setmaxnreg.inc.sync.aligned.u32 232;");
    Cons c;
    c.sb = sb; c.pf = 0; c.wg = wgi - 1; c.tid = threadIdx.x & 127;
    const int lane = threadIdx.x & 31, t = lane & 3;
    const int row = c.wg * 64 + (warp & 3) * 16 + (lane >> 2);
    const uint32_t dkk = desc_k(sb), dk0 = dkk + c.wg * 512, dm0 = desc_mn<8192>(sb), dv0 = desc_mn<16384>(sb);
    const uint32_t dsw = DG + 512 - c.wg * 1024;
    if (c.wg == 1) bar_arrive(1, 256);
    c.pfree = 1;
    asm("mapa.shared::cluster.u32 %0, %1, %2;" : "=r"(c.relb) : "r"(sb + SM_BAR + (B_EMPTY + (c.tid >> 1)) * 8), "r"(c.tid & 1));
    c.zero = p.zero;
    c.rnd = 0;
    const uint32_t stg = sb + (c.wg * 64 + (warp & 3) * 16 + ((lane >> 3) & 1) * 8 + (lane & 7)) * 128 + (((lane >> 4) ^ (lane & 7)) << 4);

    if (spare) {
      c.wait_full(1);
      int g = 2;
#pragma unroll 1
      for (int r = 0; r < 4; r++) {
        float d[4] = {0.f, 0.f, 0.f, 0.f}, e[4] = {0.f, 0.f, 0.f, 0.f};
#pragma unroll 1
        for (int kb = 0; kb < 16; kb += 2) {
          c.wait_full(g);
          wg_fence();
#pragma unroll
          for (int k = 0; k < 4; k++) {
            mma_ss_n8(d, dk0 + g * DG + k * 2, dkk + DG + kb * 8 + k * 2);
            mma_ss_n8(e, dk0 + (g + 1) * DG + k * 2, dkk + DG + kb * 8 + 8 + k * 2);
          }
          wg_commit();
          wg_wait<0>();
          c.release(g, 2);
          g = g == NGR - 2 ? 2 : g + 2;
        }
        reg_fence(d); reg_fence(e);
        d[0] += e[0]; d[2] += e[2];
        if (t == 0) {
          float* gp = g_gate + (lb - NMAIN) * 512 + r * 128 + row;
          gp[0] = rcp(1.f + ex2(-1.4426950408889634f * d[0])); gp[8] = rcp(1.f + ex2(-1.4426950408889634f * d[2]));
        }
      }
      fence_release();
      __syncwarp();
      if (lane == 0) flag_add(FLAG(F_GATE));
      TS(1);
    }
    uint32_t dd0 = __bfloat16_as_ushort(p.ssd[cch + c.wg * cstep]);
    asm volatile("" : "+r"(dd0));
    const float dmask = (float)(2 * t - (row & 63));
    uint32_t pv[32];
#pragma unroll
    for (int i = 0; i < 32; i++) pv[i] = 0;
#pragma unroll 1
    for (int rnd = 0; rnd < (spare ? 0 : 2); rnd++) {
      float O[64];
      FTM(rnd * 8);
      FTG(0);
      FTH(56, c.rnd == rnd);
      c.wait_full(2);
      FTM(rnd * 8 + 1);
      FTH(57, c.rnd == rnd);
#pragma unroll 1
      for (int tile = c.zero; tile < 2; tile++) {
        float acc[128];
        const bool single = tile == 0;
        {
          FTG(tile * 32 + 1);
          const uint32_t a = dk0 + 2 * DG, b = dm0 + 3 * DG;
          c.turn_begin();
          FTG(tile * 32 + 2);
          FTH(58, c.rnd == rnd);
          wg_fence();
          mma_ss_n256_init<1>(acc, a, b);
#pragma unroll
          for (int k = 1; k < 4; k++) mma_ss_n256<1>(acc, a + k * 2, b + k * 128);
          wg_commit();
          if (single) c.turn_end();
          FTG(tile * 32 + 3);
        }
#pragma unroll 1
        for (int kb = 1; kb < 8; kb++) {
          const int g0 = 2 + 3 * (kb & 3);
          const uint32_t a = dk0 + g0 * DG, b = dm0 + (g0 + 1) * DG;
          const bool second = (kb == 1 && !single) || kb == 7;
          FTG(tile * 32 + kb * 4);
          if (!second) { wg_wait<0>(); c.release(2 + 3 * ((kb - 1) & 3), 3); }
          FTG(tile * 32 + kb * 4 + 1);
          c.wait_full(g0);
          if (!second) c.turn_begin();
          FTG(tile * 32 + kb * 4 + 2);
          wg_fence();
#pragma unroll
          for (int k = 0; k < 4; k++) mma_ss_n256<1>(acc, a + k * 2, b + k * 128);
          wg_commit();
          if (kb != 6) c.turn_end();
          if (second) { wg_wait<1>(); c.release(2 + 3 * ((kb - 1) & 3), 3); }
          FTG(tile * 32 + kb * 4 + 3);
          FTH(58 + kb, c.rnd == rnd || kb > 3);
          if (tile == 1 && kb == 3) { c.wait_stage_free(); stsm_frag<0, 4>(pv, stg); }
          if (tile == 1 && kb == 4) { stsm_frag<4, 8>(pv, stg); c.staged(0); }
        }
        c.rnd = rnd;
        c.wait_stage_free();
        const bool nxt = c.try_full(2);
        wg_wait<0>();
        reg_fence(acc);
        c.release(11, 3);
        pack_frag_scaled(acc, pv, SM_C, SM_C);
        stsm_frag(pv, stg);
        c.staged(0);
        pack_frag<64>(acc, pv);
        pin32(pv, sb);
        FTG(32 + tile * 32);
        if (!nxt) mbar_wait(sb + SM_BAR + (B_FULL + 2) * 8, (c.pf >> 2) & 1);
        c.pf ^= 4;
      }
      TS(1 + rnd * 3);
      FTM(rnd * 8 + 2);
      {
        float qa[64];
        float (&qb)[64] = O;
        {
          FTG(65);
          const uint32_t a = dk0 + 2 * DG, b = dm0 + 4 * DG;
          c.turn_begin();
          FTG(66);
          wg_fence();
          mma_ss_n128_init<1>(qa, a, b);
          mma_ss_n128_init<1>(qb, a + dsw, b);
#pragma unroll
          for (int k = 1; k < 4; k++) {
            mma_ss_n128<1>(qa, a + k * 2, b + k * 128);
            mma_ss_n128<1>(qb, a + dsw + k * 2, b + k * 128);
          }
          wg_commit();
          FTG(67);
        }
#pragma unroll 1
        for (int kb = 1; kb < 16; kb++) {
          const int g0 = 2 + 3 * (kb & 3);
          const uint32_t a = dk0 + g0 * DG, b = dm0 + (g0 + 2) * DG;
          const bool second = kb == 1 || kb == 15;
          FTG(64 + kb * 4);
          if (!second) { wg_wait<0>(); c.release(2 + 3 * ((kb - 1) & 3), 3); }
          FTG(65 + kb * 4);
          c.wait_full(g0);
          if (!second) c.turn_begin();
          FTG(66 + kb * 4);
          FTH(kb - 14, kb < 14);
          wg_fence();
#pragma unroll
          for (int k = 0; k < 4; k++) {
            mma_ss_n128<1>(qa, a + k * 2, b + k * 128);
            mma_ss_n128<1>(qb, a + dsw + k * 2, b + k * 128);
          }
          wg_commit();
          if (kb != 14) c.turn_end();
          if (second) { wg_wait<1>(); c.release(2 + 3 * ((kb - 1) & 3), 3); }
          FTG(67 + kb * 4);
          FTH(2, kb < 15);
          if (kb == QFLUSH) { c.wait_stage_free(); stsm_frag<0, 4>(pv, stg); }
          if (kb == QFLUSH + 1) { stsm_frag<4, 8>(pv, stg); c.staged(0); }
        }
        c.wait_stage_free();
        mbar_wait(sb + SM_BAR + (B_EMPTY + 2) * 8, rnd ^ 1);
        FTM(rnd * 8 + 3);
        FTH(3, 0);
        wg_wait<0>();
        reg_fence(qa); reg_fence(qb);
        FTH(4, 0);
        c.release(11, 3);
        pack_frag<0>(qa, pv);
        stsm_frag(pv, stg + 2 * GR);
        if (c.wg == 0) {
          pack_frag<0>(qb, pv);
          stsm_frag(pv, stg);
#pragma unroll
          for (int i = 16; i < 32; i++) pv[i] = 0;
        }
        fence_async_smem();
        c.wait_full(4);
      }
      TS(2 + rnd * 3);
      FTM(rnd * 8 + 4);
      FTH(5, 0);
      {
        const int nA = idx + 1;
        uint32_t (&P)[32] = pv;
        SoftState z;
        z.m0 = z.m1 = z.l0 = z.l1 = 0.f; z.shifted = c.zero;
#pragma unroll 1
        for (int seg = c.zero;; seg++) {
        if (c.wg == seg) attn_half(c, O, P, z, dk0, dkk, dv0, dmask, seg);
        if (seg) break;
        FTM(rnd * 8 + 5);
        int gk = c.wg ? 4 : 6, gv = c.wg ? 4 : 8;
        uint32_t dq = dk0 + (1 - c.wg < nA ? 2 * DG : 0), dk = dkk + gk * DG;
#pragma unroll 1
        for (int it = 1 - c.wg; it < 17 - c.wg; it++) {
          float S[64];
          FTA(it * 7 + 0); FTH((it < 3 ? 8 + it * 8 : it * 8 - 88) + 0, it >= 3 && it < 15);
          c.turn_begin();
          FTA(it * 7 + 2); FTH((it < 3 ? 8 + it * 8 : it * 8 - 88) + 1, it >= 3 && it < 15);
          wg_fence();
          issue_qk(S, dq, dk);
          wg_commit();
          const uint32_t dv = dv0 + gv * DG;
          uint32_t relk = c.relb + gk * 8, relv = c.relb + gv * 8;
          gk = it == 6 ? 12 : gv == 12 ? 4 : gv + 2;
          gv = it == 16 ? gk : gk == 12 ? 4 : gk + 2;
          uint32_t fk = sb + SM_BAR + (B_FULL + gk) * 8, fv = sb + SM_BAR + (B_FULL + gv) * 8, park = (c.pf >> gk) & 1, parv = (c.pf >> gv) & 1;
          c.pf ^= (1u << gk) | (1u << gv);
          dq = dk0 + (it + 1 < nA ? 2 * DG : 0); dk = dkk + gk * DG;
          float lo0 = z.l0, lo1 = z.l1;
          const bool first = it == nA || it == 0;
          if (it == nA) {
            if (EARLY_RCP) { lo0 = rcp(quad_sum(lo0)); lo1 = rcp(quad_sum(lo1)); }
            z.m0 = z.m1 = z.l0 = z.l1 = 0.f; z.shifted = 0;
          }
          float s0, s1, d0 = z.m0, d1 = z.m1;
          int pre = z.shifted || (it & 15) == 0;
          float lim = first ? -1.f : SM_LIMIT;
          asm volatile("" : "+r"(relk), "+r"(relv), "+r"(fk), "+r"(fv), "+r"(park), "+r"(parv), "+r"(dq), "+r"(dk), "+r"(pre), "+f"(lim), "+f"(d0), "+f"(d1), "+f"(z.l0), "+f"(z.l1));
          if (it) {
            issue_pv<0>(O, P, dv, it != nA + 1 && it != 1, true);
            issue_pv<1>(O, P, dv, 1, HALFPV ? it + c.wg > 1 : true);
            c.turn_end();
          } else stage_q2(c, O, P, stg);
          FTA(it * 7 + 3); FTH((it < 3 ? 8 + it * 8 : it * 8 - 88) + 2, it >= 3 && it < 15);
          wg_wait<4>();
          reg_fence(S);
          FTA(it * 7 + 4); FTH((it < 3 ? 8 + it * 8 : it * 8 - 88) + 3, it >= 3 && it < 15);
          if (c.tid < 4) asm volatile("mbarrier.arrive.shared::cluster.b64 _, [%0];" ::"r"(relk) : "memory");
#pragma unroll 1
          for (int pass = 0;; pass++) {
            if (pre) {
              if ((it & 15) == 0) mask_diag(S, dmask);
              if (z.shifted) shift_scores(S, d0, d1);
            }
            float tr[ROT];
            exp_quarter<0, 3>(S, P, tr, s0, s1, sb);
            exp_quarter<1, 2>(S, P, tr, s0, s1, sb);
            exp_quarter<2, 1>(S, P, tr, s0, s1, sb);
            exp_quarter<3, 0>(S, P, tr, s0, s1, sb);
            reg_fence(O);
            if (c.tid < (pass || !it ? 0 : 4)) asm volatile("mbarrier.arrive.shared::cluster.b64 _, [%0];" ::"r"(relv) : "memory");
            const bool ok = mbar_test(fk, park) & mbar_test(fv, parv);
            if (!ok) lim = -1.f;
            FTA(it * 7 + 5); FTH((it < 3 ? 8 + it * 8 : it * 8 - 88) + 4, it >= 3 && it < 15);
            if (!__any_sync(0xffffffffu, !(s0 <= lim && s1 <= lim))) break;
            if (pass) break;
            if (it == nA) {
              uint32_t pk[32];
              if (!EARLY_RCP) { lo0 = rcp(quad_sum(lo0)); lo1 = rcp(quad_sum(lo1)); }
              pack_frag_scaled(O, pk, lo0, lo1);
              stsm_frag(pk, stg + 2 * GR);
              c.staged(1);
            }
            if (!ok) { mbar_wait(fk, park); mbar_wait(fv, parv); }
            if (!soft_unsafe(s0, s1, first)) break;
            soft_fix(S, O, z, first, d0, d1);
            pre = 1;
          }
          z.l0 += s0; z.l1 += s1;
          FTA(it * 7 + 6); FTH((it < 3 ? 8 + it * 8 : it * 8 - 88) + 5, it >= 3 && it < 15);
        }
        FTM(rnd * 8 + 6);
        }
        FTH(48, 0);
        c.turn_begin();
        FTH(49, 0);
        wg_fence();
        issue_pv<0>(O, P, dv0 + 12 * DG, 1, true);
        issue_pv<1>(O, P, dv0 + 12 * DG, 1, !c.wg);
        c.turn_end();
        z.l0 = rcp(quad_sum(z.l0)); z.l1 = rcp(quad_sum(z.l1));
        wg_wait<0>();
        reg_fence(O); reg_fence(P);
        FTH(50, 0);
        c.release(12, 2);
        pack_frag_scaled(O, P, z.l0, z.l1);
        stsm_frag(P, stg);
        c.staged(0);
        FTM(rnd * 8 + 7);
        FTH(51, 0);
      }
      TS(3 + rnd * 3);
    }
    conv_tasks(c, p, (cn + 1 - c.wg) / 2, ((cn - 1) & 1) == c.wg, spare, cch + c.wg * cstep, 2 * cstep, dd0, dkk, warp & 3, lane);
    if (c.wg == 1) c.pf ^= 0x14;
    TS(7);
    if (!spare) {
      const int rt = 2 * grp + rank, ct = idx;
      float acc[64];
      int g0 = P3G + 2, pg = P3G;
      {
        FTO(0);
        c.wait_full(P3G);
        FTO(1);
        const uint32_t a = dk0 + P3G * DG, b = dm0 + (P3G + 1) * DG;
        wg_fence();
        mma_ss_n128_init<1>(acc, a, b);
#pragma unroll
        for (int k = 1; k < 4; k++) mma_ss_n128<1>(acc, a + k * 2, b + k * 128);
        wg_commit();
      }
#pragma unroll 1
      for (int kb = 1; kb < 64; kb++) {
        FTO(kb * 2);
        c.wait_full(g0);
        FTO(kb * 2 + 1);
        const uint32_t a = dk0 + g0 * DG, b = dm0 + (g0 + 1) * DG;
        wg_fence();
#pragma unroll
        for (int k = 0; k < 4; k++) mma_ss_n128<1>(acc, a + k * 2, b + k * 128);
        wg_commit();
        wg_wait<1>();
        c.release(pg, kb <= 59 ? 2 : 0);
        if (kb == 40) FTDUMP();
        pg = g0;
        g0 = g0 == 12 ? (kb == 3 ? 2 : 0) : g0 + 2;
      }
      cluster_arrive();
      c.wait_full(P3X);
      c.wait_full(P3Y);
      const float g0f = __uint_as_float(lds32(sb + SM_GATE + row * 4)), g1f = __uint_as_float(lds32(sb + SM_GATE + row * 4 + 32));
      const uint32_t gp0 = pack_bf16(g0f, g0f), gp1 = pack_bf16(g1f, g1f);
      const float h0 = 1.f - g0f, h1 = 1.f - g1f;
      const int w = warp & 3;
      const uint32_t xa = stg + P3X * GR;
      const uint32_t ya = sb + P3Y * GR + c.wg * 16384 + ((lane >> 4) * 8 + (lane & 7)) * 128 + (((2 * w + ((lane >> 3) & 1)) ^ (lane & 7)) << 4);
      uint32_t xy[32];
#pragma unroll
      for (int jj = 0; jj < 8; jj++) {
        uint32_t x[4], y[4];
        asm volatile("ldmatrix.sync.aligned.m8n8.x4.shared.b16 {%0,%1,%2,%3}, [%4];" : "=r"(x[0]), "=r"(x[1]), "=r"(x[2]), "=r"(x[3]) : "r"((xa ^ ((jj & 3) << 5)) + (jj >> 2) * 16384) : "memory");
        asm volatile("ldmatrix.sync.aligned.m8n8.x4.trans.shared.b16 {%0,%1,%2,%3}, [%4];" : "=r"(y[0]), "=r"(y[1]), "=r"(y[2]), "=r"(y[3]) : "r"(ya + jj * 2048) : "memory");
#pragma unroll
        for (int i = 0; i < 4; i++) xy[4 * jj + i] = hmul2(x[i], y[i]);
      }
      wg_wait<0>();
      reg_fence(acc);
      TS(8);
#pragma unroll
      for (int i = 0; i < 32; i++) {
        const float h = (i & 1) ? h1 : h0;
        xy[i] = hfma2((i & 1) ? gp1 : gp0, xy[i], pack_bf16(acc[2 * i] * h, acc[2 * i + 1] * h));
      }
      stsm_frag(xy, xa);
      fence_async_smem();
      __syncwarp();
      if (lane == 0) {
        const int r0 = c.wg * 64 + w * 16;
        tma2d_store(&p.out, sb + P3X * GR + r0 * 128, ct * 128, rt * 128 + r0);
        tma2d_store(&p.out, sb + (P3X + 1) * GR + r0 * 128, ct * 128 + 64, rt * 128 + r0);
        asm volatile("cp.async.bulk.commit_group;\ncp.async.bulk.wait_group.read 0;" ::: "memory");
      }
    } else { FTDUMP(); cluster_arrive(); }
    if (lane == 0) mbar_arrive(sb + SM_BAR + B_DONE * 8);
    __syncwarp();
    TS(9);
    cluster_wait();
  }
}

typedef CUresult (*EncFn)(CUtensorMap*, CUtensorMapDataType, cuuint32_t, void*, const cuuint64_t*, const cuuint64_t*, const cuuint32_t*,
                          const cuuint32_t*, CUtensorMapInterleave, CUtensorMapSwizzle, CUtensorMapL2promotion, CUtensorMapFloatOOBfill);

void enc2d(EncFn enc, CUtensorMap* tm, const void* base, uint64_t cols, uint64_t rows, uint32_t bc, uint32_t br) {
  cuuint64_t dims[2] = {cols, rows}; cuuint64_t strides[1] = {cols * 2}; cuuint32_t box[2] = {bc, br}; cuuint32_t es[2] = {1, 1};
  enc(tm, CU_TENSOR_MAP_DATA_TYPE_BFLOAT16, 2, const_cast<void*>(base), dims, strides, box, es, CU_TENSOR_MAP_INTERLEAVE_NONE,
      CU_TENSOR_MAP_SWIZZLE_128B, CU_TENSOR_MAP_L2_PROMOTION_L2_256B, CU_TENSOR_MAP_FLOAT_OOB_FILL_NONE);
}
void enc3d(EncFn enc, CUtensorMap* tm, const void* base, uint64_t K, uint64_t N) {
  cuuint64_t dims[3] = {64, K, N / 64}; cuuint64_t strides[2] = {N * 2, 128}; cuuint32_t box[3] = {64, 64, 2}; cuuint32_t es[3] = {1, 1, 1};
  enc(tm, CU_TENSOR_MAP_DATA_TYPE_BFLOAT16, 3, const_cast<void*>(base), dims, strides, box, es, CU_TENSOR_MAP_INTERLEAVE_NONE,
      CU_TENSOR_MAP_SWIZZLE_128B, CU_TENSOR_MAP_L2_PROMOTION_L2_256B, CU_TENSOR_MAP_FLOAT_OOB_FILL_NONE);
}

}

extern "C" void kernel_launch(void* const* d_in, const int* in_sizes, int n_in, void* d_out, int out_size) {
  (void)in_sizes; (void)n_in; (void)out_size;
  typedef const __nv_bfloat16* BP;
  BP xq = (BP)d_in[0], ak = (BP)d_in[1], av = (BP)d_in[2], shk = (BP)d_in[3], ssk = (BP)d_in[4], ssd = (BP)d_in[5];
  BP ckv = (BP)d_in[7], wq = (BP)d_in[8], wuk = (BP)d_in[9], wuv = (BP)d_in[10], wo = (BP)d_in[11], gw = (BP)d_in[12];

  static EncFn enc = nullptr;
  if (!enc) {
    cudaDriverEntryPointQueryResult qr;
    cudaGetDriverEntryPoint("cuTensorMapEncodeTiled", (void**)&enc, cudaEnableDefault, &qr);
    cudaFuncSetAttribute(mega_kernel, cudaFuncAttributeMaxDynamicSharedMemorySize, SMEM_BYTES);
  }
  Params p;
  void* yT = nullptr;
  cudaGetSymbolAddress(&yT, g_yT);
  enc2d(enc, &p.x, xq, DM, SEQ, 64, 128);
  enc2d(enc, &p.c, ckv, DC, SEQ, 64, 128);
  enc3d(enc, &p.wq, wq, DM, NH * HD);
  enc3d(enc, &p.wuk, wuk, DC, NH * HD);
  enc3d(enc, &p.wuv, wuv, DC, NH * HD);
  enc2d(enc, &p.wo, wo, DM, NH * HD, 64, 64);
  enc2d(enc, &p.y, yT, SEQ, DM, 64, 128);
  enc2d(enc, &p.out, d_out, DM, SEQ, 64, 16);
  {
    void* wp = nullptr;
    cudaGetSymbolAddress(&wp, g_w);
    cuuint64_t dims[3] = {WSTRIDE / 2, DM / 2, 2}; cuuint64_t strides[2] = {2 * WSTRIDE, WSTRIDE}; cuuint32_t box[3] = {16, 32, 2}; cuuint32_t es[3] = {1, 1, 1};
    enc(&p.w, CU_TENSOR_MAP_DATA_TYPE_BFLOAT16, 3, wp, dims, strides, box, es, CU_TENSOR_MAP_INTERLEAVE_NONE,
        CU_TENSOR_MAP_SWIZZLE_32B, CU_TENSOR_MAP_L2_PROMOTION_NONE, CU_TENSOR_MAP_FLOAT_OOB_FILL_NONE);
  }
  p.zero = 0;
  p.cp = ckv; p.wukp = wuk; p.wuvp = wuv;
  p.xp = xq; p.gate_w = gw; p.ak = ak; p.av = av; p.shk = shk; p.ssk = ssk; p.ssd = ssd;

  mega_kernel<<<132, NTHREADS, SMEM_BYTES>>>(p);
}
```

```cpp
#include <cuda_runtime.h>
#include <cuda.h>
#include <cuda_bf16.h>
#include <stdint.h>

namespace {

constexpr int SEQ = 2048, DM = 1024, DC = 512, NH = 32, HD = 128;
constexpr int GR = 16384;
constexpr int NGR = 14;
constexpr int SM_BAR = NGR * GR;
constexpr int SM_GATE = SM_BAR + 512;
constexpr int SM_UST = SM_GATE + 512;
constexpr int SMEM_BYTES = SM_UST + 2048;
constexpr int NTHREADS = 384;
#define SM_LIMIT 1.0995116e12f
#define SM_LOW 9.094947e-13f
constexpr int CN_MAIN = 5, CN_SPARE = 96;
constexpr int P3G = 6, P3X = 10, P3Y = 12;
constexpr int NMAIN = 128;

constexpr int B_FULL = 0, B_FREE = 14, B_SLOT = 16, B_DONE = 17, B_EMPTY = 18, B_EV = 32, V_SLOT = 36;

__device__ __align__(1024) uint8_t g_kv[2 * 16 * 16 * 32768];
__device__ __align__(1024) uint8_t g_cimg[16 * NH * 32768];
__device__ __align__(1024) __nv_bfloat16 g_yT[DM * SEQ];
__device__ __align__(1024) float g_gate[SEQ];
#define CWIDE 0
constexpr int WZ = CWIDE ? 768 : 256, WPL = WZ + 4096, WBYTES = 2 * WPL + 32, WSTRIDE = 2 * WPL + 128;
__device__ __align__(1024) uint8_t g_w[DM * WSTRIDE];
__device__ unsigned g_flags[128 * 8];
constexpr int F_KV = 0, F_CTX = 16, F_U = 48, F_AD = 56, F_Y = 64, F_GATE = 72, F_EXIT = 73;
constexpr int NSLOT = 66;
__device__ unsigned g_claim[96];
#define FLAG(i) (&g_flags[(i) * 8])

#define TS(slot)
#define TSW(slot)
#define FTX(i, off)
#define FTDUMP()

#define ST_OUT 0
#define QFLUSH 4
#define POL_W EV_NORMAL
#define POL_WO EV_FIRST
#define POL_KV EV_NORMAL
#define POL_C EV_FIRST
#define POL_CTX EV_FIRST
#define HALFPV 1
#define PRE_SLEEP 1500
#define EXPV 1
#define SUMV 0
#define ROT 8
#define EARLY_RCP 1
#define DFOLD 1
#define FINE_MODE 0
#define FINE_RND 1
#define FTA(i) do { if (FINE_MODE == 0) FTX(i, rnd ^ FINE_RND); } while (0)
#define FTG(i) do { if (FINE_MODE == 1) FTX(i, rnd ^ FINE_RND); } while (0)
#define FTM(i) do { if (FINE_MODE == 4) FTX(i, 0); } while (0)
#define FTC(k) do { if (FINE_MODE == 5) FTX((i & 7) * 8 + (k), (i >> 3) ^ FINE_RND); } while (0)
#define FTH(i, off) do { if (FINE_MODE == 6) FTX(i, (c.rnd ^ FINE_RND) | (off)); } while (0)
#define FTO(i) do { if (FINE_MODE == 2) FTX(i, 0); } while (0)

__device__ __forceinline__ uint32_t smem_u32(const void* p) { return (uint32_t)__cvta_generic_to_shared(p); }
__device__ __forceinline__ void mbar_init(uint32_t bar, int cnt) { asm volatile("mbarrier.init.shared::cta.b64 [%0], %1;" ::"r"(bar), "r"(cnt) : "memory"); }
__device__ __forceinline__ void mbar_expect_tx(uint32_t bar, uint32_t bytes) { asm volatile("mbarrier.arrive.expect_tx.shared::cta.b64 _, [%0], %1;" ::"r"(bar), "r"(bytes) : "memory"); }
__device__ __forceinline__ void mbar_arrive(uint32_t bar) { asm volatile("mbarrier.arrive.shared::cta.b64 _, [%0];" ::"r"(bar) : "memory"); }
__device__ __forceinline__ void mbar_arrive_cluster(uint32_t bar, uint32_t cta) {
  asm volatile("{\n.reg .b32 r;\nmapa.shared::cluster.u32 r, %0, %1;\nmbarrier.arrive.shared::cluster.b64 _, [r];\n}\n" ::"r"(bar), "r"(cta) : "memory");
}
__device__ __forceinline__ bool mbar_try(uint32_t bar, uint32_t parity) {
  uint32_t ok;
  asm volatile("{\n.reg .pred p;\nmbarrier.try_wait.parity.shared::cta.b64 p, [%1], %2, 20000;\nselp.u32 %0, 1, 0, p;\n}\n" : "=r"(ok) : "r"(bar), "r"(parity) : "memory");
  return ok;
}
__device__ __forceinline__ bool mbar_test(uint32_t bar, uint32_t parity) {
  uint32_t ok;
  asm volatile("{\n.reg .pred p;\nmbarrier.test_wait.parity.shared::cta.b64 p, [%1], %2;\nselp.u32 %0, 1, 0, p;\n}\n" : "=r"(ok) : "r"(bar), "r"(parity) : "memory");
  return ok;
}
__device__ __forceinline__ void mbar_wait(uint32_t bar, uint32_t parity) {
  asm volatile("{\n.reg .pred p;\nWAIT_LOOP:\nbar.warp.sync -1;\nmbarrier.try_wait.parity.shared::cta.b64 p, [%0], %1;\n@!p bra WAIT_LOOP;\n}\n" ::"r"(bar), "r"(parity) : "memory");
}
__device__ __forceinline__ void mbar_wait1(uint32_t bar, uint32_t parity) {
  asm volatile("{\n.reg .pred p;\nWAIT_LOOP:\nbar.warp.sync -1;\nmbarrier.try_wait.parity.shared::cta.b64 p, [%0], %1, 4000;\n@!p bra WAIT_LOOP;\n}\n" ::"r"(bar), "r"(parity) : "memory");
}
constexpr uint64_t EV_NORMAL = 0x1000000000000000ull, EV_FIRST = 0x12F0000000000000ull;
__device__ __forceinline__ uint32_t ldg_stream(const uint32_t* p) {
  uint32_t r; asm volatile("ld.global.nc.L1::no_allocate.L2::cache_hint.b32 %0, [%1], %2;" : "=r"(r) : "l"(p), "l"(EV_FIRST)); return r;
}
__device__ __forceinline__ void tma2d(uint32_t dst, const CUtensorMap* tm, int c0, int c1, uint32_t bar, uint64_t pol) {
  asm volatile("cp.async.bulk.tensor.2d.shared::cluster.global.mbarrier::complete_tx::bytes.L2::cache_hint [%0], [%1, {%3, %4}], [%2], %5;"
               ::"r"(dst), "l"(tm), "r"(bar), "r"(c0), "r"(c1), "l"(pol) : "memory");
}
__device__ __forceinline__ void tma2d_mc(uint32_t dst, const CUtensorMap* tm, int c0, int c1, uint32_t bar, uint64_t pol) {
  asm volatile("cp.async.bulk.tensor.2d.shared::cluster.global.mbarrier::complete_tx::bytes.multicast::cluster.L2::cache_hint [%0], [%1, {%3, %4}], [%2], %5, %6;"
               ::"r"(dst), "l"(tm), "r"(bar), "r"(c0), "r"(c1), "h"((uint16_t)3), "l"(pol) : "memory");
}
__device__ __forceinline__ void tma3d(uint32_t dst, const CUtensorMap* tm, int c0, int c1, int c2, uint32_t bar, uint64_t pol) {
  asm volatile("cp.async.bulk.tensor.3d.shared::cluster.global.mbarrier::complete_tx::bytes.L2::cache_hint [%0], [%1, {%3, %4, %5}], [%2], %6;"
               ::"r"(dst), "l"(tm), "r"(bar), "r"(c0), "r"(c1), "r"(c2), "l"(pol) : "memory");
}
__device__ __forceinline__ void tma3d_mc(uint32_t dst, const CUtensorMap* tm, int c0, int c1, int c2, uint32_t bar, uint64_t pol) {
  asm volatile("cp.async.bulk.tensor.3d.shared::cluster.global.mbarrier::complete_tx::bytes.multicast::cluster.L2::cache_hint [%0], [%1, {%3, %4, %5}], [%2], %6, %7;"
               ::"r"(dst), "l"(tm), "r"(bar), "r"(c0), "r"(c1), "r"(c2), "h"((uint16_t)3), "l"(pol) : "memory");
}
__device__ __forceinline__ void bulk_g2s(uint32_t dst, const void* src, uint32_t bytes, uint32_t bar, uint64_t pol) {
  asm volatile("cp.async.bulk.shared::cluster.global.mbarrier::complete_tx::bytes.L2::cache_hint [%0], [%1], %2, [%3], %4;"
               ::"r"(dst), "l"(src), "r"(bytes), "r"(bar), "l"(pol) : "memory");
}
__device__ __forceinline__ void tma2d_store(const CUtensorMap* tm, uint32_t src, int c0, int c1) {
  asm volatile("cp.async.bulk.tensor.2d.global.shared::cta.bulk_group [%0, {%2, %3}], [%1];" ::"l"(tm), "r"(src), "r"(c0), "r"(c1) : "memory");
}
__device__ __forceinline__ void prefetch_tm(const CUtensorMap* tm) { asm volatile("prefetch.tensormap [%0];" ::"l"(tm) : "memory"); }
__device__ __forceinline__ void wg_fence() { asm volatile("wgmma.fence.sync.aligned;" ::: "memory"); }
__device__ __forceinline__ void wg_commit() { asm volatile("wgmma.commit_group.sync.aligned;" ::: "memory"); }
template <int N> __device__ __forceinline__ void wg_wait() { asm volatile("wgmma.wait_group.sync.aligned %0;" ::"n"(N) : "memory"); }
__device__ __forceinline__ void bar_sync(int id, int n) { asm volatile("bar.sync %0, %1;" ::"r"(id), "r"(n) : "memory"); }
__device__ __forceinline__ void bar_arrive(int id, int n) { asm volatile("bar.arrive %0, %1;" ::"r"(id), "r"(n) : "memory"); }
__device__ __forceinline__ void fence_async_smem() { asm volatile("fence.proxy.async.shared::cta;" ::: "memory"); }
__device__ __forceinline__ void fence_async_all() { asm volatile("fence.proxy.async.global;" ::: "memory"); }
__device__ __forceinline__ uint32_t pack_bf16(float lo, float hi) { uint32_t r; asm("cvt.rn.bf16x2.f32 %0, %1, %2;" : "=r"(r) : "f"(hi), "f"(lo)); return r; }
__device__ __forceinline__ float ex2(float x) { float r; asm("ex2.approx.ftz.f32 %0, %1;" : "=f"(r) : "f"(x)); return r; }
__device__ __forceinline__ float rcp(float x) { float r; asm("rcp.approx.ftz.f32 %0, %1;" : "=f"(r) : "f"(x)); return r; }
__device__ __forceinline__ void flag_wait(const unsigned* f, unsigned target) {
  unsigned v;
  do { asm volatile("ld.acquire.gpu.global.u32 %0, [%1];" : "=r"(v) : "l"(f) : "memory"); } while (__any_sync(0xffffffffu, v < target));
}
__device__ __forceinline__ bool elect() {
  uint32_t r;
  asm volatile("{\n.reg .pred p;\nelect.sync _|p, -1;\nselp.u32 %0, 1, 0, p;\n}\n" : "=r"(r));
  return r;
}
__device__ __forceinline__ void fence_release() { asm volatile("fence.release.gpu;" ::: "memory"); }
__device__ __forceinline__ void flag_add(unsigned* f) { asm volatile("red.relaxed.gpu.global.add.u32 [%0], 1;" ::"l"(f) : "memory"); }
__device__ __forceinline__ void cluster_arrive() { asm volatile("barrier.cluster.arrive.relaxed.aligned;" ::: "memory"); }
__device__ __forceinline__ void cluster_wait() { asm volatile("barrier.cluster.wait.aligned;" ::: "memory"); }
__device__ __forceinline__ uint32_t hmul2(uint32_t a, uint32_t b) { uint32_t r; asm("mul.rn.bf16x2 %0, %1, %2;" : "=r"(r) : "r"(a), "r"(b)); return r; }
__device__ __forceinline__ uint32_t hadd2(uint32_t a, uint32_t b) { uint32_t r; asm("add.rn.bf16x2 %0, %1, %2;" : "=r"(r) : "r"(a), "r"(b)); return r; }
__device__ __forceinline__ uint32_t hfma2(uint32_t a, uint32_t b, uint32_t c) { uint32_t r; asm("fma.rn.bf16x2 %0, %1, %2, %3;" : "=r"(r) : "r"(a), "r"(b), "r"(c)); return r; }
__device__ __forceinline__ uint32_t lds32(uint32_t a) { uint32_t r; asm volatile("ld.shared.b32 %0, [%1];" : "=r"(r) : "r"(a) : "memory"); return r; }
__device__ __forceinline__ uint4 lds128(uint32_t a) { uint4 r; asm volatile("ld.shared.v4.b32 {%0,%1,%2,%3}, [%4];" : "=r"(r.x), "=r"(r.y), "=r"(r.z), "=r"(r.w) : "r"(a) : "memory"); return r; }
__device__ __forceinline__ uint32_t desc_k(uint32_t addr) { return ((addr & 0x3FFFF) >> 4) | (1u << 16); }
template <int LBO> __device__ __forceinline__ uint32_t desc_mn(uint32_t addr) { return ((addr & 0x3FFFF) >> 4) | ((uint32_t)(LBO >> 4) << 16); }
#define DHI "0x40000040"

#define R8(d, o) "+f"(d[o]), "+f"(d[o + 1]), "+f"(d[o + 2]), "+f"(d[o + 3]), "+f"(d[o + 4]), "+f"(d[o + 5]), "+f"(d[o + 6]), "+f"(d[o + 7])
#define R32(d, o) R8(d, o), R8(d, o + 8), R8(d, o + 16), R8(d, o + 24)
#define R64(d, o) R32(d, o), R32(d, o + 32)
#define L64 "%0,%1,%2,%3,%4,%5,%6,%7,%8,%9,%10,%11,%12,%13,%14,%15,%16,%17,%18,%19,%20,%21,%22,%23,%24,%25,%26,%27,%28,%29,%30,%31," \
            "%32,%33,%34,%35,%36,%37,%38,%39,%40,%41,%42,%43,%44,%45,%46,%47,%48,%49,%50,%51,%52,%53,%54,%55,%56,%57,%58,%59,%60,%61,%62,%63"
#define L128 L64 ",%64,%65,%66,%67,%68,%69,%70,%71,%72,%73,%74,%75,%76,%77,%78,%79,%80,%81,%82,%83,%84,%85,%86,%87,%88,%89,%90,%91,%92,%93,%94,%95," \
            "%96,%97,%98,%99,%100,%101,%102,%103,%104,%105,%106,%107,%108,%109,%110,%111,%112,%113,%114,%115,%116,%117,%118,%119,%120,%121,%122,%123,%124,%125,%126,%127"

template <int TB> __device__ __forceinline__ void mma_ss_n128(float (&d)[64], uint32_t da, uint32_t db) {
  asm volatile("{\n.reg .b64 da, db;\nmov.b64 da, {%64, " DHI "};\nmov.b64 db, {%65, " DHI "};\n"
               "wgmma.mma_async.sync.aligned.m64n128k16.f32.bf16.bf16 {" L64 "}, da, db, 1, 1, 1, 0, %66;\n}\n"
               : R64(d, 0) : "r"(da), "r"(db), "n"(TB));
}
template <int TB> __device__ __forceinline__ void mma_rs_n128(float (&d)[64], uint32_t a0, uint32_t a1, uint32_t a2, uint32_t a3, uint32_t db, int sd) {
  asm volatile("{\n.reg .pred p;\n.reg .b64 db;\nsetp.ne.b32 p, %69, 0;\nmov.b64 db, {%68, " DHI "};\n"
               "wgmma.mma_async.sync.aligned.m64n128k16.f32.bf16.bf16 {" L64 "}, {%64,%65,%66,%67}, db, p, 1, 1, %70;\n}\n"
               : R64(d, 0) : "r"(a0), "r"(a1), "r"(a2), "r"(a3), "r"(db), "r"(sd), "n"(TB));
}
template <int TB> __device__ __forceinline__ void mma_ss_n256(float (&d)[128], uint32_t da, uint32_t db) {
  asm volatile("{\n.reg .b64 da, db;\nmov.b64 da, {%128, " DHI "};\nmov.b64 db, {%129, " DHI "};\n"
               "wgmma.mma_async.sync.aligned.m64n256k16.f32.bf16.bf16 {" L128 "}, da, db, 1, 1, 1, 0, %130;\n}\n"
               : R64(d, 0), R64(d, 64) : "r"(da), "r"(db), "n"(TB));
}
#define W8(d, o) "=f"(d[o]), "=f"(d[o + 1]), "=f"(d[o + 2]), "=f"(d[o + 3]), "=f"(d[o + 4]), "=f"(d[o + 5]), "=f"(d[o + 6]), "=f"(d[o + 7])
#define W32(d, o) W8(d, o), W8(d, o + 8), W8(d, o + 16), W8(d, o + 24)
#define W64(d, o) W32(d, o), W32(d, o + 32)
template <int TB> __device__ __forceinline__ void mma_ss_n128_init(float (&d)[64], uint32_t da, uint32_t db) {
  asm volatile("{\n.reg .b64 da, db;\nmov.b64 da, {%64, " DHI "};\nmov.b64 db, {%65, " DHI "};\n"
               "wgmma.mma_async.sync.aligned.m64n128k16.f32.bf16.bf16 {" L64 "}, da, db, 0, 1, 1, 0, %66;\n}\n"
               : W64(d, 0) : "r"(da), "r"(db), "n"(TB));
}
template <int TB> __device__ __forceinline__ void mma_ss_n256_init(float (&d)[128], uint32_t da, uint32_t db) {
  asm volatile("{\n.reg .b64 da, db;\nmov.b64 da, {%128, " DHI "};\nmov.b64 db, {%129, " DHI "};\n"
               "wgmma.mma_async.sync.aligned.m64n256k16.f32.bf16.bf16 {" L128 "}, da, db, 0, 1, 1, 0, %130;\n}\n"
               : W64(d, 0), W64(d, 64) : "r"(da), "r"(db), "n"(TB));
}
#define L32 "%0,%1,%2,%3,%4,%5,%6,%7,%8,%9,%10,%11,%12,%13,%14,%15,%16,%17,%18,%19,%20,%21,%22,%23,%24,%25,%26,%27,%28,%29,%30,%31"
__device__ __forceinline__ void mma_ss_n64(float (&d)[32], uint32_t da, uint32_t db) {
  asm volatile("{\n.reg .b64 da, db;\nmov.b64 da, {%32, " DHI "};\nmov.b64 db, {%33, " DHI "};\n"
               "wgmma.mma_async.sync.aligned.m64n64k16.f32.bf16.bf16 {" L32 "}, da, db, 1, 1, 1, 0, 0;\n}\n"
               : R32(d, 0) : "r"(da), "r"(db));
}
__device__ __forceinline__ void mma_ss_n64_init(float (&d)[32], uint32_t da, uint32_t db) {
  asm volatile("{\n.reg .b64 da, db;\nmov.b64 da, {%32, " DHI "};\nmov.b64 db, {%33, " DHI "};\n"
               "wgmma.mma_async.sync.aligned.m64n64k16.f32.bf16.bf16 {" L32 "}, da, db, 0, 1, 1, 0, 0;\n}\n"
               : W32(d, 0) : "r"(da), "r"(db));
}
#define L16 "%0,%1,%2,%3,%4,%5,%6,%7,%8,%9,%10,%11,%12,%13,%14,%15"
template <int O, bool INIT> __device__ __forceinline__ void mma_rs_n32(float (&d)[128], uint32_t a0, uint32_t a1, uint32_t a2, uint32_t a3, uint32_t db) {
  if (INIT) asm volatile("{\n.reg .b64 db;\nmov.b64 db, {%20, 0x00000008};\n"
               "wgmma.mma_async.sync.aligned.m64n32k16.f32.bf16.bf16 {" L16 "}, {%16,%17,%18,%19}, db, 0, 1, 1, 0;\n}\n"
               : W8(d, O), W8(d, O + 8) : "r"(a0), "r"(a1), "r"(a2), "r"(a3), "r"(db));
  else asm volatile("{\n.reg .b64 db;\nmov.b64 db, {%20, 0x00000008};\n"
               "wgmma.mma_async.sync.aligned.m64n32k16.f32.bf16.bf16 {" L16 "}, {%16,%17,%18,%19}, db, 1, 1, 1, 0;\n}\n"
               : R8(d, O), R8(d, O + 8) : "r"(a0), "r"(a1), "r"(a2), "r"(a3), "r"(db));
}
template <int O, bool INIT> __device__ __forceinline__ void mma_rs_n64(float (&d)[128], uint32_t a0, uint32_t a1, uint32_t a2, uint32_t a3, uint32_t db) {
  if (INIT) asm volatile("{\n.reg .b64 db;\nmov.b64 db, {%36, 0x00000008};\n"
               "wgmma.mma_async.sync.aligned.m64n64k16.f32.bf16.bf16 {" L32 "}, {%32,%33,%34,%35}, db, 0, 1, 1, 0;\n}\n"
               : W32(d, O) : "r"(a0), "r"(a1), "r"(a2), "r"(a3), "r"(db));
  else asm volatile("{\n.reg .b64 db;\nmov.b64 db, {%36, 0x00000008};\n"
               "wgmma.mma_async.sync.aligned.m64n64k16.f32.bf16.bf16 {" L32 "}, {%32,%33,%34,%35}, db, 1, 1, 1, 0;\n}\n"
               : R32(d, O) : "r"(a0), "r"(a1), "r"(a2), "r"(a3), "r"(db));
}
template <int S, int J> __device__ __forceinline__ void conv_step(float (&d)[128], const uint32_t (&a)[64], uint32_t db) {
  if constexpr (J >= 0 && J >= (S >> 1)) {
    if constexpr (J >= 8 - 2 * CWIDE) {
      mma_rs_n64<16 * (J - 1), S == 0>(d, a[4 * S], a[4 * S + 1], a[4 * S + 2], a[4 * S + 3], db + (uint32_t)((2 * (J - 1) - S) * 16));
      conv_step<S, J - 2>(d, a, db);
    } else {
      mma_rs_n32<16 * J, S == 0>(d, a[4 * S], a[4 * S + 1], a[4 * S + 2], a[4 * S + 3], db + (uint32_t)((2 * J - S) * 16));
      conv_step<S, J - 1>(d, a, db);
    }
  }
}
__device__ __forceinline__ void mma_ss_n8(float (&d)[4], uint32_t da, uint32_t db) {
  asm volatile("{\n.reg .b64 da, db;\nmov.b64 da, {%4, " DHI "};\nmov.b64 db, {%5, 0x00000008};\n"
               "wgmma.mma_async.sync.aligned.m64n8k16.f32.bf16.bf16 {%0,%1,%2,%3}, da, db, 1, 1, 1, 0, 0;\n}\n"
               : "+f"(d[0]), "+f"(d[1]), "+f"(d[2]), "+f"(d[3]) : "r"(da), "r"(db));
}
template <int N> __device__ __forceinline__ void reg_fence(float (&d)[N]) {
#pragma unroll
  for (int i = 0; i < N; i++) asm volatile("" : "+f"(d[i])::"memory");
}
template <int N> __device__ __forceinline__ void reg_fence(uint32_t (&d)[N]) {
#pragma unroll
  for (int i = 0; i < N; i++) asm volatile("" : "+r"(d[i])::"memory");
}

struct __align__(64) Params {
  CUtensorMap x, c, wq, wuk, wuv, wo, y, out, w;
  const __nv_bfloat16* xp;
  const __nv_bfloat16* gate_w;
  const __nv_bfloat16 *ak, *av, *shk, *ssk, *ssd;
  int zero;
  uint8_t pref[128];
};

template <int O, int N, int M> __device__ __forceinline__ void pack_frag(const float (&acc)[N], uint32_t (&pk)[M]) {
#pragma unroll
  for (int i = 0; i < 32; i++) pk[i] = pack_bf16(acc[O + 2 * i], acc[O + 2 * i + 1]);
}
template <int N> __device__ __forceinline__ void pack_frag_scaled(const float (&acc)[N], uint32_t (&pk)[32], float s0, float s1) {
#pragma unroll
  for (int i = 0; i < 32; i++) { const float s = (i & 1) ? s1 : s0; pk[i] = pack_bf16(acc[2 * i] * s, acc[2 * i + 1] * s); }
}
template <int J0 = 0, int J1 = 8, int M> __device__ __forceinline__ void stsm_frag(const uint32_t (&pk)[M], uint32_t a) {
#pragma unroll
  for (int jj = J0; jj < J1; jj++)
    asm volatile("stmatrix.sync.aligned.m8n8.x4.shared.b16 [%0], {%1,%2,%3,%4};" ::"r"((a ^ ((jj & 3) << 5)) + (jj >> 2) * 16384),
                 "r"(pk[4 * jj]), "r"(pk[4 * jj + 1]), "r"(pk[4 * jj + 2]), "r"(pk[4 * jj + 3]) : "memory");
}

struct Cons {
  uint32_t sb;
  uint32_t pf;
  int wg, tid;
  __device__ __forceinline__ void wait_full(int g) { mbar_wait(sb + SM_BAR + (B_FULL + g) * 8, (pf >> g) & 1); pf ^= 1u << g; }
  uint32_t relb;
  __device__ __forceinline__ void release(int g, int n) {
    if (tid < 2 * n) asm volatile("mbarrier.arrive.shared::cluster.b64 _, [%0];" ::"r"(relb + g * 8) : "memory");
  }
  __device__ __forceinline__ void turn_begin() { bar_sync(1 + wg, 256); }
  __device__ __forceinline__ void turn_end() { bar_arrive(2 - wg, 256); }
  __device__ __forceinline__ void staged(int e) { __syncwarp(); if ((tid & 31) == 0) mbar_arrive(sb + SM_BAR + (B_EV + 2 * e + wg) * 8); }
  int zero;
  int rnd;
  uint32_t pfree;
  __device__ __forceinline__ void wait_stage_free() { mbar_wait(sb + SM_BAR + (B_FREE + wg) * 8, pfree); pfree ^= 1; }
  __device__ __forceinline__ bool try_full(int g) { return mbar_test(sb + SM_BAR + (B_FULL + g) * 8, (pf >> g) & 1); }
};

constexpr float SM_C = 0.08838834764831845f * 1.4426950408889634f;
struct SoftState { float m0, m1, l0, l1; int shifted; };
__device__ __forceinline__ void ex2_rot(float& t, float s, uint32_t never_zero) {
  asm("{\n.reg .pred p;\nsetp.ne.u32 p, %2, 0;\n@p ex2.approx.ftz.f32 %0, %1;\n}\n" : "+f"(t) : "f"(s), "r"(never_zero));
}
__device__ __forceinline__ void pin(float a, uint32_t never_zero) {
  asm volatile("{\n.reg .pred p;\nsetp.eq.u32 p, %1, 0;\n@p st.shared.f32 [%1], %0;\n}\n" ::"f"(a), "r"(never_zero) : "memory");
}
template <int O, int N> __device__ __forceinline__ void reg_fence_part(uint32_t (&d)[32]) {
#pragma unroll
  for (int i = O; i < O + N; i++) asm volatile("" : "+r"(d[i])::"memory");
}
template <int Q, int W, int N> __device__ __forceinline__ void exp_quarter(const float (&S)[N], uint32_t (&P)[32], float (&t)[ROT], float& s0, float& s1, uint32_t nz) {
#pragma unroll
  for (int i = 8 * Q; i < 8 * Q + 8; i++) {
    float& a = t[(2 * i) % ROT];
    float& b = t[(2 * i + 1) % ROT];
    if (2 * i < ROT) { a = ex2(S[2 * i]); b = ex2(S[2 * i + 1]); }
    else { ex2_rot(a, S[2 * i], nz); ex2_rot(b, S[2 * i + 1], nz); }
    if (i < 2) { if (i) s1 = a + b; else s0 = a + b; }
    else if (SUMV == 0) { if (i & 1) { s1 += a; s1 += b; } else { s0 += a; s0 += b; } }
    else { if (i & 1) s1 += a + b; else s0 += a + b; }
    if (i == 8 * Q) { pin(EXPV == 1 && Q ? s1 : s0, nz); wg_wait<W>(); reg_fence_part<8 * Q, 8>(P); }
    P[i] = pack_bf16(a, b);
  }
}
template <int N> __device__ __forceinline__ void shift_scores(float (&S)[N], float d0, float d1) {
#pragma unroll
  for (int i = 0; i < N; i++) S[i] -= (i & 2) ? d1 : d0;
}
__device__ __forceinline__ bool soft_high(float s0, float s1, float lim = SM_LIMIT) { return s0 > lim || s1 > lim; }
__device__ __forceinline__ bool soft_unsafe(float s0, float s1, bool first) {
  uint32_t b0 = __ballot_sync(0xffffffffu, s0 >= SM_LOW), b1 = __ballot_sync(0xffffffffu, s1 >= SM_LOW);
  b0 |= b0 >> 1; b0 |= b0 >> 2; b1 |= b1 >> 1; b1 |= b1 >> 2;
  return __any_sync(0xffffffffu, soft_high(s0, s1)) || (first && (b0 & b1 & 0x11111111u) != 0x11111111u);
}
template <int N> __device__ __forceinline__ void soft_fix(const float (&S)[N], float (&O)[64], SoftState& z, bool first, float& d0, float& d1) {
  d0 = d1 = first ? -INFINITY : 0.f;
#pragma unroll
  for (int j = 0; j < N / 4; j++) { d0 = fmaxf(d0, fmaxf(S[4 * j], S[4 * j + 1])); d1 = fmaxf(d1, fmaxf(S[4 * j + 2], S[4 * j + 3])); }
  d0 = fmaxf(d0, __shfl_xor_sync(0xffffffffu, d0, 1)); d1 = fmaxf(d1, __shfl_xor_sync(0xffffffffu, d1, 1));
  d0 = fmaxf(d0, __shfl_xor_sync(0xffffffffu, d0, 2)); d1 = fmaxf(d1, __shfl_xor_sync(0xffffffffu, d1, 2));
  const float sc0 = ex2(-fmaxf(d0, 0.f)), sc1 = ex2(-fmaxf(d1, 0.f));
  z.m0 += d0; z.m1 += d1; z.l0 *= sc0; z.l1 *= sc1; z.shifted = 1;
#pragma unroll
  for (int j = 0; j < 16; j++) { O[4 * j] *= sc0; O[4 * j + 1] *= sc0; O[4 * j + 2] *= sc1; O[4 * j + 3] *= sc1; }
}
template <int M> __device__ __forceinline__ void pin32(const uint32_t (&v)[M], uint32_t never_zero) {
#pragma unroll
  for (int i = 0; i < 32; i += 4)
    asm volatile("{\n.reg .pred p;\nsetp.eq.u32 p, %4, 0;\n@p st.shared.v4.b32 [%4], {%0,%1,%2,%3};\n}\n" ::"r"(v[i]), "r"(v[i + 1]), "r"(v[i + 2]), "r"(v[i + 3]), "r"(never_zero) : "memory");
}
template <int N> __device__ __forceinline__ void mask_diag(float (&S)[N], float nd) {
  asm volatile("" : "+f"(nd));
#pragma unroll
  for (int i = 0; i < 32; i++) {
    const float beyond = __saturatef(nd + (float)(8 * (i >> 2) + (i & 1) - 4 * (i & 2)));
    S[N - 32 + i] = fmaf(beyond, -3.0e38f, S[N - 32 + i]);
  }
}
__device__ __forceinline__ float quad_sum(float v) {
  v += __shfl_xor_sync(0xffffffffu, v, 1);
  v += __shfl_xor_sync(0xffffffffu, v, 2);
  return v;
}
__device__ __forceinline__ void issue_qk(float (&S)[64], uint32_t dq, uint32_t dk) {
  mma_ss_n128_init<0>(S, dq, dk);
#pragma unroll
  for (int s = 1; s < 8; s++) mma_ss_n128<0>(S, dq + (s >> 2) * 1024 + (s & 3) * 2, dk + (s >> 2) * 1024 + (s & 3) * 2);
}
__device__ __forceinline__ void issue_qk(float (&S)[32], uint32_t dq, uint32_t dk) {
  mma_ss_n64_init(S, dq, dk);
#pragma unroll
  for (int s = 1; s < 8; s++) mma_ss_n64(S, dq + (s >> 2) * 1024 + (s & 3) * 2, dk + (s >> 2) * 1024 + (s & 3) * 2);
}
template <int H> __device__ __forceinline__ void issue_pv(float (&O)[64], const uint32_t (&P)[32], uint32_t dv, int acc, bool on) {
  if (on) {
#pragma unroll
    for (int s = 4 * H; s < 4 * H + 4; s++) {
      mma_rs_n128<1>(O, P[4 * s], P[4 * s + 1], P[4 * s + 2], P[4 * s + 3], dv + s * 128, s != 0 ? 1 : acc);
      if (s & 1) wg_commit();
    }
  } else { wg_commit(); wg_commit(); }
}
constexpr uint32_t DG = GR >> 4;
__device__ __forceinline__ void stage_q2(Cons& c, const float (&O)[64], uint32_t (&P)[32], uint32_t stg) {
  wg_commit(); wg_commit(); wg_commit(); wg_commit();
  c.turn_end();
  pack_frag<0>(O, P);
  stsm_frag(P, stg);
  fence_async_smem();
}
__device__ __forceinline__ void attn_half(Cons& c, float (&O)[64], uint32_t (&P)[32], SoftState& z, uint32_t dk0, uint32_t dkk, uint32_t dv0, float dmask, int last) {
  float S[32];
  FTH(8 + last * 32, 0);
  c.turn_begin();
  FTH(9 + last * 32, 0);
  wg_fence();
  issue_qk(S, dk0 + (last ? 0 : 2 * DG), dkk + (last ? 8 : 4) * DG);
  wg_commit();
  issue_pv<0>(O, P, dv0 + 10 * DG, 1, last);
  issue_pv<1>(O, P, dv0 + 10 * DG, 1, last);
  c.turn_end();
  c.wait_full(last ? 12 : 6);
  FTH(10 + last * 32, 0);
  wg_wait<4>();
  reg_fence(S);
  FTH(11 + last * 32, 0);
  c.release(last ? 8 : 4, 2);
  mask_diag(S, dmask);
  float s0, s1, d0 = z.m0, d1 = z.m1;
#pragma unroll 1
  for (int pass = 0;; pass++) {
    if (z.shifted) shift_scores(S, d0, d1);
    float tr[ROT];
    exp_quarter<0, 3>(S, P, tr, s0, s1, c.sb);
    exp_quarter<1, 2>(S, P, tr, s0, s1, c.sb);
    pin(s1, c.sb); wg_wait<0>(); reg_fence_part<16, 16>(P); reg_fence(O);
    if (!soft_unsafe(s0, s1, !last) || pass) break;
    soft_fix(S, O, z, !last, d0, d1);
  }
  FTH(12 + last * 32, 0);
  z.l0 += s0; z.l1 += s1;
  c.release(10, last ? 2 : 0);
  if (!last) c.wait_full(8);
  FTH(13 + last * 32, 0);
}

template <int V> struct IC { static constexpr int value = V; };
__device__ __forceinline__ int conv_next(int g, bool spare) { return g >= NGR - 2 ? g - (NGR - 4) : !spare && g == 4 ? 1 : g + 2; }
__device__ __forceinline__ void conv_final(uint32_t rb, uint32_t yb, const uint4& u, uint32_t dd, bool on) {
  const uint4 q0 = lds128(rb), q1 = lds128(rb + 4096), q2 = lds128(rb + 8192), q3 = lds128(rb + 12288);
  auto fin = [&](uint32_t x0, uint32_t x1, uint32_t x2, uint32_t x3, uint32_t uu) {
    if (DFOLD) return hadd2(hadd2(x0, x1), hadd2(x2, x3));
    return hfma2(dd, __byte_perm(uu, uu, 0x1032), hadd2(hadd2(x0, x1), hadd2(x2, x3)));
  };
  asm volatile("{\n.reg .pred p;\nsetp.ne.b32 p, %5, 0;\n@p st.shared.v4.b32 [%0], {%1,%2,%3,%4};\n}\n" ::"r"(yb), "r"(fin(q0.x, q1.x, q2.x, q3.x, u.w)),
               "r"(fin(q0.y, q1.y, q2.y, q3.y, u.z)), "r"(fin(q0.z, q1.z, q2.z, q3.z, u.y)), "r"(fin(q0.w, q1.w, q2.w, q3.w, u.x)), "r"((int)on) : "memory");
}
__device__ __forceinline__ void conv_tasks(Cons& c, const Params& p, int ntask, bool last, bool spare, int ch, int chstep, uint32_t dd, uint32_t dkk, int w, int lane) {
  const uint32_t sb = c.sb;
  int g = 2 + c.wg;
  uint4 u0 = make_uint4(0, 0, 0, 0), u1 = u0;
  uint32_t rb = sb + g * GR;
  const uint32_t yb = sb + c.wg * 8192 + c.tid * 16;
  c.wait_full(g);
#pragma unroll 1
  for (int i = 0; i < ntask; i++) {
    const uint32_t base = sb + g * GR;
    FTC(0);
    uint32_t a[64];
    const uint32_t hb = base + WBYTES - 28 + (8 * w + (lane >> 2) + (lane & 3)) * 4;
    auto lda = [&](int s) {
      a[4 * s] = lds32(hb + s * 256); a[4 * s + 1] = lds32(hb + s * 256 + 128);
      a[4 * s + 2] = lds32(hb + s * 256 + 16); a[4 * s + 3] = lds32(hb + s * 256 + 144);
    };
    lda(0); lda(15); lda(1); lda(14);
    if (DFOLD) {
      const int gt = 8 * w + (lane >> 2) + (lane & 3);
      a[0] = hadd2(a[0], gt == 7 ? dd : 0u); a[2] = hadd2(a[2], gt == 3 ? dd : 0u);
    }
    float acc[128];
    const uint32_t db = dkk + ((WPL / 16 - 1) << 16) + g * DG + WZ / 16;
    FTC(2);
    c.turn_begin();
    FTC(3);
    auto pair = [&](auto kc) {
      constexpr int k = decltype(kc)::value;
      if (k < 7) wg_fence();
      if (k == 7 && !(last && i == ntask - 1)) c.turn_end();
      conv_step<k, 7>(acc, a, db);
      conv_step<15 - k, 7>(acc, a, db);
      if (k < 6) { lda(k + 2); lda(13 - k); }
      if (k == 0) conv_final(rb, yb, u0, dd, i > 0);
      if (k == 1) {
        conv_final(rb + 2048, yb + 2048, u1, dd, i > 0);
        __syncwarp();
        if (lane == 0 && i > 0) mbar_arrive(sb + SM_BAR + (B_EV + c.wg) * 8);
      }
      if (DFOLD) { if (k == 6) dd = __bfloat16_as_ushort(p.ssd[(ch + chstep) & (DM - 1)]); }
      else if (k == 6) {
        const uint32_t ub = base + WZ + 16 + (c.tid >> 1) * 32 + ((c.tid & 1) ^ 1) * WPL;
        u0 = lds128(ub); u1 = lds128(ub + 2048);
        dd = __bfloat16_as_ushort(p.ssd[ch]) * 0x10001u;
      }
    };
    pair(IC<0>()); pair(IC<1>()); pair(IC<2>()); pair(IC<3>()); pair(IC<4>()); pair(IC<5>()); pair(IC<6>()); pair(IC<7>());
    wg_commit();
    FTC(4);
    g = conv_next(g, spare);
    ch += chstep;
    rb = base + c.tid * 16;
    wg_wait<0>();
    reg_fence(acc);
    reg_fence(a);
    bar_sync(3 + c.wg, 128);
    FTC(5);
    const int tw = (lane & 3) + w;
    const uint32_t xb = base + w * 4096 + tw * 32 + (lane >> 2) * 4;
#pragma unroll
    for (int j = 0; j < 32; j++) {
      float v0 = acc[4 * j], v1 = acc[4 * j + 1];
      if (j > 0) { v0 += acc[j > 0 ? 4 * j - 2 : 0]; v1 += acc[j > 0 ? 4 * j - 1 : 0]; }
      uint32_t v = pack_bf16(v0, v1), ad = xb + j * 128;
      if (j == 31 && tw >= 4) { v = 0; ad -= 4096; }
      asm volatile("st.shared.b32 [%0], %1;" ::"r"(ad), "r"(v) : "memory");
    }
    c.wait_stage_free();
    if (i + 1 < ntask) c.wait_full(g);
    bar_sync(3 + c.wg, 128);
    FTC(6);
  }
  conv_final(rb, yb, u0, dd, true);
  conv_final(rb + 2048, yb + 2048, u1, dd, true);
  c.staged(0);
}

__global__ void __cluster_dims__(2, 1, 1) __launch_bounds__(NTHREADS, 1) mega_kernel(const __grid_constant__ Params p) {
  extern __shared__ __align__(1024) uint8_t smem_raw[];
  const uint32_t sb = smem_u32(smem_raw);
  const int wgi = __shfl_sync(0xffffffffu, threadIdx.x >> 7, 0);
  const int warp = __shfl_sync(0xffffffffu, threadIdx.x >> 5, 0);
  const uint32_t rank = blockIdx.x & 1;
  int slot;
  {
    uint32_t smid; asm volatile("mov.u32 %0, %smid;" : "=r"(smid));
    slot = p.pref[(smid >> 1) & 127];
  }
  const int pref = slot;
  unsigned taken = 0;
  if (threadIdx.x == 96 && rank == 0) taken = atomicExch(&g_claim[slot], 1u);
  if (elect()) {
    if (warp == 2) { prefetch_tm(&p.c); prefetch_tm(rank ? &p.wuv : &p.wuk); }
#pragma unroll
    for (int k = 0; k < 3; k++) mbar_init(sb + SM_BAR + (warp * 3 + k) * 8, k == 2 && warp == B_DONE / 3 ? 11 : warp < B_EMPTY / 3 ? 1 : 4);
    if (warp == B_SLOT / 3) mbar_expect_tx(sb + SM_BAR + B_SLOT * 8, 8);
    asm volatile("fence.mbarrier_init.release.cluster;" ::: "memory");
  }
  __syncwarp();
  cluster_arrive();
#pragma unroll 1
  for (int n = 1; n < NSLOT && taken; n++) { slot = slot == NSLOT - 1 ? 0 : slot + 1; taken = atomicExch(&g_claim[slot], 1u); }
  __syncwarp();
  cluster_wait();
  if (threadIdx.x == 96) {
#pragma unroll
    for (int r = 0; r < 2; r++)
      asm volatile("{\n.reg .b32 a, b;\nmapa.shared::cluster.u32 a, %0, %1;\nadd.u32 b, a, %3;\nst.async.shared::cluster.mbarrier::complete_tx::bytes.u32 [b], %2, [a];\n}\n"
                   ::"r"(sb + SM_BAR + B_SLOT * 8), "r"(r), "r"(slot | pref << 8), "r"((V_SLOT - B_SLOT) * 8 + rank * 4) : "memory");
  }
  if (warp == 0) {
    if (elect()) {
#pragma unroll 1
      for (int kk = 0; kk < 4; kk++) {
        const int g0 = 2 + 3 * kk;
        const uint32_t fb = sb + SM_BAR + (B_FULL + g0) * 8;
        mbar_expect_tx(fb, 3 * GR);
        tma2d(sb + g0 * GR, &p.c, kk * 64, (2 * (pref & 7) + rank) * 128, fb, EV_NORMAL);
        tma3d_mc(sb + (g0 + 1 + rank) * GR, rank ? &p.wuv : &p.wuk, 0, kk * 64, (pref >> 3) * 4, fb, POL_W);
      }
      prefetch_tm(&p.x); prefetch_tm(&p.wq);
    }
  }
  mbar_wait(sb + SM_BAR + B_SLOT * 8, 0);
  const uint32_t sv0 = __shfl_sync(0xffffffffu, lds32(sb + SM_BAR + V_SLOT * 8), 0), sv1 = __shfl_sync(0xffffffffu, lds32(sb + SM_BAR + V_SLOT * 8 + 4), 0);
  slot = sv0 & 255;
  const int grp = slot >> 3, idx = slot & 7;
  const int lb = slot * 2 + rank;
  const bool spare = grp == 8;
  const bool redo = spare || sv0 != sv1;
  const int cn = spare ? CN_SPARE : CN_MAIN, cch = spare ? lb - NMAIN : 4 * CN_SPARE + CN_MAIN * lb, cstep = spare ? 4 : 1;
  TS(0);

  if (wgi == 0) {
    asm volatile("setmaxnreg.dec.sync.aligned.u32 40;");
    const int lane = threadIdx.x & 31;
    cluster_arrive();
    if (warp == 3) {
      if (!spare) {
        const int s0 = lb * 16;
#pragma unroll 1
        for (int cg = 0; cg < 16; cg++) {
          __nanosleep(PRE_SLEEP);
          const int ch = cg * 64 + 2 * lane;
          const uint32_t* kp = reinterpret_cast<const uint32_t*>(p.ak + (size_t)s0 * DM + ch);
          const uint32_t* vp = reinterpret_cast<const uint32_t*>(p.av + (size_t)s0 * DM + ch);
          const uint4 sw = __ldg(reinterpret_cast<const uint4*>(p.shk + ch * 4));
          uint32_t k3 = 0, k2 = 0, k1 = 0, k0 = 0, up = 0;
          if (lb > 0) { k3 = ldg_stream(kp - 4 * 512); k2 = ldg_stream(kp - 3 * 512); k1 = ldg_stream(kp - 2 * 512); k0 = ldg_stream(kp - 512); up = ldg_stream(vp - 512); }
          const uint32_t w0 = __byte_perm(sw.x, sw.z, 0x5410), w1 = __byte_perm(sw.x, sw.z, 0x7632);
          const uint32_t w2 = __byte_perm(sw.y, sw.w, 0x5410), w3 = __byte_perm(sw.y, sw.w, 0x7632);
          up = hmul2(hfma2(k0, w0, hfma2(k1, w1, hfma2(k2, w2, hmul2(k3, w3)))), up);
#pragma unroll 1
          for (int hb = 0; hb < 2; hb++) {
            uint32_t kk[8], u[8];
#pragma unroll
            for (int r = 0; r < 8; r++) { kk[r] = ldg_stream(kp + r * 512); u[r] = ldg_stream(vp + r * 512); }
#pragma unroll
            for (int r = 0; r < 8; r++) {
              k3 = k2; k2 = k1; k1 = k0; k0 = kk[r];
              u[r] = hmul2(hfma2(k0, w0, hfma2(k1, w1, hfma2(k2, w2, hmul2(k3, w3)))), u[r]);
            }
            if (lane == 0) asm volatile("cp.async.bulk.wait_group.read 0;" ::: "memory");
            __syncwarp();
            const uint32_t dst = sb + SM_UST + lane * 32 + ((lane & 4) << 2);
#pragma unroll
            for (int cc = 0; cc < 2; cc++) {
              const uint32_t sel = cc ? 0x7632 : 0x5410;
              asm volatile("st.shared.v4.b32 [%0], {%1,%2,%3,%4};" ::"r"(dst + cc * 1024), "r"(__byte_perm(u[6], u[5], sel)), "r"(__byte_perm(u[4], u[3], sel)),
                           "r"(__byte_perm(u[2], u[1], sel)), "r"(__byte_perm(u[0], up, sel)) : "memory");
              asm volatile("st.shared.v4.b32 [%0], {%1,%2,%3,%4};" ::"r"((dst ^ 16) + cc * 1024), "r"(__byte_perm(u[7], u[6], sel)), "r"(__byte_perm(u[5], u[4], sel)),
                           "r"(__byte_perm(u[3], u[2], sel)), "r"(__byte_perm(u[1], u[0], sel)) : "memory");
            }
            fence_async_smem();
            __syncwarp();
            if (lane == 0) {
              asm volatile("cp.async.bulk.tensor.3d.global.shared::cta.bulk_group [%0, {%2, %3, %4}], [%1];\ncp.async.bulk.commit_group;"
                           ::"l"(&p.w), "r"(sb + SM_UST), "r"(WZ / 2 + lb * 16 + (hb ^ 1) * (WPL / 2)), "r"(cg * 32), "r"(0) : "memory");
            }
            up = u[7];
            kp += 8 * 512; vp += 8 * 512;
          }
          if ((cg & (cg + 1)) == 0 && lane == 0) {
            asm volatile("cp.async.bulk.wait_group 0;" ::: "memory");
            fence_release();
            flag_add(FLAG(F_U + 32 - __clz(cg)));
          }
          TSW(10 + cg);
        }
      }
      if (lane == 0) {
        unsigned long long t0, t1;
        asm volatile("mov.u64 %0, %globaltimer;" : "=l"(t0));
        while (!mbar_try(sb + SM_BAR + B_DONE * 8, 0)) {
          asm volatile("mov.u64 %0, %globaltimer;" : "=l"(t1));
          if (t1 - t0 > 2000000000ull) __trap();
        }
      }
    } else if (warp != 0) {
      const int w = warp - 1, ne = 12 + (cn + 1 - w) / 2;
      uint32_t p0 = 0;
      int cg = 2 + w, ch = cch + w * cstep;
#pragma unroll 1
      for (int e = spare ? 12 : 0; e < ne; e++) {
        const int rnd = e >= 6, k = e - 6 * rnd, rt = k == 4 ? idx : 15 - idx;
        uint8_t* dst = k < 4 ? g_kv + (size_t)(((k & 1) * 16 + 2 * grp + (k >> 1)) * 16 + 2 * idx + rank) * 32768 + w * 8192
                     : k < 6 ? g_cimg + (size_t)(rt * 32 + 16 * rnd + 2 * grp + rank) * 32768 + (w ^ (k & 1)) * 8192
                             : reinterpret_cast<uint8_t*>(g_yT + (size_t)ch * SEQ);
        const uint32_t src = sb + w * 8192 + (k == 4 ? 2 * GR : 0);
        if (e == 6) flag_wait(FLAG(F_AD + grp), 32);
        mbar_wait1(sb + SM_BAR + (B_EV + (k == 4 ? 2 : 0) + w) * 8, k == 4 ? rnd : p0);
        if (k != 4) p0 ^= 1;
        if (lane < 4 && k >= 6 && (!spare || e < ne - 6)) mbar_arrive_cluster(sb + SM_BAR + (B_EMPTY + cg) * 8, lane & 1);
        fence_async_smem();
        if (elect()) {
#pragma unroll 1
          for (int i = 0; i < (k >= 6 ? 1 : 8); i++) {
            const uint32_t o = (i >> 2) * 16384 + (i & 3) * 2048;
            asm volatile("cp.async.bulk.global.shared::cta.bulk_group [%0], [%1], %2;" ::"l"(dst + o), "r"(src + o), "r"(k >= 6 ? 4096 : 2048) : "memory");
            asm volatile("cp.async.bulk.commit_group;\ncp.async.bulk.wait_group.read %0;" ::"n"(ST_OUT) : "memory");
          }
          asm volatile("cp.async.bulk.wait_group 0;" ::: "memory");
          if (k != 4) mbar_arrive(sb + SM_BAR + (B_FREE + w) * 8);
        }
        __syncwarp();
        if (lane < (k == 4 ? 4 : e == 11 || (e == ne - 1 && !spare) ? 2 : 0))
          mbar_arrive_cluster(sb + SM_BAR + (B_EMPTY + (k == 4 ? 2 : e == 11) + (lane >> 1)) * 8, lane & 1);
        if (k >= 3) {
          fence_release();
          if (lane == 0 || (lane == 1 && e == 5))
            flag_add(FLAG(lane ? F_AD + grp : k == 3 ? F_KV + rnd * 8 + grp : k < 6 ? F_CTX + rt * 2 + rnd : F_Y + (ch >> 7)));
        }
        if (k >= 6) { cg = conv_next(cg, spare); ch += 2 * cstep; }
      }
      if (lane == 0) mbar_arrive(sb + SM_BAR + B_DONE * 8);
    } else {
      uint32_t pe = 0;
      auto acquire = [&](int g) { mbar_wait1(sb + SM_BAR + (B_EMPTY + g) * 8, (pe >> g) & 1); pe ^= 1u << g; };
#pragma unroll 1
      for (int rnd = 0; rnd < (spare ? 0 : 2); rnd++) {
        const int hp = 16 * rnd + 2 * grp, head = hp + rank;
#pragma unroll 1
        for (int kk = rnd || redo ? 0 : 4; kk < 32; kk++) {
          const int g0 = 2 + 3 * (kk & 3);
          acquire(g0);
          if (kk < 4) { acquire(g0 + 1); acquire(g0 + 2); } else pe ^= 6u << g0;
          if (elect()) {
            const uint32_t fb = sb + SM_BAR + (B_FULL + g0) * 8;
            mbar_expect_tx(fb, 3 * GR);
            if (kk < 16) {
              tma2d(sb + g0 * GR, &p.c, (kk & 7) * 64, (2 * idx + rank) * 128, fb, EV_NORMAL);
              tma3d_mc(sb + (g0 + 1 + rank) * GR, rank ? &p.wuv : &p.wuk, 0, (kk & 7) * 64, (hp + (kk >> 3)) * 2, fb, POL_W);
            } else {
              tma2d_mc(sb + (g0 + rank) * GR, &p.x, (kk - 16) * 64, (rank ? 15 - idx : idx) * 128, fb, EV_NORMAL);
              tma3d(sb + (g0 + 2) * GR, &p.wq, 0, (kk - 16) * 64, head * 2, fb, POL_W);
            }
          }
        }
        flag_wait(FLAG(F_KV + rnd * 8 + grp), 32);
        fence_async_all();
        acquire(2); pe ^= 8u;
        int g0 = 4;
#pragma unroll 1
        for (int f = 0; f < 34; f++) {
          const bool isk = (f == 0) || ((f & 1) && f < 33);
          const int it = (f == 0) ? 0 : (f == 33) ? 16 : isk ? (f + 1) >> 1 : (f >> 1) - 1;
          const int blk = it == 0 ? idx : it <= idx ? it - 1 : it < 16 ? 15 - it : 15 - idx;
          acquire(g0);
          if (f < 5) acquire(g0 + 1); else pe ^= 2u << g0;
          if (elect()) {
            const uint32_t fb = sb + SM_BAR + (B_FULL + g0) * 8;
            mbar_expect_tx(fb, 2 * GR);
            bulk_g2s(sb + g0 * GR, g_kv + (size_t)(((isk ? 0 : 16) + (head & 15)) * 16 + blk) * 32768, 2 * GR, fb, POL_KV);
          }
          g0 = f == 12 ? 12 : g0 == 12 ? 4 : g0 + 2;
        }
      }
      if (spare) {
#pragma unroll 1
        for (int i = 0, g = 2; i < 32; i++) {
          acquire(g); acquire(g + 1);
          if (elect()) {
            const uint32_t fb = sb + SM_BAR + (B_FULL + g) * 8;
            if (i == 0) { mbar_expect_tx(fb - 8, 2048); bulk_g2s(sb + GR, p.gate_w, 2048, fb - 8, EV_NORMAL); }
            mbar_expect_tx(fb, 2 * GR);
            tma2d(sb + g * GR, &p.x, (i & 7) * 128, (lb - NMAIN) * 512 + (i >> 3) * 128, fb, EV_NORMAL);
            tma2d(sb + (g + 1) * GR, &p.x, (i & 7) * 128 + 64, (lb - NMAIN) * 512 + (i >> 3) * 128, fb, EV_NORMAL);
          }
          g = g == NGR - 2 ? 2 : g + 2;
        }
      }
      auto conv_fill = [&](int g, int ch) {
        acquire(g);
        if (elect()) {
          const uint32_t fb = sb + SM_BAR + (B_FULL + g) * 8;
          mbar_expect_tx(fb, WBYTES + 4096);
          bulk_g2s(sb + g * GR, g_w + (size_t)ch * WSTRIDE, WBYTES, fb, POL_C);
          bulk_g2s(sb + g * GR + WBYTES, p.ssk + (size_t)ch * SEQ, 4096, fb, POL_C);
        }
      };
#pragma unroll 1
      for (int i = 0, g = 2; i < cn; i++) {
        if ((i & 15) == 0) { flag_wait(FLAG(F_U + (spare ? 32 - __clz(i >> 4) : 4)), NMAIN); fence_async_all(); }
        conv_fill(g + (i & 1), cch + i * cstep);
        if (i & 1) g = conv_next(g, spare);
      }
      if (!spare) {
        const int rt = 2 * grp + rank, ct = idx;
        int g0 = P3G;
#pragma unroll 1
        for (int kb = 0; kb < 66; kb++) {
          if (kb == 0 || kb == 32 || kb >= 64) {
            flag_wait(FLAG(kb < 64 ? F_CTX + rt * 2 + (kb >> 5) : kb == 64 ? F_GATE : F_Y + ct), kb <= 64 ? 32 : 128);
            fence_async_all();
          }
          acquire(g0);
          if (kb < 11) acquire(g0 + 1);
          if (elect()) {
            const uint32_t fb = sb + SM_BAR + (B_FULL + g0) * 8;
            mbar_expect_tx(fb, kb == 64 ? 2 * GR + 512 : 2 * GR);
            if (kb <= 64) bulk_g2s(kb < 64 ? sb + g0 * GR : sb + SM_GATE, kb < 64 ? (const void*)(g_cimg + (size_t)(rt * 64 + kb) * GR) : (const void*)(g_gate + rt * 128), kb < 64 ? GR : 512, fb, POL_CTX);
            if (kb < 64) {
              tma2d_mc(sb + (g0 + 1) * GR + rank * 8192, &p.wo, ct * 128 + rank * 64, kb * 64, fb, POL_WO);
              if (kb == 40) { prefetch_tm(&p.y); prefetch_tm(&p.out); }
            } else {
              const CUtensorMap* tm = kb == 64 ? &p.x : &p.y;
              const int c0 = (kb == 64 ? ct : rt) * 128, c1 = (kb == 64 ? rt : ct) * 128;
              tma2d(sb + g0 * GR, tm, c0, c1, fb, EV_NORMAL);
              tma2d(sb + (g0 + 1) * GR, tm, c0 + 64, c1, fb, EV_NORMAL);
            }
          }
          g0 = g0 == 12 ? (kb == 3 ? 2 : 0) : g0 + 2;
        }
        unsigned n = 0;
        if (lane == 0) n = atomicAdd(FLAG(F_EXIT), 1);
        if (__shfl_sync(0xffffffffu, n, 0) == NMAIN - 1) {
#pragma unroll 1
          for (int i = lane; i < 96; i += 32) { *FLAG(i) = 0; g_claim[i] = 0; }
        }
      }
      if (lane == 0) mbar_arrive(sb + SM_BAR + B_DONE * 8);
    }
    __syncwarp();
    cluster_wait();
  } else {
    asm volatile("setmaxnreg.inc.sync.aligned.u32 232;");
    Cons c;
    c.sb = sb; c.pf = 0; c.wg = wgi - 1; c.tid = threadIdx.x & 127;
    const int lane = threadIdx.x & 31, t = lane & 3;
    const int row = c.wg * 64 + (warp & 3) * 16 + (lane >> 2);
    const uint32_t dkk = desc_k(sb), dk0 = dkk + c.wg * 512, dm0 = desc_mn<8192>(sb), dv0 = desc_mn<16384>(sb);
    const uint32_t dsw = DG + 512 - c.wg * 1024;
    if (c.wg == 1) bar_arrive(1, 256);
    c.pfree = 1;
    asm("mapa.shared::cluster.u32 %0, %1, %2;" : "=r"(c.relb) : "r"(sb + SM_BAR + (B_EMPTY + (c.tid >> 1)) * 8), "r"(c.tid & 1));
    c.zero = p.zero;
    c.rnd = 0;
    const uint32_t stg = sb + (c.wg * 64 + (warp & 3) * 16 + ((lane >> 3) & 1) * 8 + (lane & 7)) * 128 + (((lane >> 4) ^ (lane & 7)) << 4);

    uint32_t dd0;
    auto load_dd = [&]() { asm volatile("ld.global.nc.u16 %0, [%1];" : "=r"(dd0) : "l"(p.ssd + (unsigned)(cch + c.wg * cstep + (lane & c.zero)))); };
    if (redo) {
      load_dd();
#pragma unroll 1
      for (int g = 2; g < NGR; g += 3) { mbar_wait(sb + SM_BAR + (B_FULL + g) * 8, 0); c.release(g, 3); }
      c.pf = 0x924;
    }
    if (spare) {
      c.wait_full(1);
      int g = 2;
#pragma unroll 1
      for (int r = 0; r < 4; r++) {
        float d[4] = {0.f, 0.f, 0.f, 0.f}, e[4] = {0.f, 0.f, 0.f, 0.f};
#pragma unroll 1
        for (int kb = 0; kb < 16; kb += 2) {
          c.wait_full(g);
          wg_fence();
#pragma unroll
          for (int k = 0; k < 4; k++) {
            mma_ss_n8(d, dk0 + g * DG + k * 2, dkk + DG + kb * 8 + k * 2);
            mma_ss_n8(e, dk0 + (g + 1) * DG + k * 2, dkk + DG + kb * 8 + 8 + k * 2);
          }
          wg_commit();
          wg_wait<0>();
          c.release(g, 2);
          g = g == NGR - 2 ? 2 : g + 2;
        }
        reg_fence(d); reg_fence(e);
        d[0] += e[0]; d[2] += e[2];
        if (t == 0) {
          float* gp = g_gate + (lb - NMAIN) * 512 + r * 128 + row;
          gp[0] = rcp(1.f + ex2(-1.4426950408889634f * d[0])); gp[8] = rcp(1.f + ex2(-1.4426950408889634f * d[2]));
        }
      }
      fence_release();
      __syncwarp();
      if (lane == 0) flag_add(FLAG(F_GATE));
      TS(1);
    }
    const float dmask = (float)(2 * t - (row & 63));
    uint32_t pv[32];
#pragma unroll
    for (int i = 0; i < 32; i++) pv[i] = 0;
#pragma unroll 1
    for (int rnd = 0; rnd < (spare ? 0 : 2); rnd++) {
      float O[64];
      FTM(rnd * 8);
      FTG(0);
      FTH(56, c.rnd == rnd);
      c.wait_full(2);
      FTM(rnd * 8 + 1);
      FTH(57, c.rnd == rnd);
#pragma unroll 1
      for (int tile = c.zero; tile < 2; tile++) {
        float acc[128];
        const bool single = tile == 0;
        {
          FTG(tile * 32 + 1);
          const uint32_t a = dk0 + 2 * DG, b = dm0 + 3 * DG;
          c.turn_begin();
          FTG(tile * 32 + 2);
          FTH(58, c.rnd == rnd);
          wg_fence();
          mma_ss_n256_init<1>(acc, a, b);
#pragma unroll
          for (int k = 1; k < 4; k++) mma_ss_n256<1>(acc, a + k * 2, b + k * 128);
          wg_commit();
          if (single) c.turn_end();
          FTG(tile * 32 + 3);
        }
#pragma unroll 1
        for (int kb = 1; kb < 8; kb++) {
          const int g0 = 2 + 3 * (kb & 3);
          const uint32_t a = dk0 + g0 * DG, b = dm0 + (g0 + 1) * DG;
          const bool second = (kb == 1 && !single) || kb == 7;
          FTG(tile * 32 + kb * 4);
          if (!second) { wg_wait<0>(); c.release(2 + 3 * ((kb - 1) & 3), 3); }
          FTG(tile * 32 + kb * 4 + 1);
          c.wait_full(g0);
          if (!second) c.turn_begin();
          FTG(tile * 32 + kb * 4 + 2);
          wg_fence();
#pragma unroll
          for (int k = 0; k < 4; k++) mma_ss_n256<1>(acc, a + k * 2, b + k * 128);
          wg_commit();
          if (kb != 6) c.turn_end();
          if (second) { wg_wait<1>(); c.release(2 + 3 * ((kb - 1) & 3), 3); }
          FTG(tile * 32 + kb * 4 + 3);
          FTH(58 + kb, c.rnd == rnd || kb > 3);
          if (tile == 1 && kb == 3) { c.wait_stage_free(); stsm_frag<0, 4>(pv, stg); }
          if (tile == 1 && kb == 4) { stsm_frag<4, 8>(pv, stg); c.staged(0); }
        }
        c.rnd = rnd;
        c.wait_stage_free();
        const bool nxt = c.try_full(2);
        wg_wait<0>();
        reg_fence(acc);
        c.release(11, 3);
        pack_frag_scaled(acc, pv, SM_C, SM_C);
        stsm_frag(pv, stg);
        c.staged(0);
        pack_frag<64>(acc, pv);
        pin32(pv, sb);
        FTG(32 + tile * 32);
        if (!nxt) mbar_wait(sb + SM_BAR + (B_FULL + 2) * 8, (c.pf >> 2) & 1);
        c.pf ^= 4;
      }
      TS(1 + rnd * 3);
      FTM(rnd * 8 + 2);
      {
        float qa[64];
        float (&qb)[64] = O;
        {
          FTG(65);
          const uint32_t a = dk0 + 2 * DG, b = dm0 + 4 * DG;
          c.turn_begin();
          FTG(66);
          wg_fence();
          mma_ss_n128_init<1>(qa, a, b);
          mma_ss_n128_init<1>(qb, a + dsw, b);
#pragma unroll
          for (int k = 1; k < 4; k++) {
            mma_ss_n128<1>(qa, a + k * 2, b + k * 128);
            mma_ss_n128<1>(qb, a + dsw + k * 2, b + k * 128);
          }
          wg_commit();
          FTG(67);
        }
#pragma unroll 1
        for (int kb = 1; kb < 16; kb++) {
          const int g0 = 2 + 3 * (kb & 3);
          const uint32_t a = dk0 + g0 * DG, b = dm0 + (g0 + 2) * DG;
          const bool second = kb == 1 || kb == 15;
          FTG(64 + kb * 4);
          if (!second) { wg_wait<0>(); c.release(2 + 3 * ((kb - 1) & 3), 3); }
          FTG(65 + kb * 4);
          c.wait_full(g0);
          if (!second) c.turn_begin();
          FTG(66 + kb * 4);
          FTH(kb - 14, kb < 14);
          wg_fence();
#pragma unroll
          for (int k = 0; k < 4; k++) {
            mma_ss_n128<1>(qa, a + k * 2, b + k * 128);
            mma_ss_n128<1>(qb, a + dsw + k * 2, b + k * 128);
          }
          wg_commit();
          if (kb != 14) c.turn_end();
          if (second) { wg_wait<1>(); c.release(2 + 3 * ((kb - 1) & 3), 3); }
          FTG(67 + kb * 4);
          FTH(2, kb < 15);
          if (kb == QFLUSH) { c.wait_stage_free(); stsm_frag<0, 4>(pv, stg); }
          if (kb == QFLUSH + 1) { stsm_frag<4, 8>(pv, stg); c.staged(0); }
        }
        c.wait_stage_free();
        mbar_wait(sb + SM_BAR + (B_EMPTY + 2) * 8, rnd ^ !redo);
        FTM(rnd * 8 + 3);
        FTH(3, 0);
        wg_wait<0>();
        reg_fence(qa); reg_fence(qb);
        FTH(4, 0);
        c.release(11, 3);
        pack_frag<0>(qa, pv);
        stsm_frag(pv, stg + 2 * GR);
        if (c.wg == 0) {
          pack_frag<0>(qb, pv);
          stsm_frag(pv, stg);
#pragma unroll
          for (int i = 16; i < 32; i++) pv[i] = 0;
        }
        fence_async_smem();
        c.wait_full(4);
      }
      TS(2 + rnd * 3);
      FTM(rnd * 8 + 4);
      FTH(5, 0);
      {
        const int nA = idx + 1;
        uint32_t (&P)[32] = pv;
        SoftState z;
        z.m0 = z.m1 = z.l0 = z.l1 = 0.f; z.shifted = c.zero;
#pragma unroll 1
        for (int seg = c.zero;; seg++) {
        if (c.wg == seg) attn_half(c, O, P, z, dk0, dkk, dv0, dmask, seg);
        if (seg) break;
        FTM(rnd * 8 + 5);
        int gk = c.wg ? 4 : 6, gv = c.wg ? 4 : 8;
        uint32_t dq = dk0 + (1 - c.wg < nA ? 2 * DG : 0), dk = dkk + gk * DG;
#pragma unroll 1
        for (int it = 1 - c.wg; it < 17 - c.wg; it++) {
          float S[64];
          FTA(it * 7 + 0); FTH((it < 3 ? 8 + it * 8 : it * 8 - 88) + 0, it >= 3 && it < 15);
          c.turn_begin();
          FTA(it * 7 + 2); FTH((it < 3 ? 8 + it * 8 : it * 8 - 88) + 1, it >= 3 && it < 15);
          wg_fence();
          issue_qk(S, dq, dk);
          wg_commit();
          const uint32_t dv = dv0 + gv * DG;
          uint32_t relk = c.relb + gk * 8, relv = c.relb + gv * 8;
          gk = it == 6 ? 12 : gv == 12 ? 4 : gv + 2;
          gv = it == 16 ? gk : gk == 12 ? 4 : gk + 2;
          uint32_t fk = sb + SM_BAR + (B_FULL + gk) * 8, fv = sb + SM_BAR + (B_FULL + gv) * 8, park = (c.pf >> gk) & 1, parv = (c.pf >> gv) & 1;
          c.pf ^= (1u << gk) | (1u << gv);
          dq = dk0 + (it + 1 < nA ? 2 * DG : 0); dk = dkk + gk * DG;
          float lo0 = z.l0, lo1 = z.l1;
          const bool first = it == nA || it == 0;
          if (it == nA) {
            if (EARLY_RCP) { lo0 = rcp(quad_sum(lo0)); lo1 = rcp(quad_sum(lo1)); }
            z.m0 = z.m1 = z.l0 = z.l1 = 0.f; z.shifted = 0;
          }
          float s0, s1, d0 = z.m0, d1 = z.m1;
          int pre = z.shifted || (it & 15) == 0;
          float lim = first ? -1.f : SM_LIMIT;
          asm volatile("" : "+r"(relk), "+r"(relv), "+r"(fk), "+r"(fv), "+r"(park), "+r"(parv), "+r"(dq), "+r"(dk), "+r"(pre), "+f"(lim), "+f"(d0), "+f"(d1), "+f"(z.l0), "+f"(z.l1));
          if (it) {
            issue_pv<0>(O, P, dv, it != nA + 1 && it != 1, true);
            issue_pv<1>(O, P, dv, 1, HALFPV ? it + c.wg > 1 : true);
            c.turn_end();
          } else stage_q2(c, O, P, stg);
          FTA(it * 7 + 3); FTH((it < 3 ? 8 + it * 8 : it * 8 - 88) + 2, it >= 3 && it < 15);
          wg_wait<4>();
          reg_fence(S);
          FTA(it * 7 + 4); FTH((it < 3 ? 8 + it * 8 : it * 8 - 88) + 3, it >= 3 && it < 15);
          if (c.tid < 4) asm volatile("mbarrier.arrive.shared::cluster.b64 _, [%0];" ::"r"(relk) : "memory");
#pragma unroll 1
          for (int pass = 0;; pass++) {
            if (pre) {
              if ((it & 15) == 0) mask_diag(S, dmask);
              if (z.shifted) shift_scores(S, d0, d1);
            }
            float tr[ROT];
            exp_quarter<0, 3>(S, P, tr, s0, s1, sb);
            exp_quarter<1, 2>(S, P, tr, s0, s1, sb);
            exp_quarter<2, 1>(S, P, tr, s0, s1, sb);
            exp_quarter<3, 0>(S, P, tr, s0, s1, sb);
            reg_fence(O);
            if (c.tid < (pass || !it ? 0 : 4)) asm volatile("mbarrier.arrive.shared::cluster.b64 _, [%0];" ::"r"(relv) : "memory");
            const bool ok = mbar_test(fk, park) & mbar_test(fv, parv);
            if (!ok) lim = -1.f;
            FTA(it * 7 + 5); FTH((it < 3 ? 8 + it * 8 : it * 8 - 88) + 4, it >= 3 && it < 15);
            if (!__any_sync(0xffffffffu, !(s0 <= lim && s1 <= lim))) break;
            if (pass) break;
            if (it == nA) {
              uint32_t pk[32];
              if (!EARLY_RCP) { lo0 = rcp(quad_sum(lo0)); lo1 = rcp(quad_sum(lo1)); }
              pack_frag_scaled(O, pk, lo0, lo1);
              stsm_frag(pk, stg + 2 * GR);
              c.staged(1);
            }
            if (!ok) { mbar_wait(fk, park); mbar_wait(fv, parv); }
            if (!soft_unsafe(s0, s1, first)) break;
            soft_fix(S, O, z, first, d0, d1);
            pre = 1;
          }
          z.l0 += s0; z.l1 += s1;
          FTA(it * 7 + 6); FTH((it < 3 ? 8 + it * 8 : it * 8 - 88) + 5, it >= 3 && it < 15);
        }
        FTM(rnd * 8 + 6);
        }
        FTH(48, 0);
        load_dd();
        c.turn_begin();
        FTH(49, 0);
        wg_fence();
        issue_pv<0>(O, P, dv0 + 12 * DG, 1, true);
        issue_pv<1>(O, P, dv0 + 12 * DG, 1, !c.wg);
        c.turn_end();
        z.l0 = rcp(quad_sum(z.l0)); z.l1 = rcp(quad_sum(z.l1));
        wg_wait<0>();
        reg_fence(O); reg_fence(P);
        FTH(50, 0);
        c.release(12, 2);
        pack_frag_scaled(O, P, z.l0, z.l1);
        stsm_frag(P, stg);
        c.staged(0);
        FTM(rnd * 8 + 7);
        FTH(51, 0);
      }
      TS(3 + rnd * 3);
    }
    conv_tasks(c, p, (cn + 1 - c.wg) / 2, ((cn - 1) & 1) == c.wg, spare, cch + c.wg * cstep, 2 * cstep, dd0, dkk, warp & 3, lane);
    if (c.wg == 1) c.pf ^= 0x14;
    TS(7);
    if (!spare) {
      const int rt = 2 * grp + rank, ct = idx;
      float acc[64];
      int g0 = P3G + 2, pg = P3G;
      {
        FTO(0);
        c.wait_full(P3G);
        FTO(1);
        const uint32_t a = dk0 + P3G * DG, b = dm0 + (P3G + 1) * DG;
        wg_fence();
        mma_ss_n128_init<1>(acc, a, b);
#pragma unroll
        for (int k = 1; k < 4; k++) mma_ss_n128<1>(acc, a + k * 2, b + k * 128);
        wg_commit();
      }
#pragma unroll 1
      for (int kb = 1; kb < 64; kb++) {
        FTO(kb * 2);
        c.wait_full(g0);
        FTO(kb * 2 + 1);
        const uint32_t a = dk0 + g0 * DG, b = dm0 + (g0 + 1) * DG;
        wg_fence();
#pragma unroll
        for (int k = 0; k < 4; k++) mma_ss_n128<1>(acc, a + k * 2, b + k * 128);
        wg_commit();
        wg_wait<1>();
        c.release(pg, kb <= 59 ? 2 : 0);
        if (kb == 40) FTDUMP();
        pg = g0;
        g0 = g0 == 12 ? (kb == 3 ? 2 : 0) : g0 + 2;
      }
      cluster_arrive();
      c.wait_full(P3X);
      c.wait_full(P3Y);
      const float g0f = __uint_as_float(lds32(sb + SM_GATE + row * 4)), g1f = __uint_as_float(lds32(sb + SM_GATE + row * 4 + 32));
      const uint32_t gp0 = pack_bf16(g0f, g0f), gp1 = pack_bf16(g1f, g1f);
      const float h0 = 1.f - g0f, h1 = 1.f - g1f;
      const int w = warp & 3;
      const uint32_t xa = stg + P3X * GR;
      const uint32_t ya = sb + P3Y * GR + c.wg * 16384 + ((lane >> 4) * 8 + (lane & 7)) * 128 + (((2 * w + ((lane >> 3) & 1)) ^ (lane & 7)) << 4);
      uint32_t xy[32];
#pragma unroll
      for (int jj = 0; jj < 8; jj++) {
        uint32_t x[4], y[4];
        asm volatile("ldmatrix.sync.aligned.m8n8.x4.shared.b16 {%0,%1,%2,%3}, [%4];" : "=r"(x[0]), "=r"(x[1]), "=r"(x[2]), "=r"(x[3]) : "r"((xa ^ ((jj & 3) << 5)) + (jj >> 2) * 16384) : "memory");
        asm volatile("ldmatrix.sync.aligned.m8n8.x4.trans.shared.b16 {%0,%1,%2,%3}, [%4];" : "=r"(y[0]), "=r"(y[1]), "=r"(y[2]), "=r"(y[3]) : "r"(ya + jj * 2048) : "memory");
#pragma unroll
        for (int i = 0; i < 4; i++) xy[4 * jj + i] = hmul2(x[i], y[i]);
      }
      wg_wait<0>();
      reg_fence(acc);
      TS(8);
#pragma unroll
      for (int i = 0; i < 32; i++) {
        const float h = (i & 1) ? h1 : h0;
        xy[i] = hfma2((i & 1) ? gp1 : gp0, xy[i], pack_bf16(acc[2 * i] * h, acc[2 * i + 1] * h));
      }
      stsm_frag(xy, xa);
      fence_async_smem();
      __syncwarp();
      if (lane == 0) {
        const int r0 = c.wg * 64 + w * 16;
        tma2d_store(&p.out, sb + P3X * GR + r0 * 128, ct * 128, rt * 128 + r0);
        tma2d_store(&p.out, sb + (P3X + 1) * GR + r0 * 128, ct * 128 + 64, rt * 128 + r0);
        asm volatile("cp.async.bulk.commit_group;\ncp.async.bulk.wait_group.read 0;" ::: "memory");
      }
    } else { FTDUMP(); cluster_arrive(); }
    if (lane == 0) mbar_arrive(sb + SM_BAR + B_DONE * 8);
    __syncwarp();
    TS(9);
    cluster_wait();
  }
}

typedef CUresult (*EncFn)(CUtensorMap*, CUtensorMapDataType, cuuint32_t, void*, const cuuint64_t*, const cuuint64_t*, const cuuint32_t*,
                          const cuuint32_t*, CUtensorMapInterleave, CUtensorMapSwizzle, CUtensorMapL2promotion, CUtensorMapFloatOOBfill);

void enc2d(EncFn enc, CUtensorMap* tm, const void* base, uint64_t cols, uint64_t rows, uint32_t bc, uint32_t br) {
  cuuint64_t dims[2] = {cols, rows}; cuuint64_t strides[1] = {cols * 2}; cuuint32_t box[2] = {bc, br}; cuuint32_t es[2] = {1, 1};
  enc(tm, CU_TENSOR_MAP_DATA_TYPE_BFLOAT16, 2, const_cast<void*>(base), dims, strides, box, es, CU_TENSOR_MAP_INTERLEAVE_NONE,
      CU_TENSOR_MAP_SWIZZLE_128B, CU_TENSOR_MAP_L2_PROMOTION_L2_256B, CU_TENSOR_MAP_FLOAT_OOB_FILL_NONE);
}
void enc3d(EncFn enc, CUtensorMap* tm, const void* base, uint64_t K, uint64_t N) {
  cuuint64_t dims[3] = {64, K, N / 64}; cuuint64_t strides[2] = {N * 2, 128}; cuuint32_t box[3] = {64, 64, 2}; cuuint32_t es[3] = {1, 1, 1};
  enc(tm, CU_TENSOR_MAP_DATA_TYPE_BFLOAT16, 3, const_cast<void*>(base), dims, strides, box, es, CU_TENSOR_MAP_INTERLEAVE_NONE,
      CU_TENSOR_MAP_SWIZZLE_128B, CU_TENSOR_MAP_L2_PROMOTION_L2_256B, CU_TENSOR_MAP_FLOAT_OOB_FILL_NONE);
}

}

extern "C" void kernel_launch(void* const* d_in, const int* in_sizes, int n_in, void* d_out, int out_size) {
  (void)in_sizes; (void)n_in; (void)out_size;
  typedef const __nv_bfloat16* BP;
  BP xq = (BP)d_in[0], ak = (BP)d_in[1], av = (BP)d_in[2], shk = (BP)d_in[3], ssk = (BP)d_in[4], ssd = (BP)d_in[5];
  BP ckv = (BP)d_in[7], wq = (BP)d_in[8], wuk = (BP)d_in[9], wuv = (BP)d_in[10], wo = (BP)d_in[11], gw = (BP)d_in[12];

  static EncFn enc = nullptr;
  if (!enc) {
    cudaDriverEntryPointQueryResult qr;
    cudaGetDriverEntryPoint("cuTensorMapEncodeTiled", (void**)&enc, cudaEnableDefault, &qr);
    cudaFuncSetAttribute(mega_kernel, cudaFuncAttributeMaxDynamicSharedMemorySize, SMEM_BYTES);
  }
  Params p;
  void* yT = nullptr;
  cudaGetSymbolAddress(&yT, g_yT);
  enc2d(enc, &p.x, xq, DM, SEQ, 64, 128);
  enc2d(enc, &p.c, ckv, DC, SEQ, 64, 128);
  enc3d(enc, &p.wq, wq, DM, NH * HD);
  enc3d(enc, &p.wuk, wuk, DC, NH * HD);
  enc3d(enc, &p.wuv, wuv, DC, NH * HD);
  enc2d(enc, &p.wo, wo, DM, NH * HD, 64, 64);
  enc2d(enc, &p.y, yT, SEQ, DM, 64, 128);
  enc2d(enc, &p.out, d_out, DM, SEQ, 64, 16);
  {
    void* wp = nullptr;
    cudaGetSymbolAddress(&wp, g_w);
    cuuint64_t dims[3] = {WSTRIDE / 2, DM / 2, 2}; cuuint64_t strides[2] = {2 * WSTRIDE, WSTRIDE}; cuuint32_t box[3] = {16, 32, 2}; cuuint32_t es[3] = {1, 1, 1};
    enc(&p.w, CU_TENSOR_MAP_DATA_TYPE_BFLOAT16, 3, wp, dims, strides, box, es, CU_TENSOR_MAP_INTERLEAVE_NONE,
        CU_TENSOR_MAP_SWIZZLE_32B, CU_TENSOR_MAP_L2_PROMOTION_NONE, CU_TENSOR_MAP_FLOAT_OOB_FILL_NONE);
  }
  p.zero = 0;
  for (int i = 0; i < 128; i++) {
    const int tp = i % NSLOT;
    p.pref[i] = tp < 32 ? (tp & 7) * 8 + (tp >> 3) : tp < 60 ? (1 + (tp - 32) % 7) * 8 + 4 + (tp - 32) / 7 : tp < 62 ? tp + 4 : tp - 58;
  }
  p.xp = xq; p.gate_w = gw; p.ak = ak; p.av = av; p.shk = shk; p.ssk = ssk; p.ssd = ssd;

  mega_kernel<<<132, NTHREADS, SMEM_BYTES>>>(p);
}
```

```cpp
#include <cuda_runtime.h>
#include <cuda.h>
#include <cuda_bf16.h>
#include <stdint.h>

namespace {

constexpr int SEQ = 2048, DM = 1024, DC = 512, NH = 32, HD = 128;
constexpr int GR = 16384;
constexpr int NGR = 14;
constexpr int SM_BAR = NGR * GR;
constexpr int SM_GATE = SM_BAR + 512;
constexpr int SM_UST = SM_GATE + 512;
constexpr int SMEM_BYTES = SM_UST + 2048;
constexpr int NTHREADS = 384;
#define SM_LIMIT 1.0995116e12f
#define SM_LOW 9.094947e-13f
constexpr int CN_MAIN = 5, CN_SPARE = 96;
constexpr int P3G = 6, P3X = 10, P3Y = 12;
constexpr int NMAIN = 128;

constexpr int B_FULL = 0, B_FREE = 14, B_SLOT = 16, B_DONE = 17, B_EMPTY = 18, B_EV = 32, V_SLOT = 36;

__device__ __align__(1024) uint8_t g_kv[2 * 16 * 16 * 32768];
__device__ __align__(1024) uint8_t g_cimg[16 * NH * 32768];
__device__ __align__(1024) __nv_bfloat16 g_yT[DM * SEQ];
__device__ __align__(1024) float g_gate[SEQ];
#define CWIDE 0
constexpr int WZ = CWIDE ? 768 : 256, WPL = WZ + 4096, WBYTES = 2 * WPL + 32, WSTRIDE = 2 * WPL + 128;
__device__ __align__(1024) uint8_t g_w[DM * WSTRIDE];
__device__ __align__(32) unsigned g_flags[96 * 8];
constexpr int F_KV = 0, F_CTX = 16, F_U = 48, F_AD = 56, F_Y = 64, F_GATE = 72, F_EXIT = 73;
constexpr int NSLOT = 66;
#define FLAG(i) (&g_flags[(i) * 8])
#define CLAIMP(i) (p.flags + (i) * 8 + 1)

#define TS(slot)
#define TSW(slot)
#define FTX(i, off)
#define FTDUMP()

#define ST_OUT 0
#define QFLUSH 4
#define POL_W EV_NORMAL
#define POL_WO EV_FIRST
#define POL_KV EV_NORMAL
#define POL_C EV_FIRST
#define POL_CTX EV_FIRST
#define HALFPV 1
#define PRE_SLEEP 1500
#define EXPV 1
#define SUMV 0
#define ROT 8
#define EARLY_RCP 1
#define START_PF 1
#define DFOLD 1
#define FINE_MODE 0
#define FINE_RND 1
#define FTA(i) do { if (FINE_MODE == 0) FTX(i, rnd ^ FINE_RND); } while (0)
#define FTG(i) do { if (FINE_MODE == 1) FTX(i, rnd ^ FINE_RND); } while (0)
#define FTM(i) do { if (FINE_MODE == 4) FTX(i, 0); } while (0)
#define FTC(k) do { if (FINE_MODE == 5) FTX((i & 7) * 8 + (k), (i >> 3) ^ FINE_RND); } while (0)
#define FTH(i, off) do { if (FINE_MODE == 6) FTX(i, (c.rnd ^ FINE_RND) | (off)); } while (0)
#define FTO(i) do { if (FINE_MODE == 2) FTX(i, 0); } while (0)

__device__ __forceinline__ uint32_t smem_u32(const void* p) { return (uint32_t)__cvta_generic_to_shared(p); }
__device__ __forceinline__ void mbar_init(uint32_t bar, int cnt) { asm volatile("mbarrier.init.shared::cta.b64 [%0], %1;" ::"r"(bar), "r"(cnt) : "memory"); }
__device__ __forceinline__ void mbar_expect_tx(uint32_t bar, uint32_t bytes) { asm volatile("mbarrier.arrive.expect_tx.shared::cta.b64 _, [%0], %1;" ::"r"(bar), "r"(bytes) : "memory"); }
__device__ __forceinline__ void mbar_arrive(uint32_t bar) { asm volatile("mbarrier.arrive.shared::cta.b64 _, [%0];" ::"r"(bar) : "memory"); }
__device__ __forceinline__ void mbar_arrive_cluster(uint32_t bar, uint32_t cta) {
  asm volatile("{\n.reg .b32 r;\nmapa.shared::cluster.u32 r, %0, %1;\nmbarrier.arrive.shared::cluster.b64 _, [r];\n}\n" ::"r"(bar), "r"(cta) : "memory");
}
__device__ __forceinline__ bool mbar_try(uint32_t bar, uint32_t parity) {
  uint32_t ok;
  asm volatile("{\n.reg .pred p;\nmbarrier.try_wait.parity.shared::cta.b64 p, [%1], %2, 20000;\nselp.u32 %0, 1, 0, p;\n}\n" : "=r"(ok) : "r"(bar), "r"(parity) : "memory");
  return ok;
}
__device__ __forceinline__ bool mbar_test(uint32_t bar, uint32_t parity) {
  uint32_t ok;
  asm volatile("{\n.reg .pred p;\nmbarrier.test_wait.parity.shared::cta.b64 p, [%1], %2;\nselp.u32 %0, 1, 0, p;\n}\n" : "=r"(ok) : "r"(bar), "r"(parity) : "memory");
  return ok;
}
__device__ __forceinline__ void mbar_wait(uint32_t bar, uint32_t parity) {
  asm volatile("{\n.reg .pred p;\nWAIT_LOOP:\nbar.warp.sync -1;\nmbarrier.try_wait.parity.shared::cta.b64 p, [%0], %1;\n@!p bra WAIT_LOOP;\n}\n" ::"r"(bar), "r"(parity) : "memory");
}
__device__ __forceinline__ void mbar_wait1(uint32_t bar, uint32_t parity) {
  asm volatile("{\n.reg .pred p;\nWAIT_LOOP:\nbar.warp.sync -1;\nmbarrier.try_wait.parity.shared::cta.b64 p, [%0], %1, 4000;\n@!p bra WAIT_LOOP;\n}\n" ::"r"(bar), "r"(parity) : "memory");
}
constexpr uint64_t EV_NORMAL = 0x1000000000000000ull, EV_FIRST = 0x12F0000000000000ull;
__device__ __forceinline__ uint32_t ldg_stream(const uint32_t* p) {
  uint32_t r; asm volatile("ld.global.nc.L1::no_allocate.L2::cache_hint.b32 %0, [%1], %2;" : "=r"(r) : "l"(p), "l"(EV_FIRST)); return r;
}
__device__ __forceinline__ void tma2d(uint32_t dst, const CUtensorMap* tm, int c0, int c1, uint32_t bar, uint64_t pol) {
  asm volatile("cp.async.bulk.tensor.2d.shared::cluster.global.mbarrier::complete_tx::bytes.L2::cache_hint [%0], [%1, {%3, %4}], [%2], %5;"
               ::"r"(dst), "l"(tm), "r"(bar), "r"(c0), "r"(c1), "l"(pol) : "memory");
}
__device__ __forceinline__ void tma2d_mc(uint32_t dst, const CUtensorMap* tm, int c0, int c1, uint32_t bar, uint64_t pol) {
  asm volatile("cp.async.bulk.tensor.2d.shared::cluster.global.mbarrier::complete_tx::bytes.multicast::cluster.L2::cache_hint [%0], [%1, {%3, %4}], [%2], %5, %6;"
               ::"r"(dst), "l"(tm), "r"(bar), "r"(c0), "r"(c1), "h"((uint16_t)3), "l"(pol) : "memory");
}
__device__ __forceinline__ void tma3d(uint32_t dst, const CUtensorMap* tm, int c0, int c1, int c2, uint32_t bar, uint64_t pol) {
  asm volatile("cp.async.bulk.tensor.3d.shared::cluster.global.mbarrier::complete_tx::bytes.L2::cache_hint [%0], [%1, {%3, %4, %5}], [%2], %6;"
               ::"r"(dst), "l"(tm), "r"(bar), "r"(c0), "r"(c1), "r"(c2), "l"(pol) : "memory");
}
__device__ __forceinline__ void tma3d_mc(uint32_t dst, const CUtensorMap* tm, int c0, int c1, int c2, uint32_t bar, uint64_t pol) {
  asm volatile("cp.async.bulk.tensor.3d.shared::cluster.global.mbarrier::complete_tx::bytes.multicast::cluster.L2::cache_hint [%0], [%1, {%3, %4, %5}], [%2], %6, %7;"
               ::"r"(dst), "l"(tm), "r"(bar), "r"(c0), "r"(c1), "r"(c2), "h"((uint16_t)3), "l"(pol) : "memory");
}
__device__ __forceinline__ void bulk_g2s(uint32_t dst, const void* src, uint32_t bytes, uint32_t bar, uint64_t pol) {
  asm volatile("cp.async.bulk.shared::cluster.global.mbarrier::complete_tx::bytes.L2::cache_hint [%0], [%1], %2, [%3], %4;"
               ::"r"(dst), "l"(src), "r"(bytes), "r"(bar), "l"(pol) : "memory");
}
__device__ __forceinline__ void tma2d_store(const CUtensorMap* tm, uint32_t src, int c0, int c1) {
  asm volatile("cp.async.bulk.tensor.2d.global.shared::cta.bulk_group [%0, {%2, %3}], [%1];" ::"l"(tm), "r"(src), "r"(c0), "r"(c1) : "memory");
}
__device__ __forceinline__ void prefetch_tm(const CUtensorMap* tm) { asm volatile("prefetch.tensormap [%0];" ::"l"(tm) : "memory"); }
__device__ __forceinline__ void wg_fence() { asm volatile("wgmma.fence.sync.aligned;" ::: "memory"); }
__device__ __forceinline__ void wg_commit() { asm volatile("wgmma.commit_group.sync.aligned;" ::: "memory"); }
template <int N> __device__ __forceinline__ void wg_wait() { asm volatile("wgmma.wait_group.sync.aligned %0;" ::"n"(N) : "memory"); }
__device__ __forceinline__ void bar_sync(int id, int n) { asm volatile("bar.sync %0, %1;" ::"r"(id), "r"(n) : "memory"); }
__device__ __forceinline__ void bar_arrive(int id, int n) { asm volatile("bar.arrive %0, %1;" ::"r"(id), "r"(n) : "memory"); }
__device__ __forceinline__ void fence_async_smem() { asm volatile("fence.proxy.async.shared::cta;" ::: "memory"); }
__device__ __forceinline__ void fence_async_all() { asm volatile("fence.proxy.async.global;" ::: "memory"); }
__device__ __forceinline__ uint32_t pack_bf16(float lo, float hi) { uint32_t r; asm("cvt.rn.bf16x2.f32 %0, %1, %2;" : "=r"(r) : "f"(hi), "f"(lo)); return r; }
__device__ __forceinline__ float ex2(float x) { float r; asm("ex2.approx.ftz.f32 %0, %1;" : "=f"(r) : "f"(x)); return r; }
__device__ __forceinline__ float rcp(float x) { float r; asm("rcp.approx.ftz.f32 %0, %1;" : "=f"(r) : "f"(x)); return r; }
__device__ __forceinline__ void flag_wait(const unsigned* f, unsigned target) {
  unsigned v;
  do { asm volatile("ld.acquire.gpu.global.u32 %0, [%1];" : "=r"(v) : "l"(f) : "memory"); } while (__any_sync(0xffffffffu, v < target));
}
__device__ __forceinline__ bool elect() {
  uint32_t r;
  asm volatile("{\n.reg .pred p;\nelect.sync _|p, -1;\nselp.u32 %0, 1, 0, p;\n}\n" : "=r"(r));
  return r;
}
__device__ __forceinline__ uint32_t sel(bool c, uint32_t a, uint32_t b) {
  uint32_t r; asm("{\n.reg .pred p;\nsetp.ne.b32 p, %3, 0;\nselp.b32 %0, %1, %2, p;\n}\n" : "=r"(r) : "r"(a), "r"(b), "r"((int)c)); return r;
}
__device__ __forceinline__ void fence_release() { asm volatile("fence.release.gpu;" ::: "memory"); }
__device__ __forceinline__ void flag_add(unsigned* f) { asm volatile("red.relaxed.gpu.global.inc.u32 [%0], 0x7fffffff;" ::"l"(f) : "memory"); }
__device__ __forceinline__ void cluster_arrive() { asm volatile("barrier.cluster.arrive.relaxed.aligned;" ::: "memory"); }
__device__ __forceinline__ void cluster_wait() { asm volatile("barrier.cluster.wait.aligned;" ::: "memory"); }
__device__ __forceinline__ uint32_t hmul2(uint32_t a, uint32_t b) { uint32_t r; asm("mul.rn.bf16x2 %0, %1, %2;" : "=r"(r) : "r"(a), "r"(b)); return r; }
__device__ __forceinline__ uint32_t hadd2(uint32_t a, uint32_t b) { uint32_t r; asm("add.rn.bf16x2 %0, %1, %2;" : "=r"(r) : "r"(a), "r"(b)); return r; }
__device__ __forceinline__ uint32_t hfma2(uint32_t a, uint32_t b, uint32_t c) { uint32_t r; asm("fma.rn.bf16x2 %0, %1, %2, %3;" : "=r"(r) : "r"(a), "r"(b), "r"(c)); return r; }
__device__ __forceinline__ uint32_t lds32(uint32_t a) { uint32_t r; asm volatile("ld.shared.b32 %0, [%1];" : "=r"(r) : "r"(a) : "memory"); return r; }
__device__ __forceinline__ uint4 lds128(uint32_t a) { uint4 r; asm volatile("ld.shared.v4.b32 {%0,%1,%2,%3}, [%4];" : "=r"(r.x), "=r"(r.y), "=r"(r.z), "=r"(r.w) : "r"(a) : "memory"); return r; }
__device__ __forceinline__ uint32_t desc_k(uint32_t addr) { return ((addr & 0x3FFFF) >> 4) | (1u << 16); }
template <int LBO> __device__ __forceinline__ uint32_t desc_mn(uint32_t addr) { return ((addr & 0x3FFFF) >> 4) | ((uint32_t)(LBO >> 4) << 16); }
#define DHI "0x40000040"

#define R8(d, o) "+f"(d[o]), "+f"(d[o + 1]), "+f"(d[o + 2]), "+f"(d[o + 3]), "+f"(d[o + 4]), "+f"(d[o + 5]), "+f"(d[o + 6]), "+f"(d[o + 7])
#define R32(d, o) R8(d, o), R8(d, o + 8), R8(d, o + 16), R8(d, o + 24)
#define R64(d, o) R32(d, o), R32(d, o + 32)
#define L64 "%0,%1,%2,%3,%4,%5,%6,%7,%8,%9,%10,%11,%12,%13,%14,%15,%16,%17,%18,%19,%20,%21,%22,%23,%24,%25,%26,%27,%28,%29,%30,%31," \
            "%32,%33,%34,%35,%36,%37,%38,%39,%40,%41,%42,%43,%44,%45,%46,%47,%48,%49,%50,%51,%52,%53,%54,%55,%56,%57,%58,%59,%60,%61,%62,%63"
#define L128 L64 ",%64,%65,%66,%67,%68,%69,%70,%71,%72,%73,%74,%75,%76,%77,%78,%79,%80,%81,%82,%83,%84,%85,%86,%87,%88,%89,%90,%91,%92,%93,%94,%95," \
            "%96,%97,%98,%99,%100,%101,%102,%103,%104,%105,%106,%107,%108,%109,%110,%111,%112,%113,%114,%115,%116,%117,%118,%119,%120,%121,%122,%123,%124,%125,%126,%127"

template <int TB> __device__ __forceinline__ void mma_ss_n128(float (&d)[64], uint32_t da, uint32_t db) {
  asm volatile("{\n.reg .b64 da, db;\nmov.b64 da, {%64, " DHI "};\nmov.b64 db, {%65, " DHI "};\n"
               "wgmma.mma_async.sync.aligned.m64n128k16.f32.bf16.bf16 {" L64 "}, da, db, 1, 1, 1, 0, %66;\n}\n"
               : R64(d, 0) : "r"(da), "r"(db), "n"(TB));
}
template <int TB> __device__ __forceinline__ void mma_rs_n128(float (&d)[64], uint32_t a0, uint32_t a1, uint32_t a2, uint32_t a3, uint32_t db, int sd) {
  asm volatile("{\n.reg .pred p;\n.reg .b64 db;\nsetp.ne.b32 p, %69, 0;\nmov.b64 db, {%68, " DHI "};\n"
               "wgmma.mma_async.sync.aligned.m64n128k16.f32.bf16.bf16 {" L64 "}, {%64,%65,%66,%67}, db, p, 1, 1, %70;\n}\n"
               : R64(d, 0) : "r"(a0), "r"(a1), "r"(a2), "r"(a3), "r"(db), "r"(sd), "n"(TB));
}
template <int TB> __device__ __forceinline__ void mma_ss_n256(float (&d)[128], uint32_t da, uint32_t db) {
  asm volatile("{\n.reg .b64 da, db;\nmov.b64 da, {%128, " DHI "};\nmov.b64 db, {%129, " DHI "};\n"
               "wgmma.mma_async.sync.aligned.m64n256k16.f32.bf16.bf16 {" L128 "}, da, db, 1, 1, 1, 0, %130;\n}\n"
               : R64(d, 0), R64(d, 64) : "r"(da), "r"(db), "n"(TB));
}
#define W8(d, o) "=f"(d[o]), "=f"(d[o + 1]), "=f"(d[o + 2]), "=f"(d[o + 3]), "=f"(d[o + 4]), "=f"(d[o + 5]), "=f"(d[o + 6]), "=f"(d[o + 7])
#define W32(d, o) W8(d, o), W8(d, o + 8), W8(d, o + 16), W8(d, o + 24)
#define W64(d, o) W32(d, o), W32(d, o + 32)
template <int TB> __device__ __forceinline__ void mma_ss_n128_init(float (&d)[64], uint32_t da, uint32_t db) {
  asm volatile("{\n.reg .b64 da, db;\nmov.b64 da, {%64, " DHI "};\nmov.b64 db, {%65, " DHI "};\n"
               "wgmma.mma_async.sync.aligned.m64n128k16.f32.bf16.bf16 {" L64 "}, da, db, 0, 1, 1, 0, %66;\n}\n"
               : W64(d, 0) : "r"(da), "r"(db), "n"(TB));
}
template <int TB> __device__ __forceinline__ void mma_ss_n256_init(float (&d)[128], uint32_t da, uint32_t db) {
  asm volatile("{\n.reg .b64 da, db;\nmov.b64 da, {%128, " DHI "};\nmov.b64 db, {%129, " DHI "};\n"
               "wgmma.mma_async.sync.aligned.m64n256k16.f32.bf16.bf16 {" L128 "}, da, db, 0, 1, 1, 0, %130;\n}\n"
               : W64(d, 0), W64(d, 64) : "r"(da), "r"(db), "n"(TB));
}
#define L32 "%0,%1,%2,%3,%4,%5,%6,%7,%8,%9,%10,%11,%12,%13,%14,%15,%16,%17,%18,%19,%20,%21,%22,%23,%24,%25,%26,%27,%28,%29,%30,%31"
__device__ __forceinline__ void mma_ss_n64(float (&d)[32], uint32_t da, uint32_t db) {
  asm volatile("{\n.reg .b64 da, db;\nmov.b64 da, {%32, " DHI "};\nmov.b64 db, {%33, " DHI "};\n"
               "wgmma.mma_async.sync.aligned.m64n64k16.f32.bf16.bf16 {" L32 "}, da, db, 1, 1, 1, 0, 0;\n}\n"
               : R32(d, 0) : "r"(da), "r"(db));
}
__device__ __forceinline__ void mma_ss_n64_init(float (&d)[32], uint32_t da, uint32_t db) {
  asm volatile("{\n.reg .b64 da, db;\nmov.b64 da, {%32, " DHI "};\nmov.b64 db, {%33, " DHI "};\n"
               "wgmma.mma_async.sync.aligned.m64n64k16.f32.bf16.bf16 {" L32 "}, da, db, 0, 1, 1, 0, 0;\n}\n"
               : W32(d, 0) : "r"(da), "r"(db));
}
#define L16 "%0,%1,%2,%3,%4,%5,%6,%7,%8,%9,%10,%11,%12,%13,%14,%15"
template <int O, bool INIT> __device__ __forceinline__ void mma_rs_n32(float (&d)[128], uint32_t a0, uint32_t a1, uint32_t a2, uint32_t a3, uint32_t db) {
  if (INIT) asm volatile("{\n.reg .b64 db;\nmov.b64 db, {%20, 0x00000008};\n"
               "wgmma.mma_async.sync.aligned.m64n32k16.f32.bf16.bf16 {" L16 "}, {%16,%17,%18,%19}, db, 0, 1, 1, 0;\n}\n"
               : W8(d, O), W8(d, O + 8) : "r"(a0), "r"(a1), "r"(a2), "r"(a3), "r"(db));
  else asm volatile("{\n.reg .b64 db;\nmov.b64 db, {%20, 0x00000008};\n"
               "wgmma.mma_async.sync.aligned.m64n32k16.f32.bf16.bf16 {" L16 "}, {%16,%17,%18,%19}, db, 1, 1, 1, 0;\n}\n"
               : R8(d, O), R8(d, O + 8) : "r"(a0), "r"(a1), "r"(a2), "r"(a3), "r"(db));
}
template <int O, bool INIT> __device__ __forceinline__ void mma_rs_n64(float (&d)[128], uint32_t a0, uint32_t a1, uint32_t a2, uint32_t a3, uint32_t db) {
  if (INIT) asm volatile("{\n.reg .b64 db;\nmov.b64 db, {%36, 0x00000008};\n"
               "wgmma.mma_async.sync.aligned.m64n64k16.f32.bf16.bf16 {" L32 "}, {%32,%33,%34,%35}, db, 0, 1, 1, 0;\n}\n"
               : W32(d, O) : "r"(a0), "r"(a1), "r"(a2), "r"(a3), "r"(db));
  else asm volatile("{\n.reg .b64 db;\nmov.b64 db, {%36, 0x00000008};\n"
               "wgmma.mma_async.sync.aligned.m64n64k16.f32.bf16.bf16 {" L32 "}, {%32,%33,%34,%35}, db, 1, 1, 1, 0;\n}\n"
               : R32(d, O) : "r"(a0), "r"(a1), "r"(a2), "r"(a3), "r"(db));
}
template <int S, int J> __device__ __forceinline__ void conv_step(float (&d)[128], const uint32_t (&a)[64], uint32_t db) {
  if constexpr (J >= 0 && J >= (S >> 1)) {
    if constexpr (J >= 8 - 2 * CWIDE) {
      mma_rs_n64<16 * (J - 1), S == 0>(d, a[4 * S], a[4 * S + 1], a[4 * S + 2], a[4 * S + 3], db + (uint32_t)((2 * (J - 1) - S) * 16));
      conv_step<S, J - 2>(d, a, db);
    } else {
      mma_rs_n32<16 * J, S == 0>(d, a[4 * S], a[4 * S + 1], a[4 * S + 2], a[4 * S + 3], db + (uint32_t)((2 * J - S) * 16));
      conv_step<S, J - 1>(d, a, db);
    }
  }
}
__device__ __forceinline__ void mma_ss_n8(float (&d)[4], uint32_t da, uint32_t db) {
  asm volatile("{\n.reg .b64 da, db;\nmov.b64 da, {%4, " DHI "};\nmov.b64 db, {%5, 0x00000008};\n"
               "wgmma.mma_async.sync.aligned.m64n8k16.f32.bf16.bf16 {%0,%1,%2,%3}, da, db, 1, 1, 1, 0, 0;\n}\n"
               : "+f"(d[0]), "+f"(d[1]), "+f"(d[2]), "+f"(d[3]) : "r"(da), "r"(db));
}
template <int N> __device__ __forceinline__ void reg_fence(float (&d)[N]) {
#pragma unroll
  for (int i = 0; i < N; i++) asm volatile("" : "+f"(d[i])::"memory");
}
template <int N> __device__ __forceinline__ void reg_fence(uint32_t (&d)[N]) {
#pragma unroll
  for (int i = 0; i < N; i++) asm volatile("" : "+r"(d[i])::"memory");
}

struct __align__(64) Params {
  CUtensorMap x, c, wq, wuk, wuv, wo, y, out, w;
  const __nv_bfloat16* xp;
  const __nv_bfloat16* gate_w;
  const __nv_bfloat16 *ak, *av, *shk, *ssk, *ssd;
  const __nv_bfloat16* first[3];
  unsigned* flags;
  int zero;
  uint8_t pref[128];
};

template <int O, int N, int M> __device__ __forceinline__ void pack_frag(const float (&acc)[N], uint32_t (&pk)[M]) {
#pragma unroll
  for (int i = 0; i < 32; i++) pk[i] = pack_bf16(acc[O + 2 * i], acc[O + 2 * i + 1]);
}
template <int N> __device__ __forceinline__ void pack_frag_scaled(const float (&acc)[N], uint32_t (&pk)[32], float s0, float s1) {
#pragma unroll
  for (int i = 0; i < 32; i++) { const float s = (i & 1) ? s1 : s0; pk[i] = pack_bf16(acc[2 * i] * s, acc[2 * i + 1] * s); }
}
template <int J0 = 0, int J1 = 8, int M> __device__ __forceinline__ void stsm_frag(const uint32_t (&pk)[M], uint32_t a) {
#pragma unroll
  for (int jj = J0; jj < J1; jj++)
    asm volatile("stmatrix.sync.aligned.m8n8.x4.shared.b16 [%0], {%1,%2,%3,%4};" ::"r"((a ^ ((jj & 3) << 5)) + (jj >> 2) * 16384),
                 "r"(pk[4 * jj]), "r"(pk[4 * jj + 1]), "r"(pk[4 * jj + 2]), "r"(pk[4 * jj + 3]) : "memory");
}

struct Cons {
  uint32_t sb;
  uint32_t pf;
  int wg, tid;
  __device__ __forceinline__ void wait_full(int g) { mbar_wait(sb + SM_BAR + (B_FULL + g) * 8, (pf >> g) & 1); pf ^= 1u << g; }
  uint32_t relb;
  __device__ __forceinline__ void release(int g, int n) {
    if (tid < 2 * n) asm volatile("mbarrier.arrive.shared::cluster.b64 _, [%0];" ::"r"(relb + g * 8) : "memory");
  }
  __device__ __forceinline__ void turn_begin() { bar_sync(1 + wg, 256); }
  __device__ __forceinline__ void turn_end() { bar_arrive(2 - wg, 256); }
  __device__ __forceinline__ void staged(int e) { __syncwarp(); if ((tid & 31) == 0) mbar_arrive(sb + SM_BAR + (B_EV + 2 * e + wg) * 8); }
  int zero;
  int rnd;
  uint32_t pfree;
  __device__ __forceinline__ void wait_stage_free() { mbar_wait(sb + SM_BAR + (B_FREE + wg) * 8, pfree); pfree ^= 1; }
  __device__ __forceinline__ bool try_full(int g) { return mbar_test(sb + SM_BAR + (B_FULL + g) * 8, (pf >> g) & 1); }
};

constexpr float SM_C = 0.08838834764831845f * 1.4426950408889634f;
struct SoftState { float m0, m1, l0, l1; int shifted; };
__device__ __forceinline__ void ex2_rot(float& t, float s, uint32_t never_zero) {
  asm("{\n.reg .pred p;\nsetp.ne.u32 p, %2, 0;\n@p ex2.approx.ftz.f32 %0, %1;\n}\n" : "+f"(t) : "f"(s), "r"(never_zero));
}
__device__ __forceinline__ void pin(float a, uint32_t never_zero) {
  asm volatile("{\n.reg .pred p;\nsetp.eq.u32 p, %1, 0;\n@p st.shared.f32 [%1], %0;\n}\n" ::"f"(a), "r"(never_zero) : "memory");
}
template <int O, int N> __device__ __forceinline__ void reg_fence_part(uint32_t (&d)[32]) {
#pragma unroll
  for (int i = O; i < O + N; i++) asm volatile("" : "+r"(d[i])::"memory");
}
template <int Q, int W, int N> __device__ __forceinline__ void exp_quarter(const float (&S)[N], uint32_t (&P)[32], float (&t)[ROT], float& s0, float& s1, uint32_t nz) {
#pragma unroll
  for (int i = 8 * Q; i < 8 * Q + 8; i++) {
    float& a = t[(2 * i) % ROT];
    float& b = t[(2 * i + 1) % ROT];
    if (2 * i < ROT) { a = ex2(S[2 * i]); b = ex2(S[2 * i + 1]); }
    else { ex2_rot(a, S[2 * i], nz); ex2_rot(b, S[2 * i + 1], nz); }
    if (i < 2) { if (i) s1 = a + b; else s0 = a + b; }
    else if (SUMV == 0) { if (i & 1) { s1 += a; s1 += b; } else { s0 += a; s0 += b; } }
    else { if (i & 1) s1 += a + b; else s0 += a + b; }
    if (i == 8 * Q) { pin(EXPV == 1 && Q ? s1 : s0, nz); wg_wait<W>(); reg_fence_part<8 * Q, 8>(P); }
    P[i] = pack_bf16(a, b);
  }
}
template <int N> __device__ __forceinline__ void shift_scores(float (&S)[N], float d0, float d1) {
#pragma unroll
  for (int i = 0; i < N; i++) S[i] -= (i & 2) ? d1 : d0;
}
__device__ __forceinline__ bool soft_high(float s0, float s1, float lim = SM_LIMIT) { return s0 > lim || s1 > lim; }
__device__ __forceinline__ bool soft_unsafe(float s0, float s1, bool first) {
  uint32_t b0 = __ballot_sync(0xffffffffu, s0 >= SM_LOW), b1 = __ballot_sync(0xffffffffu, s1 >= SM_LOW);
  b0 |= b0 >> 1; b0 |= b0 >> 2; b1 |= b1 >> 1; b1 |= b1 >> 2;
  return __any_sync(0xffffffffu, soft_high(s0, s1)) || (first && (b0 & b1 & 0x11111111u) != 0x11111111u);
}
template <int N> __device__ __forceinline__ void soft_fix(const float (&S)[N], float (&O)[64], SoftState& z, bool first, float& d0, float& d1) {
  d0 = d1 = first ? -INFINITY : 0.f;
#pragma unroll
  for (int j = 0; j < N / 4; j++) { d0 = fmaxf(d0, fmaxf(S[4 * j], S[4 * j + 1])); d1 = fmaxf(d1, fmaxf(S[4 * j + 2], S[4 * j + 3])); }
  d0 = fmaxf(d0, __shfl_xor_sync(0xffffffffu, d0, 1)); d1 = fmaxf(d1, __shfl_xor_sync(0xffffffffu, d1, 1));
  d0 = fmaxf(d0, __shfl_xor_sync(0xffffffffu, d0, 2)); d1 = fmaxf(d1, __shfl_xor_sync(0xffffffffu, d1, 2));
  const float sc0 = ex2(-fmaxf(d0, 0.f)), sc1 = ex2(-fmaxf(d1, 0.f));
  z.m0 += d0; z.m1 += d1; z.l0 *= sc0; z.l1 *= sc1; z.shifted = 1;
#pragma unroll
  for (int j = 0; j < 16; j++) { O[4 * j] *= sc0; O[4 * j + 1] *= sc0; O[4 * j + 2] *= sc1; O[4 * j + 3] *= sc1; }
}
template <int M> __device__ __forceinline__ void pin32(const uint32_t (&v)[M], uint32_t never_zero) {
#pragma unroll
  for (int i = 0; i < 32; i += 4)
    asm volatile("{\n.reg .pred p;\nsetp.eq.u32 p, %4, 0;\n@p st.shared.v4.b32 [%4], {%0,%1,%2,%3};\n}\n" ::"r"(v[i]), "r"(v[i + 1]), "r"(v[i + 2]), "r"(v[i + 3]), "r"(never_zero) : "memory");
}
template <int N> __device__ __forceinline__ void mask_diag(float (&S)[N], float nd) {
  asm volatile("" : "+f"(nd));
#pragma unroll
  for (int i = 0; i < 32; i++) {
    const float beyond = __saturatef(nd + (float)(8 * (i >> 2) + (i & 1) - 4 * (i & 2)));
    S[N - 32 + i] = fmaf(beyond, -3.0e38f, S[N - 32 + i]);
  }
}
__device__ __forceinline__ float quad_sum(float v) {
  v += __shfl_xor_sync(0xffffffffu, v, 1);
  v += __shfl_xor_sync(0xffffffffu, v, 2);
  return v;
}
__device__ __forceinline__ void issue_qk(float (&S)[64], uint32_t dq, uint32_t dk) {
  mma_ss_n128_init<0>(S, dq, dk);
#pragma unroll
  for (int s = 1; s < 8; s++) mma_ss_n128<0>(S, dq + (s >> 2) * 1024 + (s & 3) * 2, dk + (s >> 2) * 1024 + (s & 3) * 2);
}
__device__ __forceinline__ void issue_qk(float (&S)[32], uint32_t dq, uint32_t dk) {
  mma_ss_n64_init(S, dq, dk);
#pragma unroll
  for (int s = 1; s < 8; s++) mma_ss_n64(S, dq + (s >> 2) * 1024 + (s & 3) * 2, dk + (s >> 2) * 1024 + (s & 3) * 2);
}
template <int H> __device__ __forceinline__ void issue_pv(float (&O)[64], const uint32_t (&P)[32], uint32_t dv, int acc, bool on) {
  if (on) {
#pragma unroll
    for (int s = 4 * H; s < 4 * H + 4; s++) {
      mma_rs_n128<1>(O, P[4 * s], P[4 * s + 1], P[4 * s + 2], P[4 * s + 3], dv + s * 128, s != 0 ? 1 : acc);
      if (s & 1) wg_commit();
    }
  } else { wg_commit(); wg_commit(); }
}
constexpr uint32_t DG = GR >> 4;
__device__ __forceinline__ void stage_q2(Cons& c, const float (&O)[64], uint32_t (&P)[32], uint32_t stg) {
  wg_commit(); wg_commit(); wg_commit(); wg_commit();
  c.turn_end();
  pack_frag<0>(O, P);
  stsm_frag(P, stg);
  fence_async_smem();
}
__device__ __forceinline__ void attn_half(Cons& c, float (&O)[64], uint32_t (&P)[32], SoftState& z, uint32_t dk0, uint32_t dkk, uint32_t dv0, float dmask, int last) {
  float S[32];
  FTH(8 + last * 32, 0);
  c.turn_begin();
  FTH(9 + last * 32, 0);
  wg_fence();
  issue_qk(S, dk0 + (last ? 0 : 2 * DG), dkk + (last ? 8 : 4) * DG);
  wg_commit();
  issue_pv<0>(O, P, dv0 + 10 * DG, 1, last);
  issue_pv<1>(O, P, dv0 + 10 * DG, 1, last);
  c.turn_end();
  c.wait_full(last ? 12 : 6);
  FTH(10 + last * 32, 0);
  wg_wait<4>();
  reg_fence(S);
  FTH(11 + last * 32, 0);
  c.release(last ? 8 : 4, 2);
  mask_diag(S, dmask);
  float s0, s1, d0 = z.m0, d1 = z.m1;
#pragma unroll 1
  for (int pass = 0;; pass++) {
    if (z.shifted) shift_scores(S, d0, d1);
    float tr[ROT];
    exp_quarter<0, 3>(S, P, tr, s0, s1, c.sb);
    exp_quarter<1, 2>(S, P, tr, s0, s1, c.sb);
    pin(s1, c.sb); wg_wait<0>(); reg_fence_part<16, 16>(P); reg_fence(O);
    if (!soft_unsafe(s0, s1, !last) || pass) break;
    soft_fix(S, O, z, !last, d0, d1);
  }
  FTH(12 + last * 32, 0);
  z.l0 += s0; z.l1 += s1;
  c.release(10, last ? 2 : 0);
  if (!last) c.wait_full(8);
  FTH(13 + last * 32, 0);
}

template <int V> struct IC { static constexpr int value = V; };
__device__ __forceinline__ int conv_next(int g, bool spare) { return g >= NGR - 2 ? g - (NGR - 4) : !spare && g == 4 ? 1 : g + 2; }
__device__ __forceinline__ void conv_final(uint32_t rb, uint32_t yb, const uint4& u, uint32_t dd, bool on) {
  const uint4 q0 = lds128(rb), q1 = lds128(rb + 4096), q2 = lds128(rb + 8192), q3 = lds128(rb + 12288);
  auto fin = [&](uint32_t x0, uint32_t x1, uint32_t x2, uint32_t x3, uint32_t uu) {
    if (DFOLD) return hadd2(hadd2(x0, x1), hadd2(x2, x3));
    return hfma2(dd, __byte_perm(uu, uu, 0x1032), hadd2(hadd2(x0, x1), hadd2(x2, x3)));
  };
  asm volatile("{\n.reg .pred p;\nsetp.ne.b32 p, %5, 0;\n@p st.shared.v4.b32 [%0], {%1,%2,%3,%4};\n}\n" ::"r"(yb), "r"(fin(q0.x, q1.x, q2.x, q3.x, u.w)),
               "r"(fin(q0.y, q1.y, q2.y, q3.y, u.z)), "r"(fin(q0.z, q1.z, q2.z, q3.z, u.y)), "r"(fin(q0.w, q1.w, q2.w, q3.w, u.x)), "r"((int)on) : "memory");
}
__device__ __forceinline__ void conv_tasks(Cons& c, const Params& p, int ntask, bool last, bool spare, int ch, int chstep, uint32_t dd, uint32_t dkk, int w, int lane) {
  const uint32_t sb = c.sb;
  int g = 2 + c.wg;
  uint4 u0 = make_uint4(0, 0, 0, 0), u1 = u0;
  uint32_t rb = sb + g * GR;
  const uint32_t yb = sb + c.wg * 8192 + c.tid * 16;
  c.wait_full(g);
#pragma unroll 1
  for (int i = 0; i < ntask; i++) {
    const uint32_t base = sb + g * GR;
    FTC(0);
    uint32_t a[64];
    const uint32_t hb = base + WBYTES - 28 + (8 * w + (lane >> 2) + (lane & 3)) * 4;
    auto lda = [&](int s) {
      a[4 * s] = lds32(hb + s * 256); a[4 * s + 1] = lds32(hb + s * 256 + 128);
      a[4 * s + 2] = lds32(hb + s * 256 + 16); a[4 * s + 3] = lds32(hb + s * 256 + 144);
    };
    lda(0); lda(15); lda(1); lda(14);
    if (DFOLD) {
      const int gt = 8 * w + (lane >> 2) + (lane & 3);
      a[0] = hadd2(a[0], gt == 7 ? dd : 0u); a[2] = hadd2(a[2], gt == 3 ? dd : 0u);
    }
    float acc[128];
    const uint32_t db = dkk + ((WPL / 16 - 1) << 16) + g * DG + WZ / 16;
    FTC(2);
    c.turn_begin();
    FTC(3);
    auto pair = [&](auto kc) {
      constexpr int k = decltype(kc)::value;
      if (k < 7) wg_fence();
      if (k == 7 && !(last && i == ntask - 1)) c.turn_end();
      conv_step<k, 7>(acc, a, db);
      conv_step<15 - k, 7>(acc, a, db);
      if (k < 6) { lda(k + 2); lda(13 - k); }
      if (k == 0) conv_final(rb, yb, u0, dd, i > 0);
      if (k == 1) {
        conv_final(rb + 2048, yb + 2048, u1, dd, i > 0);
        __syncwarp();
        if (lane == 0 && i > 0) mbar_arrive(sb + SM_BAR + (B_EV + c.wg) * 8);
      }
      if (DFOLD) { if (k == 6) dd = __bfloat16_as_ushort(p.ssd[(ch + chstep) & (DM - 1)]); }
      else if (k == 6) {
        const uint32_t ub = base + WZ + 16 + (c.tid >> 1) * 32 + ((c.tid & 1) ^ 1) * WPL;
        u0 = lds128(ub); u1 = lds128(ub + 2048);
        dd = __bfloat16_as_ushort(p.ssd[ch]) * 0x10001u;
      }
    };
    pair(IC<0>()); pair(IC<1>()); pair(IC<2>()); pair(IC<3>()); pair(IC<4>()); pair(IC<5>()); pair(IC<6>()); pair(IC<7>());
    wg_commit();
    FTC(4);
    g = conv_next(g, spare);
    ch += chstep;
    rb = base + c.tid * 16;
    wg_wait<0>();
    reg_fence(acc);
    reg_fence(a);
    bar_sync(3 + c.wg, 128);
    FTC(5);
    const int tw = (lane & 3) + w;
    const uint32_t xb = base + w * 4096 + tw * 32 + (lane >> 2) * 4;
#pragma unroll
    for (int j = 0; j < 32; j++) {
      float v0 = acc[4 * j], v1 = acc[4 * j + 1];
      if (j > 0) { v0 += acc[j > 0 ? 4 * j - 2 : 0]; v1 += acc[j > 0 ? 4 * j - 1 : 0]; }
      uint32_t v = pack_bf16(v0, v1), ad = xb + j * 128;
      if (j == 31 && tw >= 4) { v = 0; ad -= 4096; }
      asm volatile("st.shared.b32 [%0], %1;" ::"r"(ad), "r"(v) : "memory");
    }
    c.wait_stage_free();
    if (i + 1 < ntask) c.wait_full(g);
    bar_sync(3 + c.wg, 128);
    FTC(6);
  }
  conv_final(rb, yb, u0, dd, true);
  conv_final(rb + 2048, yb + 2048, u1, dd, true);
  c.staged(0);
}

__global__ void __cluster_dims__(2, 1, 1) __launch_bounds__(NTHREADS, 1) mega_kernel(const __grid_constant__ Params p) {
  extern __shared__ __align__(1024) uint8_t smem_raw[];
  const uint32_t sb = smem_u32(smem_raw);
  const int wgi = __shfl_sync(0xffffffffu, threadIdx.x >> 7, 0);
  const int warp = __shfl_sync(0xffffffffu, threadIdx.x >> 5, 0);
  const uint32_t rank = blockIdx.x & 1;
  int slot;
  {
    uint32_t smid; asm volatile("mov.u32 %0, %smid;" : "=r"(smid));
    slot = p.pref[(smid >> 1) & 127];
  }
  const int pref = slot;
  unsigned taken = 0;
  auto claim = [&](bool on) {
    asm volatile("{\n.reg .pred p;\nsetp.ne.b32 p, %2, 0;\n@p atom.relaxed.gpu.global.exch.b32 %0, [%1], 1;\n}\n" : "+r"(taken) : "l"(CLAIMP(slot)), "r"((int)on) : "memory");
  };
  claim(threadIdx.x == (rank ? NTHREADS : 96));
  if (elect()) {
    if (warp == 2) { prefetch_tm(&p.c); prefetch_tm(rank ? &p.wuv : &p.wuk); }
#pragma unroll
    for (int k = 0; k < 3; k++) mbar_init(sb + SM_BAR + (warp * 3 + k) * 8, k == 2 && warp == B_DONE / 3 ? 11 : warp < B_EMPTY / 3 ? 1 : 4);
    if (warp == B_SLOT / 3) mbar_expect_tx(sb + SM_BAR + B_SLOT * 8, 8);
    asm volatile("fence.mbarrier_init.release.cluster;" ::: "memory");
  }
  if (wgi) {
    const unsigned j = threadIdx.x & 127;
    const unsigned o1 = ((2 * (pref & 7) + rank) * 128 + j) * DC, o2 = (j & 63) * (NH * HD) + (j & 64) + (pref >> 3) * 256;
    asm volatile("prefetch.global.L2 [%0];" ::"l"(p.first[wgi == 1 ? 2 : rank] + sel(wgi == 1, o1, o2)));
  }
  __syncwarp();
  cluster_arrive();
  if (warp == 3) {
#pragma unroll 1
    for (int n = 1; n < NSLOT && __any_sync(0xffffffffu, taken); n++) { slot = slot == NSLOT - 1 ? 0 : slot + 1; claim(taken); }
  }
  cluster_wait();
  if (threadIdx.x == 96) {
#pragma unroll
    for (int r = 0; r < 2; r++)
      asm volatile("{\n.reg .b32 a, b;\nmapa.shared::cluster.u32 a, %0, %1;\nadd.u32 b, a, %3;\nst.async.shared::cluster.mbarrier::complete_tx::bytes.u32 [b], %2, [a];\n}\n"
                   ::"r"(sb + SM_BAR + B_SLOT * 8), "r"(r), "r"(slot | pref << 8), "r"((V_SLOT - B_SLOT) * 8 + rank * 4) : "memory");
  }
  if (warp == 0) {
    if (elect()) {
#pragma unroll 1
      for (int kk = 0; kk < 4; kk++) {
        const int g0 = 2 + 3 * kk;
        const uint32_t fb = sb + SM_BAR + (B_FULL + g0) * 8;
        mbar_expect_tx(fb, 3 * GR);
        tma2d(sb + g0 * GR, &p.c, kk * 64, (2 * (pref & 7) + rank) * 128, fb, EV_NORMAL);
        tma3d_mc(sb + (g0 + 1 + rank) * GR, rank ? &p.wuv : &p.wuk, 0, kk * 64, (pref >> 3) * 4, fb, POL_W);
      }
      prefetch_tm(&p.x); prefetch_tm(&p.wq);
    }
  }
  mbar_wait(sb + SM_BAR + B_SLOT * 8, 0);
  const uint32_t sv0 = __shfl_sync(0xffffffffu, lds32(sb + SM_BAR + V_SLOT * 8), 0), sv1 = __shfl_sync(0xffffffffu, lds32(sb + SM_BAR + V_SLOT * 8 + 4), 0);
  slot = sv0 & 255;
  const int grp = slot >> 3, idx = slot & 7;
  const int lb = slot * 2 + rank;
  const bool spare = grp == 8;
  const bool redo = spare || sv0 != sv1;
  const int cn = spare ? CN_SPARE : CN_MAIN, cch = spare ? lb - NMAIN : 4 * CN_SPARE + CN_MAIN * lb, cstep = spare ? 4 : 1;
  TS(0);

  if (wgi == 0) {
    asm volatile("setmaxnreg.dec.sync.aligned.u32 40;");
    const int lane = threadIdx.x & 31;
    cluster_arrive();
    if (warp == 3) {
      if (!spare) {
        const int s0 = lb * 16;
#pragma unroll 1
        for (int cg = 0; cg < 16; cg++) {
          __nanosleep(PRE_SLEEP);
          const int ch = cg * 64 + 2 * lane;
          const uint32_t* kp = reinterpret_cast<const uint32_t*>(p.ak + (size_t)s0 * DM + ch);
          const uint32_t* vp = reinterpret_cast<const uint32_t*>(p.av + (size_t)s0 * DM + ch);
          const uint4 sw = __ldg(reinterpret_cast<const uint4*>(p.shk + ch * 4));
          uint32_t k3 = 0, k2 = 0, k1 = 0, k0 = 0, up = 0;
          if (lb > 0) { k3 = ldg_stream(kp - 4 * 512); k2 = ldg_stream(kp - 3 * 512); k1 = ldg_stream(kp - 2 * 512); k0 = ldg_stream(kp - 512); up = ldg_stream(vp - 512); }
          const uint32_t w0 = __byte_perm(sw.x, sw.z, 0x5410), w1 = __byte_perm(sw.x, sw.z, 0x7632);
          const uint32_t w2 = __byte_perm(sw.y, sw.w, 0x5410), w3 = __byte_perm(sw.y, sw.w, 0x7632);
          up = hmul2(hfma2(k0, w0, hfma2(k1, w1, hfma2(k2, w2, hmul2(k3, w3)))), up);
#pragma unroll 1
          for (int hb = 0; hb < 2; hb++) {
            uint32_t kk[8], u[8];
#pragma unroll
            for (int r = 0; r < 8; r++) { kk[r] = ldg_stream(kp + r * 512); u[r] = ldg_stream(vp + r * 512); }
#pragma unroll
            for (int r = 0; r < 8; r++) {
              k3 = k2; k2 = k1; k1 = k0; k0 = kk[r];
              u[r] = hmul2(hfma2(k0, w0, hfma2(k1, w1, hfma2(k2, w2, hmul2(k3, w3)))), u[r]);
            }
            if (lane == 0) asm volatile("cp.async.bulk.wait_group.read 0;" ::: "memory");
            __syncwarp();
            const uint32_t dst = sb + SM_UST + lane * 32 + ((lane & 4) << 2);
#pragma unroll
            for (int cc = 0; cc < 2; cc++) {
              const uint32_t sel = cc ? 0x7632 : 0x5410;
              asm volatile("st.shared.v4.b32 [%0], {%1,%2,%3,%4};" ::"r"(dst + cc * 1024), "r"(__byte_perm(u[6], u[5], sel)), "r"(__byte_perm(u[4], u[3], sel)),
                           "r"(__byte_perm(u[2], u[1], sel)), "r"(__byte_perm(u[0], up, sel)) : "memory");
              asm volatile("st.shared.v4.b32 [%0], {%1,%2,%3,%4};" ::"r"((dst ^ 16) + cc * 1024), "r"(__byte_perm(u[7], u[6], sel)), "r"(__byte_perm(u[5], u[4], sel)),
                           "r"(__byte_perm(u[3], u[2], sel)), "r"(__byte_perm(u[1], u[0], sel)) : "memory");
            }
            fence_async_smem();
            __syncwarp();
            if (lane == 0) {
              asm volatile("cp.async.bulk.tensor.3d.global.shared::cta.bulk_group [%0, {%2, %3, %4}], [%1];\ncp.async.bulk.commit_group;"
                           ::"l"(&p.w), "r"(sb + SM_UST), "r"(WZ / 2 + lb * 16 + (hb ^ 1) * (WPL / 2)), "r"(cg * 32), "r"(0) : "memory");
            }
            up = u[7];
            kp += 8 * 512; vp += 8 * 512;
          }
          if ((cg & (cg + 1)) == 0 && lane == 0) {
            asm volatile("cp.async.bulk.wait_group 0;" ::: "memory");
            fence_release();
            flag_add(FLAG(F_U + 32 - __clz(cg)));
          }
          TSW(10 + cg);
        }
      }
      if (lane == 0) {
        unsigned long long t0, t1;
        asm volatile("mov.u64 %0, %globaltimer;" : "=l"(t0));
        while (!mbar_try(sb + SM_BAR + B_DONE * 8, 0)) {
          asm volatile("mov.u64 %0, %globaltimer;" : "=l"(t1));
          if (t1 - t0 > 2000000000ull) __trap();
        }
      }
    } else if (warp != 0) {
      const int w = warp - 1, ne = 12 + (cn + 1 - w) / 2;
      uint32_t p0 = 0;
      int cg = 2 + w, ch = cch + w * cstep;
#pragma unroll 1
      for (int e = spare ? 12 : 0; e < ne; e++) {
        const int rnd = e >= 6, k = e - 6 * rnd, rt = k == 4 ? idx : 15 - idx;
        uint8_t* dst = k < 4 ? g_kv + (size_t)(((k & 1) * 16 + 2 * grp + (k >> 1)) * 16 + 2 * idx + rank) * 32768 + w * 8192
                     : k < 6 ? g_cimg + (size_t)(rt * 32 + 16 * rnd + 2 * grp + rank) * 32768 + (w ^ (k & 1)) * 8192
                             : reinterpret_cast<uint8_t*>(g_yT + (size_t)ch * SEQ);
        const uint32_t src = sb + w * 8192 + (k == 4 ? 2 * GR : 0);
        if (e == 6) flag_wait(FLAG(F_AD + grp), 32);
        mbar_wait1(sb + SM_BAR + (B_EV + (k == 4 ? 2 : 0) + w) * 8, k == 4 ? rnd : p0);
        if (k != 4) p0 ^= 1;
        if (lane < 4 && k >= 6 && (!spare || e < ne - 6)) mbar_arrive_cluster(sb + SM_BAR + (B_EMPTY + cg) * 8, lane & 1);
        fence_async_smem();
        if (elect()) {
#pragma unroll 1
          for (int i = 0; i < (k >= 6 ? 1 : 8); i++) {
            const uint32_t o = (i >> 2) * 16384 + (i & 3) * 2048;
            asm volatile("cp.async.bulk.global.shared::cta.bulk_group [%0], [%1], %2;" ::"l"(dst + o), "r"(src + o), "r"(k >= 6 ? 4096 : 2048) : "memory");
            asm volatile("cp.async.bulk.commit_group;\ncp.async.bulk.wait_group.read %0;" ::"n"(ST_OUT) : "memory");
          }
          asm volatile("cp.async.bulk.wait_group 0;" ::: "memory");
          if (k != 4) mbar_arrive(sb + SM_BAR + (B_FREE + w) * 8);
        }
        __syncwarp();
        if (lane < (k == 4 ? 4 : e == 11 || (e == ne - 1 && !spare) ? 2 : 0))
          mbar_arrive_cluster(sb + SM_BAR + (B_EMPTY + (k == 4 ? 2 : e == 11) + (lane >> 1)) * 8, lane & 1);
        if (k >= 3) {
          fence_release();
          if (lane == 0 || (lane == 1 && e == 5))
            flag_add(FLAG(lane ? F_AD + grp : k == 3 ? F_KV + rnd * 8 + grp : k < 6 ? F_CTX + rt * 2 + rnd : F_Y + (ch >> 7)));
        }
        if (k >= 6) { cg = conv_next(cg, spare); ch += 2 * cstep; }
      }
      if (lane == 0) mbar_arrive(sb + SM_BAR + B_DONE * 8);
    } else {
      uint32_t pe = 0;
      auto acquire = [&](int g, int n, uint32_t m) {
        int i = g;
#pragma unroll 1
        do mbar_wait1(sb + SM_BAR + (B_EMPTY + i) * 8, (pe >> i) & 1); while (++i < g + n);
        pe ^= m << g;
      };
#pragma unroll 1
      for (int rnd = 0; rnd < (spare ? 0 : 2); rnd++) {
        const int hp = 16 * rnd + 2 * grp, head = hp + rank;
#pragma unroll 1
        for (int kk = rnd || redo ? 0 : 4; kk < 32; kk++) {
          const int g0 = 2 + 3 * (kk & 3);
          acquire(g0, kk < 4 ? 3 : 1, 7);
          if (elect()) {
            const uint32_t fb = sb + SM_BAR + (B_FULL + g0) * 8;
            mbar_expect_tx(fb, 3 * GR);
            if (kk < 16) {
              tma2d(sb + g0 * GR, &p.c, (kk & 7) * 64, (2 * idx + rank) * 128, fb, EV_NORMAL);
              tma3d_mc(sb + (g0 + 1 + rank) * GR, rank ? &p.wuv : &p.wuk, 0, (kk & 7) * 64, (hp + (kk >> 3)) * 2, fb, POL_W);
            } else {
              tma2d_mc(sb + (g0 + rank) * GR, &p.x, (kk - 16) * 64, (rank ? 15 - idx : idx) * 128, fb, EV_NORMAL);
              tma3d(sb + (g0 + 2) * GR, &p.wq, 0, (kk - 16) * 64, head * 2, fb, POL_W);
            }
          }
        }
        flag_wait(FLAG(F_KV + rnd * 8 + grp), 32);
        fence_async_all();
        acquire(2, 1, 3);
        int g0 = 4;
#pragma unroll 1
        for (int f = 0; f < 34; f++) {
          const bool isk = (f == 0) || ((f & 1) && f < 33);
          const int it = (f == 0) ? 0 : (f == 33) ? 16 : isk ? (f + 1) >> 1 : (f >> 1) - 1;
          const int blk = it == 0 ? idx : it <= idx ? it - 1 : it < 16 ? 15 - it : 15 - idx;
          acquire(g0, f < 5 ? 2 : 1, 3);
          if (elect()) {
            const uint32_t fb = sb + SM_BAR + (B_FULL + g0) * 8;
            mbar_expect_tx(fb, 2 * GR);
            bulk_g2s(sb + g0 * GR, g_kv + (size_t)(((isk ? 0 : 16) + (head & 15)) * 16 + blk) * 32768, 2 * GR, fb, POL_KV);
          }
          g0 = f == 12 ? 12 : g0 == 12 ? 4 : g0 + 2;
        }
      }
      if (spare) {
#pragma unroll 1
        for (int i = 0, g = 2; i < 32; i++) {
          acquire(g, 2, 3);
          if (elect()) {
            const uint32_t fb = sb + SM_BAR + (B_FULL + g) * 8;
            if (i == 0) { mbar_expect_tx(fb - 8, 2048); bulk_g2s(sb + GR, p.gate_w, 2048, fb - 8, EV_NORMAL); }
            mbar_expect_tx(fb, 2 * GR);
            tma2d(sb + g * GR, &p.x, (i & 7) * 128, (lb - NMAIN) * 512 + (i >> 3) * 128, fb, EV_NORMAL);
            tma2d(sb + (g + 1) * GR, &p.x, (i & 7) * 128 + 64, (lb - NMAIN) * 512 + (i >> 3) * 128, fb, EV_NORMAL);
          }
          g = g == NGR - 2 ? 2 : g + 2;
        }
      }
      auto conv_fill = [&](int g, int ch) {
        acquire(g, 1, 1);
        if (elect()) {
          const uint32_t fb = sb + SM_BAR + (B_FULL + g) * 8;
          mbar_expect_tx(fb, WBYTES + 4096);
          bulk_g2s(sb + g * GR, g_w + (size_t)ch * WSTRIDE, WBYTES, fb, POL_C);
          bulk_g2s(sb + g * GR + WBYTES, p.ssk + (size_t)ch * SEQ, 4096, fb, POL_C);
        }
      };
#pragma unroll 1
      for (int i = 0, g = 2; i < cn; i++) {
        if ((i & 15) == 0) { flag_wait(FLAG(F_U + (spare ? 32 - __clz(i >> 4) : 4)), NMAIN); fence_async_all(); }
        conv_fill(g + (i & 1), cch + i * cstep);
        if (i & 1) g = conv_next(g, spare);
      }
      if (!spare) {
        const int rt = 2 * grp + rank, ct = idx;
        int g0 = P3G;
        prefetch_tm(&p.y); prefetch_tm(&p.out);
#pragma unroll 1
        for (int kb = 0; kb < 66; kb++) {
          if (kb == 0 || kb == 32 || kb >= 64) {
            flag_wait(FLAG(kb < 64 ? F_CTX + rt * 2 + (kb >> 5) : kb == 64 ? F_GATE : F_Y + ct), kb <= 64 ? 32 : 128);
            fence_async_all();
          }
          acquire(g0, kb < 11 ? 2 : 1, 3);
          if (elect()) {
            const uint32_t fb = sb + SM_BAR + (B_FULL + g0) * 8;
            mbar_expect_tx(fb, kb == 64 ? 2 * GR + 512 : 2 * GR);
            if (kb <= 64) bulk_g2s(kb < 64 ? sb + g0 * GR : sb + SM_GATE, kb < 64 ? (const void*)(g_cimg + (size_t)(rt * 64 + kb) * GR) : (const void*)(g_gate + rt * 128), kb < 64 ? GR : 512, fb, POL_CTX);
            if (kb < 64) {
              tma2d_mc(sb + (g0 + 1) * GR + rank * 8192, &p.wo, ct * 128 + rank * 64, kb * 64, fb, POL_WO);
            } else {
              const CUtensorMap* tm = kb == 64 ? &p.x : &p.y;
              const int c0 = (kb == 64 ? ct : rt) * 128, c1 = (kb == 64 ? rt : ct) * 128;
              tma2d(sb + g0 * GR, tm, c0, c1, fb, EV_NORMAL);
              tma2d(sb + (g0 + 1) * GR, tm, c0 + 64, c1, fb, EV_NORMAL);
            }
          }
          g0 = g0 == 12 ? (kb == 3 ? 2 : 0) : g0 + 2;
        }
        unsigned n = 0;
        if (lane == 0) n = atomicInc(FLAG(F_EXIT), 0x7fffffffu);
        if (__any_sync(0xffffffffu, n == NMAIN - 1)) {
#pragma unroll
          for (int i = lane; i < 96; i += 32) *reinterpret_cast<uint2*>(FLAG(i)) = make_uint2(0, 0);
        }
      }
      if (lane == 0) mbar_arrive(sb + SM_BAR + B_DONE * 8);
    }
    __syncwarp();
    cluster_wait();
  } else {
    asm volatile("setmaxnreg.inc.sync.aligned.u32 232;");
    Cons c;
    c.sb = sb; c.pf = 0; c.wg = wgi - 1; c.tid = threadIdx.x & 127;
    const int lane = threadIdx.x & 31, t = lane & 3;
    const int row = c.wg * 64 + (warp & 3) * 16 + (lane >> 2);
    const uint32_t dkk = desc_k(sb), dk0 = dkk + c.wg * 512, dm0 = desc_mn<8192>(sb), dv0 = desc_mn<16384>(sb);
    const uint32_t dsw = DG + 512 - c.wg * 1024;
    if (c.wg == 1) bar_arrive(1, 256);
    c.pfree = 1;
    asm("mapa.shared::cluster.u32 %0, %1, %2;" : "=r"(c.relb) : "r"(sb + SM_BAR + (B_EMPTY + (c.tid >> 1)) * 8), "r"(c.tid & 1));
    c.zero = p.zero;
    c.rnd = 0;
    const uint32_t stg = sb + (c.wg * 64 + (warp & 3) * 16 + ((lane >> 3) & 1) * 8 + (lane & 7)) * 128 + (((lane >> 4) ^ (lane & 7)) << 4);

    uint32_t dd0;
    auto load_dd = [&]() { asm volatile("ld.global.nc.u16 %0, [%1];" : "=r"(dd0) : "l"(p.ssd + (unsigned)(cch + c.wg * cstep + (lane & c.zero)))); };
    if (redo) {
      load_dd();
#pragma unroll 1
      for (int g = 2; g < NGR; g += 3) { mbar_wait(sb + SM_BAR + (B_FULL + g) * 8, 0); c.release(g, 3); }
      c.pf = 0x924;
    }
    if (spare) {
      c.wait_full(1);
      int g = 2;
#pragma unroll 1
      for (int r = 0; r < 4; r++) {
        float d[4] = {0.f, 0.f, 0.f, 0.f}, e[4] = {0.f, 0.f, 0.f, 0.f};
#pragma unroll 1
        for (int kb = 0; kb < 16; kb += 2) {
          c.wait_full(g);
          wg_fence();
#pragma unroll
          for (int k = 0; k < 4; k++) {
            mma_ss_n8(d, dk0 + g * DG + k * 2, dkk + DG + kb * 8 + k * 2);
            mma_ss_n8(e, dk0 + (g + 1) * DG + k * 2, dkk + DG + kb * 8 + 8 + k * 2);
          }
          wg_commit();
          wg_wait<0>();
          c.release(g, 2);
          g = g == NGR - 2 ? 2 : g + 2;
        }
        reg_fence(d); reg_fence(e);
        d[0] += e[0]; d[2] += e[2];
        if (t == 0) {
          float* gp = g_gate + (unsigned)((lb - NMAIN) * 512 + r * 128 + row);
          gp[0] = rcp(1.f + ex2(-1.4426950408889634f * d[0])); gp[8] = rcp(1.f + ex2(-1.4426950408889634f * d[2]));
        }
      }
      fence_release();
      __syncwarp();
      if (lane == 0) flag_add(FLAG(F_GATE));
      TS(1);
    }
    const float dmask = (float)(2 * t - (row & 63));
    uint32_t pv[32];
#pragma unroll 1
    for (int rnd = 0; rnd < (spare ? 0 : 2); rnd++) {
      float O[64];
      FTM(rnd * 8);
      FTG(0);
      FTH(56, c.rnd == rnd);
      c.wait_full(2);
      FTM(rnd * 8 + 1);
      FTH(57, c.rnd == rnd);
#pragma unroll 1
      for (int tile = c.zero; tile < 2; tile++) {
        float acc[128];
        const bool single = tile == 0;
        {
          FTG(tile * 32 + 1);
          const uint32_t a = dk0 + 2 * DG, b = dm0 + 3 * DG;
          c.turn_begin();
          FTG(tile * 32 + 2);
          FTH(58, c.rnd == rnd);
          wg_fence();
          mma_ss_n256_init<1>(acc, a, b);
#pragma unroll
          for (int k = 1; k < 4; k++) mma_ss_n256<1>(acc, a + k * 2, b + k * 128);
          wg_commit();
          if (single) c.turn_end();
          FTG(tile * 32 + 3);
        }
#pragma unroll 1
        for (int kb = 1; kb < 8; kb++) {
          const int g0 = 2 + 3 * (kb & 3);
          const uint32_t a = dk0 + g0 * DG, b = dm0 + (g0 + 1) * DG;
          const bool second = (kb == 1 && !single) || kb == 7;
          FTG(tile * 32 + kb * 4);
          if (!second) { wg_wait<0>(); c.release(2 + 3 * ((kb - 1) & 3), 3); }
          FTG(tile * 32 + kb * 4 + 1);
          c.wait_full(g0);
          if (!second) c.turn_begin();
          FTG(tile * 32 + kb * 4 + 2);
          wg_fence();
#pragma unroll
          for (int k = 0; k < 4; k++) mma_ss_n256<1>(acc, a + k * 2, b + k * 128);
          wg_commit();
          if (kb != 6) c.turn_end();
          if (second) { wg_wait<1>(); c.release(2 + 3 * ((kb - 1) & 3), 3); }
          FTG(tile * 32 + kb * 4 + 3);
          FTH(58 + kb, c.rnd == rnd || kb > 3);
          if (tile == 1 && kb == 3) { c.wait_stage_free(); stsm_frag<0, 4>(pv, stg); }
          if (tile == 1 && kb == 4) { stsm_frag<4, 8>(pv, stg); c.staged(0); }
        }
        c.rnd = rnd;
        c.wait_stage_free();
        const bool nxt = c.try_full(2);
        wg_wait<0>();
        reg_fence(acc);
        c.release(11, 3);
        pack_frag_scaled(acc, pv, SM_C, SM_C);
        stsm_frag(pv, stg);
        c.staged(0);
        pack_frag<64>(acc, pv);
        pin32(pv, sb);
        FTG(32 + tile * 32);
        if (!nxt) mbar_wait(sb + SM_BAR + (B_FULL + 2) * 8, (c.pf >> 2) & 1);
        c.pf ^= 4;
      }
      TS(1 + rnd * 3);
      FTM(rnd * 8 + 2);
      {
        float qa[64];
        float (&qb)[64] = O;
        {
          FTG(65);
          const uint32_t a = dk0 + 2 * DG, b = dm0 + 4 * DG;
          c.turn_begin();
          FTG(66);
          wg_fence();
          mma_ss_n128_init<1>(qa, a, b);
          mma_ss_n128_init<1>(qb, a + dsw, b);
#pragma unroll
          for (int k = 1; k < 4; k++) {
            mma_ss_n128<1>(qa, a + k * 2, b + k * 128);
            mma_ss_n128<1>(qb, a + dsw + k * 2, b + k * 128);
          }
          wg_commit();
          FTG(67);
        }
#pragma unroll 1
        for (int kb = 1; kb < 16; kb++) {
          const int g0 = 2 + 3 * (kb & 3);
          const uint32_t a = dk0 + g0 * DG, b = dm0 + (g0 + 2) * DG;
          const bool second = kb == 1 || kb == 15;
          FTG(64 + kb * 4);
          if (!second) { wg_wait<0>(); c.release(2 + 3 * ((kb - 1) & 3), 3); }
          FTG(65 + kb * 4);
          c.wait_full(g0);
          if (!second) c.turn_begin();
          FTG(66 + kb * 4);
          FTH(kb - 14, kb < 14);
          wg_fence();
#pragma unroll
          for (int k = 0; k < 4; k++) {
            mma_ss_n128<1>(qa, a + k * 2, b + k * 128);
            mma_ss_n128<1>(qb, a + dsw + k * 2, b + k * 128);
          }
          wg_commit();
          if (kb != 14) c.turn_end();
          if (second) { wg_wait<1>(); c.release(2 + 3 * ((kb - 1) & 3), 3); }
          FTG(67 + kb * 4);
          FTH(2, kb < 15);
          if (kb == QFLUSH) { c.wait_stage_free(); stsm_frag<0, 4>(pv, stg); }
          if (kb == QFLUSH + 1) { stsm_frag<4, 8>(pv, stg); c.staged(0); }
        }
        c.wait_stage_free();
        mbar_wait(sb + SM_BAR + (B_EMPTY + 2) * 8, rnd ^ !redo);
        FTM(rnd * 8 + 3);
        FTH(3, 0);
        wg_wait<0>();
        reg_fence(qa); reg_fence(qb);
        FTH(4, 0);
        c.release(11, 3);
        pack_frag<0>(qa, pv);
        stsm_frag(pv, stg + 2 * GR);
        if (c.wg == 0) {
          pack_frag<0>(qb, pv);
          stsm_frag(pv, stg);
#pragma unroll
          for (int i = 16; i < 32; i++) pv[i] = 0;
        }
        fence_async_smem();
        c.wait_full(4);
      }
      TS(2 + rnd * 3);
      FTM(rnd * 8 + 4);
      FTH(5, 0);
      {
        const int nA = idx + 1;
        uint32_t (&P)[32] = pv;
        SoftState z;
        z.m0 = z.m1 = z.l0 = z.l1 = 0.f; z.shifted = c.zero;
#pragma unroll 1
        for (int seg = c.zero;; seg++) {
        if (c.wg == seg) attn_half(c, O, P, z, dk0, dkk, dv0, dmask, seg);
        if (seg) break;
        FTM(rnd * 8 + 5);
        int gk = c.wg ? 4 : 6, gv = c.wg ? 4 : 8;
        uint32_t dq = dk0 + (1 - c.wg < nA ? 2 * DG : 0), dk = dkk + gk * DG;
#pragma unroll 1
        for (int it = 1 - c.wg; it < 17 - c.wg; it++) {
          float S[64];
          FTA(it * 7 + 0); FTH((it < 3 ? 8 + it * 8 : it * 8 - 88) + 0, it >= 3 && it < 15);
          c.turn_begin();
          FTA(it * 7 + 2); FTH((it < 3 ? 8 + it * 8 : it * 8 - 88) + 1, it >= 3 && it < 15);
          wg_fence();
          issue_qk(S, dq, dk);
          wg_commit();
          const uint32_t dv = dv0 + gv * DG;
          uint32_t relk = c.relb + gk * 8, relv = c.relb + gv * 8;
          gk = it == 6 ? 12 : gv == 12 ? 4 : gv + 2;
          gv = it == 16 ? gk : gk == 12 ? 4 : gk + 2;
          uint32_t fk = sb + SM_BAR + (B_FULL + gk) * 8, fv = sb + SM_BAR + (B_FULL + gv) * 8, park = (c.pf >> gk) & 1, parv = (c.pf >> gv) & 1;
          c.pf ^= (1u << gk) | (1u << gv);
          dq = dk0 + (it + 1 < nA ? 2 * DG : 0); dk = dkk + gk * DG;
          float lo0 = z.l0, lo1 = z.l1;
          const bool first = it == nA || it == 0;
          if (it == nA) {
            if (EARLY_RCP) { lo0 = rcp(quad_sum(lo0)); lo1 = rcp(quad_sum(lo1)); }
            z.m0 = z.m1 = z.l0 = z.l1 = 0.f; z.shifted = 0;
          }
          float s0, s1, d0 = z.m0, d1 = z.m1;
          int pre = z.shifted || (it & 15) == 0;
          float lim = first ? -1.f : SM_LIMIT;
          asm volatile("" : "+r"(relk), "+r"(relv), "+r"(fk), "+r"(fv), "+r"(park), "+r"(parv), "+r"(dq), "+r"(dk), "+r"(pre), "+f"(lim), "+f"(d0), "+f"(d1), "+f"(z.l0), "+f"(z.l1));
          if (it) {
            issue_pv<0>(O, P, dv, it != nA + 1 && it != 1, true);
            issue_pv<1>(O, P, dv, 1, HALFPV ? it + c.wg > 1 : true);
            c.turn_end();
          } else stage_q2(c, O, P, stg);
          FTA(it * 7 + 3); FTH((it < 3 ? 8 + it * 8 : it * 8 - 88) + 2, it >= 3 && it < 15);
          wg_wait<4>();
          reg_fence(S);
          FTA(it * 7 + 4); FTH((it < 3 ? 8 + it * 8 : it * 8 - 88) + 3, it >= 3 && it < 15);
          if (c.tid < 4) asm volatile("mbarrier.arrive.shared::cluster.b64 _, [%0];" ::"r"(relk) : "memory");
#pragma unroll 1
          for (int pass = 0;; pass++) {
            if (pre) {
              if ((it & 15) == 0) mask_diag(S, dmask);
              if (z.shifted) shift_scores(S, d0, d1);
            }
            float tr[ROT];
            exp_quarter<0, 3>(S, P, tr, s0, s1, sb);
            exp_quarter<1, 2>(S, P, tr, s0, s1, sb);
            exp_quarter<2, 1>(S, P, tr, s0, s1, sb);
            exp_quarter<3, 0>(S, P, tr, s0, s1, sb);
            reg_fence(O);
            if (c.tid < (pass || !it ? 0 : 4)) asm volatile("mbarrier.arrive.shared::cluster.b64 _, [%0];" ::"r"(relv) : "memory");
            const bool ok = mbar_test(fk, park) & mbar_test(fv, parv);
            if (!ok) lim = -1.f;
            FTA(it * 7 + 5); FTH((it < 3 ? 8 + it * 8 : it * 8 - 88) + 4, it >= 3 && it < 15);
            if (!__any_sync(0xffffffffu, !(s0 <= lim && s1 <= lim))) break;
            if (pass) break;
            if (it == nA) {
              uint32_t pk[32];
              if (!EARLY_RCP) { lo0 = rcp(quad_sum(lo0)); lo1 = rcp(quad_sum(lo1)); }
              pack_frag_scaled(O, pk, lo0, lo1);
              stsm_frag(pk, stg + 2 * GR);
              c.staged(1);
            }
            if (!ok) { mbar_wait(fk, park); mbar_wait(fv, parv); }
            if (!soft_unsafe(s0, s1, first)) break;
            soft_fix(S, O, z, first, d0, d1);
            pre = 1;
          }
          z.l0 += s0; z.l1 += s1;
          FTA(it * 7 + 6); FTH((it < 3 ? 8 + it * 8 : it * 8 - 88) + 5, it >= 3 && it < 15);
        }
        FTM(rnd * 8 + 6);
        }
        FTH(48, 0);
        load_dd();
        c.turn_begin();
        FTH(49, 0);
        wg_fence();
        issue_pv<0>(O, P, dv0 + 12 * DG, 1, true);
        issue_pv<1>(O, P, dv0 + 12 * DG, 1, !c.wg);
        c.turn_end();
        z.l0 = rcp(quad_sum(z.l0)); z.l1 = rcp(quad_sum(z.l1));
        wg_wait<0>();
        reg_fence(O); reg_fence(P);
        FTH(50, 0);
        c.release(12, 2);
        pack_frag_scaled(O, P, z.l0, z.l1);
        stsm_frag(P, stg);
        c.staged(0);
        FTM(rnd * 8 + 7);
        FTH(51, 0);
      }
      TS(3 + rnd * 3);
    }
    conv_tasks(c, p, (cn + 1 - c.wg) / 2, ((cn - 1) & 1) == c.wg, spare, cch + c.wg * cstep, 2 * cstep, dd0, dkk, warp & 3, lane);
    if (c.wg == 1) c.pf ^= 0x14;
    TS(7);
    if (!spare) {
      const int rt = 2 * grp + rank, ct = idx;
      float acc[64];
      int g0 = P3G + 2, pg = P3G;
      {
        FTO(0);
        c.wait_full(P3G);
        FTO(1);
        const uint32_t a = dk0 + P3G * DG, b = dm0 + (P3G + 1) * DG;
        wg_fence();
        mma_ss_n128_init<1>(acc, a, b);
#pragma unroll
        for (int k = 1; k < 4; k++) mma_ss_n128<1>(acc, a + k * 2, b + k * 128);
        wg_commit();
      }
#pragma unroll 1
      for (int kb = 1; kb < 64; kb++) {
        FTO(kb * 2);
        c.wait_full(g0);
        FTO(kb * 2 + 1);
        const uint32_t a = dk0 + g0 * DG, b = dm0 + (g0 + 1) * DG;
        wg_fence();
#pragma unroll
        for (int k = 0; k < 4; k++) mma_ss_n128<1>(acc, a + k * 2, b + k * 128);
        wg_commit();
        wg_wait<1>();
        c.release(pg, kb <= 59 ? 2 : 0);
        if (kb == 40) FTDUMP();
        pg = g0;
        g0 = g0 == 12 ? (kb == 3 ? 2 : 0) : g0 + 2;
      }
      cluster_arrive();
      c.wait_full(P3X);
      c.wait_full(P3Y);
      const float g0f = __uint_as_float(lds32(sb + SM_GATE + row * 4)), g1f = __uint_as_float(lds32(sb + SM_GATE + row * 4 + 32));
      const uint32_t gp0 = pack_bf16(g0f, g0f), gp1 = pack_bf16(g1f, g1f);
      const float h0 = 1.f - g0f, h1 = 1.f - g1f;
      const int w = warp & 3;
      const uint32_t xa = stg + P3X * GR;
      const uint32_t ya = sb + P3Y * GR + c.wg * 16384 + ((lane >> 4) * 8 + (lane & 7)) * 128 + (((2 * w + ((lane >> 3) & 1)) ^ (lane & 7)) << 4);
      uint32_t xy[32];
#pragma unroll
      for (int jj = 0; jj < 8; jj++) {
        uint32_t x[4], y[4];
        asm volatile("ldmatrix.sync.aligned.m8n8.x4.shared.b16 {%0,%1,%2,%3}, [%4];" : "=r"(x[0]), "=r"(x[1]), "=r"(x[2]), "=r"(x[3]) : "r"((xa ^ ((jj & 3) << 5)) + (jj >> 2) * 16384) : "memory");
        asm volatile("ldmatrix.sync.aligned.m8n8.x4.trans.shared.b16 {%0,%1,%2,%3}, [%4];" : "=r"(y[0]), "=r"(y[1]), "=r"(y[2]), "=r"(y[3]) : "r"(ya + jj * 2048) : "memory");
#pragma unroll
        for (int i = 0; i < 4; i++) xy[4 * jj + i] = hmul2(x[i], y[i]);
      }
      wg_wait<0>();
      reg_fence(acc);
      TS(8);
#pragma unroll
      for (int i = 0; i < 32; i++) {
        const float h = (i & 1) ? h1 : h0;
        xy[i] = hfma2((i & 1) ? gp1 : gp0, xy[i], pack_bf16(acc[2 * i] * h, acc[2 * i + 1] * h));
      }
      stsm_frag(xy, xa);
      fence_async_smem();
      __syncwarp();
      if (lane == 0) {
        const int r0 = c.wg * 64 + w * 16;
        tma2d_store(&p.out, sb + P3X * GR + r0 * 128, ct * 128, rt * 128 + r0);
        tma2d_store(&p.out, sb + (P3X + 1) * GR + r0 * 128, ct * 128 + 64, rt * 128 + r0);
        asm volatile("cp.async.bulk.commit_group;\ncp.async.bulk.wait_group.read 0;" ::: "memory");
      }
    } else { FTDUMP(); cluster_arrive(); }
    if (lane == 0) mbar_arrive(sb + SM_BAR + B_DONE * 8);
    __syncwarp();
    TS(9);
    cluster_wait();
  }
}

typedef CUresult (*EncFn)(CUtensorMap*, CUtensorMapDataType, cuuint32_t, void*, const cuuint64_t*, const cuuint64_t*, const cuuint32_t*,
                          const cuuint32_t*, CUtensorMapInterleave, CUtensorMapSwizzle, CUtensorMapL2promotion, CUtensorMapFloatOOBfill);

void enc2d(EncFn enc, CUtensorMap* tm, const void* base, uint64_t cols, uint64_t rows, uint32_t bc, uint32_t br) {
  cuuint64_t dims[2] = {cols, rows}; cuuint64_t strides[1] = {cols * 2}; cuuint32_t box[2] = {bc, br}; cuuint32_t es[2] = {1, 1};
  enc(tm, CU_TENSOR_MAP_DATA_TYPE_BFLOAT16, 2, const_cast<void*>(base), dims, strides, box, es, CU_TENSOR_MAP_INTERLEAVE_NONE,
      CU_TENSOR_MAP_SWIZZLE_128B, CU_TENSOR_MAP_L2_PROMOTION_L2_256B, CU_TENSOR_MAP_FLOAT_OOB_FILL_NONE);
}
void enc3d(EncFn enc, CUtensorMap* tm, const void* base, uint64_t K, uint64_t N) {
  cuuint64_t dims[3] = {64, K, N / 64}; cuuint64_t strides[2] = {N * 2, 128}; cuuint32_t box[3] = {64, 64, 2}; cuuint32_t es[3] = {1, 1, 1};
  enc(tm, CU_TENSOR_MAP_DATA_TYPE_BFLOAT16, 3, const_cast<void*>(base), dims, strides, box, es, CU_TENSOR_MAP_INTERLEAVE_NONE,
      CU_TENSOR_MAP_SWIZZLE_128B, CU_TENSOR_MAP_L2_PROMOTION_L2_256B, CU_TENSOR_MAP_FLOAT_OOB_FILL_NONE);
}

}

extern "C" void kernel_launch(void* const* d_in, const int* in_sizes, int n_in, void* d_out, int out_size) {
  (void)in_sizes; (void)n_in; (void)out_size;
  typedef const __nv_bfloat16* BP;
  BP xq = (BP)d_in[0], ak = (BP)d_in[1], av = (BP)d_in[2], shk = (BP)d_in[3], ssk = (BP)d_in[4], ssd = (BP)d_in[5];
  BP ckv = (BP)d_in[7], wq = (BP)d_in[8], wuk = (BP)d_in[9], wuv = (BP)d_in[10], wo = (BP)d_in[11], gw = (BP)d_in[12];

  static EncFn enc = nullptr;
  if (!enc) {
    cudaDriverEntryPointQueryResult qr;
    cudaGetDriverEntryPoint("cuTensorMapEncodeTiled", (void**)&enc, cudaEnableDefault, &qr);
    cudaFuncSetAttribute(mega_kernel, cudaFuncAttributeMaxDynamicSharedMemorySize, SMEM_BYTES);
  }
  Params p;
  void* yT = nullptr;
  cudaGetSymbolAddress(&yT, g_yT);
  enc2d(enc, &p.x, xq, DM, SEQ, 64, 128);
  enc2d(enc, &p.c, ckv, DC, SEQ, 64, 128);
  enc3d(enc, &p.wq, wq, DM, NH * HD);
  enc3d(enc, &p.wuk, wuk, DC, NH * HD);
  enc3d(enc, &p.wuv, wuv, DC, NH * HD);
  enc2d(enc, &p.wo, wo, DM, NH * HD, 64, 64);
  enc2d(enc, &p.y, yT, SEQ, DM, 64, 128);
  enc2d(enc, &p.out, d_out, DM, SEQ, 64, 16);
  {
    void* wp = nullptr;
    cudaGetSymbolAddress(&wp, g_w);
    cuuint64_t dims[3] = {WSTRIDE / 2, DM / 2, 2}; cuuint64_t strides[2] = {2 * WSTRIDE, WSTRIDE}; cuuint32_t box[3] = {16, 32, 2}; cuuint32_t es[3] = {1, 1, 1};
    enc(&p.w, CU_TENSOR_MAP_DATA_TYPE_BFLOAT16, 3, wp, dims, strides, box, es, CU_TENSOR_MAP_INTERLEAVE_NONE,
        CU_TENSOR_MAP_SWIZZLE_32B, CU_TENSOR_MAP_L2_PROMOTION_NONE, CU_TENSOR_MAP_FLOAT_OOB_FILL_NONE);
  }
  p.zero = 0;
  cudaGetSymbolAddress((void**)&p.flags, g_flags);
  p.first[0] = wuk; p.first[1] = wuv; p.first[2] = ckv;
  for (int i = 0; i < 128; i++) {
    const int tp = i % NSLOT;
    p.pref[i] = tp < 32 ? (tp & 7) * 8 + (tp >> 3) : tp < 60 ? (1 + (tp - 32) % 7) * 8 + 4 + (tp - 32) / 7 : tp < 62 ? tp + 4 : tp - 58;
  }
  p.xp = xq; p.gate_w = gw; p.ak = ak; p.av = av; p.shk = shk; p.ssk = ssk; p.ssd = ssd;

  mega_kernel<<<132, NTHREADS, SMEM_BYTES>>>(p);
}
```

```cpp
#include <cuda_runtime.h>
#include <cuda.h>
#include <cuda_bf16.h>
#include <stdint.h>

namespace {

constexpr int SEQ = 2048, DM = 1024, DC = 512, NH = 32, HD = 128;
constexpr int GR = 16384;
constexpr int NGR = 14;
constexpr int SM_BAR = NGR * GR;
constexpr int SM_GATE = SM_BAR + 512;
constexpr int SM_UST = SM_GATE + 512;
constexpr int SMEM_BYTES = SM_UST + 2048;
constexpr int NTHREADS = 384;
#define SM_LIMIT 1.0995116e12f
#define SM_LOW 9.094947e-13f
constexpr int CN_MAIN = 5, CN_SPARE = 96;
constexpr int P3G = 6, P3X = 10, P3Y = 12;
constexpr int NMAIN = 128;

constexpr int B_FULL = 0, B_FREE = 14, B_SLOT = 16, B_DONE = 17, B_EMPTY = 18, B_EV = 32, V_SLOT = 36;

__device__ __align__(1024) uint8_t g_kv[2 * 16 * 16 * 32768];
__device__ __align__(1024) uint8_t g_cimg[16 * NH * 32768];
__device__ __align__(1024) __nv_bfloat16 g_yT[DM * SEQ];
__device__ __align__(1024) float g_gate[SEQ];
#define CWIDE 0
constexpr int WZ = CWIDE ? 768 : 256, WPL = WZ + 4096, WBYTES = 2 * WPL + 32, WSTRIDE = 2 * WPL + 128;
__device__ __align__(1024) uint8_t g_w[DM * WSTRIDE];
__device__ __align__(32) unsigned g_flags[96 * 8];
constexpr int F_KV = 0, F_CTX = 16, F_U = 48, F_AD = 56, F_Y = 64, F_GATE = 72, F_EXIT = 73;
constexpr int NSLOT = 66;
#define FLAG(i) (&g_flags[(i) * 8])
#define CLAIMP(i) (p.flags + (i) * 8 + 1)

#define TS(slot)
#define TSW(slot)
#define FTX(i, off)
#define FTDUMP()

#define ST_OUT 0
#define QFLUSH 4
#define POL_W EV_NORMAL
#define POL_WO EV_FIRST
#define POL_KV EV_NORMAL
#define POL_C EV_FIRST
#define POL_CTX EV_FIRST
#define HALFPV 1
#define PRE_SLEEP 1500
#define EXPV 1
#define SUMV 0
#define ROT 8
#define EARLY_RCP 1
#define KVARR 1
#define KV_ROW(idx, t) (KVARR ? 8 * (t) + 2 * ((idx) & 3) : 2 * (idx))
#define KV_HEAD(idx, t) (KVARR ? (idx) >> 2 : (t))
#define DFOLD 1
#define FINE_MODE 0
#define FINE_RND 1
#define FTA(i) do { if (FINE_MODE == 0) FTX(i, rnd ^ FINE_RND); } while (0)
#define FTG(i) do { if (FINE_MODE == 1) FTX(i, rnd ^ FINE_RND); } while (0)
#define FTM(i) do { if (FINE_MODE == 4) FTX(i, 0); } while (0)
#define FTC(k) do { if (FINE_MODE == 5) FTX((i & 7) * 8 + (k), (i >> 3) ^ FINE_RND); } while (0)
#define FTH(i, off) do { if (FINE_MODE == 6) FTX(i, (c.rnd ^ FINE_RND) | (off)); } while (0)
#define FTS(i)
#define FTSD(i)
#define FTSW(i)
#define FTO(i) do { if (FINE_MODE == 2) FTX(i, 0); } while (0)

__device__ __forceinline__ uint32_t smem_u32(const void* p) { return (uint32_t)__cvta_generic_to_shared(p); }
__device__ __forceinline__ void mbar_init(uint32_t bar, int cnt) { asm volatile("mbarrier.init.shared::cta.b64 [%0], %1;" ::"r"(bar), "r"(cnt) : "memory"); }
__device__ __forceinline__ void mbar_expect_tx(uint32_t bar, uint32_t bytes) { asm volatile("mbarrier.arrive.expect_tx.shared::cta.b64 _, [%0], %1;" ::"r"(bar), "r"(bytes) : "memory"); }
__device__ __forceinline__ void mbar_arrive(uint32_t bar) { asm volatile("mbarrier.arrive.shared::cta.b64 _, [%0];" ::"r"(bar) : "memory"); }
__device__ __forceinline__ void mbar_arrive_cluster(uint32_t bar, uint32_t cta) {
  asm volatile("{\n.reg .b32 r;\nmapa.shared::cluster.u32 r, %0, %1;\nmbarrier.arrive.shared::cluster.b64 _, [r];\n}\n" ::"r"(bar), "r"(cta) : "memory");
}
__device__ __forceinline__ bool mbar_try(uint32_t bar, uint32_t parity) {
  uint32_t ok;
  asm volatile("{\n.reg .pred p;\nmbarrier.try_wait.parity.shared::cta.b64 p, [%1], %2, 20000;\nselp.u32 %0, 1, 0, p;\n}\n" : "=r"(ok) : "r"(bar), "r"(parity) : "memory");
  return ok;
}
__device__ __forceinline__ bool mbar_test(uint32_t bar, uint32_t parity) {
  uint32_t ok;
  asm volatile("{\n.reg .pred p;\nmbarrier.test_wait.parity.shared::cta.b64 p, [%1], %2;\nselp.u32 %0, 1, 0, p;\n}\n" : "=r"(ok) : "r"(bar), "r"(parity) : "memory");
  return ok;
}
__device__ __forceinline__ void mbar_wait(uint32_t bar, uint32_t parity) {
  asm volatile("{\n.reg .pred p;\nWAIT_LOOP:\nbar.warp.sync -1;\nmbarrier.try_wait.parity.shared::cta.b64 p, [%0], %1;\n@!p bra WAIT_LOOP;\n}\n" ::"r"(bar), "r"(parity) : "memory");
}
__device__ __forceinline__ void mbar_wait1(uint32_t bar, uint32_t parity) {
  asm volatile("{\n.reg .pred p;\nWAIT_LOOP:\nbar.warp.sync -1;\nmbarrier.try_wait.parity.shared::cta.b64 p, [%0], %1, 4000;\n@!p bra WAIT_LOOP;\n}\n" ::"r"(bar), "r"(parity) : "memory");
}
constexpr uint64_t EV_NORMAL = 0x1000000000000000ull, EV_FIRST = 0x12F0000000000000ull;
__device__ __forceinline__ uint32_t ldg_stream(const uint32_t* p) {
  uint32_t r; asm volatile("ld.global.nc.L1::no_allocate.L2::cache_hint.b32 %0, [%1], %2;" : "=r"(r) : "l"(p), "l"(EV_FIRST)); return r;
}
__device__ __forceinline__ void tma2d(uint32_t dst, const CUtensorMap* tm, int c0, int c1, uint32_t bar, uint64_t pol) {
  asm volatile("cp.async.bulk.tensor.2d.shared::cluster.global.mbarrier::complete_tx::bytes.L2::cache_hint [%0], [%1, {%3, %4}], [%2], %5;"
               ::"r"(dst), "l"(tm), "r"(bar), "r"(c0), "r"(c1), "l"(pol) : "memory");
}
__device__ __forceinline__ void tma2d_mc(uint32_t dst, const CUtensorMap* tm, int c0, int c1, uint32_t bar, uint64_t pol) {
  asm volatile("cp.async.bulk.tensor.2d.shared::cluster.global.mbarrier::complete_tx::bytes.multicast::cluster.L2::cache_hint [%0], [%1, {%3, %4}], [%2], %5, %6;"
               ::"r"(dst), "l"(tm), "r"(bar), "r"(c0), "r"(c1), "h"((uint16_t)3), "l"(pol) : "memory");
}
__device__ __forceinline__ void tma3d(uint32_t dst, const CUtensorMap* tm, int c0, int c1, int c2, uint32_t bar, uint64_t pol) {
  asm volatile("cp.async.bulk.tensor.3d.shared::cluster.global.mbarrier::complete_tx::bytes.L2::cache_hint [%0], [%1, {%3, %4, %5}], [%2], %6;"
               ::"r"(dst), "l"(tm), "r"(bar), "r"(c0), "r"(c1), "r"(c2), "l"(pol) : "memory");
}
__device__ __forceinline__ void tma3d_mc(uint32_t dst, const CUtensorMap* tm, int c0, int c1, int c2, uint32_t bar, uint64_t pol) {
  asm volatile("cp.async.bulk.tensor.3d.shared::cluster.global.mbarrier::complete_tx::bytes.multicast::cluster.L2::cache_hint [%0], [%1, {%3, %4, %5}], [%2], %6, %7;"
               ::"r"(dst), "l"(tm), "r"(bar), "r"(c0), "r"(c1), "r"(c2), "h"((uint16_t)3), "l"(pol) : "memory");
}
__device__ __forceinline__ void bulk_g2s(uint32_t dst, const void* src, uint32_t bytes, uint32_t bar, uint64_t pol) {
  asm volatile("cp.async.bulk.shared::cluster.global.mbarrier::complete_tx::bytes.L2::cache_hint [%0], [%1], %2, [%3], %4;"
               ::"r"(dst), "l"(src), "r"(bytes), "r"(bar), "l"(pol) : "memory");
}
__device__ __forceinline__ void tma2d_store(const CUtensorMap* tm, uint32_t src, int c0, int c1) {
  asm volatile("cp.async.bulk.tensor.2d.global.shared::cta.bulk_group [%0, {%2, %3}], [%1];" ::"l"(tm), "r"(src), "r"(c0), "r"(c1) : "memory");
}
__device__ __forceinline__ void prefetch_tm(const CUtensorMap* tm) { asm volatile("prefetch.tensormap [%0];" ::"l"(tm) : "memory"); }
__device__ __forceinline__ void wg_fence() { asm volatile("wgmma.fence.sync.aligned;" ::: "memory"); }
__device__ __forceinline__ void wg_commit() { asm volatile("wgmma.commit_group.sync.aligned;" ::: "memory"); }
template <int N> __device__ __forceinline__ void wg_wait() { asm volatile("wgmma.wait_group.sync.aligned %0;" ::"n"(N) : "memory"); }
__device__ __forceinline__ void bar_sync(int id, int n) { asm volatile("bar.sync %0, %1;" ::"r"(id), "r"(n) : "memory"); }
__device__ __forceinline__ void bar_arrive(int id, int n) { asm volatile("bar.arrive %0, %1;" ::"r"(id), "r"(n) : "memory"); }
__device__ __forceinline__ void fence_async_smem() { asm volatile("fence.proxy.async.shared::cta;" ::: "memory"); }
__device__ __forceinline__ void fence_async_all() { asm volatile("fence.proxy.async.global;" ::: "memory"); }
__device__ __forceinline__ uint32_t pack_bf16(float lo, float hi) { uint32_t r; asm("cvt.rn.bf16x2.f32 %0, %1, %2;" : "=r"(r) : "f"(hi), "f"(lo)); return r; }
__device__ __forceinline__ float ex2(float x) { float r; asm("ex2.approx.ftz.f32 %0, %1;" : "=f"(r) : "f"(x)); return r; }
__device__ __forceinline__ float rcp(float x) { float r; asm("rcp.approx.ftz.f32 %0, %1;" : "=f"(r) : "f"(x)); return r; }
__device__ __forceinline__ void flag_wait(const unsigned* f, unsigned target) {
  unsigned v;
  do { asm volatile("ld.acquire.gpu.global.u32 %0, [%1];" : "=r"(v) : "l"(f) : "memory"); } while (__any_sync(0xffffffffu, v < target));
}
__device__ __forceinline__ bool elect() {
  uint32_t r;
  asm volatile("{\n.reg .pred p;\nelect.sync _|p, -1;\nselp.u32 %0, 1, 0, p;\n}\n" : "=r"(r));
  return r;
}
__device__ __forceinline__ void fence_release() { asm volatile("fence.release.gpu;" ::: "memory"); }
__device__ __forceinline__ void flag_add(unsigned* f) { asm volatile("red.relaxed.gpu.global.inc.u32 [%0], 0x7fffffff;" ::"l"(f) : "memory"); }
__device__ __forceinline__ void cluster_arrive() { asm volatile("barrier.cluster.arrive.relaxed.aligned;" ::: "memory"); }
__device__ __forceinline__ void cluster_wait() { asm volatile("barrier.cluster.wait.aligned;" ::: "memory"); }
__device__ __forceinline__ uint32_t hmul2(uint32_t a, uint32_t b) { uint32_t r; asm("mul.rn.bf16x2 %0, %1, %2;" : "=r"(r) : "r"(a), "r"(b)); return r; }
__device__ __forceinline__ uint32_t hadd2(uint32_t a, uint32_t b) { uint32_t r; asm("add.rn.bf16x2 %0, %1, %2;" : "=r"(r) : "r"(a), "r"(b)); return r; }
__device__ __forceinline__ uint32_t hfma2(uint32_t a, uint32_t b, uint32_t c) { uint32_t r; asm("fma.rn.bf16x2 %0, %1, %2, %3;" : "=r"(r) : "r"(a), "r"(b), "r"(c)); return r; }
__device__ __forceinline__ uint32_t lds32(uint32_t a) { uint32_t r; asm volatile("ld.shared.b32 %0, [%1];" : "=r"(r) : "r"(a) : "memory"); return r; }
__device__ __forceinline__ uint4 lds128(uint32_t a) { uint4 r; asm volatile("ld.shared.v4.b32 {%0,%1,%2,%3}, [%4];" : "=r"(r.x), "=r"(r.y), "=r"(r.z), "=r"(r.w) : "r"(a) : "memory"); return r; }
__device__ __forceinline__ uint32_t desc_k(uint32_t addr) { return ((addr & 0x3FFFF) >> 4) | (1u << 16); }
template <int LBO> __device__ __forceinline__ uint32_t desc_mn(uint32_t addr) { return ((addr & 0x3FFFF) >> 4) | ((uint32_t)(LBO >> 4) << 16); }
#define DHI "0x40000040"

#define R8(d, o) "+f"(d[o]), "+f"(d[o + 1]), "+f"(d[o + 2]), "+f"(d[o + 3]), "+f"(d[o + 4]), "+f"(d[o + 5]), "+f"(d[o + 6]), "+f"(d[o + 7])
#define R32(d, o) R8(d, o), R8(d, o + 8), R8(d, o + 16), R8(d, o + 24)
#define R64(d, o) R32(d, o), R32(d, o + 32)
#define L64 "%0,%1,%2,%3,%4,%5,%6,%7,%8,%9,%10,%11,%12,%13,%14,%15,%16,%17,%18,%19,%20,%21,%22,%23,%24,%25,%26,%27,%28,%29,%30,%31," \
            "%32,%33,%34,%35,%36,%37,%38,%39,%40,%41,%42,%43,%44,%45,%46,%47,%48,%49,%50,%51,%52,%53,%54,%55,%56,%57,%58,%59,%60,%61,%62,%63"
#define L128 L64 ",%64,%65,%66,%67,%68,%69,%70,%71,%72,%73,%74,%75,%76,%77,%78,%79,%80,%81,%82,%83,%84,%85,%86,%87,%88,%89,%90,%91,%92,%93,%94,%95," \
            "%96,%97,%98,%99,%100,%101,%102,%103,%104,%105,%106,%107,%108,%109,%110,%111,%112,%113,%114,%115,%116,%117,%118,%119,%120,%121,%122,%123,%124,%125,%126,%127"

template <int TB> __device__ __forceinline__ void mma_ss_n128(float (&d)[64], uint32_t da, uint32_t db) {
  asm volatile("{\n.reg .b64 da, db;\nmov.b64 da, {%64, " DHI "};\nmov.b64 db, {%65, " DHI "};\n"
               "wgmma.mma_async.sync.aligned.m64n128k16.f32.bf16.bf16 {" L64 "}, da, db, 1, 1, 1, 0, %66;\n}\n"
               : R64(d, 0) : "r"(da), "r"(db), "n"(TB));
}
template <int TB> __device__ __forceinline__ void mma_rs_n128(float (&d)[64], uint32_t a0, uint32_t a1, uint32_t a2, uint32_t a3, uint32_t db, int sd) {
  asm volatile("{\n.reg .pred p;\n.reg .b64 db;\nsetp.ne.b32 p, %69, 0;\nmov.b64 db, {%68, " DHI "};\n"
               "wgmma.mma_async.sync.aligned.m64n128k16.f32.bf16.bf16 {" L64 "}, {%64,%65,%66,%67}, db, p, 1, 1, %70;\n}\n"
               : R64(d, 0) : "r"(a0), "r"(a1), "r"(a2), "r"(a3), "r"(db), "r"(sd), "n"(TB));
}
template <int TB> __device__ __forceinline__ void mma_ss_n256(float (&d)[128], uint32_t da, uint32_t db) {
  asm volatile("{\n.reg .b64 da, db;\nmov.b64 da, {%128, " DHI "};\nmov.b64 db, {%129, " DHI "};\n"
               "wgmma.mma_async.sync.aligned.m64n256k16.f32.bf16.bf16 {" L128 "}, da, db, 1, 1, 1, 0, %130;\n}\n"
               : R64(d, 0), R64(d, 64) : "r"(da), "r"(db), "n"(TB));
}
#define W8(d, o) "=f"(d[o]), "=f"(d[o + 1]), "=f"(d[o + 2]), "=f"(d[o + 3]), "=f"(d[o + 4]), "=f"(d[o + 5]), "=f"(d[o + 6]), "=f"(d[o + 7])
#define W32(d, o) W8(d, o), W8(d, o + 8), W8(d, o + 16), W8(d, o + 24)
#define W64(d, o) W32(d, o), W32(d, o + 32)
template <int TB> __device__ __forceinline__ void mma_ss_n128_init(float (&d)[64], uint32_t da, uint32_t db) {
  asm volatile("{\n.reg .b64 da, db;\nmov.b64 da, {%64, " DHI "};\nmov.b64 db, {%65, " DHI "};\n"
               "wgmma.mma_async.sync.aligned.m64n128k16.f32.bf16.bf16 {" L64 "}, da, db, 0, 1, 1, 0, %66;\n}\n"
               : W64(d, 0) : "r"(da), "r"(db), "n"(TB));
}
template <int TB> __device__ __forceinline__ void mma_ss_n256_init(float (&d)[128], uint32_t da, uint32_t db) {
  asm volatile("{\n.reg .b64 da, db;\nmov.b64 da, {%128, " DHI "};\nmov.b64 db, {%129, " DHI "};\n"
               "wgmma.mma_async.sync.aligned.m64n256k16.f32.bf16.bf16 {" L128 "}, da, db, 0, 1, 1, 0, %130;\n}\n"
               : W64(d, 0), W64(d, 64) : "r"(da), "r"(db), "n"(TB));
}
#define L32 "%0,%1,%2,%3,%4,%5,%6,%7,%8,%9,%10,%11,%12,%13,%14,%15,%16,%17,%18,%19,%20,%21,%22,%23,%24,%25,%26,%27,%28,%29,%30,%31"
__device__ __forceinline__ void mma_ss_n64(float (&d)[32], uint32_t da, uint32_t db) {
  asm volatile("{\n.reg .b64 da, db;\nmov.b64 da, {%32, " DHI "};\nmov.b64 db, {%33, " DHI "};\n"
               "wgmma.mma_async.sync.aligned.m64n64k16.f32.bf16.bf16 {" L32 "}, da, db, 1, 1, 1, 0, 0;\n}\n"
               : R32(d, 0) : "r"(da), "r"(db));
}
__device__ __forceinline__ void mma_ss_n64_init(float (&d)[32], uint32_t da, uint32_t db) {
  asm volatile("{\n.reg .b64 da, db;\nmov.b64 da, {%32, " DHI "};\nmov.b64 db, {%33, " DHI "};\n"
               "wgmma.mma_async.sync.aligned.m64n64k16.f32.bf16.bf16 {" L32 "}, da, db, 0, 1, 1, 0, 0;\n}\n"
               : W32(d, 0) : "r"(da), "r"(db));
}
#define L16 "%0,%1,%2,%3,%4,%5,%6,%7,%8,%9,%10,%11,%12,%13,%14,%15"
template <int O, bool INIT> __device__ __forceinline__ void mma_rs_n32(float (&d)[128], uint32_t a0, uint32_t a1, uint32_t a2, uint32_t a3, uint32_t db) {
  if (INIT) asm volatile("{\n.reg .b64 db;\nmov.b64 db, {%20, 0x00000008};\n"
               "wgmma.mma_async.sync.aligned.m64n32k16.f32.bf16.bf16 {" L16 "}, {%16,%17,%18,%19}, db, 0, 1, 1, 0;\n}\n"
               : W8(d, O), W8(d, O + 8) : "r"(a0), "r"(a1), "r"(a2), "r"(a3), "r"(db));
  else asm volatile("{\n.reg .b64 db;\nmov.b64 db, {%20, 0x00000008};\n"
               "wgmma.mma_async.sync.aligned.m64n32k16.f32.bf16.bf16 {" L16 "}, {%16,%17,%18,%19}, db, 1, 1, 1, 0;\n}\n"
               : R8(d, O), R8(d, O + 8) : "r"(a0), "r"(a1), "r"(a2), "r"(a3), "r"(db));
}
template <int O, bool INIT> __device__ __forceinline__ void mma_rs_n64(float (&d)[128], uint32_t a0, uint32_t a1, uint32_t a2, uint32_t a3, uint32_t db) {
  if (INIT) asm volatile("{\n.reg .b64 db;\nmov.b64 db, {%36, 0x00000008};\n"
               "wgmma.mma_async.sync.aligned.m64n64k16.f32.bf16.bf16 {" L32 "}, {%32,%33,%34,%35}, db, 0, 1, 1, 0;\n}\n"
               : W32(d, O) : "r"(a0), "r"(a1), "r"(a2), "r"(a3), "r"(db));
  else asm volatile("{\n.reg .b64 db;\nmov.b64 db, {%36, 0x00000008};\n"
               "wgmma.mma_async.sync.aligned.m64n64k16.f32.bf16.bf16 {" L32 "}, {%32,%33,%34,%35}, db, 1, 1, 1, 0;\n}\n"
               : R32(d, O) : "r"(a0), "r"(a1), "r"(a2), "r"(a3), "r"(db));
}
template <int S, int J> __device__ __forceinline__ void conv_step(float (&d)[128], const uint32_t (&a)[64], uint32_t db) {
  if constexpr (J >= 0 && J >= (S >> 1)) {
    if constexpr (J >= 8 - 2 * CWIDE) {
      mma_rs_n64<16 * (J - 1), S == 0>(d, a[4 * S], a[4 * S + 1], a[4 * S + 2], a[4 * S + 3], db + (uint32_t)((2 * (J - 1) - S) * 16));
      conv_step<S, J - 2>(d, a, db);
    } else {
      mma_rs_n32<16 * J, S == 0>(d, a[4 * S], a[4 * S + 1], a[4 * S + 2], a[4 * S + 3], db + (uint32_t)((2 * J - S) * 16));
      conv_step<S, J - 1>(d, a, db);
    }
  }
}
__device__ __forceinline__ void mma_ss_n8(float (&d)[4], uint32_t da, uint32_t db) {
  asm volatile("{\n.reg .b64 da, db;\nmov.b64 da, {%4, " DHI "};\nmov.b64 db, {%5, 0x00000008};\n"
               "wgmma.mma_async.sync.aligned.m64n8k16.f32.bf16.bf16 {%0,%1,%2,%3}, da, db, 1, 1, 1, 0, 0;\n}\n"
               : "+f"(d[0]), "+f"(d[1]), "+f"(d[2]), "+f"(d[3]) : "r"(da), "r"(db));
}
template <int N> __device__ __forceinline__ void reg_fence(float (&d)[N]) {
#pragma unroll
  for (int i = 0; i < N; i++) asm volatile("" : "+f"(d[i])::"memory");
}
template <int N> __device__ __forceinline__ void reg_fence(uint32_t (&d)[N]) {
#pragma unroll
  for (int i = 0; i < N; i++) asm volatile("" : "+r"(d[i])::"memory");
}

struct __align__(64) Params {
  unsigned* flags;
  int zero;
  uint8_t pref[128];
  const __nv_bfloat16 *gate_w, *ak, *av, *shk, *ssk, *ssd;
  CUtensorMap x, c, wq, wuk, wuv, wo, y, out, w;
};

template <int O, int N, int M> __device__ __forceinline__ void pack_frag(const float (&acc)[N], uint32_t (&pk)[M]) {
#pragma unroll
  for (int i = 0; i < 32; i++) pk[i] = pack_bf16(acc[O + 2 * i], acc[O + 2 * i + 1]);
}
template <int N> __device__ __forceinline__ void pack_frag_scaled(const float (&acc)[N], uint32_t (&pk)[32], float s0, float s1) {
#pragma unroll
  for (int i = 0; i < 32; i++) { const float s = (i & 1) ? s1 : s0; pk[i] = pack_bf16(acc[2 * i] * s, acc[2 * i + 1] * s); }
}
template <int J0 = 0, int J1 = 8, int M> __device__ __forceinline__ void stsm_frag(const uint32_t (&pk)[M], uint32_t a) {
#pragma unroll
  for (int jj = J0; jj < J1; jj++)
    asm volatile("stmatrix.sync.aligned.m8n8.x4.shared.b16 [%0], {%1,%2,%3,%4};" ::"r"((a ^ ((jj & 3) << 5)) + (jj >> 2) * 16384),
                 "r"(pk[4 * jj]), "r"(pk[4 * jj + 1]), "r"(pk[4 * jj + 2]), "r"(pk[4 * jj + 3]) : "memory");
}

struct Cons {
  uint32_t sb;
  uint32_t pf;
  int wg, tid;
  __device__ __forceinline__ void wait_full(int g) { mbar_wait(sb + SM_BAR + (B_FULL + g) * 8, (pf >> g) & 1); pf ^= 1u << g; }
  uint32_t relb;
  __device__ __forceinline__ void release(int g, int n) {
    if (tid < 2 * n) asm volatile("mbarrier.arrive.shared::cluster.b64 _, [%0];" ::"r"(relb + g * 8) : "memory");
  }
  __device__ __forceinline__ void turn_begin() { bar_sync(1 + wg, 256); }
  __device__ __forceinline__ void turn_end() { bar_arrive(2 - wg, 256); }
  __device__ __forceinline__ void staged(int e) { __syncwarp(); if ((tid & 31) == 0) mbar_arrive(sb + SM_BAR + (B_EV + 2 * e + wg) * 8); }
  int zero;
  int rnd;
  uint32_t pfree;
  __device__ __forceinline__ void wait_stage_free() { mbar_wait(sb + SM_BAR + (B_FREE + wg) * 8, pfree); pfree ^= 1; }
  __device__ __forceinline__ bool try_full(int g) { return mbar_test(sb + SM_BAR + (B_FULL + g) * 8, (pf >> g) & 1); }
};

constexpr float SM_C = 0.08838834764831845f * 1.4426950408889634f;
struct SoftState { float m0, m1, l0, l1; int shifted; };
__device__ __forceinline__ void ex2_rot(float& t, float s, uint32_t never_zero) {
  asm("{\n.reg .pred p;\nsetp.ne.u32 p, %2, 0;\n@p ex2.approx.ftz.f32 %0, %1;\n}\n" : "+f"(t) : "f"(s), "r"(never_zero));
}
__device__ __forceinline__ void pin(float a, uint32_t never_zero) {
  asm volatile("{\n.reg .pred p;\nsetp.eq.u32 p, %1, 0;\n@p st.shared.f32 [%1], %0;\n}\n" ::"f"(a), "r"(never_zero) : "memory");
}
template <int O, int N> __device__ __forceinline__ void reg_fence_part(uint32_t (&d)[32]) {
#pragma unroll
  for (int i = O; i < O + N; i++) asm volatile("" : "+r"(d[i])::"memory");
}
template <int Q, int W, int N> __device__ __forceinline__ void exp_quarter(const float (&S)[N], uint32_t (&P)[32], float (&t)[ROT], float& s0, float& s1, uint32_t nz) {
#pragma unroll
  for (int i = 8 * Q; i < 8 * Q + 8; i++) {
    float& a = t[(2 * i) % ROT];
    float& b = t[(2 * i + 1) % ROT];
    if (2 * i < ROT) { a = ex2(S[2 * i]); b = ex2(S[2 * i + 1]); }
    else { ex2_rot(a, S[2 * i], nz); ex2_rot(b, S[2 * i + 1], nz); }
    if (i < 2) { if (i) s1 = a + b; else s0 = a + b; }
    else if (SUMV == 0) { if (i & 1) { s1 += a; s1 += b; } else { s0 += a; s0 += b; } }
    else { if (i & 1) s1 += a + b; else s0 += a + b; }
    if (i == 8 * Q) { pin(EXPV == 1 && Q ? s1 : s0, nz); wg_wait<W>(); reg_fence_part<8 * Q, 8>(P); }
    P[i] = pack_bf16(a, b);
  }
}
template <int N> __device__ __forceinline__ void shift_scores(float (&S)[N], float d0, float d1) {
#pragma unroll
  for (int i = 0; i < N; i++) S[i] -= (i & 2) ? d1 : d0;
}
__device__ __forceinline__ bool soft_high(float s0, float s1, float lim = SM_LIMIT) { return s0 > lim || s1 > lim; }
__device__ __forceinline__ bool soft_unsafe(float s0, float s1, bool first) {
  uint32_t b0 = __ballot_sync(0xffffffffu, s0 >= SM_LOW), b1 = __ballot_sync(0xffffffffu, s1 >= SM_LOW);
  b0 |= b0 >> 1; b0 |= b0 >> 2; b1 |= b1 >> 1; b1 |= b1 >> 2;
  return __any_sync(0xffffffffu, soft_high(s0, s1)) || (first && (b0 & b1 & 0x11111111u) != 0x11111111u);
}
template <int N> __device__ __forceinline__ void soft_fix(const float (&S)[N], float (&O)[64], SoftState& z, bool first, float& d0, float& d1) {
  d0 = d1 = first ? -INFINITY : 0.f;
#pragma unroll
  for (int j = 0; j < N / 4; j++) { d0 = fmaxf(d0, fmaxf(S[4 * j], S[4 * j + 1])); d1 = fmaxf(d1, fmaxf(S[4 * j + 2], S[4 * j + 3])); }
  d0 = fmaxf(d0, __shfl_xor_sync(0xffffffffu, d0, 1)); d1 = fmaxf(d1, __shfl_xor_sync(0xffffffffu, d1, 1));
  d0 = fmaxf(d0, __shfl_xor_sync(0xffffffffu, d0, 2)); d1 = fmaxf(d1, __shfl_xor_sync(0xffffffffu, d1, 2));
  const float sc0 = ex2(-fmaxf(d0, 0.f)), sc1 = ex2(-fmaxf(d1, 0.f));
  z.m0 += d0; z.m1 += d1; z.l0 *= sc0; z.l1 *= sc1; z.shifted = 1;
#pragma unroll
  for (int j = 0; j < 16; j++) { O[4 * j] *= sc0; O[4 * j + 1] *= sc0; O[4 * j + 2] *= sc1; O[4 * j + 3] *= sc1; }
}
template <int M> __device__ __forceinline__ void pin32(const uint32_t (&v)[M], uint32_t never_zero) {
#pragma unroll
  for (int i = 0; i < 32; i += 4)
    asm volatile("{\n.reg .pred p;\nsetp.eq.u32 p, %4, 0;\n@p st.shared.v4.b32 [%4], {%0,%1,%2,%3};\n}\n" ::"r"(v[i]), "r"(v[i + 1]), "r"(v[i + 2]), "r"(v[i + 3]), "r"(never_zero) : "memory");
}
template <int N> __device__ __forceinline__ void mask_diag(float (&S)[N], float nd) {
  asm volatile("" : "+f"(nd));
#pragma unroll
  for (int i = 0; i < 32; i++) {
    const float beyond = __saturatef(nd + (float)(8 * (i >> 2) + (i & 1) - 4 * (i & 2)));
    S[N - 32 + i] = fmaf(beyond, -3.0e38f, S[N - 32 + i]);
  }
}
__device__ __forceinline__ float quad_sum(float v) {
  v += __shfl_xor_sync(0xffffffffu, v, 1);
  v += __shfl_xor_sync(0xffffffffu, v, 2);
  return v;
}
__device__ __forceinline__ void issue_qk(float (&S)[64], uint32_t dq, uint32_t dk) {
  mma_ss_n128_init<0>(S, dq, dk);
#pragma unroll
  for (int s = 1; s < 8; s++) mma_ss_n128<0>(S, dq + (s >> 2) * 1024 + (s & 3) * 2, dk + (s >> 2) * 1024 + (s & 3) * 2);
}
__device__ __forceinline__ void issue_qk(float (&S)[32], uint32_t dq, uint32_t dk) {
  mma_ss_n64_init(S, dq, dk);
#pragma unroll
  for (int s = 1; s < 8; s++) mma_ss_n64(S, dq + (s >> 2) * 1024 + (s & 3) * 2, dk + (s >> 2) * 1024 + (s & 3) * 2);
}
template <int H> __device__ __forceinline__ void issue_pv(float (&O)[64], const uint32_t (&P)[32], uint32_t dv, int acc, bool on) {
  if (on) {
#pragma unroll
    for (int s = 4 * H; s < 4 * H + 4; s++) {
      mma_rs_n128<1>(O, P[4 * s], P[4 * s + 1], P[4 * s + 2], P[4 * s + 3], dv + s * 128, s != 0 ? 1 : acc);
      if (s & 1) wg_commit();
    }
  } else { wg_commit(); wg_commit(); }
}
constexpr uint32_t DG = GR >> 4;
__device__ __forceinline__ void stage_q2(Cons& c, const float (&O)[64], uint32_t (&P)[32], uint32_t stg) {
  wg_commit(); wg_commit(); wg_commit(); wg_commit();
  c.turn_end();
  pack_frag<0>(O, P);
  stsm_frag(P, stg);
  fence_async_smem();
}
__device__ __forceinline__ void attn_half(Cons& c, float (&O)[64], uint32_t (&P)[32], SoftState& z, uint32_t dk0, uint32_t dkk, uint32_t dv0, float dmask, int last) {
  float S[32];
  FTH(8 + last * 32, 0);
  c.turn_begin();
  FTH(9 + last * 32, 0);
  wg_fence();
  issue_qk(S, dk0 + (last ? 0 : 2 * DG), dkk + (last ? 8 : 4) * DG);
  wg_commit();
  issue_pv<0>(O, P, dv0 + 10 * DG, 1, last);
  issue_pv<1>(O, P, dv0 + 10 * DG, 1, last);
  c.turn_end();
  c.wait_full(last ? 12 : 6);
  FTH(10 + last * 32, 0);
  wg_wait<4>();
  reg_fence(S);
  FTH(11 + last * 32, 0);
  c.release(last ? 8 : 4, 2);
  mask_diag(S, dmask);
  float s0, s1, d0 = z.m0, d1 = z.m1;
#pragma unroll 1
  for (int pass = 0;; pass++) {
    if (z.shifted) shift_scores(S, d0, d1);
    float tr[ROT];
    exp_quarter<0, 3>(S, P, tr, s0, s1, c.sb);
    exp_quarter<1, 2>(S, P, tr, s0, s1, c.sb);
    pin(s1, c.sb); wg_wait<0>(); reg_fence_part<16, 16>(P); reg_fence(O);
    if (!soft_unsafe(s0, s1, !last) || pass) break;
    soft_fix(S, O, z, !last, d0, d1);
  }
  FTH(12 + last * 32, 0);
  z.l0 += s0; z.l1 += s1;
  c.release(10, last ? 2 : 0);
  if (!last) c.wait_full(8);
  FTH(13 + last * 32, 0);
}

template <int V> struct IC { static constexpr int value = V; };
__device__ __forceinline__ int conv_next(int g, bool spare) { return g >= NGR - 2 ? g - (NGR - 4) : !spare && g == 4 ? 1 : g + 2; }
__device__ __forceinline__ void conv_final(uint32_t rb, uint32_t yb, const uint4& u, uint32_t dd, bool on) {
  const uint4 q0 = lds128(rb), q1 = lds128(rb + 4096), q2 = lds128(rb + 8192), q3 = lds128(rb + 12288);
  auto fin = [&](uint32_t x0, uint32_t x1, uint32_t x2, uint32_t x3, uint32_t uu) {
    if (DFOLD) return hadd2(hadd2(x0, x1), hadd2(x2, x3));
    return hfma2(dd, __byte_perm(uu, uu, 0x1032), hadd2(hadd2(x0, x1), hadd2(x2, x3)));
  };
  asm volatile("{\n.reg .pred p;\nsetp.ne.b32 p, %5, 0;\n@p st.shared.v4.b32 [%0], {%1,%2,%3,%4};\n}\n" ::"r"(yb), "r"(fin(q0.x, q1.x, q2.x, q3.x, u.w)),
               "r"(fin(q0.y, q1.y, q2.y, q3.y, u.z)), "r"(fin(q0.z, q1.z, q2.z, q3.z, u.y)), "r"(fin(q0.w, q1.w, q2.w, q3.w, u.x)), "r"((int)on) : "memory");
}
__device__ __forceinline__ void conv_tasks(Cons& c, const Params& p, int ntask, bool last, bool spare, int ch, int chstep, uint32_t dd, uint32_t dkk, int w, int lane) {
  const uint32_t sb = c.sb;
  int g = 2 + c.wg;
  uint4 u0 = make_uint4(0, 0, 0, 0), u1 = u0;
  uint32_t rb = sb + g * GR;
  const uint32_t yb = sb + c.wg * 8192 + c.tid * 16;
  c.wait_full(g);
#pragma unroll 1
  for (int i = 0; i < ntask; i++) {
    const uint32_t base = sb + g * GR;
    FTC(0);
    uint32_t a[64];
    const uint32_t hb = base + WBYTES - 28 + (8 * w + (lane >> 2) + (lane & 3)) * 4;
    auto lda = [&](int s) {
      a[4 * s] = lds32(hb + s * 256); a[4 * s + 1] = lds32(hb + s * 256 + 128);
      a[4 * s + 2] = lds32(hb + s * 256 + 16); a[4 * s + 3] = lds32(hb + s * 256 + 144);
    };
    lda(0); lda(15); lda(1); lda(14);
    if (DFOLD) {
      const int gt = 8 * w + (lane >> 2) + (lane & 3);
      a[0] = hadd2(a[0], gt == 7 ? dd : 0u); a[2] = hadd2(a[2], gt == 3 ? dd : 0u);
    }
    float acc[128];
    const uint32_t db = dkk + ((WPL / 16 - 1) << 16) + g * DG + WZ / 16;
    FTC(2);
    c.turn_begin();
    FTC(3);
    auto pair = [&](auto kc) {
      constexpr int k = decltype(kc)::value;
      if (k < 7) wg_fence();
      if (k == 7 && !(last && i == ntask - 1)) c.turn_end();
      conv_step<k, 7>(acc, a, db);
      conv_step<15 - k, 7>(acc, a, db);
      if (k < 6) { lda(k + 2); lda(13 - k); }
      if (k == 0) conv_final(rb, yb, u0, dd, i > 0);
      if (k == 1) {
        conv_final(rb + 2048, yb + 2048, u1, dd, i > 0);
        __syncwarp();
        if (lane == 0 && i > 0) mbar_arrive(sb + SM_BAR + (B_EV + c.wg) * 8);
      }
      if (DFOLD) { if (k == 6) dd = __bfloat16_as_ushort(p.ssd[(ch + chstep) & (DM - 1)]); }
      else if (k == 6) {
        const uint32_t ub = base + WZ + 16 + (c.tid >> 1) * 32 + ((c.tid & 1) ^ 1) * WPL;
        u0 = lds128(ub); u1 = lds128(ub + 2048);
        dd = __bfloat16_as_ushort(p.ssd[ch]) * 0x10001u;
      }
    };
    pair(IC<0>()); pair(IC<1>()); pair(IC<2>()); pair(IC<3>()); pair(IC<4>()); pair(IC<5>()); pair(IC<6>()); pair(IC<7>());
    wg_commit();
    FTC(4);
    g = conv_next(g, spare);
    ch += chstep;
    rb = base + c.tid * 16;
    wg_wait<0>();
    reg_fence(acc);
    reg_fence(a);
    bar_sync(3 + c.wg, 128);
    FTC(5);
    const int tw = (lane & 3) + w;
    const uint32_t xb = base + w * 4096 + tw * 32 + (lane >> 2) * 4;
#pragma unroll
    for (int j = 0; j < 32; j++) {
      float v0 = acc[4 * j], v1 = acc[4 * j + 1];
      if (j > 0) { v0 += acc[j > 0 ? 4 * j - 2 : 0]; v1 += acc[j > 0 ? 4 * j - 1 : 0]; }
      uint32_t v = pack_bf16(v0, v1), ad = xb + j * 128;
      if (j == 31 && tw >= 4) { v = 0; ad -= 4096; }
      asm volatile("st.shared.b32 [%0], %1;" ::"r"(ad), "r"(v) : "memory");
    }
    c.wait_stage_free();
    if (i + 1 < ntask) c.wait_full(g);
    bar_sync(3 + c.wg, 128);
    FTC(6);
  }
  conv_final(rb, yb, u0, dd, true);
  conv_final(rb + 2048, yb + 2048, u1, dd, true);
  c.staged(0);
}

__global__ void __cluster_dims__(2, 1, 1) __launch_bounds__(NTHREADS, 1) mega_kernel(const __grid_constant__ Params p) {
  extern __shared__ __align__(1024) uint8_t smem_raw[];
  FTS(0);
  const uint32_t sb = smem_u32(smem_raw);
  const int wgi = __shfl_sync(0xffffffffu, threadIdx.x >> 7, 0);
  const int warp = __shfl_sync(0xffffffffu, threadIdx.x >> 5, 0);
  const uint32_t rank = blockIdx.x & 1;
  int slot;
  {
    uint32_t smid; asm volatile("mov.u32 %0, %smid;" : "=r"(smid));
    slot = p.pref[((smid >> 1) + (threadIdx.x & (smid >> 16))) & 127];
  }
  if (warp >= 3) {
    if (elect()) {
#pragma unroll
      for (int k = 0; k < 4; k++) mbar_init(sb + SM_BAR + ((warp - 3) * 4 + k) * 8, k == 1 && warp == 7 ? 11 : warp < (k ? 7 : 8) ? 1 : 4);
      if (warp == 7) mbar_expect_tx(sb + SM_BAR + B_SLOT * 8, 8);
      asm volatile("fence.mbarrier_init.release.cluster;" ::: "memory");
    }
    __syncwarp();
  }
  FTS(1);
  cluster_arrive();
  if (warp == 2) { prefetch_tm(&p.c); prefetch_tm(rank ? &p.wuv : &p.wuk); FTSW(5); }
  slot = __shfl_sync(0xffffffffu, slot, 0);
  const int pref = slot;
  if (warp < 4) {
    asm volatile("setmaxnreg.dec.sync.aligned.u32 40;");
    if (warp == 1 + 4 * rank) {
      unsigned taken = threadIdx.x == 32;
#pragma unroll 1
      for (int n = 0; n < NSLOT; n++) {
        asm volatile("{\n.reg .pred p;\nsetp.ne.b32 p, %0, 0;\n@p atom.relaxed.gpu.global.exch.b32 %0, [%1], 1;\n}\n" : "+r"(taken) : "l"(CLAIMP(slot)) : "memory");
        if (!__any_sync(0xffffffffu, taken)) break;
        slot = slot == NSLOT - 1 ? 0 : slot + 1;
      }
    }
    cluster_wait();
    if (threadIdx.x == 32) {
#pragma unroll
      for (int r = 0; r < 2; r++)
        asm volatile("{\n.reg .b32 a, b;\nmapa.shared::cluster.u32 a, %0, %1;\nadd.u32 b, a, %3;\nst.async.shared::cluster.mbarrier::complete_tx::bytes.u32 [b], %2, [a];\n}\n"
                     ::"r"(sb + SM_BAR + B_SLOT * 8), "r"(r), "r"(slot | pref << 8), "r"((V_SLOT - B_SLOT) * 8 + rank * 4) : "memory");
    }
    if (warp == 0) {
      if (elect()) {
#pragma unroll 1
        for (int kk = 0; kk < 4; kk++) {
          const int g0 = 2 + 3 * kk;
          const uint32_t fb = sb + SM_BAR + (B_FULL + g0) * 8;
          FTSW(kk);
          mbar_expect_tx(fb, 3 * GR);
          tma2d(sb + g0 * GR, &p.c, kk * 64, (KV_ROW(pref & 7, 0) + rank) * 128, fb, EV_NORMAL);
          tma3d_mc(sb + (g0 + 1 + rank) * GR, rank ? &p.wuv : &p.wuk, 0, kk * 64, ((pref & 56) >> 1) + 2 * KV_HEAD(pref & 7, 0), fb, POL_W);
        }
        FTSW(4);
        prefetch_tm(&p.x); prefetch_tm(&p.wq);
      }
    }
  }
  int grp, idx, lb;
  int cn, cch, cstep;
  bool spare, redo;
  auto get_slot = [&]() {
    mbar_wait(sb + SM_BAR + B_SLOT * 8, 0);
    const uint32_t sv0 = __shfl_sync(0xffffffffu, lds32(sb + SM_BAR + V_SLOT * 8), 0), sv1 = __shfl_sync(0xffffffffu, lds32(sb + SM_BAR + V_SLOT * 8 + 4), 0);
    grp = (sv0 & 255) >> 3; idx = sv0 & 7; lb = (sv0 & 255) * 2 + rank;
    spare = grp == 8; redo = spare || sv0 != sv1;
    cn = spare ? CN_SPARE : CN_MAIN; cch = spare ? lb - NMAIN : 4 * CN_SPARE + CN_MAIN * lb; cstep = spare ? 4 : 1;
    if (FINE_MODE != 7) TS(0);
  };

  if (wgi == 0) {
    asm volatile("setmaxnreg.dec.sync.aligned.u32 40;");
    const int lane = threadIdx.x & 31;
    cluster_arrive();
    get_slot();
    if (warp == 3) {
      if (!spare) {
        const int s0 = lb * 16;
#pragma unroll 1
        for (int cg = 0; cg < 16; cg++) {
          __nanosleep(PRE_SLEEP);
          const int ch = cg * 64 + 2 * lane;
          const uint32_t* kp = reinterpret_cast<const uint32_t*>(p.ak + (size_t)s0 * DM + ch);
          const uint32_t* vp = reinterpret_cast<const uint32_t*>(p.av + (size_t)s0 * DM + ch);
          const uint4 sw = __ldg(reinterpret_cast<const uint4*>(p.shk + ch * 4));
          uint32_t k3 = 0, k2 = 0, k1 = 0, k0 = 0, up = 0;
          if (lb > 0) { k3 = ldg_stream(kp - 4 * 512); k2 = ldg_stream(kp - 3 * 512); k1 = ldg_stream(kp - 2 * 512); k0 = ldg_stream(kp - 512); up = ldg_stream(vp - 512); }
          const uint32_t w0 = __byte_perm(sw.x, sw.z, 0x5410), w1 = __byte_perm(sw.x, sw.z, 0x7632);
          const uint32_t w2 = __byte_perm(sw.y, sw.w, 0x5410), w3 = __byte_perm(sw.y, sw.w, 0x7632);
          up = hmul2(hfma2(k0, w0, hfma2(k1, w1, hfma2(k2, w2, hmul2(k3, w3)))), up);
#pragma unroll 1
          for (int hb = 0; hb < 2; hb++) {
            uint32_t kk[8], u[8];
#pragma unroll
            for (int r = 0; r < 8; r++) { kk[r] = ldg_stream(kp + r * 512); u[r] = ldg_stream(vp + r * 512); }
#pragma unroll
            for (int r = 0; r < 8; r++) {
              k3 = k2; k2 = k1; k1 = k0; k0 = kk[r];
              u[r] = hmul2(hfma2(k0, w0, hfma2(k1, w1, hfma2(k2, w2, hmul2(k3, w3)))), u[r]);
            }
            if (lane == 0) asm volatile("cp.async.bulk.wait_group.read 0;" ::: "memory");
            __syncwarp();
            const uint32_t dst = sb + SM_UST + lane * 32 + ((lane & 4) << 2);
#pragma unroll
            for (int cc = 0; cc < 2; cc++) {
              const uint32_t sel = cc ? 0x7632 : 0x5410;
              asm volatile("st.shared.v4.b32 [%0], {%1,%2,%3,%4};" ::"r"(dst + cc * 1024), "r"(__byte_perm(u[6], u[5], sel)), "r"(__byte_perm(u[4], u[3], sel)),
                           "r"(__byte_perm(u[2], u[1], sel)), "r"(__byte_perm(u[0], up, sel)) : "memory");
              asm volatile("st.shared.v4.b32 [%0], {%1,%2,%3,%4};" ::"r"((dst ^ 16) + cc * 1024), "r"(__byte_perm(u[7], u[6], sel)), "r"(__byte_perm(u[5], u[4], sel)),
                           "r"(__byte_perm(u[3], u[2], sel)), "r"(__byte_perm(u[1], u[0], sel)) : "memory");
            }
            fence_async_smem();
            __syncwarp();
            if (lane == 0) {
              asm volatile("cp.async.bulk.tensor.3d.global.shared::cta.bulk_group [%0, {%2, %3, %4}], [%1];\ncp.async.bulk.commit_group;"
                           ::"l"(&p.w), "r"(sb + SM_UST), "r"(WZ / 2 + lb * 16 + (hb ^ 1) * (WPL / 2)), "r"(cg * 32), "r"(0) : "memory");
            }
            up = u[7];
            kp += 8 * 512; vp += 8 * 512;
          }
          if ((cg & (cg + 1)) == 0 && lane == 0) {
            asm volatile("cp.async.bulk.wait_group 0;" ::: "memory");
            fence_release();
            flag_add(FLAG(F_U + 32 - __clz(cg)));
          }
          TSW(10 + cg);
        }
      }
      if (lane == 0) {
        unsigned long long t0, t1;
        asm volatile("mov.u64 %0, %globaltimer;" : "=l"(t0));
        while (!mbar_try(sb + SM_BAR + B_DONE * 8, 0)) {
          asm volatile("mov.u64 %0, %globaltimer;" : "=l"(t1));
          if (t1 - t0 > 2000000000ull) __trap();
        }
      }
    } else if (warp != 0) {
      const int w = warp - 1, ne = 12 + (cn + 1 - w) / 2;
      uint32_t p0 = 0;
      int cg = 2 + w, ch = cch + w * cstep;
#pragma unroll 1
      for (int e = spare ? 12 : 0; e < ne; e++) {
        const int rnd = e >= 6, k = e - 6 * rnd, rt = k == 4 ? idx : 15 - idx;
        uint8_t* dst = k < 4 ? g_kv + (size_t)(((k & 1) * 16 + 2 * grp + KV_HEAD(idx, k >> 1)) * 16 + KV_ROW(idx, k >> 1) + rank) * 32768 + w * 8192
                     : k < 6 ? g_cimg + (size_t)(rt * 32 + 16 * rnd + 2 * grp + rank) * 32768 + (w ^ (k & 1)) * 8192
                             : reinterpret_cast<uint8_t*>(g_yT + (size_t)ch * SEQ);
        const uint32_t src = sb + w * 8192 + (k == 4 ? 2 * GR : 0);
        if (e == 6) flag_wait(FLAG(F_AD + grp), 32);
        mbar_wait1(sb + SM_BAR + (B_EV + (k == 4 ? 2 : 0) + w) * 8, k == 4 ? rnd : p0);
        if (k != 4) p0 ^= 1;
        if (lane < 4 && k >= 6 && (!spare || e < ne - 6)) mbar_arrive_cluster(sb + SM_BAR + (B_EMPTY + cg) * 8, lane & 1);
        fence_async_smem();
        if (elect()) {
#pragma unroll 1
          for (int i = 0; i < (k >= 6 ? 1 : 8); i++) {
            const uint32_t o = (i >> 2) * 16384 + (i & 3) * 2048;
            asm volatile("cp.async.bulk.global.shared::cta.bulk_group [%0], [%1], %2;" ::"l"(dst + o), "r"(src + o), "r"(k >= 6 ? 4096 : 2048) : "memory");
            asm volatile("cp.async.bulk.commit_group;\ncp.async.bulk.wait_group.read %0;" ::"n"(ST_OUT) : "memory");
          }
          asm volatile("cp.async.bulk.wait_group 0;" ::: "memory");
          if (k != 4) mbar_arrive(sb + SM_BAR + (B_FREE + w) * 8);
        }
        __syncwarp();
        if (lane < (k == 4 ? 4 : e == 11 || (e == ne - 1 && !spare) ? 2 : 0))
          mbar_arrive_cluster(sb + SM_BAR + (B_EMPTY + (k == 4 ? 2 : e == 11) + (lane >> 1)) * 8, lane & 1);
        if (k >= 3) {
          fence_release();
          const unsigned fl = k == 3 ? F_KV + rnd * 8 + grp : k < 6 ? F_CTX + rt * 2 + rnd : F_Y + ((unsigned)ch >> 7);
          if (lane <= (e == 5)) flag_add(FLAG(lane ? F_AD + grp : fl));
        }
        if (k >= 6) { cg = conv_next(cg, spare); ch += 2 * cstep; }
      }
      if (lane == 0) mbar_arrive(sb + SM_BAR + B_DONE * 8);
    } else {
      uint32_t pe = 0;
      auto acquire = [&](int g, int n, uint32_t m) {
        int i = g;
#pragma unroll 1
        do mbar_wait1(sb + SM_BAR + (B_EMPTY + i) * 8, (pe >> i) & 1); while (++i < g + n);
        pe ^= m << g;
      };
#pragma unroll 1
      for (int rnd = 0; rnd < (spare ? 0 : 2); rnd++) {
        const int hp = 16 * rnd + 2 * grp, head = hp + rank;
#pragma unroll 1
        for (int kk = rnd || redo ? 0 : 4; kk < 32; kk++) {
          const int g0 = 2 + 3 * (kk & 3);
          acquire(g0, kk < 4 ? 3 : 1, 7);
          if (elect()) {
            const uint32_t fb = sb + SM_BAR + (B_FULL + g0) * 8;
            mbar_expect_tx(fb, 3 * GR);
            if (kk < 16) {
              tma2d(sb + g0 * GR, &p.c, (kk & 7) * 64, (KV_ROW(idx, kk >> 3) + rank) * 128, fb, EV_NORMAL);
              tma3d_mc(sb + (g0 + 1 + rank) * GR, rank ? &p.wuv : &p.wuk, 0, (kk & 7) * 64, (hp + KV_HEAD(idx, kk >> 3)) * 2, fb, POL_W);
            } else {
              tma2d_mc(sb + (g0 + rank) * GR, &p.x, (kk - 16) * 64, (rank ? 15 - idx : idx) * 128, fb, EV_NORMAL);
              tma3d(sb + (g0 + 2) * GR, &p.wq, 0, (kk - 16) * 64, head * 2, fb, POL_W);
            }
          }
        }
        flag_wait(FLAG(F_KV + rnd * 8 + grp), 32);
        fence_async_all();
        acquire(2, 1, 3);
        int g0 = 4;
#pragma unroll 1
        for (int f = 0; f < 34; f++) {
          const bool isk = (f == 0) || ((f & 1) && f < 33);
          const int it = (f == 0) ? 0 : (f == 33) ? 16 : isk ? (f + 1) >> 1 : (f >> 1) - 1;
          const int blk = it == 0 ? idx : it <= idx ? it - 1 : it < 16 ? 15 - it : 15 - idx;
          acquire(g0, f < 5 ? 2 : 1, 3);
          if (elect()) {
            const uint32_t fb = sb + SM_BAR + (B_FULL + g0) * 8;
            mbar_expect_tx(fb, 2 * GR);
            bulk_g2s(sb + g0 * GR, g_kv + (size_t)(((isk ? 0 : 16) + (head & 15)) * 16 + blk) * 32768, 2 * GR, fb, POL_KV);
          }
          g0 = f == 12 ? 12 : g0 == 12 ? 4 : g0 + 2;
        }
      }
      if (spare) {
#pragma unroll 1
        for (int i = 0, g = 2; i < 32; i++) {
          acquire(g, 2, 3);
          if (elect()) {
            const uint32_t fb = sb + SM_BAR + (B_FULL + g) * 8;
            if (i == 0) { mbar_expect_tx(fb - 8, 2048); bulk_g2s(sb + GR, p.gate_w, 2048, fb - 8, EV_NORMAL); }
            mbar_expect_tx(fb, 2 * GR);
            tma2d(sb + g * GR, &p.x, (i & 7) * 128, (lb - NMAIN) * 512 + (i >> 3) * 128, fb, EV_NORMAL);
            tma2d(sb + (g + 1) * GR, &p.x, (i & 7) * 128 + 64, (lb - NMAIN) * 512 + (i >> 3) * 128, fb, EV_NORMAL);
          }
          g = g == NGR - 2 ? 2 : g + 2;
        }
      }
      auto conv_fill = [&](int g, int ch) {
        acquire(g, 1, 1);
        if (elect()) {
          const uint32_t fb = sb + SM_BAR + (B_FULL + g) * 8;
          mbar_expect_tx(fb, WBYTES + 4096);
          bulk_g2s(sb + g * GR, g_w + (size_t)ch * WSTRIDE, WBYTES, fb, POL_C);
          bulk_g2s(sb + g * GR + WBYTES, p.ssk + (size_t)ch * SEQ, 4096, fb, POL_C);
        }
      };
#pragma unroll 1
      for (int i = 0, g = 2; i < cn; i++) {
        if ((i & 15) == 0) { flag_wait(FLAG(F_U + (spare ? 32 - __clz(i >> 4) : 4)), NMAIN); fence_async_all(); }
        conv_fill(g + (i & 1), cch + i * cstep);
        if (i & 1) g = conv_next(g, spare);
      }
      if (!spare) {
        const int rt = 2 * grp + rank, ct = idx;
        int g0 = P3G;
        prefetch_tm(&p.y); prefetch_tm(&p.out);
#pragma unroll 1
        for (int kb = 0; kb < 66; kb++) {
          if (kb == 0 || kb == 32 || kb >= 64) {
            flag_wait(FLAG(kb < 64 ? F_CTX + rt * 2 + (kb >> 5) : kb == 64 ? F_GATE : F_Y + ct), kb <= 64 ? 32 : 128);
            fence_async_all();
          }
          acquire(g0, kb < 11 ? 2 : 1, 3);
          if (elect()) {
            const uint32_t fb = sb + SM_BAR + (B_FULL + g0) * 8;
            mbar_expect_tx(fb, kb == 64 ? 2 * GR + 512 : 2 * GR);
            if (kb <= 64) bulk_g2s(kb < 64 ? sb + g0 * GR : sb + SM_GATE, kb < 64 ? (const void*)(g_cimg + (size_t)(rt * 64 + kb) * GR) : (const void*)(g_gate + rt * 128), kb < 64 ? GR : 512, fb, POL_CTX);
            if (kb < 64) {
              tma2d_mc(sb + (g0 + 1) * GR + rank * 8192, &p.wo, ct * 128 + rank * 64, kb * 64, fb, POL_WO);
            } else {
              const CUtensorMap* tm = kb == 64 ? &p.x : &p.y;
              const int c0 = (kb == 64 ? ct : rt) * 128, c1 = (kb == 64 ? rt : ct) * 128;
              tma2d(sb + g0 * GR, tm, c0, c1, fb, EV_NORMAL);
              tma2d(sb + (g0 + 1) * GR, tm, c0 + 64, c1, fb, EV_NORMAL);
            }
          }
          g0 = g0 == 12 ? (kb == 3 ? 2 : 0) : g0 + 2;
        }
        unsigned n = 0;
        if (lane == 0) n = atomicInc(FLAG(F_EXIT), 0x7fffffffu);
        if (__any_sync(0xffffffffu, n == NMAIN - 1)) {
#pragma unroll
          for (int i = lane; i < 96; i += 32) *reinterpret_cast<uint2*>(FLAG(i)) = make_uint2(0, 0);
        }
      }
      if (lane == 0) mbar_arrive(sb + SM_BAR + B_DONE * 8);
    }
    __syncwarp();
    cluster_wait();
  } else {
    asm volatile("setmaxnreg.inc.sync.aligned.u32 232;");
    FTS(2);
    Cons c;
    c.sb = sb; c.pf = 0; c.wg = wgi - 1; c.tid = threadIdx.x & 127;
    const int lane = threadIdx.x & 31, t = lane & 3;
    const int row = c.wg * 64 + (warp & 3) * 16 + (lane >> 2);
    const uint32_t dkk = desc_k(sb), dk0 = dkk + c.wg * 512, dm0 = desc_mn<8192>(sb), dv0 = desc_mn<16384>(sb);
    const uint32_t dsw = DG + 512 - c.wg * 1024;
    if (c.wg == 1) bar_arrive(1, 256);
    c.pfree = 1;
    asm("mapa.shared::cluster.u32 %0, %1, %2;" : "=r"(c.relb) : "r"(sb + SM_BAR + (B_EMPTY + (c.tid >> 1)) * 8), "r"(c.tid & 1));
    c.zero = p.zero;
    c.rnd = 0;
    const uint32_t stg = sb + (c.wg * 64 + (warp & 3) * 16 + ((lane >> 3) & 1) * 8 + (lane & 7)) * 128 + (((lane >> 4) ^ (lane & 7)) << 4);

    uint32_t dd0;
    auto load_dd = [&]() { asm volatile("ld.global.nc.u16 %0, [%1];" : "=r"(dd0) : "l"(p.ssd + (unsigned)(cch + c.wg * cstep + (lane & c.zero)))); };
    int pass = c.zero;
#pragma unroll 1
    do {
    if (pass) {
      load_dd();
#pragma unroll 1
      for (int g = 2; g < NGR; g += 3) { mbar_wait(sb + SM_BAR + (B_FULL + g) * 8, 0); c.release(g, 3); }
      c.pf = 0x924;
    if (spare) {
      c.wait_full(1);
      int g = 2;
#pragma unroll 1
      for (int r = 0; r < 4; r++) {
        float d[4] = {0.f, 0.f, 0.f, 0.f}, e[4] = {0.f, 0.f, 0.f, 0.f};
#pragma unroll 1
        for (int kb = 0; kb < 16; kb += 2) {
          c.wait_full(g);
          wg_fence();
#pragma unroll 1
          for (int k = 0; k < 4; k++) {
            mma_ss_n8(d, dk0 + g * DG + k * 2, dkk + DG + kb * 8 + k * 2);
            mma_ss_n8(e, dk0 + (g + 1) * DG + k * 2, dkk + DG + kb * 8 + 8 + k * 2);
          }
          wg_commit();
          wg_wait<0>();
          c.release(g, 2);
          g = g == NGR - 2 ? 2 : g + 2;
        }
        reg_fence(d); reg_fence(e);
        d[0] += e[0]; d[2] += e[2];
        if (t == 0) {
          float* gp = g_gate + (unsigned)((lb - NMAIN) * 512 + r * 128 + row);
          gp[0] = rcp(1.f + ex2(-1.4426950408889634f * d[0])); gp[8] = rcp(1.f + ex2(-1.4426950408889634f * d[2]));
        }
      }
      fence_release();
      __syncwarp();
      if (lane == 0) flag_add(FLAG(F_GATE));
      TS(1);
    }
    } else cluster_wait();
    get_slot();
    } while (redo && !pass++);
    FTS(3);
    const float dmask = (float)(2 * t - (row & 63));
    uint32_t pv[32];
#pragma unroll 1
    for (int rnd = 0; rnd < (spare ? 0 : 2); rnd++) {
      float O[64];
      FTM(rnd * 8);
      FTG(0);
      FTH(56, c.rnd == rnd);
      c.wait_full(2);
      FTM(rnd * 8 + 1);
      FTH(57, c.rnd == rnd);
#pragma unroll 1
      for (int tile = c.zero; tile < 2; tile++) {
        float acc[128];
        const bool single = tile == 0;
        {
          FTG(tile * 32 + 1);
          const uint32_t a = dk0 + 2 * DG, b = dm0 + 3 * DG;
          c.turn_begin();
          FTG(tile * 32 + 2);
          FTH(58, c.rnd == rnd);
          wg_fence();
          mma_ss_n256_init<1>(acc, a, b);
#pragma unroll
          for (int k = 1; k < 4; k++) mma_ss_n256<1>(acc, a + k * 2, b + k * 128);
          wg_commit();
          if (single) c.turn_end();
          FTG(tile * 32 + 3);
        }
#pragma unroll 1
        for (int kb = 1; kb < 8; kb++) {
          const int g0 = 2 + 3 * (kb & 3);
          const uint32_t a = dk0 + g0 * DG, b = dm0 + (g0 + 1) * DG;
          const bool second = (kb == 1 && !single) || kb == 7;
          FTG(tile * 32 + kb * 4);
          if (!second) { wg_wait<0>(); c.release(2 + 3 * ((kb - 1) & 3), 3); }
          FTG(tile * 32 + kb * 4 + 1);
          c.wait_full(g0);
          if (!second) c.turn_begin();
          FTG(tile * 32 + kb * 4 + 2);
          wg_fence();
#pragma unroll
          for (int k = 0; k < 4; k++) mma_ss_n256<1>(acc, a + k * 2, b + k * 128);
          wg_commit();
          if (kb != 6) c.turn_end();
          if (second) { wg_wait<1>(); c.release(2 + 3 * ((kb - 1) & 3), 3); }
          FTG(tile * 32 + kb * 4 + 3);
          FTH(58 + kb, c.rnd == rnd || kb > 3);
          if (tile == 1 && kb == 3) { c.wait_stage_free(); stsm_frag<0, 4>(pv, stg); }
          if (tile == 1 && kb == 4) { stsm_frag<4, 8>(pv, stg); c.staged(0); }
        }
        c.rnd = rnd;
        c.wait_stage_free();
        const bool nxt = c.try_full(2);
        wg_wait<0>();
        reg_fence(acc);
        c.release(11, 3);
        pack_frag_scaled(acc, pv, SM_C, SM_C);
        stsm_frag(pv, stg);
        c.staged(0);
        pack_frag<64>(acc, pv);
        pin32(pv, sb);
        FTG(32 + tile * 32);
        if (!nxt) mbar_wait(sb + SM_BAR + (B_FULL + 2) * 8, (c.pf >> 2) & 1);
        c.pf ^= 4;
      }
      TS(1 + rnd * 3);
      FTM(rnd * 8 + 2);
      {
        float qa[64];
        float (&qb)[64] = O;
        {
          FTG(65);
          const uint32_t a = dk0 + 2 * DG, b = dm0 + 4 * DG;
          c.turn_begin();
          FTG(66);
          wg_fence();
          mma_ss_n128_init<1>(qa, a, b);
          mma_ss_n128_init<1>(qb, a + dsw, b);
#pragma unroll
          for (int k = 1; k < 4; k++) {
            mma_ss_n128<1>(qa, a + k * 2, b + k * 128);
            mma_ss_n128<1>(qb, a + dsw + k * 2, b + k * 128);
          }
          wg_commit();
          FTG(67);
        }
#pragma unroll 1
        for (int kb = 1; kb < 16; kb++) {
          const int g0 = 2 + 3 * (kb & 3);
          const uint32_t a = dk0 + g0 * DG, b = dm0 + (g0 + 2) * DG;
          const bool second = kb == 1 || kb == 15;
          FTG(64 + kb * 4);
          if (!second) { wg_wait<0>(); c.release(2 + 3 * ((kb - 1) & 3), 3); }
          FTG(65 + kb * 4);
          c.wait_full(g0);
          if (!second) c.turn_begin();
          FTG(66 + kb * 4);
          FTH(kb - 14, kb < 14);
          wg_fence();
#pragma unroll
          for (int k = 0; k < 4; k++) {
            mma_ss_n128<1>(qa, a + k * 2, b + k * 128);
            mma_ss_n128<1>(qb, a + dsw + k * 2, b + k * 128);
          }
          wg_commit();
          if (kb != 14) c.turn_end();
          if (second) { wg_wait<1>(); c.release(2 + 3 * ((kb - 1) & 3), 3); }
          FTG(67 + kb * 4);
          FTH(2, kb < 15);
          if (kb == QFLUSH) { c.wait_stage_free(); stsm_frag<0, 4>(pv, stg); }
          if (kb == QFLUSH + 1) { stsm_frag<4, 8>(pv, stg); c.staged(0); }
        }
        c.wait_stage_free();
        mbar_wait(sb + SM_BAR + (B_EMPTY + 2) * 8, rnd ^ !redo);
        FTM(rnd * 8 + 3);
        FTH(3, 0);
        wg_wait<0>();
        reg_fence(qa); reg_fence(qb);
        FTH(4, 0);
        c.release(11, 3);
        pack_frag<0>(qa, pv);
        stsm_frag(pv, stg + 2 * GR);
        if (c.wg == 0) {
          pack_frag<0>(qb, pv);
          stsm_frag(pv, stg);
#pragma unroll
          for (int i = 16; i < 32; i++) pv[i] = 0;
        }
        fence_async_smem();
        c.wait_full(4);
      }
      TS(2 + rnd * 3);
      FTM(rnd * 8 + 4);
      FTH(5, 0);
      {
        const int nA = idx + 1;
        uint32_t (&P)[32] = pv;
        SoftState z;
        z.m0 = z.m1 = z.l0 = z.l1 = 0.f; z.shifted = c.zero;
#pragma unroll 1
        for (int seg = c.zero;; seg++) {
        if (c.wg == seg) attn_half(c, O, P, z, dk0, dkk, dv0, dmask, seg);
        if (seg) break;
        FTM(rnd * 8 + 5);
        int gk = c.wg ? 4 : 6, gv = c.wg ? 4 : 8;
        uint32_t dq = dk0 + (1 - c.wg < nA ? 2 * DG : 0), dk = dkk + gk * DG;
#pragma unroll 1
        for (int it = 1 - c.wg; it < 17 - c.wg; it++) {
          float S[64];
          FTA(it * 7 + 0); FTH((it < 3 ? 8 + it * 8 : it * 8 - 88) + 0, it >= 3 && it < 15);
          c.turn_begin();
          FTA(it * 7 + 2); FTH((it < 3 ? 8 + it * 8 : it * 8 - 88) + 1, it >= 3 && it < 15);
          wg_fence();
          issue_qk(S, dq, dk);
          wg_commit();
          const uint32_t dv = dv0 + gv * DG;
          uint32_t relk = c.relb + gk * 8, relv = c.relb + gv * 8;
          gk = it == 6 ? 12 : gv == 12 ? 4 : gv + 2;
          gv = it == 16 ? gk : gk == 12 ? 4 : gk + 2;
          uint32_t fk = sb + SM_BAR + (B_FULL + gk) * 8, fv = sb + SM_BAR + (B_FULL + gv) * 8, park = (c.pf >> gk) & 1, parv = (c.pf >> gv) & 1;
          c.pf ^= (1u << gk) | (1u << gv);
          dq = dk0 + (it + 1 < nA ? 2 * DG : 0); dk = dkk + gk * DG;
          float lo0 = z.l0, lo1 = z.l1;
          const bool first = it == nA || it == 0;
          if (it == nA) {
            if (EARLY_RCP) { lo0 = rcp(quad_sum(lo0)); lo1 = rcp(quad_sum(lo1)); }
            z.m0 = z.m1 = z.l0 = z.l1 = 0.f; z.shifted = 0;
          }
          float s0, s1, d0 = z.m0, d1 = z.m1;
          int pre = z.shifted || (it & 15) == 0;
          float lim = first ? -1.f : SM_LIMIT;
          asm volatile("" : "+r"(relk), "+r"(relv), "+r"(fk), "+r"(fv), "+r"(park), "+r"(parv), "+r"(dq), "+r"(dk), "+r"(pre), "+f"(lim), "+f"(d0), "+f"(d1), "+f"(z.l0), "+f"(z.l1));
          if (it) {
            issue_pv<0>(O, P, dv, it != nA + 1 && it != 1, true);
            issue_pv<1>(O, P, dv, 1, HALFPV ? it + c.wg > 1 : true);
            c.turn_end();
          } else stage_q2(c, O, P, stg);
          FTA(it * 7 + 3); FTH((it < 3 ? 8 + it * 8 : it * 8 - 88) + 2, it >= 3 && it < 15);
          wg_wait<4>();
          reg_fence(S);
          FTA(it * 7 + 4); FTH((it < 3 ? 8 + it * 8 : it * 8 - 88) + 3, it >= 3 && it < 15);
          if (c.tid < 4) asm volatile("mbarrier.arrive.shared::cluster.b64 _, [%0];" ::"r"(relk) : "memory");
#pragma unroll 1
          for (int pass = 0;; pass++) {
            if (pre) {
              if ((it & 15) == 0) mask_diag(S, dmask);
              if (z.shifted) shift_scores(S, d0, d1);
            }
            float tr[ROT];
            exp_quarter<0, 3>(S, P, tr, s0, s1, sb);
            exp_quarter<1, 2>(S, P, tr, s0, s1, sb);
            exp_quarter<2, 1>(S, P, tr, s0, s1, sb);
            exp_quarter<3, 0>(S, P, tr, s0, s1, sb);
            reg_fence(O);
            if (c.tid < (pass || !it ? 0 : 4)) asm volatile("mbarrier.arrive.shared::cluster.b64 _, [%0];" ::"r"(relv) : "memory");
            const bool ok = mbar_test(fk, park) & mbar_test(fv, parv);
            if (!ok) lim = -1.f;
            FTA(it * 7 + 5); FTH((it < 3 ? 8 + it * 8 : it * 8 - 88) + 4, it >= 3 && it < 15);
            if (!__any_sync(0xffffffffu, !(s0 <= lim && s1 <= lim))) break;
            if (pass) break;
            if (it == nA) {
              uint32_t pk[32];
              if (!EARLY_RCP) { lo0 = rcp(quad_sum(lo0)); lo1 = rcp(quad_sum(lo1)); }
              pack_frag_scaled(O, pk, lo0, lo1);
              stsm_frag(pk, stg + 2 * GR);
              c.staged(1);
            }
            if (!ok) { mbar_wait(fk, park); mbar_wait(fv, parv); }
            if (!soft_unsafe(s0, s1, first)) break;
            soft_fix(S, O, z, first, d0, d1);
            pre = 1;
          }
          z.l0 += s0; z.l1 += s1;
          FTA(it * 7 + 6); FTH((it < 3 ? 8 + it * 8 : it * 8 - 88) + 5, it >= 3 && it < 15);
        }
        FTM(rnd * 8 + 6);
        }
        FTH(48, 0);
        load_dd();
        c.turn_begin();
        FTH(49, 0);
        wg_fence();
        issue_pv<0>(O, P, dv0 + 12 * DG, 1, true);
        issue_pv<1>(O, P, dv0 + 12 * DG, 1, !c.wg);
        c.turn_end();
        z.l0 = rcp(quad_sum(z.l0)); z.l1 = rcp(quad_sum(z.l1));
        wg_wait<0>();
        reg_fence(O); reg_fence(P);
        FTH(50, 0);
        c.release(12, 2);
        pack_frag_scaled(O, P, z.l0, z.l1);
        stsm_frag(P, stg);
        c.staged(0);
        FTM(rnd * 8 + 7);
        FTH(51, 0);
      }
      TS(3 + rnd * 3);
    }
    conv_tasks(c, p, (cn + 1 - c.wg) / 2, ((cn - 1) & 1) == c.wg, spare, cch + c.wg * cstep, 2 * cstep, dd0, dkk, warp & 3, lane);
    if (c.wg == 1) c.pf ^= 0x14;
    TS(7);
    if (!spare) {
      const int rt = 2 * grp + rank, ct = idx;
      float acc[64];
      int g0 = P3G + 2, pg = P3G;
      {
        FTO(0);
        c.wait_full(P3G);
        FTO(1);
        const uint32_t a = dk0 + P3G * DG, b = dm0 + (P3G + 1) * DG;
        wg_fence();
        mma_ss_n128_init<1>(acc, a, b);
#pragma unroll
        for (int k = 1; k < 4; k++) mma_ss_n128<1>(acc, a + k * 2, b + k * 128);
        wg_commit();
      }
#pragma unroll 1
      for (int kb = 1; kb < 64; kb++) {
        FTO(kb * 2);
        c.wait_full(g0);
        FTO(kb * 2 + 1);
        const uint32_t a = dk0 + g0 * DG, b = dm0 + (g0 + 1) * DG;
        wg_fence();
#pragma unroll
        for (int k = 0; k < 4; k++) mma_ss_n128<1>(acc, a + k * 2, b + k * 128);
        wg_commit();
        wg_wait<1>();
        c.release(pg, kb <= 59 ? 2 : 0);
        if (kb == 40) FTDUMP();
        pg = g0;
        g0 = g0 == 12 ? (kb == 3 ? 2 : 0) : g0 + 2;
      }
      cluster_arrive();
      c.wait_full(P3X);
      c.wait_full(P3Y);
      const float g0f = __uint_as_float(lds32(sb + SM_GATE + row * 4)), g1f = __uint_as_float(lds32(sb + SM_GATE + row * 4 + 32));
      const uint32_t gp0 = pack_bf16(g0f, g0f), gp1 = pack_bf16(g1f, g1f);
      const float h0 = 1.f - g0f, h1 = 1.f - g1f;
      const int w = warp & 3;
      const uint32_t xa = stg + P3X * GR;
      const uint32_t ya = sb + P3Y * GR + c.wg * 16384 + ((lane >> 4) * 8 + (lane & 7)) * 128 + (((2 * w + ((lane >> 3) & 1)) ^ (lane & 7)) << 4);
      uint32_t xy[32];
#pragma unroll
      for (int jj = 0; jj < 8; jj++) {
        uint32_t x[4], y[4];
        asm volatile("ldmatrix.sync.aligned.m8n8.x4.shared.b16 {%0,%1,%2,%3}, [%4];" : "=r"(x[0]), "=r"(x[1]), "=r"(x[2]), "=r"(x[3]) : "r"((xa ^ ((jj & 3) << 5)) + (jj >> 2) * 16384) : "memory");
        asm volatile("ldmatrix.sync.aligned.m8n8.x4.trans.shared.b16 {%0,%1,%2,%3}, [%4];" : "=r"(y[0]), "=r"(y[1]), "=r"(y[2]), "=r"(y[3]) : "r"(ya + jj * 2048) : "memory");
#pragma unroll
        for (int i = 0; i < 4; i++) xy[4 * jj + i] = hmul2(x[i], y[i]);
      }
      wg_wait<0>();
      reg_fence(acc);
      TS(8);
#pragma unroll
      for (int i = 0; i < 32; i++) {
        const float h = (i & 1) ? h1 : h0;
        xy[i] = hfma2((i & 1) ? gp1 : gp0, xy[i], pack_bf16(acc[2 * i] * h, acc[2 * i + 1] * h));
      }
      stsm_frag(xy, xa);
      fence_async_smem();
      __syncwarp();
      if (lane == 0) {
        const int r0 = c.wg * 64 + w * 16;
        tma2d_store(&p.out, sb + P3X * GR + r0 * 128, ct * 128, rt * 128 + r0);
        tma2d_store(&p.out, sb + (P3X + 1) * GR + r0 * 128, ct * 128 + 64, rt * 128 + r0);
        asm volatile("cp.async.bulk.commit_group;\ncp.async.bulk.wait_group.read 0;" ::: "memory");
      }
    } else { FTDUMP(); cluster_arrive(); }
    if (lane == 0) mbar_arrive(sb + SM_BAR + B_DONE * 8);
    __syncwarp();
    TS(9);
    cluster_wait();
  }
}

typedef CUresult (*EncFn)(CUtensorMap*, CUtensorMapDataType, cuuint32_t, void*, const cuuint64_t*, const cuuint64_t*, const cuuint32_t*,
                          const cuuint32_t*, CUtensorMapInterleave, CUtensorMapSwizzle, CUtensorMapL2promotion, CUtensorMapFloatOOBfill);

void enc2d(EncFn enc, CUtensorMap* tm, const void* base, uint64_t cols, uint64_t rows, uint32_t bc, uint32_t br) {
  cuuint64_t dims[2] = {cols, rows}; cuuint64_t strides[1] = {cols * 2}; cuuint32_t box[2] = {bc, br}; cuuint32_t es[2] = {1, 1};
  enc(tm, CU_TENSOR_MAP_DATA_TYPE_BFLOAT16, 2, const_cast<void*>(base), dims, strides, box, es, CU_TENSOR_MAP_INTERLEAVE_NONE,
      CU_TENSOR_MAP_SWIZZLE_128B, CU_TENSOR_MAP_L2_PROMOTION_L2_256B, CU_TENSOR_MAP_FLOAT_OOB_FILL_NONE);
}
void enc3d(EncFn enc, CUtensorMap* tm, const void* base, uint64_t K, uint64_t N) {
  cuuint64_t dims[3] = {64, K, N / 64}; cuuint64_t strides[2] = {N * 2, 128}; cuuint32_t box[3] = {64, 64, 2}; cuuint32_t es[3] = {1, 1, 1};
  enc(tm, CU_TENSOR_MAP_DATA_TYPE_BFLOAT16, 3, const_cast<void*>(base), dims, strides, box, es, CU_TENSOR_MAP_INTERLEAVE_NONE,
      CU_TENSOR_MAP_SWIZZLE_128B, CU_TENSOR_MAP_L2_PROMOTION_L2_256B, CU_TENSOR_MAP_FLOAT_OOB_FILL_NONE);
}

}

extern "C" void kernel_launch(void* const* d_in, const int* in_sizes, int n_in, void* d_out, int out_size) {
  (void)in_sizes; (void)n_in; (void)out_size;
  typedef const __nv_bfloat16* BP;
  BP xq = (BP)d_in[0], ak = (BP)d_in[1], av = (BP)d_in[2], shk = (BP)d_in[3], ssk = (BP)d_in[4], ssd = (BP)d_in[5];
  BP ckv = (BP)d_in[7], wq = (BP)d_in[8], wuk = (BP)d_in[9], wuv = (BP)d_in[10], wo = (BP)d_in[11], gw = (BP)d_in[12];

  static EncFn enc = nullptr;
  if (!enc) {
    cudaDriverEntryPointQueryResult qr;
    cudaGetDriverEntryPoint("cuTensorMapEncodeTiled", (void**)&enc, cudaEnableDefault, &qr);
    cudaFuncSetAttribute(mega_kernel, cudaFuncAttributeMaxDynamicSharedMemorySize, SMEM_BYTES);
  }
  Params p;
  void* yT = nullptr;
  cudaGetSymbolAddress(&yT, g_yT);
  enc2d(enc, &p.x, xq, DM, SEQ, 64, 128);
  enc2d(enc, &p.c, ckv, DC, SEQ, 64, 128);
  enc3d(enc, &p.wq, wq, DM, NH * HD);
  enc3d(enc, &p.wuk, wuk, DC, NH * HD);
  enc3d(enc, &p.wuv, wuv, DC, NH * HD);
  enc2d(enc, &p.wo, wo, DM, NH * HD, 64, 64);
  enc2d(enc, &p.y, yT, SEQ, DM, 64, 128);
  enc2d(enc, &p.out, d_out, DM, SEQ, 64, 16);
  {
    void* wp = nullptr;
    cudaGetSymbolAddress(&wp, g_w);
    cuuint64_t dims[3] = {WSTRIDE / 2, DM / 2, 2}; cuuint64_t strides[2] = {2 * WSTRIDE, WSTRIDE}; cuuint32_t box[3] = {16, 32, 2}; cuuint32_t es[3] = {1, 1, 1};
    enc(&p.w, CU_TENSOR_MAP_DATA_TYPE_BFLOAT16, 3, wp, dims, strides, box, es, CU_TENSOR_MAP_INTERLEAVE_NONE,
        CU_TENSOR_MAP_SWIZZLE_32B, CU_TENSOR_MAP_L2_PROMOTION_NONE, CU_TENSOR_MAP_FLOAT_OOB_FILL_NONE);
  }
  p.zero = 0;
  cudaGetSymbolAddress((void**)&p.flags, g_flags);
  for (int i = 0; i < 128; i++) {
    const int tp = i % NSLOT;
    p.pref[i] = tp < 32 ? (tp & 7) * 8 + (tp >> 3) : tp < 60 ? (1 + (tp - 32) % 7) * 8 + 4 + (tp - 32) / 7 : tp < 62 ? tp + 4 : tp - 58;
  }
  p.gate_w = gw; p.ak = ak; p.av = av; p.shk = shk; p.ssk = ssk; p.ssd = ssd;

  mega_kernel<<<132, NTHREADS, SMEM_BYTES>>>(p);
}
```

```cpp
#include <cuda_runtime.h>
#include <cuda.h>
#include <cuda_bf16.h>
#include <stdint.h>

namespace {

constexpr int SEQ = 2048, DM = 1024, DC = 512, NH = 32, HD = 128;
constexpr int GR = 16384;
constexpr int NGR = 14;
constexpr int SM_BAR = NGR * GR;
constexpr int SM_GATE = SM_BAR + 512;
constexpr int SM_UST = SM_GATE + 512;
constexpr int SMEM_BYTES = SM_UST + 2048;
constexpr int NTHREADS = 384;
#define SM_LIMIT 1.0995116e12f
#define SM_LOW 9.094947e-13f
constexpr int CN_MAIN = 5, CN_SPARE = 96;
constexpr int P3G = 6, P3X = 10, P3Y = 12;
constexpr int NMAIN = 128;

constexpr int B_FULL = 0, B_FREE = 14, B_SLOT = 16, B_DONE = 17, B_EMPTY = 18, B_EV = 32, V_SLOT = 36;

__device__ __align__(1024) uint8_t g_kv[2 * 16 * 16 * 32768];
__device__ __align__(1024) uint8_t g_cimg[16 * NH * 32768];
__device__ __align__(1024) __nv_bfloat16 g_yT[DM * SEQ];
__device__ __align__(1024) float g_gate[SEQ];
#define CWIDE 0
constexpr int WZ = CWIDE ? 768 : 256, WPL = WZ + 4096, WBYTES = 2 * WPL + 32, WSTRIDE = 2 * WPL + 128;
__device__ __align__(1024) uint8_t g_w[DM * WSTRIDE];
__device__ __align__(32) unsigned g_flags[96 * 8];
constexpr int F_KV = 0, F_CTX = 16, F_U = 48, F_AD = 56, F_Y = 64, F_GATE = 72, F_EXIT = 73;
constexpr int NSLOT = 66;
#define FLAG(i) (&g_flags[(i) * 8])
#define CLAIMP(i) (p.flags + (i) * 8 + 1)

#define TS(slot)
#define TSW(slot)
#define FTX(i, off)
#define FTDUMP()

#define ST_OUT 0
#define QFLUSH 4
#define POL_W EV_NORMAL
#define POL_W2 EV_NORMAL
#define POL_WQ EV_NORMAL
#define POL_WO EV_FIRST
#define POL_KV EV_NORMAL
#define POL_C EV_FIRST
#define POL_CTX EV_FIRST
#define HALFPV 1
#define EXPV 1
#define SUMV 0
#define ROT 8
#define EARLY_RCP 1
#define KVARR 1
#define KV_ROW(idx, t) (KVARR ? 8 * (t) + 2 * ((idx) & 3) : 2 * (idx))
#define KV_HEAD(idx, t) (KVARR ? (idx) >> 2 : (t))
#define DFOLD 1
#define FINE_MODE 0
#define FDUMP_KB 40
#define FINE_RND 1
#define FTA(i) do { if (FINE_MODE == 0) FTX(i, rnd ^ FINE_RND); } while (0)
#define FTG(i) do { if (FINE_MODE == 1) FTX(i, rnd ^ FINE_RND); } while (0)
#define FTM(i) do { if (FINE_MODE == 4) FTX(i, 0); } while (0)
#define FTC(k) do { if (FINE_MODE == 5) FTX((i & 7) * 8 + (k), (i >> 3) ^ FINE_RND); } while (0)
#define FTH(i, off) do { if (FINE_MODE == 6) FTX(i, (c.rnd ^ FINE_RND) | (off)); } while (0)
#define FTS(i)
#define FTSD(i)
#define FTSW(i)
#define FTO(i) do { if (FINE_MODE == 2) FTX(i, 0); } while (0)

__device__ __forceinline__ uint32_t smem_u32(const void* p) { return (uint32_t)__cvta_generic_to_shared(p); }
__device__ __forceinline__ void mbar_init(uint32_t bar, int cnt) { asm volatile("mbarrier.init.shared::cta.b64 [%0], %1;" ::"r"(bar), "r"(cnt) : "memory"); }
__device__ __forceinline__ void mbar_expect_tx(uint32_t bar, uint32_t bytes) { asm volatile("mbarrier.arrive.expect_tx.shared::cta.b64 _, [%0], %1;" ::"r"(bar), "r"(bytes) : "memory"); }
__device__ __forceinline__ void mbar_arrive(uint32_t bar) { asm volatile("mbarrier.arrive.shared::cta.b64 _, [%0];" ::"r"(bar) : "memory"); }
__device__ __forceinline__ void mbar_arrive_cluster(uint32_t bar, uint32_t cta) {
  asm volatile("{\n.reg .b32 r;\nmapa.shared::cluster.u32 r, %0, %1;\nmbarrier.arrive.shared::cluster.b64 _, [r];\n}\n" ::"r"(bar), "r"(cta) : "memory");
}
__device__ __forceinline__ bool mbar_try(uint32_t bar, uint32_t parity) {
  uint32_t ok;
  asm volatile("{\n.reg .pred p;\nmbarrier.try_wait.parity.shared::cta.b64 p, [%1], %2, 20000;\nselp.u32 %0, 1, 0, p;\n}\n" : "=r"(ok) : "r"(bar), "r"(parity) : "memory");
  return ok;
}
__device__ __forceinline__ bool mbar_test(uint32_t bar, uint32_t parity) {
  uint32_t ok;
  asm volatile("{\n.reg .pred p;\nmbarrier.test_wait.parity.shared::cta.b64 p, [%1], %2;\nselp.u32 %0, 1, 0, p;\n}\n" : "=r"(ok) : "r"(bar), "r"(parity) : "memory");
  return ok;
}
__device__ __forceinline__ void mbar_wait(uint32_t bar, uint32_t parity) {
  asm volatile("{\n.reg .pred p;\nWAIT_LOOP:\nbar.warp.sync -1;\nmbarrier.try_wait.parity.shared::cta.b64 p, [%0], %1;\n@!p bra WAIT_LOOP;\n}\n" ::"r"(bar), "r"(parity) : "memory");
}
__device__ __forceinline__ void mbar_wait1(uint32_t bar, uint32_t parity) {
  asm volatile("{\n.reg .pred p;\nWAIT_LOOP:\nbar.warp.sync -1;\nmbarrier.try_wait.parity.shared::cta.b64 p, [%0], %1, 4000;\n@!p bra WAIT_LOOP;\n}\n" ::"r"(bar), "r"(parity) : "memory");
}
constexpr uint64_t EV_NORMAL = 0x1000000000000000ull, EV_FIRST = 0x12F0000000000000ull;
__device__ __forceinline__ uint32_t ldg_stream(const uint32_t* p) {
  uint32_t r; asm volatile("ld.global.nc.L1::no_allocate.L2::cache_hint.b32 %0, [%1], %2;" : "=r"(r) : "l"(p), "l"(EV_FIRST)); return r;
}
__device__ __forceinline__ void tma2d(uint32_t dst, const CUtensorMap* tm, int c0, int c1, uint32_t bar, uint64_t pol) {
  asm volatile("cp.async.bulk.tensor.2d.shared::cluster.global.mbarrier::complete_tx::bytes.L2::cache_hint [%0], [%1, {%3, %4}], [%2], %5;"
               ::"r"(dst), "l"(tm), "r"(bar), "r"(c0), "r"(c1), "l"(pol) : "memory");
}
__device__ __forceinline__ void tma2d_mc(uint32_t dst, const CUtensorMap* tm, int c0, int c1, uint32_t bar, uint64_t pol) {
  asm volatile("cp.async.bulk.tensor.2d.shared::cluster.global.mbarrier::complete_tx::bytes.multicast::cluster.L2::cache_hint [%0], [%1, {%3, %4}], [%2], %5, %6;"
               ::"r"(dst), "l"(tm), "r"(bar), "r"(c0), "r"(c1), "h"((uint16_t)3), "l"(pol) : "memory");
}
__device__ __forceinline__ void tma3d(uint32_t dst, const CUtensorMap* tm, int c0, int c1, int c2, uint32_t bar, uint64_t pol) {
  asm volatile("cp.async.bulk.tensor.3d.shared::cluster.global.mbarrier::complete_tx::bytes.L2::cache_hint [%0], [%1, {%3, %4, %5}], [%2], %6;"
               ::"r"(dst), "l"(tm), "r"(bar), "r"(c0), "r"(c1), "r"(c2), "l"(pol) : "memory");
}
__device__ __forceinline__ void tma3d_mc(uint32_t dst, const CUtensorMap* tm, int c0, int c1, int c2, uint32_t bar, uint64_t pol) {
  asm volatile("cp.async.bulk.tensor.3d.shared::cluster.global.mbarrier::complete_tx::bytes.multicast::cluster.L2::cache_hint [%0], [%1, {%3, %4, %5}], [%2], %6, %7;"
               ::"r"(dst), "l"(tm), "r"(bar), "r"(c0), "r"(c1), "r"(c2), "h"((uint16_t)3), "l"(pol) : "memory");
}
__device__ __forceinline__ void bulk_g2s(uint32_t dst, const void* src, uint32_t bytes, uint32_t bar, uint64_t pol) {
  asm volatile("cp.async.bulk.shared::cluster.global.mbarrier::complete_tx::bytes.L2::cache_hint [%0], [%1], %2, [%3], %4;"
               ::"r"(dst), "l"(src), "r"(bytes), "r"(bar), "l"(pol) : "memory");
}
__device__ __forceinline__ void tma2d_store(const CUtensorMap* tm, uint32_t src, int c0, int c1) {
  asm volatile("cp.async.bulk.tensor.2d.global.shared::cta.bulk_group [%0, {%2, %3}], [%1];" ::"l"(tm), "r"(src), "r"(c0), "r"(c1) : "memory");
}
__device__ __forceinline__ void prefetch_tm(const CUtensorMap* tm) { asm volatile("prefetch.tensormap [%0];" ::"l"(tm) : "memory"); }
__device__ __forceinline__ void wg_fence() { asm volatile("wgmma.fence.sync.aligned;" ::: "memory"); }
__device__ __forceinline__ void wg_commit() { asm volatile("wgmma.commit_group.sync.aligned;" ::: "memory"); }
template <int N> __device__ __forceinline__ void wg_wait() { asm volatile("wgmma.wait_group.sync.aligned %0;" ::"n"(N) : "memory"); }
__device__ __forceinline__ void bar_sync(int id, int n) { asm volatile("bar.sync %0, %1;" ::"r"(id), "r"(n) : "memory"); }
__device__ __forceinline__ void bar_arrive(int id, int n) { asm volatile("bar.arrive %0, %1;" ::"r"(id), "r"(n) : "memory"); }
__device__ __forceinline__ void fence_async_smem() { asm volatile("fence.proxy.async.shared::cta;" ::: "memory"); }
__device__ __forceinline__ void fence_async_all() { asm volatile("fence.proxy.async.global;" ::: "memory"); }
__device__ __forceinline__ uint32_t pack_bf16(float lo, float hi) { uint32_t r; asm("cvt.rn.bf16x2.f32 %0, %1, %2;" : "=r"(r) : "f"(hi), "f"(lo)); return r; }
__device__ __forceinline__ float ex2(float x) { float r; asm("ex2.approx.ftz.f32 %0, %1;" : "=f"(r) : "f"(x)); return r; }
__device__ __forceinline__ float rcp(float x) { float r; asm("rcp.approx.ftz.f32 %0, %1;" : "=f"(r) : "f"(x)); return r; }
__device__ __forceinline__ void flag_wait(const unsigned* f, unsigned target) {
  unsigned v;
  do { asm volatile("ld.acquire.gpu.global.u32 %0, [%1];" : "=r"(v) : "l"(f) : "memory"); } while (__any_sync(0xffffffffu, v < target));
}
__device__ __forceinline__ bool elect() {
  uint32_t r;
  asm volatile("{\n.reg .pred p;\nelect.sync _|p, -1;\nselp.u32 %0, 1, 0, p;\n}\n" : "=r"(r));
  return r;
}
__device__ __forceinline__ void fence_release() { asm volatile("fence.release.gpu;" ::: "memory"); }
__device__ __forceinline__ void flag_add(unsigned* f) { asm volatile("red.relaxed.gpu.global.inc.u32 [%0], 0x7fffffff;" ::"l"(f) : "memory"); }
__device__ __forceinline__ void cluster_arrive() { asm volatile("barrier.cluster.arrive.relaxed.aligned;" ::: "memory"); }
__device__ __forceinline__ void cluster_wait() { asm volatile("barrier.cluster.wait.aligned;" ::: "memory"); }
__device__ __forceinline__ uint32_t hmul2(uint32_t a, uint32_t b) { uint32_t r; asm("mul.rn.bf16x2 %0, %1, %2;" : "=r"(r) : "r"(a), "r"(b)); return r; }
__device__ __forceinline__ uint32_t hadd2(uint32_t a, uint32_t b) { uint32_t r; asm("add.rn.bf16x2 %0, %1, %2;" : "=r"(r) : "r"(a), "r"(b)); return r; }
__device__ __forceinline__ uint32_t hfma2(uint32_t a, uint32_t b, uint32_t c) { uint32_t r; asm("fma.rn.bf16x2 %0, %1, %2, %3;" : "=r"(r) : "r"(a), "r"(b), "r"(c)); return r; }
__device__ __forceinline__ uint32_t lds32(uint32_t a) { uint32_t r; asm volatile("ld.shared.b32 %0, [%1];" : "=r"(r) : "r"(a) : "memory"); return r; }
__device__ __forceinline__ uint4 lds128(uint32_t a) { uint4 r; asm volatile("ld.shared.v4.b32 {%0,%1,%2,%3}, [%4];" : "=r"(r.x), "=r"(r.y), "=r"(r.z), "=r"(r.w) : "r"(a) : "memory"); return r; }
__device__ __forceinline__ uint32_t desc_k(uint32_t addr) { return ((addr & 0x3FFFF) >> 4) | (1u << 16); }
template <int LBO> __device__ __forceinline__ uint32_t desc_mn(uint32_t addr) { return ((addr & 0x3FFFF) >> 4) | ((uint32_t)(LBO >> 4) << 16); }
#define DHI "0x40000040"

#define R8(d, o) "+f"(d[o]), "+f"(d[o + 1]), "+f"(d[o + 2]), "+f"(d[o + 3]), "+f"(d[o + 4]), "+f"(d[o + 5]), "+f"(d[o + 6]), "+f"(d[o + 7])
#define R32(d, o) R8(d, o), R8(d, o + 8), R8(d, o + 16), R8(d, o + 24)
#define R64(d, o) R32(d, o), R32(d, o + 32)
#define L64 "%0,%1,%2,%3,%4,%5,%6,%7,%8,%9,%10,%11,%12,%13,%14,%15,%16,%17,%18,%19,%20,%21,%22,%23,%24,%25,%26,%27,%28,%29,%30,%31," \
            "%32,%33,%34,%35,%36,%37,%38,%39,%40,%41,%42,%43,%44,%45,%46,%47,%48,%49,%50,%51,%52,%53,%54,%55,%56,%57,%58,%59,%60,%61,%62,%63"
#define L128 L64 ",%64,%65,%66,%67,%68,%69,%70,%71,%72,%73,%74,%75,%76,%77,%78,%79,%80,%81,%82,%83,%84,%85,%86,%87,%88,%89,%90,%91,%92,%93,%94,%95," \
            "%96,%97,%98,%99,%100,%101,%102,%103,%104,%105,%106,%107,%108,%109,%110,%111,%112,%113,%114,%115,%116,%117,%118,%119,%120,%121,%122,%123,%124,%125,%126,%127"

template <int TB> __device__ __forceinline__ void mma_ss_n128(float (&d)[64], uint32_t da, uint32_t db) {
  asm volatile("{\n.reg .b64 da, db;\nmov.b64 da, {%64, " DHI "};\nmov.b64 db, {%65, " DHI "};\n"
               "wgmma.mma_async.sync.aligned.m64n128k16.f32.bf16.bf16 {" L64 "}, da, db, 1, 1, 1, 0, %66;\n}\n"
               : R64(d, 0) : "r"(da), "r"(db), "n"(TB));
}
template <int TB> __device__ __forceinline__ void mma_rs_n128(float (&d)[64], uint32_t a0, uint32_t a1, uint32_t a2, uint32_t a3, uint32_t db, int sd) {
  asm volatile("{\n.reg .pred p;\n.reg .b64 db;\nsetp.ne.b32 p, %69, 0;\nmov.b64 db, {%68, " DHI "};\n"
               "wgmma.mma_async.sync.aligned.m64n128k16.f32.bf16.bf16 {" L64 "}, {%64,%65,%66,%67}, db, p, 1, 1, %70;\n}\n"
               : R64(d, 0) : "r"(a0), "r"(a1), "r"(a2), "r"(a3), "r"(db), "r"(sd), "n"(TB));
}
template <int TB> __device__ __forceinline__ void mma_ss_n256(float (&d)[128], uint32_t da, uint32_t db) {
  asm volatile("{\n.reg .b64 da, db;\nmov.b64 da, {%128, " DHI "};\nmov.b64 db, {%129, " DHI "};\n"
               "wgmma.mma_async.sync.aligned.m64n256k16.f32.bf16.bf16 {" L128 "}, da, db, 1, 1, 1, 0, %130;\n}\n"
               : R64(d, 0), R64(d, 64) : "r"(da), "r"(db), "n"(TB));
}
#define W8(d, o) "=f"(d[o]), "=f"(d[o + 1]), "=f"(d[o + 2]), "=f"(d[o + 3]), "=f"(d[o + 4]), "=f"(d[o + 5]), "=f"(d[o + 6]), "=f"(d[o + 7])
#define W32(d, o) W8(d, o), W8(d, o + 8), W8(d, o + 16), W8(d, o + 24)
#define W64(d, o) W32(d, o), W32(d, o + 32)
template <int TB> __device__ __forceinline__ void mma_ss_n128_init(float (&d)[64], uint32_t da, uint32_t db) {
  asm volatile("{\n.reg .b64 da, db;\nmov.b64 da, {%64, " DHI "};\nmov.b64 db, {%65, " DHI "};\n"
               "wgmma.mma_async.sync.aligned.m64n128k16.f32.bf16.bf16 {" L64 "}, da, db, 0, 1, 1, 0, %66;\n}\n"
               : W64(d, 0) : "r"(da), "r"(db), "n"(TB));
}
template <int TB> __device__ __forceinline__ void mma_ss_n256_init(float (&d)[128], uint32_t da, uint32_t db) {
  asm volatile("{\n.reg .b64 da, db;\nmov.b64 da, {%128, " DHI "};\nmov.b64 db, {%129, " DHI "};\n"
               "wgmma.mma_async.sync.aligned.m64n256k16.f32.bf16.bf16 {" L128 "}, da, db, 0, 1, 1, 0, %130;\n}\n"
               : W64(d, 0), W64(d, 64) : "r"(da), "r"(db), "n"(TB));
}
#define L32 "%0,%1,%2,%3,%4,%5,%6,%7,%8,%9,%10,%11,%12,%13,%14,%15,%16,%17,%18,%19,%20,%21,%22,%23,%24,%25,%26,%27,%28,%29,%30,%31"
__device__ __forceinline__ void mma_ss_n64(float (&d)[32], uint32_t da, uint32_t db) {
  asm volatile("{\n.reg .b64 da, db;\nmov.b64 da, {%32, " DHI "};\nmov.b64 db, {%33, " DHI "};\n"
               "wgmma.mma_async.sync.aligned.m64n64k16.f32.bf16.bf16 {" L32 "}, da, db, 1, 1, 1, 0, 0;\n}\n"
               : R32(d, 0) : "r"(da), "r"(db));
}
__device__ __forceinline__ void mma_ss_n64_init(float (&d)[32], uint32_t da, uint32_t db) {
  asm volatile("{\n.reg .b64 da, db;\nmov.b64 da, {%32, " DHI "};\nmov.b64 db, {%33, " DHI "};\n"
               "wgmma.mma_async.sync.aligned.m64n64k16.f32.bf16.bf16 {" L32 "}, da, db, 0, 1, 1, 0, 0;\n}\n"
               : W32(d, 0) : "r"(da), "r"(db));
}
#define L16 "%0,%1,%2,%3,%4,%5,%6,%7,%8,%9,%10,%11,%12,%13,%14,%15"
template <int O, bool INIT> __device__ __forceinline__ void mma_rs_n32(float (&d)[128], uint32_t a0, uint32_t a1, uint32_t a2, uint32_t a3, uint32_t db) {
  if (INIT) asm volatile("{\n.reg .b64 db;\nmov.b64 db, {%20, 0x00000008};\n"
               "wgmma.mma_async.sync.aligned.m64n32k16.f32.bf16.bf16 {" L16 "}, {%16,%17,%18,%19}, db, 0, 1, 1, 0;\n}\n"
               : W8(d, O), W8(d, O + 8) : "r"(a0), "r"(a1), "r"(a2), "r"(a3), "r"(db));
  else asm volatile("{\n.reg .b64 db;\nmov.b64 db, {%20, 0x00000008};\n"
               "wgmma.mma_async.sync.aligned.m64n32k16.f32.bf16.bf16 {" L16 "}, {%16,%17,%18,%19}, db, 1, 1, 1, 0;\n}\n"
               : R8(d, O), R8(d, O + 8) : "r"(a0), "r"(a1), "r"(a2), "r"(a3), "r"(db));
}
template <int O, bool INIT> __device__ __forceinline__ void mma_rs_n64(float (&d)[128], uint32_t a0, uint32_t a1, uint32_t a2, uint32_t a3, uint32_t db) {
  if (INIT) asm volatile("{\n.reg .b64 db;\nmov.b64 db, {%36, 0x00000008};\n"
               "wgmma.mma_async.sync.aligned.m64n64k16.f32.bf16.bf16 {" L32 "}, {%32,%33,%34,%35}, db, 0, 1, 1, 0;\n}\n"
               : W32(d, O) : "r"(a0), "r"(a1), "r"(a2), "r"(a3), "r"(db));
  else asm volatile("{\n.reg .b64 db;\nmov.b64 db, {%36, 0x00000008};\n"
               "wgmma.mma_async.sync.aligned.m64n64k16.f32.bf16.bf16 {" L32 "}, {%32,%33,%34,%35}, db, 1, 1, 1, 0;\n}\n"
               : R32(d, O) : "r"(a0), "r"(a1), "r"(a2), "r"(a3), "r"(db));
}
template <int S, int J> __device__ __forceinline__ void conv_step(float (&d)[128], const uint32_t (&a)[64], uint32_t db) {
  if constexpr (J >= 0 && J >= (S >> 1)) {
    if constexpr (J >= 8 - 2 * CWIDE) {
      mma_rs_n64<16 * (J - 1), S == 0>(d, a[4 * S], a[4 * S + 1], a[4 * S + 2], a[4 * S + 3], db + (uint32_t)((2 * (J - 1) - S) * 16));
      conv_step<S, J - 2>(d, a, db);
    } else {
      mma_rs_n32<16 * J, S == 0>(d, a[4 * S], a[4 * S + 1], a[4 * S + 2], a[4 * S + 3], db + (uint32_t)((2 * J - S) * 16));
      conv_step<S, J - 1>(d, a, db);
    }
  }
}
__device__ __forceinline__ void mma_ss_n8(float (&d)[4], uint32_t da, uint32_t db) {
  asm volatile("{\n.reg .b64 da, db;\nmov.b64 da, {%4, " DHI "};\nmov.b64 db, {%5, 0x00000008};\n"
               "wgmma.mma_async.sync.aligned.m64n8k16.f32.bf16.bf16 {%0,%1,%2,%3}, da, db, 1, 1, 1, 0, 0;\n}\n"
               : "+f"(d[0]), "+f"(d[1]), "+f"(d[2]), "+f"(d[3]) : "r"(da), "r"(db));
}
template <int N> __device__ __forceinline__ void reg_fence(float (&d)[N]) {
#pragma unroll
  for (int i = 0; i < N; i++) asm volatile("" : "+f"(d[i])::"memory");
}
template <int N> __device__ __forceinline__ void reg_fence(uint32_t (&d)[N]) {
#pragma unroll
  for (int i = 0; i < N; i++) asm volatile("" : "+r"(d[i])::"memory");
}

struct __align__(64) Params {
  unsigned* flags;
  int zero;
  uint8_t pref[128];
  const __nv_bfloat16 *gate_w, *ak, *av, *shk, *ssk, *ssd;
  CUtensorMap x, c, wq, wuk, wuv, wo, y, out, w;
};

template <int O, int N, int M> __device__ __forceinline__ void pack_frag(const float (&acc)[N], uint32_t (&pk)[M]) {
#pragma unroll
  for (int i = 0; i < 32; i++) pk[i] = pack_bf16(acc[O + 2 * i], acc[O + 2 * i + 1]);
}
template <int N> __device__ __forceinline__ void pack_frag_scaled(const float (&acc)[N], uint32_t (&pk)[32], float s0, float s1) {
#pragma unroll
  for (int i = 0; i < 32; i++) { const float s = (i & 1) ? s1 : s0; pk[i] = pack_bf16(acc[2 * i] * s, acc[2 * i + 1] * s); }
}
template <int J0 = 0, int J1 = 8, int M> __device__ __forceinline__ void stsm_frag(const uint32_t (&pk)[M], uint32_t a) {
#pragma unroll
  for (int jj = J0; jj < J1; jj++)
    asm volatile("stmatrix.sync.aligned.m8n8.x4.shared.b16 [%0], {%1,%2,%3,%4};" ::"r"((a ^ ((jj & 3) << 5)) + (jj >> 2) * 16384),
                 "r"(pk[4 * jj]), "r"(pk[4 * jj + 1]), "r"(pk[4 * jj + 2]), "r"(pk[4 * jj + 3]) : "memory");
}

struct Cons {
  uint32_t sb;
  uint32_t pf;
  int wg, tid;
  __device__ __forceinline__ void wait_full(int g) { mbar_wait(sb + SM_BAR + (B_FULL + g) * 8, (pf >> g) & 1); pf ^= 1u << g; }
  uint32_t relb;
  __device__ __forceinline__ void release(int g, int n) {
    if (tid < 2 * n) asm volatile("mbarrier.arrive.shared::cluster.b64 _, [%0];" ::"r"(relb + g * 8) : "memory");
  }
  __device__ __forceinline__ void turn_begin() { bar_sync(1 + wg, 256); }
  __device__ __forceinline__ void turn_end() { bar_arrive(2 - wg, 256); }
  __device__ __forceinline__ void staged(int e) { __syncwarp(); if ((tid & 31) == 0) mbar_arrive(sb + SM_BAR + (B_EV + 2 * e + wg) * 8); }
  int zero;
  int rnd;
  uint32_t pfree;
  __device__ __forceinline__ void wait_stage_free() { mbar_wait(sb + SM_BAR + (B_FREE + wg) * 8, pfree); pfree ^= 1; }
  __device__ __forceinline__ bool try_full(int g) { return mbar_test(sb + SM_BAR + (B_FULL + g) * 8, (pf >> g) & 1); }
};

constexpr float SM_C = 0.08838834764831845f * 1.4426950408889634f;
struct SoftState { float m0, m1, l0, l1; int shifted; };
__device__ __forceinline__ void ex2_rot(float& t, float s, uint32_t never_zero) {
  asm("{\n.reg .pred p;\nsetp.ne.u32 p, %2, 0;\n@p ex2.approx.ftz.f32 %0, %1;\n}\n" : "+f"(t) : "f"(s), "r"(never_zero));
}
__device__ __forceinline__ void pin(float a, uint32_t never_zero) {
  asm volatile("{\n.reg .pred p;\nsetp.eq.u32 p, %1, 0;\n@p st.shared.f32 [%1], %0;\n}\n" ::"f"(a), "r"(never_zero) : "memory");
}
template <int O, int N> __device__ __forceinline__ void reg_fence_part(uint32_t (&d)[32]) {
#pragma unroll
  for (int i = O; i < O + N; i++) asm volatile("" : "+r"(d[i])::"memory");
}
template <int Q, int W, int N> __device__ __forceinline__ void exp_quarter(const float (&S)[N], uint32_t (&P)[32], float (&t)[ROT], float& s0, float& s1, uint32_t nz) {
#pragma unroll
  for (int i = 8 * Q; i < 8 * Q + 8; i++) {
    float& a = t[(2 * i) % ROT];
    float& b = t[(2 * i + 1) % ROT];
    if (2 * i < ROT) { a = ex2(S[2 * i]); b = ex2(S[2 * i + 1]); }
    else { ex2_rot(a, S[2 * i], nz); ex2_rot(b, S[2 * i + 1], nz); }
    if (i < 2) { if (i) s1 = a + b; else s0 = a + b; }
    else if (SUMV == 0) { if (i & 1) { s1 += a; s1 += b; } else { s0 += a; s0 += b; } }
    else { if (i & 1) s1 += a + b; else s0 += a + b; }
    if (i == 8 * Q) { pin(EXPV == 1 && Q ? s1 : s0, nz); wg_wait<W>(); reg_fence_part<8 * Q, 8>(P); }
    P[i] = pack_bf16(a, b);
  }
}
template <int N> __device__ __forceinline__ void shift_scores(float (&S)[N], float d0, float d1) {
#pragma unroll
  for (int i = 0; i < N; i++) S[i] -= (i & 2) ? d1 : d0;
}
__device__ __forceinline__ bool soft_high(float s0, float s1, float lim = SM_LIMIT) { return s0 > lim || s1 > lim; }
__device__ __forceinline__ bool soft_unsafe(float s0, float s1, bool first) {
  uint32_t b0 = __ballot_sync(0xffffffffu, s0 >= SM_LOW), b1 = __ballot_sync(0xffffffffu, s1 >= SM_LOW);
  b0 |= b0 >> 1; b0 |= b0 >> 2; b1 |= b1 >> 1; b1 |= b1 >> 2;
  return __any_sync(0xffffffffu, soft_high(s0, s1)) || (first && (b0 & b1 & 0x11111111u) != 0x11111111u);
}
template <int N> __device__ __forceinline__ void soft_fix(const float (&S)[N], float (&O)[64], SoftState& z, bool first, float& d0, float& d1) {
  d0 = d1 = first ? -INFINITY : 0.f;
#pragma unroll
  for (int j = 0; j < N / 4; j++) { d0 = fmaxf(d0, fmaxf(S[4 * j], S[4 * j + 1])); d1 = fmaxf(d1, fmaxf(S[4 * j + 2], S[4 * j + 3])); }
  d0 = fmaxf(d0, __shfl_xor_sync(0xffffffffu, d0, 1)); d1 = fmaxf(d1, __shfl_xor_sync(0xffffffffu, d1, 1));
  d0 = fmaxf(d0, __shfl_xor_sync(0xffffffffu, d0, 2)); d1 = fmaxf(d1, __shfl_xor_sync(0xffffffffu, d1, 2));
  const float sc0 = ex2(-fmaxf(d0, 0.f)), sc1 = ex2(-fmaxf(d1, 0.f));
  z.m0 += d0; z.m1 += d1; z.l0 *= sc0; z.l1 *= sc1; z.shifted = 1;
#pragma unroll
  for (int j = 0; j < 16; j++) { O[4 * j] *= sc0; O[4 * j + 1] *= sc0; O[4 * j + 2] *= sc1; O[4 * j + 3] *= sc1; }
}
template <int M> __device__ __forceinline__ void pin32(const uint32_t (&v)[M], uint32_t never_zero) {
#pragma unroll
  for (int i = 0; i < 32; i += 4)
    asm volatile("{\n.reg .pred p;\nsetp.eq.u32 p, %4, 0;\n@p st.shared.v4.b32 [%4], {%0,%1,%2,%3};\n}\n" ::"r"(v[i]), "r"(v[i + 1]), "r"(v[i + 2]), "r"(v[i + 3]), "r"(never_zero) : "memory");
}
template <int N> __device__ __forceinline__ void mask_diag(float (&S)[N], float nd) {
  asm volatile("" : "+f"(nd));
#pragma unroll
  for (int i = 0; i < 32; i++) {
    const float beyond = __saturatef(nd + (float)(8 * (i >> 2) + (i & 1) - 4 * (i & 2)));
    S[N - 32 + i] = fmaf(beyond, -3.0e38f, S[N - 32 + i]);
  }
}
__device__ __forceinline__ float quad_sum(float v) {
  v += __shfl_xor_sync(0xffffffffu, v, 1);
  v += __shfl_xor_sync(0xffffffffu, v, 2);
  return v;
}
__device__ __forceinline__ void issue_qk(float (&S)[64], uint32_t dq, uint32_t dk) {
  mma_ss_n128_init<0>(S, dq, dk);
#pragma unroll
  for (int s = 1; s < 8; s++) mma_ss_n128<0>(S, dq + (s >> 2) * 1024 + (s & 3) * 2, dk + (s >> 2) * 1024 + (s & 3) * 2);
}
__device__ __forceinline__ void issue_qk(float (&S)[32], uint32_t dq, uint32_t dk) {
  mma_ss_n64_init(S, dq, dk);
#pragma unroll
  for (int s = 1; s < 8; s++) mma_ss_n64(S, dq + (s >> 2) * 1024 + (s & 3) * 2, dk + (s >> 2) * 1024 + (s & 3) * 2);
}
template <int H> __device__ __forceinline__ void issue_pv(float (&O)[64], const uint32_t (&P)[32], uint32_t dv, int acc, bool on) {
  if (on) {
#pragma unroll
    for (int s = 4 * H; s < 4 * H + 4; s++) {
      mma_rs_n128<1>(O, P[4 * s], P[4 * s + 1], P[4 * s + 2], P[4 * s + 3], dv + s * 128, s != 0 ? 1 : acc);
      if (s & 1) wg_commit();
    }
  } else { wg_commit(); wg_commit(); }
}
constexpr uint32_t DG = GR >> 4;
__device__ __forceinline__ void stage_q2(Cons& c, const float (&O)[64], uint32_t (&P)[32], uint32_t stg) {
  wg_commit(); wg_commit(); wg_commit(); wg_commit();
  c.turn_end();
  pack_frag<0>(O, P);
  stsm_frag(P, stg);
  fence_async_smem();
}
__device__ __forceinline__ void attn_half(Cons& c, float (&O)[64], uint32_t (&P)[32], SoftState& z, uint32_t dk0, uint32_t dkk, uint32_t dv0, float dmask, int last) {
  float S[32];
  FTH(8 + last * 32, 0);
  c.turn_begin();
  FTH(9 + last * 32, 0);
  wg_fence();
  issue_qk(S, dk0 + (last ? 0 : 2 * DG), dkk + (last ? 8 : 4) * DG);
  wg_commit();
  issue_pv<0>(O, P, dv0 + 10 * DG, 1, last);
  issue_pv<1>(O, P, dv0 + 10 * DG, 1, last);
  c.turn_end();
  c.wait_full(last ? 12 : 6);
  FTH(10 + last * 32, 0);
  wg_wait<4>();
  reg_fence(S);
  FTH(11 + last * 32, 0);
  c.release(last ? 8 : 4, 2);
  mask_diag(S, dmask);
  float s0, s1, d0 = z.m0, d1 = z.m1;
#pragma unroll 1
  for (int pass = 0;; pass++) {
    if (z.shifted) shift_scores(S, d0, d1);
    float tr[ROT];
    exp_quarter<0, 3>(S, P, tr, s0, s1, c.sb);
    exp_quarter<1, 2>(S, P, tr, s0, s1, c.sb);
    pin(s1, c.sb); wg_wait<0>(); reg_fence_part<16, 16>(P); reg_fence(O);
    if (!soft_unsafe(s0, s1, !last) || pass) break;
    soft_fix(S, O, z, !last, d0, d1);
  }
  FTH(12 + last * 32, 0);
  z.l0 += s0; z.l1 += s1;
  c.release(10, last ? 2 : 0);
  if (!last) c.wait_full(8);
  FTH(13 + last * 32, 0);
}

template <int V> struct IC { static constexpr int value = V; };
__device__ __forceinline__ int conv_next(int g, bool spare) { return g >= NGR - 2 ? g - (NGR - 4) : !spare && g == 4 ? 1 : g + 2; }
__device__ __forceinline__ void conv_final(uint32_t rb, uint32_t yb, const uint4& u, uint32_t dd, bool on) {
  const uint4 q0 = lds128(rb), q1 = lds128(rb + 4096), q2 = lds128(rb + 8192), q3 = lds128(rb + 12288);
  auto fin = [&](uint32_t x0, uint32_t x1, uint32_t x2, uint32_t x3, uint32_t uu) {
    if (DFOLD) return hadd2(hadd2(x0, x1), hadd2(x2, x3));
    return hfma2(dd, __byte_perm(uu, uu, 0x1032), hadd2(hadd2(x0, x1), hadd2(x2, x3)));
  };
  asm volatile("{\n.reg .pred p;\nsetp.ne.b32 p, %5, 0;\n@p st.shared.v4.b32 [%0], {%1,%2,%3,%4};\n}\n" ::"r"(yb), "r"(fin(q0.x, q1.x, q2.x, q3.x, u.w)),
               "r"(fin(q0.y, q1.y, q2.y, q3.y, u.z)), "r"(fin(q0.z, q1.z, q2.z, q3.z, u.y)), "r"(fin(q0.w, q1.w, q2.w, q3.w, u.x)), "r"((int)on) : "memory");
}
__device__ __forceinline__ void conv_tasks(Cons& c, const Params& p, int ntask, bool last, bool spare, int ch, int chstep, uint32_t dd, uint32_t dkk, int w, int lane) {
  const uint32_t sb = c.sb;
  int g = 2 + c.wg;
  uint4 u0 = make_uint4(0, 0, 0, 0), u1 = u0;
  uint32_t rb = sb + g * GR;
  const uint32_t yb = sb + c.wg * 8192 + c.tid * 16;
  c.wait_full(g);
#pragma unroll 1
  for (int i = 0; i < ntask; i++) {
    const uint32_t base = sb + g * GR;
    FTC(0);
    uint32_t a[64];
    const uint32_t hb = base + WBYTES - 28 + (8 * w + (lane >> 2) + (lane & 3)) * 4;
    auto lda = [&](int s) {
      a[4 * s] = lds32(hb + s * 256); a[4 * s + 1] = lds32(hb + s * 256 + 128);
      a[4 * s + 2] = lds32(hb + s * 256 + 16); a[4 * s + 3] = lds32(hb + s * 256 + 144);
    };
    lda(0); lda(15); lda(1); lda(14);
    if (DFOLD) {
      const int gt = 8 * w + (lane >> 2) + (lane & 3);
      a[0] = hadd2(a[0], gt == 7 ? dd : 0u); a[2] = hadd2(a[2], gt == 3 ? dd : 0u);
    }
    float acc[128];
    const uint32_t db = dkk + ((WPL / 16 - 1) << 16) + g * DG + WZ / 16;
    FTC(2);
    c.turn_begin();
    FTC(3);
    auto pair = [&](auto kc) {
      constexpr int k = decltype(kc)::value;
      if (k < 7) wg_fence();
      if (k == 7 && !(last && i == ntask - 1)) c.turn_end();
      conv_step<k, 7>(acc, a, db);
      conv_step<15 - k, 7>(acc, a, db);
      if (k < 6) { lda(k + 2); lda(13 - k); }
      if (k == 0) conv_final(rb, yb, u0, dd, i > 0);
      if (k == 1) {
        conv_final(rb + 2048, yb + 2048, u1, dd, i > 0);
        __syncwarp();
        if (lane == 0 && i > 0) mbar_arrive(sb + SM_BAR + (B_EV + c.wg) * 8);
      }
      if (DFOLD) { if (k == 6) dd = __bfloat16_as_ushort(p.ssd[(ch + chstep) & (DM - 1)]); }
      else if (k == 6) {
        const uint32_t ub = base + WZ + 16 + (c.tid >> 1) * 32 + ((c.tid & 1) ^ 1) * WPL;
        u0 = lds128(ub); u1 = lds128(ub + 2048);
        dd = __bfloat16_as_ushort(p.ssd[ch]) * 0x10001u;
      }
    };
    pair(IC<0>()); pair(IC<1>()); pair(IC<2>()); pair(IC<3>()); pair(IC<4>()); pair(IC<5>()); pair(IC<6>()); pair(IC<7>());
    wg_commit();
    FTC(4);
    g = conv_next(g, spare);
    ch += chstep;
    rb = base + c.tid * 16;
    wg_wait<0>();
    reg_fence(acc);
    reg_fence(a);
    bar_sync(3 + c.wg, 128);
    FTC(5);
    const int tw = (lane & 3) + w;
    const uint32_t xb = base + w * 4096 + tw * 32 + (lane >> 2) * 4;
#pragma unroll
    for (int j = 0; j < 32; j++) {
      float v0 = acc[4 * j], v1 = acc[4 * j + 1];
      if (j > 0) { v0 += acc[j > 0 ? 4 * j - 2 : 0]; v1 += acc[j > 0 ? 4 * j - 1 : 0]; }
      uint32_t v = pack_bf16(v0, v1), ad = xb + j * 128;
      if (j == 31 && tw >= 4) { v = 0; ad -= 4096; }
      asm volatile("st.shared.b32 [%0], %1;" ::"r"(ad), "r"(v) : "memory");
    }
    c.wait_stage_free();
    if (i + 1 < ntask) c.wait_full(g);
    bar_sync(3 + c.wg, 128);
    FTC(6);
  }
  conv_final(rb, yb, u0, dd, true);
  conv_final(rb + 2048, yb + 2048, u1, dd, true);
  c.staged(0);
}

__global__ void __cluster_dims__(2, 1, 1) __launch_bounds__(NTHREADS, 1) mega_kernel(const __grid_constant__ Params p) {
  extern __shared__ __align__(1024) uint8_t smem_raw[];
  FTS(0);
  const uint32_t sb = smem_u32(smem_raw);
  const int wgi = __shfl_sync(0xffffffffu, threadIdx.x >> 7, 0);
  const int warp = __shfl_sync(0xffffffffu, threadIdx.x >> 5, 0);
  const uint32_t rank = blockIdx.x & 1;
  int slot;
  {
    uint32_t smid; asm volatile("mov.u32 %0, %smid;" : "=r"(smid));
    slot = p.pref[((smid >> 1) + (threadIdx.x & (smid >> 16))) & 127];
  }
  if (warp >= 3) {
    if (elect()) {
#pragma unroll
      for (int k = 0; k < 4; k++) mbar_init(sb + SM_BAR + ((warp - 3) * 4 + k) * 8, k == 1 && warp == 7 ? 11 : warp < (k ? 7 : 8) ? 1 : 4);
      if (warp == 7) mbar_expect_tx(sb + SM_BAR + B_SLOT * 8, 8);
      asm volatile("fence.mbarrier_init.release.cluster;" ::: "memory");
    }
    __syncwarp();
  }
  FTS(1);
  cluster_arrive();
  if (warp == 2) { prefetch_tm(&p.c); prefetch_tm(rank ? &p.wuv : &p.wuk); FTSW(5); }
  slot = __shfl_sync(0xffffffffu, slot, 0);
  const int pref = slot;
  if (warp < 4) {
    asm volatile("setmaxnreg.dec.sync.aligned.u32 40;");
    if (warp == 1 + 4 * rank) {
      unsigned taken = threadIdx.x == 32;
#pragma unroll 1
      for (int n = 0; n < NSLOT; n++) {
        asm volatile("{\n.reg .pred p;\nsetp.ne.b32 p, %0, 0;\n@p atom.relaxed.gpu.global.exch.b32 %0, [%1], 1;\n}\n" : "+r"(taken) : "l"(CLAIMP(slot)) : "memory");
        if (!__any_sync(0xffffffffu, taken)) break;
        slot = slot == NSLOT - 1 ? 0 : slot + 1;
      }
    }
    cluster_wait();
    if (threadIdx.x == 32) {
#pragma unroll
      for (int r = 0; r < 2; r++)
        asm volatile("{\n.reg .b32 a, b;\nmapa.shared::cluster.u32 a, %0, %1;\nadd.u32 b, a, %3;\nst.async.shared::cluster.mbarrier::complete_tx::bytes.u32 [b], %2, [a];\n}\n"
                     ::"r"(sb + SM_BAR + B_SLOT * 8), "r"(r), "r"(slot | pref << 8), "r"((V_SLOT - B_SLOT) * 8 + rank * 4) : "memory");
    }
    if (warp == 0) {
      if (elect()) {
#pragma unroll 1
        for (int kk = 0; kk < 4; kk++) {
          const int g0 = 2 + 3 * kk;
          const uint32_t fb = sb + SM_BAR + (B_FULL + g0) * 8;
          FTSW(kk);
          mbar_expect_tx(fb, 3 * GR);
          tma2d(sb + g0 * GR, &p.c, kk * 64, (KV_ROW(pref & 7, 0) + rank) * 128, fb, EV_NORMAL);
          tma3d_mc(sb + (g0 + 1 + rank) * GR, rank ? &p.wuv : &p.wuk, 0, kk * 64, ((pref & 56) >> 1) + 2 * KV_HEAD(pref & 7, 0), fb, POL_W);
        }
        FTSW(4);
        prefetch_tm(&p.x); prefetch_tm(&p.wq);
      }
    }
  }
  int grp, idx, lb;
  int cn, cch, cstep;
  bool spare, redo;
  auto get_slot = [&]() {
    mbar_wait(sb + SM_BAR + B_SLOT * 8, 0);
    const uint32_t sv0 = __shfl_sync(0xffffffffu, lds32(sb + SM_BAR + V_SLOT * 8), 0), sv1 = __shfl_sync(0xffffffffu, lds32(sb + SM_BAR + V_SLOT * 8 + 4), 0);
    grp = (sv0 & 255) >> 3; idx = sv0 & 7; lb = (sv0 & 255) * 2 + rank;
    spare = grp == 8; redo = spare || sv0 != sv1;
    cn = spare ? CN_SPARE : CN_MAIN; cch = spare ? lb - NMAIN : 4 * CN_SPARE + CN_MAIN * lb; cstep = spare ? 4 : 1;
    if (FINE_MODE != 7) TS(0);
  };

  if (wgi == 0) {
    asm volatile("setmaxnreg.dec.sync.aligned.u32 40;");
    const int lane = threadIdx.x & 31;
    cluster_arrive();
    get_slot();
    if (warp == 3) {
      if (!spare) {
        const int s0 = lb * 16;
#pragma unroll 1
        for (int cg = 0; cg < 16; cg++) {
          if (cg == 3 || cg == 10) {
#pragma unroll 1
            for (int n = 0; n < 20 && !__any_sync(0xffffffffu, mbar_try(sb + SM_BAR + B_SLOT * 8, cg == 3)); n++);
          } else if (cg < 3) __nanosleep(800);
          const int ch = cg * 64 + 2 * lane;
          const uint32_t* kp = reinterpret_cast<const uint32_t*>(p.ak + (size_t)s0 * DM + ch);
          const uint32_t* vp = reinterpret_cast<const uint32_t*>(p.av + (size_t)s0 * DM + ch);
          const uint4 sw = __ldg(reinterpret_cast<const uint4*>(p.shk + ch * 4));
          uint32_t k3 = 0, k2 = 0, k1 = 0, k0 = 0, up = 0;
          if (lb > 0) { k3 = ldg_stream(kp - 4 * 512); k2 = ldg_stream(kp - 3 * 512); k1 = ldg_stream(kp - 2 * 512); k0 = ldg_stream(kp - 512); up = ldg_stream(vp - 512); }
          const uint32_t w0 = __byte_perm(sw.x, sw.z, 0x5410), w1 = __byte_perm(sw.x, sw.z, 0x7632);
          const uint32_t w2 = __byte_perm(sw.y, sw.w, 0x5410), w3 = __byte_perm(sw.y, sw.w, 0x7632);
          up = hmul2(hfma2(k0, w0, hfma2(k1, w1, hfma2(k2, w2, hmul2(k3, w3)))), up);
#pragma unroll 1
          for (int hb = 0; hb < 2; hb++) {
            uint32_t kk[8], u[8];
#pragma unroll
            for (int r = 0; r < 8; r++) { kk[r] = ldg_stream(kp + r * 512); u[r] = ldg_stream(vp + r * 512); }
#pragma unroll
            for (int r = 0; r < 8; r++) {
              k3 = k2; k2 = k1; k1 = k0; k0 = kk[r];
              u[r] = hmul2(hfma2(k0, w0, hfma2(k1, w1, hfma2(k2, w2, hmul2(k3, w3)))), u[r]);
            }
            if (lane == 0) asm volatile("cp.async.bulk.wait_group.read 0;" ::: "memory");
            __syncwarp();
            const uint32_t dst = sb + SM_UST + lane * 32 + ((lane & 4) << 2);
#pragma unroll
            for (int cc = 0; cc < 2; cc++) {
              const uint32_t sel = cc ? 0x7632 : 0x5410;
              asm volatile("st.shared.v4.b32 [%0], {%1,%2,%3,%4};" ::"r"(dst + cc * 1024), "r"(__byte_perm(u[6], u[5], sel)), "r"(__byte_perm(u[4], u[3], sel)),
                           "r"(__byte_perm(u[2], u[1], sel)), "r"(__byte_perm(u[0], up, sel)) : "memory");
              asm volatile("st.shared.v4.b32 [%0], {%1,%2,%3,%4};" ::"r"((dst ^ 16) + cc * 1024), "r"(__byte_perm(u[7], u[6], sel)), "r"(__byte_perm(u[5], u[4], sel)),
                           "r"(__byte_perm(u[3], u[2], sel)), "r"(__byte_perm(u[1], u[0], sel)) : "memory");
            }
            fence_async_smem();
            __syncwarp();
            if (lane == 0) {
              asm volatile("cp.async.bulk.tensor.3d.global.shared::cta.bulk_group [%0, {%2, %3, %4}], [%1];\ncp.async.bulk.commit_group;"
                           ::"l"(&p.w), "r"(sb + SM_UST), "r"(WZ / 2 + lb * 16 + (hb ^ 1) * (WPL / 2)), "r"(cg * 32), "r"(0) : "memory");
            }
            up = u[7];
            kp += 8 * 512; vp += 8 * 512;
          }
          if ((cg & (cg + 1)) == 0 && lane == 0) {
            asm volatile("cp.async.bulk.wait_group 0;" ::: "memory");
            fence_release();
            flag_add(FLAG(F_U + 32 - __clz(cg)));
          }
          TSW(10 + cg);
        }
      }
      if (lane == 0) {
        unsigned long long t0, t1;
        asm volatile("mov.u64 %0, %globaltimer;" : "=l"(t0));
        while (!mbar_try(sb + SM_BAR + B_DONE * 8, 0)) {
          asm volatile("mov.u64 %0, %globaltimer;" : "=l"(t1));
          if (t1 - t0 > 2000000000ull) __trap();
        }
      }
    } else if (warp != 0) {
      const int w = warp - 1, ne = 12 + (cn + 1 - w) / 2;
      uint32_t p0 = 0;
      int cg = 2 + w, ch = cch + w * cstep;
#pragma unroll 1
      for (int e = spare ? 12 : 0; e < ne; e++) {
        const int rnd = e >= 6, k = e - 6 * rnd, rt = k == 4 ? idx : 15 - idx;
        uint8_t* dst = k < 4 ? g_kv + (size_t)(((k & 1) * 16 + 2 * grp + KV_HEAD(idx, k >> 1)) * 16 + KV_ROW(idx, k >> 1) + rank) * 32768 + w * 8192
                     : k < 6 ? g_cimg + (size_t)(rt * 32 + 16 * rnd + 2 * grp + rank) * 32768 + (w ^ (k & 1)) * 8192
                             : reinterpret_cast<uint8_t*>(g_yT + (size_t)ch * SEQ);
        const uint32_t src = sb + w * 8192 + (k == 4 ? 2 * GR : 0);
        if (e == 6) flag_wait(FLAG(F_AD + grp), 32);
        mbar_wait1(sb + SM_BAR + (B_EV + (k == 4 ? 2 : 0) + w) * 8, k == 4 ? rnd : p0);
        if (k != 4) p0 ^= 1;
        if (lane < 4 && k >= 6 && (!spare || e < ne - 6)) mbar_arrive_cluster(sb + SM_BAR + (B_EMPTY + cg) * 8, lane & 1);
        fence_async_smem();
        if (elect()) {
#pragma unroll 1
          for (int i = 0; i < (k >= 6 ? 1 : 8); i++) {
            const uint32_t o = (i >> 2) * 16384 + (i & 3) * 2048;
            asm volatile("cp.async.bulk.global.shared::cta.bulk_group [%0], [%1], %2;" ::"l"(dst + o), "r"(src + o), "r"(k >= 6 ? 4096 : 2048) : "memory");
            asm volatile("cp.async.bulk.commit_group;\ncp.async.bulk.wait_group.read %0;" ::"n"(ST_OUT) : "memory");
          }
          asm volatile("cp.async.bulk.wait_group 0;" ::: "memory");
          if (k != 4) mbar_arrive(sb + SM_BAR + (B_FREE + w) * 8);
        }
        __syncwarp();
        if (lane < (k == 4 ? 4 : e == 11 || (e == ne - 1 && !spare) ? 2 : 0))
          mbar_arrive_cluster(sb + SM_BAR + (B_EMPTY + (k == 4 ? 2 : e == 11) + (lane >> 1)) * 8, lane & 1);
        if (k >= 3) {
          fence_release();
          const unsigned fl = k == 3 ? F_KV + rnd * 8 + grp : k < 6 ? F_CTX + rt * 2 + rnd : F_Y + ((unsigned)ch >> 7);
          if (lane <= (e == 5)) flag_add(FLAG(lane ? F_AD + grp : fl));
        }
        if (k >= 6) { cg = conv_next(cg, spare); ch += 2 * cstep; }
      }
      if (lane == 0) mbar_arrive(sb + SM_BAR + B_DONE * 8);
    } else {
      uint32_t pe = 0;
      auto acquire = [&](int g, int n, uint32_t m) {
        int i = g;
#pragma unroll 1
        do mbar_wait1(sb + SM_BAR + (B_EMPTY + i) * 8, (pe >> i) & 1); while (++i < g + n);
        pe ^= m << g;
      };
#pragma unroll 1
      for (int rnd = 0; rnd < (spare ? 0 : 2); rnd++) {
        const int hp = 16 * rnd + 2 * grp, head = hp + rank;
#pragma unroll 1
        for (int kk = rnd || redo ? 0 : 4; kk < 32; kk++) {
          const int g0 = 2 + 3 * (kk & 3);
          acquire(g0, kk < 4 ? 3 : 1, 7);
          if (elect()) {
            const uint32_t fb = sb + SM_BAR + (B_FULL + g0) * 8;
            mbar_expect_tx(fb, 3 * GR);
            if (kk < 16) {
              tma2d(sb + g0 * GR, &p.c, (kk & 7) * 64, (KV_ROW(idx, kk >> 3) + rank) * 128, fb, EV_NORMAL);
              tma3d_mc(sb + (g0 + 1 + rank) * GR, rank ? &p.wuv : &p.wuk, 0, (kk & 7) * 64, (hp + KV_HEAD(idx, kk >> 3)) * 2, fb, kk < 8 ? POL_W : POL_W2);
            } else {
              tma2d_mc(sb + (g0 + rank) * GR, &p.x, (kk - 16) * 64, (rank ? 15 - idx : idx) * 128, fb, EV_NORMAL);
              tma3d(sb + (g0 + 2) * GR, &p.wq, 0, (kk - 16) * 64, head * 2, fb, POL_WQ);
            }
          }
        }
        flag_wait(FLAG(F_KV + rnd * 8 + grp), 32);
        fence_async_all();
        acquire(2, 1, 3);
        int g0 = 4;
#pragma unroll 1
        for (int f = 0; f < 34; f++) {
          const bool isk = (f == 0) || ((f & 1) && f < 33);
          const int it = (f == 0) ? 0 : (f == 33) ? 16 : isk ? (f + 1) >> 1 : (f >> 1) - 1;
          const int blk = it == 0 ? idx : it <= idx ? it - 1 : it < 16 ? 15 - it : 15 - idx;
          acquire(g0, f < 5 ? 2 : 1, 3);
          if (elect()) {
            const uint32_t fb = sb + SM_BAR + (B_FULL + g0) * 8;
            if (f == 4) mbar_arrive(sb + SM_BAR + B_SLOT * 8);
            mbar_expect_tx(fb, 2 * GR);
            bulk_g2s(sb + g0 * GR, g_kv + (size_t)(((isk ? 0 : 16) + (head & 15)) * 16 + blk) * 32768, 2 * GR, fb, POL_KV);
          }
          g0 = f == 12 ? 12 : g0 == 12 ? 4 : g0 + 2;
        }
      }
      if (spare) {
#pragma unroll 1
        for (int i = 0, g = 2; i < 32; i++) {
          acquire(g, 2, 3);
          if (elect()) {
            const uint32_t fb = sb + SM_BAR + (B_FULL + g) * 8;
            if (i == 0) { mbar_expect_tx(fb - 8, 2048); bulk_g2s(sb + GR, p.gate_w, 2048, fb - 8, EV_NORMAL); }
            mbar_expect_tx(fb, 2 * GR);
            tma2d(sb + g * GR, &p.x, (i & 7) * 128, (lb - NMAIN) * 512 + (i >> 3) * 128, fb, EV_NORMAL);
            tma2d(sb + (g + 1) * GR, &p.x, (i & 7) * 128 + 64, (lb - NMAIN) * 512 + (i >> 3) * 128, fb, EV_NORMAL);
          }
          g = g == NGR - 2 ? 2 : g + 2;
        }
      }
      auto conv_fill = [&](int g, int ch) {
        acquire(g, 1, 1);
        if (elect()) {
          const uint32_t fb = sb + SM_BAR + (B_FULL + g) * 8;
          mbar_expect_tx(fb, WBYTES + 4096);
          bulk_g2s(sb + g * GR, g_w + (size_t)ch * WSTRIDE, WBYTES, fb, POL_C);
          bulk_g2s(sb + g * GR + WBYTES, p.ssk + (size_t)ch * SEQ, 4096, fb, POL_C);
        }
      };
#pragma unroll 1
      for (int i = 0, g = 2; i < cn; i++) {
        if ((i & 15) == 0) { flag_wait(FLAG(F_U + (spare ? 32 - __clz(i >> 4) : 4)), NMAIN); fence_async_all(); }
        conv_fill(g + (i & 1), cch + i * cstep);
        if (i & 1) g = conv_next(g, spare);
      }
      if (!spare) {
        const int rt = 2 * grp + rank, ct = idx;
        int g0 = P3G;
        prefetch_tm(&p.y); prefetch_tm(&p.out);
#pragma unroll 1
        for (int kb = 0; kb < 66; kb++) {
          if (kb == 0 || kb == 32 || kb >= 64) {
            flag_wait(FLAG(kb < 64 ? F_CTX + rt * 2 + (kb >> 5) : kb == 64 ? F_GATE : F_Y + ct), kb <= 64 ? 32 : 128);
            fence_async_all();
          }
          acquire(g0, kb < 11 ? 2 : 1, 3);
          if (elect()) {
            const uint32_t fb = sb + SM_BAR + (B_FULL + g0) * 8;
            mbar_expect_tx(fb, kb == 64 ? 2 * GR + 512 : 2 * GR);
            if (kb <= 64) bulk_g2s(kb < 64 ? sb + g0 * GR : sb + SM_GATE, kb < 64 ? (const void*)(g_cimg + (size_t)(rt * 64 + kb) * GR) : (const void*)(g_gate + rt * 128), kb < 64 ? GR : 512, fb, POL_CTX);
            if (kb < 64) {
              tma2d_mc(sb + (g0 + 1) * GR + rank * 8192, &p.wo, ct * 128 + rank * 64, kb * 64, fb, POL_WO);
            } else {
              const CUtensorMap* tm = kb == 64 ? &p.x : &p.y;
              const int c0 = (kb == 64 ? ct : rt) * 128, c1 = (kb == 64 ? rt : ct) * 128;
              tma2d(sb + g0 * GR, tm, c0, c1, fb, EV_NORMAL);
              tma2d(sb + (g0 + 1) * GR, tm, c0 + 64, c1, fb, EV_NORMAL);
            }
          }
          g0 = g0 == 12 ? (kb == 3 ? 2 : 0) : g0 + 2;
        }
        unsigned n = 0;
        if (lane == 0) n = atomicInc(FLAG(F_EXIT), 0x7fffffffu);
        if (__any_sync(0xffffffffu, n == NMAIN - 1)) {
#pragma unroll
          for (int i = lane; i < 96; i += 32) *reinterpret_cast<uint2*>(FLAG(i)) = make_uint2(0, 0);
        }
      }
      if (lane == 0) mbar_arrive(sb + SM_BAR + B_DONE * 8);
    }
    __syncwarp();
    cluster_wait();
  } else {
    asm volatile("setmaxnreg.inc.sync.aligned.u32 232;");
    FTS(2);
    Cons c;
    c.sb = sb; c.pf = 0; c.wg = wgi - 1; c.tid = threadIdx.x & 127;
    const int lane = threadIdx.x & 31, t = lane & 3;
    const int row = c.wg * 64 + (warp & 3) * 16 + (lane >> 2);
    const uint32_t dkk = desc_k(sb), dk0 = dkk + c.wg * 512, dm0 = desc_mn<8192>(sb), dv0 = desc_mn<16384>(sb);
    const uint32_t dsw = DG + 512 - c.wg * 1024;
    if (c.wg == 1) bar_arrive(1, 256);
    c.pfree = 1;
    asm("mapa.shared::cluster.u32 %0, %1, %2;" : "=r"(c.relb) : "r"(sb + SM_BAR + (B_EMPTY + (c.tid >> 1)) * 8), "r"(c.tid & 1));
    c.zero = p.zero;
    c.rnd = 0;
    const uint32_t stg = sb + (c.wg * 64 + (warp & 3) * 16 + ((lane >> 3) & 1) * 8 + (lane & 7)) * 128 + (((lane >> 4) ^ (lane & 7)) << 4);

    uint32_t dd0;
    auto load_dd = [&]() { asm volatile("ld.global.nc.u16 %0, [%1];" : "=r"(dd0) : "l"(p.ssd + (unsigned)(cch + c.wg * cstep + (lane & c.zero)))); };
    int pass = c.zero;
#pragma unroll 1
    do {
    if (pass) {
      load_dd();
#pragma unroll 1
      for (int g = 2; g < NGR; g += 3) { mbar_wait(sb + SM_BAR + (B_FULL + g) * 8, 0); c.release(g, 3); }
      c.pf = 0x924;
    if (spare) {
      c.wait_full(1);
      int g = 2;
#pragma unroll 1
      for (int r = 0; r < 4; r++) {
        float d[4] = {0.f, 0.f, 0.f, 0.f}, e[4] = {0.f, 0.f, 0.f, 0.f};
#pragma unroll 1
        for (int kb = 0; kb < 16; kb += 2) {
          c.wait_full(g);
          wg_fence();
#pragma unroll 1
          for (int k = 0; k < 4; k++) {
            mma_ss_n8(d, dk0 + g * DG + k * 2, dkk + DG + kb * 8 + k * 2);
            mma_ss_n8(e, dk0 + (g + 1) * DG + k * 2, dkk + DG + kb * 8 + 8 + k * 2);
          }
          wg_commit();
          wg_wait<0>();
          c.release(g, 2);
          g = g == NGR - 2 ? 2 : g + 2;
        }
        reg_fence(d); reg_fence(e);
        d[0] += e[0]; d[2] += e[2];
        if (t == 0) {
          float* gp = g_gate + (unsigned)((lb - NMAIN) * 512 + r * 128 + row);
          gp[0] = rcp(1.f + ex2(-1.4426950408889634f * d[0])); gp[8] = rcp(1.f + ex2(-1.4426950408889634f * d[2]));
        }
      }
      fence_release();
      __syncwarp();
      if (lane == 0) flag_add(FLAG(F_GATE));
      TS(1);
    }
    } else cluster_wait();
    get_slot();
    } while (redo && !pass++);
    FTS(3);
    const float dmask = (float)(2 * t - (row & 63));
    uint32_t pv[32];
#pragma unroll 1
    for (int rnd = 0; rnd < (spare ? 0 : 2); rnd++) {
      float O[64];
      FTM(rnd * 8);
      FTG(0);
      FTH(56, c.rnd == rnd);
      c.wait_full(2);
      FTM(rnd * 8 + 1);
      FTH(57, c.rnd == rnd);
#pragma unroll 1
      for (int tile = c.zero; tile < 2; tile++) {
        float acc[128];
        const bool single = tile == 0;
        {
          FTG(tile * 32 + 1);
          const uint32_t a = dk0 + 2 * DG, b = dm0 + 3 * DG;
          c.turn_begin();
          FTG(tile * 32 + 2);
          FTH(58, c.rnd == rnd);
          wg_fence();
          mma_ss_n256_init<1>(acc, a, b);
#pragma unroll
          for (int k = 1; k < 4; k++) mma_ss_n256<1>(acc, a + k * 2, b + k * 128);
          wg_commit();
          if (single) c.turn_end();
          FTG(tile * 32 + 3);
        }
#pragma unroll 1
        for (int kb = 1; kb < 8; kb++) {
          const int g0 = 2 + 3 * (kb & 3);
          const uint32_t a = dk0 + g0 * DG, b = dm0 + (g0 + 1) * DG;
          const bool second = (kb == 1 && !single) || kb == 7;
          FTG(tile * 32 + kb * 4);
          if (!second) { wg_wait<0>(); c.release(2 + 3 * ((kb - 1) & 3), 3); }
          FTG(tile * 32 + kb * 4 + 1);
          c.wait_full(g0);
          if (!second) c.turn_begin();
          FTG(tile * 32 + kb * 4 + 2);
          wg_fence();
#pragma unroll
          for (int k = 0; k < 4; k++) mma_ss_n256<1>(acc, a + k * 2, b + k * 128);
          wg_commit();
          if (kb != 6) c.turn_end();
          if (second) { wg_wait<1>(); c.release(2 + 3 * ((kb - 1) & 3), 3); }
          FTG(tile * 32 + kb * 4 + 3);
          FTH(58 + kb, c.rnd == rnd || kb > 3);
          if (tile == 1 && kb == 3) { c.wait_stage_free(); stsm_frag<0, 4>(pv, stg); }
          if (tile == 1 && kb == 4) { stsm_frag<4, 8>(pv, stg); c.staged(0); }
        }
        c.rnd = rnd;
        c.wait_stage_free();
        const bool nxt = c.try_full(2);
        wg_wait<0>();
        reg_fence(acc);
        c.release(11, 3);
        pack_frag_scaled(acc, pv, SM_C, SM_C);
        stsm_frag(pv, stg);
        c.staged(0);
        pack_frag<64>(acc, pv);
        pin32(pv, sb);
        FTG(32 + tile * 32);
        if (!nxt) mbar_wait(sb + SM_BAR + (B_FULL + 2) * 8, (c.pf >> 2) & 1);
        c.pf ^= 4;
      }
      TS(1 + rnd * 3);
      FTM(rnd * 8 + 2);
      {
        float qa[64];
        float (&qb)[64] = O;
        {
          FTG(65);
          const uint32_t a = dk0 + 2 * DG, b = dm0 + 4 * DG;
          c.turn_begin();
          FTG(66);
          wg_fence();
          mma_ss_n128_init<1>(qa, a, b);
          mma_ss_n128_init<1>(qb, a + dsw, b);
#pragma unroll
          for (int k = 1; k < 4; k++) {
            mma_ss_n128<1>(qa, a + k * 2, b + k * 128);
            mma_ss_n128<1>(qb, a + dsw + k * 2, b + k * 128);
          }
          wg_commit();
          FTG(67);
        }
#pragma unroll 1
        for (int kb = 1; kb < 16; kb++) {
          const int g0 = 2 + 3 * (kb & 3);
          const uint32_t a = dk0 + g0 * DG, b = dm0 + (g0 + 2) * DG;
          const bool second = kb == 1 || kb == 15;
          FTG(64 + kb * 4);
          if (!second) { wg_wait<0>(); c.release(2 + 3 * ((kb - 1) & 3), 3); }
          FTG(65 + kb * 4);
          c.wait_full(g0);
          if (!second) c.turn_begin();
          FTG(66 + kb * 4);
          FTH(kb - 14, kb < 14);
          wg_fence();
#pragma unroll
          for (int k = 0; k < 4; k++) {
            mma_ss_n128<1>(qa, a + k * 2, b + k * 128);
            mma_ss_n128<1>(qb, a + dsw + k * 2, b + k * 128);
          }
          wg_commit();
          if (kb != 14) c.turn_end();
          if (second) { wg_wait<1>(); c.release(2 + 3 * ((kb - 1) & 3), 3); }
          FTG(67 + kb * 4);
          FTH(2, kb < 15);
          if (kb == QFLUSH) { c.wait_stage_free(); stsm_frag<0, 4>(pv, stg); }
          if (kb == QFLUSH + 1) { stsm_frag<4, 8>(pv, stg); c.staged(0); }
        }
        c.wait_stage_free();
        mbar_wait(sb + SM_BAR + (B_EMPTY + 2) * 8, rnd ^ !redo);
        FTM(rnd * 8 + 3);
        FTH(3, 0);
        wg_wait<0>();
        reg_fence(qa); reg_fence(qb);
        FTH(4, 0);
        c.release(11, 3);
        pack_frag<0>(qa, pv);
        stsm_frag(pv, stg + 2 * GR);
        if (c.wg == 0) {
          pack_frag<0>(qb, pv);
          stsm_frag(pv, stg);
#pragma unroll
          for (int i = 16; i < 32; i++) pv[i] = 0;
        }
        fence_async_smem();
        c.wait_full(4);
      }
      TS(2 + rnd * 3);
      FTM(rnd * 8 + 4);
      FTH(5, 0);
      {
        const int nA = idx + 1;
        uint32_t (&P)[32] = pv;
        SoftState z;
        z.m0 = z.m1 = z.l0 = z.l1 = 0.f; z.shifted = c.zero;
#pragma unroll 1
        for (int seg = c.zero;; seg++) {
        if (c.wg == seg) attn_half(c, O, P, z, dk0, dkk, dv0, dmask, seg);
        if (seg) break;
        FTM(rnd * 8 + 5);
        int gk = c.wg ? 4 : 6, gv = c.wg ? 4 : 8;
        uint32_t dq = dk0 + (1 - c.wg < nA ? 2 * DG : 0), dk = dkk + gk * DG;
#pragma unroll 1
        for (int it = 1 - c.wg; it < 17 - c.wg; it++) {
          float S[64];
          FTA(it * 7 + 0); FTH((it < 3 ? 8 + it * 8 : it * 8 - 88) + 0, it >= 3 && it < 15);
          c.turn_begin();
          FTA(it * 7 + 2); FTH((it < 3 ? 8 + it * 8 : it * 8 - 88) + 1, it >= 3 && it < 15);
          wg_fence();
          issue_qk(S, dq, dk);
          wg_commit();
          const uint32_t dv = dv0 + gv * DG;
          uint32_t relk = c.relb + gk * 8, relv = c.relb + gv * 8;
          gk = it == 6 ? 12 : gv == 12 ? 4 : gv + 2;
          gv = it == 16 ? gk : gk == 12 ? 4 : gk + 2;
          uint32_t fk = sb + SM_BAR + (B_FULL + gk) * 8, fv = sb + SM_BAR + (B_FULL + gv) * 8, park = (c.pf >> gk) & 1, parv = (c.pf >> gv) & 1;
          c.pf ^= (1u << gk) | (1u << gv);
          dq = dk0 + (it + 1 < nA ? 2 * DG : 0); dk = dkk + gk * DG;
          float lo0 = z.l0, lo1 = z.l1;
          const bool first = it == nA || it == 0;
          if (it == nA) {
            if (EARLY_RCP) { lo0 = rcp(quad_sum(lo0)); lo1 = rcp(quad_sum(lo1)); }
            z.m0 = z.m1 = z.l0 = z.l1 = 0.f; z.shifted = 0;
          }
          float s0, s1, d0 = z.m0, d1 = z.m1;
          int pre = z.shifted || (it & 15) == 0;
          float lim = first ? -1.f : SM_LIMIT;
          asm volatile("" : "+r"(relk), "+r"(relv), "+r"(fk), "+r"(fv), "+r"(park), "+r"(parv), "+r"(dq), "+r"(dk), "+r"(pre), "+f"(lim), "+f"(d0), "+f"(d1), "+f"(z.l0), "+f"(z.l1));
          if (it) {
            issue_pv<0>(O, P, dv, it != nA + 1 && it != 1, true);
            issue_pv<1>(O, P, dv, 1, HALFPV ? it + c.wg > 1 : true);
            c.turn_end();
          } else stage_q2(c, O, P, stg);
          FTA(it * 7 + 3); FTH((it < 3 ? 8 + it * 8 : it * 8 - 88) + 2, it >= 3 && it < 15);
          wg_wait<4>();
          reg_fence(S);
          FTA(it * 7 + 4); FTH((it < 3 ? 8 + it * 8 : it * 8 - 88) + 3, it >= 3 && it < 15);
          if (c.tid < 4) asm volatile("mbarrier.arrive.shared::cluster.b64 _, [%0];" ::"r"(relk) : "memory");
#pragma unroll 1
          for (int pass = 0;; pass++) {
            if (pre) {
              if ((it & 15) == 0) mask_diag(S, dmask);
              if (z.shifted) shift_scores(S, d0, d1);
            }
            float tr[ROT];
            exp_quarter<0, 3>(S, P, tr, s0, s1, sb);
            exp_quarter<1, 2>(S, P, tr, s0, s1, sb);
            exp_quarter<2, 1>(S, P, tr, s0, s1, sb);
            exp_quarter<3, 0>(S, P, tr, s0, s1, sb);
            reg_fence(O);
            if (c.tid < (pass || !it ? 0 : 4)) asm volatile("mbarrier.arrive.shared::cluster.b64 _, [%0];" ::"r"(relv) : "memory");
            const bool ok = mbar_test(fk, park) & mbar_test(fv, parv);
            if (!ok) lim = -1.f;
            FTA(it * 7 + 5); FTH((it < 3 ? 8 + it * 8 : it * 8 - 88) + 4, it >= 3 && it < 15);
            if (!__any_sync(0xffffffffu, !(s0 <= lim && s1 <= lim))) break;
            if (pass) break;
            if (it == nA) {
              uint32_t pk[32];
              if (!EARLY_RCP) { lo0 = rcp(quad_sum(lo0)); lo1 = rcp(quad_sum(lo1)); }
              pack_frag_scaled(O, pk, lo0, lo1);
              stsm_frag(pk, stg + 2 * GR);
              c.staged(1);
            }
            if (!ok) { mbar_wait(fk, park); mbar_wait(fv, parv); }
            if (!soft_unsafe(s0, s1, first)) break;
            soft_fix(S, O, z, first, d0, d1);
            pre = 1;
          }
          z.l0 += s0; z.l1 += s1;
          FTA(it * 7 + 6); FTH((it < 3 ? 8 + it * 8 : it * 8 - 88) + 5, it >= 3 && it < 15);
        }
        FTM(rnd * 8 + 6);
        }
        FTH(48, 0);
        load_dd();
        c.turn_begin();
        FTH(49, 0);
        wg_fence();
        issue_pv<0>(O, P, dv0 + 12 * DG, 1, true);
        issue_pv<1>(O, P, dv0 + 12 * DG, 1, !c.wg);
        c.turn_end();
        z.l0 = rcp(quad_sum(z.l0)); z.l1 = rcp(quad_sum(z.l1));
        wg_wait<0>();
        reg_fence(O); reg_fence(P);
        FTH(50, 0);
        c.release(12, 2);
        pack_frag_scaled(O, P, z.l0, z.l1);
        stsm_frag(P, stg);
        c.staged(0);
        FTM(rnd * 8 + 7);
        FTH(51, 0);
      }
      TS(3 + rnd * 3);
    }
    conv_tasks(c, p, (cn + 1 - c.wg) / 2, ((cn - 1) & 1) == c.wg, spare, cch + c.wg * cstep, 2 * cstep, dd0, dkk, warp & 3, lane);
    if (c.wg == 1) c.pf ^= 0x14;
    TS(7);
    if (!spare) {
      const int rt = 2 * grp + rank, ct = idx;
      float acc[64];
      int g0 = P3G + 2, pg = P3G;
      {
        FTO(0);
        c.wait_full(P3G);
        FTO(1);
        const uint32_t a = dk0 + P3G * DG, b = dm0 + (P3G + 1) * DG;
        wg_fence();
        mma_ss_n128_init<1>(acc, a, b);
#pragma unroll
        for (int k = 1; k < 4; k++) mma_ss_n128<1>(acc, a + k * 2, b + k * 128);
        wg_commit();
      }
#pragma unroll 1
      for (int kb = 1; kb < 64; kb++) {
        FTO(kb * 2);
        c.wait_full(g0);
        FTO(kb * 2 + 1);
        const uint32_t a = dk0 + g0 * DG, b = dm0 + (g0 + 1) * DG;
        wg_fence();
#pragma unroll
        for (int k = 0; k < 4; k++) mma_ss_n128<1>(acc, a + k * 2, b + k * 128);
        wg_commit();
        wg_wait<1>();
        c.release(pg, kb <= 59 ? 2 : 0);
        if (kb == FDUMP_KB) FTDUMP();
        pg = g0;
        g0 = g0 == 12 ? (kb == 3 ? 2 : 0) : g0 + 2;
      }
      cluster_arrive();
      c.wait_full(P3X);
      c.wait_full(P3Y);
      const float g0f = __uint_as_float(lds32(sb + SM_GATE + row * 4)), g1f = __uint_as_float(lds32(sb + SM_GATE + row * 4 + 32));
      const uint32_t gp0 = pack_bf16(g0f, g0f), gp1 = pack_bf16(g1f, g1f);
      const float h0 = 1.f - g0f, h1 = 1.f - g1f;
      const int w = warp & 3;
      const uint32_t xa = stg + P3X * GR;
      const uint32_t ya = sb + P3Y * GR + c.wg * 16384 + ((lane >> 4) * 8 + (lane & 7)) * 128 + (((2 * w + ((lane >> 3) & 1)) ^ (lane & 7)) << 4);
      uint32_t xy[32];
#pragma unroll
      for (int jj = 0; jj < 8; jj++) {
        uint32_t x[4], y[4];
        asm volatile("ldmatrix.sync.aligned.m8n8.x4.shared.b16 {%0,%1,%2,%3}, [%4];" : "=r"(x[0]), "=r"(x[1]), "=r"(x[2]), "=r"(x[3]) : "r"((xa ^ ((jj & 3) << 5)) + (jj >> 2) * 16384) : "memory");
        asm volatile("ldmatrix.sync.aligned.m8n8.x4.trans.shared.b16 {%0,%1,%2,%3}, [%4];" : "=r"(y[0]), "=r"(y[1]), "=r"(y[2]), "=r"(y[3]) : "r"(ya + jj * 2048) : "memory");
#pragma unroll
        for (int i = 0; i < 4; i++) xy[4 * jj + i] = hmul2(x[i], y[i]);
      }
      wg_wait<0>();
      reg_fence(acc);
      TS(8);
#pragma unroll
      for (int i = 0; i < 32; i++) {
        const float h = (i & 1) ? h1 : h0;
        xy[i] = hfma2((i & 1) ? gp1 : gp0, xy[i], pack_bf16(acc[2 * i] * h, acc[2 * i + 1] * h));
      }
      stsm_frag(xy, xa);
      fence_async_smem();
      __syncwarp();
      if (lane == 0) {
        const int r0 = c.wg * 64 + w * 16;
        tma2d_store(&p.out, sb + P3X * GR + r0 * 128, ct * 128, rt * 128 + r0);
        tma2d_store(&p.out, sb + (P3X + 1) * GR + r0 * 128, ct * 128 + 64, rt * 128 + r0);
        asm volatile("cp.async.bulk.commit_group;\ncp.async.bulk.wait_group.read 0;" ::: "memory");
      }
    } else { FTDUMP(); cluster_arrive(); }
    if (lane == 0) mbar_arrive(sb + SM_BAR + B_DONE * 8);
    __syncwarp();
    TS(9);
    cluster_wait();
  }
}

typedef CUresult (*EncFn)(CUtensorMap*, CUtensorMapDataType, cuuint32_t, void*, const cuuint64_t*, const cuuint64_t*, const cuuint32_t*,
                          const cuuint32_t*, CUtensorMapInterleave, CUtensorMapSwizzle, CUtensorMapL2promotion, CUtensorMapFloatOOBfill);

void enc2d(EncFn enc, CUtensorMap* tm, const void* base, uint64_t cols, uint64_t rows, uint32_t bc, uint32_t br) {
  cuuint64_t dims[2] = {cols, rows}; cuuint64_t strides[1] = {cols * 2}; cuuint32_t box[2] = {bc, br}; cuuint32_t es[2] = {1, 1};
  enc(tm, CU_TENSOR_MAP_DATA_TYPE_BFLOAT16, 2, const_cast<void*>(base), dims, strides, box, es, CU_TENSOR_MAP_INTERLEAVE_NONE,
      CU_TENSOR_MAP_SWIZZLE_128B, CU_TENSOR_MAP_L2_PROMOTION_L2_256B, CU_TENSOR_MAP_FLOAT_OOB_FILL_NONE);
}
void enc3d(EncFn enc, CUtensorMap* tm, const void* base, uint64_t K, uint64_t N) {
  cuuint64_t dims[3] = {64, K, N / 64}; cuuint64_t strides[2] = {N * 2, 128}; cuuint32_t box[3] = {64, 64, 2}; cuuint32_t es[3] = {1, 1, 1};
  enc(tm, CU_TENSOR_MAP_DATA_TYPE_BFLOAT16, 3, const_cast<void*>(base), dims, strides, box, es, CU_TENSOR_MAP_INTERLEAVE_NONE,
      CU_TENSOR_MAP_SWIZZLE_128B, CU_TENSOR_MAP_L2_PROMOTION_L2_256B, CU_TENSOR_MAP_FLOAT_OOB_FILL_NONE);
}

}

extern "C" void kernel_launch(void* const* d_in, const int* in_sizes, int n_in, void* d_out, int out_size) {
  (void)in_sizes; (void)n_in; (void)out_size;
  typedef const __nv_bfloat16* BP;
  BP xq = (BP)d_in[0], ak = (BP)d_in[1], av = (BP)d_in[2], shk = (BP)d_in[3], ssk = (BP)d_in[4], ssd = (BP)d_in[5];
  BP ckv = (BP)d_in[7], wq = (BP)d_in[8], wuk = (BP)d_in[9], wuv = (BP)d_in[10], wo = (BP)d_in[11], gw = (BP)d_in[12];

  static EncFn enc = nullptr;
  if (!enc) {
    cudaDriverEntryPointQueryResult qr;
    cudaGetDriverEntryPoint("cuTensorMapEncodeTiled", (void**)&enc, cudaEnableDefault, &qr);
    cudaFuncSetAttribute(mega_kernel, cudaFuncAttributeMaxDynamicSharedMemorySize, SMEM_BYTES);
  }
  Params p;
  void* yT = nullptr;
  cudaGetSymbolAddress(&yT, g_yT);
  enc2d(enc, &p.x, xq, DM, SEQ, 64, 128);
  enc2d(enc, &p.c, ckv, DC, SEQ, 64, 128);
  enc3d(enc, &p.wq, wq, DM, NH * HD);
  enc3d(enc, &p.wuk, wuk, DC, NH * HD);
  enc3d(enc, &p.wuv, wuv, DC, NH * HD);
  enc2d(enc, &p.wo, wo, DM, NH * HD, 64, 64);
  enc2d(enc, &p.y, yT, SEQ, DM, 64, 128);
  enc2d(enc, &p.out, d_out, DM, SEQ, 64, 16);
  {
    void* wp = nullptr;
    cudaGetSymbolAddress(&wp, g_w);
    cuuint64_t dims[3] = {WSTRIDE / 2, DM / 2, 2}; cuuint64_t strides[2] = {2 * WSTRIDE, WSTRIDE}; cuuint32_t box[3] = {16, 32, 2}; cuuint32_t es[3] = {1, 1, 1};
    enc(&p.w, CU_TENSOR_MAP_DATA_TYPE_BFLOAT16, 3, wp, dims, strides, box, es, CU_TENSOR_MAP_INTERLEAVE_NONE,
        CU_TENSOR_MAP_SWIZZLE_32B, CU_TENSOR_MAP_L2_PROMOTION_NONE, CU_TENSOR_MAP_FLOAT_OOB_FILL_NONE);
  }
  p.zero = 0;
  cudaGetSymbolAddress((void**)&p.flags, g_flags);
  for (int i = 0; i < 128; i++) {
    const int tp = i % NSLOT;
    p.pref[i] = tp < 32 ? (tp & 7) * 8 + (tp >> 3) : tp < 60 ? (1 + (tp - 32) % 7) * 8 + 4 + (tp - 32) / 7 : tp < 62 ? tp + 4 : tp - 58;
  }
  p.gate_w = gw; p.ak = ak; p.av = av; p.shk = shk; p.ssk = ssk; p.ssd = ssd;

  mega_kernel<<<132, NTHREADS, SMEM_BYTES>>>(p);
}
```

```cpp
#include <cuda_runtime.h>
#include <cuda.h>
#include <cuda_bf16.h>
#include <stdint.h>

namespace {

constexpr int SEQ = 2048, DM = 1024, DC = 512, NH = 32, HD = 128;
constexpr int GR = 16384;
constexpr int NGR = 14;
constexpr int SM_BAR = NGR * GR;
constexpr int SM_GATE = SM_BAR + 512;
constexpr int SM_UST = SM_GATE + 512;
constexpr int SMEM_BYTES = SM_UST + 2048;
constexpr int NTHREADS = 384;
#define SM_LIMIT 1.0995116e12f
#define SM_LOW 9.094947e-13f
constexpr int CN_MAIN = 5, CN_SPARE = 96;
constexpr int P3G = 6, P3X = 10, P3Y = 12;
constexpr int NMAIN = 128;

constexpr int B_FULL = 0, B_FREE = 14, B_SLOT = 16, B_DONE = 17, B_EMPTY = 18, B_EV = 32, V_SLOT = 36;

__device__ __align__(1024) uint8_t g_kv[2 * 16 * 16 * 32768];
__device__ __align__(1024) uint8_t g_cimg[16 * NH * 32768];
__device__ __align__(1024) __nv_bfloat16 g_yT[DM * SEQ];
__device__ __align__(1024) float g_gate[SEQ];
#define CWIDE 0
constexpr int WZ = CWIDE ? 768 : 256, WPL = WZ + 4096, WBYTES = 2 * WPL + 32, WSTRIDE = 2 * WPL + 128;
__device__ __align__(1024) uint8_t g_w[DM * WSTRIDE];
__device__ __align__(32) unsigned g_flags[96 * 8];
constexpr int F_KV = 0, F_CTX = 16, F_U = 48, F_AD = 56, F_Y = 64, F_GATE = 72, F_EXIT = 73;
constexpr int NSLOT = 66;
#define FLAG(i) (&g_flags[(i) * 8])
#define CLAIMP(i) (p.flags + (i) * 8 + 1)

#define TS(slot)
#define TSW(slot)
#define FTX(i, off)
#define FTDUMP()

#define ST_OUT 0
#define QFLUSH 4
#define P3PF 10
#define P3PF0 5
#define HALFPV 1
#define EXPV 1
#define SUMV 0
#define ROT 8
#define EARLY_RCP 1
#define KVARR 1
#define KV_ROW(idx, t) (KVARR ? 8 * (t) + 2 * ((idx) & 3) : 2 * (idx))
#define KV_HEAD(idx, t) (KVARR ? (idx) >> 2 : (t))
#define FINE_MODE 0
#define FDUMP_KB 40
#define FINE_RND 1
#define FTA(i) do { if (FINE_MODE == 0) FTX(i, rnd ^ FINE_RND); } while (0)
#define FTG(i) do { if (FINE_MODE == 1) FTX(i, rnd ^ FINE_RND); } while (0)
#define FTM(i) do { if (FINE_MODE == 4) FTX(i, 0); } while (0)
#define FTC(k) do { if (FINE_MODE == 5) FTX((i & 7) * 8 + (k), (i >> 3) ^ FINE_RND); } while (0)
#define FTH(i, off) do { if (FINE_MODE == 6) FTX(i, (c.rnd ^ FINE_RND) | (off)); } while (0)
#define FTS(i)
#define FTSD(i)
#define FTSW(i)
#define FTP(i)
#define FTO(i) do { if (FINE_MODE == 2) FTX(i, 0); } while (0)

__device__ __forceinline__ uint32_t smem_u32(const void* p) { return (uint32_t)__cvta_generic_to_shared(p); }
__device__ __forceinline__ void mbar_init(uint32_t bar, int cnt) { asm volatile("mbarrier.init.shared::cta.b64 [%0], %1;" ::"r"(bar), "r"(cnt) : "memory"); }
__device__ __forceinline__ void mbar_expect_tx(uint32_t bar, uint32_t bytes) { asm volatile("mbarrier.arrive.expect_tx.shared::cta.b64 _, [%0], %1;" ::"r"(bar), "r"(bytes) : "memory"); }
__device__ __forceinline__ void mbar_arrive(uint32_t bar) { asm volatile("mbarrier.arrive.shared::cta.b64 _, [%0];" ::"r"(bar) : "memory"); }
__device__ __forceinline__ void mbar_arrive_cluster(uint32_t bar, uint32_t cta) {
  asm volatile("{\n.reg .b32 r;\nmapa.shared::cluster.u32 r, %0, %1;\nmbarrier.arrive.shared::cluster.b64 _, [r];\n}\n" ::"r"(bar), "r"(cta) : "memory");
}
__device__ __forceinline__ bool mbar_try(uint32_t bar, uint32_t parity) {
  uint32_t ok;
  asm volatile("{\n.reg .pred p;\nmbarrier.try_wait.parity.shared::cta.b64 p, [%1], %2, 20000;\nselp.u32 %0, 1, 0, p;\n}\n" : "=r"(ok) : "r"(bar), "r"(parity) : "memory");
  return ok;
}
__device__ __forceinline__ bool mbar_test(uint32_t bar, uint32_t parity) {
  uint32_t ok;
  asm volatile("{\n.reg .pred p;\nmbarrier.test_wait.parity.shared::cta.b64 p, [%1], %2;\nselp.u32 %0, 1, 0, p;\n}\n" : "=r"(ok) : "r"(bar), "r"(parity) : "memory");
  return ok;
}
__device__ __forceinline__ void mbar_wait(uint32_t bar, uint32_t parity) {
  asm volatile("{\n.reg .pred p;\nWAIT_LOOP:\nbar.warp.sync -1;\nmbarrier.try_wait.parity.shared::cta.b64 p, [%0], %1;\n@!p bra WAIT_LOOP;\n}\n" ::"r"(bar), "r"(parity) : "memory");
}
__device__ __forceinline__ void mbar_wait1(uint32_t bar, uint32_t parity) {
  asm volatile("{\n.reg .pred p;\nWAIT_LOOP:\nbar.warp.sync -1;\nmbarrier.try_wait.parity.shared::cta.b64 p, [%0], %1, 4000;\n@!p bra WAIT_LOOP;\n}\n" ::"r"(bar), "r"(parity) : "memory");
}
constexpr uint64_t EV_FIRST = 0x12F0000000000000ull;
__device__ __forceinline__ uint32_t ldg_stream(const uint32_t* p) {
  uint32_t r; asm volatile("ld.global.nc.L1::no_allocate.L2::cache_hint.b32 %0, [%1], %2;" : "=r"(r) : "l"(p), "l"(EV_FIRST)); return r;
}
#define TMA_LD "cp.async.bulk.tensor."
#define TMA_MB ".shared::cluster.global.mbarrier::complete_tx::bytes"
__device__ __forceinline__ void tma2d(uint32_t dst, const CUtensorMap* tm, int c0, int c1, uint32_t bar) {
  asm volatile(TMA_LD "2d" TMA_MB " [%0], [%1, {%3, %4}], [%2];" ::"r"(dst), "l"(tm), "r"(bar), "r"(c0), "r"(c1) : "memory");
}
template <bool ONCE = false> __device__ __forceinline__ void tma2d_mc(uint32_t dst, const CUtensorMap* tm, int c0, int c1, uint32_t bar) {
  if (ONCE) asm volatile(TMA_LD "2d" TMA_MB ".multicast::cluster.L2::cache_hint [%0], [%1, {%3, %4}], [%2], %5, %6;"
                         ::"r"(dst), "l"(tm), "r"(bar), "r"(c0), "r"(c1), "h"((uint16_t)3), "l"(EV_FIRST) : "memory");
  else asm volatile(TMA_LD "2d" TMA_MB ".multicast::cluster [%0], [%1, {%3, %4}], [%2], %5;"
                    ::"r"(dst), "l"(tm), "r"(bar), "r"(c0), "r"(c1), "h"((uint16_t)3) : "memory");
}
__device__ __forceinline__ void tma3d(uint32_t dst, const CUtensorMap* tm, int c0, int c1, int c2, uint32_t bar) {
  asm volatile(TMA_LD "3d" TMA_MB " [%0], [%1, {%3, %4, %5}], [%2];" ::"r"(dst), "l"(tm), "r"(bar), "r"(c0), "r"(c1), "r"(c2) : "memory");
}
__device__ __forceinline__ void tma3d_mc(uint32_t dst, const CUtensorMap* tm, int c0, int c1, int c2, uint32_t bar) {
  asm volatile(TMA_LD "3d" TMA_MB ".multicast::cluster [%0], [%1, {%3, %4, %5}], [%2], %6;"
               ::"r"(dst), "l"(tm), "r"(bar), "r"(c0), "r"(c1), "r"(c2), "h"((uint16_t)3) : "memory");
}
template <bool ONCE = false> __device__ __forceinline__ void bulk_g2s(uint32_t dst, const void* src, uint32_t bytes, uint32_t bar) {
  if (ONCE) asm volatile("cp.async.bulk" TMA_MB ".L2::cache_hint [%0], [%1], %2, [%3], %4;" ::"r"(dst), "l"(src), "r"(bytes), "r"(bar), "l"(EV_FIRST) : "memory");
  else asm volatile("cp.async.bulk" TMA_MB " [%0], [%1], %2, [%3];" ::"r"(dst), "l"(src), "r"(bytes), "r"(bar) : "memory");
}
__device__ __forceinline__ void tma2d_store(const CUtensorMap* tm, uint32_t src, int c0, int c1) {
  asm volatile("cp.async.bulk.tensor.2d.global.shared::cta.bulk_group [%0, {%2, %3}], [%1];" ::"l"(tm), "r"(src), "r"(c0), "r"(c1) : "memory");
}
__device__ __forceinline__ void prefetch_tm(const CUtensorMap* tm) { asm volatile("prefetch.tensormap [%0];" ::"l"(tm) : "memory"); }
__device__ __forceinline__ void wg_fence() { asm volatile("wgmma.fence.sync.aligned;" ::: "memory"); }
__device__ __forceinline__ void wg_commit() { asm volatile("wgmma.commit_group.sync.aligned;" ::: "memory"); }
template <int N> __device__ __forceinline__ void wg_wait() { asm volatile("wgmma.wait_group.sync.aligned %0;" ::"n"(N) : "memory"); }
__device__ __forceinline__ void bar_sync(int id, int n) { asm volatile("bar.sync %0, %1;" ::"r"(id), "r"(n) : "memory"); }
__device__ __forceinline__ void bar_arrive(int id, int n) { asm volatile("bar.arrive %0, %1;" ::"r"(id), "r"(n) : "memory"); }
__device__ __forceinline__ void fence_async_smem() { asm volatile("fence.proxy.async.shared::cta;" ::: "memory"); }
__device__ __forceinline__ void fence_async_all() { asm volatile("fence.proxy.async.global;" ::: "memory"); }
__device__ __forceinline__ uint32_t pack_bf16(float lo, float hi) { uint32_t r; asm("cvt.rn.bf16x2.f32 %0, %1, %2;" : "=r"(r) : "f"(hi), "f"(lo)); return r; }
__device__ __forceinline__ float ex2(float x) { float r; asm("ex2.approx.ftz.f32 %0, %1;" : "=f"(r) : "f"(x)); return r; }
__device__ __forceinline__ float rcp(float x) { float r; asm("rcp.approx.ftz.f32 %0, %1;" : "=f"(r) : "f"(x)); return r; }
__device__ __forceinline__ void flag_wait(const unsigned* f, unsigned target) {
  unsigned v;
  do { asm volatile("ld.acquire.gpu.global.u32 %0, [%1];" : "=r"(v) : "l"(f) : "memory"); } while (__any_sync(0xffffffffu, v < target));
}
__device__ __forceinline__ bool elect() {
  uint32_t r;
  asm volatile("{\n.reg .pred p;\nelect.sync _|p, -1;\nselp.u32 %0, 1, 0, p;\n}\n" : "=r"(r));
  return r;
}
__device__ __forceinline__ void fence_release() { asm volatile("fence.release.gpu;" ::: "memory"); }
__device__ __forceinline__ void flag_add(unsigned* f) { asm volatile("red.relaxed.gpu.global.inc.u32 [%0], 0x7fffffff;" ::"l"(f) : "memory"); }
__device__ __forceinline__ void cluster_arrive() { asm volatile("barrier.cluster.arrive.relaxed.aligned;" ::: "memory"); }
__device__ __forceinline__ void cluster_wait() { asm volatile("barrier.cluster.wait.aligned;" ::: "memory"); }
__device__ __forceinline__ uint32_t hmul2(uint32_t a, uint32_t b) { uint32_t r; asm("mul.rn.bf16x2 %0, %1, %2;" : "=r"(r) : "r"(a), "r"(b)); return r; }
__device__ __forceinline__ uint32_t hadd2(uint32_t a, uint32_t b) { uint32_t r; asm("add.rn.bf16x2 %0, %1, %2;" : "=r"(r) : "r"(a), "r"(b)); return r; }
__device__ __forceinline__ uint32_t hfma2(uint32_t a, uint32_t b, uint32_t c) { uint32_t r; asm("fma.rn.bf16x2 %0, %1, %2, %3;" : "=r"(r) : "r"(a), "r"(b), "r"(c)); return r; }
__device__ __forceinline__ uint32_t lds32(uint32_t a) { uint32_t r; asm volatile("ld.shared.b32 %0, [%1];" : "=r"(r) : "r"(a) : "memory"); return r; }
__device__ __forceinline__ uint4 lds128(uint32_t a) { uint4 r; asm volatile("ld.shared.v4.b32 {%0,%1,%2,%3}, [%4];" : "=r"(r.x), "=r"(r.y), "=r"(r.z), "=r"(r.w) : "r"(a) : "memory"); return r; }
__device__ __forceinline__ uint32_t desc_k(uint32_t addr) { return ((addr & 0x3FFFF) >> 4) | (1u << 16); }
template <int LBO> __device__ __forceinline__ uint32_t desc_mn(uint32_t addr) { return ((addr & 0x3FFFF) >> 4) | ((uint32_t)(LBO >> 4) << 16); }
#define DHI "0x40000040"

#define R8(d, o) "+f"(d[o]), "+f"(d[o + 1]), "+f"(d[o + 2]), "+f"(d[o + 3]), "+f"(d[o + 4]), "+f"(d[o + 5]), "+f"(d[o + 6]), "+f"(d[o + 7])
#define R32(d, o) R8(d, o), R8(d, o + 8), R8(d, o + 16), R8(d, o + 24)
#define R64(d, o) R32(d, o), R32(d, o + 32)
#define L64 "%0,%1,%2,%3,%4,%5,%6,%7,%8,%9,%10,%11,%12,%13,%14,%15,%16,%17,%18,%19,%20,%21,%22,%23,%24,%25,%26,%27,%28,%29,%30,%31," \
            "%32,%33,%34,%35,%36,%37,%38,%39,%40,%41,%42,%43,%44,%45,%46,%47,%48,%49,%50,%51,%52,%53,%54,%55,%56,%57,%58,%59,%60,%61,%62,%63"
#define L128 L64 ",%64,%65,%66,%67,%68,%69,%70,%71,%72,%73,%74,%75,%76,%77,%78,%79,%80,%81,%82,%83,%84,%85,%86,%87,%88,%89,%90,%91,%92,%93,%94,%95," \
            "%96,%97,%98,%99,%100,%101,%102,%103,%104,%105,%106,%107,%108,%109,%110,%111,%112,%113,%114,%115,%116,%117,%118,%119,%120,%121,%122,%123,%124,%125,%126,%127"

template <int TB> __device__ __forceinline__ void mma_ss_n128(float (&d)[64], uint32_t da, uint32_t db) {
  asm volatile("{\n.reg .b64 da, db;\nmov.b64 da, {%64, " DHI "};\nmov.b64 db, {%65, " DHI "};\n"
               "wgmma.mma_async.sync.aligned.m64n128k16.f32.bf16.bf16 {" L64 "}, da, db, 1, 1, 1, 0, %66;\n}\n"
               : R64(d, 0) : "r"(da), "r"(db), "n"(TB));
}
template <int TB> __device__ __forceinline__ void mma_rs_n128(float (&d)[64], uint32_t a0, uint32_t a1, uint32_t a2, uint32_t a3, uint32_t db, int sd) {
  asm volatile("{\n.reg .pred p;\n.reg .b64 db;\nsetp.ne.b32 p, %69, 0;\nmov.b64 db, {%68, " DHI "};\n"
               "wgmma.mma_async.sync.aligned.m64n128k16.f32.bf16.bf16 {" L64 "}, {%64,%65,%66,%67}, db, p, 1, 1, %70;\n}\n"
               : R64(d, 0) : "r"(a0), "r"(a1), "r"(a2), "r"(a3), "r"(db), "r"(sd), "n"(TB));
}
template <int TB> __device__ __forceinline__ void mma_ss_n256(float (&d)[128], uint32_t da, uint32_t db) {
  asm volatile("{\n.reg .b64 da, db;\nmov.b64 da, {%128, " DHI "};\nmov.b64 db, {%129, " DHI "};\n"
               "wgmma.mma_async.sync.aligned.m64n256k16.f32.bf16.bf16 {" L128 "}, da, db, 1, 1, 1, 0, %130;\n}\n"
               : R64(d, 0), R64(d, 64) : "r"(da), "r"(db), "n"(TB));
}
#define W8(d, o) "=f"(d[o]), "=f"(d[o + 1]), "=f"(d[o + 2]), "=f"(d[o + 3]), "=f"(d[o + 4]), "=f"(d[o + 5]), "=f"(d[o + 6]), "=f"(d[o + 7])
#define W32(d, o) W8(d, o), W8(d, o + 8), W8(d, o + 16), W8(d, o + 24)
#define W64(d, o) W32(d, o), W32(d, o + 32)
template <int TB> __device__ __forceinline__ void mma_ss_n128_init(float (&d)[64], uint32_t da, uint32_t db) {
  asm volatile("{\n.reg .b64 da, db;\nmov.b64 da, {%64, " DHI "};\nmov.b64 db, {%65, " DHI "};\n"
               "wgmma.mma_async.sync.aligned.m64n128k16.f32.bf16.bf16 {" L64 "}, da, db, 0, 1, 1, 0, %66;\n}\n"
               : W64(d, 0) : "r"(da), "r"(db), "n"(TB));
}
template <int TB> __device__ __forceinline__ void mma_ss_n256_init(float (&d)[128], uint32_t da, uint32_t db) {
  asm volatile("{\n.reg .b64 da, db;\nmov.b64 da, {%128, " DHI "};\nmov.b64 db, {%129, " DHI "};\n"
               "wgmma.mma_async.sync.aligned.m64n256k16.f32.bf16.bf16 {" L128 "}, da, db, 0, 1, 1, 0, %130;\n}\n"
               : W64(d, 0), W64(d, 64) : "r"(da), "r"(db), "n"(TB));
}
#define L32 "%0,%1,%2,%3,%4,%5,%6,%7,%8,%9,%10,%11,%12,%13,%14,%15,%16,%17,%18,%19,%20,%21,%22,%23,%24,%25,%26,%27,%28,%29,%30,%31"
__device__ __forceinline__ void mma_ss_n64(float (&d)[32], uint32_t da, uint32_t db) {
  asm volatile("{\n.reg .b64 da, db;\nmov.b64 da, {%32, " DHI "};\nmov.b64 db, {%33, " DHI "};\n"
               "wgmma.mma_async.sync.aligned.m64n64k16.f32.bf16.bf16 {" L32 "}, da, db, 1, 1, 1, 0, 0;\n}\n"
               : R32(d, 0) : "r"(da), "r"(db));
}
__device__ __forceinline__ void mma_ss_n64_init(float (&d)[32], uint32_t da, uint32_t db) {
  asm volatile("{\n.reg .b64 da, db;\nmov.b64 da, {%32, " DHI "};\nmov.b64 db, {%33, " DHI "};\n"
               "wgmma.mma_async.sync.aligned.m64n64k16.f32.bf16.bf16 {" L32 "}, da, db, 0, 1, 1, 0, 0;\n}\n"
               : W32(d, 0) : "r"(da), "r"(db));
}
#define L16 "%0,%1,%2,%3,%4,%5,%6,%7,%8,%9,%10,%11,%12,%13,%14,%15"
template <int O, bool INIT> __device__ __forceinline__ void mma_rs_n32(float (&d)[128], uint32_t a0, uint32_t a1, uint32_t a2, uint32_t a3, uint32_t db) {
  if (INIT) asm volatile("{\n.reg .b64 db;\nmov.b64 db, {%20, 0x00000008};\n"
               "wgmma.mma_async.sync.aligned.m64n32k16.f32.bf16.bf16 {" L16 "}, {%16,%17,%18,%19}, db, 0, 1, 1, 0;\n}\n"
               : W8(d, O), W8(d, O + 8) : "r"(a0), "r"(a1), "r"(a2), "r"(a3), "r"(db));
  else asm volatile("{\n.reg .b64 db;\nmov.b64 db, {%20, 0x00000008};\n"
               "wgmma.mma_async.sync.aligned.m64n32k16.f32.bf16.bf16 {" L16 "}, {%16,%17,%18,%19}, db, 1, 1, 1, 0;\n}\n"
               : R8(d, O), R8(d, O + 8) : "r"(a0), "r"(a1), "r"(a2), "r"(a3), "r"(db));
}
template <int O, bool INIT> __device__ __forceinline__ void mma_rs_n64(float (&d)[128], uint32_t a0, uint32_t a1, uint32_t a2, uint32_t a3, uint32_t db) {
  if (INIT) asm volatile("{\n.reg .b64 db;\nmov.b64 db, {%36, 0x00000008};\n"
               "wgmma.mma_async.sync.aligned.m64n64k16.f32.bf16.bf16 {" L32 "}, {%32,%33,%34,%35}, db, 0, 1, 1, 0;\n}\n"
               : W32(d, O) : "r"(a0), "r"(a1), "r"(a2), "r"(a3), "r"(db));
  else asm volatile("{\n.reg .b64 db;\nmov.b64 db, {%36, 0x00000008};\n"
               "wgmma.mma_async.sync.aligned.m64n64k16.f32.bf16.bf16 {" L32 "}, {%32,%33,%34,%35}, db, 1, 1, 1, 0;\n}\n"
               : R32(d, O) : "r"(a0), "r"(a1), "r"(a2), "r"(a3), "r"(db));
}
template <int S, int J> __device__ __forceinline__ void conv_step(float (&d)[128], const uint32_t (&a)[64], uint32_t db) {
  if constexpr (J >= 0 && J >= (S >> 1)) {
    if constexpr (J >= 8 - 2 * CWIDE) {
      mma_rs_n64<16 * (J - 1), S == 0>(d, a[4 * S], a[4 * S + 1], a[4 * S + 2], a[4 * S + 3], db + (uint32_t)((2 * (J - 1) - S) * 16));
      conv_step<S, J - 2>(d, a, db);
    } else {
      mma_rs_n32<16 * J, S == 0>(d, a[4 * S], a[4 * S + 1], a[4 * S + 2], a[4 * S + 3], db + (uint32_t)((2 * J - S) * 16));
      conv_step<S, J - 1>(d, a, db);
    }
  }
}
__device__ __forceinline__ void mma_ss_n8(float (&d)[4], uint32_t da, uint32_t db) {
  asm volatile("{\n.reg .b64 da, db;\nmov.b64 da, {%4, " DHI "};\nmov.b64 db, {%5, 0x00000008};\n"
               "wgmma.mma_async.sync.aligned.m64n8k16.f32.bf16.bf16 {%0,%1,%2,%3}, da, db, 1, 1, 1, 0, 0;\n}\n"
               : "+f"(d[0]), "+f"(d[1]), "+f"(d[2]), "+f"(d[3]) : "r"(da), "r"(db));
}
template <int N> __device__ __forceinline__ void reg_fence(float (&d)[N]) {
#pragma unroll
  for (int i = 0; i < N; i++) asm volatile("" : "+f"(d[i])::"memory");
}
template <int N> __device__ __forceinline__ void reg_fence(uint32_t (&d)[N]) {
#pragma unroll
  for (int i = 0; i < N; i++) asm volatile("" : "+r"(d[i])::"memory");
}

struct __align__(64) Params {
  unsigned* flags;
  int zero;
  uint8_t pref[128];
  const __nv_bfloat16 *gate_w, *ak, *av, *shk, *ssk, *ssd, *wop;
  CUtensorMap x, c, wq, wuk, wuv, wo, x3, y3, out, w;
};

template <int O, int N, int M> __device__ __forceinline__ void pack_frag(const float (&acc)[N], uint32_t (&pk)[M]) {
#pragma unroll
  for (int i = 0; i < 32; i++) pk[i] = pack_bf16(acc[O + 2 * i], acc[O + 2 * i + 1]);
}
template <int N> __device__ __forceinline__ void pack_frag_scaled(const float (&acc)[N], uint32_t (&pk)[32], float s0, float s1) {
#pragma unroll
  for (int i = 0; i < 32; i++) { const float s = (i & 1) ? s1 : s0; pk[i] = pack_bf16(acc[2 * i] * s, acc[2 * i + 1] * s); }
}
template <int J0 = 0, int J1 = 8, int M> __device__ __forceinline__ void stsm_frag(const uint32_t (&pk)[M], uint32_t a) {
#pragma unroll
  for (int jj = J0; jj < J1; jj++)
    asm volatile("stmatrix.sync.aligned.m8n8.x4.shared.b16 [%0], {%1,%2,%3,%4};" ::"r"((a ^ ((jj & 3) << 5)) + (jj >> 2) * 16384),
                 "r"(pk[4 * jj]), "r"(pk[4 * jj + 1]), "r"(pk[4 * jj + 2]), "r"(pk[4 * jj + 3]) : "memory");
}

struct Cons {
  uint32_t sb;
  uint32_t pf;
  int wg, tid;
  __device__ __forceinline__ void wait_full(int g) { mbar_wait(sb + SM_BAR + (B_FULL + g) * 8, (pf >> g) & 1); pf ^= 1u << g; }
  uint32_t relb;
  __device__ __forceinline__ void release(int g, int n) {
    if (tid < 2 * n) asm volatile("mbarrier.arrive.shared::cluster.b64 _, [%0];" ::"r"(relb + g * 8) : "memory");
  }
  __device__ __forceinline__ void turn_begin() { bar_sync(1 + wg, 256); }
  __device__ __forceinline__ void turn_end() { bar_arrive(2 - wg, 256); }
  __device__ __forceinline__ void staged(int e) { __syncwarp(); if ((tid & 31) == 0) mbar_arrive(sb + SM_BAR + (B_EV + 2 * e + wg) * 8); }
  int zero;
  int rnd;
  uint32_t pfree;
  __device__ __forceinline__ void wait_stage_free() { mbar_wait(sb + SM_BAR + (B_FREE + wg) * 8, pfree); pfree ^= 1; }
  __device__ __forceinline__ bool try_full(int g) { return mbar_test(sb + SM_BAR + (B_FULL + g) * 8, (pf >> g) & 1); }
};

constexpr float SM_C = 0.08838834764831845f * 1.4426950408889634f;
struct SoftState { float m0, m1, l0, l1; int shifted; };
__device__ __forceinline__ void ex2_rot(float& t, float s, uint32_t never_zero) {
  asm("{\n.reg .pred p;\nsetp.ne.u32 p, %2, 0;\n@p ex2.approx.ftz.f32 %0, %1;\n}\n" : "+f"(t) : "f"(s), "r"(never_zero));
}
__device__ __forceinline__ void pin(float a, uint32_t never_zero) {
  asm volatile("{\n.reg .pred p;\nsetp.eq.u32 p, %1, 0;\n@p st.shared.f32 [%1], %0;\n}\n" ::"f"(a), "r"(never_zero) : "memory");
}
template <int O, int N> __device__ __forceinline__ void reg_fence_part(uint32_t (&d)[32]) {
#pragma unroll
  for (int i = O; i < O + N; i++) asm volatile("" : "+r"(d[i])::"memory");
}
template <int Q, int W, int N> __device__ __forceinline__ void exp_quarter(const float (&S)[N], uint32_t (&P)[32], float (&t)[ROT], float& s0, float& s1, uint32_t nz) {
#pragma unroll
  for (int i = 8 * Q; i < 8 * Q + 8; i++) {
    float& a = t[(2 * i) % ROT];
    float& b = t[(2 * i + 1) % ROT];
    if (2 * i < ROT) { a = ex2(S[2 * i]); b = ex2(S[2 * i + 1]); }
    else { ex2_rot(a, S[2 * i], nz); ex2_rot(b, S[2 * i + 1], nz); }
    if (i < 2) { if (i) s1 = a + b; else s0 = a + b; }
    else if (SUMV == 0) { if (i & 1) { s1 += a; s1 += b; } else { s0 += a; s0 += b; } }
    else { if (i & 1) s1 += a + b; else s0 += a + b; }
    if (i == 8 * Q) { pin(EXPV == 1 && Q ? s1 : s0, nz); wg_wait<W>(); reg_fence_part<8 * Q, 8>(P); }
    P[i] = pack_bf16(a, b);
  }
}
template <int N> __device__ __forceinline__ void shift_scores(float (&S)[N], float d0, float d1) {
#pragma unroll
  for (int i = 0; i < N; i++) S[i] -= (i & 2) ? d1 : d0;
}
__device__ __forceinline__ bool soft_high(float s0, float s1, float lim = SM_LIMIT) { return s0 > lim || s1 > lim; }
__device__ __forceinline__ bool soft_unsafe(float s0, float s1, bool first) {
  uint32_t b0 = __ballot_sync(0xffffffffu, s0 >= SM_LOW), b1 = __ballot_sync(0xffffffffu, s1 >= SM_LOW);
  b0 |= b0 >> 1; b0 |= b0 >> 2; b1 |= b1 >> 1; b1 |= b1 >> 2;
  return __any_sync(0xffffffffu, soft_high(s0, s1)) || (first && (b0 & b1 & 0x11111111u) != 0x11111111u);
}
template <int N> __device__ __forceinline__ void soft_fix(const float (&S)[N], float (&O)[64], SoftState& z, bool first, float& d0, float& d1) {
  d0 = d1 = first ? -INFINITY : 0.f;
#pragma unroll
  for (int j = 0; j < N / 4; j++) { d0 = fmaxf(d0, fmaxf(S[4 * j], S[4 * j + 1])); d1 = fmaxf(d1, fmaxf(S[4 * j + 2], S[4 * j + 3])); }
  d0 = fmaxf(d0, __shfl_xor_sync(0xffffffffu, d0, 1)); d1 = fmaxf(d1, __shfl_xor_sync(0xffffffffu, d1, 1));
  d0 = fmaxf(d0, __shfl_xor_sync(0xffffffffu, d0, 2)); d1 = fmaxf(d1, __shfl_xor_sync(0xffffffffu, d1, 2));
  const float sc0 = ex2(-fmaxf(d0, 0.f)), sc1 = ex2(-fmaxf(d1, 0.f));
  z.m0 += d0; z.m1 += d1; z.l0 *= sc0; z.l1 *= sc1; z.shifted = 1;
#pragma unroll
  for (int j = 0; j < 16; j++) { O[4 * j] *= sc0; O[4 * j + 1] *= sc0; O[4 * j + 2] *= sc1; O[4 * j + 3] *= sc1; }
}
template <int M> __device__ __forceinline__ void pin32(const uint32_t (&v)[M], uint32_t never_zero) {
#pragma unroll
  for (int i = 0; i < 32; i += 4)
    asm volatile("{\n.reg .pred p;\nsetp.eq.u32 p, %4, 0;\n@p st.shared.v4.b32 [%4], {%0,%1,%2,%3};\n}\n" ::"r"(v[i]), "r"(v[i + 1]), "r"(v[i + 2]), "r"(v[i + 3]), "r"(never_zero) : "memory");
}
template <int N> __device__ __forceinline__ void mask_diag(float (&S)[N], float nd) {
  asm volatile("" : "+f"(nd));
#pragma unroll
  for (int i = 0; i < 32; i++) {
    const float beyond = __saturatef(nd + (float)(8 * (i >> 2) + (i & 1) - 4 * (i & 2)));
    S[N - 32 + i] = fmaf(beyond, -3.0e38f, S[N - 32 + i]);
  }
}
__device__ __forceinline__ float quad_sum(float v) {
  v += __shfl_xor_sync(0xffffffffu, v, 1);
  v += __shfl_xor_sync(0xffffffffu, v, 2);
  return v;
}
__device__ __forceinline__ void issue_qk(float (&S)[64], uint32_t dq, uint32_t dk) {
  mma_ss_n128_init<0>(S, dq, dk);
#pragma unroll
  for (int s = 1; s < 8; s++) mma_ss_n128<0>(S, dq + (s >> 2) * 1024 + (s & 3) * 2, dk + (s >> 2) * 1024 + (s & 3) * 2);
}
__device__ __forceinline__ void issue_qk(float (&S)[32], uint32_t dq, uint32_t dk) {
  mma_ss_n64_init(S, dq, dk);
#pragma unroll
  for (int s = 1; s < 8; s++) mma_ss_n64(S, dq + (s >> 2) * 1024 + (s & 3) * 2, dk + (s >> 2) * 1024 + (s & 3) * 2);
}
template <int H> __device__ __forceinline__ void issue_pv(float (&O)[64], const uint32_t (&P)[32], uint32_t dv, int acc, bool on) {
  if (on) {
#pragma unroll
    for (int s = 4 * H; s < 4 * H + 4; s++) {
      mma_rs_n128<1>(O, P[4 * s], P[4 * s + 1], P[4 * s + 2], P[4 * s + 3], dv + s * 128, s != 0 ? 1 : acc);
      if (s & 1) wg_commit();
    }
  } else { wg_commit(); wg_commit(); }
}
constexpr uint32_t DG = GR >> 4;
__device__ __forceinline__ void stage_q2(Cons& c, const float (&O)[64], uint32_t (&P)[32], uint32_t stg) {
  wg_commit(); wg_commit(); wg_commit(); wg_commit();
  c.turn_end();
  pack_frag<0>(O, P);
  stsm_frag(P, stg);
  fence_async_smem();
}
__device__ __forceinline__ void attn_half(Cons& c, float (&O)[64], uint32_t (&P)[32], SoftState& z, uint32_t dk0, uint32_t dkk, uint32_t dv0, float dmask, int last) {
  float S[32];
  FTH(8 + last * 32, 0);
  c.turn_begin();
  FTH(9 + last * 32, 0);
  wg_fence();
  issue_qk(S, dk0 + (last ? 0 : 2 * DG), dkk + (last ? 8 : 4) * DG);
  wg_commit();
  issue_pv<0>(O, P, dv0 + 10 * DG, 1, last);
  issue_pv<1>(O, P, dv0 + 10 * DG, 1, last);
  c.turn_end();
  c.wait_full(last ? 12 : 6);
  FTH(10 + last * 32, 0);
  wg_wait<4>();
  reg_fence(S);
  FTH(11 + last * 32, 0);
  c.release(last ? 8 : 4, 2);
  mask_diag(S, dmask);
  float s0, s1, d0 = z.m0, d1 = z.m1;
#pragma unroll 1
  for (int pass = 0;; pass++) {
    if (z.shifted) shift_scores(S, d0, d1);
    float tr[ROT];
    exp_quarter<0, 3>(S, P, tr, s0, s1, c.sb);
    exp_quarter<1, 2>(S, P, tr, s0, s1, c.sb);
    pin(s1, c.sb); wg_wait<0>(); reg_fence_part<16, 16>(P); reg_fence(O);
    if (!soft_unsafe(s0, s1, !last) || pass) break;
    soft_fix(S, O, z, !last, d0, d1);
  }
  FTH(12 + last * 32, 0);
  z.l0 += s0; z.l1 += s1;
  c.release(10, last ? 2 : 0);
  if (!last) c.wait_full(8);
  FTH(13 + last * 32, 0);
}

template <int V> struct IC { static constexpr int value = V; };
__device__ __forceinline__ int conv_next(int g, bool spare) { return g >= NGR - 2 ? g - (NGR - 4) : !spare && g == 4 ? 1 : g + 2; }
__device__ __forceinline__ void conv_final(uint32_t rb, uint32_t yb, bool on) {
  const uint4 q0 = lds128(rb), q1 = lds128(rb + 4096), q2 = lds128(rb + 8192), q3 = lds128(rb + 12288);
  auto fin = [&](uint32_t x0, uint32_t x1, uint32_t x2, uint32_t x3) { return hadd2(hadd2(x0, x1), hadd2(x2, x3)); };
  asm volatile("{\n.reg .pred p;\nsetp.ne.b32 p, %5, 0;\n@p st.shared.v4.b32 [%0], {%1,%2,%3,%4};\n}\n" ::"r"(yb), "r"(fin(q0.x, q1.x, q2.x, q3.x)),
               "r"(fin(q0.y, q1.y, q2.y, q3.y)), "r"(fin(q0.z, q1.z, q2.z, q3.z)), "r"(fin(q0.w, q1.w, q2.w, q3.w)), "r"((int)on) : "memory");
}
__device__ __forceinline__ void conv_tasks(Cons& c, const Params& p, int ntask, bool spare, int ch, int chstep, uint32_t dd, uint32_t dkk, int w, int lane) {
  const uint32_t sb = c.sb;
  int g = 2 + c.wg;
  uint32_t rb = sb + g * GR;
  const uint32_t yb = sb + c.wg * 8192 + c.tid * 16;
  const int gt = 8 * w + (lane >> 2) + (lane & 3);
  uint32_t a[64], hb;
  auto lda = [&](int s) {
    a[4 * s] = lds32(hb + s * 256); a[4 * s + 1] = lds32(hb + s * 256 + 128);
    a[4 * s + 2] = lds32(hb + s * 256 + 16); a[4 * s + 3] = lds32(hb + s * 256 + 144);
  };
  auto first_a = [&]() {
    hb = sb + g * GR + WBYTES - 28 + gt * 4;
    lda(0); lda(15);
  };
  c.wait_full(g);
  first_a();
#pragma unroll 1
  for (int i = 0; i < ntask; i++) {
    const uint32_t base = sb + g * GR;
    FTC(0);
    lda(1); lda(14);
    a[0] = hadd2(a[0], gt == 7 ? dd : 0u); a[2] = hadd2(a[2], gt == 3 ? dd : 0u);
    float acc[128];
    const uint32_t db = dkk + ((WPL / 16 - 1) << 16) + g * DG + WZ / 16;
    FTC(2);
    c.turn_begin();
    FTC(3);
    auto pair = [&](auto kc) {
      constexpr int k = decltype(kc)::value;
      if (k < 7) wg_fence();
      if (k == 7) c.turn_end();
      conv_step<k, 7>(acc, a, db);
      conv_step<15 - k, 7>(acc, a, db);
      if (k < 6) { lda(k + 2); lda(13 - k); }
      if (k == 0) conv_final(rb, yb, i > 0);
      if (k == 1) {
        conv_final(rb + 2048, yb + 2048, i > 0);
        __syncwarp();
        if (lane == 0 && i > 0) mbar_arrive(sb + SM_BAR + (B_EV + c.wg) * 8);
      }
      if (k == 6) dd = __bfloat16_as_ushort(p.ssd[(ch + chstep) & (DM - 1)]);
    };
    pair(IC<0>()); pair(IC<1>()); pair(IC<2>()); pair(IC<3>()); pair(IC<4>()); pair(IC<5>()); pair(IC<6>()); pair(IC<7>());
    wg_commit();
    FTC(4);
    g = conv_next(g, spare);
    ch += chstep;
    rb = base + c.tid * 16;
    if (i + 1 < ntask) c.wait_full(g);
    wg_wait<0>();
    reg_fence(acc);
    reg_fence(a);
    bar_sync(3 + c.wg, 128);
    FTC(5);
    first_a();
    const int tw = (lane & 3) + w;
    const uint32_t xb = base + w * 4096 + tw * 32 + (lane >> 2) * 4;
#pragma unroll
    for (int j = 0; j < 32; j++) {
      float v0 = acc[4 * j], v1 = acc[4 * j + 1];
      if (j > 0) { v0 += acc[j > 0 ? 4 * j - 2 : 0]; v1 += acc[j > 0 ? 4 * j - 1 : 0]; }
      uint32_t v = pack_bf16(v0, v1), ad = xb + j * 128;
      if (j == 31 && tw >= 4) { v = 0; ad -= 4096; }
      asm volatile("st.shared.b32 [%0], %1;" ::"r"(ad), "r"(v) : "memory");
    }
    c.wait_stage_free();
    FTC(6);
  }
  bar_sync(3 + c.wg, 128);
  conv_final(rb, yb, true);
  conv_final(rb + 2048, yb + 2048, true);
  c.staged(0);
}

__global__ void __cluster_dims__(2, 1, 1) __launch_bounds__(NTHREADS, 1) mega_kernel(const __grid_constant__ Params p) {
  extern __shared__ __align__(1024) uint8_t smem_raw[];
  FTS(0);
  const uint32_t sb = smem_u32(smem_raw);
  const int wgi = __shfl_sync(0xffffffffu, threadIdx.x >> 7, 0);
  const int warp = __shfl_sync(0xffffffffu, threadIdx.x >> 5, 0);
  const uint32_t rank = blockIdx.x & 1;
  int slot;
  {
    uint32_t smid; asm volatile("mov.u32 %0, %smid;" : "=r"(smid));
    slot = p.pref[((smid >> 1) + (threadIdx.x & (smid >> 16))) & 127];
  }
  if (warp >= 3) {
    if (elect()) {
#pragma unroll
      for (int k = 0; k < 4; k++) mbar_init(sb + SM_BAR + ((warp - 3) * 4 + k) * 8, k == 1 && warp == 7 ? 11 : warp < (k ? 7 : 8) ? 1 : 4);
      if (warp == 7) mbar_expect_tx(sb + SM_BAR + B_SLOT * 8, 8);
      asm volatile("fence.mbarrier_init.release.cluster;" ::: "memory");
    }
    __syncwarp();
  }
  FTS(1);
  cluster_arrive();
  if (warp == 2) { prefetch_tm(&p.c); prefetch_tm(rank ? &p.wuv : &p.wuk); FTSW(5); }
  slot = __shfl_sync(0xffffffffu, slot, 0);
  const int pref = slot;
  if (warp < 4) {
    asm volatile("setmaxnreg.dec.sync.aligned.u32 40;");
    if (warp == 1 + 4 * rank) {
      unsigned taken = threadIdx.x == 32;
#pragma unroll 1
      for (int n = 0; n < NSLOT; n++) {
        asm volatile("{\n.reg .pred p;\nsetp.ne.b32 p, %0, 0;\n@p atom.relaxed.gpu.global.exch.b32 %0, [%1], 1;\n}\n" : "+r"(taken) : "l"(CLAIMP(slot)) : "memory");
        if (!__any_sync(0xffffffffu, taken)) break;
        slot = slot == NSLOT - 1 ? 0 : slot + 1;
      }
    }
    cluster_wait();
    if (threadIdx.x == 32) {
#pragma unroll
      for (int r = 0; r < 2; r++)
        asm volatile("{\n.reg .b32 a, b;\nmapa.shared::cluster.u32 a, %0, %1;\nadd.u32 b, a, %3;\nst.async.shared::cluster.mbarrier::complete_tx::bytes.u32 [b], %2, [a];\n}\n"
                     ::"r"(sb + SM_BAR + B_SLOT * 8), "r"(r), "r"(slot | pref << 8), "r"((V_SLOT - B_SLOT) * 8 + rank * 4) : "memory");
    }
    if (warp == 0) {
      if (elect()) {
#pragma unroll 1
        for (int kk = 0; kk < 4; kk++) {
          const int g0 = 2 + 3 * kk;
          const uint32_t fb = sb + SM_BAR + (B_FULL + g0) * 8;
          FTSW(kk);
          mbar_expect_tx(fb, 3 * GR);
          tma2d(sb + g0 * GR, &p.c, kk * 64, (KV_ROW(pref & 7, 0) + rank) * 128, fb);
          tma3d_mc(sb + (g0 + 1 + rank) * GR, rank ? &p.wuv : &p.wuk, 0, kk * 64, ((pref & 56) >> 1) + 2 * KV_HEAD(pref & 7, 0), fb);
        }
        FTSW(4);
        prefetch_tm(&p.x); prefetch_tm(&p.wq);
      }
    }
  }
  int grp, idx, lb;
  int cn, cch, cstep;
  bool spare, redo;
  auto get_slot = [&]() {
    mbar_wait(sb + SM_BAR + B_SLOT * 8, 0);
    const uint32_t sv0 = __shfl_sync(0xffffffffu, lds32(sb + SM_BAR + V_SLOT * 8), 0), sv1 = __shfl_sync(0xffffffffu, lds32(sb + SM_BAR + V_SLOT * 8 + 4), 0);
    grp = (sv0 & 255) >> 3; idx = sv0 & 7; lb = (sv0 & 255) * 2 + rank;
    spare = grp == 8; redo = spare || sv0 != sv1;
    cn = spare ? CN_SPARE : CN_MAIN; cch = spare ? lb - NMAIN : 4 * CN_SPARE + CN_MAIN * lb; cstep = spare ? 4 : 1;
    if (FINE_MODE != 7) TS(0);
  };

  if (wgi == 0) {
    asm volatile("setmaxnreg.dec.sync.aligned.u32 40;");
    const int lane = threadIdx.x & 31;
    cluster_arrive();
    get_slot();
    uint32_t pe = 0;
    auto acquire = [&](int g, int n, uint32_t m) {
      int i = g;
#pragma unroll 1
      do mbar_wait1(sb + SM_BAR + (B_EMPTY + i) * 8, (pe >> i) & 1); while (++i < g + n);
      pe ^= m << g;
    };
    if (warp == 3) {
      if (!spare) {
        const int s0 = lb * 16;
#pragma unroll 1
        for (int cg = 0; cg < 16; cg++) {
          if (cg == 3 || cg == 10) {
#pragma unroll 1
            for (int n = 0; n < 20 && !__any_sync(0xffffffffu, mbar_try(sb + SM_BAR + B_SLOT * 8, cg == 3)); n++);
          } else if (cg < 3) __nanosleep(800);
          const int ch = cg * 64 + 2 * lane;
          const uint32_t* kp = reinterpret_cast<const uint32_t*>(p.ak + (size_t)s0 * DM + ch);
          const uint32_t* vp = reinterpret_cast<const uint32_t*>(p.av + (size_t)s0 * DM + ch);
          const uint4 sw = __ldg(reinterpret_cast<const uint4*>(p.shk + ch * 4));
          uint32_t k3 = 0, k2 = 0, k1 = 0, k0 = 0, up = 0;
          if (lb > 0) { k3 = ldg_stream(kp - 4 * 512); k2 = ldg_stream(kp - 3 * 512); k1 = ldg_stream(kp - 2 * 512); k0 = ldg_stream(kp - 512); up = ldg_stream(vp - 512); }
          const uint32_t w0 = __byte_perm(sw.x, sw.z, 0x5410), w1 = __byte_perm(sw.x, sw.z, 0x7632);
          const uint32_t w2 = __byte_perm(sw.y, sw.w, 0x5410), w3 = __byte_perm(sw.y, sw.w, 0x7632);
          up = hmul2(hfma2(k0, w0, hfma2(k1, w1, hfma2(k2, w2, hmul2(k3, w3)))), up);
#pragma unroll 1
          for (int hb = 0; hb < 2; hb++) {
            uint32_t kk[8], u[8];
#pragma unroll
            for (int r = 0; r < 8; r++) { kk[r] = ldg_stream(kp + r * 512); u[r] = ldg_stream(vp + r * 512); }
#pragma unroll
            for (int r = 0; r < 8; r++) {
              k3 = k2; k2 = k1; k1 = k0; k0 = kk[r];
              u[r] = hmul2(hfma2(k0, w0, hfma2(k1, w1, hfma2(k2, w2, hmul2(k3, w3)))), u[r]);
            }
            if (lane == 0) asm volatile("cp.async.bulk.wait_group.read 0;" ::: "memory");
            __syncwarp();
            const uint32_t dst = sb + SM_UST + lane * 32 + ((lane & 4) << 2);
#pragma unroll
            for (int cc = 0; cc < 2; cc++) {
              const uint32_t sel = cc ? 0x7632 : 0x5410;
              asm volatile("st.shared.v4.b32 [%0], {%1,%2,%3,%4};" ::"r"(dst + cc * 1024), "r"(__byte_perm(u[6], u[5], sel)), "r"(__byte_perm(u[4], u[3], sel)),
                           "r"(__byte_perm(u[2], u[1], sel)), "r"(__byte_perm(u[0], up, sel)) : "memory");
              asm volatile("st.shared.v4.b32 [%0], {%1,%2,%3,%4};" ::"r"((dst ^ 16) + cc * 1024), "r"(__byte_perm(u[7], u[6], sel)), "r"(__byte_perm(u[5], u[4], sel)),
                           "r"(__byte_perm(u[3], u[2], sel)), "r"(__byte_perm(u[1], u[0], sel)) : "memory");
            }
            fence_async_smem();
            __syncwarp();
            if (lane == 0) {
              asm volatile("cp.async.bulk.tensor.3d.global.shared::cta.bulk_group [%0, {%2, %3, %4}], [%1];\ncp.async.bulk.commit_group;"
                           ::"l"(&p.w), "r"(sb + SM_UST), "r"(WZ / 2 + lb * 16 + (hb ^ 1) * (WPL / 2)), "r"(cg * 32), "r"(0) : "memory");
            }
            up = u[7];
            kp += 8 * 512; vp += 8 * 512;
          }
          if ((cg & (cg + 1)) == 0 && lane == 0) {
            asm volatile("cp.async.bulk.wait_group 0;" ::: "memory");
            fence_release();
            flag_add(FLAG(F_U + 32 - __clz(cg)));
          }
          TSW(10 + cg);
        }
        prefetch_tm(&p.wo); prefetch_tm(&p.x3); prefetch_tm(&p.y3); prefetch_tm(&p.out);
        if (P3PF) {
          const int rt = 2 * grp + rank;
          unsigned v;
          asm volatile("ld.acquire.gpu.global.u32 %0, [%1];" : "=r"(v) : "l"(FLAG(F_CTX + rt * 2)) : "memory");
#pragma unroll 1
          for (int kb = P3PF0; kb < P3PF0 + P3PF; kb++) {
            const uint8_t* a = lane < 16 ? g_cimg + (unsigned)((rt * 64 + kb) * GR + (idx * 16 + lane) * 128) : (const uint8_t*)p.wop + (unsigned)(kb * 64 * DM * 2 + (lb * 8 + (lane & 7)) * 128);
            if (lane < 24 && v == 32) asm volatile("prefetch.global.L2 [%0];" ::"l"(a));
          }
        }
      } else {
#pragma unroll 1
        for (int i = 0, g = 2; i < 32; i++) {
          acquire(g, 2, 3);
          if (elect()) {
            const uint32_t fb = sb + SM_BAR + (B_FULL + g) * 8;
            if (i == 0) { mbar_expect_tx(fb - 8, 2048); bulk_g2s(sb + GR, p.gate_w, 2048, fb - 8); }
            mbar_expect_tx(fb, 2 * GR);
            tma3d(sb + g * GR, &p.x3, 0, (lb - NMAIN) * 512 + (i >> 3) * 128, (i & 7) * 2, fb);
          }
          g = g == NGR - 2 ? 2 : g + 2;
        }
        bar_arrive(5, 64);
      }
      if (lane == 0) {
        unsigned long long t0, t1;
        asm volatile("mov.u64 %0, %globaltimer;" : "=l"(t0));
        while (!mbar_try(sb + SM_BAR + B_DONE * 8, 0)) {
          asm volatile("mov.u64 %0, %globaltimer;" : "=l"(t1));
          if (t1 - t0 > 2000000000ull) __trap();
        }
      }
    } else if (warp != 0) {
      const int w = warp - 1, ne = 12 + (cn + 1 - w) / 2;
      uint32_t p0 = 0;
      int cg = 2 + w, ch = cch + w * cstep;
#pragma unroll 1
      for (int e = spare ? 12 : 0; e < ne; e++) {
        const int rnd = e >= 6, k = e - 6 * rnd, rt = k == 4 ? idx : 15 - idx;
        uint8_t* dst = k < 4 ? g_kv + (size_t)(((k & 1) * 16 + 2 * grp + KV_HEAD(idx, k >> 1)) * 16 + KV_ROW(idx, k >> 1) + rank) * 32768 + w * 8192
                     : k < 6 ? g_cimg + (size_t)(rt * 32 + 16 * rnd + 2 * grp + rank) * 32768 + (w ^ (k & 1)) * 8192
                             : reinterpret_cast<uint8_t*>(g_yT + (size_t)ch * SEQ);
        const uint32_t src = sb + w * 8192 + (k == 4 ? 2 * GR : 0);
        if (e == 6) flag_wait(FLAG(F_AD + grp), 32);
        mbar_wait1(sb + SM_BAR + (B_EV + (k == 4 ? 2 : 0) + w) * 8, k == 4 ? rnd : p0);
        if (k != 4) p0 ^= 1;
        if (lane < 4 && k >= 6 && (!spare || e < ne - 6)) mbar_arrive_cluster(sb + SM_BAR + (B_EMPTY + cg) * 8, lane & 1);
        fence_async_smem();
        if (elect()) {
#pragma unroll 1
          for (int i = 0; i < (k >= 6 ? 1 : 8); i++) {
            const uint32_t o = (i >> 2) * 16384 + (i & 3) * 2048;
            asm volatile("cp.async.bulk.global.shared::cta.bulk_group [%0], [%1], %2;" ::"l"(dst + o), "r"(src + o), "r"(k >= 6 ? 4096 : 2048) : "memory");
            asm volatile("cp.async.bulk.commit_group;\ncp.async.bulk.wait_group.read %0;" ::"n"(ST_OUT) : "memory");
          }
          asm volatile("cp.async.bulk.wait_group 0;" ::: "memory");
          if (k != 4) mbar_arrive(sb + SM_BAR + (B_FREE + w) * 8);
        }
        __syncwarp();
        if (lane < (k == 4 ? 4 : e == 11 || (e == ne - 1 && !spare) ? 2 : 0))
          mbar_arrive_cluster(sb + SM_BAR + (B_EMPTY + (k == 4 ? 2 : e == 11) + (lane >> 1)) * 8, lane & 1);
        if (k >= 3) {
          fence_release();
          const unsigned fl = k == 3 ? F_KV + rnd * 8 + grp : k < 6 ? F_CTX + rt * 2 + rnd : F_Y + ((unsigned)ch >> 7);
          if (lane <= (e == 5)) flag_add(FLAG(lane ? F_AD + grp : fl));
        }
        if (k >= 6) { cg = conv_next(cg, spare); ch += 2 * cstep; }
      }
      if (lane == 0) mbar_arrive(sb + SM_BAR + B_DONE * 8);
    } else {
#pragma unroll 1
      for (int rnd = 0; rnd < (spare ? 0 : 2); rnd++) {
        const int hp = 16 * rnd + 2 * grp, head = hp + rank;
#pragma unroll 1
        for (int kk = rnd || redo ? 0 : 4; kk < 32; kk++) {
          const int g0 = 2 + 3 * (kk & 3);
          acquire(g0, kk < 4 ? 3 : 1, 7);
          if (elect()) {
            const uint32_t fb = sb + SM_BAR + (B_FULL + g0) * 8;
            mbar_expect_tx(fb, 3 * GR);
            if (kk < 16) {
              tma2d(sb + g0 * GR, &p.c, (kk & 7) * 64, (KV_ROW(idx, kk >> 3) + rank) * 128, fb);
              tma3d_mc(sb + (g0 + 1 + rank) * GR, rank ? &p.wuv : &p.wuk, 0, (kk & 7) * 64, (hp + KV_HEAD(idx, kk >> 3)) * 2, fb);
            } else {
              tma2d_mc(sb + (g0 + rank) * GR, &p.x, (kk - 16) * 64, (rank ? 15 - idx : idx) * 128, fb);
              tma3d(sb + (g0 + 2) * GR, &p.wq, 0, (kk - 16) * 64, head * 2, fb);
            }
          }
        }
        flag_wait(FLAG(F_KV + rnd * 8 + grp), 32);
        fence_async_all();
        acquire(2, 1, 3);
        int g0 = 4;
#pragma unroll 1
        for (int n = 0; n < 36; n += n == 0 || n == 33 ? 2 : 1) {
          const int it = (n >> 1) - (n & 1);
          const int blk = it & 15 ? (it <= idx ? it - 1 : 15 - it) : it ? 15 - idx : idx;
          acquire(g0, n < 6 ? 2 : 1, 3);
          if (elect()) {
            const uint32_t fb = sb + SM_BAR + (B_FULL + g0) * 8;
            if (n == 5) mbar_arrive(sb + SM_BAR + B_SLOT * 8);
            mbar_expect_tx(fb, 2 * GR);
            bulk_g2s(sb + g0 * GR, g_kv + (unsigned)((((n & 1) * 16 + (head & 15)) * 16 + blk) * 32768), 2 * GR, fb);
          }
          g0 = n == 13 ? 12 : g0 == 12 ? 4 : g0 + 2;
        }
      }
      if (spare) { bar_sync(5, 64); pe = 0x3FC0; }
      auto conv_fill = [&](int g, int ch) {
        acquire(g, 1, 1);
        if (elect()) {
          const uint32_t fb = sb + SM_BAR + (B_FULL + g) * 8;
          if (!spare) FTP(64 + 48 + g);
          mbar_expect_tx(fb, WBYTES + 4096);
          bulk_g2s<true>(sb + g * GR, g_w + (size_t)ch * WSTRIDE, WBYTES, fb);
          bulk_g2s<true>(sb + g * GR + WBYTES, p.ssk + (size_t)ch * SEQ, 4096, fb);
        }
      };
#pragma unroll 1
      for (int i = 0, g = 2; i < cn; i++) {
        if ((i & 15) == 0) { flag_wait(FLAG(F_U + (spare ? 32 - __clz(i >> 4) : 4)), NMAIN); fence_async_all(); }
        conv_fill(g + (i & 1), cch + i * cstep);
        if (i & 1) g = conv_next(g, spare);
      }
      if (!spare) {
        const int rt = 2 * grp + rank, ct = idx;
        int g0 = P3G;
        const uint8_t* src = g_cimg + (unsigned)(rt * 64 * GR);
#pragma unroll 1
        for (int kb = 0; kb < 64; kb++) {
          if (!(kb & 31)) { flag_wait(FLAG(F_CTX + rt * 2 + (kb >> 5)), 32); fence_async_all(); }
          acquire(g0, kb < 11 ? 2 : 1, 3);
          if (elect()) {
            const uint32_t fb = sb + SM_BAR + (B_FULL + g0) * 8;
            if (kb < 16) FTP(48 + kb);
            mbar_expect_tx(fb, 2 * GR);
            bulk_g2s<true>(sb + g0 * GR, src, GR, fb);
            tma2d_mc<true>(sb + (g0 + 1) * GR + rank * 8192, &p.wo, ct * 128 + rank * 64, kb * 64, fb);
          }
          src += GR;
          g0 = g0 == 12 ? (kb == 3 ? 2 : 0) : g0 + 2;
        }
#pragma unroll 1
        for (int j = 0; j < 2; j++) {
          const int g = P3X + 2 * j;
          flag_wait(FLAG(j ? F_Y + ct : F_GATE), j ? 128 : 32);
          fence_async_all();
          acquire(g, 1, 0);
          if (elect()) {
            const uint32_t fb = sb + SM_BAR + (B_FULL + g) * 8;
            mbar_expect_tx(fb, 2 * GR + 256);
            bulk_g2s(sb + SM_GATE + j * 256, g_gate + (unsigned)(rt * 128 + j * 64), 256, fb);
            tma3d(sb + g * GR, j ? &p.y3 : &p.x3, 0, (j ? ct : rt) * 128, (j ? rt : ct) * 2, fb);
          }
        }
        unsigned n = 0;
        if (lane == 0) n = atomicInc(FLAG(F_EXIT), 0x7fffffffu);
        if (__any_sync(0xffffffffu, n == NMAIN - 1)) {
#pragma unroll
          for (int i = lane; i < 96; i += 32) *reinterpret_cast<uint2*>(FLAG(i)) = make_uint2(0, 0);
        }
      }
      if (lane == 0) mbar_arrive(sb + SM_BAR + B_DONE * 8);
    }
    __syncwarp();
    cluster_wait();
  } else {
    asm volatile("setmaxnreg.inc.sync.aligned.u32 232;");
    FTS(2);
    Cons c;
    c.sb = sb; c.pf = 0; c.wg = wgi - 1; c.tid = threadIdx.x & 127;
    const int lane = threadIdx.x & 31, t = lane & 3;
    const int row = c.wg * 64 + (warp & 3) * 16 + (lane >> 2);
    const uint32_t dkk = desc_k(sb), dk0 = dkk + c.wg * 512, dm0 = desc_mn<8192>(sb), dv0 = desc_mn<16384>(sb);
    const uint32_t dsw = DG + 512 - c.wg * 1024;
    if (c.wg == 1) bar_arrive(1, 256);
    c.pfree = 1;
    asm("mapa.shared::cluster.u32 %0, %1, %2;" : "=r"(c.relb) : "r"(sb + SM_BAR + (B_EMPTY + (c.tid >> 1)) * 8), "r"(c.tid & 1));
    c.zero = p.zero;
    c.rnd = 0;
    const uint32_t stg = sb + (c.wg * 64 + (warp & 3) * 16 + ((lane >> 3) & 1) * 8 + (lane & 7)) * 128 + (((lane >> 4) ^ (lane & 7)) << 4);

    uint32_t dd0;
    auto load_dd = [&]() { asm volatile("ld.global.nc.u16 %0, [%1];" : "=r"(dd0) : "l"(p.ssd + (unsigned)(cch + c.wg * cstep + (lane & c.zero)))); };
    int pass = c.zero;
#pragma unroll 1
    do {
    if (pass) {
      load_dd();
#pragma unroll 1
      for (int g = 2; g < NGR; g += 3) { mbar_wait(sb + SM_BAR + (B_FULL + g) * 8, 0); c.release(g, 3); }
      c.pf = 0x924;
    if (spare) {
      c.wait_full(1);
      int g = 2;
#pragma unroll 1
      for (int r = 0; r < 4; r++) {
        float d[4] = {0.f, 0.f, 0.f, 0.f}, e[4] = {0.f, 0.f, 0.f, 0.f};
#pragma unroll 1
        for (int kb = 0; kb < 16; kb += 2) {
          c.wait_full(g);
          wg_fence();
#pragma unroll 1
          for (int k = 0; k < 4; k++) {
            mma_ss_n8(d, dk0 + g * DG + k * 2, dkk + DG + kb * 8 + k * 2);
            mma_ss_n8(e, dk0 + (g + 1) * DG + k * 2, dkk + DG + kb * 8 + 8 + k * 2);
          }
          wg_commit();
          wg_wait<0>();
          c.release(g, 2);
          g = g == NGR - 2 ? 2 : g + 2;
        }
        reg_fence(d); reg_fence(e);
        d[0] += e[0]; d[2] += e[2];
        if (t == 0) {
          float* gp = g_gate + (unsigned)((lb - NMAIN) * 512 + r * 128 + row);
          gp[0] = rcp(1.f + ex2(-1.4426950408889634f * d[0])); gp[8] = rcp(1.f + ex2(-1.4426950408889634f * d[2]));
        }
      }
      fence_release();
      __syncwarp();
      if (lane == 0) flag_add(FLAG(F_GATE));
      TS(1);
    }
    } else cluster_wait();
    get_slot();
    } while (redo && !pass++);
    FTS(3);
    const float dmask = (float)(2 * t - (row & 63));
    uint32_t pv[32];
#pragma unroll 1
    for (int rnd = 0; rnd < (spare ? 0 : 2); rnd++) {
      float O[64];
      FTM(rnd * 8);
      FTG(0);
      FTH(56, c.rnd == rnd);
      c.wait_full(2);
      FTM(rnd * 8 + 1);
      FTH(57, c.rnd == rnd);
#pragma unroll 1
      for (int tile = c.zero; tile < 2; tile++) {
        float acc[128];
        const bool single = tile == 0;
        {
          FTG(tile * 32 + 1);
          const uint32_t a = dk0 + 2 * DG, b = dm0 + 3 * DG;
          c.turn_begin();
          FTG(tile * 32 + 2);
          FTH(58, c.rnd == rnd);
          wg_fence();
          mma_ss_n256_init<1>(acc, a, b);
#pragma unroll
          for (int k = 1; k < 4; k++) mma_ss_n256<1>(acc, a + k * 2, b + k * 128);
          wg_commit();
          if (single) c.turn_end();
          FTG(tile * 32 + 3);
        }
#pragma unroll 1
        for (int kb = 1; kb < 8; kb++) {
          const int g0 = 2 + 3 * (kb & 3);
          const uint32_t a = dk0 + g0 * DG, b = dm0 + (g0 + 1) * DG;
          const bool second = (kb == 1 && !single) || kb == 7;
          FTG(tile * 32 + kb * 4);
          if (!second) { wg_wait<0>(); c.release(2 + 3 * ((kb - 1) & 3), 3); }
          FTG(tile * 32 + kb * 4 + 1);
          c.wait_full(g0);
          if (!second) c.turn_begin();
          FTG(tile * 32 + kb * 4 + 2);
          wg_fence();
#pragma unroll
          for (int k = 0; k < 4; k++) mma_ss_n256<1>(acc, a + k * 2, b + k * 128);
          wg_commit();
          if (kb != 6) c.turn_end();
          if (second) { wg_wait<1>(); c.release(2 + 3 * ((kb - 1) & 3), 3); }
          FTG(tile * 32 + kb * 4 + 3);
          FTH(58 + kb, c.rnd == rnd || kb > 3);
          if (tile == 1 && kb == 3) { c.wait_stage_free(); stsm_frag<0, 4>(pv, stg); }
          if (tile == 1 && kb == 4) { stsm_frag<4, 8>(pv, stg); c.staged(0); }
        }
        c.rnd = rnd;
        c.wait_stage_free();
        const bool nxt = c.try_full(2);
        wg_wait<0>();
        reg_fence(acc);
        c.release(11, 3);
        pack_frag_scaled(acc, pv, SM_C, SM_C);
        stsm_frag(pv, stg);
        c.staged(0);
        pack_frag<64>(acc, pv);
        pin32(pv, sb);
        FTG(32 + tile * 32);
        if (!nxt) mbar_wait(sb + SM_BAR + (B_FULL + 2) * 8, (c.pf >> 2) & 1);
        c.pf ^= 4;
      }
      TS(1 + rnd * 3);
      FTM(rnd * 8 + 2);
      {
        float qa[64];
        float (&qb)[64] = O;
        {
          FTG(65);
          const uint32_t a = dk0 + 2 * DG, b = dm0 + 4 * DG;
          c.turn_begin();
          FTG(66);
          wg_fence();
          mma_ss_n128_init<1>(qa, a, b);
          mma_ss_n128_init<1>(qb, a + dsw, b);
#pragma unroll
          for (int k = 1; k < 4; k++) {
            mma_ss_n128<1>(qa, a + k * 2, b + k * 128);
            mma_ss_n128<1>(qb, a + dsw + k * 2, b + k * 128);
          }
          wg_commit();
          FTG(67);
        }
#pragma unroll 1
        for (int kb = 1; kb < 16; kb++) {
          const int g0 = 2 + 3 * (kb & 3);
          const uint32_t a = dk0 + g0 * DG, b = dm0 + (g0 + 2) * DG;
          const bool second = kb == 1 || kb == 15;
          FTG(64 + kb * 4);
          if (!second) { wg_wait<0>(); c.release(2 + 3 * ((kb - 1) & 3), 3); }
          FTG(65 + kb * 4);
          c.wait_full(g0);
          if (!second) c.turn_begin();
          FTG(66 + kb * 4);
          FTH(kb - 14, kb < 14);
          wg_fence();
#pragma unroll
          for (int k = 0; k < 4; k++) {
            mma_ss_n128<1>(qa, a + k * 2, b + k * 128);
            mma_ss_n128<1>(qb, a + dsw + k * 2, b + k * 128);
          }
          wg_commit();
          if (kb != 14) c.turn_end();
          if (second) { wg_wait<1>(); c.release(2 + 3 * ((kb - 1) & 3), 3); }
          FTG(67 + kb * 4);
          FTH(2, kb < 15);
          if (kb == QFLUSH) { c.wait_stage_free(); stsm_frag<0, 4>(pv, stg); }
          if (kb == QFLUSH + 1) { stsm_frag<4, 8>(pv, stg); c.staged(0); }
        }
        c.wait_stage_free();
        mbar_wait(sb + SM_BAR + (B_EMPTY + 2) * 8, rnd ^ !redo);
        FTM(rnd * 8 + 3);
        FTH(3, 0);
        wg_wait<0>();
        reg_fence(qa); reg_fence(qb);
        FTH(4, 0);
        c.release(11, 3);
        pack_frag<0>(qa, pv);
        stsm_frag(pv, stg + 2 * GR);
        if (c.wg == 0) {
          pack_frag<0>(qb, pv);
          stsm_frag(pv, stg);
#pragma unroll
          for (int i = 16; i < 32; i++) pv[i] = 0;
        }
        fence_async_smem();
        c.wait_full(4);
      }
      TS(2 + rnd * 3);
      FTM(rnd * 8 + 4);
      FTH(5, 0);
      {
        const int nA = idx + 1;
        uint32_t (&P)[32] = pv;
        SoftState z;
        z.m0 = z.m1 = z.l0 = z.l1 = 0.f; z.shifted = c.zero;
#pragma unroll 1
        for (int seg = c.zero;; seg++) {
        if (c.wg == seg) attn_half(c, O, P, z, dk0, dkk, dv0, dmask, seg);
        if (seg) break;
        FTM(rnd * 8 + 5);
        int gk = c.wg ? 4 : 6, gv = c.wg ? 4 : 8;
        uint32_t dq = dk0 + (1 - c.wg < nA ? 2 * DG : 0), dk = dkk + gk * DG;
#pragma unroll 1
        for (int it = 1 - c.wg; it < 17 - c.wg; it++) {
          float S[64];
          FTA(it * 7 + 0); FTH((it < 3 ? 8 + it * 8 : it * 8 - 88) + 0, it >= 3 && it < 15);
          c.turn_begin();
          FTA(it * 7 + 2); FTH((it < 3 ? 8 + it * 8 : it * 8 - 88) + 1, it >= 3 && it < 15);
          wg_fence();
          issue_qk(S, dq, dk);
          wg_commit();
          const uint32_t dv = dv0 + gv * DG;
          uint32_t relk = c.relb + gk * 8, relv = c.relb + gv * 8;
          gk = it == 6 ? 12 : gv == 12 ? 4 : gv + 2;
          gv = it == 16 ? gk : gk == 12 ? 4 : gk + 2;
          uint32_t fk = sb + SM_BAR + (B_FULL + gk) * 8, fv = sb + SM_BAR + (B_FULL + gv) * 8, park = (c.pf >> gk) & 1, parv = (c.pf >> gv) & 1;
          c.pf ^= (1u << gk) | (1u << gv);
          dq = dk0 + (it + 1 < nA ? 2 * DG : 0); dk = dkk + gk * DG;
          float lo0 = z.l0, lo1 = z.l1;
          const bool first = it == nA || it == 0;
          if (it == nA) {
            if (EARLY_RCP) { lo0 = rcp(quad_sum(lo0)); lo1 = rcp(quad_sum(lo1)); }
            z.m0 = z.m1 = z.l0 = z.l1 = 0.f; z.shifted = 0;
          }
          float s0, s1, d0 = z.m0, d1 = z.m1;
          int pre = z.shifted || (it & 15) == 0;
          float lim = first ? -1.f : SM_LIMIT;
          asm volatile("" : "+r"(relk), "+r"(relv), "+r"(fk), "+r"(fv), "+r"(park), "+r"(parv), "+r"(dq), "+r"(dk), "+r"(pre), "+f"(lim), "+f"(d0), "+f"(d1), "+f"(z.l0), "+f"(z.l1));
          if (it) {
            issue_pv<0>(O, P, dv, it != nA + 1 && it != 1, true);
            issue_pv<1>(O, P, dv, 1, HALFPV ? it + c.wg > 1 : true);
            c.turn_end();
          } else stage_q2(c, O, P, stg);
          FTA(it * 7 + 3); FTH((it < 3 ? 8 + it * 8 : it * 8 - 88) + 2, it >= 3 && it < 15);
          wg_wait<4>();
          reg_fence(S);
          FTA(it * 7 + 4); FTH((it < 3 ? 8 + it * 8 : it * 8 - 88) + 3, it >= 3 && it < 15);
          if (c.tid < 4) asm volatile("mbarrier.arrive.shared::cluster.b64 _, [%0];" ::"r"(relk) : "memory");
#pragma unroll 1
          for (int pass = 0;; pass++) {
            if (pre) {
              if ((it & 15) == 0) mask_diag(S, dmask);
              if (z.shifted) shift_scores(S, d0, d1);
            }
            float tr[ROT];
            exp_quarter<0, 3>(S, P, tr, s0, s1, sb);
            exp_quarter<1, 2>(S, P, tr, s0, s1, sb);
            exp_quarter<2, 1>(S, P, tr, s0, s1, sb);
            exp_quarter<3, 0>(S, P, tr, s0, s1, sb);
            reg_fence(O);
            if (c.tid < (pass || !it ? 0 : 4)) asm volatile("mbarrier.arrive.shared::cluster.b64 _, [%0];" ::"r"(relv) : "memory");
            const bool ok = mbar_test(fk, park) & mbar_test(fv, parv);
            if (!ok) lim = -1.f;
            FTA(it * 7 + 5); FTH((it < 3 ? 8 + it * 8 : it * 8 - 88) + 4, it >= 3 && it < 15);
            if (!__any_sync(0xffffffffu, !(s0 <= lim && s1 <= lim))) break;
            if (pass) break;
            if (it == nA) {
              uint32_t pk[32];
              if (!EARLY_RCP) { lo0 = rcp(quad_sum(lo0)); lo1 = rcp(quad_sum(lo1)); }
              pack_frag_scaled(O, pk, lo0, lo1);
              stsm_frag(pk, stg + 2 * GR);
              c.staged(1);
            }
            if (!ok) { mbar_wait(fk, park); mbar_wait(fv, parv); }
            if (!soft_unsafe(s0, s1, first)) break;
            soft_fix(S, O, z, first, d0, d1);
            pre = 1;
          }
          z.l0 += s0; z.l1 += s1;
          FTA(it * 7 + 6); FTH((it < 3 ? 8 + it * 8 : it * 8 - 88) + 5, it >= 3 && it < 15);
        }
        FTM(rnd * 8 + 6);
        }
        FTH(48, 0);
        load_dd();
        c.turn_begin();
        FTH(49, 0);
        wg_fence();
        issue_pv<0>(O, P, dv0 + 12 * DG, 1, true);
        issue_pv<1>(O, P, dv0 + 12 * DG, 1, !c.wg);
        c.turn_end();
        z.l0 = rcp(quad_sum(z.l0)); z.l1 = rcp(quad_sum(z.l1));
        wg_wait<0>();
        reg_fence(O); reg_fence(P);
        FTH(50, 0);
        c.release(12, 2);
        pack_frag_scaled(O, P, z.l0, z.l1);
        stsm_frag(P, stg);
        c.staged(0);
        FTM(rnd * 8 + 7);
        FTH(51, 0);
      }
      TS(3 + rnd * 3);
    }
    conv_tasks(c, p, (cn + 1 - c.wg) / 2, spare, cch + c.wg * cstep, 2 * cstep, dd0, dkk, warp & 3, lane);
    if (c.wg == 1) c.pf ^= 0x14;
    if (c.wg != spare) c.turn_begin();
    TS(7);
    if (!spare) {
      const int rt = 2 * grp + rank, ct = idx;
      float acc[64];
      int g0 = P3G + 2, pg = P3G;
      {
        FTO(0);
        c.wait_full(P3G);
        FTO(1);
        const uint32_t a = dk0 + P3G * DG, b = dm0 + (P3G + 1) * DG;
        wg_fence();
        mma_ss_n128_init<1>(acc, a, b);
#pragma unroll
        for (int k = 1; k < 4; k++) mma_ss_n128<1>(acc, a + k * 2, b + k * 128);
        wg_commit();
      }
#pragma unroll 1
      for (int kb = 1; kb < 64; kb++) {
        FTO(kb * 2);
        c.wait_full(g0);
        FTO(kb * 2 + 1);
        const uint32_t a = dk0 + g0 * DG, b = dm0 + (g0 + 1) * DG;
        wg_fence();
#pragma unroll
        for (int k = 0; k < 4; k++) mma_ss_n128<1>(acc, a + k * 2, b + k * 128);
        wg_commit();
        wg_wait<1>();
        c.release(pg, kb <= 59 ? 2 : 0);
        if (kb == FDUMP_KB) FTDUMP();
        pg = g0;
        g0 = g0 == 12 ? (kb == 3 ? 2 : 0) : g0 + 2;
      }
      cluster_arrive();
      c.wait_full(P3X);
      c.wait_full(P3Y);
      const float g0f = __uint_as_float(lds32(sb + SM_GATE + row * 4)), g1f = __uint_as_float(lds32(sb + SM_GATE + row * 4 + 32));
      const uint32_t gp0 = pack_bf16(g0f, g0f), gp1 = pack_bf16(g1f, g1f);
      const float h0 = 1.f - g0f, h1 = 1.f - g1f;
      const int w = warp & 3;
      const uint32_t xa = stg + P3X * GR;
      const uint32_t ya = sb + P3Y * GR + c.wg * 16384 + ((lane >> 4) * 8 + (lane & 7)) * 128 + (((2 * w + ((lane >> 3) & 1)) ^ (lane & 7)) << 4);
      uint32_t xy[32];
#pragma unroll
      for (int jj = 0; jj < 8; jj++) {
        uint32_t x[4], y[4];
        asm volatile("ldmatrix.sync.aligned.m8n8.x4.shared.b16 {%0,%1,%2,%3}, [%4];" : "=r"(x[0]), "=r"(x[1]), "=r"(x[2]), "=r"(x[3]) : "r"((xa ^ ((jj & 3) << 5)) + (jj >> 2) * 16384) : "memory");
        asm volatile("ldmatrix.sync.aligned.m8n8.x4.trans.shared.b16 {%0,%1,%2,%3}, [%4];" : "=r"(y[0]), "=r"(y[1]), "=r"(y[2]), "=r"(y[3]) : "r"(ya + jj * 2048) : "memory");
#pragma unroll
        for (int i = 0; i < 4; i++) xy[4 * jj + i] = hmul2(x[i], y[i]);
      }
      wg_wait<0>();
      reg_fence(acc);
      TS(8);
#pragma unroll
      for (int i = 0; i < 32; i++) {
        const float h = (i & 1) ? h1 : h0;
        xy[i] = hfma2((i & 1) ? gp1 : gp0, xy[i], pack_bf16(acc[2 * i] * h, acc[2 * i + 1] * h));
      }
      stsm_frag(xy, xa);
      fence_async_smem();
      __syncwarp();
      if (lane == 0) {
        const int r0 = c.wg * 64 + w * 16;
        tma2d_store(&p.out, sb + P3X * GR + r0 * 128, ct * 128, rt * 128 + r0);
        tma2d_store(&p.out, sb + (P3X + 1) * GR + r0 * 128, ct * 128 + 64, rt * 128 + r0);
        asm volatile("cp.async.bulk.commit_group;\ncp.async.bulk.wait_group.read 0;" ::: "memory");
      }
    } else { FTDUMP(); cluster_arrive(); }
    if (lane == 0) mbar_arrive(sb + SM_BAR + B_DONE * 8);
    __syncwarp();
    TS(9);
    cluster_wait();
  }
}

typedef CUresult (*EncFn)(CUtensorMap*, CUtensorMapDataType, cuuint32_t, void*, const cuuint64_t*, const cuuint64_t*, const cuuint32_t*,
                          const cuuint32_t*, CUtensorMapInterleave, CUtensorMapSwizzle, CUtensorMapL2promotion, CUtensorMapFloatOOBfill);

void enc2d(EncFn enc, CUtensorMap* tm, const void* base, uint64_t cols, uint64_t rows, uint32_t bc, uint32_t br) {
  cuuint64_t dims[2] = {cols, rows}; cuuint64_t strides[1] = {cols * 2}; cuuint32_t box[2] = {bc, br}; cuuint32_t es[2] = {1, 1};
  enc(tm, CU_TENSOR_MAP_DATA_TYPE_BFLOAT16, 2, const_cast<void*>(base), dims, strides, box, es, CU_TENSOR_MAP_INTERLEAVE_NONE,
      CU_TENSOR_MAP_SWIZZLE_128B, CU_TENSOR_MAP_L2_PROMOTION_L2_256B, CU_TENSOR_MAP_FLOAT_OOB_FILL_NONE);
}
void enc3d(EncFn enc, CUtensorMap* tm, const void* base, uint64_t K, uint64_t N, uint32_t bk = 64) {
  cuuint64_t dims[3] = {64, K, N / 64}; cuuint64_t strides[2] = {N * 2, 128}; cuuint32_t box[3] = {64, bk, 2}; cuuint32_t es[3] = {1, 1, 1};
  enc(tm, CU_TENSOR_MAP_DATA_TYPE_BFLOAT16, 3, const_cast<void*>(base), dims, strides, box, es, CU_TENSOR_MAP_INTERLEAVE_NONE,
      CU_TENSOR_MAP_SWIZZLE_128B, CU_TENSOR_MAP_L2_PROMOTION_L2_256B, CU_TENSOR_MAP_FLOAT_OOB_FILL_NONE);
}

}

extern "C" void kernel_launch(void* const* d_in, const int* in_sizes, int n_in, void* d_out, int out_size) {
  (void)in_sizes; (void)n_in; (void)out_size;
  typedef const __nv_bfloat16* BP;
  BP xq = (BP)d_in[0], ak = (BP)d_in[1], av = (BP)d_in[2], shk = (BP)d_in[3], ssk = (BP)d_in[4], ssd = (BP)d_in[5];
  BP ckv = (BP)d_in[7], wq = (BP)d_in[8], wuk = (BP)d_in[9], wuv = (BP)d_in[10], wo = (BP)d_in[11], gw = (BP)d_in[12];

  static EncFn enc = nullptr;
  if (!enc) {
    cudaDriverEntryPointQueryResult qr;
    cudaGetDriverEntryPoint("cuTensorMapEncodeTiled", (void**)&enc, cudaEnableDefault, &qr);
    cudaFuncSetAttribute(mega_kernel, cudaFuncAttributeMaxDynamicSharedMemorySize, SMEM_BYTES);
  }
  Params p;
  void* yT = nullptr;
  cudaGetSymbolAddress(&yT, g_yT);
  enc2d(enc, &p.x, xq, DM, SEQ, 64, 128);
  enc2d(enc, &p.c, ckv, DC, SEQ, 64, 128);
  enc3d(enc, &p.wq, wq, DM, NH * HD);
  enc3d(enc, &p.wuk, wuk, DC, NH * HD);
  enc3d(enc, &p.wuv, wuv, DC, NH * HD);
  enc2d(enc, &p.wo, wo, DM, NH * HD, 64, 64);
  enc3d(enc, &p.x3, xq, SEQ, DM, 128);
  enc3d(enc, &p.y3, yT, DM, SEQ, 128);
  enc2d(enc, &p.out, d_out, DM, SEQ, 64, 16);
  {
    void* wp = nullptr;
    cudaGetSymbolAddress(&wp, g_w);
    cuuint64_t dims[3] = {WSTRIDE / 2, DM / 2, 2}; cuuint64_t strides[2] = {2 * WSTRIDE, WSTRIDE}; cuuint32_t box[3] = {16, 32, 2}; cuuint32_t es[3] = {1, 1, 1};
    enc(&p.w, CU_TENSOR_MAP_DATA_TYPE_BFLOAT16, 3, wp, dims, strides, box, es, CU_TENSOR_MAP_INTERLEAVE_NONE,
        CU_TENSOR_MAP_SWIZZLE_32B, CU_TENSOR_MAP_L2_PROMOTION_NONE, CU_TENSOR_MAP_FLOAT_OOB_FILL_NONE);
  }
  p.zero = 0;
  cudaGetSymbolAddress((void**)&p.flags, g_flags);
  for (int i = 0; i < 128; i++) {
    const int tp = i % NSLOT;
    p.pref[i] = tp < 32 ? (tp & 7) * 8 + (tp >> 3) : tp < 60 ? (1 + (tp - 32) % 7) * 8 + 4 + (tp - 32) / 7 : tp < 62 ? tp + 4 : tp - 58;
  }
  p.gate_w = gw; p.ak = ak; p.av = av; p.shk = shk; p.ssk = ssk; p.ssd = ssd; p.wop = wo;

  mega_kernel<<<132, NTHREADS, SMEM_BYTES>>>(p);
}
```

```cpp
#include <cuda_runtime.h>
#include <cuda.h>
#include <cuda_bf16.h>
#include <stdint.h>

namespace {

constexpr int SEQ = 2048, DM = 1024, DC = 512, NH = 32, HD = 128;
constexpr int GR = 16384;
constexpr int NGR = 14;
constexpr int SM_BAR = NGR * GR;
constexpr int SM_GATE = SM_BAR + 512;
constexpr int SM_UST = SM_GATE + 512;
constexpr int SMEM_BYTES = SM_UST + 2048;
constexpr int NTHREADS = 384;
#define SM_LIMIT 1.0995116e12f
#define SM_LOW 9.094947e-13f
constexpr int CN_MAIN = 5, CN_SPARE = 96;
constexpr int P3G = 6, P3X = 10, P3Y = 12;
constexpr int NMAIN = 128;

constexpr int B_FULL = 0, B_FREE = 14, B_SLOT = 16, B_DONE = 17, B_EMPTY = 18, B_EV = 32, V_SLOT = 36;

__device__ __align__(1024) uint8_t g_kv[2 * 16 * 16 * 32768];
__device__ __align__(1024) uint8_t g_cimg[16 * NH * 32768];
__device__ __align__(1024) __nv_bfloat16 g_yT[DM * SEQ];
__device__ __align__(1024) float g_gate[SEQ];
#define CWIDE 0
constexpr int WZ = CWIDE ? 768 : 256, WPL = WZ + 4096, WBYTES = 2 * WPL + 32, WSTRIDE = 2 * WPL + 128;
__device__ __align__(1024) uint8_t g_w[DM * WSTRIDE];
__device__ __align__(32) unsigned g_flags[96 * 8];
constexpr int F_KV = 0, F_CTX = 16, F_U = 48, F_AD = 56, F_Y = 64, F_GATE = 72, F_EXIT = 73;
constexpr int NSLOT = 66;
#define FLAG(i) (&g_flags[(i) * 8])
#define CLAIMP(i) (p.flags + (i) * 8 + 1)

#define TS(slot)
#define TSW(slot)
#define FTX(i, off)
#define FTDUMP()

#define ST_OUT 0
#define QFLUSH 4
#define X_DELAY 900
#define X_D2 600
#define P3PF 10
#define P3PF0 5
#define EXPV 1
#define SUMV 0
#define ROT 8
#define EARLY_RCP 1
#define KVARR 1
#define KV_ROW(idx, t) (KVARR ? 8 * (t) + 2 * ((idx) & 3) : 2 * (idx))
#define KV_HEAD(idx, t) (KVARR ? (idx) >> 2 : (t))
#define FINE_MODE 0
#define FDUMP_KB 40
#define FINE_RND 1
#define FTA(i) do { if (FINE_MODE == 0) FTX(i, rnd ^ FINE_RND); } while (0)
#define FTG(i) do { if (FINE_MODE == 1) FTX(i, rnd ^ FINE_RND); } while (0)
#define FTM(i) do { if (FINE_MODE == 4) FTX(i, 0); } while (0)
#define FTC(k) do { if (FINE_MODE == 5) FTX((i & 7) * 8 + (k), (i >> 3) ^ FINE_RND); } while (0)
#define FTH(i, off) do { if (FINE_MODE == 6) FTX(i, (c.rnd ^ FINE_RND) | (off)); } while (0)
#define FTS(i)
#define FTSD(i)
#define FTSW(i)
#define FTP(i)
#define FTO(i) do { if (FINE_MODE == 2) FTX(i, 0); } while (0)

__device__ __forceinline__ uint32_t smem_u32(const void* p) { return (uint32_t)__cvta_generic_to_shared(p); }
__device__ __forceinline__ void mbar_init(uint32_t bar, int cnt) { asm volatile("mbarrier.init.shared::cta.b64 [%0], %1;" ::"r"(bar), "r"(cnt) : "memory"); }
__device__ __forceinline__ void mbar_expect_tx(uint32_t bar, uint32_t bytes) { asm volatile("mbarrier.arrive.expect_tx.shared::cta.b64 _, [%0], %1;" ::"r"(bar), "r"(bytes) : "memory"); }
__device__ __forceinline__ void mbar_arrive(uint32_t bar) { asm volatile("mbarrier.arrive.shared::cta.b64 _, [%0];" ::"r"(bar) : "memory"); }
__device__ __forceinline__ void mbar_arrive_cluster(uint32_t bar, uint32_t cta) {
  asm volatile("{\n.reg .b32 r;\nmapa.shared::cluster.u32 r, %0, %1;\nmbarrier.arrive.shared::cluster.b64 _, [r];\n}\n" ::"r"(bar), "r"(cta) : "memory");
}
__device__ __forceinline__ bool mbar_try(uint32_t bar, uint32_t parity) {
  uint32_t ok;
  asm volatile("{\n.reg .pred p;\nmbarrier.try_wait.parity.shared::cta.b64 p, [%1], %2, 20000;\nselp.u32 %0, 1, 0, p;\n}\n" : "=r"(ok) : "r"(bar), "r"(parity) : "memory");
  return ok;
}
__device__ __forceinline__ bool mbar_test(uint32_t bar, uint32_t parity) {
  uint32_t ok;
  asm volatile("{\n.reg .pred p;\nmbarrier.test_wait.parity.shared::cta.b64 p, [%1], %2;\nselp.u32 %0, 1, 0, p;\n}\n" : "=r"(ok) : "r"(bar), "r"(parity) : "memory");
  return ok;
}
__device__ __forceinline__ void mbar_wait(uint32_t bar, uint32_t parity) {
  asm volatile("{\n.reg .pred p;\nWAIT_LOOP:\nbar.warp.sync -1;\nmbarrier.try_wait.parity.shared::cta.b64 p, [%0], %1;\n@!p bra WAIT_LOOP;\n}\n" ::"r"(bar), "r"(parity) : "memory");
}
__device__ __forceinline__ void mbar_wait1(uint32_t bar, uint32_t parity) {
  asm volatile("{\n.reg .pred p;\nWAIT_LOOP:\nbar.warp.sync -1;\nmbarrier.try_wait.parity.shared::cta.b64 p, [%0], %1, 4000;\n@!p bra WAIT_LOOP;\n}\n" ::"r"(bar), "r"(parity) : "memory");
}
constexpr uint64_t EV_FIRST = 0x12F0000000000000ull;
__device__ __forceinline__ uint32_t ldg_stream(const uint32_t* p) {
  uint32_t r; asm volatile("ld.global.nc.L1::no_allocate.L2::cache_hint.b32 %0, [%1], %2;" : "=r"(r) : "l"(p), "l"(EV_FIRST)); return r;
}
#define TMA_LD "cp.async.bulk.tensor."
#define TMA_MB ".shared::cluster.global.mbarrier::complete_tx::bytes"
__device__ __forceinline__ void tma2d(uint32_t dst, const CUtensorMap* tm, int c0, int c1, uint32_t bar) {
  asm volatile(TMA_LD "2d" TMA_MB " [%0], [%1, {%3, %4}], [%2];" ::"r"(dst), "l"(tm), "r"(bar), "r"(c0), "r"(c1) : "memory");
}
template <bool ONCE = false> __device__ __forceinline__ void tma2d_mc(uint32_t dst, const CUtensorMap* tm, int c0, int c1, uint32_t bar) {
  if (ONCE) asm volatile(TMA_LD "2d" TMA_MB ".multicast::cluster.L2::cache_hint [%0], [%1, {%3, %4}], [%2], %5, %6;"
                         ::"r"(dst), "l"(tm), "r"(bar), "r"(c0), "r"(c1), "h"((uint16_t)3), "l"(EV_FIRST) : "memory");
  else asm volatile(TMA_LD "2d" TMA_MB ".multicast::cluster [%0], [%1, {%3, %4}], [%2], %5;"
                    ::"r"(dst), "l"(tm), "r"(bar), "r"(c0), "r"(c1), "h"((uint16_t)3) : "memory");
}
__device__ __forceinline__ void tma3d(uint32_t dst, const CUtensorMap* tm, int c0, int c1, int c2, uint32_t bar) {
  asm volatile(TMA_LD "3d" TMA_MB " [%0], [%1, {%3, %4, %5}], [%2];" ::"r"(dst), "l"(tm), "r"(bar), "r"(c0), "r"(c1), "r"(c2) : "memory");
}
__device__ __forceinline__ void tma3d_mc(uint32_t dst, const CUtensorMap* tm, int c0, int c1, int c2, uint32_t bar) {
  asm volatile(TMA_LD "3d" TMA_MB ".multicast::cluster [%0], [%1, {%3, %4, %5}], [%2], %6;"
               ::"r"(dst), "l"(tm), "r"(bar), "r"(c0), "r"(c1), "r"(c2), "h"((uint16_t)3) : "memory");
}
template <bool ONCE = false> __device__ __forceinline__ void bulk_g2s(uint32_t dst, const void* src, uint32_t bytes, uint32_t bar) {
  if (ONCE) asm volatile("cp.async.bulk" TMA_MB ".L2::cache_hint [%0], [%1], %2, [%3], %4;" ::"r"(dst), "l"(src), "r"(bytes), "r"(bar), "l"(EV_FIRST) : "memory");
  else asm volatile("cp.async.bulk" TMA_MB " [%0], [%1], %2, [%3];" ::"r"(dst), "l"(src), "r"(bytes), "r"(bar) : "memory");
}
__device__ __forceinline__ void tma2d_store(const CUtensorMap* tm, uint32_t src, int c0, int c1) {
  asm volatile("cp.async.bulk.tensor.2d.global.shared::cta.bulk_group [%0, {%2, %3}], [%1];" ::"l"(tm), "r"(src), "r"(c0), "r"(c1) : "memory");
}
__device__ __forceinline__ void prefetch_tm(const CUtensorMap* tm) { asm volatile("prefetch.tensormap [%0];" ::"l"(tm) : "memory"); }
__device__ __forceinline__ void wg_fence() { asm volatile("wgmma.fence.sync.aligned;" ::: "memory"); }
__device__ __forceinline__ void wg_commit() { asm volatile("wgmma.commit_group.sync.aligned;" ::: "memory"); }
template <int N> __device__ __forceinline__ void wg_wait() { asm volatile("wgmma.wait_group.sync.aligned %0;" ::"n"(N) : "memory"); }
__device__ __forceinline__ void bar_sync(int id, int n) { asm volatile("bar.sync %0, %1;" ::"r"(id), "r"(n) : "memory"); }
__device__ __forceinline__ void bar_arrive(int id, int n) { asm volatile("bar.arrive %0, %1;" ::"r"(id), "r"(n) : "memory"); }
__device__ __forceinline__ void fence_async_smem() { asm volatile("fence.proxy.async.shared::cta;" ::: "memory"); }
__device__ __forceinline__ void fence_async_all() { asm volatile("fence.proxy.async.global;" ::: "memory"); }
__device__ __forceinline__ uint32_t pack_bf16(float lo, float hi) { uint32_t r; asm("cvt.rn.bf16x2.f32 %0, %1, %2;" : "=r"(r) : "f"(hi), "f"(lo)); return r; }
__device__ __forceinline__ float ex2(float x) { float r; asm("ex2.approx.ftz.f32 %0, %1;" : "=f"(r) : "f"(x)); return r; }
__device__ __forceinline__ float rcp(float x) { float r; asm("rcp.approx.ftz.f32 %0, %1;" : "=f"(r) : "f"(x)); return r; }
__device__ __forceinline__ void flag_wait(const unsigned* f, unsigned target) {
  unsigned v;
  do { asm volatile("ld.acquire.gpu.global.u32 %0, [%1];" : "=r"(v) : "l"(f) : "memory"); } while (__any_sync(0xffffffffu, v < target));
}
__device__ __forceinline__ bool elect() {
  uint32_t r;
  asm volatile("{\n.reg .pred p;\nelect.sync _|p, -1;\nselp.u32 %0, 1, 0, p;\n}\n" : "=r"(r));
  return r;
}
__device__ __forceinline__ void fence_release() { asm volatile("fence.release.gpu;" ::: "memory"); }
__device__ __forceinline__ void flag_add(unsigned* f) { asm volatile("red.relaxed.gpu.global.inc.u32 [%0], 0x7fffffff;" ::"l"(f) : "memory"); }
__device__ __forceinline__ void cluster_arrive() { asm volatile("barrier.cluster.arrive.relaxed.aligned;" ::: "memory"); }
__device__ __forceinline__ void cluster_wait() { asm volatile("barrier.cluster.wait.aligned;" ::: "memory"); }
__device__ __forceinline__ uint32_t hmul2(uint32_t a, uint32_t b) { uint32_t r; asm("mul.rn.bf16x2 %0, %1, %2;" : "=r"(r) : "r"(a), "r"(b)); return r; }
__device__ __forceinline__ uint32_t hadd2(uint32_t a, uint32_t b) { uint32_t r; asm("add.rn.bf16x2 %0, %1, %2;" : "=r"(r) : "r"(a), "r"(b)); return r; }
__device__ __forceinline__ uint32_t hfma2(uint32_t a, uint32_t b, uint32_t c) { uint32_t r; asm("fma.rn.bf16x2 %0, %1, %2, %3;" : "=r"(r) : "r"(a), "r"(b), "r"(c)); return r; }
__device__ __forceinline__ uint32_t lds32(uint32_t a) { uint32_t r; asm volatile("ld.shared.b32 %0, [%1];" : "=r"(r) : "r"(a) : "memory"); return r; }
__device__ __forceinline__ uint4 lds128(uint32_t a) { uint4 r; asm volatile("ld.shared.v4.b32 {%0,%1,%2,%3}, [%4];" : "=r"(r.x), "=r"(r.y), "=r"(r.z), "=r"(r.w) : "r"(a) : "memory"); return r; }
__device__ __forceinline__ uint32_t desc_k(uint32_t addr) { return ((addr & 0x3FFFF) >> 4) | (1u << 16); }
template <int LBO> __device__ __forceinline__ uint32_t desc_mn(uint32_t addr) { return ((addr & 0x3FFFF) >> 4) | ((uint32_t)(LBO >> 4) << 16); }
#define DHI "0x40000040"

#define R8(d, o) "+f"(d[o]), "+f"(d[o + 1]), "+f"(d[o + 2]), "+f"(d[o + 3]), "+f"(d[o + 4]), "+f"(d[o + 5]), "+f"(d[o + 6]), "+f"(d[o + 7])
#define R32(d, o) R8(d, o), R8(d, o + 8), R8(d, o + 16), R8(d, o + 24)
#define R64(d, o) R32(d, o), R32(d, o + 32)
#define L64 "%0,%1,%2,%3,%4,%5,%6,%7,%8,%9,%10,%11,%12,%13,%14,%15,%16,%17,%18,%19,%20,%21,%22,%23,%24,%25,%26,%27,%28,%29,%30,%31," \
            "%32,%33,%34,%35,%36,%37,%38,%39,%40,%41,%42,%43,%44,%45,%46,%47,%48,%49,%50,%51,%52,%53,%54,%55,%56,%57,%58,%59,%60,%61,%62,%63"
#define L128 L64 ",%64,%65,%66,%67,%68,%69,%70,%71,%72,%73,%74,%75,%76,%77,%78,%79,%80,%81,%82,%83,%84,%85,%86,%87,%88,%89,%90,%91,%92,%93,%94,%95," \
            "%96,%97,%98,%99,%100,%101,%102,%103,%104,%105,%106,%107,%108,%109,%110,%111,%112,%113,%114,%115,%116,%117,%118,%119,%120,%121,%122,%123,%124,%125,%126,%127"

template <int TB> __device__ __forceinline__ void mma_ss_n128(float (&d)[64], uint32_t da, uint32_t db) {
  asm volatile("{\n.reg .b64 da, db;\nmov.b64 da, {%64, " DHI "};\nmov.b64 db, {%65, " DHI "};\n"
               "wgmma.mma_async.sync.aligned.m64n128k16.f32.bf16.bf16 {" L64 "}, da, db, 1, 1, 1, 0, %66;\n}\n"
               : R64(d, 0) : "r"(da), "r"(db), "n"(TB));
}
template <int TB> __device__ __forceinline__ void mma_rs_n128(float (&d)[64], uint32_t a0, uint32_t a1, uint32_t a2, uint32_t a3, uint32_t db, int sd) {
  asm volatile("{\n.reg .pred p;\n.reg .b64 db;\nsetp.ne.b32 p, %69, 0;\nmov.b64 db, {%68, " DHI "};\n"
               "wgmma.mma_async.sync.aligned.m64n128k16.f32.bf16.bf16 {" L64 "}, {%64,%65,%66,%67}, db, p, 1, 1, %70;\n}\n"
               : R64(d, 0) : "r"(a0), "r"(a1), "r"(a2), "r"(a3), "r"(db), "r"(sd), "n"(TB));
}
template <int TB> __device__ __forceinline__ void mma_ss_n256(float (&d)[128], uint32_t da, uint32_t db) {
  asm volatile("{\n.reg .b64 da, db;\nmov.b64 da, {%128, " DHI "};\nmov.b64 db, {%129, " DHI "};\n"
               "wgmma.mma_async.sync.aligned.m64n256k16.f32.bf16.bf16 {" L128 "}, da, db, 1, 1, 1, 0, %130;\n}\n"
               : R64(d, 0), R64(d, 64) : "r"(da), "r"(db), "n"(TB));
}
#define W8(d, o) "=f"(d[o]), "=f"(d[o + 1]), "=f"(d[o + 2]), "=f"(d[o + 3]), "=f"(d[o + 4]), "=f"(d[o + 5]), "=f"(d[o + 6]), "=f"(d[o + 7])
#define W32(d, o) W8(d, o), W8(d, o + 8), W8(d, o + 16), W8(d, o + 24)
#define W64(d, o) W32(d, o), W32(d, o + 32)
template <int TB> __device__ __forceinline__ void mma_ss_n128_init(float (&d)[64], uint32_t da, uint32_t db) {
  asm volatile("{\n.reg .b64 da, db;\nmov.b64 da, {%64, " DHI "};\nmov.b64 db, {%65, " DHI "};\n"
               "wgmma.mma_async.sync.aligned.m64n128k16.f32.bf16.bf16 {" L64 "}, da, db, 0, 1, 1, 0, %66;\n}\n"
               : W64(d, 0) : "r"(da), "r"(db), "n"(TB));
}
template <int TB> __device__ __forceinline__ void mma_ss_n256_init(float (&d)[128], uint32_t da, uint32_t db) {
  asm volatile("{\n.reg .b64 da, db;\nmov.b64 da, {%128, " DHI "};\nmov.b64 db, {%129, " DHI "};\n"
               "wgmma.mma_async.sync.aligned.m64n256k16.f32.bf16.bf16 {" L128 "}, da, db, 0, 1, 1, 0, %130;\n}\n"
               : W64(d, 0), W64(d, 64) : "r"(da), "r"(db), "n"(TB));
}
#define L32 "%0,%1,%2,%3,%4,%5,%6,%7,%8,%9,%10,%11,%12,%13,%14,%15,%16,%17,%18,%19,%20,%21,%22,%23,%24,%25,%26,%27,%28,%29,%30,%31"
__device__ __forceinline__ void mma_ss_n64(float (&d)[32], uint32_t da, uint32_t db) {
  asm volatile("{\n.reg .b64 da, db;\nmov.b64 da, {%32, " DHI "};\nmov.b64 db, {%33, " DHI "};\n"
               "wgmma.mma_async.sync.aligned.m64n64k16.f32.bf16.bf16 {" L32 "}, da, db, 1, 1, 1, 0, 0;\n}\n"
               : R32(d, 0) : "r"(da), "r"(db));
}
__device__ __forceinline__ void mma_ss_n64_init(float (&d)[32], uint32_t da, uint32_t db) {
  asm volatile("{\n.reg .b64 da, db;\nmov.b64 da, {%32, " DHI "};\nmov.b64 db, {%33, " DHI "};\n"
               "wgmma.mma_async.sync.aligned.m64n64k16.f32.bf16.bf16 {" L32 "}, da, db, 0, 1, 1, 0, 0;\n}\n"
               : W32(d, 0) : "r"(da), "r"(db));
}
#define L16 "%0,%1,%2,%3,%4,%5,%6,%7,%8,%9,%10,%11,%12,%13,%14,%15"
template <int O, bool INIT> __device__ __forceinline__ void mma_rs_n32(float (&d)[128], uint32_t a0, uint32_t a1, uint32_t a2, uint32_t a3, uint32_t db) {
  if (INIT) asm volatile("{\n.reg .b64 db;\nmov.b64 db, {%20, 0x00000008};\n"
               "wgmma.mma_async.sync.aligned.m64n32k16.f32.bf16.bf16 {" L16 "}, {%16,%17,%18,%19}, db, 0, 1, 1, 0;\n}\n"
               : W8(d, O), W8(d, O + 8) : "r"(a0), "r"(a1), "r"(a2), "r"(a3), "r"(db));
  else asm volatile("{\n.reg .b64 db;\nmov.b64 db, {%20, 0x00000008};\n"
               "wgmma.mma_async.sync.aligned.m64n32k16.f32.bf16.bf16 {" L16 "}, {%16,%17,%18,%19}, db, 1, 1, 1, 0;\n}\n"
               : R8(d, O), R8(d, O + 8) : "r"(a0), "r"(a1), "r"(a2), "r"(a3), "r"(db));
}
template <int O, bool INIT> __device__ __forceinline__ void mma_rs_n64(float (&d)[128], uint32_t a0, uint32_t a1, uint32_t a2, uint32_t a3, uint32_t db) {
  if (INIT) asm volatile("{\n.reg .b64 db;\nmov.b64 db, {%36, 0x00000008};\n"
               "wgmma.mma_async.sync.aligned.m64n64k16.f32.bf16.bf16 {" L32 "}, {%32,%33,%34,%35}, db, 0, 1, 1, 0;\n}\n"
               : W32(d, O) : "r"(a0), "r"(a1), "r"(a2), "r"(a3), "r"(db));
  else asm volatile("{\n.reg .b64 db;\nmov.b64 db, {%36, 0x00000008};\n"
               "wgmma.mma_async.sync.aligned.m64n64k16.f32.bf16.bf16 {" L32 "}, {%32,%33,%34,%35}, db, 1, 1, 1, 0;\n}\n"
               : R32(d, O) : "r"(a0), "r"(a1), "r"(a2), "r"(a3), "r"(db));
}
template <int S, int J> __device__ __forceinline__ void conv_step(float (&d)[128], const uint32_t (&a)[64], uint32_t db) {
  if constexpr (J >= 0 && J >= (S >> 1)) {
    if constexpr (J >= 8 - 2 * CWIDE) {
      mma_rs_n64<16 * (J - 1), S == 0>(d, a[4 * S], a[4 * S + 1], a[4 * S + 2], a[4 * S + 3], db + (uint32_t)((2 * (J - 1) - S) * 16));
      conv_step<S, J - 2>(d, a, db);
    } else {
      mma_rs_n32<16 * J, S == 0>(d, a[4 * S], a[4 * S + 1], a[4 * S + 2], a[4 * S + 3], db + (uint32_t)((2 * J - S) * 16));
      conv_step<S, J - 1>(d, a, db);
    }
  }
}
__device__ __forceinline__ void mma_ss_n8(float (&d)[4], uint32_t da, uint32_t db) {
  asm volatile("{\n.reg .b64 da, db;\nmov.b64 da, {%4, " DHI "};\nmov.b64 db, {%5, 0x00000008};\n"
               "wgmma.mma_async.sync.aligned.m64n8k16.f32.bf16.bf16 {%0,%1,%2,%3}, da, db, 1, 1, 1, 0, 0;\n}\n"
               : "+f"(d[0]), "+f"(d[1]), "+f"(d[2]), "+f"(d[3]) : "r"(da), "r"(db));
}
template <int N> __device__ __forceinline__ void reg_fence(float (&d)[N]) {
#pragma unroll
  for (int i = 0; i < N; i++) asm volatile("" : "+f"(d[i])::"memory");
}
template <int N> __device__ __forceinline__ void reg_fence(uint32_t (&d)[N]) {
#pragma unroll
  for (int i = 0; i < N; i++) asm volatile("" : "+r"(d[i])::"memory");
}

struct __align__(64) Params {
  unsigned* flags;
  int zero;
  uint8_t pref[128];
  const __nv_bfloat16 *gate_w, *ak, *av, *shk, *ssk, *ssd, *wop;
  CUtensorMap x, c, wq, wuk, wuv, wo, x3, y3, out, w;
};

template <int O, int N, int M> __device__ __forceinline__ void pack_frag(const float (&acc)[N], uint32_t (&pk)[M]) {
#pragma unroll
  for (int i = 0; i < 32; i++) pk[i] = pack_bf16(acc[O + 2 * i], acc[O + 2 * i + 1]);
}
template <int N> __device__ __forceinline__ void pack_frag_scaled(const float (&acc)[N], uint32_t (&pk)[32], float s0, float s1) {
#pragma unroll
  for (int i = 0; i < 32; i++) { const float s = (i & 1) ? s1 : s0; pk[i] = pack_bf16(acc[2 * i] * s, acc[2 * i + 1] * s); }
}
template <int J0 = 0, int J1 = 8, int M> __device__ __forceinline__ void stsm_frag(const uint32_t (&pk)[M], uint32_t a) {
#pragma unroll
  for (int jj = J0; jj < J1; jj++)
    asm volatile("stmatrix.sync.aligned.m8n8.x4.shared.b16 [%0], {%1,%2,%3,%4};" ::"r"((a ^ ((jj & 3) << 5)) + (jj >> 2) * 16384),
                 "r"(pk[4 * jj]), "r"(pk[4 * jj + 1]), "r"(pk[4 * jj + 2]), "r"(pk[4 * jj + 3]) : "memory");
}

struct Cons {
  uint32_t sb;
  uint32_t pf;
  int wg, tid;
  __device__ __forceinline__ void wait_full(int g) { mbar_wait(sb + SM_BAR + (B_FULL + g) * 8, (pf >> g) & 1); pf ^= 1u << g; }
  uint32_t relb;
  __device__ __forceinline__ void release(int g, int n) {
    if (tid < 2 * n) asm volatile("mbarrier.arrive.shared::cluster.b64 _, [%0];" ::"r"(relb + g * 8) : "memory");
  }
  __device__ __forceinline__ void turn_begin() { bar_sync(1 + wg, 256); }
  __device__ __forceinline__ void turn_end() { bar_arrive(2 - wg, 256); }
  __device__ __forceinline__ void staged(int e) { __syncwarp(); if ((tid & 31) == 0) mbar_arrive(sb + SM_BAR + (B_EV + 2 * e + wg) * 8); }
  int zero;
  int rnd;
  uint32_t pfree;
  __device__ __forceinline__ void wait_stage_free() { mbar_wait(sb + SM_BAR + (B_FREE + wg) * 8, pfree); pfree ^= 1; }
  __device__ __forceinline__ bool try_full(int g) { return mbar_test(sb + SM_BAR + (B_FULL + g) * 8, (pf >> g) & 1); }
};

constexpr float SM_C = 0.08838834764831845f * 1.4426950408889634f;
struct SoftState { float m0, m1, l0, l1; int shifted; };
__device__ __forceinline__ void ex2_rot(float& t, float s, uint32_t never_zero) {
  asm("{\n.reg .pred p;\nsetp.ne.u32 p, %2, 0;\n@p ex2.approx.ftz.f32 %0, %1;\n}\n" : "+f"(t) : "f"(s), "r"(never_zero));
}
__device__ __forceinline__ void pin(float a, uint32_t never_zero) {
  asm volatile("{\n.reg .pred p;\nsetp.eq.u32 p, %1, 0;\n@p st.shared.f32 [%1], %0;\n}\n" ::"f"(a), "r"(never_zero) : "memory");
}
template <int O, int N> __device__ __forceinline__ void reg_fence_part(uint32_t (&d)[32]) {
#pragma unroll
  for (int i = O; i < O + N; i++) asm volatile("" : "+r"(d[i])::"memory");
}
template <int Q, int W, int N> __device__ __forceinline__ void exp_quarter(const float (&S)[N], uint32_t (&P)[32], float (&t)[ROT], float& s0, float& s1, uint32_t nz) {
#pragma unroll
  for (int i = 8 * Q; i < 8 * Q + 8; i++) {
    float& a = t[(2 * i) % ROT];
    float& b = t[(2 * i + 1) % ROT];
    if (2 * i < ROT) { a = ex2(S[2 * i]); b = ex2(S[2 * i + 1]); }
    else { ex2_rot(a, S[2 * i], nz); ex2_rot(b, S[2 * i + 1], nz); }
    if (i < 2) { if (i) s1 = a + b; else s0 = a + b; }
    else if (SUMV == 0) { if (i & 1) { s1 += a; s1 += b; } else { s0 += a; s0 += b; } }
    else { if (i & 1) s1 += a + b; else s0 += a + b; }
    if (i == 8 * Q) { pin(EXPV == 1 && Q ? s1 : s0, nz); wg_wait<W>(); reg_fence_part<8 * Q, 8>(P); }
    P[i] = pack_bf16(a, b);
  }
}
template <int N> __device__ __forceinline__ void shift_scores(float (&S)[N], float d0, float d1) {
#pragma unroll
  for (int i = 0; i < N; i++) S[i] -= (i & 2) ? d1 : d0;
}
__device__ __forceinline__ bool soft_high(float s0, float s1, float lim = SM_LIMIT) { return s0 > lim || s1 > lim; }
__device__ __forceinline__ bool soft_unsafe(float s0, float s1, bool first) {
  uint32_t b0 = __ballot_sync(0xffffffffu, s0 >= SM_LOW), b1 = __ballot_sync(0xffffffffu, s1 >= SM_LOW);
  b0 |= b0 >> 1; b0 |= b0 >> 2; b1 |= b1 >> 1; b1 |= b1 >> 2;
  return __any_sync(0xffffffffu, soft_high(s0, s1)) || (first && (b0 & b1 & 0x11111111u) != 0x11111111u);
}
template <int N> __device__ __forceinline__ void soft_fix(const float (&S)[N], float (&O)[64], SoftState& z, bool first, float& d0, float& d1) {
  d0 = d1 = first ? -INFINITY : 0.f;
#pragma unroll
  for (int j = 0; j < N / 4; j++) { d0 = fmaxf(d0, fmaxf(S[4 * j], S[4 * j + 1])); d1 = fmaxf(d1, fmaxf(S[4 * j + 2], S[4 * j + 3])); }
  d0 = fmaxf(d0, __shfl_xor_sync(0xffffffffu, d0, 1)); d1 = fmaxf(d1, __shfl_xor_sync(0xffffffffu, d1, 1));
  d0 = fmaxf(d0, __shfl_xor_sync(0xffffffffu, d0, 2)); d1 = fmaxf(d1, __shfl_xor_sync(0xffffffffu, d1, 2));
  const float sc0 = ex2(-fmaxf(d0, 0.f)), sc1 = ex2(-fmaxf(d1, 0.f));
  z.m0 += d0; z.m1 += d1; z.l0 *= sc0; z.l1 *= sc1; z.shifted = 1;
#pragma unroll
  for (int j = 0; j < 16; j++) { O[4 * j] *= sc0; O[4 * j + 1] *= sc0; O[4 * j + 2] *= sc1; O[4 * j + 3] *= sc1; }
}
template <int M> __device__ __forceinline__ void pin32(const uint32_t (&v)[M], uint32_t never_zero) {
#pragma unroll
  for (int i = 0; i < 32; i += 4)
    asm volatile("{\n.reg .pred p;\nsetp.eq.u32 p, %4, 0;\n@p st.shared.v4.b32 [%4], {%0,%1,%2,%3};\n}\n" ::"r"(v[i]), "r"(v[i + 1]), "r"(v[i + 2]), "r"(v[i + 3]), "r"(never_zero) : "memory");
}
template <int N> __device__ __forceinline__ void mask_diag(float (&S)[N], float nd) {
  asm volatile("" : "+f"(nd));
#pragma unroll
  for (int i = 0; i < 32; i++) {
    const float beyond = __saturatef(nd + (float)(8 * (i >> 2) + (i & 1) - 4 * (i & 2)));
    S[N - 32 + i] = fmaf(beyond, -3.0e38f, S[N - 32 + i]);
  }
}
__device__ __forceinline__ float quad_sum(float v) {
  v += __shfl_xor_sync(0xffffffffu, v, 1);
  v += __shfl_xor_sync(0xffffffffu, v, 2);
  return v;
}
__device__ __forceinline__ void issue_qk(float (&S)[64], uint32_t dq, uint32_t dk) {
  mma_ss_n128_init<0>(S, dq, dk);
#pragma unroll
  for (int s = 1; s < 8; s++) mma_ss_n128<0>(S, dq + (s >> 2) * 1024 + (s & 3) * 2, dk + (s >> 2) * 1024 + (s & 3) * 2);
}
__device__ __forceinline__ void issue_qk(float (&S)[32], uint32_t dq, uint32_t dk) {
  mma_ss_n64_init(S, dq, dk);
#pragma unroll
  for (int s = 1; s < 8; s++) mma_ss_n64(S, dq + (s >> 2) * 1024 + (s & 3) * 2, dk + (s >> 2) * 1024 + (s & 3) * 2);
}
template <int H> __device__ __forceinline__ void issue_pv(float (&O)[64], const uint32_t (&P)[32], uint32_t dv, int acc, bool on) {
  if (on) {
#pragma unroll
    for (int s = 4 * H; s < 4 * H + 4; s++) {
      mma_rs_n128<1>(O, P[4 * s], P[4 * s + 1], P[4 * s + 2], P[4 * s + 3], dv + s * 128, s != 0 ? 1 : acc);
      if (s & 1) wg_commit();
    }
  } else { wg_commit(); wg_commit(); }
}
constexpr uint32_t DG = GR >> 4;
__device__ __forceinline__ void stage_q2(Cons& c, const float (&O)[64], uint32_t (&P)[32], uint32_t stg) {
  wg_commit(); wg_commit(); wg_commit(); wg_commit();
  c.turn_end();
  pack_frag<0>(O, P);
  stsm_frag(P, stg);
  fence_async_smem();
}
__device__ __forceinline__ void attn_half(Cons& c, float (&O)[64], uint32_t (&P)[32], SoftState& z, uint32_t dk0, uint32_t dkk, uint32_t dv0, float dmask, int last) {
  float S[32];
  FTH(8 + last * 32, 0);
  c.turn_begin();
  FTH(9 + last * 32, 0);
  wg_fence();
  issue_qk(S, dk0 + (last ? 0 : 2 * DG), dkk + (last ? 8 : 4) * DG);
  wg_commit();
  issue_pv<0>(O, P, dv0 + 10 * DG, 1, last);
  issue_pv<1>(O, P, dv0 + 10 * DG, 1, last);
  c.turn_end();
  c.wait_full(last ? 12 : 6);
  FTH(10 + last * 32, 0);
  wg_wait<4>();
  reg_fence(S);
  FTH(11 + last * 32, 0);
  c.release(last ? 8 : 4, 2);
  mask_diag(S, dmask);
  float s0, s1, d0 = z.m0, d1 = z.m1;
#pragma unroll 1
  for (int pass = 0;; pass++) {
    if (z.shifted) shift_scores(S, d0, d1);
    float tr[ROT];
    exp_quarter<0, 3>(S, P, tr, s0, s1, c.sb);
    exp_quarter<1, 2>(S, P, tr, s0, s1, c.sb);
    pin(s1, c.sb); wg_wait<0>(); reg_fence_part<16, 16>(P); reg_fence(O);
    if (!soft_unsafe(s0, s1, !last) || pass) break;
    soft_fix(S, O, z, !last, d0, d1);
  }
  FTH(12 + last * 32, 0);
  z.l0 += s0; z.l1 += s1;
  c.release(10, last ? 2 : 0);
  if (!last) c.wait_full(8);
  FTH(13 + last * 32, 0);
}

template <int V> struct IC { static constexpr int value = V; };
__device__ __forceinline__ int conv_next(int g, bool spare) { return g >= NGR - 2 ? g - (NGR - 4) : !spare && g == 4 ? 1 : g + 2; }
__device__ __forceinline__ void conv_final(uint32_t rb, uint32_t yb, bool on) {
  const uint4 q0 = lds128(rb), q1 = lds128(rb + 4096), q2 = lds128(rb + 8192), q3 = lds128(rb + 12288);
  auto fin = [&](uint32_t x0, uint32_t x1, uint32_t x2, uint32_t x3) { return hadd2(hadd2(x0, x1), hadd2(x2, x3)); };
  asm volatile("{\n.reg .pred p;\nsetp.ne.b32 p, %5, 0;\n@p st.shared.v4.b32 [%0], {%1,%2,%3,%4};\n}\n" ::"r"(yb), "r"(fin(q0.x, q1.x, q2.x, q3.x)),
               "r"(fin(q0.y, q1.y, q2.y, q3.y)), "r"(fin(q0.z, q1.z, q2.z, q3.z)), "r"(fin(q0.w, q1.w, q2.w, q3.w)), "r"((int)on) : "memory");
}
__device__ __forceinline__ void conv_tasks(Cons& c, const Params& p, int ntask, bool spare, int ch, int chstep, uint32_t dd, uint32_t dkk, int w, int lane) {
  const uint32_t sb = c.sb;
  int g = 2 + c.wg;
  uint32_t rb = sb + g * GR;
  const uint32_t yb = sb + c.wg * 8192 + c.tid * 16;
  const int gt = 8 * w + (lane >> 2) + (lane & 3);
  uint32_t a[64], hb;
  auto lda = [&](int s) {
    a[4 * s] = lds32(hb + s * 256); a[4 * s + 1] = lds32(hb + s * 256 + 128);
    a[4 * s + 2] = lds32(hb + s * 256 + 16); a[4 * s + 3] = lds32(hb + s * 256 + 144);
  };
  auto first_a = [&]() {
    hb = sb + g * GR + WBYTES - 28 + gt * 4;
    lda(0); lda(15);
  };
  c.wait_full(g);
  first_a();
#pragma unroll 1
  for (int i = 0; i < ntask; i++) {
    const uint32_t base = sb + g * GR;
    FTC(0);
    lda(1); lda(14);
    a[0] = hadd2(a[0], gt == 7 ? dd : 0u); a[2] = hadd2(a[2], gt == 3 ? dd : 0u);
    float acc[128];
    const uint32_t db = dkk + ((WPL / 16 - 1) << 16) + g * DG + WZ / 16;
    FTC(2);
    c.turn_begin();
    FTC(3);
    auto pair = [&](auto kc) {
      constexpr int k = decltype(kc)::value;
      if (k < 7) wg_fence();
      if (k == 7) c.turn_end();
      conv_step<k, 7>(acc, a, db);
      conv_step<15 - k, 7>(acc, a, db);
      if (k < 6) { lda(k + 2); lda(13 - k); }
      if (k == 0) conv_final(rb, yb, i > 0);
      if (k == 1) {
        conv_final(rb + 2048, yb + 2048, i > 0);
        __syncwarp();
        if (lane == 0 && i > 0) mbar_arrive(sb + SM_BAR + (B_EV + c.wg) * 8);
      }
      if (k == 6) dd = __bfloat16_as_ushort(p.ssd[(ch + chstep) & (DM - 1)]);
    };
    pair(IC<0>()); pair(IC<1>()); pair(IC<2>()); pair(IC<3>()); pair(IC<4>()); pair(IC<5>()); pair(IC<6>()); pair(IC<7>());
    wg_commit();
    FTC(4);
    g = conv_next(g, spare);
    ch += chstep;
    rb = base + c.tid * 16;
    if (i + 1 < ntask) c.wait_full(g);
    wg_wait<0>();
    reg_fence(acc);
    reg_fence(a);
    bar_sync(3 + c.wg, 128);
    FTC(5);
    first_a();
    const int tw = (lane & 3) + w;
    const uint32_t xb = base + w * 4096 + tw * 32 + (lane >> 2) * 4;
#pragma unroll
    for (int j = 0; j < 32; j++) {
      float v0 = acc[4 * j], v1 = acc[4 * j + 1];
      if (j > 0) { v0 += acc[j > 0 ? 4 * j - 2 : 0]; v1 += acc[j > 0 ? 4 * j - 1 : 0]; }
      uint32_t v = pack_bf16(v0, v1), ad = xb + j * 128;
      if (j == 31 && tw >= 4) { v = 0; ad -= 4096; }
      asm volatile("st.shared.b32 [%0], %1;" ::"r"(ad), "r"(v) : "memory");
    }
    c.wait_stage_free();
    FTC(6);
  }
  bar_sync(3 + c.wg, 128);
  conv_final(rb, yb, true);
  conv_final(rb + 2048, yb + 2048, true);
  c.staged(0);
}

__global__ void __cluster_dims__(2, 1, 1) __launch_bounds__(NTHREADS, 1) mega_kernel(const __grid_constant__ Params p) {
  extern __shared__ __align__(1024) uint8_t smem_raw[];
  FTS(0);
  const uint32_t sb = smem_u32(smem_raw);
  if (threadIdx.x < 32) { prefetch_tm(&p.c); prefetch_tm(&p.wuk + (blockIdx.x & 1)); }
  const int wgi = __shfl_sync(0xffffffffu, threadIdx.x >> 7, 0);
  const int warp = __shfl_sync(0xffffffffu, threadIdx.x >> 5, 0);
  const uint32_t rank = blockIdx.x & 1;
  int slot;
  {
    uint32_t smid; asm volatile("mov.u32 %0, %smid;" : "=r"(smid));
    slot = p.pref[((smid >> 1) + (threadIdx.x & (smid >> 16))) & 127];
  }
  if (warp >= 3) {
    if (elect()) {
#pragma unroll
      for (int k = 0; k < 4; k++) mbar_init(sb + SM_BAR + ((warp - 3) * 4 + k) * 8, k == 1 && warp == 7 ? 11 : warp < (k ? 7 : 8) ? 1 : 4);
      if (warp == 7) mbar_expect_tx(sb + SM_BAR + B_SLOT * 8, 8);
      asm volatile("fence.mbarrier_init.release.cluster;" ::: "memory");
    }
    __syncwarp();
  }
  FTS(1);
  cluster_arrive();
  slot = __shfl_sync(0xffffffffu, slot, 0);
  const int pref = slot;
  if (warp < 4) {
    asm volatile("setmaxnreg.dec.sync.aligned.u32 40;");
    if (warp == 1 + 4 * rank) {
      unsigned taken = threadIdx.x == 32;
#pragma unroll 1
      for (int n = 0; n < NSLOT; n++) {
        asm volatile("{\n.reg .pred p;\nsetp.ne.b32 p, %0, 0;\n@p atom.relaxed.gpu.global.exch.b32 %0, [%1], 1;\n}\n" : "+r"(taken) : "l"(CLAIMP(slot)) : "memory");
        if (!__any_sync(0xffffffffu, taken)) break;
        slot = slot == NSLOT - 1 ? 0 : slot + 1;
      }
    }
    cluster_wait();
    if (threadIdx.x == 32) {
#pragma unroll
      for (int r = 0; r < 2; r++)
        asm volatile("{\n.reg .b32 a, b;\nmapa.shared::cluster.u32 a, %0, %1;\nadd.u32 b, a, %3;\nst.async.shared::cluster.mbarrier::complete_tx::bytes.u32 [b], %2, [a];\n}\n"
                     ::"r"(sb + SM_BAR + B_SLOT * 8), "r"(r), "r"(slot | pref << 8), "r"((V_SLOT - B_SLOT) * 8 + rank * 4) : "memory");
    }
    if (warp == 0) {
#pragma unroll 1
      for (int kk = 0; kk < 4; kk++) {
        const int g0 = 2 + 3 * kk;
        const uint32_t fb = sb + SM_BAR + (B_FULL + g0) * 8;
        if (elect()) {
          FTSW(kk);
          mbar_expect_tx(fb, 3 * GR);
          tma2d(sb + g0 * GR, &p.c, kk * 64, (KV_ROW(pref & 7, 0) + rank) * 128, fb);
          tma3d_mc(sb + (g0 + 1 + rank) * GR, rank ? &p.wuv : &p.wuk, 0, kk * 64, ((pref & 56) >> 1) + 2 * KV_HEAD(pref & 7, 0), fb);
        }
        if (kk < 3) {
          uint32_t c0, c1;
          asm volatile("mov.u32 %0, %clock;" : "=r"(c0));
          do asm volatile("mov.u32 %0, %clock;" : "=r"(c1)); while (c1 - c0 < (kk ? X_D2 : X_DELAY));
        }
      }
      FTSW(4);
      prefetch_tm(&p.x); prefetch_tm(&p.wq);
    }
  }
  int grp, idx, lb;
  int cn, cch, cstep;
  bool spare, redo;
  auto get_slot = [&]() {
    mbar_wait(sb + SM_BAR + B_SLOT * 8, 0);
    const uint32_t sv0 = __shfl_sync(0xffffffffu, lds32(sb + SM_BAR + V_SLOT * 8), 0), sv1 = __shfl_sync(0xffffffffu, lds32(sb + SM_BAR + V_SLOT * 8 + 4), 0);
    grp = (sv0 & 255) >> 3; idx = sv0 & 7; lb = (sv0 & 255) * 2 + rank;
    spare = grp == 8; redo = spare || sv0 != sv1;
    cn = spare ? CN_SPARE : CN_MAIN; cch = spare ? lb - NMAIN : 4 * CN_SPARE + CN_MAIN * lb; cstep = spare ? 4 : 1;
    if (FINE_MODE != 7) TS(0);
  };

  if (wgi == 0) {
    asm volatile("setmaxnreg.dec.sync.aligned.u32 40;");
    const int lane = threadIdx.x & 31;
    cluster_arrive();
    get_slot();
    uint32_t pe = 0;
    auto acquire = [&](int g, int n, uint32_t m) {
      int i = g;
#pragma unroll 1
      do mbar_wait1(sb + SM_BAR + (B_EMPTY + i) * 8, (pe >> i) & 1); while (++i < g + n);
      pe ^= m << g;
    };
    if (warp == 3) {
      if (!spare) {
        const int s0 = lb * 16;
#pragma unroll 1
        for (int cg = 0; cg < 16; cg++) {
          if (cg == 3 || cg == 10) {
#pragma unroll 1
            for (int n = 0; n < 20 && !__any_sync(0xffffffffu, mbar_try(sb + SM_BAR + B_SLOT * 8, cg == 3)); n++);
          } else if (cg < 3) __nanosleep(800);
          const int ch = cg * 64 + 2 * lane;
          const uint32_t* kp = reinterpret_cast<const uint32_t*>(p.ak + (size_t)s0 * DM + ch);
          const uint32_t* vp = reinterpret_cast<const uint32_t*>(p.av + (size_t)s0 * DM + ch);
          const uint4 sw = __ldg(reinterpret_cast<const uint4*>(p.shk + ch * 4));
          uint32_t k3 = 0, k2 = 0, k1 = 0, k0 = 0, up = 0;
          if (lb > 0) { k3 = ldg_stream(kp - 4 * 512); k2 = ldg_stream(kp - 3 * 512); k1 = ldg_stream(kp - 2 * 512); k0 = ldg_stream(kp - 512); up = ldg_stream(vp - 512); }
          const uint32_t w0 = __byte_perm(sw.x, sw.z, 0x5410), w1 = __byte_perm(sw.x, sw.z, 0x7632);
          const uint32_t w2 = __byte_perm(sw.y, sw.w, 0x5410), w3 = __byte_perm(sw.y, sw.w, 0x7632);
          up = hmul2(hfma2(k0, w0, hfma2(k1, w1, hfma2(k2, w2, hmul2(k3, w3)))), up);
#pragma unroll 1
          for (int hb = 0; hb < 2; hb++) {
            uint32_t kk[8], u[8];
#pragma unroll
            for (int r = 0; r < 8; r++) { kk[r] = ldg_stream(kp + r * 512); u[r] = ldg_stream(vp + r * 512); }
#pragma unroll
            for (int r = 0; r < 8; r++) {
              k3 = k2; k2 = k1; k1 = k0; k0 = kk[r];
              u[r] = hmul2(hfma2(k0, w0, hfma2(k1, w1, hfma2(k2, w2, hmul2(k3, w3)))), u[r]);
            }
            if (lane == 0) asm volatile("cp.async.bulk.wait_group.read 0;" ::: "memory");
            __syncwarp();
            const uint32_t dst = sb + SM_UST + lane * 32 + ((lane & 4) << 2);
#pragma unroll
            for (int cc = 0; cc < 2; cc++) {
              const uint32_t sel = cc ? 0x7632 : 0x5410;
              asm volatile("st.shared.v4.b32 [%0], {%1,%2,%3,%4};" ::"r"(dst + cc * 1024), "r"(__byte_perm(u[6], u[5], sel)), "r"(__byte_perm(u[4], u[3], sel)),
                           "r"(__byte_perm(u[2], u[1], sel)), "r"(__byte_perm(u[0], up, sel)) : "memory");
              asm volatile("st.shared.v4.b32 [%0], {%1,%2,%3,%4};" ::"r"((dst ^ 16) + cc * 1024), "r"(__byte_perm(u[7], u[6], sel)), "r"(__byte_perm(u[5], u[4], sel)),
                           "r"(__byte_perm(u[3], u[2], sel)), "r"(__byte_perm(u[1], u[0], sel)) : "memory");
            }
            fence_async_smem();
            __syncwarp();
            if (lane == 0) {
              asm volatile("cp.async.bulk.tensor.3d.global.shared::cta.bulk_group [%0, {%2, %3, %4}], [%1];\ncp.async.bulk.commit_group;"
                           ::"l"(&p.w), "r"(sb + SM_UST), "r"(WZ / 2 + lb * 16 + (hb ^ 1) * (WPL / 2)), "r"(cg * 32), "r"(0) : "memory");
            }
            up = u[7];
            kp += 8 * 512; vp += 8 * 512;
          }
          if ((cg & (cg + 1)) == 0 && lane == 0) {
            asm volatile("cp.async.bulk.wait_group 0;" ::: "memory");
            fence_release();
            flag_add(FLAG(F_U + 32 - __clz(cg)));
          }
          TSW(10 + cg);
        }
        prefetch_tm(&p.wo); prefetch_tm(&p.x3); prefetch_tm(&p.y3); prefetch_tm(&p.out);
        if (P3PF) {
          const int rt = 2 * grp + rank;
          unsigned v;
          asm volatile("ld.acquire.gpu.global.u32 %0, [%1];" : "=r"(v) : "l"(FLAG(F_CTX + rt * 2)) : "memory");
#pragma unroll 1
          for (int kb = P3PF0; kb < P3PF0 + P3PF; kb++) {
            const uint8_t* a = lane < 16 ? g_cimg + (unsigned)((rt * 64 + kb) * GR + (idx * 16 + lane) * 128) : (const uint8_t*)p.wop + (unsigned)(kb * 64 * DM * 2 + (lb * 8 + (lane & 7)) * 128);
            if (lane < 24 && v == 32) asm volatile("prefetch.global.L2 [%0];" ::"l"(a));
          }
        }
      } else {
#pragma unroll 1
        for (int i = 0, g = 2; i < 32; i++) {
          acquire(g, 2, 3);
          if (elect()) {
            const uint32_t fb = sb + SM_BAR + (B_FULL + g) * 8;
            if (i == 0) { mbar_expect_tx(fb - 8, 2048); bulk_g2s(sb + GR, p.gate_w, 2048, fb - 8); }
            mbar_expect_tx(fb, 2 * GR);
            tma3d(sb + g * GR, &p.x3, 0, (lb - NMAIN) * 512 + (i >> 3) * 128, (i & 7) * 2, fb);
          }
          g = g == NGR - 2 ? 2 : g + 2;
        }
        bar_arrive(5, 64);
      }
      if (lane == 0) {
        unsigned long long t0, t1;
        asm volatile("mov.u64 %0, %globaltimer;" : "=l"(t0));
        while (!mbar_try(sb + SM_BAR + B_DONE * 8, 0)) {
          asm volatile("mov.u64 %0, %globaltimer;" : "=l"(t1));
          if (t1 - t0 > 2000000000ull) __trap();
        }
      }
    } else if (warp != 0) {
      const int w = warp - 1, ne = 12 + (cn + 1 - w) / 2;
      uint32_t p0 = 0;
      int cg = 2 + w, ch = cch + w * cstep;
#pragma unroll 1
      for (int e = spare ? 12 : 0; e < ne; e++) {
        const int rnd = e >= 6, k = e - 6 * rnd, rt = k == 4 ? idx : 15 - idx;
        uint8_t* dst = k < 4 ? g_kv + (size_t)(((k & 1) * 16 + 2 * grp + KV_HEAD(idx, k >> 1)) * 16 + KV_ROW(idx, k >> 1) + rank) * 32768 + w * 8192
                     : k < 6 ? g_cimg + (size_t)(rt * 32 + 16 * rnd + 2 * grp + rank) * 32768 + (w ^ (k & 1)) * 8192
                             : reinterpret_cast<uint8_t*>(g_yT + (size_t)ch * SEQ);
        const uint32_t src = sb + w * 8192 + (k == 4 ? 2 * GR : 0);
        if (e == 6) flag_wait(FLAG(F_AD + grp), 32);
        mbar_wait1(sb + SM_BAR + (B_EV + (k == 4 ? 2 : 0) + w) * 8, k == 4 ? rnd : p0);
        if (k != 4) p0 ^= 1;
        if (lane < 4 && k >= 6 && (!spare || e < ne - 6)) mbar_arrive_cluster(sb + SM_BAR + (B_EMPTY + cg) * 8, lane & 1);
        fence_async_smem();
        if (elect()) {
#pragma unroll 1
          for (int i = 0; i < (k >= 6 ? 1 : 8); i++) {
            const uint32_t o = (i >> 2) * 16384 + (i & 3) * 2048;
            asm volatile("cp.async.bulk.global.shared::cta.bulk_group [%0], [%1], %2;" ::"l"(dst + o), "r"(src + o), "r"(k >= 6 ? 4096 : 2048) : "memory");
            asm volatile("cp.async.bulk.commit_group;\ncp.async.bulk.wait_group.read %0;" ::"n"(ST_OUT) : "memory");
          }
          asm volatile("cp.async.bulk.wait_group 0;" ::: "memory");
          if (k != 4) mbar_arrive(sb + SM_BAR + (B_FREE + w) * 8);
        }
        __syncwarp();
        if (lane < (k == 4 ? 4 : e == 11 || (e == ne - 1 && !spare) ? 2 : 0))
          mbar_arrive_cluster(sb + SM_BAR + (B_EMPTY + (k == 4 ? 2 : e == 11) + (lane >> 1)) * 8, lane & 1);
        if (k >= 3) {
          fence_release();
          const unsigned fl = k == 3 ? F_KV + rnd * 8 + grp : k < 6 ? F_CTX + rt * 2 + rnd : F_Y + ((unsigned)ch >> 7);
          if (lane <= (e == 5)) flag_add(FLAG(lane ? F_AD + grp : fl));
        }
        if (k >= 6) { cg = conv_next(cg, spare); ch += 2 * cstep; }
      }
      if (lane == 0) mbar_arrive(sb + SM_BAR + B_DONE * 8);
    } else {
#pragma unroll 1
      for (int rnd = 0; rnd < (spare ? 0 : 2); rnd++) {
        const int hp = 16 * rnd + 2 * grp, head = hp + rank;
#pragma unroll 1
        for (int kk = rnd || redo ? 0 : 4; kk < 32; kk++) {
          const int g0 = 2 + 3 * (kk & 3);
          acquire(g0, kk < 4 ? 3 : 1, 7);
          if (elect()) {
            const uint32_t fb = sb + SM_BAR + (B_FULL + g0) * 8;
            mbar_expect_tx(fb, 3 * GR);
            if (kk < 16) {
              tma2d(sb + g0 * GR, &p.c, (kk & 7) * 64, (KV_ROW(idx, kk >> 3) + rank) * 128, fb);
              tma3d_mc(sb + (g0 + 1 + rank) * GR, rank ? &p.wuv : &p.wuk, 0, (kk & 7) * 64, (hp + KV_HEAD(idx, kk >> 3)) * 2, fb);
            } else {
              tma2d_mc(sb + (g0 + rank) * GR, &p.x, (kk - 16) * 64, (rank ? 15 - idx : idx) * 128, fb);
              tma3d(sb + (g0 + 2) * GR, &p.wq, 0, (kk - 16) * 64, head * 2, fb);
            }
          }
        }
        flag_wait(FLAG(F_KV + rnd * 8 + grp), 32);
        fence_async_all();
        acquire(2, 1, 3);
        int g0 = 4;
#pragma unroll 1
        for (int n = 0; n < 36; n += n == 0 || n == 33 ? 2 : 1) {
          const int it = (n >> 1) - (n & 1);
          const int blk = it & 15 ? (it <= idx ? it - 1 : 15 - it) : it ? 15 - idx : idx;
          acquire(g0, n < 6 ? 2 : 1, 3);
          if (elect()) {
            const uint32_t fb = sb + SM_BAR + (B_FULL + g0) * 8;
            if (n == 5) mbar_arrive(sb + SM_BAR + B_SLOT * 8);
            mbar_expect_tx(fb, 2 * GR);
            bulk_g2s(sb + g0 * GR, g_kv + (unsigned)((((n & 1) * 16 + (head & 15)) * 16 + blk) * 32768), 2 * GR, fb);
          }
          g0 = n == 13 ? 12 : g0 == 12 ? 4 : g0 + 2;
        }
      }
      if (spare) { bar_sync(5, 64); pe = 0x3FC0; }
      auto conv_fill = [&](int g, int ch) {
        acquire(g, 1, 1);
        if (elect()) {
          const uint32_t fb = sb + SM_BAR + (B_FULL + g) * 8;
          if (!spare) FTP(64 + 48 + g);
          mbar_expect_tx(fb, WBYTES + 4096);
          bulk_g2s<true>(sb + g * GR, g_w + (size_t)ch * WSTRIDE, WBYTES, fb);
          bulk_g2s<true>(sb + g * GR + WBYTES, p.ssk + (size_t)ch * SEQ, 4096, fb);
        }
      };
#pragma unroll 1
      for (int i = 0, g = 2; i < cn; i++) {
        if ((i & 15) == 0) { flag_wait(FLAG(F_U + (spare ? 32 - __clz(i >> 4) : 4)), NMAIN); fence_async_all(); }
        conv_fill(g + (i & 1), cch + i * cstep);
        if (i & 1) g = conv_next(g, spare);
      }
      if (!spare) {
        const int rt = 2 * grp + rank, ct = idx;
        int g0 = P3G;
        const uint8_t* src = g_cimg + (unsigned)(rt * 64 * GR);
#pragma unroll 1
        for (int kb = 0; kb < 64; kb++) {
          if (!(kb & 31)) { flag_wait(FLAG(F_CTX + rt * 2 + (kb >> 5)), 32); fence_async_all(); }
          acquire(g0, kb < 11 ? 2 : 1, 3);
          if (elect()) {
            const uint32_t fb = sb + SM_BAR + (B_FULL + g0) * 8;
            if (kb < 16) FTP(48 + kb);
            mbar_expect_tx(fb, 2 * GR);
            bulk_g2s<true>(sb + g0 * GR, src, GR, fb);
            tma2d_mc<true>(sb + (g0 + 1) * GR + rank * 8192, &p.wo, ct * 128 + rank * 64, kb * 64, fb);
          }
          src += GR;
          g0 = g0 == 12 ? (kb == 3 ? 2 : 0) : g0 + 2;
        }
#pragma unroll 1
        for (int j = 0; j < 2; j++) {
          const int g = P3X + 2 * j;
          flag_wait(FLAG(j ? F_Y + ct : F_GATE), j ? 128 : 32);
          fence_async_all();
          acquire(g, 1, 0);
          if (elect()) {
            const uint32_t fb = sb + SM_BAR + (B_FULL + g) * 8;
            mbar_expect_tx(fb, 2 * GR + 256);
            bulk_g2s(sb + SM_GATE + j * 256, g_gate + (unsigned)(rt * 128 + j * 64), 256, fb);
            tma3d(sb + g * GR, j ? &p.y3 : &p.x3, 0, (j ? ct : rt) * 128, (j ? rt : ct) * 2, fb);
          }
        }
        unsigned n = 0;
        if (lane == 0) n = atomicInc(FLAG(F_EXIT), 0x7fffffffu);
        if (__any_sync(0xffffffffu, n == NMAIN - 1)) {
#pragma unroll
          for (int i = lane; i < 96; i += 32) *reinterpret_cast<uint2*>(FLAG(i)) = make_uint2(0, 0);
        }
      }
      if (lane == 0) mbar_arrive(sb + SM_BAR + B_DONE * 8);
    }
    __syncwarp();
    cluster_wait();
  } else {
    asm volatile("setmaxnreg.inc.sync.aligned.u32 232;");
    FTS(2);
    Cons c;
    c.sb = sb; c.pf = 0; c.wg = wgi - 1; c.tid = threadIdx.x & 127;
    const int lane = threadIdx.x & 31, t = lane & 3;
    const int row = c.wg * 64 + (warp & 3) * 16 + (lane >> 2);
    const uint32_t dkk = desc_k(sb), dk0 = dkk + c.wg * 512, dm0 = desc_mn<8192>(sb), dv0 = desc_mn<16384>(sb);
    const uint32_t dsw = DG + 512 - c.wg * 1024;
    if (c.wg == 1) bar_arrive(1, 256);
    c.pfree = 1;
    asm("mapa.shared::cluster.u32 %0, %1, %2;" : "=r"(c.relb) : "r"(sb + SM_BAR + (B_EMPTY + (c.tid >> 1)) * 8), "r"(c.tid & 1));
    c.zero = p.zero;
    c.rnd = 0;
    const uint32_t stg = sb + (c.wg * 64 + (warp & 3) * 16 + ((lane >> 3) & 1) * 8 + (lane & 7)) * 128 + (((lane >> 4) ^ (lane & 7)) << 4);

    uint32_t dd0;
    auto load_dd = [&]() { asm volatile("ld.global.nc.u16 %0, [%1];" : "=r"(dd0) : "l"(p.ssd + (unsigned)(cch + c.wg * cstep + (lane & c.zero)))); };
    int pass = c.zero;
#pragma unroll 1
    do {
    if (pass) {
      load_dd();
#pragma unroll 1
      for (int g = 2; g < NGR; g += 3) { mbar_wait(sb + SM_BAR + (B_FULL + g) * 8, 0); c.release(g, 3); }
      c.pf = 0x924;
    if (spare) {
      c.wait_full(1);
      int g = 2;
#pragma unroll 1
      for (int r = 0; r < 4; r++) {
        float d[4] = {0.f, 0.f, 0.f, 0.f}, e[4] = {0.f, 0.f, 0.f, 0.f};
#pragma unroll 1
        for (int kb = 0; kb < 16; kb += 2) {
          c.wait_full(g);
          wg_fence();
#pragma unroll 1
          for (int k = 0; k < 4; k++) {
            mma_ss_n8(d, dk0 + g * DG + k * 2, dkk + DG + kb * 8 + k * 2);
            mma_ss_n8(e, dk0 + (g + 1) * DG + k * 2, dkk + DG + kb * 8 + 8 + k * 2);
          }
          wg_commit();
          wg_wait<0>();
          c.release(g, 2);
          g = g == NGR - 2 ? 2 : g + 2;
        }
        reg_fence(d); reg_fence(e);
        d[0] += e[0]; d[2] += e[2];
        if (t == 0) {
          float* gp = g_gate + (unsigned)((lb - NMAIN) * 512 + r * 128 + row);
          gp[0] = rcp(1.f + ex2(-1.4426950408889634f * d[0])); gp[8] = rcp(1.f + ex2(-1.4426950408889634f * d[2]));
        }
      }
      fence_release();
      __syncwarp();
      if (lane == 0) flag_add(FLAG(F_GATE));
      TS(1);
    }
    } else cluster_wait();
    get_slot();
    } while (redo && !pass++);
    FTS(3);
    const float dmask = (float)(2 * t - (row & 63));
    uint32_t pv[32];
#pragma unroll 1
    for (int rnd = 0; rnd < (spare ? 0 : 2); rnd++) {
      float O[64];
      FTM(rnd * 8);
      FTG(0);
      FTH(56, c.rnd == rnd);
      c.wait_full(2);
      FTM(rnd * 8 + 1);
      FTH(57, c.rnd == rnd);
#pragma unroll 1
      for (int tile = c.zero; tile < 2; tile++) {
        float acc[128];
        const bool single = tile == 0;
        {
          FTG(tile * 32 + 1);
          const uint32_t a = dk0 + 2 * DG, b = dm0 + 3 * DG;
          c.turn_begin();
          FTG(tile * 32 + 2);
          FTH(58, c.rnd == rnd);
          wg_fence();
          mma_ss_n256_init<1>(acc, a, b);
#pragma unroll
          for (int k = 1; k < 4; k++) mma_ss_n256<1>(acc, a + k * 2, b + k * 128);
          wg_commit();
          if (single) c.turn_end();
          FTG(tile * 32 + 3);
        }
#pragma unroll 1
        for (int kb = 1; kb < 8; kb++) {
          const int g0 = 2 + 3 * (kb & 3);
          const uint32_t a = dk0 + g0 * DG, b = dm0 + (g0 + 1) * DG;
          const bool second = (kb == 1 && !single) || kb == 7;
          FTG(tile * 32 + kb * 4);
          if (!second) { wg_wait<0>(); c.release(2 + 3 * ((kb - 1) & 3), 3); }
          FTG(tile * 32 + kb * 4 + 1);
          c.wait_full(g0);
          if (!second) c.turn_begin();
          FTG(tile * 32 + kb * 4 + 2);
          wg_fence();
#pragma unroll
          for (int k = 0; k < 4; k++) mma_ss_n256<1>(acc, a + k * 2, b + k * 128);
          wg_commit();
          if (kb != 6) c.turn_end();
          if (second) { wg_wait<1>(); c.release(2 + 3 * ((kb - 1) & 3), 3); }
          FTG(tile * 32 + kb * 4 + 3);
          FTH(58 + kb, c.rnd == rnd || kb > 3);
          if (tile == 1 && kb == 3) { c.wait_stage_free(); stsm_frag<0, 4>(pv, stg); }
          if (tile == 1 && kb == 4) { stsm_frag<4, 8>(pv, stg); c.staged(0); }
        }
        c.rnd = rnd;
        c.wait_stage_free();
        const bool nxt = c.try_full(2);
        wg_wait<0>();
        reg_fence(acc);
        c.release(11, 3);
        pack_frag_scaled(acc, pv, SM_C, SM_C);
        stsm_frag(pv, stg);
        c.staged(0);
        pack_frag<64>(acc, pv);
        pin32(pv, sb);
        FTG(32 + tile * 32);
        if (!nxt) mbar_wait(sb + SM_BAR + (B_FULL + 2) * 8, (c.pf >> 2) & 1);
        c.pf ^= 4;
      }
      TS(1 + rnd * 3);
      FTM(rnd * 8 + 2);
      {
        float qa[64];
        float (&qb)[64] = O;
        {
          FTG(65);
          const uint32_t a = dk0 + 2 * DG, b = dm0 + 4 * DG;
          c.turn_begin();
          FTG(66);
          wg_fence();
          mma_ss_n128_init<1>(qa, a, b);
          mma_ss_n128_init<1>(qb, a + dsw, b);
#pragma unroll
          for (int k = 1; k < 4; k++) {
            mma_ss_n128<1>(qa, a + k * 2, b + k * 128);
            mma_ss_n128<1>(qb, a + dsw + k * 2, b + k * 128);
          }
          wg_commit();
          FTG(67);
        }
#pragma unroll 1
        for (int kb = 1; kb < 16; kb++) {
          const int g0 = 2 + 3 * (kb & 3);
          const uint32_t a = dk0 + g0 * DG, b = dm0 + (g0 + 2) * DG;
          const bool second = kb == 1 || kb == 15;
          FTG(64 + kb * 4);
          if (!second) { wg_wait<0>(); c.release(2 + 3 * ((kb - 1) & 3), 3); }
          FTG(65 + kb * 4);
          c.wait_full(g0);
          if (!second) c.turn_begin();
          FTG(66 + kb * 4);
          FTH(kb - 14, kb < 14);
          wg_fence();
#pragma unroll
          for (int k = 0; k < 4; k++) {
            mma_ss_n128<1>(qa, a + k * 2, b + k * 128);
            mma_ss_n128<1>(qb, a + dsw + k * 2, b + k * 128);
          }
          wg_commit();
          if (kb != 14) c.turn_end();
          if (second) { wg_wait<1>(); c.release(2 + 3 * ((kb - 1) & 3), 3); }
          FTG(67 + kb * 4);
          FTH(2, kb < 15);
          if (kb == QFLUSH) { c.wait_stage_free(); stsm_frag<0, 4>(pv, stg); }
          if (kb == QFLUSH + 1) { stsm_frag<4, 8>(pv, stg); c.staged(0); }
        }
        c.wait_stage_free();
        mbar_wait(sb + SM_BAR + (B_EMPTY + 2) * 8, rnd ^ !redo);
        FTM(rnd * 8 + 3);
        FTH(3, 0);
        wg_wait<0>();
        reg_fence(qa); reg_fence(qb);
        FTH(4, 0);
        c.release(11, 3);
        pack_frag<0>(qa, pv);
        stsm_frag(pv, stg + 2 * GR);
        if (c.wg == 0) {
          pack_frag<0>(qb, pv);
          stsm_frag(pv, stg);
        }
        FTH(6, 0);
        fence_async_smem();
        FTH(7, 0);
        c.wait_full(4);
      }
      TS(2 + rnd * 3);
      FTM(rnd * 8 + 4);
      FTH(5, 0);
      {
        const int nA = idx + 1;
        uint32_t (&P)[32] = pv;
        SoftState z;
        z.m0 = z.m1 = z.l0 = z.l1 = 0.f; z.shifted = c.zero;
#pragma unroll 1
        for (int seg = c.zero;; seg++) {
        if (c.wg == seg) attn_half(c, O, P, z, dk0, dkk, dv0, dmask, seg);
        if (seg) break;
        FTM(rnd * 8 + 5);
        int gk = c.wg ? 4 : 6, gv = c.wg ? 4 : 8;
        uint32_t dq = dk0 + (1 - c.wg < nA ? 2 * DG : 0), dk = dkk + gk * DG;
#pragma unroll 1
        for (int it = 1 - c.wg; it < 17 - c.wg; it++) {
          float S[64];
          FTA(it * 7 + 0); FTH((it < 3 ? 8 + it * 8 : it * 8 - 88) + 0, it >= 3 && it < 15);
          c.turn_begin();
          FTA(it * 7 + 2); FTH((it < 3 ? 8 + it * 8 : it * 8 - 88) + 1, it >= 3 && it < 15);
          wg_fence();
          issue_qk(S, dq, dk);
          wg_commit();
          const uint32_t dv = dv0 + gv * DG;
          uint32_t relk = c.relb + gk * 8, relv = c.relb + gv * 8;
          gk = it == 6 ? 12 : gv == 12 ? 4 : gv + 2;
          gv = it == 16 ? gk : gk == 12 ? 4 : gk + 2;
          uint32_t fk = sb + SM_BAR + (B_FULL + gk) * 8, fv = sb + SM_BAR + (B_FULL + gv) * 8, park = (c.pf >> gk) & 1, parv = (c.pf >> gv) & 1;
          c.pf ^= (1u << gk) | (1u << gv);
          dq = dk0 + (it + 1 < nA ? 2 * DG : 0); dk = dkk + gk * DG;
          float lo0 = z.l0, lo1 = z.l1;
          const bool first = it == nA || it == 0;
          if (it == nA) {
            if (EARLY_RCP) { lo0 = rcp(quad_sum(lo0)); lo1 = rcp(quad_sum(lo1)); }
            z.m0 = z.m1 = z.l0 = z.l1 = 0.f; z.shifted = 0;
          }
          float s0, s1, d0 = z.m0, d1 = z.m1;
          int pre = z.shifted || (it & 15) == 0;
          float lim = first ? -1.f : SM_LIMIT;
          asm volatile("" : "+r"(relk), "+r"(relv), "+r"(fk), "+r"(fv), "+r"(park), "+r"(parv), "+r"(dq), "+r"(dk), "+r"(pre), "+f"(lim), "+f"(d0), "+f"(d1), "+f"(z.l0), "+f"(z.l1));
          if (it) {
            issue_pv<0>(O, P, dv, it != nA + 1 && it != 1, true);
            issue_pv<1>(O, P, dv, 1, it + c.wg > 1);
            c.turn_end();
          } else stage_q2(c, O, P, stg);
          FTA(it * 7 + 3); FTH((it < 3 ? 8 + it * 8 : it * 8 - 88) + 2, it >= 3 && it < 15);
          wg_wait<4>();
          reg_fence(S);
          FTA(it * 7 + 4); FTH((it < 3 ? 8 + it * 8 : it * 8 - 88) + 3, it >= 3 && it < 15);
          if (c.tid < 4) asm volatile("mbarrier.arrive.shared::cluster.b64 _, [%0];" ::"r"(relk) : "memory");
#pragma unroll 1
          for (int pass = 0;; pass++) {
            if (pre) {
              if ((it & 15) == 0) mask_diag(S, dmask);
              if (z.shifted) shift_scores(S, d0, d1);
            }
            float tr[ROT];
            exp_quarter<0, 3>(S, P, tr, s0, s1, sb);
            exp_quarter<1, 2>(S, P, tr, s0, s1, sb);
            exp_quarter<2, 1>(S, P, tr, s0, s1, sb);
            exp_quarter<3, 0>(S, P, tr, s0, s1, sb);
            reg_fence(O);
            if (c.tid < (pass || !it ? 0 : 4)) asm volatile("mbarrier.arrive.shared::cluster.b64 _, [%0];" ::"r"(relv) : "memory");
            const bool ok = mbar_test(fk, park) & mbar_test(fv, parv);
            if (!ok) lim = -1.f;
            FTA(it * 7 + 5); FTH((it < 3 ? 8 + it * 8 : it * 8 - 88) + 4, it >= 3 && it < 15);
            if (!__any_sync(0xffffffffu, !(s0 <= lim && s1 <= lim))) break;
            if (pass) break;
            if (it == nA) {
              uint32_t pk[32];
              if (!EARLY_RCP) { lo0 = rcp(quad_sum(lo0)); lo1 = rcp(quad_sum(lo1)); }
              pack_frag_scaled(O, pk, lo0, lo1);
              stsm_frag(pk, stg + 2 * GR);
              c.staged(1);
            }
            if (!ok) { mbar_wait(fk, park); mbar_wait(fv, parv); }
            if (!soft_unsafe(s0, s1, first)) break;
            soft_fix(S, O, z, first, d0, d1);
            pre = 1;
          }
          z.l0 += s0; z.l1 += s1;
          FTA(it * 7 + 6); FTH((it < 3 ? 8 + it * 8 : it * 8 - 88) + 5, it >= 3 && it < 15);
        }
        FTM(rnd * 8 + 6);
        }
        FTH(48, 0);
        load_dd();
        c.turn_begin();
        FTH(49, 0);
        wg_fence();
        issue_pv<0>(O, P, dv0 + 12 * DG, 1, true);
        issue_pv<1>(O, P, dv0 + 12 * DG, 1, !c.wg);
        c.turn_end();
        z.l0 = rcp(quad_sum(z.l0)); z.l1 = rcp(quad_sum(z.l1));
        wg_wait<0>();
        reg_fence(O); reg_fence(P);
        FTH(50, 0);
        c.release(12, 2);
        pack_frag_scaled(O, P, z.l0, z.l1);
        stsm_frag(P, stg);
        c.staged(0);
        FTM(rnd * 8 + 7);
        FTH(51, 0);
      }
      TS(3 + rnd * 3);
    }
    conv_tasks(c, p, (cn + 1 - c.wg) / 2, spare, cch + c.wg * cstep, 2 * cstep, dd0, dkk, warp & 3, lane);
    if (c.wg == 1) c.pf ^= 0x14;
    if (c.wg != spare) c.turn_begin();
    TS(7);
    if (!spare) {
      const int rt = 2 * grp + rank, ct = idx;
      float acc[64];
      int g0 = P3G + 2, pg = P3G;
      {
        FTO(0);
        c.wait_full(P3G);
        FTO(1);
        const uint32_t a = dk0 + P3G * DG, b = dm0 + (P3G + 1) * DG;
        wg_fence();
        mma_ss_n128_init<1>(acc, a, b);
#pragma unroll
        for (int k = 1; k < 4; k++) mma_ss_n128<1>(acc, a + k * 2, b + k * 128);
        wg_commit();
      }
#pragma unroll 1
      for (int kb = 1; kb < 64; kb++) {
        FTO(kb * 2);
        c.wait_full(g0);
        FTO(kb * 2 + 1);
        const uint32_t a = dk0 + g0 * DG, b = dm0 + (g0 + 1) * DG;
        wg_fence();
#pragma unroll
        for (int k = 0; k < 4; k++) mma_ss_n128<1>(acc, a + k * 2, b + k * 128);
        wg_commit();
        wg_wait<1>();
        c.release(pg, kb <= 59 ? 2 : 0);
        if (kb == FDUMP_KB) FTDUMP();
        pg = g0;
        g0 = g0 == 12 ? (kb == 3 ? 2 : 0) : g0 + 2;
      }
      cluster_arrive();
      c.wait_full(P3X);
      c.wait_full(P3Y);
      const float g0f = __uint_as_float(lds32(sb + SM_GATE + row * 4)), g1f = __uint_as_float(lds32(sb + SM_GATE + row * 4 + 32));
      const uint32_t gp0 = pack_bf16(g0f, g0f), gp1 = pack_bf16(g1f, g1f);
      const float h0 = 1.f - g0f, h1 = 1.f - g1f;
      const int w = warp & 3;
      const uint32_t xa = stg + P3X * GR;
      const uint32_t ya = sb + P3Y * GR + c.wg * 16384 + ((lane >> 4) * 8 + (lane & 7)) * 128 + (((2 * w + ((lane >> 3) & 1)) ^ (lane & 7)) << 4);
      uint32_t xy[32];
#pragma unroll
      for (int jj = 0; jj < 8; jj++) {
        uint32_t x[4], y[4];
        asm volatile("ldmatrix.sync.aligned.m8n8.x4.shared.b16 {%0,%1,%2,%3}, [%4];" : "=r"(x[0]), "=r"(x[1]), "=r"(x[2]), "=r"(x[3]) : "r"((xa ^ ((jj & 3) << 5)) + (jj >> 2) * 16384) : "memory");
        asm volatile("ldmatrix.sync.aligned.m8n8.x4.trans.shared.b16 {%0,%1,%2,%3}, [%4];" : "=r"(y[0]), "=r"(y[1]), "=r"(y[2]), "=r"(y[3]) : "r"(ya + jj * 2048) : "memory");
#pragma unroll
        for (int i = 0; i < 4; i++) xy[4 * jj + i] = hmul2(x[i], y[i]);
      }
      wg_wait<0>();
      reg_fence(acc);
      TS(8);
#pragma unroll
      for (int i = 0; i < 32; i++) {
        const float h = (i & 1) ? h1 : h0;
        xy[i] = hfma2((i & 1) ? gp1 : gp0, xy[i], pack_bf16(acc[2 * i] * h, acc[2 * i + 1] * h));
      }
      stsm_frag(xy, xa);
      fence_async_smem();
      __syncwarp();
      if (lane == 0) {
        const int r0 = c.wg * 64 + w * 16;
        tma2d_store(&p.out, sb + P3X * GR + r0 * 128, ct * 128, rt * 128 + r0);
        tma2d_store(&p.out, sb + (P3X + 1) * GR + r0 * 128, ct * 128 + 64, rt * 128 + r0);
        asm volatile("cp.async.bulk.commit_group;\ncp.async.bulk.wait_group.read 0;" ::: "memory");
      }
    } else { FTDUMP(); cluster_arrive(); }
    if (lane == 0) mbar_arrive(sb + SM_BAR + B_DONE * 8);
    __syncwarp();
    TS(9);
    cluster_wait();
  }
}

typedef CUresult (*EncFn)(CUtensorMap*, CUtensorMapDataType, cuuint32_t, void*, const cuuint64_t*, const cuuint64_t*, const cuuint32_t*,
                          const cuuint32_t*, CUtensorMapInterleave, CUtensorMapSwizzle, CUtensorMapL2promotion, CUtensorMapFloatOOBfill);

void enc2d(EncFn enc, CUtensorMap* tm, const void* base, uint64_t cols, uint64_t rows, uint32_t bc, uint32_t br) {
  cuuint64_t dims[2] = {cols, rows}; cuuint64_t strides[1] = {cols * 2}; cuuint32_t box[2] = {bc, br}; cuuint32_t es[2] = {1, 1};
  enc(tm, CU_TENSOR_MAP_DATA_TYPE_BFLOAT16, 2, const_cast<void*>(base), dims, strides, box, es, CU_TENSOR_MAP_INTERLEAVE_NONE,
      CU_TENSOR_MAP_SWIZZLE_128B, CU_TENSOR_MAP_L2_PROMOTION_L2_256B, CU_TENSOR_MAP_FLOAT_OOB_FILL_NONE);
}
void enc3d(EncFn enc, CUtensorMap* tm, const void* base, uint64_t K, uint64_t N, uint32_t bk = 64) {
  cuuint64_t dims[3] = {64, K, N / 64}; cuuint64_t strides[2] = {N * 2, 128}; cuuint32_t box[3] = {64, bk, 2}; cuuint32_t es[3] = {1, 1, 1};
  enc(tm, CU_TENSOR_MAP_DATA_TYPE_BFLOAT16, 3, const_cast<void*>(base), dims, strides, box, es, CU_TENSOR_MAP_INTERLEAVE_NONE,
      CU_TENSOR_MAP_SWIZZLE_128B, CU_TENSOR_MAP_L2_PROMOTION_L2_256B, CU_TENSOR_MAP_FLOAT_OOB_FILL_NONE);
}

}

extern "C" void kernel_launch(void* const* d_in, const int* in_sizes, int n_in, void* d_out, int out_size) {
  (void)in_sizes; (void)n_in; (void)out_size;
  typedef const __nv_bfloat16* BP;
  BP xq = (BP)d_in[0], ak = (BP)d_in[1], av = (BP)d_in[2], shk = (BP)d_in[3], ssk = (BP)d_in[4], ssd = (BP)d_in[5];
  BP ckv = (BP)d_in[7], wq = (BP)d_in[8], wuk = (BP)d_in[9], wuv = (BP)d_in[10], wo = (BP)d_in[11], gw = (BP)d_in[12];

  static EncFn enc = nullptr;
  if (!enc) {
    cudaDriverEntryPointQueryResult qr;
    cudaGetDriverEntryPoint("cuTensorMapEncodeTiled", (void**)&enc, cudaEnableDefault, &qr);
    cudaFuncSetAttribute(mega_kernel, cudaFuncAttributeMaxDynamicSharedMemorySize, SMEM_BYTES);
  }
  Params p;
  void* yT = nullptr;
  cudaGetSymbolAddress(&yT, g_yT);
  enc2d(enc, &p.x, xq, DM, SEQ, 64, 128);
  enc2d(enc, &p.c, ckv, DC, SEQ, 64, 128);
  enc3d(enc, &p.wq, wq, DM, NH * HD);
  enc3d(enc, &p.wuk, wuk, DC, NH * HD);
  enc3d(enc, &p.wuv, wuv, DC, NH * HD);
  enc2d(enc, &p.wo, wo, DM, NH * HD, 64, 64);
  enc3d(enc, &p.x3, xq, SEQ, DM, 128);
  enc3d(enc, &p.y3, yT, DM, SEQ, 128);
  enc2d(enc, &p.out, d_out, DM, SEQ, 64, 16);
  {
    void* wp = nullptr;
    cudaGetSymbolAddress(&wp, g_w);
    cuuint64_t dims[3] = {WSTRIDE / 2, DM / 2, 2}; cuuint64_t strides[2] = {2 * WSTRIDE, WSTRIDE}; cuuint32_t box[3] = {16, 32, 2}; cuuint32_t es[3] = {1, 1, 1};
    enc(&p.w, CU_TENSOR_MAP_DATA_TYPE_BFLOAT16, 3, wp, dims, strides, box, es, CU_TENSOR_MAP_INTERLEAVE_NONE,
        CU_TENSOR_MAP_SWIZZLE_32B, CU_TENSOR_MAP_L2_PROMOTION_NONE, CU_TENSOR_MAP_FLOAT_OOB_FILL_NONE);
  }
  p.zero = 0;
  cudaGetSymbolAddress((void**)&p.flags, g_flags);
  for (int i = 0; i < 128; i++) {
    const int tp = i % NSLOT;
    p.pref[i] = tp < 32 ? (tp & 7) * 8 + (tp >> 3) : tp < 60 ? (1 + (tp - 32) % 7) * 8 + 4 + (tp - 32) / 7 : tp < 62 ? tp + 4 : tp - 58;
  }
  p.gate_w = gw; p.ak = ak; p.av = av; p.shk = shk; p.ssk = ssk; p.ssd = ssd; p.wop = wo;

  mega_kernel<<<132, NTHREADS, SMEM_BYTES>>>(p);
}
```

```cpp
#include <cuda_runtime.h>
#include <cuda.h>
#include <cuda_bf16.h>
#include <stdint.h>

namespace {

constexpr int SEQ = 2048, DM = 1024, DC = 512, NH = 32, HD = 128;
constexpr int GR = 16384;
constexpr int NGR = 14;
constexpr int SM_BAR = NGR * GR;
constexpr int SM_GATE = SM_BAR + 512;
constexpr int SM_UST = SM_GATE + 512;
constexpr int SMEM_BYTES = SM_UST + 2048;
constexpr int NTHREADS = 384;
#define SM_LIMIT 1.0995116e12f
#define SM_LOW 9.094947e-13f
constexpr int CN_MAIN = 5, CN_SPARE = 96;
constexpr int XK = 57, YK = 62;
constexpr int STR = 61;
constexpr int P3G = 6, P3X = 12, P3Y = 10;
constexpr int NMAIN = 128;

constexpr int B_FULL = 0, B_FREE = 14, B_SLOT = 16, B_DONE = 17, B_EMPTY = 18, B_EV = 32, V_SLOT = 36;

__device__ __align__(1024) uint8_t g_kv[2 * 16 * 16 * 32768];
__device__ __align__(1024) uint8_t g_cimg[16 * NH * 32768];
__device__ __align__(1024) __nv_bfloat16 g_yT[DM * SEQ];
__device__ __align__(1024) float g_gate[SEQ];
#define CWIDE 0
constexpr int WZ = CWIDE ? 768 : 256, WPL = WZ + 4096, WBYTES = 2 * WPL + 32, WSTRIDE = 2 * WPL + 128;
__device__ __align__(1024) uint8_t g_w[DM * WSTRIDE];
__device__ __align__(32) unsigned g_flags[96 * 8];
constexpr int F_KV = 0, F_CTX = 16, F_U = 48, F_AD = 56, F_Y = 64, F_GATE = 72, F_EXIT = 73;
constexpr int NSLOT = 66;
#define FLAG(i) (&g_flags[(i) * 8])
#define CLAIMP(i) (p.flags + (i) * 8 + 1)

#define TS(slot)
#define TSW(slot)
#define FTX(i, off)
#define FTDUMP()

#define ST_OUT 0
#define QFLUSH 4
#define X_DELAY 900
#define X_D2 600
#define P3PF 10
#define P3PF0 5
#define EXPV 1
#define SUMV 0
#define ROT 8
#define EARLY_RCP 1
#define KVARR 1
#define KV_ROW(idx, t) (KVARR ? 8 * (t) + 2 * ((idx) & 3) : 2 * (idx))
#define KV_HEAD(idx, t) (KVARR ? (idx) >> 2 : (t))
#define FINE_MODE 0
#define FDUMP_KB 40
#define FINE_RND 1
#define FTA(i) do { if (FINE_MODE == 0) FTX(i, rnd ^ FINE_RND); } while (0)
#define FTG(i) do { if (FINE_MODE == 1) FTX(i, rnd ^ FINE_RND); } while (0)
#define FTM(i) do { if (FINE_MODE == 4) FTX(i, 0); } while (0)
#define FTC(k) do { if (FINE_MODE == 5) FTX((i & 7) * 8 + (k), (i >> 3) ^ FINE_RND); } while (0)
#define FTH(i, off) do { if (FINE_MODE == 6) FTX(i, (c.rnd ^ FINE_RND) | (off)); } while (0)
#define FTS(i)
#define FTSD(i)
#define FTSW(i)
#define FTP(i)
#define FTO(i) do { if (FINE_MODE == 2) FTX(i, 0); } while (0)

__device__ __forceinline__ uint32_t smem_u32(const void* p) { return (uint32_t)__cvta_generic_to_shared(p); }
__device__ __forceinline__ void mbar_init(uint32_t bar, int cnt) { asm volatile("mbarrier.init.shared::cta.b64 [%0], %1;" ::"r"(bar), "r"(cnt) : "memory"); }
__device__ __forceinline__ void mbar_expect_tx(uint32_t bar, uint32_t bytes) { asm volatile("mbarrier.arrive.expect_tx.shared::cta.b64 _, [%0], %1;" ::"r"(bar), "r"(bytes) : "memory"); }
__device__ __forceinline__ void mbar_arrive(uint32_t bar) { asm volatile("mbarrier.arrive.shared::cta.b64 _, [%0];" ::"r"(bar) : "memory"); }
__device__ __forceinline__ void mbar_arrive_cluster(uint32_t bar, uint32_t cta) {
  asm volatile("{\n.reg .b32 r;\nmapa.shared::cluster.u32 r, %0, %1;\nmbarrier.arrive.shared::cluster.b64 _, [r];\n}\n" ::"r"(bar), "r"(cta) : "memory");
}
__device__ __forceinline__ bool mbar_try(uint32_t bar, uint32_t parity) {
  uint32_t ok;
  asm volatile("{\n.reg .pred p;\nmbarrier.try_wait.parity.shared::cta.b64 p, [%1], %2, 20000;\nselp.u32 %0, 1, 0, p;\n}\n" : "=r"(ok) : "r"(bar), "r"(parity) : "memory");
  return ok;
}
__device__ __forceinline__ bool mbar_test(uint32_t bar, uint32_t parity) {
  uint32_t ok;
  asm volatile("{\n.reg .pred p;\nmbarrier.test_wait.parity.shared::cta.b64 p, [%1], %2;\nselp.u32 %0, 1, 0, p;\n}\n" : "=r"(ok) : "r"(bar), "r"(parity) : "memory");
  return ok;
}
__device__ __forceinline__ void mbar_wait(uint32_t bar, uint32_t parity) {
  asm volatile("{\n.reg .pred p;\nWAIT_LOOP:\nbar.warp.sync -1;\nmbarrier.try_wait.parity.shared::cta.b64 p, [%0], %1;\n@!p bra WAIT_LOOP;\n}\n" ::"r"(bar), "r"(parity) : "memory");
}
__device__ __forceinline__ void mbar_wait1(uint32_t bar, uint32_t parity) {
  asm volatile("{\n.reg .pred p;\nWAIT_LOOP:\nbar.warp.sync -1;\nmbarrier.try_wait.parity.shared::cta.b64 p, [%0], %1, 4000;\n@!p bra WAIT_LOOP;\n}\n" ::"r"(bar), "r"(parity) : "memory");
}
constexpr uint64_t EV_FIRST = 0x12F0000000000000ull;
__device__ __forceinline__ uint32_t ldg_stream(const uint32_t* p) {
  uint32_t r; asm volatile("ld.global.nc.L1::no_allocate.L2::cache_hint.b32 %0, [%1], %2;" : "=r"(r) : "l"(p), "l"(EV_FIRST)); return r;
}
#define TMA_LD "cp.async.bulk.tensor."
#define TMA_MB ".shared::cluster.global.mbarrier::complete_tx::bytes"
__device__ __forceinline__ void tma2d(uint32_t dst, const CUtensorMap* tm, int c0, int c1, uint32_t bar) {
  asm volatile(TMA_LD "2d" TMA_MB " [%0], [%1, {%3, %4}], [%2];" ::"r"(dst), "l"(tm), "r"(bar), "r"(c0), "r"(c1) : "memory");
}
template <bool ONCE = false> __device__ __forceinline__ void tma2d_mc(uint32_t dst, const CUtensorMap* tm, int c0, int c1, uint32_t bar) {
  if (ONCE) asm volatile(TMA_LD "2d" TMA_MB ".multicast::cluster.L2::cache_hint [%0], [%1, {%3, %4}], [%2], %5, %6;"
                         ::"r"(dst), "l"(tm), "r"(bar), "r"(c0), "r"(c1), "h"((uint16_t)3), "l"(EV_FIRST) : "memory");
  else asm volatile(TMA_LD "2d" TMA_MB ".multicast::cluster [%0], [%1, {%3, %4}], [%2], %5;"
                    ::"r"(dst), "l"(tm), "r"(bar), "r"(c0), "r"(c1), "h"((uint16_t)3) : "memory");
}
__device__ __forceinline__ void tma3d(uint32_t dst, const CUtensorMap* tm, int c0, int c1, int c2, uint32_t bar) {
  asm volatile(TMA_LD "3d" TMA_MB " [%0], [%1, {%3, %4, %5}], [%2];" ::"r"(dst), "l"(tm), "r"(bar), "r"(c0), "r"(c1), "r"(c2) : "memory");
}
__device__ __forceinline__ void tma3d_mc(uint32_t dst, const CUtensorMap* tm, int c0, int c1, int c2, uint32_t bar) {
  asm volatile(TMA_LD "3d" TMA_MB ".multicast::cluster [%0], [%1, {%3, %4, %5}], [%2], %6;"
               ::"r"(dst), "l"(tm), "r"(bar), "r"(c0), "r"(c1), "r"(c2), "h"((uint16_t)3) : "memory");
}
template <bool ONCE = false> __device__ __forceinline__ void bulk_g2s(uint32_t dst, const void* src, uint32_t bytes, uint32_t bar) {
  if (ONCE) asm volatile("cp.async.bulk" TMA_MB ".L2::cache_hint [%0], [%1], %2, [%3], %4;" ::"r"(dst), "l"(src), "r"(bytes), "r"(bar), "l"(EV_FIRST) : "memory");
  else asm volatile("cp.async.bulk" TMA_MB " [%0], [%1], %2, [%3];" ::"r"(dst), "l"(src), "r"(bytes), "r"(bar) : "memory");
}
__device__ __forceinline__ void tma2d_store(const CUtensorMap* tm, uint32_t src, int c0, int c1) {
  asm volatile("cp.async.bulk.tensor.2d.global.shared::cta.bulk_group [%0, {%2, %3}], [%1];" ::"l"(tm), "r"(src), "r"(c0), "r"(c1) : "memory");
}
__device__ __forceinline__ void prefetch_tm(const CUtensorMap* tm) { asm volatile("prefetch.tensormap [%0];" ::"l"(tm) : "memory"); }
__device__ __forceinline__ void wg_fence() { asm volatile("wgmma.fence.sync.aligned;" ::: "memory"); }
__device__ __forceinline__ void wg_commit() { asm volatile("wgmma.commit_group.sync.aligned;" ::: "memory"); }
template <int N> __device__ __forceinline__ void wg_wait() { asm volatile("wgmma.wait_group.sync.aligned %0;" ::"n"(N) : "memory"); }
__device__ __forceinline__ void bar_sync(int id, int n) { asm volatile("bar.sync %0, %1;" ::"r"(id), "r"(n) : "memory"); }
__device__ __forceinline__ void bar_arrive(int id, int n) { asm volatile("bar.arrive %0, %1;" ::"r"(id), "r"(n) : "memory"); }
__device__ __forceinline__ void fence_async_smem() { asm volatile("fence.proxy.async.shared::cta;" ::: "memory"); }
__device__ __forceinline__ void fence_async_all() { asm volatile("fence.proxy.async.global;" ::: "memory"); }
__device__ __forceinline__ uint32_t pack_bf16(float lo, float hi) { uint32_t r; asm("cvt.rn.bf16x2.f32 %0, %1, %2;" : "=r"(r) : "f"(hi), "f"(lo)); return r; }
__device__ __forceinline__ float ex2(float x) { float r; asm("ex2.approx.ftz.f32 %0, %1;" : "=f"(r) : "f"(x)); return r; }
__device__ __forceinline__ float rcp(float x) { float r; asm("rcp.approx.ftz.f32 %0, %1;" : "=f"(r) : "f"(x)); return r; }
__device__ __forceinline__ void flag_wait(const unsigned* f, unsigned target) {
  unsigned v;
  do { asm volatile("ld.acquire.gpu.global.u32 %0, [%1];" : "=r"(v) : "l"(f) : "memory"); } while (__any_sync(0xffffffffu, v < target));
}
__device__ __forceinline__ bool elect() {
  uint32_t r;
  asm volatile("{\n.reg .pred p;\nelect.sync _|p, -1;\nselp.u32 %0, 1, 0, p;\n}\n" : "=r"(r));
  return r;
}
__device__ __forceinline__ void fence_release() { asm volatile("fence.release.gpu;" ::: "memory"); }
__device__ __forceinline__ void flag_add(unsigned* f) { asm volatile("red.relaxed.gpu.global.inc.u32 [%0], 0x7fffffff;" ::"l"(f) : "memory"); }
__device__ __forceinline__ void cluster_arrive() { asm volatile("barrier.cluster.arrive.relaxed.aligned;" ::: "memory"); }
__device__ __forceinline__ void cluster_wait() { asm volatile("barrier.cluster.wait.aligned;" ::: "memory"); }
__device__ __forceinline__ uint32_t hmul2(uint32_t a, uint32_t b) { uint32_t r; asm("mul.rn.bf16x2 %0, %1, %2;" : "=r"(r) : "r"(a), "r"(b)); return r; }
__device__ __forceinline__ uint32_t hadd2(uint32_t a, uint32_t b) { uint32_t r; asm("add.rn.bf16x2 %0, %1, %2;" : "=r"(r) : "r"(a), "r"(b)); return r; }
__device__ __forceinline__ uint32_t hfma2(uint32_t a, uint32_t b, uint32_t c) { uint32_t r; asm("fma.rn.bf16x2 %0, %1, %2, %3;" : "=r"(r) : "r"(a), "r"(b), "r"(c)); return r; }
__device__ __forceinline__ uint32_t lds32(uint32_t a) { uint32_t r; asm volatile("ld.shared.b32 %0, [%1];" : "=r"(r) : "r"(a) : "memory"); return r; }
__device__ __forceinline__ uint4 lds128(uint32_t a) { uint4 r; asm volatile("ld.shared.v4.b32 {%0,%1,%2,%3}, [%4];" : "=r"(r.x), "=r"(r.y), "=r"(r.z), "=r"(r.w) : "r"(a) : "memory"); return r; }
__device__ __forceinline__ uint32_t desc_k(uint32_t addr) { return ((addr & 0x3FFFF) >> 4) | (1u << 16); }
template <int LBO> __device__ __forceinline__ uint32_t desc_mn(uint32_t addr) { return ((addr & 0x3FFFF) >> 4) | ((uint32_t)(LBO >> 4) << 16); }
#define DHI "0x40000040"

#define R8(d, o) "+f"(d[o]), "+f"(d[o + 1]), "+f"(d[o + 2]), "+f"(d[o + 3]), "+f"(d[o + 4]), "+f"(d[o + 5]), "+f"(d[o + 6]), "+f"(d[o + 7])
#define R32(d, o) R8(d, o), R8(d, o + 8), R8(d, o + 16), R8(d, o + 24)
#define R64(d, o) R32(d, o), R32(d, o + 32)
#define L64 "%0,%1,%2,%3,%4,%5,%6,%7,%8,%9,%10,%11,%12,%13,%14,%15,%16,%17,%18,%19,%20,%21,%22,%23,%24,%25,%26,%27,%28,%29,%30,%31," \
            "%32,%33,%34,%35,%36,%37,%38,%39,%40,%41,%42,%43,%44,%45,%46,%47,%48,%49,%50,%51,%52,%53,%54,%55,%56,%57,%58,%59,%60,%61,%62,%63"
#define L128 L64 ",%64,%65,%66,%67,%68,%69,%70,%71,%72,%73,%74,%75,%76,%77,%78,%79,%80,%81,%82,%83,%84,%85,%86,%87,%88,%89,%90,%91,%92,%93,%94,%95," \
            "%96,%97,%98,%99,%100,%101,%102,%103,%104,%105,%106,%107,%108,%109,%110,%111,%112,%113,%114,%115,%116,%117,%118,%119,%120,%121,%122,%123,%124,%125,%126,%127"

template <int TB> __device__ __forceinline__ void mma_ss_n128(float (&d)[64], uint32_t da, uint32_t db) {
  asm volatile("{\n.reg .b64 da, db;\nmov.b64 da, {%64, " DHI "};\nmov.b64 db, {%65, " DHI "};\n"
               "wgmma.mma_async.sync.aligned.m64n128k16.f32.bf16.bf16 {" L64 "}, da, db, 1, 1, 1, 0, %66;\n}\n"
               : R64(d, 0) : "r"(da), "r"(db), "n"(TB));
}
template <int TB> __device__ __forceinline__ void mma_rs_n128(float (&d)[64], uint32_t a0, uint32_t a1, uint32_t a2, uint32_t a3, uint32_t db, int sd) {
  asm volatile("{\n.reg .pred p;\n.reg .b64 db;\nsetp.ne.b32 p, %69, 0;\nmov.b64 db, {%68, " DHI "};\n"
               "wgmma.mma_async.sync.aligned.m64n128k16.f32.bf16.bf16 {" L64 "}, {%64,%65,%66,%67}, db, p, 1, 1, %70;\n}\n"
               : R64(d, 0) : "r"(a0), "r"(a1), "r"(a2), "r"(a3), "r"(db), "r"(sd), "n"(TB));
}
template <int TB> __device__ __forceinline__ void mma_ss_n256(float (&d)[128], uint32_t da, uint32_t db) {
  asm volatile("{\n.reg .b64 da, db;\nmov.b64 da, {%128, " DHI "};\nmov.b64 db, {%129, " DHI "};\n"
               "wgmma.mma_async.sync.aligned.m64n256k16.f32.bf16.bf16 {" L128 "}, da, db, 1, 1, 1, 0, %130;\n}\n"
               : R64(d, 0), R64(d, 64) : "r"(da), "r"(db), "n"(TB));
}
#define W8(d, o) "=f"(d[o]), "=f"(d[o + 1]), "=f"(d[o + 2]), "=f"(d[o + 3]), "=f"(d[o + 4]), "=f"(d[o + 5]), "=f"(d[o + 6]), "=f"(d[o + 7])
#define W32(d, o) W8(d, o), W8(d, o + 8), W8(d, o + 16), W8(d, o + 24)
#define W64(d, o) W32(d, o), W32(d, o + 32)
template <int TB> __device__ __forceinline__ void mma_ss_n128_init(float (&d)[64], uint32_t da, uint32_t db) {
  asm volatile("{\n.reg .b64 da, db;\nmov.b64 da, {%64, " DHI "};\nmov.b64 db, {%65, " DHI "};\n"
               "wgmma.mma_async.sync.aligned.m64n128k16.f32.bf16.bf16 {" L64 "}, da, db, 0, 1, 1, 0, %66;\n}\n"
               : W64(d, 0) : "r"(da), "r"(db), "n"(TB));
}
template <int TB> __device__ __forceinline__ void mma_ss_n256_init(float (&d)[128], uint32_t da, uint32_t db) {
  asm volatile("{\n.reg .b64 da, db;\nmov.b64 da, {%128, " DHI "};\nmov.b64 db, {%129, " DHI "};\n"
               "wgmma.mma_async.sync.aligned.m64n256k16.f32.bf16.bf16 {" L128 "}, da, db, 0, 1, 1, 0, %130;\n}\n"
               : W64(d, 0), W64(d, 64) : "r"(da), "r"(db), "n"(TB));
}
#define L32 "%0,%1,%2,%3,%4,%5,%6,%7,%8,%9,%10,%11,%12,%13,%14,%15,%16,%17,%18,%19,%20,%21,%22,%23,%24,%25,%26,%27,%28,%29,%30,%31"
__device__ __forceinline__ void mma_ss_n64(float (&d)[32], uint32_t da, uint32_t db) {
  asm volatile("{\n.reg .b64 da, db;\nmov.b64 da, {%32, " DHI "};\nmov.b64 db, {%33, " DHI "};\n"
               "wgmma.mma_async.sync.aligned.m64n64k16.f32.bf16.bf16 {" L32 "}, da, db, 1, 1, 1, 0, 0;\n}\n"
               : R32(d, 0) : "r"(da), "r"(db));
}
__device__ __forceinline__ void mma_ss_n64_init(float (&d)[32], uint32_t da, uint32_t db) {
  asm volatile("{\n.reg .b64 da, db;\nmov.b64 da, {%32, " DHI "};\nmov.b64 db, {%33, " DHI "};\n"
               "wgmma.mma_async.sync.aligned.m64n64k16.f32.bf16.bf16 {" L32 "}, da, db, 0, 1, 1, 0, 0;\n}\n"
               : W32(d, 0) : "r"(da), "r"(db));
}
#define L16 "%0,%1,%2,%3,%4,%5,%6,%7,%8,%9,%10,%11,%12,%13,%14,%15"
template <int O, bool INIT> __device__ __forceinline__ void mma_rs_n32(float (&d)[128], uint32_t a0, uint32_t a1, uint32_t a2, uint32_t a3, uint32_t db) {
  if (INIT) asm volatile("{\n.reg .b64 db;\nmov.b64 db, {%20, 0x00000008};\n"
               "wgmma.mma_async.sync.aligned.m64n32k16.f32.bf16.bf16 {" L16 "}, {%16,%17,%18,%19}, db, 0, 1, 1, 0;\n}\n"
               : W8(d, O), W8(d, O + 8) : "r"(a0), "r"(a1), "r"(a2), "r"(a3), "r"(db));
  else asm volatile("{\n.reg .b64 db;\nmov.b64 db, {%20, 0x00000008};\n"
               "wgmma.mma_async.sync.aligned.m64n32k16.f32.bf16.bf16 {" L16 "}, {%16,%17,%18,%19}, db, 1, 1, 1, 0;\n}\n"
               : R8(d, O), R8(d, O + 8) : "r"(a0), "r"(a1), "r"(a2), "r"(a3), "r"(db));
}
template <int O, bool INIT> __device__ __forceinline__ void mma_rs_n64(float (&d)[128], uint32_t a0, uint32_t a1, uint32_t a2, uint32_t a3, uint32_t db) {
  if (INIT) asm volatile("{\n.reg .b64 db;\nmov.b64 db, {%36, 0x00000008};\n"
               "wgmma.mma_async.sync.aligned.m64n64k16.f32.bf16.bf16 {" L32 "}, {%32,%33,%34,%35}, db, 0, 1, 1, 0;\n}\n"
               : W32(d, O) : "r"(a0), "r"(a1), "r"(a2), "r"(a3), "r"(db));
  else asm volatile("{\n.reg .b64 db;\nmov.b64 db, {%36, 0x00000008};\n"
               "wgmma.mma_async.sync.aligned.m64n64k16.f32.bf16.bf16 {" L32 "}, {%32,%33,%34,%35}, db, 1, 1, 1, 0;\n}\n"
               : R32(d, O) : "r"(a0), "r"(a1), "r"(a2), "r"(a3), "r"(db));
}
template <int S, int J> __device__ __forceinline__ void conv_step(float (&d)[128], const uint32_t (&a)[64], uint32_t db) {
  if constexpr (J >= 0 && J >= (S >> 1)) {
    if constexpr (J >= 8 - 2 * CWIDE) {
      mma_rs_n64<16 * (J - 1), S == 0>(d, a[4 * S], a[4 * S + 1], a[4 * S + 2], a[4 * S + 3], db + (uint32_t)((2 * (J - 1) - S) * 16));
      conv_step<S, J - 2>(d, a, db);
    } else {
      mma_rs_n32<16 * J, S == 0>(d, a[4 * S], a[4 * S + 1], a[4 * S + 2], a[4 * S + 3], db + (uint32_t)((2 * J - S) * 16));
      conv_step<S, J - 1>(d, a, db);
    }
  }
}
__device__ __forceinline__ void mma_ss_n8(float (&d)[4], uint32_t da, uint32_t db) {
  asm volatile("{\n.reg .b64 da, db;\nmov.b64 da, {%4, " DHI "};\nmov.b64 db, {%5, 0x00000008};\n"
               "wgmma.mma_async.sync.aligned.m64n8k16.f32.bf16.bf16 {%0,%1,%2,%3}, da, db, 1, 1, 1, 0, 0;\n}\n"
               : "+f"(d[0]), "+f"(d[1]), "+f"(d[2]), "+f"(d[3]) : "r"(da), "r"(db));
}
template <int N> __device__ __forceinline__ void reg_fence(float (&d)[N]) {
#pragma unroll
  for (int i = 0; i < N; i++) asm volatile("" : "+f"(d[i])::"memory");
}
template <int N> __device__ __forceinline__ void reg_fence(uint32_t (&d)[N]) {
#pragma unroll
  for (int i = 0; i < N; i++) asm volatile("" : "+r"(d[i])::"memory");
}

struct __align__(64) Params {
  unsigned* flags;
  int zero;
  uint8_t pref[128];
  const __nv_bfloat16 *gate_w, *ak, *av, *shk, *ssk, *ssd, *wop;
  CUtensorMap x, c, wq, wuk, wuv, wo, x3, y3, out, w;
};

template <int O, int N, int M> __device__ __forceinline__ void pack_frag(const float (&acc)[N], uint32_t (&pk)[M]) {
#pragma unroll
  for (int i = 0; i < 32; i++) pk[i] = pack_bf16(acc[O + 2 * i], acc[O + 2 * i + 1]);
}
template <int N> __device__ __forceinline__ void pack_frag_scaled(const float (&acc)[N], uint32_t (&pk)[32], float s0, float s1) {
#pragma unroll
  for (int i = 0; i < 32; i++) { const float s = (i & 1) ? s1 : s0; pk[i] = pack_bf16(acc[2 * i] * s, acc[2 * i + 1] * s); }
}
template <int J0 = 0, int J1 = 8, int M> __device__ __forceinline__ void stsm_frag(const uint32_t (&pk)[M], uint32_t a) {
#pragma unroll
  for (int jj = J0; jj < J1; jj++)
    asm volatile("stmatrix.sync.aligned.m8n8.x4.shared.b16 [%0], {%1,%2,%3,%4};" ::"r"((a ^ ((jj & 3) << 5)) + (jj >> 2) * 16384),
                 "r"(pk[4 * jj]), "r"(pk[4 * jj + 1]), "r"(pk[4 * jj + 2]), "r"(pk[4 * jj + 3]) : "memory");
}

struct Cons {
  uint32_t sb;
  uint32_t pf;
  int wg, tid;
  __device__ __forceinline__ void wait_full(int g) { mbar_wait(sb + SM_BAR + (B_FULL + g) * 8, (pf >> g) & 1); pf ^= 1u << g; }
  uint32_t relb;
  __device__ __forceinline__ void release(int g, int n) {
    if (tid < 2 * n) asm volatile("mbarrier.arrive.shared::cluster.b64 _, [%0];" ::"r"(relb + g * 8) : "memory");
  }
  __device__ __forceinline__ void turn_begin() { bar_sync(1 + wg, 256); }
  __device__ __forceinline__ void turn_end() { bar_arrive(2 - wg, 256); }
  __device__ __forceinline__ void staged(int e) { __syncwarp(); if ((tid & 31) == 0) mbar_arrive(sb + SM_BAR + (B_EV + 2 * e + wg) * 8); }
  int zero;
  int rnd;
  uint32_t pfree;
  __device__ __forceinline__ void wait_stage_free() { mbar_wait(sb + SM_BAR + (B_FREE + wg) * 8, pfree); pfree ^= 1; }
  __device__ __forceinline__ bool try_full(int g) { return mbar_test(sb + SM_BAR + (B_FULL + g) * 8, (pf >> g) & 1); }
};

constexpr float SM_C = 0.08838834764831845f * 1.4426950408889634f;
struct SoftState { float m0, m1, l0, l1; int shifted; };
__device__ __forceinline__ void ex2_rot(float& t, float s, uint32_t never_zero) {
  asm("{\n.reg .pred p;\nsetp.ne.u32 p, %2, 0;\n@p ex2.approx.ftz.f32 %0, %1;\n}\n" : "+f"(t) : "f"(s), "r"(never_zero));
}
__device__ __forceinline__ void pin(float a, uint32_t never_zero) {
  asm volatile("{\n.reg .pred p;\nsetp.eq.u32 p, %1, 0;\n@p st.shared.f32 [%1], %0;\n}\n" ::"f"(a), "r"(never_zero) : "memory");
}
template <int O, int N> __device__ __forceinline__ void reg_fence_part(uint32_t (&d)[32]) {
#pragma unroll
  for (int i = O; i < O + N; i++) asm volatile("" : "+r"(d[i])::"memory");
}
template <int Q, int W, int N> __device__ __forceinline__ void exp_quarter(const float (&S)[N], uint32_t (&P)[32], float (&t)[ROT], float& s0, float& s1, uint32_t nz) {
#pragma unroll
  for (int i = 8 * Q; i < 8 * Q + 8; i++) {
    float& a = t[(2 * i) % ROT];
    float& b = t[(2 * i + 1) % ROT];
    if (2 * i < ROT) { a = ex2(S[2 * i]); b = ex2(S[2 * i + 1]); }
    else { ex2_rot(a, S[2 * i], nz); ex2_rot(b, S[2 * i + 1], nz); }
    if (i < 2) { if (i) s1 = a + b; else s0 = a + b; }
    else if (SUMV == 0) { if (i & 1) { s1 += a; s1 += b; } else { s0 += a; s0 += b; } }
    else { if (i & 1) s1 += a + b; else s0 += a + b; }
    if (i == 8 * Q) { pin(EXPV == 1 && Q ? s1 : s0, nz); wg_wait<W>(); reg_fence_part<8 * Q, 8>(P); }
    P[i] = pack_bf16(a, b);
  }
}
template <int N> __device__ __forceinline__ void shift_scores(float (&S)[N], float d0, float d1) {
#pragma unroll
  for (int i = 0; i < N; i++) S[i] -= (i & 2) ? d1 : d0;
}
__device__ __forceinline__ bool soft_high(float s0, float s1, float lim = SM_LIMIT) { return s0 > lim || s1 > lim; }
__device__ __forceinline__ bool soft_unsafe(float s0, float s1, bool first) {
  uint32_t b0 = __ballot_sync(0xffffffffu, s0 >= SM_LOW), b1 = __ballot_sync(0xffffffffu, s1 >= SM_LOW);
  b0 |= b0 >> 1; b0 |= b0 >> 2; b1 |= b1 >> 1; b1 |= b1 >> 2;
  return __any_sync(0xffffffffu, soft_high(s0, s1)) || (first && (b0 & b1 & 0x11111111u) != 0x11111111u);
}
template <int N> __device__ __forceinline__ void soft_fix(const float (&S)[N], float (&O)[64], SoftState& z, bool first, float& d0, float& d1) {
  d0 = d1 = first ? -INFINITY : 0.f;
#pragma unroll
  for (int j = 0; j < N / 4; j++) { d0 = fmaxf(d0, fmaxf(S[4 * j], S[4 * j + 1])); d1 = fmaxf(d1, fmaxf(S[4 * j + 2], S[4 * j + 3])); }
  d0 = fmaxf(d0, __shfl_xor_sync(0xffffffffu, d0, 1)); d1 = fmaxf(d1, __shfl_xor_sync(0xffffffffu, d1, 1));
  d0 = fmaxf(d0, __shfl_xor_sync(0xffffffffu, d0, 2)); d1 = fmaxf(d1, __shfl_xor_sync(0xffffffffu, d1, 2));
  const float sc0 = ex2(-fmaxf(d0, 0.f)), sc1 = ex2(-fmaxf(d1, 0.f));
  z.m0 += d0; z.m1 += d1; z.l0 *= sc0; z.l1 *= sc1; z.shifted = 1;
#pragma unroll
  for (int j = 0; j < 16; j++) { O[4 * j] *= sc0; O[4 * j + 1] *= sc0; O[4 * j + 2] *= sc1; O[4 * j + 3] *= sc1; }
}
template <int M> __device__ __forceinline__ void pin32(const uint32_t (&v)[M], uint32_t never_zero) {
#pragma unroll
  for (int i = 0; i < 32; i += 4)
    asm volatile("{\n.reg .pred p;\nsetp.eq.u32 p, %4, 0;\n@p st.shared.v4.b32 [%4], {%0,%1,%2,%3};\n}\n" ::"r"(v[i]), "r"(v[i + 1]), "r"(v[i + 2]), "r"(v[i + 3]), "r"(never_zero) : "memory");
}
template <int N> __device__ __forceinline__ void mask_diag(float (&S)[N], float nd) {
  asm volatile("" : "+f"(nd));
#pragma unroll
  for (int i = 0; i < 32; i++) {
    const float beyond = __saturatef(nd + (float)(8 * (i >> 2) + (i & 1) - 4 * (i & 2)));
    S[N - 32 + i] = fmaf(beyond, -3.0e38f, S[N - 32 + i]);
  }
}
__device__ __forceinline__ float quad_sum(float v) {
  v += __shfl_xor_sync(0xffffffffu, v, 1);
  v += __shfl_xor_sync(0xffffffffu, v, 2);
  return v;
}
__device__ __forceinline__ void issue_qk(float (&S)[64], uint32_t dq, uint32_t dk) {
  mma_ss_n128_init<0>(S, dq, dk);
#pragma unroll
  for (int s = 1; s < 8; s++) mma_ss_n128<0>(S, dq + (s >> 2) * 1024 + (s & 3) * 2, dk + (s >> 2) * 1024 + (s & 3) * 2);
}
__device__ __forceinline__ void issue_qk(float (&S)[32], uint32_t dq, uint32_t dk) {
  mma_ss_n64_init(S, dq, dk);
#pragma unroll
  for (int s = 1; s < 8; s++) mma_ss_n64(S, dq + (s >> 2) * 1024 + (s & 3) * 2, dk + (s >> 2) * 1024 + (s & 3) * 2);
}
template <int H> __device__ __forceinline__ void issue_pv(float (&O)[64], const uint32_t (&P)[32], uint32_t dv, int acc, bool on) {
  if (on) {
#pragma unroll
    for (int s = 4 * H; s < 4 * H + 4; s++) {
      mma_rs_n128<1>(O, P[4 * s], P[4 * s + 1], P[4 * s + 2], P[4 * s + 3], dv + s * 128, s != 0 ? 1 : acc);
      if (s & 1) wg_commit();
    }
  } else { wg_commit(); wg_commit(); }
}
constexpr uint32_t DG = GR >> 4;
__device__ __forceinline__ void stage_q2(Cons& c, const float (&O)[64], uint32_t (&P)[32], uint32_t stg) {
  wg_commit(); wg_commit(); wg_commit(); wg_commit();
  c.turn_end();
  pack_frag<0>(O, P);
  stsm_frag(P, stg);
  fence_async_smem();
}
__device__ __forceinline__ void attn_half(Cons& c, float (&O)[64], uint32_t (&P)[32], SoftState& z, uint32_t dk0, uint32_t dkk, uint32_t dv0, float dmask, int last) {
  float S[32];
  FTH(8 + last * 32, 0);
  c.turn_begin();
  FTH(9 + last * 32, 0);
  wg_fence();
  issue_qk(S, dk0 + (last ? 0 : 2 * DG), dkk + (last ? 8 : 4) * DG);
  wg_commit();
  issue_pv<0>(O, P, dv0 + 10 * DG, 1, last);
  issue_pv<1>(O, P, dv0 + 10 * DG, 1, last);
  c.turn_end();
  c.wait_full(last ? 12 : 6);
  FTH(10 + last * 32, 0);
  wg_wait<4>();
  reg_fence(S);
  FTH(11 + last * 32, 0);
  c.release(last ? 8 : 4, 2);
  mask_diag(S, dmask);
  float s0, s1, d0 = z.m0, d1 = z.m1;
#pragma unroll 1
  for (int pass = 0;; pass++) {
    if (z.shifted) shift_scores(S, d0, d1);
    float tr[ROT];
    exp_quarter<0, 3>(S, P, tr, s0, s1, c.sb);
    exp_quarter<1, 2>(S, P, tr, s0, s1, c.sb);
    pin(s1, c.sb); wg_wait<0>(); reg_fence_part<16, 16>(P); reg_fence(O);
    if (!soft_unsafe(s0, s1, !last) || pass) break;
    soft_fix(S, O, z, !last, d0, d1);
  }
  FTH(12 + last * 32, 0);
  z.l0 += s0; z.l1 += s1;
  c.release(10, last ? 2 : 0);
  if (!last) c.wait_full(8);
  FTH(13 + last * 32, 0);
}

template <int V> struct IC { static constexpr int value = V; };
__device__ __forceinline__ int conv_next(int g, bool spare) { return g >= NGR - 2 ? g - (NGR - 4) : !spare && g == 4 ? 1 : g + 2; }
__device__ __forceinline__ void conv_final(uint32_t rb, uint32_t yb, bool on) {
  const uint4 q0 = lds128(rb), q1 = lds128(rb + 4096), q2 = lds128(rb + 8192), q3 = lds128(rb + 12288);
  auto fin = [&](uint32_t x0, uint32_t x1, uint32_t x2, uint32_t x3) { return hadd2(hadd2(x0, x1), hadd2(x2, x3)); };
  asm volatile("{\n.reg .pred p;\nsetp.ne.b32 p, %5, 0;\n@p st.shared.v4.b32 [%0], {%1,%2,%3,%4};\n}\n" ::"r"(yb), "r"(fin(q0.x, q1.x, q2.x, q3.x)),
               "r"(fin(q0.y, q1.y, q2.y, q3.y)), "r"(fin(q0.z, q1.z, q2.z, q3.z)), "r"(fin(q0.w, q1.w, q2.w, q3.w)), "r"((int)on) : "memory");
}
__device__ __forceinline__ void conv_tasks(Cons& c, const Params& p, int ntask, bool spare, int ch, int chstep, uint32_t dd, uint32_t dkk, int w, int lane) {
  const uint32_t sb = c.sb;
  int g = 2 + c.wg;
  uint32_t rb = sb + g * GR;
  const uint32_t yb = sb + c.wg * 8192 + c.tid * 16;
  const int gt = 8 * w + (lane >> 2) + (lane & 3);
  uint32_t a[64], hb;
  auto lda = [&](int s) {
    a[4 * s] = lds32(hb + s * 256); a[4 * s + 1] = lds32(hb + s * 256 + 128);
    a[4 * s + 2] = lds32(hb + s * 256 + 16); a[4 * s + 3] = lds32(hb + s * 256 + 144);
  };
  auto first_a = [&]() {
    hb = sb + g * GR + WBYTES - 28 + gt * 4;
    lda(0); lda(15);
  };
  c.wait_full(g);
  first_a();
#pragma unroll 1
  for (int i = 0; i < ntask; i++) {
    const uint32_t base = sb + g * GR;
    FTC(0);
    lda(1); lda(14);
    a[0] = hadd2(a[0], gt == 7 ? dd : 0u); a[2] = hadd2(a[2], gt == 3 ? dd : 0u);
    float acc[128];
    const uint32_t db = dkk + ((WPL / 16 - 1) << 16) + g * DG + WZ / 16;
    FTC(2);
    c.turn_begin();
    FTC(3);
    auto pair = [&](auto kc) {
      constexpr int k = decltype(kc)::value;
      if (k < 7) wg_fence();
      if (k == 7) c.turn_end();
      conv_step<k, 7>(acc, a, db);
      conv_step<15 - k, 7>(acc, a, db);
      if (k < 6) { lda(k + 2); lda(13 - k); }
      if (k == 0) conv_final(rb, yb, i > 0);
      if (k == 1) {
        conv_final(rb + 2048, yb + 2048, i > 0);
        __syncwarp();
        if (lane == 0 && i > 0) mbar_arrive(sb + SM_BAR + (B_EV + c.wg) * 8);
      }
      if (k == 6) dd = __bfloat16_as_ushort(p.ssd[(ch + chstep) & (DM - 1)]);
    };
    pair(IC<0>()); pair(IC<1>()); pair(IC<2>()); pair(IC<3>()); pair(IC<4>()); pair(IC<5>()); pair(IC<6>()); pair(IC<7>());
    wg_commit();
    FTC(4);
    g = conv_next(g, spare);
    ch += chstep;
    rb = base + c.tid * 16;
    if (i + 1 < ntask) c.wait_full(g);
    wg_wait<0>();
    reg_fence(acc);
    reg_fence(a);
    bar_sync(3 + c.wg, 128);
    FTC(5);
    first_a();
    const int tw = (lane & 3) + w;
    const uint32_t xb = base + w * 4096 + tw * 32 + (lane >> 2) * 4;
#pragma unroll
    for (int j = 0; j < 32; j++) {
      float v0 = acc[4 * j], v1 = acc[4 * j + 1];
      if (j > 0) { v0 += acc[j > 0 ? 4 * j - 2 : 0]; v1 += acc[j > 0 ? 4 * j - 1 : 0]; }
      uint32_t v = pack_bf16(v0, v1), ad = xb + j * 128;
      if (j == 31 && tw >= 4) { v = 0; ad -= 4096; }
      asm volatile("st.shared.b32 [%0], %1;" ::"r"(ad), "r"(v) : "memory");
    }
    c.wait_stage_free();
    FTC(6);
  }
  bar_sync(3 + c.wg, 128);
  conv_final(rb, yb, true);
  conv_final(rb + 2048, yb + 2048, true);
  c.staged(0);
}

__global__ void __cluster_dims__(2, 1, 1) __launch_bounds__(NTHREADS, 1) mega_kernel(const __grid_constant__ Params p) {
  extern __shared__ __align__(1024) uint8_t smem_raw[];
  FTS(0);
  const uint32_t sb = smem_u32(smem_raw);
  if (threadIdx.x - 64 < 32) { prefetch_tm(&p.c); prefetch_tm(&p.wuk + (blockIdx.x & 1)); }
  const int wgi = __shfl_sync(0xffffffffu, threadIdx.x >> 7, 0);
  const int warp = __shfl_sync(0xffffffffu, threadIdx.x >> 5, 0);
  const uint32_t rank = blockIdx.x & 1;
  int slot;
  {
    uint32_t smid; asm volatile("mov.u32 %0, %smid;" : "=r"(smid));
    slot = p.pref[((smid >> 1) + (threadIdx.x & (smid >> 16))) & 127];
  }
  if (warp >= 3) {
    if (elect()) {
#pragma unroll
      for (int k = 0; k < 4; k++) mbar_init(sb + SM_BAR + ((warp - 3) * 4 + k) * 8, k == 1 && warp == 7 ? 11 : warp < (k ? 7 : 8) ? 1 : 4);
      if (warp == 7) mbar_expect_tx(sb + SM_BAR + B_SLOT * 8, 8);
      asm volatile("fence.mbarrier_init.release.cluster;" ::: "memory");
    }
    __syncwarp();
  }
  FTS(1);
  cluster_arrive();
  slot = __shfl_sync(0xffffffffu, slot, 0);
  const int pref = slot;
  if (warp < 4) {
    asm volatile("setmaxnreg.dec.sync.aligned.u32 40;");
    if (warp == 1 + 4 * rank) {
      unsigned taken = threadIdx.x == 32;
#pragma unroll 1
      for (int n = 0; n < NSLOT; n++) {
        asm volatile("{\n.reg .pred p;\nsetp.ne.b32 p, %0, 0;\n@p atom.relaxed.gpu.global.exch.b32 %0, [%1], 1;\n}\n" : "+r"(taken) : "l"(CLAIMP(slot)) : "memory");
        if (!__any_sync(0xffffffffu, taken)) break;
        slot = slot == NSLOT - 1 ? 0 : slot + 1;
      }
    }
    cluster_wait();
    if (threadIdx.x == 32) {
#pragma unroll
      for (int r = 0; r < 2; r++)
        asm volatile("{\n.reg .b32 a, b;\nmapa.shared::cluster.u32 a, %0, %1;\nadd.u32 b, a, %3;\nst.async.shared::cluster.mbarrier::complete_tx::bytes.u32 [b], %2, [a];\n}\n"
                     ::"r"(sb + SM_BAR + B_SLOT * 8), "r"(r), "r"(slot | pref << 8), "r"((V_SLOT - B_SLOT) * 8 + rank * 4) : "memory");
    }
    if (warp == 2) {
#pragma unroll 1
      for (int kk = 0; kk < 4; kk++) {
        const int g0 = 2 + 3 * kk;
        const uint32_t fb = sb + SM_BAR + (B_FULL + g0) * 8;
        if (elect()) {
          FTSW(kk);
          mbar_expect_tx(fb, 3 * GR);
          tma2d(sb + g0 * GR, &p.c, kk * 64, (KV_ROW(pref & 7, 0) + rank) * 128, fb);
          tma3d_mc(sb + (g0 + 1 + rank) * GR, rank ? &p.wuv : &p.wuk, 0, kk * 64, ((pref & 56) >> 1) + 2 * KV_HEAD(pref & 7, 0), fb);
        }
        if (kk < 3) {
          uint32_t c0, c1;
          asm volatile("mov.u32 %0, %clock;" : "=r"(c0));
          do asm volatile("mov.u32 %0, %clock;" : "=r"(c1)); while (c1 - c0 < (kk ? X_D2 : X_DELAY));
        }
      }
      FTSW(4);
      prefetch_tm(&p.x); prefetch_tm(&p.wq);
    }
  }
  int grp, idx, lb;
  int cn, cch, cstep;
  bool spare, redo;
  auto get_slot = [&]() {
    mbar_wait(sb + SM_BAR + B_SLOT * 8, 0);
    const uint32_t sv0 = __shfl_sync(0xffffffffu, lds32(sb + SM_BAR + V_SLOT * 8), 0), sv1 = __shfl_sync(0xffffffffu, lds32(sb + SM_BAR + V_SLOT * 8 + 4), 0);
    grp = (sv0 & 255) >> 3; idx = sv0 & 7; lb = (sv0 & 255) * 2 + rank;
    spare = grp == 8; redo = spare || sv0 != sv1;
    cn = spare ? CN_SPARE : CN_MAIN; cch = spare ? lb - NMAIN : 4 * CN_SPARE + CN_MAIN * lb; cstep = spare ? 4 : 1;
    if (FINE_MODE != 7) TS(0);
  };

  if (wgi == 0) {
    asm volatile("setmaxnreg.dec.sync.aligned.u32 40;");
    const int lane = threadIdx.x & 31;
    cluster_arrive();
    get_slot();
    uint32_t pe = 0;
    auto acquire = [&](int g, int n, uint32_t m) {
      int i = g;
#pragma unroll 1
      do mbar_wait1(sb + SM_BAR + (B_EMPTY + i) * 8, (pe >> i) & 1); while (++i < g + n);
      pe ^= m << g;
    };
    if (warp == 3) {
      if (!spare) {
        const int s0 = lb * 16;
#pragma unroll 1
        for (int cg = 0; cg < 16; cg++) {
          if (cg == 3 || cg == 10) {
#pragma unroll 1
            for (int n = 0; n < 20 && !__any_sync(0xffffffffu, mbar_try(sb + SM_BAR + B_SLOT * 8, cg == 3)); n++);
          } else if (cg < 3) __nanosleep(800);
          const int ch = cg * 64 + 2 * lane;
          const uint32_t* kp = reinterpret_cast<const uint32_t*>(p.ak + (size_t)s0 * DM + ch);
          const uint32_t* vp = reinterpret_cast<const uint32_t*>(p.av + (size_t)s0 * DM + ch);
          const uint4 sw = __ldg(reinterpret_cast<const uint4*>(p.shk + ch * 4));
          uint32_t k3 = 0, k2 = 0, k1 = 0, k0 = 0, up = 0;
          if (lb > 0) { k3 = ldg_stream(kp - 4 * 512); k2 = ldg_stream(kp - 3 * 512); k1 = ldg_stream(kp - 2 * 512); k0 = ldg_stream(kp - 512); up = ldg_stream(vp - 512); }
          const uint32_t w0 = __byte_perm(sw.x, sw.z, 0x5410), w1 = __byte_perm(sw.x, sw.z, 0x7632);
          const uint32_t w2 = __byte_perm(sw.y, sw.w, 0x5410), w3 = __byte_perm(sw.y, sw.w, 0x7632);
          up = hmul2(hfma2(k0, w0, hfma2(k1, w1, hfma2(k2, w2, hmul2(k3, w3)))), up);
#pragma unroll 1
          for (int hb = 0; hb < 2; hb++) {
            uint32_t kk[8], u[8];
#pragma unroll
            for (int r = 0; r < 8; r++) { kk[r] = ldg_stream(kp + r * 512); u[r] = ldg_stream(vp + r * 512); }
#pragma unroll
            for (int r = 0; r < 8; r++) {
              k3 = k2; k2 = k1; k1 = k0; k0 = kk[r];
              u[r] = hmul2(hfma2(k0, w0, hfma2(k1, w1, hfma2(k2, w2, hmul2(k3, w3)))), u[r]);
            }
            if (lane == 0) asm volatile("cp.async.bulk.wait_group.read 0;" ::: "memory");
            __syncwarp();
            const uint32_t dst = sb + SM_UST + lane * 32 + ((lane & 4) << 2);
#pragma unroll
            for (int cc = 0; cc < 2; cc++) {
              const uint32_t sel = cc ? 0x7632 : 0x5410;
              asm volatile("st.shared.v4.b32 [%0], {%1,%2,%3,%4};" ::"r"(dst + cc * 1024), "r"(__byte_perm(u[6], u[5], sel)), "r"(__byte_perm(u[4], u[3], sel)),
                           "r"(__byte_perm(u[2], u[1], sel)), "r"(__byte_perm(u[0], up, sel)) : "memory");
              asm volatile("st.shared.v4.b32 [%0], {%1,%2,%3,%4};" ::"r"((dst ^ 16) + cc * 1024), "r"(__byte_perm(u[7], u[6], sel)), "r"(__byte_perm(u[5], u[4], sel)),
                           "r"(__byte_perm(u[3], u[2], sel)), "r"(__byte_perm(u[1], u[0], sel)) : "memory");
            }
            fence_async_smem();
            __syncwarp();
            if (lane == 0) {
              asm volatile("cp.async.bulk.tensor.3d.global.shared::cta.bulk_group [%0, {%2, %3, %4}], [%1];\ncp.async.bulk.commit_group;"
                           ::"l"(&p.w), "r"(sb + SM_UST), "r"(WZ / 2 + lb * 16 + (hb ^ 1) * (WPL / 2)), "r"(cg * 32), "r"(0) : "memory");
            }
            up = u[7];
            kp += 8 * 512; vp += 8 * 512;
          }
          if ((cg & (cg + 1)) == 0 && lane == 0) {
            asm volatile("cp.async.bulk.wait_group 0;" ::: "memory");
            fence_release();
            flag_add(FLAG(F_U + 32 - __clz(cg)));
          }
          TSW(10 + cg);
        }
        prefetch_tm(&p.wo); prefetch_tm(&p.x3); prefetch_tm(&p.y3); prefetch_tm(&p.out);
        if (P3PF) {
          const int rt = 2 * grp + rank;
          unsigned v;
          asm volatile("ld.acquire.gpu.global.u32 %0, [%1];" : "=r"(v) : "l"(FLAG(F_CTX + rt * 2)) : "memory");
#pragma unroll 1
          for (int kb = P3PF0; kb < P3PF0 + P3PF; kb++) {
            const uint8_t* a = lane < 16 ? g_cimg + (unsigned)((rt * 64 + kb) * GR + (idx * 16 + lane) * 128) : (const uint8_t*)p.wop + (unsigned)(kb * 64 * DM * 2 + (lb * 8 + (lane & 7)) * 128);
            if (lane < 24 && v == 32) asm volatile("prefetch.global.L2 [%0];" ::"l"(a));
          }
        }
      } else {
#pragma unroll 1
        for (int i = 0, g = 2; i < 32; i++) {
          acquire(g, 2, 3);
          if (elect()) {
            const uint32_t fb = sb + SM_BAR + (B_FULL + g) * 8;
            if (i == 0) { mbar_expect_tx(fb - 8, 2048); bulk_g2s(sb + GR, p.gate_w, 2048, fb - 8); }
            mbar_expect_tx(fb, 2 * GR);
            tma3d(sb + g * GR, &p.x3, 0, (lb - NMAIN) * 512 + (i >> 3) * 128, (i & 7) * 2, fb);
          }
          g = g == NGR - 2 ? 2 : g + 2;
        }
        bar_arrive(5, 64);
      }
      unsigned long long t0, t1;
      asm volatile("mov.u64 %0, %globaltimer;" : "=l"(t0));
      auto check = [&]() {
        asm volatile("mov.u64 %0, %globaltimer;" : "=l"(t1));
        if (t1 - t0 > 2000000000ull) __trap();
      };
      if (!spare) {
        unsigned v;
        do {
          __nanosleep(1000);
          check();
          asm volatile("ld.acquire.gpu.global.u32 %0, [%1];" : "=r"(v) : "l"(FLAG(lane & 1 ? F_Y + idx : F_GATE)) : "memory");
        } while (__any_sync(0xffffffffu, v < (lane & 1 ? 128 : 32)));
        __syncwarp();
        if (lane == 0) mbar_arrive(sb + SM_BAR + B_SLOT * 8);
      }
      if (lane == 0) {
        while (!mbar_try(sb + SM_BAR + B_DONE * 8, 0)) check();
      }
    } else if (warp != 0) {
      const int w = warp - 1, ne = 12 + (cn + 1 - w) / 2;
      uint32_t p0 = 0;
      int cg = 2 + w, ch = cch + w * cstep;
#pragma unroll 1
      for (int e = spare ? 12 : 0; e < ne; e++) {
        const int rnd = e >= 6, k = e - 6 * rnd, rt = k == 4 ? idx : 15 - idx;
        uint8_t* dst = k < 4 ? g_kv + (size_t)(((k & 1) * 16 + 2 * grp + KV_HEAD(idx, k >> 1)) * 16 + KV_ROW(idx, k >> 1) + rank) * 32768 + w * 8192
                     : k < 6 ? g_cimg + (size_t)(rt * 32 + 16 * rnd + 2 * grp + rank) * 32768 + (w ^ (k & 1)) * 8192
                             : reinterpret_cast<uint8_t*>(g_yT + (size_t)ch * SEQ);
        const uint32_t src = sb + w * 8192 + (k == 4 ? 2 * GR : 0);
        if (e == 6) flag_wait(FLAG(F_AD + grp), 32);
        mbar_wait1(sb + SM_BAR + (B_EV + (k == 4 ? 2 : 0) + w) * 8, k == 4 ? rnd : p0);
        if (k != 4) p0 ^= 1;
        if (lane < 4 && k >= 6 && (!spare || e < ne - 6)) mbar_arrive_cluster(sb + SM_BAR + (B_EMPTY + cg) * 8, lane & 1);
        fence_async_smem();
        if (elect()) {
#pragma unroll 1
          for (int i = 0; i < (k >= 6 ? 1 : 8); i++) {
            const uint32_t o = (i >> 2) * 16384 + (i & 3) * 2048;
            asm volatile("cp.async.bulk.global.shared::cta.bulk_group [%0], [%1], %2;" ::"l"(dst + o), "r"(src + o), "r"(k >= 6 ? 4096 : 2048) : "memory");
            asm volatile("cp.async.bulk.commit_group;\ncp.async.bulk.wait_group.read %0;" ::"n"(ST_OUT) : "memory");
          }
          asm volatile("cp.async.bulk.wait_group 0;" ::: "memory");
          if (k != 4) mbar_arrive(sb + SM_BAR + (B_FREE + w) * 8);
        }
        __syncwarp();
        if (lane < (k == 4 ? 4 : e == 11 || (e == ne - 1 && !spare) ? 2 : 0))
          mbar_arrive_cluster(sb + SM_BAR + (B_EMPTY + (k == 4 ? 2 : e == 11) + (lane >> 1)) * 8, lane & 1);
        if (k >= 3) {
          fence_release();
          const unsigned fl = k == 3 ? F_KV + rnd * 8 + grp : k < 6 ? F_CTX + rt * 2 + rnd : F_Y + ((unsigned)ch >> 7);
          if (lane <= (e == 5)) flag_add(FLAG(lane ? F_AD + grp : fl));
        }
        if (k >= 6) { cg = conv_next(cg, spare); ch += 2 * cstep; }
      }
      if (lane == 0) mbar_arrive(sb + SM_BAR + B_DONE * 8);
    } else {
#pragma unroll 1
      for (int rnd = 0; rnd < (spare ? 0 : 2); rnd++) {
        const int hp = 16 * rnd + 2 * grp, head = hp + rank;
#pragma unroll 1
        for (int kk = rnd || redo ? 0 : 4; kk < 32; kk++) {
          const int g0 = 2 + 3 * (kk & 3);
          acquire(g0, kk < 4 ? 3 : 1, 7);
          if (elect()) {
            const uint32_t fb = sb + SM_BAR + (B_FULL + g0) * 8;
            mbar_expect_tx(fb, 3 * GR);
            if (kk < 16) {
              tma2d(sb + g0 * GR, &p.c, (kk & 7) * 64, (KV_ROW(idx, kk >> 3) + rank) * 128, fb);
              tma3d_mc(sb + (g0 + 1 + rank) * GR, rank ? &p.wuv : &p.wuk, 0, (kk & 7) * 64, (hp + KV_HEAD(idx, kk >> 3)) * 2, fb);
            } else {
              tma2d_mc(sb + (g0 + rank) * GR, &p.x, (kk - 16) * 64, (rank ? 15 - idx : idx) * 128, fb);
              tma3d(sb + (g0 + 2) * GR, &p.wq, 0, (kk - 16) * 64, head * 2, fb);
            }
          }
        }
        flag_wait(FLAG(F_KV + rnd * 8 + grp), 32);
        fence_async_all();
        acquire(2, 1, 3);
        int g0 = 4;
#pragma unroll 1
        for (int n = 0; n < 36; n += n == 0 || n == 33 ? 2 : 1) {
          const int it = (n >> 1) - (n & 1);
          const int blk = it & 15 ? (it <= idx ? it - 1 : 15 - it) : it ? 15 - idx : idx;
          acquire(g0, n < 6 ? 2 : 1, 3);
          if (elect()) {
            const uint32_t fb = sb + SM_BAR + (B_FULL + g0) * 8;
            if (n == 5) mbar_arrive(sb + SM_BAR + B_SLOT * 8);
            mbar_expect_tx(fb, 2 * GR);
            bulk_g2s(sb + g0 * GR, g_kv + (unsigned)((((n & 1) * 16 + (head & 15)) * 16 + blk) * 32768), 2 * GR, fb);
          }
          g0 = n == 13 ? 12 : g0 == 12 ? 4 : g0 + 2;
        }
      }
      if (spare) { bar_sync(5, 64); pe = 0x3FC0; }
      auto conv_fill = [&](int g, int ch) {
        acquire(g, 1, 1);
        if (elect()) {
          const uint32_t fb = sb + SM_BAR + (B_FULL + g) * 8;
          if (!spare) FTP(64 + 48 + g);
          mbar_expect_tx(fb, WBYTES + 4096);
          bulk_g2s<true>(sb + g * GR, g_w + (size_t)ch * WSTRIDE, WBYTES, fb);
          bulk_g2s<true>(sb + g * GR + WBYTES, p.ssk + (size_t)ch * SEQ, 4096, fb);
        }
      };
#pragma unroll 1
      for (int i = 0, g = 2; i < cn; i++) {
        if ((i & 15) == 0) { flag_wait(FLAG(F_U + (spare ? 32 - __clz(i >> 4) : 4)), NMAIN); fence_async_all(); }
        conv_fill(g + (i & 1), cch + i * cstep);
        if (i & 1) g = conv_next(g, spare);
      }
      if (!spare) {
        const int rt = 2 * grp + rank, ct = idx;
        int g0 = P3G, top = 12;
        const uint8_t* src = g_cimg + (unsigned)(rt * 64 * GR);
#pragma unroll 1
        for (int kb = 0; kb < 64; kb++) {
          if (!(kb & 31)) { flag_wait(FLAG(F_CTX + rt * 2 + (kb >> 5)), 32); fence_async_all(); }
          acquire(g0, kb < 11 ? 2 : 1, 3);
          if (elect()) {
            const uint32_t fb = sb + SM_BAR + (B_FULL + g0) * 8;
            if (kb < 16) FTP(48 + kb);
            mbar_expect_tx(fb, 2 * GR);
            bulk_g2s<true>(sb + g0 * GR, src, GR, fb);
            tma2d_mc<true>(sb + (g0 + 1) * GR + rank * 8192, &p.wo, ct * 128 + rank * 64, kb * 64, fb);
          }
          src += GR;
          g0 = g0 == top ? (kb == 3 ? 2 : 0) : g0 + 2;
          if (kb == XK || kb == YK) {
            const bool j = kb == YK;
            if (j) { mbar_wait1(sb + SM_BAR + B_SLOT * 8, 1); fence_async_all(); }
            acquire(top, 1, 0);
            if (elect()) {
              const uint32_t fb = sb + SM_BAR + (B_FULL + top) * 8;
              mbar_expect_tx(fb, j ? 2 * GR + 512 : 2 * GR);
              if (j) bulk_g2s(sb + SM_GATE, g_gate + (unsigned)(rt * 128), 512, fb);
              tma3d(sb + top * GR, j ? &p.y3 : &p.x3, 0, (j ? ct : rt) * 128, (j ? rt : ct) * 2, fb);
            }
            g0 = 0; top -= 2;
          }
        }
        unsigned n = 0;
        if (lane == 0) n = atomicInc(FLAG(F_EXIT), 0x7fffffffu);
        if (__any_sync(0xffffffffu, n == NMAIN - 1)) {
#pragma unroll
          for (int i = lane; i < 96; i += 32) *reinterpret_cast<uint2*>(FLAG(i)) = make_uint2(0, 0);
        }
      }
      if (lane == 0) mbar_arrive(sb + SM_BAR + B_DONE * 8);
    }
    __syncwarp();
    cluster_wait();
  } else {
    asm volatile("setmaxnreg.inc.sync.aligned.u32 232;");
    FTS(2);
    Cons c;
    c.sb = sb; c.pf = 0; c.wg = wgi - 1; c.tid = threadIdx.x & 127;
    const int lane = threadIdx.x & 31, t = lane & 3;
    const int row = c.wg * 64 + (warp & 3) * 16 + (lane >> 2);
    const uint32_t dkk = desc_k(sb), dk0 = dkk + c.wg * 512, dm0 = desc_mn<8192>(sb), dv0 = desc_mn<16384>(sb);
    const uint32_t dsw = DG + 512 - c.wg * 1024;
    if (c.wg == 1) bar_arrive(1, 256);
    c.pfree = 1;
    asm("mapa.shared::cluster.u32 %0, %1, %2;" : "=r"(c.relb) : "r"(sb + SM_BAR + (B_EMPTY + (c.tid >> 1)) * 8), "r"(c.tid & 1));
    c.zero = p.zero;
    c.rnd = 0;
    const uint32_t stg = sb + (c.wg * 64 + (warp & 3) * 16 + ((lane >> 3) & 1) * 8 + (lane & 7)) * 128 + (((lane >> 4) ^ (lane & 7)) << 4);

    uint32_t dd0;
    auto load_dd = [&]() { asm volatile("ld.global.nc.u16 %0, [%1];" : "=r"(dd0) : "l"(p.ssd + (unsigned)(cch + c.wg * cstep + (lane & c.zero)))); };
    int pass = c.zero;
#pragma unroll 1
    do {
    if (pass) {
      load_dd();
#pragma unroll 1
      for (int g = 2; g < NGR; g += 3) { mbar_wait(sb + SM_BAR + (B_FULL + g) * 8, 0); c.release(g, 3); }
      c.pf = 0x924;
    if (spare) {
      c.wait_full(1);
      int g = 2;
#pragma unroll 1
      for (int r = 0; r < 4; r++) {
        float d[4] = {0.f, 0.f, 0.f, 0.f}, e[4] = {0.f, 0.f, 0.f, 0.f};
#pragma unroll 1
        for (int kb = 0; kb < 16; kb += 2) {
          c.wait_full(g);
          wg_fence();
#pragma unroll 1
          for (int k = 0; k < 4; k++) {
            mma_ss_n8(d, dk0 + g * DG + k * 2, dkk + DG + kb * 8 + k * 2);
            mma_ss_n8(e, dk0 + (g + 1) * DG + k * 2, dkk + DG + kb * 8 + 8 + k * 2);
          }
          wg_commit();
          wg_wait<0>();
          c.release(g, 2);
          g = g == NGR - 2 ? 2 : g + 2;
        }
        reg_fence(d); reg_fence(e);
        d[0] += e[0]; d[2] += e[2];
        if (t == 0) {
          float* gp = g_gate + (unsigned)((lb - NMAIN) * 512 + r * 128 + row);
          gp[0] = rcp(1.f + ex2(-1.4426950408889634f * d[0])); gp[8] = rcp(1.f + ex2(-1.4426950408889634f * d[2]));
        }
      }
      fence_release();
      __syncwarp();
      if (lane == 0) flag_add(FLAG(F_GATE));
      TS(1);
    }
    } else cluster_wait();
    get_slot();
    } while (redo && !pass++);
    FTS(3);
    const float dmask = (float)(2 * t - (row & 63));
    uint32_t pv[32];
#pragma unroll 1
    for (int rnd = 0; rnd < (spare ? 0 : 2); rnd++) {
      float O[64];
      FTM(rnd * 8);
      FTG(0);
      FTH(56, c.rnd == rnd);
      c.wait_full(2);
      FTM(rnd * 8 + 1);
      FTH(57, c.rnd == rnd);
#pragma unroll 1
      for (int tile = c.zero; tile < 2; tile++) {
        float acc[128];
        const bool single = tile == 0;
        {
          FTG(tile * 32 + 1);
          const uint32_t a = dk0 + 2 * DG, b = dm0 + 3 * DG;
          c.turn_begin();
          FTG(tile * 32 + 2);
          FTH(58, c.rnd == rnd);
          wg_fence();
          mma_ss_n256_init<1>(acc, a, b);
#pragma unroll
          for (int k = 1; k < 4; k++) mma_ss_n256<1>(acc, a + k * 2, b + k * 128);
          wg_commit();
          if (single) c.turn_end();
          FTG(tile * 32 + 3);
        }
#pragma unroll 1
        for (int kb = 1; kb < 8; kb++) {
          const int g0 = 2 + 3 * (kb & 3);
          const uint32_t a = dk0 + g0 * DG, b = dm0 + (g0 + 1) * DG;
          const bool second = (kb == 1 && !single) || kb == 7;
          FTG(tile * 32 + kb * 4);
          if (!second) { wg_wait<0>(); c.release(2 + 3 * ((kb - 1) & 3), 3); }
          FTG(tile * 32 + kb * 4 + 1);
          c.wait_full(g0);
          if (!second) c.turn_begin();
          FTG(tile * 32 + kb * 4 + 2);
          wg_fence();
#pragma unroll
          for (int k = 0; k < 4; k++) mma_ss_n256<1>(acc, a + k * 2, b + k * 128);
          wg_commit();
          if (kb != 6) c.turn_end();
          if (second) { wg_wait<1>(); c.release(2 + 3 * ((kb - 1) & 3), 3); }
          FTG(tile * 32 + kb * 4 + 3);
          FTH(58 + kb, c.rnd == rnd || kb > 3);
          if (tile == 1 && kb == 3) { c.wait_stage_free(); stsm_frag<0, 4>(pv, stg); }
          if (tile == 1 && kb == 4) { stsm_frag<4, 8>(pv, stg); c.staged(0); }
        }
        c.rnd = rnd;
        c.wait_stage_free();
        const bool nxt = c.try_full(2);
        wg_wait<0>();
        reg_fence(acc);
        c.release(11, 3);
        pack_frag_scaled(acc, pv, SM_C, SM_C);
        stsm_frag(pv, stg);
        c.staged(0);
        pack_frag<64>(acc, pv);
        pin32(pv, sb);
        FTG(32 + tile * 32);
        if (!nxt) mbar_wait(sb + SM_BAR + (B_FULL + 2) * 8, (c.pf >> 2) & 1);
        c.pf ^= 4;
      }
      TS(1 + rnd * 3);
      FTM(rnd * 8 + 2);
      {
        float qa[64];
        float (&qb)[64] = O;
        {
          FTG(65);
          const uint32_t a = dk0 + 2 * DG, b = dm0 + 4 * DG;
          c.turn_begin();
          FTG(66);
          wg_fence();
          mma_ss_n128_init<1>(qa, a, b);
          mma_ss_n128_init<1>(qb, a + dsw, b);
#pragma unroll
          for (int k = 1; k < 4; k++) {
            mma_ss_n128<1>(qa, a + k * 2, b + k * 128);
            mma_ss_n128<1>(qb, a + dsw + k * 2, b + k * 128);
          }
          wg_commit();
          FTG(67);
        }
#pragma unroll 1
        for (int kb = 1; kb < 16; kb++) {
          const int g0 = 2 + 3 * (kb & 3);
          const uint32_t a = dk0 + g0 * DG, b = dm0 + (g0 + 2) * DG;
          const bool second = kb == 1 || kb == 15;
          FTG(64 + kb * 4);
          if (!second) { wg_wait<0>(); c.release(2 + 3 * ((kb - 1) & 3), 3); }
          FTG(65 + kb * 4);
          c.wait_full(g0);
          if (!second) c.turn_begin();
          FTG(66 + kb * 4);
          FTH(kb - 14, kb < 14);
          wg_fence();
#pragma unroll
          for (int k = 0; k < 4; k++) {
            mma_ss_n128<1>(qa, a + k * 2, b + k * 128);
            mma_ss_n128<1>(qb, a + dsw + k * 2, b + k * 128);
          }
          wg_commit();
          if (kb != 14) c.turn_end();
          if (second) { wg_wait<1>(); c.release(2 + 3 * ((kb - 1) & 3), 3); }
          FTG(67 + kb * 4);
          FTH(2, kb < 15);
          if (kb == QFLUSH) { c.wait_stage_free(); stsm_frag<0, 4>(pv, stg); }
          if (kb == QFLUSH + 1) { stsm_frag<4, 8>(pv, stg); c.staged(0); }
        }
        c.wait_stage_free();
        mbar_wait(sb + SM_BAR + (B_EMPTY + 2) * 8, rnd ^ !redo);
        FTM(rnd * 8 + 3);
        FTH(3, 0);
        wg_wait<0>();
        reg_fence(qa); reg_fence(qb);
        FTH(4, 0);
        c.release(11, 3);
        pack_frag<0>(qa, pv);
        stsm_frag(pv, stg + 2 * GR);
        if (c.wg == 0) {
          pack_frag<0>(qb, pv);
          stsm_frag(pv, stg);
        }
        FTH(6, 0);
        fence_async_smem();
        FTH(7, 0);
        c.wait_full(4);
      }
      TS(2 + rnd * 3);
      FTM(rnd * 8 + 4);
      FTH(5, 0);
      {
        const int nA = idx + 1;
        uint32_t (&P)[32] = pv;
        SoftState z;
        z.m0 = z.m1 = z.l0 = z.l1 = 0.f; z.shifted = c.zero;
#pragma unroll 1
        for (int seg = c.zero;; seg++) {
        if (c.wg == seg) attn_half(c, O, P, z, dk0, dkk, dv0, dmask, seg);
        if (seg) break;
        FTM(rnd * 8 + 5);
        int gk = c.wg ? 4 : 6, gv = c.wg ? 4 : 8;
        uint32_t dq = dk0 + (1 - c.wg < nA ? 2 * DG : 0), dk = dkk + gk * DG;
#pragma unroll 1
        for (int it = 1 - c.wg; it < 17 - c.wg; it++) {
          float S[64];
          FTA(it * 7 + 0); FTH((it < 3 ? 8 + it * 8 : it * 8 - 88) + 0, it >= 3 && it < 15);
          c.turn_begin();
          FTA(it * 7 + 2); FTH((it < 3 ? 8 + it * 8 : it * 8 - 88) + 1, it >= 3 && it < 15);
          wg_fence();
          issue_qk(S, dq, dk);
          wg_commit();
          const uint32_t dv = dv0 + gv * DG;
          uint32_t relk = c.relb + gk * 8, relv = c.relb + gv * 8;
          gk = it == 6 ? 12 : gv == 12 ? 4 : gv + 2;
          gv = it == 16 ? gk : gk == 12 ? 4 : gk + 2;
          uint32_t fk = sb + SM_BAR + (B_FULL + gk) * 8, fv = sb + SM_BAR + (B_FULL + gv) * 8, park = (c.pf >> gk) & 1, parv = (c.pf >> gv) & 1;
          c.pf ^= (1u << gk) | (1u << gv);
          dq = dk0 + (it + 1 < nA ? 2 * DG : 0); dk = dkk + gk * DG;
          float lo0 = z.l0, lo1 = z.l1;
          const bool first = it == nA || it == 0;
          if (it == nA) {
            if (EARLY_RCP) { lo0 = rcp(quad_sum(lo0)); lo1 = rcp(quad_sum(lo1)); }
            z.m0 = z.m1 = z.l0 = z.l1 = 0.f; z.shifted = 0;
          }
          float s0, s1, d0 = z.m0, d1 = z.m1;
          int pre = z.shifted || (it & 15) == 0;
          float lim = first ? -1.f : SM_LIMIT;
          asm volatile("" : "+r"(relk), "+r"(relv), "+r"(fk), "+r"(fv), "+r"(park), "+r"(parv), "+r"(dq), "+r"(dk), "+r"(pre), "+f"(lim), "+f"(d0), "+f"(d1), "+f"(z.l0), "+f"(z.l1));
          if (it) {
            issue_pv<0>(O, P, dv, it != nA + 1 && it != 1, true);
            issue_pv<1>(O, P, dv, 1, it + c.wg > 1);
            c.turn_end();
          } else stage_q2(c, O, P, stg);
          FTA(it * 7 + 3); FTH((it < 3 ? 8 + it * 8 : it * 8 - 88) + 2, it >= 3 && it < 15);
          wg_wait<4>();
          reg_fence(S);
          FTA(it * 7 + 4); FTH((it < 3 ? 8 + it * 8 : it * 8 - 88) + 3, it >= 3 && it < 15);
          if (c.tid < 4) asm volatile("mbarrier.arrive.shared::cluster.b64 _, [%0];" ::"r"(relk) : "memory");
#pragma unroll 1
          for (int pass = 0;; pass++) {
            if (pre) {
              if ((it & 15) == 0) mask_diag(S, dmask);
              if (z.shifted) shift_scores(S, d0, d1);
            }
            float tr[ROT];
            exp_quarter<0, 3>(S, P, tr, s0, s1, sb);
            exp_quarter<1, 2>(S, P, tr, s0, s1, sb);
            exp_quarter<2, 1>(S, P, tr, s0, s1, sb);
            exp_quarter<3, 0>(S, P, tr, s0, s1, sb);
            reg_fence(O);
            if (c.tid < (pass || !it ? 0 : 4)) asm volatile("mbarrier.arrive.shared::cluster.b64 _, [%0];" ::"r"(relv) : "memory");
            const bool ok = mbar_test(fk, park) & mbar_test(fv, parv);
            if (!ok) lim = -1.f;
            FTA(it * 7 + 5); FTH((it < 3 ? 8 + it * 8 : it * 8 - 88) + 4, it >= 3 && it < 15);
            if (!__any_sync(0xffffffffu, !(s0 <= lim && s1 <= lim))) break;
            if (pass) break;
            if (it == nA) {
              uint32_t pk[32];
              if (!EARLY_RCP) { lo0 = rcp(quad_sum(lo0)); lo1 = rcp(quad_sum(lo1)); }
              pack_frag_scaled(O, pk, lo0, lo1);
              stsm_frag(pk, stg + 2 * GR);
              c.staged(1);
            }
            if (!ok) { mbar_wait(fk, park); mbar_wait(fv, parv); }
            if (!soft_unsafe(s0, s1, first)) break;
            soft_fix(S, O, z, first, d0, d1);
            pre = 1;
          }
          z.l0 += s0; z.l1 += s1;
          FTA(it * 7 + 6); FTH((it < 3 ? 8 + it * 8 : it * 8 - 88) + 5, it >= 3 && it < 15);
        }
        FTM(rnd * 8 + 6);
        }
        FTH(48, 0);
        load_dd();
        c.turn_begin();
        FTH(49, 0);
        wg_fence();
        issue_pv<0>(O, P, dv0 + 12 * DG, 1, true);
        issue_pv<1>(O, P, dv0 + 12 * DG, 1, !c.wg);
        c.turn_end();
        z.l0 = rcp(quad_sum(z.l0)); z.l1 = rcp(quad_sum(z.l1));
        wg_wait<0>();
        reg_fence(O); reg_fence(P);
        FTH(50, 0);
        c.release(12, 2);
        pack_frag_scaled(O, P, z.l0, z.l1);
        stsm_frag(P, stg);
        c.staged(0);
        FTM(rnd * 8 + 7);
        FTH(51, 0);
      }
      TS(3 + rnd * 3);
    }
    conv_tasks(c, p, (cn + 1 - c.wg) / 2, spare, cch + c.wg * cstep, 2 * cstep, dd0, dkk, warp & 3, lane);
    if (c.wg == 1) c.pf ^= 0x14;
    if (c.wg != spare) c.turn_begin();
    TS(7);
    if (!spare) {
      const int rt = 2 * grp + rank, ct = idx;
      float acc[64];
      int g0 = P3G + 2, pg = P3G;
      {
        FTO(0);
        c.wait_full(P3G);
        FTO(1);
        const uint32_t a = dk0 + P3G * DG, b = dm0 + (P3G + 1) * DG;
        wg_fence();
        mma_ss_n128_init<1>(acc, a, b);
#pragma unroll
        for (int k = 1; k < 4; k++) mma_ss_n128<1>(acc, a + k * 2, b + k * 128);
        wg_commit();
      }
#pragma unroll 1
      for (int kb = 1; kb < 64; kb++) {
        FTO(kb * 2);
        c.wait_full(g0);
        if (kb == STR && !c.wg) c.turn_begin();
        FTO(kb * 2 + 1);
        const uint32_t a = dk0 + g0 * DG, b = dm0 + (g0 + 1) * DG;
        wg_fence();
#pragma unroll
        for (int k = 0; k < 4; k++) mma_ss_n128<1>(acc, a + k * 2, b + k * 128);
        wg_commit();
        if (kb < STR) { wg_wait<1>(); c.release(pg, kb <= 59 ? 2 : 0); }
        if (kb == FDUMP_KB) FTDUMP();
        pg = g0;
        g0 = g0 == (kb < XK ? 12 : kb < YK ? 10 : 8) ? (kb == 3 ? 2 : 0) : g0 + 2;
      }
      if (c.wg) c.turn_end();
      cluster_arrive();
      c.wait_full(P3X);
      c.wait_full(P3Y);
      const float g0f = __uint_as_float(lds32(sb + SM_GATE + row * 4)), g1f = __uint_as_float(lds32(sb + SM_GATE + row * 4 + 32));
      const uint32_t gp0 = pack_bf16(g0f, g0f), gp1 = pack_bf16(g1f, g1f);
      const float h0 = 1.f - g0f, h1 = 1.f - g1f;
      const int w = warp & 3;
      const uint32_t xa = stg + P3X * GR;
      const uint32_t ya = sb + P3Y * GR + c.wg * 16384 + ((lane >> 4) * 8 + (lane & 7)) * 128 + (((2 * w + ((lane >> 3) & 1)) ^ (lane & 7)) << 4);
      uint32_t xy[32];
      auto prep = [&](int j0, int j1) {
#pragma unroll
        for (int jj = j0; jj < j1; jj++) {
          uint32_t x[4], y[4];
          asm volatile("ldmatrix.sync.aligned.m8n8.x4.shared.b16 {%0,%1,%2,%3}, [%4];" : "=r"(x[0]), "=r"(x[1]), "=r"(x[2]), "=r"(x[3]) : "r"((xa ^ ((jj & 3) << 5)) + (jj >> 2) * 16384) : "memory");
          asm volatile("ldmatrix.sync.aligned.m8n8.x4.trans.shared.b16 {%0,%1,%2,%3}, [%4];" : "=r"(y[0]), "=r"(y[1]), "=r"(y[2]), "=r"(y[3]) : "r"(ya + jj * 2048) : "memory");
#pragma unroll
          for (int i = 0; i < 4; i++) xy[4 * jj + i] = hmul2(x[i], y[i]);
        }
      };
      prep(0, 4);
      wg_wait<0>();
      reg_fence(acc);
      TS(8);
#pragma unroll
      for (int hf = 0; hf < 2; hf++) {
#pragma unroll
        for (int i = 16 * hf; i < 16 * hf + 16; i++) {
          const float h = (i & 1) ? h1 : h0;
          xy[i] = hfma2((i & 1) ? gp1 : gp0, xy[i], pack_bf16(acc[2 * i] * h, acc[2 * i + 1] * h));
        }
        if (hf) stsm_frag<4, 8>(xy, xa); else stsm_frag<0, 4>(xy, xa);
        fence_async_smem();
        __syncwarp();
        const int r0 = c.wg * 64 + w * 16;
        if (lane == 0) tma2d_store(&p.out, sb + (P3X + hf) * GR + r0 * 128, ct * 128 + hf * 64, rt * 128 + r0);
        if (!hf) prep(4, 8);
      }
      if (lane == 0) asm volatile("cp.async.bulk.commit_group;\ncp.async.bulk.wait_group.read 0;" ::: "memory");
    } else { FTDUMP(); cluster_arrive(); }
    if (lane == 0) mbar_arrive(sb + SM_BAR + B_DONE * 8);
    __syncwarp();
    TS(9);
    cluster_wait();
  }
}

typedef CUresult (*EncFn)(CUtensorMap*, CUtensorMapDataType, cuuint32_t, void*, const cuuint64_t*, const cuuint64_t*, const cuuint32_t*,
                          const cuuint32_t*, CUtensorMapInterleave, CUtensorMapSwizzle, CUtensorMapL2promotion, CUtensorMapFloatOOBfill);

void enc2d(EncFn enc, CUtensorMap* tm, const void* base, uint64_t cols, uint64_t rows, uint32_t bc, uint32_t br) {
  cuuint64_t dims[2] = {cols, rows}; cuuint64_t strides[1] = {cols * 2}; cuuint32_t box[2] = {bc, br}; cuuint32_t es[2] = {1, 1};
  enc(tm, CU_TENSOR_MAP_DATA_TYPE_BFLOAT16, 2, const_cast<void*>(base), dims, strides, box, es, CU_TENSOR_MAP_INTERLEAVE_NONE,
      CU_TENSOR_MAP_SWIZZLE_128B, CU_TENSOR_MAP_L2_PROMOTION_L2_256B, CU_TENSOR_MAP_FLOAT_OOB_FILL_NONE);
}
void enc3d(EncFn enc, CUtensorMap* tm, const void* base, uint64_t K, uint64_t N, uint32_t bk = 64) {
  cuuint64_t dims[3] = {64, K, N / 64}; cuuint64_t strides[2] = {N * 2, 128}; cuuint32_t box[3] = {64, bk, 2}; cuuint32_t es[3] = {1, 1, 1};
  enc(tm, CU_TENSOR_MAP_DATA_TYPE_BFLOAT16, 3, const_cast<void*>(base), dims, strides, box, es, CU_TENSOR_MAP_INTERLEAVE_NONE,
      CU_TENSOR_MAP_SWIZZLE_128B, CU_TENSOR_MAP_L2_PROMOTION_L2_256B, CU_TENSOR_MAP_FLOAT_OOB_FILL_NONE);
}

}

extern "C" void kernel_launch(void* const* d_in, const int* in_sizes, int n_in, void* d_out, int out_size) {
  (void)in_sizes; (void)n_in; (void)out_size;
  typedef const __nv_bfloat16* BP;
  BP xq = (BP)d_in[0], ak = (BP)d_in[1], av = (BP)d_in[2], shk = (BP)d_in[3], ssk = (BP)d_in[4], ssd = (BP)d_in[5];
  BP ckv = (BP)d_in[7], wq = (BP)d_in[8], wuk = (BP)d_in[9], wuv = (BP)d_in[10], wo = (BP)d_in[11], gw = (BP)d_in[12];

  static EncFn enc = nullptr;
  if (!enc) {
    cudaDriverEntryPointQueryResult qr;
    cudaGetDriverEntryPoint("cuTensorMapEncodeTiled", (void**)&enc, cudaEnableDefault, &qr);
    cudaFuncSetAttribute(mega_kernel, cudaFuncAttributeMaxDynamicSharedMemorySize, SMEM_BYTES);
  }
  Params p;
  void* yT = nullptr;
  cudaGetSymbolAddress(&yT, g_yT);
  enc2d(enc, &p.x, xq, DM, SEQ, 64, 128);
  enc2d(enc, &p.c, ckv, DC, SEQ, 64, 128);
  enc3d(enc, &p.wq, wq, DM, NH * HD);
  enc3d(enc, &p.wuk, wuk, DC, NH * HD);
  enc3d(enc, &p.wuv, wuv, DC, NH * HD);
  enc2d(enc, &p.wo, wo, DM, NH * HD, 64, 64);
  enc3d(enc, &p.x3, xq, SEQ, DM, 128);
  enc3d(enc, &p.y3, yT, DM, SEQ, 128);
  enc2d(enc, &p.out, d_out, DM, SEQ, 64, 16);
  {
    void* wp = nullptr;
    cudaGetSymbolAddress(&wp, g_w);
    cuuint64_t dims[3] = {WSTRIDE / 2, DM / 2, 2}; cuuint64_t strides[2] = {2 * WSTRIDE, WSTRIDE}; cuuint32_t box[3] = {16, 32, 2}; cuuint32_t es[3] = {1, 1, 1};
    enc(&p.w, CU_TENSOR_MAP_DATA_TYPE_BFLOAT16, 3, wp, dims, strides, box, es, CU_TENSOR_MAP_INTERLEAVE_NONE,
        CU_TENSOR_MAP_SWIZZLE_32B, CU_TENSOR_MAP_L2_PROMOTION_NONE, CU_TENSOR_MAP_FLOAT_OOB_FILL_NONE);
  }
  p.zero = 0;
  cudaGetSymbolAddress((void**)&p.flags, g_flags);
  for (int i = 0; i < 128; i++) {
    const int tp = i % NSLOT;
    p.pref[i] = tp < 32 ? (tp & 7) * 8 + (tp >> 3) : tp < 60 ? (1 + (tp - 32) % 7) * 8 + 4 + (tp - 32) / 7 : tp < 62 ? tp + 4 : tp - 58;
  }
  p.gate_w = gw; p.ak = ak; p.av = av; p.shk = shk; p.ssk = ssk; p.ssd = ssd; p.wop = wo;

  mega_kernel<<<132, NTHREADS, SMEM_BYTES>>>(p);
}
```

```cpp
#include <cuda_runtime.h>
#include <cuda.h>
#include <cuda_bf16.h>
#include <stdint.h>

namespace {

constexpr int SEQ = 2048, DM = 1024, DC = 512, NH = 32, HD = 128;
constexpr int GR = 16384;
constexpr int NGR = 14;
constexpr int SM_BAR = NGR * GR;
constexpr int SM_GATE = SM_BAR + 512;
constexpr int SM_UST = SM_GATE + 512;
constexpr int SMEM_BYTES = SM_UST + 2048;
constexpr int NTHREADS = 384;
#define SM_LIMIT 1.0995116e12f
#define SM_LOW 9.094947e-13f
constexpr int CN_MAIN = 5, CN_SPARE = 96;
constexpr int XK = 57, YK = 62;
constexpr int STR = 61;
constexpr int P3G = 6, P3X = 12, P3Y = 10;
constexpr int NMAIN = 128;

constexpr int B_FULL = 0, B_FREE = 14, B_SLOT = 16, B_DONE = 17, B_EMPTY = 18, B_EV = 32, V_SLOT = 36;

__device__ __align__(1024) uint8_t g_kv[2 * 16 * 16 * 32768];
__device__ __align__(1024) uint8_t g_cimg[16 * NH * 32768];
__device__ __align__(1024) __nv_bfloat16 g_yT[DM * SEQ];
__device__ __align__(1024) float g_gate[SEQ];
#define CWIDE 0
constexpr int WZ = CWIDE ? 768 : 256, WPL = WZ + 4096, WBYTES = 2 * WPL + 32, WSTRIDE = 2 * WPL + 128;
__device__ __align__(1024) uint8_t g_w[DM * WSTRIDE];
__device__ __align__(32) unsigned g_flags[96 * 8];
constexpr int F_KV = 0, F_CTX = 16, F_U = 48, F_AD = 56, F_Y = 64, F_GATE = 72, F_EXIT = 73;
constexpr int NSLOT = 66;
#define FLAG(i) (&g_flags[(i) * 8])
#define CLAIMP(i) (p.flags + (i) * 8 + 1)

#define TS(slot)
#define TSW(slot)
#define FTX(i, off)
#define FTDUMP()

#define QFLUSH 4
#define X_DELAY 900
#define X_D2 600
#define P3PF 10
#define P3PF0 5
#define EXPV 1
#define SUMV 0
#define ROT 8
#define KVARR 1
#define KV_ROW(idx, t) (KVARR ? 8 * (t) + 2 * ((idx) & 3) : 2 * (idx))
#define KV_HEAD(idx, t) (KVARR ? (idx) >> 2 : (t))
#define FINE_MODE 0
#define FDUMP_KB 40
#define FINE_RND 1
#define FTA(i) do { if (FINE_MODE == 0) FTX(i, rnd ^ FINE_RND); } while (0)
#define FTG(i) do { if (FINE_MODE == 1) FTX(i, rnd ^ FINE_RND); } while (0)
#define FTM(i) do { if (FINE_MODE == 4) FTX(i, 0); } while (0)
#define FTC(k) do { if (FINE_MODE == 5) FTX((i & 7) * 8 + (k), (i >> 3) ^ FINE_RND); } while (0)
#define FTH(i, off) do { if (FINE_MODE == 6) FTX(i, (c.rnd ^ FINE_RND) | (off)); } while (0)
#define FTS(i)
#define FTSD(i)
#define FTSW(i)
#define FTP(i)
#define FTO(i) do { if (FINE_MODE == 2) FTX(i, 0); } while (0)

__device__ __forceinline__ uint32_t smem_u32(const void* p) { return (uint32_t)__cvta_generic_to_shared(p); }
__device__ __forceinline__ void mbar_init(uint32_t bar, int cnt) { asm volatile("mbarrier.init.shared::cta.b64 [%0], %1;" ::"r"(bar), "r"(cnt) : "memory"); }
__device__ __forceinline__ void mbar_expect_tx(uint32_t bar, uint32_t bytes) { asm volatile("mbarrier.arrive.expect_tx.shared::cta.b64 _, [%0], %1;" ::"r"(bar), "r"(bytes) : "memory"); }
__device__ __forceinline__ void mbar_arrive(uint32_t bar) { asm volatile("mbarrier.arrive.shared::cta.b64 _, [%0];" ::"r"(bar) : "memory"); }
__device__ __forceinline__ void mbar_arrive_cluster(uint32_t bar, uint32_t cta) {
  asm volatile("{\n.reg .b32 r;\nmapa.shared::cluster.u32 r, %0, %1;\nmbarrier.arrive.shared::cluster.b64 _, [r];\n}\n" ::"r"(bar), "r"(cta) : "memory");
}
__device__ __forceinline__ bool mbar_try(uint32_t bar, uint32_t parity) {
  uint32_t ok;
  asm volatile("{\n.reg .pred p;\nmbarrier.try_wait.parity.shared::cta.b64 p, [%1], %2, 20000;\nselp.u32 %0, 1, 0, p;\n}\n" : "=r"(ok) : "r"(bar), "r"(parity) : "memory");
  return ok;
}
__device__ __forceinline__ bool mbar_test(uint32_t bar, uint32_t parity) {
  uint32_t ok;
  asm volatile("{\n.reg .pred p;\nmbarrier.test_wait.parity.shared::cta.b64 p, [%1], %2;\nselp.u32 %0, 1, 0, p;\n}\n" : "=r"(ok) : "r"(bar), "r"(parity) : "memory");
  return ok;
}
__device__ __forceinline__ void mbar_wait(uint32_t bar, uint32_t parity) {
  asm volatile("{\n.reg .pred p;\nWAIT_LOOP:\nbar.warp.sync -1;\nmbarrier.try_wait.parity.shared::cta.b64 p, [%0], %1;\n@!p bra WAIT_LOOP;\n}\n" ::"r"(bar), "r"(parity) : "memory");
}
__device__ __forceinline__ void mbar_wait1(uint32_t bar, uint32_t parity) {
  asm volatile("{\n.reg .pred p;\nWAIT_LOOP:\nbar.warp.sync -1;\nmbarrier.try_wait.parity.shared::cta.b64 p, [%0], %1, 4000;\n@!p bra WAIT_LOOP;\n}\n" ::"r"(bar), "r"(parity) : "memory");
}
constexpr uint64_t EV_FIRST = 0x12F0000000000000ull;
__device__ __forceinline__ uint32_t ldg_stream(const uint32_t* p) {
  uint32_t r; asm volatile("ld.global.nc.L1::no_allocate.L2::cache_hint.b32 %0, [%1], %2;" : "=r"(r) : "l"(p), "l"(EV_FIRST)); return r;
}
#define TMA_LD "cp.async.bulk.tensor."
#define TMA_MB ".shared::cluster.global.mbarrier::complete_tx::bytes"
__device__ __forceinline__ void tma2d(uint32_t dst, const CUtensorMap* tm, int c0, int c1, uint32_t bar) {
  asm volatile(TMA_LD "2d" TMA_MB " [%0], [%1, {%3, %4}], [%2];" ::"r"(dst), "l"(tm), "r"(bar), "r"(c0), "r"(c1) : "memory");
}
template <bool ONCE = false> __device__ __forceinline__ void tma2d_mc(uint32_t dst, const CUtensorMap* tm, int c0, int c1, uint32_t bar) {
  if (ONCE) asm volatile(TMA_LD "2d" TMA_MB ".multicast::cluster.L2::cache_hint [%0], [%1, {%3, %4}], [%2], %5, %6;"
                         ::"r"(dst), "l"(tm), "r"(bar), "r"(c0), "r"(c1), "h"((uint16_t)3), "l"(EV_FIRST) : "memory");
  else asm volatile(TMA_LD "2d" TMA_MB ".multicast::cluster [%0], [%1, {%3, %4}], [%2], %5;"
                    ::"r"(dst), "l"(tm), "r"(bar), "r"(c0), "r"(c1), "h"((uint16_t)3) : "memory");
}
__device__ __forceinline__ void tma3d(uint32_t dst, const CUtensorMap* tm, int c0, int c1, int c2, uint32_t bar) {
  asm volatile(TMA_LD "3d" TMA_MB " [%0], [%1, {%3, %4, %5}], [%2];" ::"r"(dst), "l"(tm), "r"(bar), "r"(c0), "r"(c1), "r"(c2) : "memory");
}
__device__ __forceinline__ void tma3d_mc(uint32_t dst, const CUtensorMap* tm, int c0, int c1, int c2, uint32_t bar) {
  asm volatile(TMA_LD "3d" TMA_MB ".multicast::cluster [%0], [%1, {%3, %4, %5}], [%2], %6;"
               ::"r"(dst), "l"(tm), "r"(bar), "r"(c0), "r"(c1), "r"(c2), "h"((uint16_t)3) : "memory");
}
template <bool ONCE = false> __device__ __forceinline__ void bulk_g2s(uint32_t dst, const void* src, uint32_t bytes, uint32_t bar) {
  if (ONCE) asm volatile("cp.async.bulk" TMA_MB ".L2::cache_hint [%0], [%1], %2, [%3], %4;" ::"r"(dst), "l"(src), "r"(bytes), "r"(bar), "l"(EV_FIRST) : "memory");
  else asm volatile("cp.async.bulk" TMA_MB " [%0], [%1], %2, [%3];" ::"r"(dst), "l"(src), "r"(bytes), "r"(bar) : "memory");
}
__device__ __forceinline__ void tma2d_store(const CUtensorMap* tm, uint32_t src, int c0, int c1) {
  asm volatile("cp.async.bulk.tensor.2d.global.shared::cta.bulk_group [%0, {%2, %3}], [%1];" ::"l"(tm), "r"(src), "r"(c0), "r"(c1) : "memory");
}
__device__ __forceinline__ void prefetch_tm(const CUtensorMap* tm) { asm volatile("prefetch.tensormap [%0];" ::"l"(tm) : "memory"); }
__device__ __forceinline__ void wg_fence() { asm volatile("wgmma.fence.sync.aligned;" ::: "memory"); }
__device__ __forceinline__ void wg_commit() { asm volatile("wgmma.commit_group.sync.aligned;" ::: "memory"); }
template <int N> __device__ __forceinline__ void wg_wait() { asm volatile("wgmma.wait_group.sync.aligned %0;" ::"n"(N) : "memory"); }
__device__ __forceinline__ void bar_sync(int id, int n) { asm volatile("bar.sync %0, %1;" ::"r"(id), "r"(n) : "memory"); }
__device__ __forceinline__ void bar_arrive(int id, int n) { asm volatile("bar.arrive %0, %1;" ::"r"(id), "r"(n) : "memory"); }
__device__ __forceinline__ void fence_async_smem() { asm volatile("fence.proxy.async.shared::cta;" ::: "memory"); }
__device__ __forceinline__ void fence_async_all() { asm volatile("fence.proxy.async.global;" ::: "memory"); }
__device__ __forceinline__ uint32_t pack_bf16(float lo, float hi) { uint32_t r; asm("cvt.rn.bf16x2.f32 %0, %1, %2;" : "=r"(r) : "f"(hi), "f"(lo)); return r; }
__device__ __forceinline__ float ex2(float x) { float r; asm("ex2.approx.ftz.f32 %0, %1;" : "=f"(r) : "f"(x)); return r; }
__device__ __forceinline__ float rcp(float x) { float r; asm("rcp.approx.ftz.f32 %0, %1;" : "=f"(r) : "f"(x)); return r; }
__device__ __forceinline__ void flag_wait(const unsigned* f, unsigned target) {
  unsigned v;
  do { asm volatile("ld.acquire.gpu.global.u32 %0, [%1];" : "=r"(v) : "l"(f) : "memory"); } while (__any_sync(0xffffffffu, v < target));
}
__device__ __forceinline__ bool elect() {
  uint32_t r;
  asm volatile("{\n.reg .pred p;\nelect.sync _|p, -1;\nselp.u32 %0, 1, 0, p;\n}\n" : "=r"(r));
  return r;
}
__device__ __forceinline__ void fence_release() { asm volatile("fence.release.gpu;" ::: "memory"); }
__device__ __forceinline__ void flag_add(unsigned* f) { asm volatile("red.relaxed.gpu.global.inc.u32 [%0], 0x7fffffff;" ::"l"(f) : "memory"); }
__device__ __forceinline__ void cluster_arrive() { asm volatile("barrier.cluster.arrive.relaxed.aligned;" ::: "memory"); }
__device__ __forceinline__ void cluster_wait() { asm volatile("barrier.cluster.wait.aligned;" ::: "memory"); }
__device__ __forceinline__ uint32_t hmul2(uint32_t a, uint32_t b) { uint32_t r; asm("mul.rn.bf16x2 %0, %1, %2;" : "=r"(r) : "r"(a), "r"(b)); return r; }
__device__ __forceinline__ uint32_t hadd2(uint32_t a, uint32_t b) { uint32_t r; asm("add.rn.bf16x2 %0, %1, %2;" : "=r"(r) : "r"(a), "r"(b)); return r; }
__device__ __forceinline__ uint32_t hfma2(uint32_t a, uint32_t b, uint32_t c) { uint32_t r; asm("fma.rn.bf16x2 %0, %1, %2, %3;" : "=r"(r) : "r"(a), "r"(b), "r"(c)); return r; }
__device__ __forceinline__ uint32_t lds32(uint32_t a) { uint32_t r; asm volatile("ld.shared.b32 %0, [%1];" : "=r"(r) : "r"(a) : "memory"); return r; }
__device__ __forceinline__ uint4 lds128(uint32_t a) { uint4 r; asm volatile("ld.shared.v4.b32 {%0,%1,%2,%3}, [%4];" : "=r"(r.x), "=r"(r.y), "=r"(r.z), "=r"(r.w) : "r"(a) : "memory"); return r; }
__device__ __forceinline__ uint32_t desc_k(uint32_t addr) { return ((addr & 0x3FFFF) >> 4) | (1u << 16); }
template <int LBO> __device__ __forceinline__ uint32_t desc_mn(uint32_t addr) { return ((addr & 0x3FFFF) >> 4) | ((uint32_t)(LBO >> 4) << 16); }
#define DHI "0x40000040"

#define R8(d, o) "+f"(d[o]), "+f"(d[o + 1]), "+f"(d[o + 2]), "+f"(d[o + 3]), "+f"(d[o + 4]), "+f"(d[o + 5]), "+f"(d[o + 6]), "+f"(d[o + 7])
#define R32(d, o) R8(d, o), R8(d, o + 8), R8(d, o + 16), R8(d, o + 24)
#define R64(d, o) R32(d, o), R32(d, o + 32)
#define L64 "%0,%1,%2,%3,%4,%5,%6,%7,%8,%9,%10,%11,%12,%13,%14,%15,%16,%17,%18,%19,%20,%21,%22,%23,%24,%25,%26,%27,%28,%29,%30,%31," \
            "%32,%33,%34,%35,%36,%37,%38,%39,%40,%41,%42,%43,%44,%45,%46,%47,%48,%49,%50,%51,%52,%53,%54,%55,%56,%57,%58,%59,%60,%61,%62,%63"
#define L128 L64 ",%64,%65,%66,%67,%68,%69,%70,%71,%72,%73,%74,%75,%76,%77,%78,%79,%80,%81,%82,%83,%84,%85,%86,%87,%88,%89,%90,%91,%92,%93,%94,%95," \
            "%96,%97,%98,%99,%100,%101,%102,%103,%104,%105,%106,%107,%108,%109,%110,%111,%112,%113,%114,%115,%116,%117,%118,%119,%120,%121,%122,%123,%124,%125,%126,%127"

template <int TB> __device__ __forceinline__ void mma_ss_n128(float (&d)[64], uint32_t da, uint32_t db) {
  asm volatile("{\n.reg .b64 da, db;\nmov.b64 da, {%64, " DHI "};\nmov.b64 db, {%65, " DHI "};\n"
               "wgmma.mma_async.sync.aligned.m64n128k16.f32.bf16.bf16 {" L64 "}, da, db, 1, 1, 1, 0, %66;\n}\n"
               : R64(d, 0) : "r"(da), "r"(db), "n"(TB));
}
template <int TB> __device__ __forceinline__ void mma_rs_n128(float (&d)[64], uint32_t a0, uint32_t a1, uint32_t a2, uint32_t a3, uint32_t db, int sd) {
  asm volatile("{\n.reg .pred p;\n.reg .b64 db;\nsetp.ne.b32 p, %69, 0;\nmov.b64 db, {%68, " DHI "};\n"
               "wgmma.mma_async.sync.aligned.m64n128k16.f32.bf16.bf16 {" L64 "}, {%64,%65,%66,%67}, db, p, 1, 1, %70;\n}\n"
               : R64(d, 0) : "r"(a0), "r"(a1), "r"(a2), "r"(a3), "r"(db), "r"(sd), "n"(TB));
}
template <int TB> __device__ __forceinline__ void mma_ss_n256(float (&d)[128], uint32_t da, uint32_t db) {
  asm volatile("{\n.reg .b64 da, db;\nmov.b64 da, {%128, " DHI "};\nmov.b64 db, {%129, " DHI "};\n"
               "wgmma.mma_async.sync.aligned.m64n256k16.f32.bf16.bf16 {" L128 "}, da, db, 1, 1, 1, 0, %130;\n}\n"
               : R64(d, 0), R64(d, 64) : "r"(da), "r"(db), "n"(TB));
}
#define W8(d, o) "=f"(d[o]), "=f"(d[o + 1]), "=f"(d[o + 2]), "=f"(d[o + 3]), "=f"(d[o + 4]), "=f"(d[o + 5]), "=f"(d[o + 6]), "=f"(d[o + 7])
#define W32(d, o) W8(d, o), W8(d, o + 8), W8(d, o + 16), W8(d, o + 24)
#define W64(d, o) W32(d, o), W32(d, o + 32)
template <int TB> __device__ __forceinline__ void mma_ss_n128_init(float (&d)[64], uint32_t da, uint32_t db) {
  asm volatile("{\n.reg .b64 da, db;\nmov.b64 da, {%64, " DHI "};\nmov.b64 db, {%65, " DHI "};\n"
               "wgmma.mma_async.sync.aligned.m64n128k16.f32.bf16.bf16 {" L64 "}, da, db, 0, 1, 1, 0, %66;\n}\n"
               : W64(d, 0) : "r"(da), "r"(db), "n"(TB));
}
template <int TB> __device__ __forceinline__ void mma_ss_n256_init(float (&d)[128], uint32_t da, uint32_t db) {
  asm volatile("{\n.reg .b64 da, db;\nmov.b64 da, {%128, " DHI "};\nmov.b64 db, {%129, " DHI "};\n"
               "wgmma.mma_async.sync.aligned.m64n256k16.f32.bf16.bf16 {" L128 "}, da, db, 0, 1, 1, 0, %130;\n}\n"
               : W64(d, 0), W64(d, 64) : "r"(da), "r"(db), "n"(TB));
}
#define L32 "%0,%1,%2,%3,%4,%5,%6,%7,%8,%9,%10,%11,%12,%13,%14,%15,%16,%17,%18,%19,%20,%21,%22,%23,%24,%25,%26,%27,%28,%29,%30,%31"
__device__ __forceinline__ void mma_ss_n64(float (&d)[32], uint32_t da, uint32_t db) {
  asm volatile("{\n.reg .b64 da, db;\nmov.b64 da, {%32, " DHI "};\nmov.b64 db, {%33, " DHI "};\n"
               "wgmma.mma_async.sync.aligned.m64n64k16.f32.bf16.bf16 {" L32 "}, da, db, 1, 1, 1, 0, 0;\n}\n"
               : R32(d, 0) : "r"(da), "r"(db));
}
__device__ __forceinline__ void mma_ss_n64_init(float (&d)[32], uint32_t da, uint32_t db) {
  asm volatile("{\n.reg .b64 da, db;\nmov.b64 da, {%32, " DHI "};\nmov.b64 db, {%33, " DHI "};\n"
               "wgmma.mma_async.sync.aligned.m64n64k16.f32.bf16.bf16 {" L32 "}, da, db, 0, 1, 1, 0, 0;\n}\n"
               : W32(d, 0) : "r"(da), "r"(db));
}
#define L16 "%0,%1,%2,%3,%4,%5,%6,%7,%8,%9,%10,%11,%12,%13,%14,%15"
template <int O, bool INIT> __device__ __forceinline__ void mma_rs_n32(float (&d)[128], uint32_t a0, uint32_t a1, uint32_t a2, uint32_t a3, uint32_t db) {
  if (INIT) asm volatile("{\n.reg .b64 db;\nmov.b64 db, {%20, 0x00000008};\n"
               "wgmma.mma_async.sync.aligned.m64n32k16.f32.bf16.bf16 {" L16 "}, {%16,%17,%18,%19}, db, 0, 1, 1, 0;\n}\n"
               : W8(d, O), W8(d, O + 8) : "r"(a0), "r"(a1), "r"(a2), "r"(a3), "r"(db));
  else asm volatile("{\n.reg .b64 db;\nmov.b64 db, {%20, 0x00000008};\n"
               "wgmma.mma_async.sync.aligned.m64n32k16.f32.bf16.bf16 {" L16 "}, {%16,%17,%18,%19}, db, 1, 1, 1, 0;\n}\n"
               : R8(d, O), R8(d, O + 8) : "r"(a0), "r"(a1), "r"(a2), "r"(a3), "r"(db));
}
template <int O, bool INIT> __device__ __forceinline__ void mma_rs_n64(float (&d)[128], uint32_t a0, uint32_t a1, uint32_t a2, uint32_t a3, uint32_t db) {
  if (INIT) asm volatile("{\n.reg .b64 db;\nmov.b64 db, {%36, 0x00000008};\n"
               "wgmma.mma_async.sync.aligned.m64n64k16.f32.bf16.bf16 {" L32 "}, {%32,%33,%34,%35}, db, 0, 1, 1, 0;\n}\n"
               : W32(d, O) : "r"(a0), "r"(a1), "r"(a2), "r"(a3), "r"(db));
  else asm volatile("{\n.reg .b64 db;\nmov.b64 db, {%36, 0x00000008};\n"
               "wgmma.mma_async.sync.aligned.m64n64k16.f32.bf16.bf16 {" L32 "}, {%32,%33,%34,%35}, db, 1, 1, 1, 0;\n}\n"
               : R32(d, O) : "r"(a0), "r"(a1), "r"(a2), "r"(a3), "r"(db));
}
template <int S, int J> __device__ __forceinline__ void conv_step(float (&d)[128], const uint32_t (&a)[64], uint32_t db) {
  if constexpr (J >= 0 && J >= (S >> 1)) {
    if constexpr (J >= 8 - 2 * CWIDE) {
      mma_rs_n64<16 * (J - 1), S == 0>(d, a[4 * S], a[4 * S + 1], a[4 * S + 2], a[4 * S + 3], db + (uint32_t)((2 * (J - 1) - S) * 16));
      conv_step<S, J - 2>(d, a, db);
    } else {
      mma_rs_n32<16 * J, S == 0>(d, a[4 * S], a[4 * S + 1], a[4 * S + 2], a[4 * S + 3], db + (uint32_t)((2 * J - S) * 16));
      conv_step<S, J - 1>(d, a, db);
    }
  }
}
__device__ __forceinline__ void mma_ss_n8(float (&d)[4], uint32_t da, uint32_t db) {
  asm volatile("{\n.reg .b64 da, db;\nmov.b64 da, {%4, " DHI "};\nmov.b64 db, {%5, 0x00000008};\n"
               "wgmma.mma_async.sync.aligned.m64n8k16.f32.bf16.bf16 {%0,%1,%2,%3}, da, db, 1, 1, 1, 0, 0;\n}\n"
               : "+f"(d[0]), "+f"(d[1]), "+f"(d[2]), "+f"(d[3]) : "r"(da), "r"(db));
}
template <int N> __device__ __forceinline__ void reg_fence(float (&d)[N]) {
#pragma unroll
  for (int i = 0; i < N; i++) asm volatile("" : "+f"(d[i])::"memory");
}
template <int N> __device__ __forceinline__ void reg_fence(uint32_t (&d)[N]) {
#pragma unroll
  for (int i = 0; i < N; i++) asm volatile("" : "+r"(d[i])::"memory");
}

struct __align__(64) Params {
  unsigned* flags;
  int zero;
  uint8_t pref[128];
  const __nv_bfloat16 *gate_w, *ak, *av, *shk, *ssk, *ssd, *wop;
  CUtensorMap x, c, wq, wuk, wuv, wo, x3, y3, out, w;
};

template <int O, int N, int M> __device__ __forceinline__ void pack_frag(const float (&acc)[N], uint32_t (&pk)[M]) {
#pragma unroll
  for (int i = 0; i < 32; i++) pk[i] = pack_bf16(acc[O + 2 * i], acc[O + 2 * i + 1]);
}
template <int N> __device__ __forceinline__ void pack_frag_scaled(const float (&acc)[N], uint32_t (&pk)[32], float s0, float s1) {
#pragma unroll
  for (int i = 0; i < 32; i++) { const float s = (i & 1) ? s1 : s0; pk[i] = pack_bf16(acc[2 * i] * s, acc[2 * i + 1] * s); }
}
template <int J0 = 0, int J1 = 8, int M> __device__ __forceinline__ void stsm_frag(const uint32_t (&pk)[M], uint32_t a) {
#pragma unroll
  for (int jj = J0; jj < J1; jj++)
    asm volatile("stmatrix.sync.aligned.m8n8.x4.shared.b16 [%0], {%1,%2,%3,%4};" ::"r"((a ^ ((jj & 3) << 5)) + (jj >> 2) * 16384),
                 "r"(pk[4 * jj]), "r"(pk[4 * jj + 1]), "r"(pk[4 * jj + 2]), "r"(pk[4 * jj + 3]) : "memory");
}

struct Cons {
  uint32_t sb;
  uint32_t pf;
  int wg, tid;
  __device__ __forceinline__ void wait_full(int g) { mbar_wait(sb + SM_BAR + (B_FULL + g) * 8, (pf >> g) & 1); pf ^= 1u << g; }
  uint32_t relb;
  __device__ __forceinline__ void release(int g, int n) {
    if (tid < 2 * n) asm volatile("mbarrier.arrive.shared::cluster.b64 _, [%0];" ::"r"(relb + g * 8) : "memory");
  }
  __device__ __forceinline__ void turn_begin() { bar_sync(1 + wg, 256); }
  __device__ __forceinline__ void turn_end() { bar_arrive(2 - wg, 256); }
  __device__ __forceinline__ void staged(int e) { __syncwarp(); if ((tid & 31) == 0) mbar_arrive(sb + SM_BAR + (B_EV + 2 * e + wg) * 8); }
  int zero;
  int rnd;
  uint32_t pfree;
  __device__ __forceinline__ void wait_stage_free() { mbar_wait(sb + SM_BAR + (B_FREE + wg) * 8, pfree); pfree ^= 1; }
  __device__ __forceinline__ bool try_full(int g) { return mbar_test(sb + SM_BAR + (B_FULL + g) * 8, (pf >> g) & 1); }
};

constexpr float SM_C = 0.08838834764831845f * 1.4426950408889634f;
struct SoftState { float m0, m1, l0, l1; int shifted; };
__device__ __forceinline__ void ex2_rot(float& t, float s, uint32_t never_zero) {
  asm("{\n.reg .pred p;\nsetp.ne.u32 p, %2, 0;\n@p ex2.approx.ftz.f32 %0, %1;\n}\n" : "+f"(t) : "f"(s), "r"(never_zero));
}
__device__ __forceinline__ void pin(float a, uint32_t never_zero) {
  asm volatile("{\n.reg .pred p;\nsetp.eq.u32 p, %1, 0;\n@p st.shared.f32 [%1], %0;\n}\n" ::"f"(a), "r"(never_zero) : "memory");
}
template <int O, int N> __device__ __forceinline__ void reg_fence_part(uint32_t (&d)[32]) {
#pragma unroll
  for (int i = O; i < O + N; i++) asm volatile("" : "+r"(d[i])::"memory");
}
template <int Q, int W, int N> __device__ __forceinline__ void exp_quarter(const float (&S)[N], uint32_t (&P)[32], float (&t)[ROT], float& s0, float& s1, uint32_t nz) {
#pragma unroll
  for (int i = 8 * Q; i < 8 * Q + 8; i++) {
    float& a = t[(2 * i) % ROT];
    float& b = t[(2 * i + 1) % ROT];
    if (2 * i < ROT) { a = ex2(S[2 * i]); b = ex2(S[2 * i + 1]); }
    else { ex2_rot(a, S[2 * i], nz); ex2_rot(b, S[2 * i + 1], nz); }
    if (i < 2) { if (i) s1 = a + b; else s0 = a + b; }
    else if (SUMV == 0) { if (i & 1) { s1 += a; s1 += b; } else { s0 += a; s0 += b; } }
    else { if (i & 1) s1 += a + b; else s0 += a + b; }
    if (i == 8 * Q) { pin(EXPV == 1 && Q ? s1 : s0, nz); wg_wait<W>(); reg_fence_part<8 * Q, 8>(P); }
    P[i] = pack_bf16(a, b);
  }
}
template <int N> __device__ __forceinline__ void shift_scores(float (&S)[N], float d0, float d1) {
#pragma unroll
  for (int i = 0; i < N; i++) S[i] -= (i & 2) ? d1 : d0;
}
__device__ __forceinline__ bool soft_high(float s0, float s1, float lim = SM_LIMIT) { return s0 > lim || s1 > lim; }
__device__ __forceinline__ bool soft_unsafe(float s0, float s1, bool first) {
  uint32_t b0 = __ballot_sync(0xffffffffu, s0 >= SM_LOW), b1 = __ballot_sync(0xffffffffu, s1 >= SM_LOW);
  b0 |= b0 >> 1; b0 |= b0 >> 2; b1 |= b1 >> 1; b1 |= b1 >> 2;
  return __any_sync(0xffffffffu, soft_high(s0, s1)) || (first && (b0 & b1 & 0x11111111u) != 0x11111111u);
}
template <int N> __device__ __forceinline__ void soft_fix(const float (&S)[N], float (&O)[64], SoftState& z, bool first, float& d0, float& d1) {
  d0 = d1 = first ? -INFINITY : 0.f;
#pragma unroll
  for (int j = 0; j < N / 4; j++) { d0 = fmaxf(d0, fmaxf(S[4 * j], S[4 * j + 1])); d1 = fmaxf(d1, fmaxf(S[4 * j + 2], S[4 * j + 3])); }
  d0 = fmaxf(d0, __shfl_xor_sync(0xffffffffu, d0, 1)); d1 = fmaxf(d1, __shfl_xor_sync(0xffffffffu, d1, 1));
  d0 = fmaxf(d0, __shfl_xor_sync(0xffffffffu, d0, 2)); d1 = fmaxf(d1, __shfl_xor_sync(0xffffffffu, d1, 2));
  const float sc0 = ex2(-fmaxf(d0, 0.f)), sc1 = ex2(-fmaxf(d1, 0.f));
  z.m0 += d0; z.m1 += d1; z.l0 *= sc0; z.l1 *= sc1; z.shifted = 1;
#pragma unroll
  for (int j = 0; j < 16; j++) { O[4 * j] *= sc0; O[4 * j + 1] *= sc0; O[4 * j + 2] *= sc1; O[4 * j + 3] *= sc1; }
}
template <int M> __device__ __forceinline__ void pin32(const uint32_t (&v)[M], uint32_t never_zero) {
#pragma unroll
  for (int i = 0; i < 32; i += 4)
    asm volatile("{\n.reg .pred p;\nsetp.eq.u32 p, %4, 0;\n@p st.shared.v4.b32 [%4], {%0,%1,%2,%3};\n}\n" ::"r"(v[i]), "r"(v[i + 1]), "r"(v[i + 2]), "r"(v[i + 3]), "r"(never_zero) : "memory");
}
template <int N> __device__ __forceinline__ void mask_diag(float (&S)[N], float nd) {
  asm volatile("" : "+f"(nd));
#pragma unroll
  for (int i = 0; i < 32; i++) {
    const float beyond = __saturatef(nd + (float)(8 * (i >> 2) + (i & 1) - 4 * (i & 2)));
    S[N - 32 + i] = fmaf(beyond, -3.0e38f, S[N - 32 + i]);
  }
}
__device__ __forceinline__ float quad_sum(float v) {
  v += __shfl_xor_sync(0xffffffffu, v, 1);
  v += __shfl_xor_sync(0xffffffffu, v, 2);
  return v;
}
__device__ __forceinline__ void issue_qk(float (&S)[64], uint32_t dq, uint32_t dk) {
  mma_ss_n128_init<0>(S, dq, dk);
#pragma unroll
  for (int s = 1; s < 8; s++) mma_ss_n128<0>(S, dq + (s >> 2) * 1024 + (s & 3) * 2, dk + (s >> 2) * 1024 + (s & 3) * 2);
}
__device__ __forceinline__ void issue_qk(float (&S)[32], uint32_t dq, uint32_t dk) {
  mma_ss_n64_init(S, dq, dk);
#pragma unroll
  for (int s = 1; s < 8; s++) mma_ss_n64(S, dq + (s >> 2) * 1024 + (s & 3) * 2, dk + (s >> 2) * 1024 + (s & 3) * 2);
}
template <int H> __device__ __forceinline__ void issue_pv(float (&O)[64], const uint32_t (&P)[32], uint32_t dv, int acc, bool on) {
  if (on) {
#pragma unroll
    for (int s = 4 * H; s < 4 * H + 4; s++) {
      mma_rs_n128<1>(O, P[4 * s], P[4 * s + 1], P[4 * s + 2], P[4 * s + 3], dv + s * 128, s != 0 ? 1 : acc);
      if (s & 1) wg_commit();
    }
  } else { wg_commit(); wg_commit(); }
}
constexpr uint32_t DG = GR >> 4;
__device__ __forceinline__ void stage_q2(Cons& c, const float (&O)[64], uint32_t (&P)[32], uint32_t stg) {
  wg_commit(); wg_commit(); wg_commit(); wg_commit();
  c.turn_end();
  pack_frag<0>(O, P);
  stsm_frag(P, stg);
  fence_async_smem();
}
__device__ __forceinline__ void attn_half(Cons& c, float (&O)[64], uint32_t (&P)[32], SoftState& z, uint32_t dk0, uint32_t dkk, uint32_t dv0, float dmask, int last) {
  float S[32];
  FTH(8 + last * 32, 0);
  c.turn_begin();
  FTH(9 + last * 32, 0);
  wg_fence();
  issue_qk(S, dk0 + (last ? 0 : 2 * DG), dkk + (last ? 8 : 4) * DG);
  wg_commit();
  issue_pv<0>(O, P, dv0 + 10 * DG, 1, last);
  issue_pv<1>(O, P, dv0 + 10 * DG, 1, last);
  c.turn_end();
  c.wait_full(last ? 12 : 6);
  FTH(10 + last * 32, 0);
  wg_wait<4>();
  reg_fence(S);
  FTH(11 + last * 32, 0);
  c.release(last ? 8 : 4, 2);
  mask_diag(S, dmask);
  float s0, s1, d0 = z.m0, d1 = z.m1;
#pragma unroll 1
  for (int pass = 0;; pass++) {
    if (z.shifted) shift_scores(S, d0, d1);
    float tr[ROT];
    exp_quarter<0, 3>(S, P, tr, s0, s1, c.sb);
    exp_quarter<1, 2>(S, P, tr, s0, s1, c.sb);
    pin(s1, c.sb); wg_wait<0>(); reg_fence_part<16, 16>(P); reg_fence(O);
    if (!soft_unsafe(s0, s1, !last) || pass) break;
    soft_fix(S, O, z, !last, d0, d1);
  }
  FTH(12 + last * 32, 0);
  z.l0 += s0; z.l1 += s1;
  c.release(10, last ? 2 : 0);
  if (!last) c.wait_full(8);
  FTH(13 + last * 32, 0);
}

template <int V> struct IC { static constexpr int value = V; };
__device__ __forceinline__ int conv_next(int g, bool spare) { return g >= NGR - 2 ? g - (NGR - 4) : !spare && g == 4 ? 1 : g + 2; }
__device__ __forceinline__ void conv_final(uint32_t rb, uint32_t yb, bool on) {
  const uint4 q0 = lds128(rb), q1 = lds128(rb + 4096), q2 = lds128(rb + 8192), q3 = lds128(rb + 12288);
  auto fin = [&](uint32_t x0, uint32_t x1, uint32_t x2, uint32_t x3) { return hadd2(hadd2(x0, x1), hadd2(x2, x3)); };
  asm volatile("{\n.reg .pred p;\nsetp.ne.b32 p, %5, 0;\n@p st.shared.v4.b32 [%0], {%1,%2,%3,%4};\n}\n" ::"r"(yb), "r"(fin(q0.x, q1.x, q2.x, q3.x)),
               "r"(fin(q0.y, q1.y, q2.y, q3.y)), "r"(fin(q0.z, q1.z, q2.z, q3.z)), "r"(fin(q0.w, q1.w, q2.w, q3.w)), "r"((int)on) : "memory");
}
__device__ __forceinline__ void conv_tasks(Cons& c, const Params& p, int ntask, bool spare, int ch, int chstep, uint32_t dd, uint32_t dkk, int w, int lane) {
  const uint32_t sb = c.sb;
  int g = 2 + c.wg;
  uint32_t rb = sb + g * GR;
  const uint32_t yb = sb + c.wg * 8192 + c.tid * 16;
  const int gt = 8 * w + (lane >> 2) + (lane & 3);
  uint32_t a[64], hb;
  auto lda = [&](int s) {
    a[4 * s] = lds32(hb + s * 256); a[4 * s + 1] = lds32(hb + s * 256 + 128);
    a[4 * s + 2] = lds32(hb + s * 256 + 16); a[4 * s + 3] = lds32(hb + s * 256 + 144);
  };
  auto first_a = [&]() {
    hb = sb + g * GR + WBYTES - 28 + gt * 4;
    lda(0); lda(15);
  };
  c.wait_full(g);
  first_a();
#pragma unroll 1
  for (int i = 0; i < ntask; i++) {
    const uint32_t base = sb + g * GR;
    FTC(0);
    lda(1); lda(14);
    a[0] = hadd2(a[0], gt == 7 ? dd : 0u); a[2] = hadd2(a[2], gt == 3 ? dd : 0u);
    float acc[128];
    const uint32_t db = dkk + ((WPL / 16 - 1) << 16) + g * DG + WZ / 16;
    FTC(2);
    c.turn_begin();
    FTC(3);
    auto pair = [&](auto kc) {
      constexpr int k = decltype(kc)::value;
      if (k < 7) wg_fence();
      if (k == 7) c.turn_end();
      conv_step<k, 7>(acc, a, db);
      conv_step<15 - k, 7>(acc, a, db);
      if (k < 6) { lda(k + 2); lda(13 - k); }
      if (k == 0) conv_final(rb, yb, i > 0);
      if (k == 1) {
        conv_final(rb + 2048, yb + 2048, i > 0);
        __syncwarp();
        if (lane == 0 && i > 0) mbar_arrive(sb + SM_BAR + (B_EV + c.wg) * 8);
      }
      if (k == 6) dd = __bfloat16_as_ushort(p.ssd[(ch + chstep) & (DM - 1)]);
    };
    pair(IC<0>()); pair(IC<1>()); pair(IC<2>()); pair(IC<3>()); pair(IC<4>()); pair(IC<5>()); pair(IC<6>()); pair(IC<7>());
    wg_commit();
    FTC(4);
    g = conv_next(g, spare);
    ch += chstep;
    rb = base + c.tid * 16;
    if (i + 1 < ntask) c.wait_full(g);
    wg_wait<0>();
    reg_fence(acc);
    reg_fence(a);
    bar_sync(3 + c.wg, 128);
    FTC(5);
    first_a();
    const int tw = (lane & 3) + w;
    const uint32_t xb = base + w * 4096 + tw * 32 + (lane >> 2) * 4;
#pragma unroll
    for (int j = 0; j < 32; j++) {
      float v0 = acc[4 * j], v1 = acc[4 * j + 1];
      if (j > 0) { v0 += acc[j > 0 ? 4 * j - 2 : 0]; v1 += acc[j > 0 ? 4 * j - 1 : 0]; }
      uint32_t v = pack_bf16(v0, v1), ad = xb + j * 128;
      if (j == 31 && tw >= 4) { v = 0; ad -= 4096; }
      asm volatile("st.shared.b32 [%0], %1;" ::"r"(ad), "r"(v) : "memory");
    }
    c.wait_stage_free();
    FTC(6);
  }
  bar_sync(3 + c.wg, 128);
  conv_final(rb, yb, true);
  conv_final(rb + 2048, yb + 2048, true);
  c.staged(0);
}

__global__ void __cluster_dims__(2, 1, 1) __launch_bounds__(NTHREADS, 1) mega_kernel(const __grid_constant__ Params p) {
  extern __shared__ __align__(1024) uint8_t smem_raw[];
  FTS(0);
  const uint32_t sb = smem_u32(smem_raw);
  if (threadIdx.x - 64 < 32) { prefetch_tm(&p.c); prefetch_tm(&p.wuk + (blockIdx.x & 1)); }
  const int wgi = __shfl_sync(0xffffffffu, threadIdx.x >> 7, 0);
  const int warp = __shfl_sync(0xffffffffu, threadIdx.x >> 5, 0);
  const uint32_t rank = blockIdx.x & 1;
  int slot;
  {
    uint32_t smid; asm volatile("mov.u32 %0, %smid;" : "=r"(smid));
    slot = p.pref[((smid >> 1) + (threadIdx.x & (smid >> 16))) & 127];
  }
  if (warp >= 3) {
    if (elect()) {
#pragma unroll
      for (int k = 0; k < 4; k++) mbar_init(sb + SM_BAR + ((warp - 3) * 4 + k) * 8, k == 1 && warp == 7 ? 11 : warp < (k ? 7 : 8) ? 1 : 4);
      if (warp == 7) mbar_expect_tx(sb + SM_BAR + B_SLOT * 8, 8);
      asm volatile("fence.mbarrier_init.release.cluster;" ::: "memory");
    }
    __syncwarp();
  }
  FTS(1);
  cluster_arrive();
  slot = __shfl_sync(0xffffffffu, slot, 0);
  const int pref = slot;
  if (warp < 4) {
    asm volatile("setmaxnreg.dec.sync.aligned.u32 40;");
    if (warp == 1 + 4 * rank) {
      unsigned taken = threadIdx.x == 32;
#pragma unroll 1
      for (int n = 0; n < NSLOT; n++) {
        asm volatile("{\n.reg .pred p;\nsetp.ne.b32 p, %0, 0;\n@p atom.relaxed.gpu.global.exch.b32 %0, [%1], 1;\n}\n" : "+r"(taken) : "l"(CLAIMP(slot)) : "memory");
        if (!__any_sync(0xffffffffu, taken)) break;
        slot = slot == NSLOT - 1 ? 0 : slot + 1;
      }
    }
    cluster_wait();
    if (threadIdx.x == 32) {
#pragma unroll
      for (int r = 0; r < 2; r++)
        asm volatile("{\n.reg .b32 a, b;\nmapa.shared::cluster.u32 a, %0, %1;\nadd.u32 b, a, %3;\nst.async.shared::cluster.mbarrier::complete_tx::bytes.u32 [b], %2, [a];\n}\n"
                     ::"r"(sb + SM_BAR + B_SLOT * 8), "r"(r), "r"(slot | pref << 8), "r"((V_SLOT - B_SLOT) * 8 + rank * 4) : "memory");
    }
    if (warp == 2) {
#pragma unroll 1
      for (int kk = 0; kk < 4; kk++) {
        const int g0 = 2 + 3 * kk;
        const uint32_t fb = sb + SM_BAR + (B_FULL + g0) * 8;
        if (elect()) {
          FTSW(kk);
          mbar_expect_tx(fb, 3 * GR);
          tma2d(sb + g0 * GR, &p.c, kk * 64, (KV_ROW(pref & 7, 0) + rank) * 128, fb);
          tma3d_mc(sb + (g0 + 1 + rank) * GR, rank ? &p.wuv : &p.wuk, 0, kk * 64, ((pref & 56) >> 1) + 2 * KV_HEAD(pref & 7, 0), fb);
        }
        if (kk < 3) {
          uint32_t c0, c1;
          asm volatile("mov.u32 %0, %clock;" : "=r"(c0));
          do asm volatile("mov.u32 %0, %clock;" : "=r"(c1)); while (c1 - c0 < (kk ? X_D2 : X_DELAY));
        }
      }
      FTSW(4);
      prefetch_tm(&p.x); prefetch_tm(&p.wq);
    }
  }
  int grp, idx, lb;
  int cn, cch, cstep;
  bool spare, redo;
  auto get_slot = [&]() {
    mbar_wait(sb + SM_BAR + B_SLOT * 8, 0);
    const uint32_t sv0 = __shfl_sync(0xffffffffu, lds32(sb + SM_BAR + V_SLOT * 8), 0), sv1 = __shfl_sync(0xffffffffu, lds32(sb + SM_BAR + V_SLOT * 8 + 4), 0);
    grp = (sv0 & 255) >> 3; idx = sv0 & 7; lb = (sv0 & 255) * 2 + rank;
    spare = grp == 8; redo = spare || sv0 != sv1;
    cn = spare ? CN_SPARE : CN_MAIN; cch = spare ? lb - NMAIN : 4 * CN_SPARE + CN_MAIN * lb; cstep = spare ? 4 : 1;
    if (FINE_MODE != 7) TS(0);
  };

  if (wgi == 0) {
    asm volatile("setmaxnreg.dec.sync.aligned.u32 40;");
    const int lane = threadIdx.x & 31;
    cluster_arrive();
    get_slot();
    uint32_t pe = 0;
    auto acquire = [&](int g, int n, uint32_t m) {
      int i = g;
#pragma unroll 1
      do mbar_wait1(sb + SM_BAR + (B_EMPTY + i) * 8, (pe >> i) & 1); while (++i < g + n);
      pe ^= m << g;
    };
    if (warp == 3) {
      if (!spare) {
        const int s0 = lb * 16;
#pragma unroll 1
        for (int cg = 0; cg < 16; cg++) {
          if (cg == 3 || cg == 10) {
#pragma unroll 1
            for (int n = 0; n < 20 && !__any_sync(0xffffffffu, mbar_try(sb + SM_BAR + B_SLOT * 8, cg == 3)); n++);
          } else if (cg < 3) __nanosleep(800);
          const int ch = cg * 64 + 2 * lane;
          const uint32_t* kp = reinterpret_cast<const uint32_t*>(p.ak + (size_t)s0 * DM + ch);
          const uint32_t* vp = reinterpret_cast<const uint32_t*>(p.av + (size_t)s0 * DM + ch);
          const uint4 sw = __ldg(reinterpret_cast<const uint4*>(p.shk + ch * 4));
          uint32_t k3 = 0, k2 = 0, k1 = 0, k0 = 0, up = 0;
          if (lb > 0) { k3 = ldg_stream(kp - 4 * 512); k2 = ldg_stream(kp - 3 * 512); k1 = ldg_stream(kp - 2 * 512); k0 = ldg_stream(kp - 512); up = ldg_stream(vp - 512); }
          const uint32_t w0 = __byte_perm(sw.x, sw.z, 0x5410), w1 = __byte_perm(sw.x, sw.z, 0x7632);
          const uint32_t w2 = __byte_perm(sw.y, sw.w, 0x5410), w3 = __byte_perm(sw.y, sw.w, 0x7632);
          up = hmul2(hfma2(k0, w0, hfma2(k1, w1, hfma2(k2, w2, hmul2(k3, w3)))), up);
#pragma unroll 1
          for (int hb = 0; hb < 2; hb++) {
            uint32_t kk[8], u[8];
#pragma unroll
            for (int r = 0; r < 8; r++) { kk[r] = ldg_stream(kp + r * 512); u[r] = ldg_stream(vp + r * 512); }
#pragma unroll
            for (int r = 0; r < 8; r++) {
              k3 = k2; k2 = k1; k1 = k0; k0 = kk[r];
              u[r] = hmul2(hfma2(k0, w0, hfma2(k1, w1, hfma2(k2, w2, hmul2(k3, w3)))), u[r]);
            }
            if (lane == 0) asm volatile("cp.async.bulk.wait_group.read 0;" ::: "memory");
            __syncwarp();
            const uint32_t dst = sb + SM_UST + lane * 32 + ((lane & 4) << 2);
#pragma unroll
            for (int cc = 0; cc < 2; cc++) {
              const uint32_t sel = cc ? 0x7632 : 0x5410;
              asm volatile("st.shared.v4.b32 [%0], {%1,%2,%3,%4};" ::"r"(dst + cc * 1024), "r"(__byte_perm(u[6], u[5], sel)), "r"(__byte_perm(u[4], u[3], sel)),
                           "r"(__byte_perm(u[2], u[1], sel)), "r"(__byte_perm(u[0], up, sel)) : "memory");
              asm volatile("st.shared.v4.b32 [%0], {%1,%2,%3,%4};" ::"r"((dst ^ 16) + cc * 1024), "r"(__byte_perm(u[7], u[6], sel)), "r"(__byte_perm(u[5], u[4], sel)),
                           "r"(__byte_perm(u[3], u[2], sel)), "r"(__byte_perm(u[1], u[0], sel)) : "memory");
            }
            fence_async_smem();
            __syncwarp();
            if (lane == 0) {
              asm volatile("cp.async.bulk.tensor.3d.global.shared::cta.bulk_group [%0, {%2, %3, %4}], [%1];\ncp.async.bulk.commit_group;"
                           ::"l"(&p.w), "r"(sb + SM_UST), "r"(WZ / 2 + lb * 16 + (hb ^ 1) * (WPL / 2)), "r"(cg * 32), "r"(0) : "memory");
            }
            up = u[7];
            kp += 8 * 512; vp += 8 * 512;
          }
          if ((cg & (cg + 1)) == 0 && lane == 0) {
            asm volatile("cp.async.bulk.wait_group 0;" ::: "memory");
            fence_release();
            flag_add(FLAG(F_U + 32 - __clz(cg)));
          }
          TSW(10 + cg);
        }
        prefetch_tm(&p.wo); prefetch_tm(&p.x3); prefetch_tm(&p.y3); prefetch_tm(&p.out);
        if (P3PF) {
          const int rt = 2 * grp + rank;
          unsigned v;
          asm volatile("ld.acquire.gpu.global.u32 %0, [%1];" : "=r"(v) : "l"(FLAG(F_CTX + rt * 2)) : "memory");
#pragma unroll 1
          for (int kb = P3PF0; kb < P3PF0 + P3PF; kb++) {
            const uint8_t* a = lane < 16 ? g_cimg + (unsigned)((rt * 64 + kb) * GR + (idx * 16 + lane) * 128) : (const uint8_t*)p.wop + (unsigned)(kb * 64 * DM * 2 + (lb * 8 + (lane & 7)) * 128);
            if (lane < 24 && v == 32) asm volatile("prefetch.global.L2 [%0];" ::"l"(a));
          }
        }
      } else {
#pragma unroll 1
        for (int i = 0, g = 2; i < 32; i++) {
          acquire(g, 2, 3);
          if (elect()) {
            const uint32_t fb = sb + SM_BAR + (B_FULL + g) * 8;
            if (i == 0) { mbar_expect_tx(fb - 8, 2048); bulk_g2s(sb + GR, p.gate_w, 2048, fb - 8); }
            mbar_expect_tx(fb, 2 * GR);
            tma3d(sb + g * GR, &p.x3, 0, (lb - NMAIN) * 512 + (i >> 3) * 128, (i & 7) * 2, fb);
          }
          g = g == NGR - 2 ? 2 : g + 2;
        }
        bar_arrive(5, 64);
      }
      unsigned long long t0, t1;
      asm volatile("mov.u64 %0, %globaltimer;" : "=l"(t0));
      auto check = [&]() {
        asm volatile("mov.u64 %0, %globaltimer;" : "=l"(t1));
        if (t1 - t0 > 2000000000ull) __trap();
      };
      if (!spare) {
        unsigned v;
        do {
          __nanosleep(1000);
          check();
          asm volatile("ld.acquire.gpu.global.u32 %0, [%1];" : "=r"(v) : "l"(FLAG(lane & 1 ? F_Y + idx : F_GATE)) : "memory");
        } while (__any_sync(0xffffffffu, v < (lane & 1 ? 128 : 32)));
        __syncwarp();
        if (lane == 0) mbar_arrive(sb + SM_BAR + B_SLOT * 8);
      }
      if (lane == 0) {
        while (!mbar_try(sb + SM_BAR + B_DONE * 8, 0)) check();
      }
    } else if (warp != 0) {
      const int w = warp - 1, ne = 12 + (cn + 1 - w) / 2;
      uint32_t p0 = 0;
      int cg = 2 + w, ch = cch + w * cstep;
#pragma unroll 1
      for (int e = spare ? 12 : 0; e < ne; e++) {
        const int rnd = e >= 6, k = e - 6 * rnd, rt = k == 4 ? idx : 15 - idx;
        uint8_t* dst = k < 4 ? g_kv + (size_t)(((k & 1) * 16 + 2 * grp + KV_HEAD(idx, k >> 1)) * 16 + KV_ROW(idx, k >> 1) + rank) * 32768 + w * 8192
                     : k < 6 ? g_cimg + (size_t)(rt * 32 + 16 * rnd + 2 * grp + rank) * 32768 + (w ^ (k & 1)) * 8192
                             : reinterpret_cast<uint8_t*>(g_yT + (size_t)ch * SEQ);
        const uint32_t src = sb + w * 8192 + (k == 4 ? 2 * GR : 0);
        if (e == 6) flag_wait(FLAG(F_AD + grp), 32);
        mbar_wait1(sb + SM_BAR + (B_EV + (k == 4 ? 2 : 0) + w) * 8, k == 4 ? rnd : p0);
        if (k != 4) p0 ^= 1;
        if (lane < 4 && k >= 6 && (!spare || e < ne - 6)) mbar_arrive_cluster(sb + SM_BAR + (B_EMPTY + cg) * 8, lane & 1);
        fence_async_smem();
        if (elect()) {
          const uint32_t cs = k >= 6 ? 4096 : 1024;
#pragma unroll 1
          for (uint32_t i = 0; i < (k >= 6 ? 4096 : 16384); i += cs) {
            const uint32_t o = i + (i & 8192);
            asm volatile("cp.async.bulk.global.shared::cta.bulk_group [%0], [%1], %2;" ::"l"(dst + o), "r"(src + o), "r"(cs) : "memory");
            asm volatile("cp.async.bulk.commit_group;\ncp.async.bulk.wait_group.read 1;" ::: "memory");
          }
          asm volatile("cp.async.bulk.wait_group 0;" ::: "memory");
          if (k != 4) mbar_arrive(sb + SM_BAR + (B_FREE + w) * 8);
        }
        __syncwarp();
        if (lane < (k == 4 ? 4 : e == 11 || (e == ne - 1 && !spare) ? 2 : 0))
          mbar_arrive_cluster(sb + SM_BAR + (B_EMPTY + (k == 4 ? 2 : e == 11) + (lane >> 1)) * 8, lane & 1);
        if (k >= 3) {
          fence_release();
          const unsigned fl = k == 3 ? F_KV + rnd * 8 + grp : k < 6 ? F_CTX + rt * 2 + rnd : F_Y + ((unsigned)ch >> 7);
          if (lane <= (e == 5)) flag_add(FLAG(lane ? F_AD + grp : fl));
        }
        if (k >= 6) { cg = conv_next(cg, spare); ch += 2 * cstep; }
      }
      if (lane == 0) mbar_arrive(sb + SM_BAR + B_DONE * 8);
    } else {
#pragma unroll 1
      for (int rnd = 0; rnd < (spare ? 0 : 2); rnd++) {
        const int hp = 16 * rnd + 2 * grp, head = hp + rank;
#pragma unroll 1
        for (int kk = rnd || redo ? 0 : 4; kk < 32; kk++) {
          const int g0 = 2 + 3 * (kk & 3);
          acquire(g0, kk < 4 ? 3 : 1, 7);
          if (elect()) {
            const uint32_t fb = sb + SM_BAR + (B_FULL + g0) * 8;
            mbar_expect_tx(fb, 3 * GR);
            if (kk < 16) {
              tma2d(sb + g0 * GR, &p.c, (kk & 7) * 64, (KV_ROW(idx, kk >> 3) + rank) * 128, fb);
              tma3d_mc(sb + (g0 + 1 + rank) * GR, rank ? &p.wuv : &p.wuk, 0, (kk & 7) * 64, (hp + KV_HEAD(idx, kk >> 3)) * 2, fb);
            } else {
              tma2d_mc(sb + (g0 + rank) * GR, &p.x, (kk - 16) * 64, (rank ? 15 - idx : idx) * 128, fb);
              tma3d(sb + (g0 + 2) * GR, &p.wq, 0, (kk - 16) * 64, head * 2, fb);
            }
          }
        }
        flag_wait(FLAG(F_KV + rnd * 8 + grp), 32);
        fence_async_all();
        acquire(2, 1, 3);
        int g0 = 4;
#pragma unroll 1
        for (int n = 0; n < 36; n += n == 0 || n == 33 ? 2 : 1) {
          const int it = (n >> 1) - (n & 1);
          const int blk = it & 15 ? (it <= idx ? it - 1 : 15 - it) : it ? 15 - idx : idx;
          acquire(g0, n < 6 ? 2 : 1, 3);
          if (elect()) {
            const uint32_t fb = sb + SM_BAR + (B_FULL + g0) * 8;
            if (n == 5) mbar_arrive(sb + SM_BAR + B_SLOT * 8);
            mbar_expect_tx(fb, 2 * GR);
            bulk_g2s(sb + g0 * GR, g_kv + (unsigned)((((n & 1) * 16 + (head & 15)) * 16 + blk) * 32768), 2 * GR, fb);
          }
          g0 = n == 13 ? 12 : g0 == 12 ? 4 : g0 + 2;
        }
      }
      if (spare) { bar_sync(5, 64); pe = 0x3FC0; }
      auto conv_fill = [&](int g, int ch) {
        acquire(g, 1, 1);
        if (elect()) {
          const uint32_t fb = sb + SM_BAR + (B_FULL + g) * 8;
          if (!spare) FTP(64 + 48 + g);
          mbar_expect_tx(fb, WBYTES + 4096);
          bulk_g2s<true>(sb + g * GR, g_w + (size_t)ch * WSTRIDE, WBYTES, fb);
          bulk_g2s<true>(sb + g * GR + WBYTES, p.ssk + (size_t)ch * SEQ, 4096, fb);
        }
      };
#pragma unroll 1
      for (int i = 0, g = 2; i < cn; i++) {
        if ((i & 15) == 0) { flag_wait(FLAG(F_U + (spare ? 32 - __clz(i >> 4) : 4)), NMAIN); fence_async_all(); }
        conv_fill(g + (i & 1), cch + i * cstep);
        if (i & 1) g = conv_next(g, spare);
      }
      if (!spare) {
        const int rt = 2 * grp + rank, ct = idx;
        int g0 = P3G, top = 12;
        const uint8_t* src = g_cimg + (unsigned)(rt * 64 * GR);
#pragma unroll 1
        for (int kb = 0; kb < 64; kb++) {
          if (!(kb & 31)) { flag_wait(FLAG(F_CTX + rt * 2 + (kb >> 5)), 32); fence_async_all(); }
          acquire(g0, kb < 11 ? 2 : 1, 3);
          if (elect()) {
            const uint32_t fb = sb + SM_BAR + (B_FULL + g0) * 8;
            if (kb < 16) FTP(48 + kb);
            mbar_expect_tx(fb, 2 * GR);
            bulk_g2s<true>(sb + g0 * GR, src, GR, fb);
            tma2d_mc<true>(sb + (g0 + 1) * GR + rank * 8192, &p.wo, ct * 128 + rank * 64, kb * 64, fb);
          }
          src += GR;
          g0 = g0 == top ? (kb == 3 ? 2 : 0) : g0 + 2;
          if (kb == XK || kb == YK) {
            const bool j = kb == YK;
            if (j) { mbar_wait1(sb + SM_BAR + B_SLOT * 8, 1); fence_async_all(); }
            acquire(top, 1, 0);
            if (elect()) {
              const uint32_t fb = sb + SM_BAR + (B_FULL + top) * 8;
              mbar_expect_tx(fb, j ? 2 * GR + 512 : 2 * GR);
              if (j) bulk_g2s(sb + SM_GATE, g_gate + (unsigned)(rt * 128), 512, fb);
              tma3d(sb + top * GR, j ? &p.y3 : &p.x3, 0, (j ? ct : rt) * 128, (j ? rt : ct) * 2, fb);
            }
            g0 = 0; top -= 2;
          }
        }
        unsigned n = 0;
        if (lane == 0) n = atomicInc(FLAG(F_EXIT), 0x7fffffffu);
        if (__any_sync(0xffffffffu, n == NMAIN - 1)) {
#pragma unroll
          for (int i = lane; i < 96; i += 32) *reinterpret_cast<uint2*>(FLAG(i)) = make_uint2(0, 0);
        }
      }
      if (lane == 0) mbar_arrive(sb + SM_BAR + B_DONE * 8);
    }
    __syncwarp();
    cluster_wait();
  } else {
    asm volatile("setmaxnreg.inc.sync.aligned.u32 232;");
    FTS(2);
    Cons c;
    c.sb = sb; c.pf = 0; c.wg = wgi - 1; c.tid = threadIdx.x & 127;
    const int lane = threadIdx.x & 31, t = lane & 3;
    const int row = c.wg * 64 + (warp & 3) * 16 + (lane >> 2);
    const uint32_t dkk = desc_k(sb), dk0 = dkk + c.wg * 512, dm0 = desc_mn<8192>(sb), dv0 = desc_mn<16384>(sb);
    const uint32_t dsw = DG + 512 - c.wg * 1024;
    if (c.wg == 1) bar_arrive(1, 256);
    c.pfree = 1;
    asm("mapa.shared::cluster.u32 %0, %1, %2;" : "=r"(c.relb) : "r"(sb + SM_BAR + (B_EMPTY + (c.tid >> 1)) * 8), "r"(c.tid & 1));
    c.zero = p.zero;
    c.rnd = 0;
    const uint32_t stg = sb + (c.wg * 64 + (warp & 3) * 16 + ((lane >> 3) & 1) * 8 + (lane & 7)) * 128 + (((lane >> 4) ^ (lane & 7)) << 4);

    uint32_t dd0;
    auto load_dd = [&]() { asm volatile("ld.global.nc.u16 %0, [%1];" : "=r"(dd0) : "l"(p.ssd + (unsigned)(cch + c.wg * cstep + (lane & c.zero)))); };
    int pass = c.zero;
#pragma unroll 1
    do {
    if (pass) {
      load_dd();
#pragma unroll 1
      for (int g = 2; g < NGR; g += 3) { mbar_wait(sb + SM_BAR + (B_FULL + g) * 8, 0); c.release(g, 3); }
      c.pf = 0x924;
    if (spare) {
      c.wait_full(1);
      int g = 2;
#pragma unroll 1
      for (int r = 0; r < 4; r++) {
        float d[4] = {0.f, 0.f, 0.f, 0.f}, e[4] = {0.f, 0.f, 0.f, 0.f};
#pragma unroll 1
        for (int kb = 0; kb < 16; kb += 2) {
          c.wait_full(g);
          wg_fence();
#pragma unroll 1
          for (int k = 0; k < 4; k++) {
            mma_ss_n8(d, dk0 + g * DG + k * 2, dkk + DG + kb * 8 + k * 2);
            mma_ss_n8(e, dk0 + (g + 1) * DG + k * 2, dkk + DG + kb * 8 + 8 + k * 2);
          }
          wg_commit();
          wg_wait<0>();
          c.release(g, 2);
          g = g == NGR - 2 ? 2 : g + 2;
        }
        reg_fence(d); reg_fence(e);
        d[0] += e[0]; d[2] += e[2];
        if (t == 0) {
          float* gp = g_gate + (unsigned)((lb - NMAIN) * 512 + r * 128 + row);
          gp[0] = rcp(1.f + ex2(-1.4426950408889634f * d[0])); gp[8] = rcp(1.f + ex2(-1.4426950408889634f * d[2]));
        }
      }
      fence_release();
      __syncwarp();
      if (lane == 0) flag_add(FLAG(F_GATE));
      TS(1);
    }
    } else cluster_wait();
    get_slot();
    } while (redo && !pass++);
    FTS(3);
    const float dmask = (float)(2 * t - (row & 63));
    uint32_t pv[32];
#pragma unroll 1
    for (int rnd = 0; rnd < (spare ? 0 : 2); rnd++) {
      float O[64];
      FTM(rnd * 8);
      FTG(0);
      FTH(56, c.rnd == rnd);
      c.wait_full(2);
      FTM(rnd * 8 + 1);
      FTH(57, c.rnd == rnd);
#pragma unroll 1
      for (int tile = c.zero; tile < 2; tile++) {
        float acc[128];
        const bool single = tile == 0;
        {
          FTG(tile * 32 + 1);
          const uint32_t a = dk0 + 2 * DG, b = dm0 + 3 * DG;
          c.turn_begin();
          FTG(tile * 32 + 2);
          FTH(58, c.rnd == rnd);
          wg_fence();
          mma_ss_n256_init<1>(acc, a, b);
#pragma unroll
          for (int k = 1; k < 4; k++) mma_ss_n256<1>(acc, a + k * 2, b + k * 128);
          wg_commit();
          if (single) c.turn_end();
          if (single && rnd && !c.wg) { stsm_frag(pv, stg); c.staged(0); }
          FTG(tile * 32 + 3);
        }
#pragma unroll 1
        for (int kb = 1; kb < 8; kb++) {
          const int g0 = 2 + 3 * (kb & 3);
          const uint32_t a = dk0 + g0 * DG, b = dm0 + (g0 + 1) * DG;
          const bool second = (kb == 1 && !single) || kb == 7;
          FTG(tile * 32 + kb * 4);
          if (!second) { wg_wait<0>(); c.release(2 + 3 * ((kb - 1) & 3), 3); }
          FTG(tile * 32 + kb * 4 + 1);
          c.wait_full(g0);
          if (!second) c.turn_begin();
          FTG(tile * 32 + kb * 4 + 2);
          wg_fence();
#pragma unroll
          for (int k = 0; k < 4; k++) mma_ss_n256<1>(acc, a + k * 2, b + k * 128);
          wg_commit();
          if (kb != 6) c.turn_end();
          if (second) { wg_wait<1>(); c.release(2 + 3 * ((kb - 1) & 3), 3); }
          FTG(tile * 32 + kb * 4 + 3);
          FTH(58 + kb, c.rnd == rnd || kb > 3);
          if (tile == 1 && kb == 3) { c.wait_stage_free(); stsm_frag<0, 4>(pv, stg); }
          if (tile == 1 && kb == 4) { stsm_frag<4, 8>(pv, stg); c.staged(0); }
        }
        c.rnd = rnd;
        c.wait_stage_free();
        const bool nxt = c.try_full(2);
        wg_wait<0>();
        reg_fence(acc);
        c.release(11, 3);
        pack_frag_scaled(acc, pv, SM_C, SM_C);
        stsm_frag(pv, stg);
        c.staged(0);
        pack_frag<64>(acc, pv);
        pin32(pv, sb);
        FTG(32 + tile * 32);
        if (!nxt) mbar_wait(sb + SM_BAR + (B_FULL + 2) * 8, (c.pf >> 2) & 1);
        c.pf ^= 4;
      }
      TS(1 + rnd * 3);
      FTM(rnd * 8 + 2);
      {
        float qa[64];
        float (&qb)[64] = O;
        {
          FTG(65);
          const uint32_t a = dk0 + 2 * DG, b = dm0 + 4 * DG;
          c.turn_begin();
          FTG(66);
          wg_fence();
          mma_ss_n128_init<1>(qa, a, b);
          mma_ss_n128_init<1>(qb, a + dsw, b);
#pragma unroll
          for (int k = 1; k < 4; k++) {
            mma_ss_n128<1>(qa, a + k * 2, b + k * 128);
            mma_ss_n128<1>(qb, a + dsw + k * 2, b + k * 128);
          }
          wg_commit();
          FTG(67);
        }
#pragma unroll 1
        for (int kb = 1; kb < 16; kb++) {
          const int g0 = 2 + 3 * (kb & 3);
          const uint32_t a = dk0 + g0 * DG, b = dm0 + (g0 + 2) * DG;
          const bool second = kb == 1 || kb == 15;
          FTG(64 + kb * 4);
          if (!second) { wg_wait<0>(); c.release(2 + 3 * ((kb - 1) & 3), 3); }
          FTG(65 + kb * 4);
          c.wait_full(g0);
          if (!second) c.turn_begin();
          FTG(66 + kb * 4);
          FTH(kb - 14, kb < 14);
          wg_fence();
#pragma unroll
          for (int k = 0; k < 4; k++) {
            mma_ss_n128<1>(qa, a + k * 2, b + k * 128);
            mma_ss_n128<1>(qb, a + dsw + k * 2, b + k * 128);
          }
          wg_commit();
          if (kb != 14) c.turn_end();
          if (second) { wg_wait<1>(); c.release(2 + 3 * ((kb - 1) & 3), 3); }
          FTG(67 + kb * 4);
          FTH(2, kb < 15);
          if (kb == QFLUSH) { c.wait_stage_free(); stsm_frag<0, 4>(pv, stg); }
          if (kb == QFLUSH + 1) { stsm_frag<4, 8>(pv, stg); c.staged(0); }
        }
        c.wait_stage_free();
        mbar_wait(sb + SM_BAR + (B_EMPTY + 2) * 8, rnd ^ !redo);
        FTM(rnd * 8 + 3);
        FTH(3, 0);
        wg_wait<0>();
        reg_fence(qa); reg_fence(qb);
        FTH(4, 0);
        c.release(11, 3);
        pack_frag<0>(qa, pv);
        stsm_frag(pv, stg + 2 * GR);
        if (c.wg == 0) {
          pack_frag<0>(qb, pv);
          stsm_frag(pv, stg);
        }
        FTH(6, 0);
        fence_async_smem();
        FTH(7, 0);
        c.wait_full(4);
      }
      TS(2 + rnd * 3);
      FTM(rnd * 8 + 4);
      FTH(5, 0);
      {
        const int nA = idx + 1;
        uint32_t (&P)[32] = pv;
        SoftState z;
        z.m0 = z.m1 = z.l0 = z.l1 = 0.f; z.shifted = c.zero;
#pragma unroll 1
        for (int seg = c.zero;; seg++) {
        if (c.wg == seg) attn_half(c, O, P, z, dk0, dkk, dv0, dmask, seg);
        if (seg) break;
        FTM(rnd * 8 + 5);
        int gk = c.wg ? 4 : 6, gv = c.wg ? 4 : 8;
        uint32_t dq = dk0 + (1 - c.wg < nA ? 2 * DG : 0), dk = dkk + gk * DG;
#pragma unroll 1
        for (int it = 1 - c.wg; it < 17 - c.wg; it++) {
          float S[64];
          FTA(it * 7 + 0); FTH((it < 3 ? 8 + it * 8 : it * 8 - 88) + 0, it >= 3 && it < 15);
          c.turn_begin();
          FTA(it * 7 + 2); FTH((it < 3 ? 8 + it * 8 : it * 8 - 88) + 1, it >= 3 && it < 15);
          wg_fence();
          issue_qk(S, dq, dk);
          wg_commit();
          const uint32_t dv = dv0 + gv * DG;
          uint32_t relk = c.relb + gk * 8, relv = c.relb + gv * 8;
          gk = it == 6 ? 12 : gv == 12 ? 4 : gv + 2;
          gv = it == 16 ? gk : gk == 12 ? 4 : gk + 2;
          uint32_t fk = sb + SM_BAR + (B_FULL + gk) * 8, fv = sb + SM_BAR + (B_FULL + gv) * 8, park = (c.pf >> gk) & 1, parv = (c.pf >> gv) & 1;
          c.pf ^= (1u << gk) | (1u << gv);
          dq = dk0 + (it + 1 < nA ? 2 * DG : 0); dk = dkk + gk * DG;
          float lo0 = z.l0, lo1 = z.l1;
          const bool first = it == nA || it == 0;
          if (it == nA) {
            lo0 = rcp(quad_sum(lo0)); lo1 = rcp(quad_sum(lo1));
            z.m0 = z.m1 = z.l0 = z.l1 = 0.f; z.shifted = 0;
          }
          float s0, s1, d0 = z.m0, d1 = z.m1;
          int pre = z.shifted || (it & 15) == 0;
          float lim = first ? -1.f : SM_LIMIT;
          asm volatile("" : "+r"(relk), "+r"(relv), "+r"(fk), "+r"(fv), "+r"(park), "+r"(parv), "+r"(dq), "+r"(dk), "+r"(pre), "+f"(lim), "+f"(d0), "+f"(d1), "+f"(z.l0), "+f"(z.l1));
          if (it + c.wg > 1) {
            issue_pv<0>(O, P, dv, it != nA + 1 && it != 1, true);
            issue_pv<1>(O, P, dv, 1, true);
            c.turn_end();
          } else if (it) {
            issue_pv<0>(O, P, dv, 0, true);
            wg_commit(); wg_commit();
            c.turn_end();
          } else stage_q2(c, O, P, stg);
          FTA(it * 7 + 3); FTH((it < 3 ? 8 + it * 8 : it * 8 - 88) + 2, it >= 3 && it < 15);
          wg_wait<4>();
          reg_fence(S);
          FTA(it * 7 + 4); FTH((it < 3 ? 8 + it * 8 : it * 8 - 88) + 3, it >= 3 && it < 15);
          if (c.tid < 4) asm volatile("mbarrier.arrive.shared::cluster.b64 _, [%0];" ::"r"(relk) : "memory");
#pragma unroll 1
          for (int pass = 0;; pass++) {
            if (pre) {
              if ((it & 15) == 0) mask_diag(S, dmask);
              if (z.shifted) shift_scores(S, d0, d1);
            }
            float tr[ROT];
            exp_quarter<0, 3>(S, P, tr, s0, s1, sb);
            exp_quarter<1, 2>(S, P, tr, s0, s1, sb);
            exp_quarter<2, 1>(S, P, tr, s0, s1, sb);
            exp_quarter<3, 0>(S, P, tr, s0, s1, sb);
            reg_fence(O);
            if (c.tid < (pass || !it ? 0 : 4)) asm volatile("mbarrier.arrive.shared::cluster.b64 _, [%0];" ::"r"(relv) : "memory");
            const bool ok = mbar_test(fk, park) & mbar_test(fv, parv);
            if (!ok) lim = -1.f;
            FTA(it * 7 + 5); FTH((it < 3 ? 8 + it * 8 : it * 8 - 88) + 4, it >= 3 && it < 15);
            if (!__any_sync(0xffffffffu, !(s0 <= lim && s1 <= lim))) break;
            if (pass) break;
            if (it == nA) {
              uint32_t pk[32];
              pack_frag_scaled(O, pk, lo0, lo1);
              stsm_frag(pk, stg + 2 * GR);
              c.staged(1);
            }
            if (!ok) { mbar_wait(fk, park); mbar_wait(fv, parv); }
            if (!soft_unsafe(s0, s1, first)) break;
            soft_fix(S, O, z, first, d0, d1);
            pre = 1;
          }
          z.l0 += s0; z.l1 += s1;
          FTA(it * 7 + 6); FTH((it < 3 ? 8 + it * 8 : it * 8 - 88) + 5, it >= 3 && it < 15);
        }
        FTM(rnd * 8 + 6);
        }
        FTH(48, 0);
        load_dd();
        c.turn_begin();
        FTH(49, 0);
        wg_fence();
        issue_pv<0>(O, P, dv0 + 12 * DG, 1, true);
        issue_pv<1>(O, P, dv0 + 12 * DG, 1, !c.wg);
        c.turn_end();
        z.l0 = rcp(quad_sum(z.l0)); z.l1 = rcp(quad_sum(z.l1));
        wg_wait<0>();
        reg_fence(O); reg_fence(P);
        FTH(50, 0);
        c.release(12, 2);
        pack_frag_scaled(O, P, z.l0, z.l1);
        if (rnd || c.wg) { stsm_frag(P, stg); c.staged(0); }
        FTM(rnd * 8 + 7);
        FTH(51, 0);
      }
      TS(3 + rnd * 3);
    }
    conv_tasks(c, p, (cn + 1 - c.wg) / 2, spare, cch + c.wg * cstep, 2 * cstep, dd0, dkk, warp & 3, lane);
    if (c.wg == 1) c.pf ^= 0x14;
    if (c.wg != spare) c.turn_begin();
    TS(7);
    if (!spare) {
      const int rt = 2 * grp + rank, ct = idx;
      float acc[64];
      int g0 = P3G + 2, pg = P3G;
      {
        FTO(0);
        c.wait_full(P3G);
        FTO(1);
        const uint32_t a = dk0 + P3G * DG, b = dm0 + (P3G + 1) * DG;
        wg_fence();
        mma_ss_n128_init<1>(acc, a, b);
#pragma unroll
        for (int k = 1; k < 4; k++) mma_ss_n128<1>(acc, a + k * 2, b + k * 128);
        wg_commit();
      }
#pragma unroll 1
      for (int kb = 1; kb < 64; kb++) {
        FTO(kb * 2);
        c.wait_full(g0);
        if (kb == STR && !c.wg) c.turn_begin();
        FTO(kb * 2 + 1);
        const uint32_t a = dk0 + g0 * DG, b = dm0 + (g0 + 1) * DG;
        wg_fence();
#pragma unroll
        for (int k = 0; k < 4; k++) mma_ss_n128<1>(acc, a + k * 2, b + k * 128);
        wg_commit();
        if (kb < STR) { wg_wait<1>(); c.release(pg, kb <= 59 ? 2 : 0); }
        if (kb == FDUMP_KB) FTDUMP();
        pg = g0;
        g0 = g0 == (kb < XK ? 12 : kb < YK ? 10 : 8) ? (kb == 3 ? 2 : 0) : g0 + 2;
      }
      if (c.wg) c.turn_end();
      cluster_arrive();
      c.wait_full(P3X);
      c.wait_full(P3Y);
      const float g0f = __uint_as_float(lds32(sb + SM_GATE + row * 4)), g1f = __uint_as_float(lds32(sb + SM_GATE + row * 4 + 32));
      const uint32_t gp0 = pack_bf16(g0f, g0f), gp1 = pack_bf16(g1f, g1f);
      const float h0 = 1.f - g0f, h1 = 1.f - g1f;
      const int w = warp & 3;
      const uint32_t xa = stg + P3X * GR;
      const uint32_t ya = sb + P3Y * GR + c.wg * 16384 + ((lane >> 4) * 8 + (lane & 7)) * 128 + (((2 * w + ((lane >> 3) & 1)) ^ (lane & 7)) << 4);
      uint32_t xy[32];
      auto prep = [&](int j0, int j1) {
#pragma unroll
        for (int jj = j0; jj < j1; jj++) {
          uint32_t x[4], y[4];
          asm volatile("ldmatrix.sync.aligned.m8n8.x4.shared.b16 {%0,%1,%2,%3}, [%4];" : "=r"(x[0]), "=r"(x[1]), "=r"(x[2]), "=r"(x[3]) : "r"((xa ^ ((jj & 3) << 5)) + (jj >> 2) * 16384) : "memory");
          asm volatile("ldmatrix.sync.aligned.m8n8.x4.trans.shared.b16 {%0,%1,%2,%3}, [%4];" : "=r"(y[0]), "=r"(y[1]), "=r"(y[2]), "=r"(y[3]) : "r"(ya + jj * 2048) : "memory");
#pragma unroll
          for (int i = 0; i < 4; i++) xy[4 * jj + i] = hmul2(x[i], y[i]);
        }
      };
      prep(0, 4);
      wg_wait<0>();
      reg_fence(acc);
      TS(8);
#pragma unroll
      for (int hf = 0; hf < 2; hf++) {
#pragma unroll
        for (int i = 16 * hf; i < 16 * hf + 16; i++) {
          const float h = (i & 1) ? h1 : h0;
          xy[i] = hfma2((i & 1) ? gp1 : gp0, xy[i], pack_bf16(acc[2 * i] * h, acc[2 * i + 1] * h));
        }
        if (hf) stsm_frag<4, 8>(xy, xa); else stsm_frag<0, 4>(xy, xa);
        fence_async_smem();
        __syncwarp();
        const int r0 = c.wg * 64 + w * 16;
        if (lane == 0) tma2d_store(&p.out, sb + (P3X + hf) * GR + r0 * 128, ct * 128 + hf * 64, rt * 128 + r0);
        if (!hf) prep(4, 8);
      }
      if (lane == 0) asm volatile("cp.async.bulk.commit_group;\ncp.async.bulk.wait_group.read 0;" ::: "memory");
    } else { FTDUMP(); cluster_arrive(); }
    if (lane == 0) mbar_arrive(sb + SM_BAR + B_DONE * 8);
    __syncwarp();
    TS(9);
    cluster_wait();
  }
}

typedef CUresult (*EncFn)(CUtensorMap*, CUtensorMapDataType, cuuint32_t, void*, const cuuint64_t*, const cuuint64_t*, const cuuint32_t*,
                          const cuuint32_t*, CUtensorMapInterleave, CUtensorMapSwizzle, CUtensorMapL2promotion, CUtensorMapFloatOOBfill);

void enc2d(EncFn enc, CUtensorMap* tm, const void* base, uint64_t cols, uint64_t rows, uint32_t bc, uint32_t br) {
  cuuint64_t dims[2] = {cols, rows}; cuuint64_t strides[1] = {cols * 2}; cuuint32_t box[2] = {bc, br}; cuuint32_t es[2] = {1, 1};
  enc(tm, CU_TENSOR_MAP_DATA_TYPE_BFLOAT16, 2, const_cast<void*>(base), dims, strides, box, es, CU_TENSOR_MAP_INTERLEAVE_NONE,
      CU_TENSOR_MAP_SWIZZLE_128B, CU_TENSOR_MAP_L2_PROMOTION_L2_256B, CU_TENSOR_MAP_FLOAT_OOB_FILL_NONE);
}
void enc3d(EncFn enc, CUtensorMap* tm, const void* base, uint64_t K, uint64_t N, uint32_t bk = 64) {
  cuuint64_t dims[3] = {64, K, N / 64}; cuuint64_t strides[2] = {N * 2, 128}; cuuint32_t box[3] = {64, bk, 2}; cuuint32_t es[3] = {1, 1, 1};
  enc(tm, CU_TENSOR_MAP_DATA_TYPE_BFLOAT16, 3, const_cast<void*>(base), dims, strides, box, es, CU_TENSOR_MAP_INTERLEAVE_NONE,
      CU_TENSOR_MAP_SWIZZLE_128B, CU_TENSOR_MAP_L2_PROMOTION_L2_256B, CU_TENSOR_MAP_FLOAT_OOB_FILL_NONE);
}

}

extern "C" void kernel_launch(void* const* d_in, const int* in_sizes, int n_in, void* d_out, int out_size) {
  (void)in_sizes; (void)n_in; (void)out_size;
  typedef const __nv_bfloat16* BP;
  BP xq = (BP)d_in[0], ak = (BP)d_in[1], av = (BP)d_in[2], shk = (BP)d_in[3], ssk = (BP)d_in[4], ssd = (BP)d_in[5];
  BP ckv = (BP)d_in[7], wq = (BP)d_in[8], wuk = (BP)d_in[9], wuv = (BP)d_in[10], wo = (BP)d_in[11], gw = (BP)d_in[12];

  static EncFn enc = nullptr;
  if (!enc) {
    cudaDriverEntryPointQueryResult qr;
    cudaGetDriverEntryPoint("cuTensorMapEncodeTiled", (void**)&enc, cudaEnableDefault, &qr);
    cudaFuncSetAttribute(mega_kernel, cudaFuncAttributeMaxDynamicSharedMemorySize, SMEM_BYTES);
  }
  Params p;
  void* yT = nullptr;
  cudaGetSymbolAddress(&yT, g_yT);
  enc2d(enc, &p.x, xq, DM, SEQ, 64, 128);
  enc2d(enc, &p.c, ckv, DC, SEQ, 64, 128);
  enc3d(enc, &p.wq, wq, DM, NH * HD);
  enc3d(enc, &p.wuk, wuk, DC, NH * HD);
  enc3d(enc, &p.wuv, wuv, DC, NH * HD);
  enc2d(enc, &p.wo, wo, DM, NH * HD, 64, 64);
  enc3d(enc, &p.x3, xq, SEQ, DM, 128);
  enc3d(enc, &p.y3, yT, DM, SEQ, 128);
  enc2d(enc, &p.out, d_out, DM, SEQ, 64, 16);
  {
    void* wp = nullptr;
    cudaGetSymbolAddress(&wp, g_w);
    cuuint64_t dims[3] = {WSTRIDE / 2, DM / 2, 2}; cuuint64_t strides[2] = {2 * WSTRIDE, WSTRIDE}; cuuint32_t box[3] = {16, 32, 2}; cuuint32_t es[3] = {1, 1, 1};
    enc(&p.w, CU_TENSOR_MAP_DATA_TYPE_BFLOAT16, 3, wp, dims, strides, box, es, CU_TENSOR_MAP_INTERLEAVE_NONE,
        CU_TENSOR_MAP_SWIZZLE_32B, CU_TENSOR_MAP_L2_PROMOTION_NONE, CU_TENSOR_MAP_FLOAT_OOB_FILL_NONE);
  }
  p.zero = 0;
  cudaGetSymbolAddress((void**)&p.flags, g_flags);
  for (int i = 0; i < 128; i++) {
    const int tp = i % NSLOT;
    p.pref[i] = tp < 32 ? (tp & 7) * 8 + (tp >> 3) : tp < 60 ? (1 + (tp - 32) % 7) * 8 + 4 + (tp - 32) / 7 : tp < 62 ? tp + 4 : tp - 58;
  }
  p.gate_w = gw; p.ak = ak; p.av = av; p.shk = shk; p.ssk = ssk; p.ssd = ssd; p.wop = wo;

  mega_kernel<<<132, NTHREADS, SMEM_BYTES>>>(p);
}
```

```cpp
#include <cuda_runtime.h>
#include <cuda.h>
#include <cuda_bf16.h>
#include <stdint.h>

namespace {

constexpr int SEQ = 2048, DM = 1024, DC = 512, NH = 32, HD = 128;
constexpr int GR = 16384;
constexpr int NGR = 14;
constexpr int SM_BAR = NGR * GR;
constexpr int SM_GATE = SM_BAR + 512;
constexpr int SM_UST = SM_GATE + 512;
constexpr int SMEM_BYTES = SM_UST + 2048;
constexpr int NTHREADS = 384;
#define SM_LIMIT 1.0995116e12f
#define SM_LOW 9.094947e-13f
#define CNS 100
constexpr int CN_SPARE = CNS, NTICK = 256 - 2 * CN_SPARE;
constexpr int XK = 57, YK = 62;
constexpr int STR = 61;
constexpr int P3G = 6, P3X = 12, P3Y = 10;
constexpr int NMAIN = 128;

constexpr int B_FULL = 0, B_FREE = 14, B_SLOT = 16, B_DONE = 17, B_EMPTY = 18, B_EV = 32, B_TICK = 36;
constexpr int V_SLOT = 37, V_TICK = 38;

__device__ __align__(1024) uint8_t g_kv[2 * 16 * 16 * 32768];
__device__ __align__(1024) uint8_t g_cimg[16 * NH * 32768];
__device__ __align__(1024) __nv_bfloat16 g_yT[DM * SEQ];
__device__ __align__(1024) float g_gate[SEQ];
#define CWIDE 0
constexpr int WZ = CWIDE ? 768 : 256, WPL = WZ + 4096, WBYTES = 2 * WPL + 32, WSTRIDE = 2 * WPL + 128;
__device__ __align__(1024) uint8_t g_w[DM * WSTRIDE];
__device__ __align__(32) unsigned g_flags[96 * 8];
constexpr int F_KV = 0, F_CTX = 16, F_U = 48, F_AD = 56, F_Y = 64, F_GATE = 72, F_EXIT = 73, F_TICK = 74;
constexpr int NSLOT = 66;
#define FLAG(i) (&g_flags[(i) * 8])
#define CLAIMP(i) (p.flags + (i) * 8 + 1)

#define TS(slot)
#define TSW(slot)
#define FTX(i, off)
#define FTDUMP()

#define QFLUSH 4
#define TKCG 10
#define PSL 200
#define US0 800
#define X_DELAY 900
#define X_D2 600
#define P3PF 10
#define P3PF0 5
#define EXPV 1
#define SUMV 0
#define ROT 8
#define KVARR 1
#define KV_ROW(idx, t) (KVARR ? 8 * (t) + 2 * ((idx) & 3) : 2 * (idx))
#define KV_HEAD(idx, t) (KVARR ? (idx) >> 2 : (t))
#define FINE_MODE 0
#define FDUMP_KB 40
#define FINE_RND 1
#define FTA(i) do { if (FINE_MODE == 0) FTX(i, rnd ^ FINE_RND); } while (0)
#define FTG(i) do { if (FINE_MODE == 1) FTX(i, rnd ^ FINE_RND); } while (0)
#define FTM(i) do { if (FINE_MODE == 4) FTX(i, 0); } while (0)
#define FTC(k) do { if (FINE_MODE == 5) FTX((i & 7) * 8 + (k), (i >> 3) ^ FINE_RND); } while (0)
#define FTH(i, off) do { if (FINE_MODE == 6) FTX(i, (c.rnd ^ FINE_RND) | (off)); } while (0)
#define FTS(i)
#define FTSD(i)
#define FTSW(i)
#define FTP(i)
#define FTO(i) do { if (FINE_MODE == 2) FTX(i, 0); } while (0)

__device__ __forceinline__ uint32_t smem_u32(const void* p) { return (uint32_t)__cvta_generic_to_shared(p); }
__device__ __forceinline__ void mbar_init(uint32_t bar, int cnt) { asm volatile("mbarrier.init.shared::cta.b64 [%0], %1;" ::"r"(bar), "r"(cnt) : "memory"); }
__device__ __forceinline__ void mbar_expect_tx(uint32_t bar, uint32_t bytes) { asm volatile("mbarrier.arrive.expect_tx.shared::cta.b64 _, [%0], %1;" ::"r"(bar), "r"(bytes) : "memory"); }
__device__ __forceinline__ void mbar_arrive(uint32_t bar) { asm volatile("mbarrier.arrive.shared::cta.b64 _, [%0];" ::"r"(bar) : "memory"); }
__device__ __forceinline__ void mbar_arrive_cluster(uint32_t bar, uint32_t cta) {
  asm volatile("{\n.reg .b32 r;\nmapa.shared::cluster.u32 r, %0, %1;\nmbarrier.arrive.shared::cluster.b64 _, [r];\n}\n" ::"r"(bar), "r"(cta) : "memory");
}
__device__ __forceinline__ void send_both(uint32_t bar, uint32_t off, uint32_t v) {
#pragma unroll
  for (int r = 0; r < 2; r++)
    asm volatile("{\n.reg .b32 a, b;\nmapa.shared::cluster.u32 a, %0, %1;\nadd.u32 b, a, %3;\nst.async.shared::cluster.mbarrier::complete_tx::bytes.u32 [b], %2, [a];\n}\n"
                 ::"r"(bar), "r"(r), "r"(v), "r"(off) : "memory");
}
__device__ __forceinline__ bool mbar_try(uint32_t bar, uint32_t parity) {
  uint32_t ok;
  asm volatile("{\n.reg .pred p;\nmbarrier.try_wait.parity.shared::cta.b64 p, [%1], %2, 20000;\nselp.u32 %0, 1, 0, p;\n}\n" : "=r"(ok) : "r"(bar), "r"(parity) : "memory");
  return ok;
}
__device__ __forceinline__ bool mbar_test(uint32_t bar, uint32_t parity) {
  uint32_t ok;
  asm volatile("{\n.reg .pred p;\nmbarrier.test_wait.parity.shared::cta.b64 p, [%1], %2;\nselp.u32 %0, 1, 0, p;\n}\n" : "=r"(ok) : "r"(bar), "r"(parity) : "memory");
  return ok;
}
__device__ __forceinline__ void mbar_wait(uint32_t bar, uint32_t parity) {
  asm volatile("{\n.reg .pred p;\nWAIT_LOOP:\nbar.warp.sync -1;\nmbarrier.try_wait.parity.shared::cta.b64 p, [%0], %1;\n@!p bra WAIT_LOOP;\n}\n" ::"r"(bar), "r"(parity) : "memory");
}
__device__ __forceinline__ void mbar_wait1(uint32_t bar, uint32_t parity) {
  asm volatile("{\n.reg .pred p;\nWAIT_LOOP:\nbar.warp.sync -1;\nmbarrier.try_wait.parity.shared::cta.b64 p, [%0], %1, 4000;\n@!p bra WAIT_LOOP;\n}\n" ::"r"(bar), "r"(parity) : "memory");
}
constexpr uint64_t EV_FIRST = 0x12F0000000000000ull;
__device__ __forceinline__ uint32_t ldg_stream(const uint32_t* p) {
  uint32_t r; asm volatile("ld.global.nc.L1::no_allocate.L2::cache_hint.b32 %0, [%1], %2;" : "=r"(r) : "l"(p), "l"(EV_FIRST)); return r;
}
#define TMA_LD "cp.async.bulk.tensor."
#define TMA_MB ".shared::cluster.global.mbarrier::complete_tx::bytes"
__device__ __forceinline__ void tma2d(uint32_t dst, const CUtensorMap* tm, int c0, int c1, uint32_t bar) {
  asm volatile(TMA_LD "2d" TMA_MB " [%0], [%1, {%3, %4}], [%2];" ::"r"(dst), "l"(tm), "r"(bar), "r"(c0), "r"(c1) : "memory");
}
template <bool ONCE = false> __device__ __forceinline__ void tma2d_mc(uint32_t dst, const CUtensorMap* tm, int c0, int c1, uint32_t bar) {
  if (ONCE) asm volatile(TMA_LD "2d" TMA_MB ".multicast::cluster.L2::cache_hint [%0], [%1, {%3, %4}], [%2], %5, %6;"
                         ::"r"(dst), "l"(tm), "r"(bar), "r"(c0), "r"(c1), "h"((uint16_t)3), "l"(EV_FIRST) : "memory");
  else asm volatile(TMA_LD "2d" TMA_MB ".multicast::cluster [%0], [%1, {%3, %4}], [%2], %5;"
                    ::"r"(dst), "l"(tm), "r"(bar), "r"(c0), "r"(c1), "h"((uint16_t)3) : "memory");
}
__device__ __forceinline__ void tma3d(uint32_t dst, const CUtensorMap* tm, int c0, int c1, int c2, uint32_t bar) {
  asm volatile(TMA_LD "3d" TMA_MB " [%0], [%1, {%3, %4, %5}], [%2];" ::"r"(dst), "l"(tm), "r"(bar), "r"(c0), "r"(c1), "r"(c2) : "memory");
}
__device__ __forceinline__ void tma3d_mc(uint32_t dst, const CUtensorMap* tm, int c0, int c1, int c2, uint32_t bar) {
  asm volatile(TMA_LD "3d" TMA_MB ".multicast::cluster [%0], [%1, {%3, %4, %5}], [%2], %6;"
               ::"r"(dst), "l"(tm), "r"(bar), "r"(c0), "r"(c1), "r"(c2), "h"((uint16_t)3) : "memory");
}
template <bool ONCE = false> __device__ __forceinline__ void bulk_g2s(uint32_t dst, const void* src, uint32_t bytes, uint32_t bar) {
  if (ONCE) asm volatile("cp.async.bulk" TMA_MB ".L2::cache_hint [%0], [%1], %2, [%3], %4;" ::"r"(dst), "l"(src), "r"(bytes), "r"(bar), "l"(EV_FIRST) : "memory");
  else asm volatile("cp.async.bulk" TMA_MB " [%0], [%1], %2, [%3];" ::"r"(dst), "l"(src), "r"(bytes), "r"(bar) : "memory");
}
__device__ __forceinline__ void tma2d_store(const CUtensorMap* tm, uint32_t src, int c0, int c1) {
  asm volatile("cp.async.bulk.tensor.2d.global.shared::cta.bulk_group [%0, {%2, %3}], [%1];" ::"l"(tm), "r"(src), "r"(c0), "r"(c1) : "memory");
}
__device__ __forceinline__ void prefetch_tm(const CUtensorMap* tm) { asm volatile("prefetch.tensormap [%0];" ::"l"(tm) : "memory"); }
__device__ __forceinline__ void wg_fence() { asm volatile("wgmma.fence.sync.aligned;" ::: "memory"); }
__device__ __forceinline__ void wg_commit() { asm volatile("wgmma.commit_group.sync.aligned;" ::: "memory"); }
template <int N> __device__ __forceinline__ void wg_wait() { asm volatile("wgmma.wait_group.sync.aligned %0;" ::"n"(N) : "memory"); }
__device__ __forceinline__ void bar_sync(int id, int n) { asm volatile("bar.sync %0, %1;" ::"r"(id), "r"(n) : "memory"); }
__device__ __forceinline__ void bar_arrive(int id, int n) { asm volatile("bar.arrive %0, %1;" ::"r"(id), "r"(n) : "memory"); }
__device__ __forceinline__ void fence_async_smem() { asm volatile("fence.proxy.async.shared::cta;" ::: "memory"); }
__device__ __forceinline__ void fence_async_all() { asm volatile("fence.proxy.async.global;" ::: "memory"); }
__device__ __forceinline__ uint32_t pack_bf16(float lo, float hi) { uint32_t r; asm("cvt.rn.bf16x2.f32 %0, %1, %2;" : "=r"(r) : "f"(hi), "f"(lo)); return r; }
__device__ __forceinline__ float ex2(float x) { float r; asm("ex2.approx.ftz.f32 %0, %1;" : "=f"(r) : "f"(x)); return r; }
__device__ __forceinline__ float rcp(float x) { float r; asm("rcp.approx.ftz.f32 %0, %1;" : "=f"(r) : "f"(x)); return r; }
__device__ __forceinline__ void flag_wait(const unsigned* f, unsigned target) {
  unsigned v;
  do { asm volatile("ld.acquire.gpu.global.u32 %0, [%1];" : "=r"(v) : "l"(f) : "memory"); } while (__any_sync(0xffffffffu, v < target));
}
__device__ __forceinline__ bool elect() {
  uint32_t r;
  asm volatile("{\n.reg .pred p;\nelect.sync _|p, -1;\nselp.u32 %0, 1, 0, p;\n}\n" : "=r"(r));
  return r;
}
__device__ __forceinline__ void fence_release() { asm volatile("fence.release.gpu;" ::: "memory"); }
__device__ __forceinline__ void flag_add(unsigned* f) { asm volatile("red.relaxed.gpu.global.inc.u32 [%0], 0x7fffffff;" ::"l"(f) : "memory"); }
__device__ __forceinline__ void cluster_arrive() { asm volatile("barrier.cluster.arrive.relaxed.aligned;" ::: "memory"); }
__device__ __forceinline__ void cluster_wait() { asm volatile("barrier.cluster.wait.aligned;" ::: "memory"); }
__device__ __forceinline__ uint32_t hmul2(uint32_t a, uint32_t b) { uint32_t r; asm("mul.rn.bf16x2 %0, %1, %2;" : "=r"(r) : "r"(a), "r"(b)); return r; }
__device__ __forceinline__ uint32_t hadd2(uint32_t a, uint32_t b) { uint32_t r; asm("add.rn.bf16x2 %0, %1, %2;" : "=r"(r) : "r"(a), "r"(b)); return r; }
__device__ __forceinline__ uint32_t hfma2(uint32_t a, uint32_t b, uint32_t c) { uint32_t r; asm("fma.rn.bf16x2 %0, %1, %2, %3;" : "=r"(r) : "r"(a), "r"(b), "r"(c)); return r; }
__device__ __forceinline__ uint32_t lds32(uint32_t a) { uint32_t r; asm volatile("ld.shared.b32 %0, [%1];" : "=r"(r) : "r"(a) : "memory"); return r; }
__device__ __forceinline__ uint4 lds128(uint32_t a) { uint4 r; asm volatile("ld.shared.v4.b32 {%0,%1,%2,%3}, [%4];" : "=r"(r.x), "=r"(r.y), "=r"(r.z), "=r"(r.w) : "r"(a) : "memory"); return r; }
__device__ __forceinline__ uint32_t desc_k(uint32_t addr) { return ((addr & 0x3FFFF) >> 4) | (1u << 16); }
template <int LBO> __device__ __forceinline__ uint32_t desc_mn(uint32_t addr) { return ((addr & 0x3FFFF) >> 4) | ((uint32_t)(LBO >> 4) << 16); }
#define DHI "0x40000040"

#define R8(d, o) "+f"(d[o]), "+f"(d[o + 1]), "+f"(d[o + 2]), "+f"(d[o + 3]), "+f"(d[o + 4]), "+f"(d[o + 5]), "+f"(d[o + 6]), "+f"(d[o + 7])
#define R32(d, o) R8(d, o), R8(d, o + 8), R8(d, o + 16), R8(d, o + 24)
#define R64(d, o) R32(d, o), R32(d, o + 32)
#define L64 "%0,%1,%2,%3,%4,%5,%6,%7,%8,%9,%10,%11,%12,%13,%14,%15,%16,%17,%18,%19,%20,%21,%22,%23,%24,%25,%26,%27,%28,%29,%30,%31," \
            "%32,%33,%34,%35,%36,%37,%38,%39,%40,%41,%42,%43,%44,%45,%46,%47,%48,%49,%50,%51,%52,%53,%54,%55,%56,%57,%58,%59,%60,%61,%62,%63"
#define L128 L64 ",%64,%65,%66,%67,%68,%69,%70,%71,%72,%73,%74,%75,%76,%77,%78,%79,%80,%81,%82,%83,%84,%85,%86,%87,%88,%89,%90,%91,%92,%93,%94,%95," \
            "%96,%97,%98,%99,%100,%101,%102,%103,%104,%105,%106,%107,%108,%109,%110,%111,%112,%113,%114,%115,%116,%117,%118,%119,%120,%121,%122,%123,%124,%125,%126,%127"

template <int TB> __device__ __forceinline__ void mma_ss_n128(float (&d)[64], uint32_t da, uint32_t db) {
  asm volatile("{\n.reg .b64 da, db;\nmov.b64 da, {%64, " DHI "};\nmov.b64 db, {%65, " DHI "};\n"
               "wgmma.mma_async.sync.aligned.m64n128k16.f32.bf16.bf16 {" L64 "}, da, db, 1, 1, 1, 0, %66;\n}\n"
               : R64(d, 0) : "r"(da), "r"(db), "n"(TB));
}
template <int TB> __device__ __forceinline__ void mma_rs_n128(float (&d)[64], uint32_t a0, uint32_t a1, uint32_t a2, uint32_t a3, uint32_t db, int sd) {
  asm volatile("{\n.reg .pred p;\n.reg .b64 db;\nsetp.ne.b32 p, %69, 0;\nmov.b64 db, {%68, " DHI "};\n"
               "wgmma.mma_async.sync.aligned.m64n128k16.f32.bf16.bf16 {" L64 "}, {%64,%65,%66,%67}, db, p, 1, 1, %70;\n}\n"
               : R64(d, 0) : "r"(a0), "r"(a1), "r"(a2), "r"(a3), "r"(db), "r"(sd), "n"(TB));
}
template <int TB> __device__ __forceinline__ void mma_ss_n256(float (&d)[128], uint32_t da, uint32_t db) {
  asm volatile("{\n.reg .b64 da, db;\nmov.b64 da, {%128, " DHI "};\nmov.b64 db, {%129, " DHI "};\n"
               "wgmma.mma_async.sync.aligned.m64n256k16.f32.bf16.bf16 {" L128 "}, da, db, 1, 1, 1, 0, %130;\n}\n"
               : R64(d, 0), R64(d, 64) : "r"(da), "r"(db), "n"(TB));
}
#define W8(d, o) "=f"(d[o]), "=f"(d[o + 1]), "=f"(d[o + 2]), "=f"(d[o + 3]), "=f"(d[o + 4]), "=f"(d[o + 5]), "=f"(d[o + 6]), "=f"(d[o + 7])
#define W32(d, o) W8(d, o), W8(d, o + 8), W8(d, o + 16), W8(d, o + 24)
#define W64(d, o) W32(d, o), W32(d, o + 32)
template <int TB> __device__ __forceinline__ void mma_ss_n128_init(float (&d)[64], uint32_t da, uint32_t db) {
  asm volatile("{\n.reg .b64 da, db;\nmov.b64 da, {%64, " DHI "};\nmov.b64 db, {%65, " DHI "};\n"
               "wgmma.mma_async.sync.aligned.m64n128k16.f32.bf16.bf16 {" L64 "}, da, db, 0, 1, 1, 0, %66;\n}\n"
               : W64(d, 0) : "r"(da), "r"(db), "n"(TB));
}
template <int TB> __device__ __forceinline__ void mma_ss_n256_init(float (&d)[128], uint32_t da, uint32_t db) {
  asm volatile("{\n.reg .b64 da, db;\nmov.b64 da, {%128, " DHI "};\nmov.b64 db, {%129, " DHI "};\n"
               "wgmma.mma_async.sync.aligned.m64n256k16.f32.bf16.bf16 {" L128 "}, da, db, 0, 1, 1, 0, %130;\n}\n"
               : W64(d, 0), W64(d, 64) : "r"(da), "r"(db), "n"(TB));
}
#define L32 "%0,%1,%2,%3,%4,%5,%6,%7,%8,%9,%10,%11,%12,%13,%14,%15,%16,%17,%18,%19,%20,%21,%22,%23,%24,%25,%26,%27,%28,%29,%30,%31"
__device__ __forceinline__ void mma_ss_n64(float (&d)[32], uint32_t da, uint32_t db) {
  asm volatile("{\n.reg .b64 da, db;\nmov.b64 da, {%32, " DHI "};\nmov.b64 db, {%33, " DHI "};\n"
               "wgmma.mma_async.sync.aligned.m64n64k16.f32.bf16.bf16 {" L32 "}, da, db, 1, 1, 1, 0, 0;\n}\n"
               : R32(d, 0) : "r"(da), "r"(db));
}
__device__ __forceinline__ void mma_ss_n64_init(float (&d)[32], uint32_t da, uint32_t db) {
  asm volatile("{\n.reg .b64 da, db;\nmov.b64 da, {%32, " DHI "};\nmov.b64 db, {%33, " DHI "};\n"
               "wgmma.mma_async.sync.aligned.m64n64k16.f32.bf16.bf16 {" L32 "}, da, db, 0, 1, 1, 0, 0;\n}\n"
               : W32(d, 0) : "r"(da), "r"(db));
}
#define L16 "%0,%1,%2,%3,%4,%5,%6,%7,%8,%9,%10,%11,%12,%13,%14,%15"
template <int O, bool INIT> __device__ __forceinline__ void mma_rs_n32(float (&d)[128], uint32_t a0, uint32_t a1, uint32_t a2, uint32_t a3, uint32_t db) {
  if (INIT) asm volatile("{\n.reg .b64 db;\nmov.b64 db, {%20, 0x00000008};\n"
               "wgmma.mma_async.sync.aligned.m64n32k16.f32.bf16.bf16 {" L16 "}, {%16,%17,%18,%19}, db, 0, 1, 1, 0;\n}\n"
               : W8(d, O), W8(d, O + 8) : "r"(a0), "r"(a1), "r"(a2), "r"(a3), "r"(db));
  else asm volatile("{\n.reg .b64 db;\nmov.b64 db, {%20, 0x00000008};\n"
               "wgmma.mma_async.sync.aligned.m64n32k16.f32.bf16.bf16 {" L16 "}, {%16,%17,%18,%19}, db, 1, 1, 1, 0;\n}\n"
               : R8(d, O), R8(d, O + 8) : "r"(a0), "r"(a1), "r"(a2), "r"(a3), "r"(db));
}
template <int O, bool INIT> __device__ __forceinline__ void mma_rs_n64(float (&d)[128], uint32_t a0, uint32_t a1, uint32_t a2, uint32_t a3, uint32_t db) {
  if (INIT) asm volatile("{\n.reg .b64 db;\nmov.b64 db, {%36, 0x00000008};\n"
               "wgmma.mma_async.sync.aligned.m64n64k16.f32.bf16.bf16 {" L32 "}, {%32,%33,%34,%35}, db, 0, 1, 1, 0;\n}\n"
               : W32(d, O) : "r"(a0), "r"(a1), "r"(a2), "r"(a3), "r"(db));
  else asm volatile("{\n.reg .b64 db;\nmov.b64 db, {%36, 0x00000008};\n"
               "wgmma.mma_async.sync.aligned.m64n64k16.f32.bf16.bf16 {" L32 "}, {%32,%33,%34,%35}, db, 1, 1, 1, 0;\n}\n"
               : R32(d, O) : "r"(a0), "r"(a1), "r"(a2), "r"(a3), "r"(db));
}
template <int S, int J> __device__ __forceinline__ void conv_step(float (&d)[128], const uint32_t (&a)[64], uint32_t db) {
  if constexpr (J >= 0 && J >= (S >> 1)) {
    if constexpr (J >= 8 - 2 * CWIDE) {
      mma_rs_n64<16 * (J - 1), S == 0>(d, a[4 * S], a[4 * S + 1], a[4 * S + 2], a[4 * S + 3], db + (uint32_t)((2 * (J - 1) - S) * 16));
      conv_step<S, J - 2>(d, a, db);
    } else {
      mma_rs_n32<16 * J, S == 0>(d, a[4 * S], a[4 * S + 1], a[4 * S + 2], a[4 * S + 3], db + (uint32_t)((2 * J - S) * 16));
      conv_step<S, J - 1>(d, a, db);
    }
  }
}
__device__ __forceinline__ void mma_ss_n8(float (&d)[4], uint32_t da, uint32_t db) {
  asm volatile("{\n.reg .b64 da, db;\nmov.b64 da, {%4, " DHI "};\nmov.b64 db, {%5, 0x00000008};\n"
               "wgmma.mma_async.sync.aligned.m64n8k16.f32.bf16.bf16 {%0,%1,%2,%3}, da, db, 1, 1, 1, 0, 0;\n}\n"
               : "+f"(d[0]), "+f"(d[1]), "+f"(d[2]), "+f"(d[3]) : "r"(da), "r"(db));
}
template <int N> __device__ __forceinline__ void reg_fence(float (&d)[N]) {
#pragma unroll
  for (int i = 0; i < N; i++) asm volatile("" : "+f"(d[i])::"memory");
}
template <int N> __device__ __forceinline__ void reg_fence(uint32_t (&d)[N]) {
#pragma unroll
  for (int i = 0; i < N; i++) asm volatile("" : "+r"(d[i])::"memory");
}

struct __align__(64) Params {
  unsigned* flags;
  int zero;
  uint8_t pref[128];
  const __nv_bfloat16 *gate_w, *ak, *av, *shk, *ssk, *ssd, *wop;
  CUtensorMap x, c, wq, wuk, wuv, wo, x3, y3, out, w;
};

template <int O, int N, int M> __device__ __forceinline__ void pack_frag(const float (&acc)[N], uint32_t (&pk)[M]) {
#pragma unroll
  for (int i = 0; i < 32; i++) pk[i] = pack_bf16(acc[O + 2 * i], acc[O + 2 * i + 1]);
}
template <int N> __device__ __forceinline__ void pack_frag_scaled(const float (&acc)[N], uint32_t (&pk)[32], float s0, float s1) {
#pragma unroll
  for (int i = 0; i < 32; i++) { const float s = (i & 1) ? s1 : s0; pk[i] = pack_bf16(acc[2 * i] * s, acc[2 * i + 1] * s); }
}
template <int J0 = 0, int J1 = 8, int M> __device__ __forceinline__ void stsm_frag(const uint32_t (&pk)[M], uint32_t a) {
#pragma unroll
  for (int jj = J0; jj < J1; jj++)
    asm volatile("stmatrix.sync.aligned.m8n8.x4.shared.b16 [%0], {%1,%2,%3,%4};" ::"r"((a ^ ((jj & 3) << 5)) + (jj >> 2) * 16384),
                 "r"(pk[4 * jj]), "r"(pk[4 * jj + 1]), "r"(pk[4 * jj + 2]), "r"(pk[4 * jj + 3]) : "memory");
}

struct Cons {
  uint32_t sb;
  uint32_t pf;
  int wg, tid;
  __device__ __forceinline__ void wait_full(int g) { mbar_wait(sb + SM_BAR + (B_FULL + g) * 8, (pf >> g) & 1); pf ^= 1u << g; }
  uint32_t relb;
  __device__ __forceinline__ void release(int g, int n) {
    if (tid < 2 * n) asm volatile("mbarrier.arrive.shared::cluster.b64 _, [%0];" ::"r"(relb + g * 8) : "memory");
  }
  __device__ __forceinline__ void turn_begin() { bar_sync(1 + wg, 256); }
  __device__ __forceinline__ void turn_end() { bar_arrive(2 - wg, 256); }
  __device__ __forceinline__ void staged(int e) { __syncwarp(); if ((tid & 31) == 0) mbar_arrive(sb + SM_BAR + (B_EV + 2 * e + wg) * 8); }
  int zero;
  int rnd;
  uint32_t pfree;
  __device__ __forceinline__ void wait_stage_free() { mbar_wait(sb + SM_BAR + (B_FREE + wg) * 8, pfree); pfree ^= 1; }
  __device__ __forceinline__ bool try_full(int g) { return mbar_test(sb + SM_BAR + (B_FULL + g) * 8, (pf >> g) & 1); }
};

constexpr float SM_C = 0.08838834764831845f * 1.4426950408889634f;
struct SoftState { float m0, m1, l0, l1; int shifted; };
__device__ __forceinline__ void ex2_rot(float& t, float s, uint32_t never_zero) {
  asm("{\n.reg .pred p;\nsetp.ne.u32 p, %2, 0;\n@p ex2.approx.ftz.f32 %0, %1;\n}\n" : "+f"(t) : "f"(s), "r"(never_zero));
}
__device__ __forceinline__ void pin(float a, uint32_t never_zero) {
  asm volatile("{\n.reg .pred p;\nsetp.eq.u32 p, %1, 0;\n@p st.shared.f32 [%1], %0;\n}\n" ::"f"(a), "r"(never_zero) : "memory");
}
template <int O, int N> __device__ __forceinline__ void reg_fence_part(uint32_t (&d)[32]) {
#pragma unroll
  for (int i = O; i < O + N; i++) asm volatile("" : "+r"(d[i])::"memory");
}
template <int Q, int W, int N> __device__ __forceinline__ void exp_quarter(const float (&S)[N], uint32_t (&P)[32], float (&t)[ROT], float& s0, float& s1, uint32_t nz) {
#pragma unroll
  for (int i = 8 * Q; i < 8 * Q + 8; i++) {
    float& a = t[(2 * i) % ROT];
    float& b = t[(2 * i + 1) % ROT];
    if (2 * i < ROT) { a = ex2(S[2 * i]); b = ex2(S[2 * i + 1]); }
    else { ex2_rot(a, S[2 * i], nz); ex2_rot(b, S[2 * i + 1], nz); }
    if (i < 2) { if (i) s1 = a + b; else s0 = a + b; }
    else if (SUMV == 0) { if (i & 1) { s1 += a; s1 += b; } else { s0 += a; s0 += b; } }
    else { if (i & 1) s1 += a + b; else s0 += a + b; }
    if (i == 8 * Q) { pin(EXPV == 1 && Q ? s1 : s0, nz); wg_wait<W>(); reg_fence_part<8 * Q, 8>(P); }
    P[i] = pack_bf16(a, b);
  }
}
template <int N> __device__ __forceinline__ void shift_scores(float (&S)[N], float d0, float d1) {
#pragma unroll
  for (int i = 0; i < N; i++) S[i] -= (i & 2) ? d1 : d0;
}
__device__ __forceinline__ bool soft_high(float s0, float s1, float lim = SM_LIMIT) { return s0 > lim || s1 > lim; }
__device__ __forceinline__ bool soft_unsafe(float s0, float s1, bool first) {
  uint32_t b0 = __ballot_sync(0xffffffffu, s0 >= SM_LOW), b1 = __ballot_sync(0xffffffffu, s1 >= SM_LOW);
  b0 |= b0 >> 1; b0 |= b0 >> 2; b1 |= b1 >> 1; b1 |= b1 >> 2;
  return __any_sync(0xffffffffu, soft_high(s0, s1)) || (first && (b0 & b1 & 0x11111111u) != 0x11111111u);
}
template <int N> __device__ __forceinline__ void soft_fix(const float (&S)[N], float (&O)[64], SoftState& z, bool first, float& d0, float& d1) {
  d0 = d1 = first ? -INFINITY : 0.f;
#pragma unroll
  for (int j = 0; j < N / 4; j++) { d0 = fmaxf(d0, fmaxf(S[4 * j], S[4 * j + 1])); d1 = fmaxf(d1, fmaxf(S[4 * j + 2], S[4 * j + 3])); }
  d0 = fmaxf(d0, __shfl_xor_sync(0xffffffffu, d0, 1)); d1 = fmaxf(d1, __shfl_xor_sync(0xffffffffu, d1, 1));
  d0 = fmaxf(d0, __shfl_xor_sync(0xffffffffu, d0, 2)); d1 = fmaxf(d1, __shfl_xor_sync(0xffffffffu, d1, 2));
  const float sc0 = ex2(-fmaxf(d0, 0.f)), sc1 = ex2(-fmaxf(d1, 0.f));
  z.m0 += d0; z.m1 += d1; z.l0 *= sc0; z.l1 *= sc1; z.shifted = 1;
#pragma unroll
  for (int j = 0; j < 16; j++) { O[4 * j] *= sc0; O[4 * j + 1] *= sc0; O[4 * j + 2] *= sc1; O[4 * j + 3] *= sc1; }
}
template <int M> __device__ __forceinline__ void pin32(const uint32_t (&v)[M], uint32_t never_zero) {
#pragma unroll
  for (int i = 0; i < 32; i += 4)
    asm volatile("{\n.reg .pred p;\nsetp.eq.u32 p, %4, 0;\n@p st.shared.v4.b32 [%4], {%0,%1,%2,%3};\n}\n" ::"r"(v[i]), "r"(v[i + 1]), "r"(v[i + 2]), "r"(v[i + 3]), "r"(never_zero) : "memory");
}
template <int N> __device__ __forceinline__ void mask_diag(float (&S)[N], float nd) {
  asm volatile("" : "+f"(nd));
#pragma unroll
  for (int i = 0; i < 32; i++) {
    const float beyond = __saturatef(nd + (float)(8 * (i >> 2) + (i & 1) - 4 * (i & 2)));
    S[N - 32 + i] = fmaf(beyond, -3.0e38f, S[N - 32 + i]);
  }
}
__device__ __forceinline__ float quad_sum(float v) {
  v += __shfl_xor_sync(0xffffffffu, v, 1);
  v += __shfl_xor_sync(0xffffffffu, v, 2);
  return v;
}
__device__ __forceinline__ void issue_qk(float (&S)[64], uint32_t dq, uint32_t dk) {
  mma_ss_n128_init<0>(S, dq, dk);
#pragma unroll
  for (int s = 1; s < 8; s++) mma_ss_n128<0>(S, dq + (s >> 2) * 1024 + (s & 3) * 2, dk + (s >> 2) * 1024 + (s & 3) * 2);
}
__device__ __forceinline__ void issue_qk(float (&S)[32], uint32_t dq, uint32_t dk) {
  mma_ss_n64_init(S, dq, dk);
#pragma unroll
  for (int s = 1; s < 8; s++) mma_ss_n64(S, dq + (s >> 2) * 1024 + (s & 3) * 2, dk + (s >> 2) * 1024 + (s & 3) * 2);
}
template <int H> __device__ __forceinline__ void issue_pv(float (&O)[64], const uint32_t (&P)[32], uint32_t dv, int acc, bool on) {
  if (on) {
#pragma unroll
    for (int s = 4 * H; s < 4 * H + 4; s++) {
      mma_rs_n128<1>(O, P[4 * s], P[4 * s + 1], P[4 * s + 2], P[4 * s + 3], dv + s * 128, s != 0 ? 1 : acc);
      if (s & 1) wg_commit();
    }
  } else { wg_commit(); wg_commit(); }
}
constexpr uint32_t DG = GR >> 4;
__device__ __forceinline__ void stage_q2(Cons& c, const float (&O)[64], uint32_t (&P)[32], uint32_t stg) {
  wg_commit(); wg_commit(); wg_commit(); wg_commit();
  c.turn_end();
  pack_frag<0>(O, P);
  stsm_frag(P, stg);
  fence_async_smem();
}
__device__ __forceinline__ void attn_half(Cons& c, float (&O)[64], uint32_t (&P)[32], SoftState& z, uint32_t dk0, uint32_t dkk, uint32_t dv0, float dmask, int last) {
  float S[32];
  FTH(8 + last * 32, 0);
  c.turn_begin();
  FTH(9 + last * 32, 0);
  wg_fence();
  issue_qk(S, dk0 + (last ? 0 : 2 * DG), dkk + (last ? 8 : 4) * DG);
  wg_commit();
  issue_pv<0>(O, P, dv0 + 10 * DG, 1, last);
  issue_pv<1>(O, P, dv0 + 10 * DG, 1, last);
  c.turn_end();
  c.wait_full(last ? 12 : 6);
  FTH(10 + last * 32, 0);
  wg_wait<4>();
  reg_fence(S);
  FTH(11 + last * 32, 0);
  c.release(last ? 8 : 4, 2);
  mask_diag(S, dmask);
  float s0, s1, d0 = z.m0, d1 = z.m1;
#pragma unroll 1
  for (int pass = 0;; pass++) {
    if (z.shifted) shift_scores(S, d0, d1);
    float tr[ROT];
    exp_quarter<0, 3>(S, P, tr, s0, s1, c.sb);
    exp_quarter<1, 2>(S, P, tr, s0, s1, c.sb);
    pin(s1, c.sb); wg_wait<0>(); reg_fence_part<16, 16>(P); reg_fence(O);
    if (!soft_unsafe(s0, s1, !last) || pass) break;
    soft_fix(S, O, z, !last, d0, d1);
  }
  FTH(12 + last * 32, 0);
  z.l0 += s0; z.l1 += s1;
  c.release(10, last ? 2 : 0);
  if (!last) c.wait_full(8);
  FTH(13 + last * 32, 0);
}

template <int V> struct IC { static constexpr int value = V; };
__device__ __forceinline__ int conv_next(int g, bool spare) { return g >= NGR - 2 ? g - (NGR - 4) : !spare && g == 4 ? 1 : g + 2; }
__device__ __forceinline__ void conv_final(uint32_t rb, uint32_t yb, bool on) {
  const uint4 q0 = lds128(rb), q1 = lds128(rb + 4096), q2 = lds128(rb + 8192), q3 = lds128(rb + 12288);
  auto fin = [&](uint32_t x0, uint32_t x1, uint32_t x2, uint32_t x3) { return hadd2(hadd2(x0, x1), hadd2(x2, x3)); };
  asm volatile("{\n.reg .pred p;\nsetp.ne.b32 p, %5, 0;\n@p st.shared.v4.b32 [%0], {%1,%2,%3,%4};\n}\n" ::"r"(yb), "r"(fin(q0.x, q1.x, q2.x, q3.x)),
               "r"(fin(q0.y, q1.y, q2.y, q3.y)), "r"(fin(q0.z, q1.z, q2.z, q3.z)), "r"(fin(q0.w, q1.w, q2.w, q3.w)), "r"((int)on) : "memory");
}
__device__ __forceinline__ void conv_tasks(Cons& c, const Params& p, int ntask, bool spare, int ch, int chstep, int c5, uint32_t dd, uint32_t dkk, int w, int lane) {
  const uint32_t sb = c.sb;
  int g = 2 + c.wg;
  uint32_t rb = sb + g * GR;
  const uint32_t yb = sb + c.wg * 8192 + c.tid * 16;
  const int gt = 8 * w + (lane >> 2) + (lane & 3);
  uint32_t a[64], hb;
  auto lda = [&](int s) {
    a[4 * s] = lds32(hb + s * 256); a[4 * s + 1] = lds32(hb + s * 256 + 128);
    a[4 * s + 2] = lds32(hb + s * 256 + 16); a[4 * s + 3] = lds32(hb + s * 256 + 144);
  };
  auto first_a = [&]() {
    hb = sb + g * GR + WBYTES - 28 + gt * 4;
    lda(0); lda(15);
  };
  c.wait_full(g);
  first_a();
#pragma unroll 1
  for (int i = 0; i < ntask; i++) {
    const uint32_t base = sb + g * GR;
    FTC(0);
    lda(1); lda(14);
    a[0] = hadd2(a[0], gt == 7 ? dd : 0u); a[2] = hadd2(a[2], gt == 3 ? dd : 0u);
    float acc[128];
    const uint32_t db = dkk + ((WPL / 16 - 1) << 16) + g * DG + WZ / 16;
    FTC(2);
    c.turn_begin();
    FTC(3);
    auto pair = [&](auto kc) {
      constexpr int k = decltype(kc)::value;
      if (k < 7) wg_fence();
      if (k == 7) c.turn_end();
      conv_step<k, 7>(acc, a, db);
      conv_step<15 - k, 7>(acc, a, db);
      if (k < 6) { lda(k + 2); lda(13 - k); }
      if (k == 0) conv_final(rb, yb, i > 0);
      if (k == 1) {
        conv_final(rb + 2048, yb + 2048, i > 0);
        __syncwarp();
        if (lane == 0 && i > 0) mbar_arrive(sb + SM_BAR + (B_EV + c.wg) * 8);
      }
      if (k == 6) dd = __bfloat16_as_ushort(p.ssd[(ch + chstep + (i == 1 ? c5 : 0)) & (DM - 1)]);
    };
    pair(IC<0>()); pair(IC<1>()); pair(IC<2>()); pair(IC<3>()); pair(IC<4>()); pair(IC<5>()); pair(IC<6>()); pair(IC<7>());
    wg_commit();
    FTC(4);
    g = conv_next(g, spare);
    ch += chstep;
    rb = base + c.tid * 16;
    if (i + 1 < ntask) c.wait_full(g);
    wg_wait<0>();
    reg_fence(acc);
    reg_fence(a);
    bar_sync(3 + c.wg, 128);
    FTC(5);
    first_a();
    const int tw = (lane & 3) + w;
    const uint32_t xb = base + w * 4096 + tw * 32 + (lane >> 2) * 4;
#pragma unroll
    for (int j = 0; j < 32; j++) {
      float v0 = acc[4 * j], v1 = acc[4 * j + 1];
      if (j > 0) { v0 += acc[j > 0 ? 4 * j - 2 : 0]; v1 += acc[j > 0 ? 4 * j - 1 : 0]; }
      uint32_t v = pack_bf16(v0, v1), ad = xb + j * 128;
      if (j == 31 && tw >= 4) { v = 0; ad -= 4096; }
      asm volatile("st.shared.b32 [%0], %1;" ::"r"(ad), "r"(v) : "memory");
    }
    c.wait_stage_free();
    FTC(6);
  }
  bar_sync(3 + c.wg, 128);
  conv_final(rb, yb, true);
  conv_final(rb + 2048, yb + 2048, true);
  c.staged(0);
}

__global__ void __cluster_dims__(2, 1, 1) __launch_bounds__(NTHREADS, 1) mega_kernel(const __grid_constant__ Params p) {
  extern __shared__ __align__(1024) uint8_t smem_raw[];
  FTS(0);
  const uint32_t sb = smem_u32(smem_raw);
  if (threadIdx.x - 64 < 32) { prefetch_tm(&p.c); prefetch_tm(&p.wuk + (blockIdx.x & 1)); }
  const int wgi = __shfl_sync(0xffffffffu, threadIdx.x >> 7, 0);
  const int warp = __shfl_sync(0xffffffffu, threadIdx.x >> 5, 0);
  const uint32_t rank = blockIdx.x & 1;
  int slot;
  {
    uint32_t smid; asm volatile("mov.u32 %0, %smid;" : "=r"(smid));
    slot = p.pref[((smid >> 1) + (threadIdx.x & (smid >> 16))) & 127];
  }
  if (warp >= 3) {
    if (elect()) {
#pragma unroll
      for (int k = 0; k < 4; k++) mbar_init(sb + SM_BAR + ((warp - 3) * 4 + k) * 8, k == 1 && warp == 7 ? 11 : warp < (k ? 7 : 8) ? 1 : 4);
      if (warp == 7) { mbar_init(sb + SM_BAR + B_TICK * 8, 1); mbar_expect_tx(sb + SM_BAR + B_SLOT * 8, 8); mbar_expect_tx(sb + SM_BAR + B_TICK * 8, 4); }
      asm volatile("fence.mbarrier_init.release.cluster;" ::: "memory");
    }
    __syncwarp();
  }
  FTS(1);
  cluster_arrive();
  slot = __shfl_sync(0xffffffffu, slot, 0);
  const int pref = slot;
  if (warp < 4) {
    asm volatile("setmaxnreg.dec.sync.aligned.u32 40;");
    if (warp == 1 + 4 * rank) {
      unsigned taken = threadIdx.x == 32;
#pragma unroll 1
      for (int n = 0; n < NSLOT; n++) {
        asm volatile("{\n.reg .pred p;\nsetp.ne.b32 p, %0, 0;\n@p atom.relaxed.gpu.global.exch.b32 %0, [%1], 1;\n}\n" : "+r"(taken) : "l"(CLAIMP(slot)) : "memory");
        if (!__any_sync(0xffffffffu, taken)) break;
        slot = slot == NSLOT - 1 ? 0 : slot + 1;
      }
    }
    cluster_wait();
    if (threadIdx.x == 32) {
      send_both(sb + SM_BAR + B_SLOT * 8, (V_SLOT - B_SLOT) * 8 + rank * 4, slot | pref << 8);
    }
    if (warp == 2) {
#pragma unroll 1
      for (int kk = 0; kk < 4; kk++) {
        const int g0 = 2 + 3 * kk;
        const uint32_t fb = sb + SM_BAR + (B_FULL + g0) * 8;
        if (elect()) {
          FTSW(kk);
          mbar_expect_tx(fb, 3 * GR);
          tma2d(sb + g0 * GR, &p.c, kk * 64, (KV_ROW(pref & 7, 0) + rank) * 128, fb);
          tma3d_mc(sb + (g0 + 1 + rank) * GR, rank ? &p.wuv : &p.wuk, 0, kk * 64, ((pref & 56) >> 1) + 2 * KV_HEAD(pref & 7, 0), fb);
        }
        if (kk < 3) {
          uint32_t c0, c1;
          asm volatile("mov.u32 %0, %clock;" : "=r"(c0));
          do asm volatile("mov.u32 %0, %clock;" : "=r"(c1)); while (c1 - c0 < (kk ? X_D2 : X_DELAY));
        }
      }
      FTSW(4);
      prefetch_tm(&p.x); prefetch_tm(&p.wq);
    }
  }
  int grp, idx, lb;
  int cn, cch, cstep;
  bool spare, redo;
  auto get_slot = [&]() {
    mbar_wait(sb + SM_BAR + B_SLOT * 8, 0);
    const uint32_t sv0 = __shfl_sync(0xffffffffu, lds32(sb + SM_BAR + V_SLOT * 8), 0), sv1 = __shfl_sync(0xffffffffu, lds32(sb + SM_BAR + V_SLOT * 8 + 4), 0);
    grp = (sv0 & 255) >> 3; idx = sv0 & 7; lb = (sv0 & 255) * 2 + rank;
    spare = grp == 8; redo = spare || sv0 != sv1;
    cn = CN_SPARE; cch = spare ? lb - NMAIN : 4 * CN_SPARE + 4 * lb; cstep = spare ? 4 : 1;
    if (FINE_MODE != 7) TS(0);
  };
  auto get_ticket = [&]() {
    mbar_wait(sb + SM_BAR + B_TICK * 8, 0);
    const int tk = __shfl_sync(0xffffffffu, lds32(sb + SM_BAR + V_TICK * 8), 0);
    cn = tk < NTICK ? 5 : 4;
    return 4 * NMAIN - 4 * lb - 4 + 2 * tk + rank;
  };

  if (wgi == 0) {
    asm volatile("setmaxnreg.dec.sync.aligned.u32 40;");
    const int lane = threadIdx.x & 31;
    cluster_arrive();
    get_slot();
    uint32_t pe = 0;
    auto acquire = [&](int g, int n, uint32_t m) {
      int i = g;
#pragma unroll 1
      do mbar_wait1(sb + SM_BAR + (B_EMPTY + i) * 8, (pe >> i) & 1); while (++i < g + n);
      pe ^= m << g;
    };
    if (warp == 3) {
      if (!spare) {
        const int s0 = lb * 16;
#pragma unroll 1
        for (int cg = 0; cg < 16; cg++) {
          if (cg == 3 || cg == 10) {
#pragma unroll 1
            for (int n = 0; n < 20 && !__any_sync(0xffffffffu, mbar_try(sb + SM_BAR + B_SLOT * 8, cg == 3)); n++);
          } else if (cg < 3) __nanosleep(US0);
          if (cg == TKCG && lane == rank * 32) send_both(sb + SM_BAR + B_TICK * 8, (V_TICK - B_TICK) * 8, atomicInc(FLAG(F_TICK), 0x7fffffffu));
          const int ch = cg * 64 + 2 * lane;
          const uint32_t* kp = reinterpret_cast<const uint32_t*>(p.ak + (size_t)s0 * DM + ch);
          const uint32_t* vp = reinterpret_cast<const uint32_t*>(p.av + (size_t)s0 * DM + ch);
          const uint4 sw = __ldg(reinterpret_cast<const uint4*>(p.shk + ch * 4));
          uint32_t k3 = 0, k2 = 0, k1 = 0, k0 = 0, up = 0;
          if (lb > 0) { k3 = ldg_stream(kp - 4 * 512); k2 = ldg_stream(kp - 3 * 512); k1 = ldg_stream(kp - 2 * 512); k0 = ldg_stream(kp - 512); up = ldg_stream(vp - 512); }
          const uint32_t w0 = __byte_perm(sw.x, sw.z, 0x5410), w1 = __byte_perm(sw.x, sw.z, 0x7632);
          const uint32_t w2 = __byte_perm(sw.y, sw.w, 0x5410), w3 = __byte_perm(sw.y, sw.w, 0x7632);
          up = hmul2(hfma2(k0, w0, hfma2(k1, w1, hfma2(k2, w2, hmul2(k3, w3)))), up);
#pragma unroll 1
          for (int hb = 0; hb < 2; hb++) {
            uint32_t kk[8], u[8];
#pragma unroll
            for (int r = 0; r < 8; r++) { kk[r] = ldg_stream(kp + r * 512); u[r] = ldg_stream(vp + r * 512); }
#pragma unroll
            for (int r = 0; r < 8; r++) {
              k3 = k2; k2 = k1; k1 = k0; k0 = kk[r];
              u[r] = hmul2(hfma2(k0, w0, hfma2(k1, w1, hfma2(k2, w2, hmul2(k3, w3)))), u[r]);
            }
            if (lane == 0) asm volatile("cp.async.bulk.wait_group.read 0;" ::: "memory");
            __syncwarp();
            const uint32_t dst = sb + SM_UST + lane * 32 + ((lane & 4) << 2);
#pragma unroll
            for (int cc = 0; cc < 2; cc++) {
              const uint32_t sel = cc ? 0x7632 : 0x5410;
              asm volatile("st.shared.v4.b32 [%0], {%1,%2,%3,%4};" ::"r"(dst + cc * 1024), "r"(__byte_perm(u[6], u[5], sel)), "r"(__byte_perm(u[4], u[3], sel)),
                           "r"(__byte_perm(u[2], u[1], sel)), "r"(__byte_perm(u[0], up, sel)) : "memory");
              asm volatile("st.shared.v4.b32 [%0], {%1,%2,%3,%4};" ::"r"((dst ^ 16) + cc * 1024), "r"(__byte_perm(u[7], u[6], sel)), "r"(__byte_perm(u[5], u[4], sel)),
                           "r"(__byte_perm(u[3], u[2], sel)), "r"(__byte_perm(u[1], u[0], sel)) : "memory");
            }
            fence_async_smem();
            __syncwarp();
            if (lane == 0) {
              asm volatile("cp.async.bulk.tensor.3d.global.shared::cta.bulk_group [%0, {%2, %3, %4}], [%1];\ncp.async.bulk.commit_group;"
                           ::"l"(&p.w), "r"(sb + SM_UST), "r"(WZ / 2 + lb * 16 + (hb ^ 1) * (WPL / 2)), "r"(cg * 32), "r"(0) : "memory");
            }
            up = u[7];
            kp += 8 * 512; vp += 8 * 512;
          }
          if ((cg & (cg + 1)) == 0 && lane == 0) {
            asm volatile("cp.async.bulk.wait_group 0;" ::: "memory");
            fence_release();
            flag_add(FLAG(F_U + 32 - __clz(cg)));
          }
          TSW(10 + cg);
        }
        prefetch_tm(&p.wo); prefetch_tm(&p.x3); prefetch_tm(&p.y3); prefetch_tm(&p.out);
        if (P3PF) {
          const int rt = 2 * grp + rank;
          unsigned v;
          asm volatile("ld.acquire.gpu.global.u32 %0, [%1];" : "=r"(v) : "l"(FLAG(F_CTX + rt * 2)) : "memory");
#pragma unroll 1
          for (int kb = P3PF0; kb < P3PF0 + P3PF; kb++) {
            const uint8_t* a = lane < 16 ? g_cimg + (unsigned)((rt * 64 + kb) * GR + (idx * 16 + lane) * 128) : (const uint8_t*)p.wop + (unsigned)(kb * 64 * DM * 2 + (lb * 8 + (lane & 7)) * 128);
            if (lane < 24 && v == 32) asm volatile("prefetch.global.L2 [%0];" ::"l"(a));
          }
        }
      } else {
#pragma unroll 1
        for (int i = 0, g = 2; i < 32; i++) {
          acquire(g, 2, 3);
          if (elect()) {
            const uint32_t fb = sb + SM_BAR + (B_FULL + g) * 8;
            if (i == 0) { mbar_expect_tx(fb - 8, 2048); bulk_g2s(sb + GR, p.gate_w, 2048, fb - 8); }
            mbar_expect_tx(fb, 2 * GR);
            tma3d(sb + g * GR, &p.x3, 0, (lb - NMAIN) * 512 + (i >> 3) * 128, (i & 7) * 2, fb);
          }
          g = g == NGR - 2 ? 2 : g + 2;
        }
        bar_arrive(5, 64);
      }
      unsigned long long t0, t1;
      asm volatile("mov.u64 %0, %globaltimer;" : "=l"(t0));
      auto check = [&]() {
        asm volatile("mov.u64 %0, %globaltimer;" : "=l"(t1));
        if (t1 - t0 > 2000000000ull) __trap();
      };
      if (!spare) {
        unsigned v;
        do {
          __nanosleep(PSL);
          check();
          asm volatile("ld.acquire.gpu.global.u32 %0, [%1];" : "=r"(v) : "l"(FLAG(lane & 1 ? F_Y + idx : F_GATE)) : "memory");
        } while (__any_sync(0xffffffffu, v < (lane & 1 ? 128 : 32)));
        __syncwarp();
        if (lane == 0) mbar_arrive(sb + SM_BAR + B_SLOT * 8);
      }
      if (lane == 0) {
        while (!mbar_try(sb + SM_BAR + B_DONE * 8, 0)) check();
      }
    } else if (warp != 0) {
      const int w = warp - 1;
      int ne = 12 + (CN_SPARE + 1 - w) / 2, c5 = 0;
      uint32_t p0 = 0;
      int cg = 2 + w, ch = cch + w * cstep;
#pragma unroll 1
      for (int e = spare ? 12 : 0; e < ne; e++) {
        const int rnd = e >= 6, k = e - 6 * rnd, rt = k == 4 ? idx : 15 - idx;
        uint8_t* dst = k < 4 ? g_kv + (size_t)(((k & 1) * 16 + 2 * grp + KV_HEAD(idx, k >> 1)) * 16 + KV_ROW(idx, k >> 1) + rank) * 32768 + w * 8192
                     : k < 6 ? g_cimg + (size_t)(rt * 32 + 16 * rnd + 2 * grp + rank) * 32768 + (w ^ (k & 1)) * 8192
                             : reinterpret_cast<uint8_t*>(g_yT + (size_t)ch * SEQ);
        const uint32_t src = sb + w * 8192 + (k == 4 ? 2 * GR : 0);
        if (e == 11) { c5 = get_ticket(); ne = 12 + ((cn + 1 - w) >> 1); }
        if (e == 6) flag_wait(FLAG(F_AD + grp), 32);
        mbar_wait1(sb + SM_BAR + (B_EV + (k == 4 ? 2 : 0) + w) * 8, k == 4 ? rnd : p0);
        if (k != 4) p0 ^= 1;
        if (lane < 4 && k >= 6 && (!spare || e < ne - 6)) mbar_arrive_cluster(sb + SM_BAR + (B_EMPTY + cg) * 8, lane & 1);
        fence_async_smem();
        if (elect()) {
          const uint32_t cs = k >= 6 ? 4096 : 1024;
#pragma unroll 1
          for (uint32_t i = 0; i < (k >= 6 ? 4096 : 16384); i += cs) {
            const uint32_t o = i + (i & 8192);
            asm volatile("cp.async.bulk.global.shared::cta.bulk_group [%0], [%1], %2;" ::"l"(dst + o), "r"(src + o), "r"(cs) : "memory");
            asm volatile("cp.async.bulk.commit_group;\ncp.async.bulk.wait_group.read 1;" ::: "memory");
          }
          asm volatile("cp.async.bulk.wait_group 0;" ::: "memory");
          if (k != 4) mbar_arrive(sb + SM_BAR + (B_FREE + w) * 8);
        }
        __syncwarp();
        if (lane < (k == 4 ? 4 : e == 11 || (e == ne - 1 && !spare) ? 2 : 0))
          mbar_arrive_cluster(sb + SM_BAR + (B_EMPTY + (k == 4 ? 2 : e == 11) + (lane >> 1)) * 8, lane & 1);
        if (k >= 3) {
          fence_release();
          const unsigned fl = k == 3 ? F_KV + rnd * 8 + grp : k < 6 ? F_CTX + rt * 2 + rnd : F_Y + ((unsigned)ch >> 7);
          if (lane <= (e == 5)) flag_add(FLAG(lane ? F_AD + grp : fl));
        }
        if (k >= 6) { cg = conv_next(cg, spare); ch += 2 * cstep + (k == 7 ? c5 : 0); }
      }
      if (lane == 0) mbar_arrive(sb + SM_BAR + B_DONE * 8);
    } else {
#pragma unroll 1
      for (int rnd = 0; rnd < (spare ? 0 : 2); rnd++) {
        const int hp = 16 * rnd + 2 * grp, head = hp + rank;
#pragma unroll 1
        for (int kk = rnd || redo ? 0 : 4; kk < 32; kk++) {
          const int g0 = 2 + 3 * (kk & 3);
          acquire(g0, kk < 4 ? 3 : 1, 7);
          if (elect()) {
            const uint32_t fb = sb + SM_BAR + (B_FULL + g0) * 8;
            mbar_expect_tx(fb, 3 * GR);
            if (kk < 16) {
              tma2d(sb + g0 * GR, &p.c, (kk & 7) * 64, (KV_ROW(idx, kk >> 3) + rank) * 128, fb);
              tma3d_mc(sb + (g0 + 1 + rank) * GR, rank ? &p.wuv : &p.wuk, 0, (kk & 7) * 64, (hp + KV_HEAD(idx, kk >> 3)) * 2, fb);
            } else {
              tma2d_mc(sb + (g0 + rank) * GR, &p.x, (kk - 16) * 64, (rank ? 15 - idx : idx) * 128, fb);
              tma3d(sb + (g0 + 2) * GR, &p.wq, 0, (kk - 16) * 64, head * 2, fb);
            }
          }
        }
        flag_wait(FLAG(F_KV + rnd * 8 + grp), 32);
        fence_async_all();
        acquire(2, 1, 3);
        int g0 = 4;
#pragma unroll 1
        for (int n = 0; n < 36; n += n == 0 || n == 33 ? 2 : 1) {
          const int it = (n >> 1) - (n & 1);
          const int blk = it & 15 ? (it <= idx ? it - 1 : 15 - it) : it ? 15 - idx : idx;
          acquire(g0, n < 6 ? 2 : 1, 3);
          if (elect()) {
            const uint32_t fb = sb + SM_BAR + (B_FULL + g0) * 8;
            if (n == 5) mbar_arrive(sb + SM_BAR + B_SLOT * 8);
            mbar_expect_tx(fb, 2 * GR);
            bulk_g2s(sb + g0 * GR, g_kv + (unsigned)((((n & 1) * 16 + (head & 15)) * 16 + blk) * 32768), 2 * GR, fb);
          }
          g0 = n == 13 ? 12 : g0 == 12 ? 4 : g0 + 2;
        }
      }
      int c5 = 0;
      if (spare) { bar_sync(5, 64); pe = 0x3FC0; }
      else c5 = get_ticket();
      auto conv_fill = [&](int g, int ch) {
        acquire(g, 1, 1);
        if (elect()) {
          const uint32_t fb = sb + SM_BAR + (B_FULL + g) * 8;
          if (!spare) FTP(64 + 48 + g);
          mbar_expect_tx(fb, WBYTES + 4096);
          bulk_g2s<true>(sb + g * GR, g_w + (size_t)ch * WSTRIDE, WBYTES, fb);
          bulk_g2s<true>(sb + g * GR + WBYTES, p.ssk + (size_t)ch * SEQ, 4096, fb);
        }
      };
#pragma unroll 1
      for (int i = 0, g = 2; i < cn; i++) {
        if ((i & 15) == 0) { flag_wait(FLAG(F_U + (spare ? 32 - __clz(i >> 4) : 4)), NMAIN); fence_async_all(); }
        conv_fill(g + (i & 1), cch + i * cstep + (i == 4 ? c5 : 0));
        if (i & 1) g = conv_next(g, spare);
      }
      if (!spare) {
        const int rt = 2 * grp + rank, ct = idx;
        int g0 = P3G, top = 12;
        const uint8_t* src = g_cimg + (unsigned)(rt * 64 * GR);
#pragma unroll 1
        for (int kb = 0; kb < 64; kb++) {
          if (!(kb & 31)) { flag_wait(FLAG(F_CTX + rt * 2 + (kb >> 5)), 32); fence_async_all(); }
          acquire(g0, kb < 11 ? 2 : 1, 3);
          if (elect()) {
            const uint32_t fb = sb + SM_BAR + (B_FULL + g0) * 8;
            if (kb < 16) FTP(48 + kb);
            mbar_expect_tx(fb, 2 * GR);
            bulk_g2s<true>(sb + g0 * GR, src, GR, fb);
            tma2d_mc<true>(sb + (g0 + 1) * GR + rank * 8192, &p.wo, ct * 128 + rank * 64, kb * 64, fb);
          }
          src += GR;
          g0 = g0 == (kb < XK ? 12 : kb < YK ? 10 : 8) ? (kb == 3 ? 2 : 0) : g0 + 2;
          if (kb == XK || (kb >= YK && top == P3Y && (kb == 63 || mbar_test(sb + SM_BAR + B_SLOT * 8, 1)))) {
            const bool j = kb != XK;
            if (j) { mbar_wait1(sb + SM_BAR + B_SLOT * 8, 1); fence_async_all(); }
            acquire(top, 1, 0);
            if (elect()) {
              const uint32_t fb = sb + SM_BAR + (B_FULL + top) * 8;
              mbar_expect_tx(fb, j ? 2 * GR + 512 : 2 * GR);
              if (j) bulk_g2s(sb + SM_GATE, g_gate + (unsigned)(rt * 128), 512, fb);
              tma3d(sb + top * GR, j ? &p.y3 : &p.x3, 0, (j ? ct : rt) * 128, (j ? rt : ct) * 2, fb);
            }
            top -= 2;
          }
        }
        unsigned n = 0;
        if (lane == 0) n = atomicInc(FLAG(F_EXIT), 0x7fffffffu);
        if (__any_sync(0xffffffffu, n == NMAIN - 1)) {
#pragma unroll
          for (int i = lane; i < 96; i += 32) *reinterpret_cast<uint2*>(FLAG(i)) = make_uint2(0, 0);
        }
      }
      if (lane == 0) mbar_arrive(sb + SM_BAR + B_DONE * 8);
    }
    __syncwarp();
    cluster_wait();
  } else {
    asm volatile("setmaxnreg.inc.sync.aligned.u32 232;");
    FTS(2);
    Cons c;
    c.sb = sb; c.pf = 0; c.wg = wgi - 1; c.tid = threadIdx.x & 127;
    const int lane = threadIdx.x & 31, t = lane & 3;
    const int row = c.wg * 64 + (warp & 3) * 16 + (lane >> 2);
    const uint32_t dkk = desc_k(sb), dk0 = dkk + c.wg * 512, dm0 = desc_mn<8192>(sb), dv0 = desc_mn<16384>(sb);
    const uint32_t dsw = DG + 512 - c.wg * 1024;
    if (c.wg == 1) bar_arrive(1, 256);
    c.pfree = 1;
    asm("mapa.shared::cluster.u32 %0, %1, %2;" : "=r"(c.relb) : "r"(sb + SM_BAR + (B_EMPTY + (c.tid >> 1)) * 8), "r"(c.tid & 1));
    c.zero = p.zero;
    c.rnd = 0;
    const uint32_t stg = sb + (c.wg * 64 + (warp & 3) * 16 + ((lane >> 3) & 1) * 8 + (lane & 7)) * 128 + (((lane >> 4) ^ (lane & 7)) << 4);

    uint32_t dd0;
    auto load_dd = [&]() { asm volatile("ld.global.nc.u16 %0, [%1];" : "=r"(dd0) : "l"(p.ssd + (unsigned)(cch + c.wg * cstep + (lane & c.zero)))); };
    int pass = c.zero;
#pragma unroll 1
    do {
    if (pass) {
      load_dd();
#pragma unroll 1
      for (int g = 2; g < NGR; g += 3) { mbar_wait(sb + SM_BAR + (B_FULL + g) * 8, 0); c.release(g, 3); }
      c.pf = 0x924;
    if (spare) {
      c.wait_full(1);
      int g = 2;
#pragma unroll 1
      for (int r = 0; r < 4; r++) {
        float d[4] = {0.f, 0.f, 0.f, 0.f}, e[4] = {0.f, 0.f, 0.f, 0.f};
#pragma unroll 1
        for (int kb = 0; kb < 16; kb += 2) {
          c.wait_full(g);
          wg_fence();
#pragma unroll 1
          for (int k = 0; k < 4; k++) {
            mma_ss_n8(d, dk0 + g * DG + k * 2, dkk + DG + kb * 8 + k * 2);
            mma_ss_n8(e, dk0 + (g + 1) * DG + k * 2, dkk + DG + kb * 8 + 8 + k * 2);
          }
          wg_commit();
          wg_wait<0>();
          c.release(g, 2);
          g = g == NGR - 2 ? 2 : g + 2;
        }
        reg_fence(d); reg_fence(e);
        d[0] += e[0]; d[2] += e[2];
        if (t == 0) {
          float* gp = g_gate + (unsigned)((lb - NMAIN) * 512 + r * 128 + row);
          gp[0] = rcp(1.f + ex2(-1.4426950408889634f * d[0])); gp[8] = rcp(1.f + ex2(-1.4426950408889634f * d[2]));
        }
      }
      fence_release();
      __syncwarp();
      if (lane == 0) flag_add(FLAG(F_GATE));
      TS(1);
    }
    } else cluster_wait();
    get_slot();
    } while (redo && !pass++);
    FTS(3);
    const float dmask = (float)(2 * t - (row & 63));
    int c5 = 0;
    uint32_t pv[32];
#pragma unroll 1
    for (int rnd = 0; rnd < (spare ? 0 : 2); rnd++) {
      float O[64];
      FTM(rnd * 8);
      FTG(0);
      FTH(56, c.rnd == rnd);
      c.wait_full(2);
      FTM(rnd * 8 + 1);
      FTH(57, c.rnd == rnd);
#pragma unroll 1
      for (int tile = c.zero; tile < 2; tile++) {
        float acc[128];
        const bool single = tile == 0;
        {
          FTG(tile * 32 + 1);
          const uint32_t a = dk0 + 2 * DG, b = dm0 + 3 * DG;
          c.turn_begin();
          FTG(tile * 32 + 2);
          FTH(58, c.rnd == rnd);
          wg_fence();
          mma_ss_n256_init<1>(acc, a, b);
#pragma unroll
          for (int k = 1; k < 4; k++) mma_ss_n256<1>(acc, a + k * 2, b + k * 128);
          wg_commit();
          if (single) c.turn_end();
          if (single && rnd && !c.wg) { stsm_frag(pv, stg); c.staged(0); }
          FTG(tile * 32 + 3);
        }
#pragma unroll 1
        for (int kb = 1; kb < 8; kb++) {
          const int g0 = 2 + 3 * (kb & 3);
          const uint32_t a = dk0 + g0 * DG, b = dm0 + (g0 + 1) * DG;
          const bool second = (kb == 1 && !single) || kb == 7;
          FTG(tile * 32 + kb * 4);
          if (!second) { wg_wait<0>(); c.release(2 + 3 * ((kb - 1) & 3), 3); }
          FTG(tile * 32 + kb * 4 + 1);
          c.wait_full(g0);
          if (!second) c.turn_begin();
          FTG(tile * 32 + kb * 4 + 2);
          wg_fence();
#pragma unroll
          for (int k = 0; k < 4; k++) mma_ss_n256<1>(acc, a + k * 2, b + k * 128);
          wg_commit();
          if (kb != 6) c.turn_end();
          if (second) { wg_wait<1>(); c.release(2 + 3 * ((kb - 1) & 3), 3); }
          FTG(tile * 32 + kb * 4 + 3);
          FTH(58 + kb, c.rnd == rnd || kb > 3);
          if (tile == 1 && kb == 3) { c.wait_stage_free(); stsm_frag<0, 4>(pv, stg); }
          if (tile == 1 && kb == 4) { stsm_frag<4, 8>(pv, stg); c.staged(0); }
        }
        c.rnd = rnd;
        c.wait_stage_free();
        const bool nxt = c.try_full(2);
        wg_wait<0>();
        reg_fence(acc);
        c.release(11, 3);
        pack_frag_scaled(acc, pv, SM_C, SM_C);
        stsm_frag(pv, stg);
        c.staged(0);
        pack_frag<64>(acc, pv);
        pin32(pv, sb);
        FTG(32 + tile * 32);
        if (!nxt) mbar_wait(sb + SM_BAR + (B_FULL + 2) * 8, (c.pf >> 2) & 1);
        c.pf ^= 4;
      }
      TS(1 + rnd * 3);
      FTM(rnd * 8 + 2);
      {
        float qa[64];
        float (&qb)[64] = O;
        {
          FTG(65);
          const uint32_t a = dk0 + 2 * DG, b = dm0 + 4 * DG;
          c.turn_begin();
          FTG(66);
          wg_fence();
          mma_ss_n128_init<1>(qa, a, b);
          mma_ss_n128_init<1>(qb, a + dsw, b);
#pragma unroll
          for (int k = 1; k < 4; k++) {
            mma_ss_n128<1>(qa, a + k * 2, b + k * 128);
            mma_ss_n128<1>(qb, a + dsw + k * 2, b + k * 128);
          }
          wg_commit();
          FTG(67);
        }
#pragma unroll 1
        for (int kb = 1; kb < 16; kb++) {
          const int g0 = 2 + 3 * (kb & 3);
          const uint32_t a = dk0 + g0 * DG, b = dm0 + (g0 + 2) * DG;
          const bool second = kb == 1 || kb == 15;
          FTG(64 + kb * 4);
          if (!second) { wg_wait<0>(); c.release(2 + 3 * ((kb - 1) & 3), 3); }
          FTG(65 + kb * 4);
          c.wait_full(g0);
          if (!second) c.turn_begin();
          FTG(66 + kb * 4);
          FTH(kb - 14, kb < 14);
          wg_fence();
#pragma unroll
          for (int k = 0; k < 4; k++) {
            mma_ss_n128<1>(qa, a + k * 2, b + k * 128);
            mma_ss_n128<1>(qb, a + dsw + k * 2, b + k * 128);
          }
          wg_commit();
          if (kb != 14) c.turn_end();
          if (second) { wg_wait<1>(); c.release(2 + 3 * ((kb - 1) & 3), 3); }
          FTG(67 + kb * 4);
          FTH(2, kb < 15);
          if (kb == QFLUSH) { c.wait_stage_free(); stsm_frag<0, 4>(pv, stg); }
          if (kb == QFLUSH + 1) { stsm_frag<4, 8>(pv, stg); c.staged(0); }
        }
        c.wait_stage_free();
        mbar_wait(sb + SM_BAR + (B_EMPTY + 2) * 8, rnd ^ !redo);
        FTM(rnd * 8 + 3);
        FTH(3, 0);
        wg_wait<0>();
        reg_fence(qa); reg_fence(qb);
        FTH(4, 0);
        c.release(11, 3);
        pack_frag<0>(qa, pv);
        stsm_frag(pv, stg + 2 * GR);
        if (c.wg == 0) {
          pack_frag<0>(qb, pv);
          stsm_frag(pv, stg);
        }
        FTH(6, 0);
        fence_async_smem();
        FTH(7, 0);
        c.wait_full(4);
      }
      TS(2 + rnd * 3);
      FTM(rnd * 8 + 4);
      FTH(5, 0);
      {
        const int nA = idx + 1;
        uint32_t (&P)[32] = pv;
        SoftState z;
        z.m0 = z.m1 = z.l0 = z.l1 = 0.f; z.shifted = c.zero;
#pragma unroll 1
        for (int seg = c.zero;; seg++) {
        if (c.wg == seg) attn_half(c, O, P, z, dk0, dkk, dv0, dmask, seg);
        if (seg) break;
        FTM(rnd * 8 + 5);
        int gk = c.wg ? 4 : 6, gv = c.wg ? 4 : 8;
        uint32_t dq = dk0 + (1 - c.wg < nA ? 2 * DG : 0), dk = dkk + gk * DG;
#pragma unroll 1
        for (int it = 1 - c.wg; it < 17 - c.wg; it++) {
          float S[64];
          FTA(it * 7 + 0); FTH((it < 3 ? 8 + it * 8 : it * 8 - 88) + 0, it >= 3 && it < 15);
          c.turn_begin();
          FTA(it * 7 + 2); FTH((it < 3 ? 8 + it * 8 : it * 8 - 88) + 1, it >= 3 && it < 15);
          wg_fence();
          issue_qk(S, dq, dk);
          wg_commit();
          const uint32_t dv = dv0 + gv * DG;
          uint32_t relk = c.relb + gk * 8, relv = c.relb + gv * 8;
          gk = it == 6 ? 12 : gv == 12 ? 4 : gv + 2;
          gv = it == 16 ? gk : gk == 12 ? 4 : gk + 2;
          uint32_t fk = sb + SM_BAR + (B_FULL + gk) * 8, fv = sb + SM_BAR + (B_FULL + gv) * 8, park = (c.pf >> gk) & 1, parv = (c.pf >> gv) & 1;
          c.pf ^= (1u << gk) | (1u << gv);
          dq = dk0 + (it + 1 < nA ? 2 * DG : 0); dk = dkk + gk * DG;
          float lo0 = z.l0, lo1 = z.l1;
          const bool first = it == nA || it == 0;
          if (it == nA) {
            lo0 = rcp(quad_sum(lo0)); lo1 = rcp(quad_sum(lo1));
            z.m0 = z.m1 = z.l0 = z.l1 = 0.f; z.shifted = 0;
          }
          float s0, s1, d0 = z.m0, d1 = z.m1;
          int pre = z.shifted || (it & 15) == 0;
          float lim = first ? -1.f : SM_LIMIT;
          asm volatile("" : "+r"(relk), "+r"(relv), "+r"(fk), "+r"(fv), "+r"(park), "+r"(parv), "+r"(dq), "+r"(dk), "+r"(pre), "+f"(lim), "+f"(d0), "+f"(d1), "+f"(z.l0), "+f"(z.l1));
          if (it + c.wg > 1) {
            issue_pv<0>(O, P, dv, it != nA + 1 && it != 1, true);
            issue_pv<1>(O, P, dv, 1, true);
            c.turn_end();
          } else if (it) {
            issue_pv<0>(O, P, dv, 0, true);
            wg_commit(); wg_commit();
            c.turn_end();
          } else stage_q2(c, O, P, stg);
          FTA(it * 7 + 3); FTH((it < 3 ? 8 + it * 8 : it * 8 - 88) + 2, it >= 3 && it < 15);
          wg_wait<4>();
          reg_fence(S);
          FTA(it * 7 + 4); FTH((it < 3 ? 8 + it * 8 : it * 8 - 88) + 3, it >= 3 && it < 15);
          if (c.tid < 4) asm volatile("mbarrier.arrive.shared::cluster.b64 _, [%0];" ::"r"(relk) : "memory");
#pragma unroll 1
          for (int pass = 0;; pass++) {
            if (pre) {
              if ((it & 15) == 0) mask_diag(S, dmask);
              if (z.shifted) shift_scores(S, d0, d1);
            }
            float tr[ROT];
            exp_quarter<0, 3>(S, P, tr, s0, s1, sb);
            exp_quarter<1, 2>(S, P, tr, s0, s1, sb);
            exp_quarter<2, 1>(S, P, tr, s0, s1, sb);
            exp_quarter<3, 0>(S, P, tr, s0, s1, sb);
            reg_fence(O);
            if (c.tid < (pass || !it ? 0 : 4)) asm volatile("mbarrier.arrive.shared::cluster.b64 _, [%0];" ::"r"(relv) : "memory");
            const bool ok = mbar_test(fk, park) & mbar_test(fv, parv);
            if (!ok) lim = -1.f;
            FTA(it * 7 + 5); FTH((it < 3 ? 8 + it * 8 : it * 8 - 88) + 4, it >= 3 && it < 15);
            if (!__any_sync(0xffffffffu, !(s0 <= lim && s1 <= lim))) break;
            if (pass) break;
            if (it == nA) {
              uint32_t pk[32];
              pack_frag_scaled(O, pk, lo0, lo1);
              stsm_frag(pk, stg + 2 * GR);
              c.staged(1);
            }
            if (!ok) { mbar_wait(fk, park); mbar_wait(fv, parv); }
            if (!soft_unsafe(s0, s1, first)) break;
            soft_fix(S, O, z, first, d0, d1);
            pre = 1;
          }
          z.l0 += s0; z.l1 += s1;
          FTA(it * 7 + 6); FTH((it < 3 ? 8 + it * 8 : it * 8 - 88) + 5, it >= 3 && it < 15);
        }
        FTM(rnd * 8 + 6);
        }
        FTH(48, 0);
        load_dd();
        c.turn_begin();
        FTH(49, 0);
        wg_fence();
        issue_pv<0>(O, P, dv0 + 12 * DG, 1, true);
        issue_pv<1>(O, P, dv0 + 12 * DG, 1, !c.wg);
        c.turn_end();
        z.l0 = rcp(quad_sum(z.l0)); z.l1 = rcp(quad_sum(z.l1));
        if (rnd) c5 = get_ticket();
        wg_wait<0>();
        reg_fence(O); reg_fence(P);
        FTH(50, 0);
        c.release(12, 2);
        pack_frag_scaled(O, P, z.l0, z.l1);
        if (rnd || c.wg) { stsm_frag(P, stg); c.staged(0); }
        FTM(rnd * 8 + 7);
        FTH(51, 0);
      }
      TS(3 + rnd * 3);
    }
    conv_tasks(c, p, (cn + 1 - c.wg) >> 1, spare, cch + c.wg * cstep, 2 * cstep, c5, dd0, dkk, warp & 3, lane);
    if (c.wg == 1) c.pf ^= 0x14;
    if (c.wg == (cn & 1)) c.turn_begin();
    TS(7);
    if (!spare) {
      const int rt = 2 * grp + rank, ct = idx;
      float acc[64];
      int g0 = P3G + 2, pg = P3G;
      {
        FTO(0);
        c.wait_full(P3G);
        FTO(1);
        const uint32_t a = dk0 + P3G * DG, b = dm0 + (P3G + 1) * DG;
        wg_fence();
        mma_ss_n128_init<1>(acc, a, b);
#pragma unroll
        for (int k = 1; k < 4; k++) mma_ss_n128<1>(acc, a + k * 2, b + k * 128);
        wg_commit();
      }
#pragma unroll 1
      for (int kb = 1; kb < 64; kb++) {
        FTO(kb * 2);
        c.wait_full(g0);
        if (kb == STR && !c.wg) c.turn_begin();
        FTO(kb * 2 + 1);
        const uint32_t a = dk0 + g0 * DG, b = dm0 + (g0 + 1) * DG;
        wg_fence();
#pragma unroll
        for (int k = 0; k < 4; k++) mma_ss_n128<1>(acc, a + k * 2, b + k * 128);
        wg_commit();
        if (kb < STR) { wg_wait<1>(); c.release(pg, kb <= 59 ? 2 : 0); }
        if (kb == FDUMP_KB) FTDUMP();
        pg = g0;
        g0 = g0 == (kb < XK ? 12 : kb < YK ? 10 : 8) ? (kb == 3 ? 2 : 0) : g0 + 2;
      }
      if (c.wg) c.turn_end();
      cluster_arrive();
      c.wait_full(P3X);
      c.wait_full(P3Y);
      const float g0f = __uint_as_float(lds32(sb + SM_GATE + row * 4)), g1f = __uint_as_float(lds32(sb + SM_GATE + row * 4 + 32));
      const uint32_t gp0 = pack_bf16(g0f, g0f), gp1 = pack_bf16(g1f, g1f);
      const float h0 = 1.f - g0f, h1 = 1.f - g1f;
      const int w = warp & 3;
      const uint32_t xa = stg + P3X * GR;
      const uint32_t ya = sb + P3Y * GR + c.wg * 16384 + ((lane >> 4) * 8 + (lane & 7)) * 128 + (((2 * w + ((lane >> 3) & 1)) ^ (lane & 7)) << 4);
      uint32_t xy[32];
      auto prep = [&](int j0, int j1) {
#pragma unroll
        for (int jj = j0; jj < j1; jj++) {
          uint32_t x[4], y[4];
          asm volatile("ldmatrix.sync.aligned.m8n8.x4.shared.b16 {%0,%1,%2,%3}, [%4];" : "=r"(x[0]), "=r"(x[1]), "=r"(x[2]), "=r"(x[3]) : "r"((xa ^ ((jj & 3) << 5)) + (jj >> 2) * 16384) : "memory");
          asm volatile("ldmatrix.sync.aligned.m8n8.x4.trans.shared.b16 {%0,%1,%2,%3}, [%4];" : "=r"(y[0]), "=r"(y[1]), "=r"(y[2]), "=r"(y[3]) : "r"(ya + jj * 2048) : "memory");
#pragma unroll
          for (int i = 0; i < 4; i++) xy[4 * jj + i] = hmul2(x[i], y[i]);
        }
      };
      prep(0, 4);
      wg_wait<0>();
      reg_fence(acc);
      TS(8);
#pragma unroll
      for (int hf = 0; hf < 2; hf++) {
#pragma unroll
        for (int i = 16 * hf; i < 16 * hf + 16; i++) {
          const float h = (i & 1) ? h1 : h0;
          xy[i] = hfma2((i & 1) ? gp1 : gp0, xy[i], pack_bf16(acc[2 * i] * h, acc[2 * i + 1] * h));
        }
        if (hf) stsm_frag<4, 8>(xy, xa); else stsm_frag<0, 4>(xy, xa);
        fence_async_smem();
        __syncwarp();
        const int r0 = c.wg * 64 + w * 16;
        if (lane == 0) tma2d_store(&p.out, sb + (P3X + hf) * GR + r0 * 128, ct * 128 + hf * 64, rt * 128 + r0);
        if (!hf) prep(4, 8);
      }
      if (lane == 0) asm volatile("cp.async.bulk.commit_group;\ncp.async.bulk.wait_group.read 0;" ::: "memory");
    } else { FTDUMP(); cluster_arrive(); }
    if (lane == 0) mbar_arrive(sb + SM_BAR + B_DONE * 8);
    __syncwarp();
    TS(9);
    cluster_wait();
  }
}

typedef CUresult (*EncFn)(CUtensorMap*, CUtensorMapDataType, cuuint32_t, void*, const cuuint64_t*, const cuuint64_t*, const cuuint32_t*,
                          const cuuint32_t*, CUtensorMapInterleave, CUtensorMapSwizzle, CUtensorMapL2promotion, CUtensorMapFloatOOBfill);

void enc2d(EncFn enc, CUtensorMap* tm, const void* base, uint64_t cols, uint64_t rows, uint32_t bc, uint32_t br) {
  cuuint64_t dims[2] = {cols, rows}; cuuint64_t strides[1] = {cols * 2}; cuuint32_t box[2] = {bc, br}; cuuint32_t es[2] = {1, 1};
  enc(tm, CU_TENSOR_MAP_DATA_TYPE_BFLOAT16, 2, const_cast<void*>(base), dims, strides, box, es, CU_TENSOR_MAP_INTERLEAVE_NONE,
      CU_TENSOR_MAP_SWIZZLE_128B, CU_TENSOR_MAP_L2_PROMOTION_L2_256B, CU_TENSOR_MAP_FLOAT_OOB_FILL_NONE);
}
void enc3d(EncFn enc, CUtensorMap* tm, const void* base, uint64_t K, uint64_t N, uint32_t bk = 64) {
  cuuint64_t dims[3] = {64, K, N / 64}; cuuint64_t strides[2] = {N * 2, 128}; cuuint32_t box[3] = {64, bk, 2}; cuuint32_t es[3] = {1, 1, 1};
  enc(tm, CU_TENSOR_MAP_DATA_TYPE_BFLOAT16, 3, const_cast<void*>(base), dims, strides, box, es, CU_TENSOR_MAP_INTERLEAVE_NONE,
      CU_TENSOR_MAP_SWIZZLE_128B, CU_TENSOR_MAP_L2_PROMOTION_L2_256B, CU_TENSOR_MAP_FLOAT_OOB_FILL_NONE);
}

}

extern "C" void kernel_launch(void* const* d_in, const int* in_sizes, int n_in, void* d_out, int out_size) {
  (void)in_sizes; (void)n_in; (void)out_size;
  typedef const __nv_bfloat16* BP;
  BP xq = (BP)d_in[0], ak = (BP)d_in[1], av = (BP)d_in[2], shk = (BP)d_in[3], ssk = (BP)d_in[4], ssd = (BP)d_in[5];
  BP ckv = (BP)d_in[7], wq = (BP)d_in[8], wuk = (BP)d_in[9], wuv = (BP)d_in[10], wo = (BP)d_in[11], gw = (BP)d_in[12];

  static EncFn enc = nullptr;
  if (!enc) {
    cudaDriverEntryPointQueryResult qr;
    cudaGetDriverEntryPoint("cuTensorMapEncodeTiled", (void**)&enc, cudaEnableDefault, &qr);
    cudaFuncSetAttribute(mega_kernel, cudaFuncAttributeMaxDynamicSharedMemorySize, SMEM_BYTES);
  }
  Params p;
  void* yT = nullptr;
  cudaGetSymbolAddress(&yT, g_yT);
  enc2d(enc, &p.x, xq, DM, SEQ, 64, 128);
  enc2d(enc, &p.c, ckv, DC, SEQ, 64, 128);
  enc3d(enc, &p.wq, wq, DM, NH * HD);
  enc3d(enc, &p.wuk, wuk, DC, NH * HD);
  enc3d(enc, &p.wuv, wuv, DC, NH * HD);
  enc2d(enc, &p.wo, wo, DM, NH * HD, 64, 64);
  enc3d(enc, &p.x3, xq, SEQ, DM, 128);
  enc3d(enc, &p.y3, yT, DM, SEQ, 128);
  enc2d(enc, &p.out, d_out, DM, SEQ, 64, 16);
  {
    void* wp = nullptr;
    cudaGetSymbolAddress(&wp, g_w);
    cuuint64_t dims[3] = {WSTRIDE / 2, DM / 2, 2}; cuuint64_t strides[2] = {2 * WSTRIDE, WSTRIDE}; cuuint32_t box[3] = {16, 32, 2}; cuuint32_t es[3] = {1, 1, 1};
    enc(&p.w, CU_TENSOR_MAP_DATA_TYPE_BFLOAT16, 3, wp, dims, strides, box, es, CU_TENSOR_MAP_INTERLEAVE_NONE,
        CU_TENSOR_MAP_SWIZZLE_32B, CU_TENSOR_MAP_L2_PROMOTION_NONE, CU_TENSOR_MAP_FLOAT_OOB_FILL_NONE);
  }
  p.zero = 0;
  cudaGetSymbolAddress((void**)&p.flags, g_flags);
  for (int i = 0; i < 128; i++) {
    const int tp = i % NSLOT;
    p.pref[i] = tp < 32 ? (tp & 7) * 8 + (tp >> 3) : tp < 60 ? (1 + (tp - 32) % 7) * 8 + 4 + (tp - 32) / 7 : tp < 62 ? tp + 4 : tp - 58;
  }
  p.gate_w = gw; p.ak = ak; p.av = av; p.shk = shk; p.ssk = ssk; p.ssd = ssd; p.wop = wo;

  mega_kernel<<<132, NTHREADS, SMEM_BYTES>>>(p);
}
```

```cpp
#include <cuda_runtime.h>
#include <cuda.h>
#include <cuda_bf16.h>
#include <stdint.h>

namespace {

constexpr int SEQ = 2048, DM = 1024, DC = 512, NH = 32, HD = 128;
constexpr int GR = 16384;
constexpr int NGR = 14;
constexpr int SM_BAR = NGR * GR;
constexpr int SM_GATE = SM_BAR + 512;
constexpr int SM_UST = SM_GATE + 512;
constexpr int SMEM_BYTES = SM_UST + 2048;
constexpr int NTHREADS = 384;
#define SM_LIMIT 1.0995116e12f
#define SM_LOW 9.094947e-13f
#define CNS 103
constexpr int CN_SPARE = CNS, NTICK = 256 - 2 * CN_SPARE;
constexpr int XK = 57, YK = 62;
constexpr int STR = 61;
constexpr int P3G = 6, P3X = 12, P3Y = 10;
constexpr int NMAIN = 128;

constexpr int B_FULL = 0, B_FREE = 14, B_SLOT = 16, B_DONE = 17, B_EMPTY = 18, B_EV = 32, B_TICK = 36;
constexpr int V_SLOT = 37, V_TICK = 38;

__device__ __align__(1024) uint8_t g_kv[2 * 16 * 16 * 32768];
__device__ __align__(1024) uint8_t g_cimg[16 * NH * 32768];
__device__ __align__(1024) __nv_bfloat16 g_yT[DM * SEQ];
__device__ __align__(1024) float g_gate[SEQ];
constexpr int WZ = 256, WPL = WZ + 4096, WBYTES = 2 * WPL + 32, WSTRIDE = 2 * WPL + 128;
__device__ __align__(1024) uint8_t g_w[DM * WSTRIDE];
__device__ __align__(32) unsigned g_flags[96 * 8];
constexpr int F_KV = 0, F_CTX = 16, F_U = 48, F_AD = 56, F_Y = 64, F_GATE = 72, F_EXIT = 73, F_TICK = 74;
constexpr int NSLOT = 66;
#define FLAG(i) (&g_flags[(i) * 8])
#define CLAIMP(i) (p.flags + (i) * 8 + 1)

#define TS(slot)
#define TSW(slot)
#define FTX(i, off)
#define FTDUMP()

#define QFLUSH 4
#define TKCG 10
#define PSL 200
#define US0 800
#define X_DELAY 900
#define X_D2 600
#define P3PF 10
#define P3PF0 5
#define EXPV 1
#define SUMV 0
#define ROT 8
#define KVARR 1
#define KV_ROW(idx, t) (KVARR ? 8 * (t) + 2 * ((idx) & 3) : 2 * (idx))
#define KV_HEAD(idx, t) (KVARR ? (idx) >> 2 : (t))
#define FINE_MODE 0
#define FDUMP_KB 40
#define FINE_RND 1
#define FTA(i) do { if (FINE_MODE == 0) FTX(i, rnd ^ FINE_RND); } while (0)
#define FTG(i) do { if (FINE_MODE == 1) FTX(i, rnd ^ FINE_RND); } while (0)
#define FTM(i) do { if (FINE_MODE == 4) FTX(i, 0); } while (0)
#define FTC(k) do { if (FINE_MODE == 5) FTX((i & 7) * 8 + (k), (i >> 3) ^ FINE_RND); } while (0)
#define FTH(i, off) do { if (FINE_MODE == 6) FTX(i, (c.rnd ^ FINE_RND) | (off)); } while (0)
#define FTS(i)
#define FTSD(i)
#define FTSW(i)
#define FTP(i)
#define FTO(i) do { if (FINE_MODE == 2) FTX(i, 0); } while (0)

__device__ __forceinline__ uint32_t smem_u32(const void* p) { return (uint32_t)__cvta_generic_to_shared(p); }
__device__ __forceinline__ void mbar_init(uint32_t bar, int cnt) { asm volatile("mbarrier.init.shared::cta.b64 [%0], %1;" ::"r"(bar), "r"(cnt) : "memory"); }
__device__ __forceinline__ void mbar_expect_tx(uint32_t bar, uint32_t bytes) { asm volatile("mbarrier.arrive.expect_tx.shared::cta.b64 _, [%0], %1;" ::"r"(bar), "r"(bytes) : "memory"); }
__device__ __forceinline__ void mbar_arrive(uint32_t bar) { asm volatile("mbarrier.arrive.shared::cta.b64 _, [%0];" ::"r"(bar) : "memory"); }
__device__ __forceinline__ void mbar_arrive_cluster(uint32_t bar, uint32_t cta) {
  asm volatile("{\n.reg .b32 r;\nmapa.shared::cluster.u32 r, %0, %1;\nmbarrier.arrive.shared::cluster.b64 _, [r];\n}\n" ::"r"(bar), "r"(cta) : "memory");
}
__device__ __forceinline__ void send_both(uint32_t bar, uint32_t off, uint32_t v) {
#pragma unroll
  for (int r = 0; r < 2; r++)
    asm volatile("{\n.reg .b32 a, b;\nmapa.shared::cluster.u32 a, %0, %1;\nadd.u32 b, a, %3;\nst.async.shared::cluster.mbarrier::complete_tx::bytes.u32 [b], %2, [a];\n}\n"
                 ::"r"(bar), "r"(r), "r"(v), "r"(off) : "memory");
}
__device__ __forceinline__ bool mbar_try(uint32_t bar, uint32_t parity) {
  uint32_t ok;
  asm volatile("{\n.reg .pred p;\nmbarrier.try_wait.parity.shared::cta.b64 p, [%1], %2, 20000;\nselp.u32 %0, 1, 0, p;\n}\n" : "=r"(ok) : "r"(bar), "r"(parity) : "memory");
  return ok;
}
__device__ __forceinline__ bool mbar_test(uint32_t bar, uint32_t parity) {
  uint32_t ok;
  asm volatile("{\n.reg .pred p;\nmbarrier.test_wait.parity.shared::cta.b64 p, [%1], %2;\nselp.u32 %0, 1, 0, p;\n}\n" : "=r"(ok) : "r"(bar), "r"(parity) : "memory");
  return ok;
}
__device__ __forceinline__ void mbar_wait(uint32_t bar, uint32_t parity) {
  asm volatile("{\n.reg .pred p;\nWAIT_LOOP:\nbar.warp.sync -1;\nmbarrier.try_wait.parity.shared::cta.b64 p, [%0], %1;\n@!p bra WAIT_LOOP;\n}\n" ::"r"(bar), "r"(parity) : "memory");
}
__device__ __forceinline__ void mbar_wait1(uint32_t bar, uint32_t parity) {
  asm volatile("{\n.reg .pred p;\nWAIT_LOOP:\nbar.warp.sync -1;\nmbarrier.try_wait.parity.shared::cta.b64 p, [%0], %1, 4000;\n@!p bra WAIT_LOOP;\n}\n" ::"r"(bar), "r"(parity) : "memory");
}
constexpr uint64_t EV_FIRST = 0x12F0000000000000ull;
__device__ __forceinline__ uint32_t ldg_stream(const uint32_t* p) {
  uint32_t r; asm volatile("ld.global.nc.L1::no_allocate.L2::cache_hint.b32 %0, [%1], %2;" : "=r"(r) : "l"(p), "l"(EV_FIRST)); return r;
}
#define TMA_LD "cp.async.bulk.tensor."
#define TMA_MB ".shared::cluster.global.mbarrier::complete_tx::bytes"
__device__ __forceinline__ void tma2d(uint32_t dst, const CUtensorMap* tm, int c0, int c1, uint32_t bar) {
  asm volatile(TMA_LD "2d" TMA_MB " [%0], [%1, {%3, %4}], [%2];" ::"r"(dst), "l"(tm), "r"(bar), "r"(c0), "r"(c1) : "memory");
}
template <bool ONCE = false> __device__ __forceinline__ void tma2d_mc(uint32_t dst, const CUtensorMap* tm, int c0, int c1, uint32_t bar) {
  if (ONCE) asm volatile(TMA_LD "2d" TMA_MB ".multicast::cluster.L2::cache_hint [%0], [%1, {%3, %4}], [%2], %5, %6;"
                         ::"r"(dst), "l"(tm), "r"(bar), "r"(c0), "r"(c1), "h"((uint16_t)3), "l"(EV_FIRST) : "memory");
  else asm volatile(TMA_LD "2d" TMA_MB ".multicast::cluster [%0], [%1, {%3, %4}], [%2], %5;"
                    ::"r"(dst), "l"(tm), "r"(bar), "r"(c0), "r"(c1), "h"((uint16_t)3) : "memory");
}
__device__ __forceinline__ void tma3d(uint32_t dst, const CUtensorMap* tm, int c0, int c1, int c2, uint32_t bar) {
  asm volatile(TMA_LD "3d" TMA_MB " [%0], [%1, {%3, %4, %5}], [%2];" ::"r"(dst), "l"(tm), "r"(bar), "r"(c0), "r"(c1), "r"(c2) : "memory");
}
__device__ __forceinline__ void tma3d_mc(uint32_t dst, const CUtensorMap* tm, int c0, int c1, int c2, uint32_t bar) {
  asm volatile(TMA_LD "3d" TMA_MB ".multicast::cluster [%0], [%1, {%3, %4, %5}], [%2], %6;"
               ::"r"(dst), "l"(tm), "r"(bar), "r"(c0), "r"(c1), "r"(c2), "h"((uint16_t)3) : "memory");
}
template <bool ONCE = false> __device__ __forceinline__ void bulk_g2s(uint32_t dst, const void* src, uint32_t bytes, uint32_t bar) {
  if (ONCE) asm volatile("cp.async.bulk" TMA_MB ".L2::cache_hint [%0], [%1], %2, [%3], %4;" ::"r"(dst), "l"(src), "r"(bytes), "r"(bar), "l"(EV_FIRST) : "memory");
  else asm volatile("cp.async.bulk" TMA_MB " [%0], [%1], %2, [%3];" ::"r"(dst), "l"(src), "r"(bytes), "r"(bar) : "memory");
}
__device__ __forceinline__ void tma2d_store(const CUtensorMap* tm, uint32_t src, int c0, int c1) {
  asm volatile("cp.async.bulk.tensor.2d.global.shared::cta.bulk_group [%0, {%2, %3}], [%1];" ::"l"(tm), "r"(src), "r"(c0), "r"(c1) : "memory");
}
__device__ __forceinline__ void prefetch_tm(const CUtensorMap* tm) { asm volatile("prefetch.tensormap [%0];" ::"l"(tm) : "memory"); }
__device__ __forceinline__ void wg_fence() { asm volatile("wgmma.fence.sync.aligned;" ::: "memory"); }
__device__ __forceinline__ void wg_commit() { asm volatile("wgmma.commit_group.sync.aligned;" ::: "memory"); }
template <int N> __device__ __forceinline__ void wg_wait() { asm volatile("wgmma.wait_group.sync.aligned %0;" ::"n"(N) : "memory"); }
__device__ __forceinline__ void bar_sync(int id, int n) { asm volatile("bar.sync %0, %1;" ::"r"(id), "r"(n) : "memory"); }
__device__ __forceinline__ void bar_arrive(int id, int n) { asm volatile("bar.arrive %0, %1;" ::"r"(id), "r"(n) : "memory"); }
__device__ __forceinline__ void fence_async_smem() { asm volatile("fence.proxy.async.shared::cta;" ::: "memory"); }
__device__ __forceinline__ void fence_async_all() { asm volatile("fence.proxy.async.global;" ::: "memory"); }
__device__ __forceinline__ uint32_t pack_bf16(float lo, float hi) { uint32_t r; asm("cvt.rn.bf16x2.f32 %0, %1, %2;" : "=r"(r) : "f"(hi), "f"(lo)); return r; }
__device__ __forceinline__ float ex2(float x) { float r; asm("ex2.approx.ftz.f32 %0, %1;" : "=f"(r) : "f"(x)); return r; }
__device__ __forceinline__ float rcp(float x) { float r; asm("rcp.approx.ftz.f32 %0, %1;" : "=f"(r) : "f"(x)); return r; }
__device__ __forceinline__ void flag_wait(const unsigned* f, unsigned target) {
  unsigned v;
  do { asm volatile("ld.acquire.gpu.global.u32 %0, [%1];" : "=r"(v) : "l"(f) : "memory"); } while (__any_sync(0xffffffffu, v < target));
}
__device__ __forceinline__ bool elect() {
  uint32_t r;
  asm volatile("{\n.reg .pred p;\nelect.sync _|p, -1;\nselp.u32 %0, 1, 0, p;\n}\n" : "=r"(r));
  return r;
}
__device__ __forceinline__ void fence_release() { asm volatile("fence.release.gpu;" ::: "memory"); }
__device__ __forceinline__ void flag_add(unsigned* f) { asm volatile("red.relaxed.gpu.global.inc.u32 [%0], 0x7fffffff;" ::"l"(f) : "memory"); }
__device__ __forceinline__ void cluster_arrive() { asm volatile("barrier.cluster.arrive.relaxed.aligned;" ::: "memory"); }
__device__ __forceinline__ void cluster_wait() { asm volatile("barrier.cluster.wait.aligned;" ::: "memory"); }
__device__ __forceinline__ uint32_t hmul2(uint32_t a, uint32_t b) { uint32_t r; asm("mul.rn.bf16x2 %0, %1, %2;" : "=r"(r) : "r"(a), "r"(b)); return r; }
__device__ __forceinline__ uint32_t hadd2(uint32_t a, uint32_t b) { uint32_t r; asm("add.rn.bf16x2 %0, %1, %2;" : "=r"(r) : "r"(a), "r"(b)); return r; }
__device__ __forceinline__ uint32_t hfma2(uint32_t a, uint32_t b, uint32_t c) { uint32_t r; asm("fma.rn.bf16x2 %0, %1, %2, %3;" : "=r"(r) : "r"(a), "r"(b), "r"(c)); return r; }
__device__ __forceinline__ uint32_t lds32(uint32_t a) { uint32_t r; asm volatile("ld.shared.b32 %0, [%1];" : "=r"(r) : "r"(a) : "memory"); return r; }
__device__ __forceinline__ uint4 lds128(uint32_t a) { uint4 r; asm volatile("ld.shared.v4.b32 {%0,%1,%2,%3}, [%4];" : "=r"(r.x), "=r"(r.y), "=r"(r.z), "=r"(r.w) : "r"(a) : "memory"); return r; }
__device__ __forceinline__ uint32_t desc_k(uint32_t addr) { return ((addr & 0x3FFFF) >> 4) | (1u << 16); }
template <int LBO> __device__ __forceinline__ uint32_t desc_mn(uint32_t addr) { return ((addr & 0x3FFFF) >> 4) | ((uint32_t)(LBO >> 4) << 16); }
#define DHI "0x40000040"

#define R8(d, o) "+f"(d[o]), "+f"(d[o + 1]), "+f"(d[o + 2]), "+f"(d[o + 3]), "+f"(d[o + 4]), "+f"(d[o + 5]), "+f"(d[o + 6]), "+f"(d[o + 7])
#define R32(d, o) R8(d, o), R8(d, o + 8), R8(d, o + 16), R8(d, o + 24)
#define R64(d, o) R32(d, o), R32(d, o + 32)
#define L64 "%0,%1,%2,%3,%4,%5,%6,%7,%8,%9,%10,%11,%12,%13,%14,%15,%16,%17,%18,%19,%20,%21,%22,%23,%24,%25,%26,%27,%28,%29,%30,%31," \
            "%32,%33,%34,%35,%36,%37,%38,%39,%40,%41,%42,%43,%44,%45,%46,%47,%48,%49,%50,%51,%52,%53,%54,%55,%56,%57,%58,%59,%60,%61,%62,%63"
#define L128 L64 ",%64,%65,%66,%67,%68,%69,%70,%71,%72,%73,%74,%75,%76,%77,%78,%79,%80,%81,%82,%83,%84,%85,%86,%87,%88,%89,%90,%91,%92,%93,%94,%95," \
            "%96,%97,%98,%99,%100,%101,%102,%103,%104,%105,%106,%107,%108,%109,%110,%111,%112,%113,%114,%115,%116,%117,%118,%119,%120,%121,%122,%123,%124,%125,%126,%127"

template <int TB> __device__ __forceinline__ void mma_ss_n128(float (&d)[64], uint32_t da, uint32_t db) {
  asm volatile("{\n.reg .b64 da, db;\nmov.b64 da, {%64, " DHI "};\nmov.b64 db, {%65, " DHI "};\n"
               "wgmma.mma_async.sync.aligned.m64n128k16.f32.bf16.bf16 {" L64 "}, da, db, 1, 1, 1, 0, %66;\n}\n"
               : R64(d, 0) : "r"(da), "r"(db), "n"(TB));
}
template <int TB> __device__ __forceinline__ void mma_rs_n128(float (&d)[64], uint32_t a0, uint32_t a1, uint32_t a2, uint32_t a3, uint32_t db, int sd) {
  asm volatile("{\n.reg .pred p;\n.reg .b64 db;\nsetp.ne.b32 p, %69, 0;\nmov.b64 db, {%68, " DHI "};\n"
               "wgmma.mma_async.sync.aligned.m64n128k16.f32.bf16.bf16 {" L64 "}, {%64,%65,%66,%67}, db, p, 1, 1, %70;\n}\n"
               : R64(d, 0) : "r"(a0), "r"(a1), "r"(a2), "r"(a3), "r"(db), "r"(sd), "n"(TB));
}
template <int TB> __device__ __forceinline__ void mma_ss_n256(float (&d)[128], uint32_t da, uint32_t db) {
  asm volatile("{\n.reg .b64 da, db;\nmov.b64 da, {%128, " DHI "};\nmov.b64 db, {%129, " DHI "};\n"
               "wgmma.mma_async.sync.aligned.m64n256k16.f32.bf16.bf16 {" L128 "}, da, db, 1, 1, 1, 0, %130;\n}\n"
               : R64(d, 0), R64(d, 64) : "r"(da), "r"(db), "n"(TB));
}
#define W8(d, o) "=f"(d[o]), "=f"(d[o + 1]), "=f"(d[o + 2]), "=f"(d[o + 3]), "=f"(d[o + 4]), "=f"(d[o + 5]), "=f"(d[o + 6]), "=f"(d[o + 7])
#define W32(d, o) W8(d, o), W8(d, o + 8), W8(d, o + 16), W8(d, o + 24)
#define W64(d, o) W32(d, o), W32(d, o + 32)
template <int TB> __device__ __forceinline__ void mma_ss_n128_init(float (&d)[64], uint32_t da, uint32_t db) {
  asm volatile("{\n.reg .b64 da, db;\nmov.b64 da, {%64, " DHI "};\nmov.b64 db, {%65, " DHI "};\n"
               "wgmma.mma_async.sync.aligned.m64n128k16.f32.bf16.bf16 {" L64 "}, da, db, 0, 1, 1, 0, %66;\n}\n"
               : W64(d, 0) : "r"(da), "r"(db), "n"(TB));
}
template <int TB> __device__ __forceinline__ void mma_ss_n256_init(float (&d)[128], uint32_t da, uint32_t db) {
  asm volatile("{\n.reg .b64 da, db;\nmov.b64 da, {%128, " DHI "};\nmov.b64 db, {%129, " DHI "};\n"
               "wgmma.mma_async.sync.aligned.m64n256k16.f32.bf16.bf16 {" L128 "}, da, db, 0, 1, 1, 0, %130;\n}\n"
               : W64(d, 0), W64(d, 64) : "r"(da), "r"(db), "n"(TB));
}
#define L32 "%0,%1,%2,%3,%4,%5,%6,%7,%8,%9,%10,%11,%12,%13,%14,%15,%16,%17,%18,%19,%20,%21,%22,%23,%24,%25,%26,%27,%28,%29,%30,%31"
__device__ __forceinline__ void mma_ss_n64(float (&d)[32], uint32_t da, uint32_t db) {
  asm volatile("{\n.reg .b64 da, db;\nmov.b64 da, {%32, " DHI "};\nmov.b64 db, {%33, " DHI "};\n"
               "wgmma.mma_async.sync.aligned.m64n64k16.f32.bf16.bf16 {" L32 "}, da, db, 1, 1, 1, 0, 0;\n}\n"
               : R32(d, 0) : "r"(da), "r"(db));
}
__device__ __forceinline__ void mma_ss_n64_init(float (&d)[32], uint32_t da, uint32_t db) {
  asm volatile("{\n.reg .b64 da, db;\nmov.b64 da, {%32, " DHI "};\nmov.b64 db, {%33, " DHI "};\n"
               "wgmma.mma_async.sync.aligned.m64n64k16.f32.bf16.bf16 {" L32 "}, da, db, 0, 1, 1, 0, 0;\n}\n"
               : W32(d, 0) : "r"(da), "r"(db));
}
#define L16 "%0,%1,%2,%3,%4,%5,%6,%7,%8,%9,%10,%11,%12,%13,%14,%15"
template <int O, bool INIT> __device__ __forceinline__ void mma_rs_n32(float (&d)[128], uint32_t a0, uint32_t a1, uint32_t a2, uint32_t a3, uint32_t db) {
  if (INIT) asm volatile("{\n.reg .b64 db;\nmov.b64 db, {%20, 0x00000008};\n"
               "wgmma.mma_async.sync.aligned.m64n32k16.f32.bf16.bf16 {" L16 "}, {%16,%17,%18,%19}, db, 0, 1, 1, 0;\n}\n"
               : W8(d, O), W8(d, O + 8) : "r"(a0), "r"(a1), "r"(a2), "r"(a3), "r"(db));
  else asm volatile("{\n.reg .b64 db;\nmov.b64 db, {%20, 0x00000008};\n"
               "wgmma.mma_async.sync.aligned.m64n32k16.f32.bf16.bf16 {" L16 "}, {%16,%17,%18,%19}, db, 1, 1, 1, 0;\n}\n"
               : R8(d, O), R8(d, O + 8) : "r"(a0), "r"(a1), "r"(a2), "r"(a3), "r"(db));
}
template <int S, int J> __device__ __forceinline__ void conv_step(float (&d)[128], const uint32_t (&a)[64], uint32_t db) {
  if constexpr (J >= 0 && J >= (S >> 1)) {
    mma_rs_n32<16 * J, S == 0>(d, a[4 * S], a[4 * S + 1], a[4 * S + 2], a[4 * S + 3], db + (uint32_t)((2 * J - S) * 16));
    conv_step<S, J - 1>(d, a, db);
  }
}
__device__ __forceinline__ void mma_ss_n8(float (&d)[4], uint32_t da, uint32_t db) {
  asm volatile("{\n.reg .b64 da, db;\nmov.b64 da, {%4, " DHI "};\nmov.b64 db, {%5, 0x00000008};\n"
               "wgmma.mma_async.sync.aligned.m64n8k16.f32.bf16.bf16 {%0,%1,%2,%3}, da, db, 1, 1, 1, 0, 0;\n}\n"
               : "+f"(d[0]), "+f"(d[1]), "+f"(d[2]), "+f"(d[3]) : "r"(da), "r"(db));
}
template <int N> __device__ __forceinline__ void reg_fence(float (&d)[N]) {
#pragma unroll
  for (int i = 0; i < N; i++) asm volatile("" : "+f"(d[i])::"memory");
}
template <int N> __device__ __forceinline__ void reg_fence(uint32_t (&d)[N]) {
#pragma unroll
  for (int i = 0; i < N; i++) asm volatile("" : "+r"(d[i])::"memory");
}

struct __align__(64) Params {
  unsigned* flags;
  int zero;
  uint8_t pref[128];
  const __nv_bfloat16 *gate_w, *ak, *av, *shk, *ssk, *ssd, *wop;
  CUtensorMap x, c, wq, wuk, wuv, wo, x3, y3, out, w;
};

template <int O, int N, int M> __device__ __forceinline__ void pack_frag(const float (&acc)[N], uint32_t (&pk)[M]) {
#pragma unroll
  for (int i = 0; i < 32; i++) pk[i] = pack_bf16(acc[O + 2 * i], acc[O + 2 * i + 1]);
}
template <int N> __device__ __forceinline__ void pack_frag_scaled(const float (&acc)[N], uint32_t (&pk)[32], float s0, float s1) {
#pragma unroll
  for (int i = 0; i < 32; i++) { const float s = (i & 1) ? s1 : s0; pk[i] = pack_bf16(acc[2 * i] * s, acc[2 * i + 1] * s); }
}
template <int J0 = 0, int J1 = 8, int M> __device__ __forceinline__ void stsm_frag(const uint32_t (&pk)[M], uint32_t a) {
#pragma unroll
  for (int jj = J0; jj < J1; jj++)
    asm volatile("stmatrix.sync.aligned.m8n8.x4.shared.b16 [%0], {%1,%2,%3,%4};" ::"r"((a ^ ((jj & 3) << 5)) + (jj >> 2) * 16384),
                 "r"(pk[4 * jj]), "r"(pk[4 * jj + 1]), "r"(pk[4 * jj + 2]), "r"(pk[4 * jj + 3]) : "memory");
}

struct Cons {
  uint32_t sb;
  uint32_t pf;
  int wg, tid;
  __device__ __forceinline__ void wait_full(int g) { mbar_wait(sb + SM_BAR + (B_FULL + g) * 8, (pf >> g) & 1); pf ^= 1u << g; }
  uint32_t relb;
  __device__ __forceinline__ void release(int g, int n) {
    if (tid < 2 * n) asm volatile("mbarrier.arrive.shared::cluster.b64 _, [%0];" ::"r"(relb + g * 8) : "memory");
  }
  __device__ __forceinline__ void turn_begin() { bar_sync(1 + wg, 256); }
  __device__ __forceinline__ void turn_end() { bar_arrive(2 - wg, 256); }
  __device__ __forceinline__ void staged(int e) { __syncwarp(); if ((tid & 31) == 0) mbar_arrive(sb + SM_BAR + (B_EV + 2 * e + wg) * 8); }
  int zero;
  int rnd;
  uint32_t pfree;
  __device__ __forceinline__ void wait_stage_free() { mbar_wait(sb + SM_BAR + (B_FREE + wg) * 8, pfree); pfree ^= 1; }
  __device__ __forceinline__ bool try_full(int g) { return mbar_test(sb + SM_BAR + (B_FULL + g) * 8, (pf >> g) & 1); }
};

constexpr float SM_C = 0.08838834764831845f * 1.4426950408889634f;
struct SoftState { float m0, m1, l0, l1; int shifted; };
__device__ __forceinline__ void ex2_rot(float& t, float s, uint32_t never_zero) {
  asm("{\n.reg .pred p;\nsetp.ne.u32 p, %2, 0;\n@p ex2.approx.ftz.f32 %0, %1;\n}\n" : "+f"(t) : "f"(s), "r"(never_zero));
}
__device__ __forceinline__ void pin(float a, uint32_t never_zero) {
  asm volatile("{\n.reg .pred p;\nsetp.eq.u32 p, %1, 0;\n@p st.shared.f32 [%1], %0;\n}\n" ::"f"(a), "r"(never_zero) : "memory");
}
template <int O, int N> __device__ __forceinline__ void reg_fence_part(uint32_t (&d)[32]) {
#pragma unroll
  for (int i = O; i < O + N; i++) asm volatile("" : "+r"(d[i])::"memory");
}
template <int Q, int W, int N> __device__ __forceinline__ void exp_quarter(const float (&S)[N], uint32_t (&P)[32], float (&t)[ROT], float& s0, float& s1, uint32_t nz) {
#pragma unroll
  for (int i = 8 * Q; i < 8 * Q + 8; i++) {
    float& a = t[(2 * i) % ROT];
    float& b = t[(2 * i + 1) % ROT];
    if (2 * i < ROT) { a = ex2(S[2 * i]); b = ex2(S[2 * i + 1]); }
    else { ex2_rot(a, S[2 * i], nz); ex2_rot(b, S[2 * i + 1], nz); }
    if (i < 2) { if (i) s1 = a + b; else s0 = a + b; }
    else if (SUMV == 0) { if (i & 1) { s1 += a; s1 += b; } else { s0 += a; s0 += b; } }
    else { if (i & 1) s1 += a + b; else s0 += a + b; }
    if (i == 8 * Q) { pin(EXPV == 1 && Q ? s1 : s0, nz); wg_wait<W>(); reg_fence_part<8 * Q, 8>(P); }
    P[i] = pack_bf16(a, b);
  }
}
template <int N> __device__ __forceinline__ void shift_scores(float (&S)[N], float d0, float d1) {
#pragma unroll
  for (int i = 0; i < N; i++) S[i] -= (i & 2) ? d1 : d0;
}
__device__ __forceinline__ bool soft_high(float s0, float s1, float lim = SM_LIMIT) { return s0 > lim || s1 > lim; }
__device__ __forceinline__ bool soft_unsafe(float s0, float s1, bool first) {
  uint32_t b0 = __ballot_sync(0xffffffffu, s0 >= SM_LOW), b1 = __ballot_sync(0xffffffffu, s1 >= SM_LOW);
  b0 |= b0 >> 1; b0 |= b0 >> 2; b1 |= b1 >> 1; b1 |= b1 >> 2;
  return __any_sync(0xffffffffu, soft_high(s0, s1)) || (first && (b0 & b1 & 0x11111111u) != 0x11111111u);
}
template <int N> __device__ __forceinline__ void soft_fix(const float (&S)[N], float (&O)[64], SoftState& z, bool first, float& d0, float& d1) {
  d0 = d1 = first ? -INFINITY : 0.f;
#pragma unroll
  for (int j = 0; j < N / 4; j++) { d0 = fmaxf(d0, fmaxf(S[4 * j], S[4 * j + 1])); d1 = fmaxf(d1, fmaxf(S[4 * j + 2], S[4 * j + 3])); }
  d0 = fmaxf(d0, __shfl_xor_sync(0xffffffffu, d0, 1)); d1 = fmaxf(d1, __shfl_xor_sync(0xffffffffu, d1, 1));
  d0 = fmaxf(d0, __shfl_xor_sync(0xffffffffu, d0, 2)); d1 = fmaxf(d1, __shfl_xor_sync(0xffffffffu, d1, 2));
  const float sc0 = ex2(-fmaxf(d0, 0.f)), sc1 = ex2(-fmaxf(d1, 0.f));
  z.m0 += d0; z.m1 += d1; z.l0 *= sc0; z.l1 *= sc1; z.shifted = 1;
#pragma unroll
  for (int j = 0; j < 16; j++) { O[4 * j] *= sc0; O[4 * j + 1] *= sc0; O[4 * j + 2] *= sc1; O[4 * j + 3] *= sc1; }
}
template <int M> __device__ __forceinline__ void pin32(const uint32_t (&v)[M], uint32_t never_zero) {
#pragma unroll
  for (int i = 0; i < 32; i += 4)
    asm volatile("{\n.reg .pred p;\nsetp.eq.u32 p, %4, 0;\n@p st.shared.v4.b32 [%4], {%0,%1,%2,%3};\n}\n" ::"r"(v[i]), "r"(v[i + 1]), "r"(v[i + 2]), "r"(v[i + 3]), "r"(never_zero) : "memory");
}
template <int N> __device__ __forceinline__ void mask_diag(float (&S)[N], float nd) {
  asm volatile("" : "+f"(nd));
#pragma unroll
  for (int i = 0; i < 32; i++) {
    const float beyond = __saturatef(nd + (float)(8 * (i >> 2) + (i & 1) - 4 * (i & 2)));
    S[N - 32 + i] = fmaf(beyond, -3.0e38f, S[N - 32 + i]);
  }
}
__device__ __forceinline__ float quad_sum(float v) {
  v += __shfl_xor_sync(0xffffffffu, v, 1);
  v += __shfl_xor_sync(0xffffffffu, v, 2);
  return v;
}
__device__ __forceinline__ void issue_qk(float (&S)[64], uint32_t dq, uint32_t dk) {
  mma_ss_n128_init<0>(S, dq, dk);
#pragma unroll
  for (int s = 1; s < 8; s++) mma_ss_n128<0>(S, dq + (s >> 2) * 1024 + (s & 3) * 2, dk + (s >> 2) * 1024 + (s & 3) * 2);
}
__device__ __forceinline__ void issue_qk(float (&S)[32], uint32_t dq, uint32_t dk) {
  mma_ss_n64_init(S, dq, dk);
#pragma unroll
  for (int s = 1; s < 8; s++) mma_ss_n64(S, dq + (s >> 2) * 1024 + (s & 3) * 2, dk + (s >> 2) * 1024 + (s & 3) * 2);
}
template <int H> __device__ __forceinline__ void issue_pv(float (&O)[64], const uint32_t (&P)[32], uint32_t dv, int acc, bool on) {
  if (on) {
#pragma unroll
    for (int s = 4 * H; s < 4 * H + 4; s++) {
      mma_rs_n128<1>(O, P[4 * s], P[4 * s + 1], P[4 * s + 2], P[4 * s + 3], dv + s * 128, s != 0 ? 1 : acc);
      if (s & 1) wg_commit();
    }
  } else { wg_commit(); wg_commit(); }
}
constexpr uint32_t DG = GR >> 4;
__device__ __forceinline__ void stage_q2(Cons& c, const float (&O)[64], uint32_t (&P)[32], uint32_t stg) {
  wg_commit(); wg_commit(); wg_commit(); wg_commit();
  c.turn_end();
  pack_frag<0>(O, P);
  stsm_frag(P, stg);
  fence_async_smem();
}
__device__ __forceinline__ void attn_half(Cons& c, float (&O)[64], uint32_t (&P)[32], SoftState& z, uint32_t dk0, uint32_t dkk, uint32_t dv0, float dmask, int last) {
  float S[32];
  FTH(8 + last * 32, 0);
  c.turn_begin();
  FTH(9 + last * 32, 0);
  wg_fence();
  issue_qk(S, dk0 + (last ? 0 : 2 * DG), dkk + (last ? 8 : 4) * DG);
  wg_commit();
  issue_pv<0>(O, P, dv0 + 10 * DG, 1, last);
  issue_pv<1>(O, P, dv0 + 10 * DG, 1, last);
  c.turn_end();
  c.wait_full(last ? 12 : 6);
  FTH(10 + last * 32, 0);
  wg_wait<4>();
  reg_fence(S);
  FTH(11 + last * 32, 0);
  c.release(last ? 8 : 4, 2);
  mask_diag(S, dmask);
  float s0, s1, d0 = z.m0, d1 = z.m1;
#pragma unroll 1
  for (int pass = 0;; pass++) {
    if (z.shifted) shift_scores(S, d0, d1);
    float tr[ROT];
    exp_quarter<0, 3>(S, P, tr, s0, s1, c.sb);
    exp_quarter<1, 2>(S, P, tr, s0, s1, c.sb);
    pin(s1, c.sb); wg_wait<0>(); reg_fence_part<16, 16>(P); reg_fence(O);
    if (!soft_unsafe(s0, s1, !last) || pass) break;
    soft_fix(S, O, z, !last, d0, d1);
  }
  FTH(12 + last * 32, 0);
  z.l0 += s0; z.l1 += s1;
  c.release(10, last ? 2 : 0);
  if (!last) c.wait_full(8);
  FTH(13 + last * 32, 0);
}

template <int V> struct IC { static constexpr int value = V; };
__device__ __forceinline__ int conv_next(int g, bool spare) { return g >= NGR - 2 ? g - (NGR - 4) : !spare && g == 4 ? 1 : g + 2; }
__device__ __forceinline__ void conv_final(uint32_t rb, uint32_t yb, bool on) {
  const uint4 q0 = lds128(rb), q1 = lds128(rb + 4096), q2 = lds128(rb + 8192), q3 = lds128(rb + 12288);
  auto fin = [&](uint32_t x0, uint32_t x1, uint32_t x2, uint32_t x3) { return hadd2(hadd2(x0, x1), hadd2(x2, x3)); };
  asm volatile("{\n.reg .pred p;\nsetp.ne.b32 p, %5, 0;\n@p st.shared.v4.b32 [%0], {%1,%2,%3,%4};\n}\n" ::"r"(yb), "r"(fin(q0.x, q1.x, q2.x, q3.x)),
               "r"(fin(q0.y, q1.y, q2.y, q3.y)), "r"(fin(q0.z, q1.z, q2.z, q3.z)), "r"(fin(q0.w, q1.w, q2.w, q3.w)), "r"((int)on) : "memory");
}
__device__ __forceinline__ void conv_tasks(Cons& c, const Params& p, int ntask, bool spare, int ch, int chstep, int c5, uint32_t dd, uint32_t dkk, int w, int lane) {
  const uint32_t sb = c.sb;
  int g = 2 + c.wg;
  uint32_t rb = sb + g * GR;
  const uint32_t yb = sb + c.wg * 8192 + c.tid * 16;
  const int gt = 8 * w + (lane >> 2) + (lane & 3);
  uint32_t a[64], hb;
  auto lda = [&](int s) {
    a[4 * s] = lds32(hb + s * 256); a[4 * s + 1] = lds32(hb + s * 256 + 128);
    a[4 * s + 2] = lds32(hb + s * 256 + 16); a[4 * s + 3] = lds32(hb + s * 256 + 144);
  };
  auto first_a = [&]() {
    hb = sb + g * GR + WBYTES - 28 + gt * 4;
    lda(0); lda(15);
  };
  c.wait_full(g);
  first_a();
#pragma unroll 1
  for (int i = 0; i < ntask; i++) {
    const uint32_t base = sb + g * GR;
    FTC(0);
    lda(1); lda(14);
    a[0] = hadd2(a[0], gt == 7 ? dd : 0u); a[2] = hadd2(a[2], gt == 3 ? dd : 0u);
    float acc[128];
    const uint32_t db = dkk + ((WPL / 16 - 1) << 16) + g * DG + WZ / 16;
    FTC(2);
    c.turn_begin();
    FTC(3);
    auto pair = [&](auto kc) {
      constexpr int k = decltype(kc)::value;
      if (k < 7) wg_fence();
      if (k == 6) c.turn_end();
      conv_step<k, 7>(acc, a, db);
      conv_step<15 - k, 7>(acc, a, db);
      if (k < 6) { lda(k + 2); lda(13 - k); }
      if (k == 0) conv_final(rb, yb, i > 0);
      if (k == 1) {
        conv_final(rb + 2048, yb + 2048, i > 0);
        __syncwarp();
        if (lane == 0 && i > 0) mbar_arrive(sb + SM_BAR + (B_EV + c.wg) * 8);
      }
      if (k == 6) dd = __bfloat16_as_ushort(p.ssd[(ch + chstep + (i == 1 ? c5 : 0)) & (DM - 1)]);
    };
    pair(IC<0>()); pair(IC<1>()); pair(IC<2>()); pair(IC<3>()); pair(IC<4>()); pair(IC<5>()); pair(IC<6>()); pair(IC<7>());
    wg_commit();
    FTC(4);
    g = conv_next(g, spare);
    ch += chstep;
    rb = base + c.tid * 16;
    if (i + 1 < ntask) c.wait_full(g);
    wg_wait<0>();
    reg_fence(acc);
    reg_fence(a);
    bar_sync(3 + c.wg, 128);
    FTC(5);
    first_a();
    const int tw = (lane & 3) + w;
    const uint32_t xb = base + w * 4096 + tw * 32 + (lane >> 2) * 4;
#pragma unroll
    for (int j = 0; j < 32; j++) {
      float v0 = acc[4 * j], v1 = acc[4 * j + 1];
      if (j > 0) { v0 += acc[j > 0 ? 4 * j - 2 : 0]; v1 += acc[j > 0 ? 4 * j - 1 : 0]; }
      uint32_t v = pack_bf16(v0, v1), ad = xb + j * 128;
      if (j == 31 && tw >= 4) { v = 0; ad -= 4096; }
      asm volatile("st.shared.b32 [%0], %1;" ::"r"(ad), "r"(v) : "memory");
    }
    c.wait_stage_free();
    FTC(6);
  }
  bar_sync(3 + c.wg, 128);
  conv_final(rb, yb, true);
  conv_final(rb + 2048, yb + 2048, true);
  c.staged(0);
}

__global__ void __cluster_dims__(2, 1, 1) __launch_bounds__(NTHREADS, 1) mega_kernel(const __grid_constant__ Params p) {
  extern __shared__ __align__(1024) uint8_t smem_raw[];
  FTS(0);
  const uint32_t sb = smem_u32(smem_raw);
  if (threadIdx.x - 64 < 32) { prefetch_tm(&p.c); prefetch_tm(&p.wuk + (blockIdx.x & 1)); }
  const int wgi = __shfl_sync(0xffffffffu, threadIdx.x >> 7, 0);
  const int warp = __shfl_sync(0xffffffffu, threadIdx.x >> 5, 0);
  const uint32_t rank = blockIdx.x & 1;
  int slot;
  {
    uint32_t smid; asm volatile("mov.u32 %0, %smid;" : "=r"(smid));
    slot = p.pref[((smid >> 1) + (threadIdx.x & (smid >> 16))) & 127];
  }
  if (warp >= 3) {
    if (elect()) {
#pragma unroll
      for (int k = 0; k < 4; k++) mbar_init(sb + SM_BAR + ((warp - 3) * 4 + k) * 8, k == 1 && warp == 7 ? 11 : warp < (k ? 7 : 8) ? 1 : 4);
      if (warp == 7) { mbar_init(sb + SM_BAR + B_TICK * 8, 1); mbar_expect_tx(sb + SM_BAR + B_SLOT * 8, 8); mbar_expect_tx(sb + SM_BAR + B_TICK * 8, 4); }
      asm volatile("fence.mbarrier_init.release.cluster;" ::: "memory");
    }
    __syncwarp();
  }
  FTS(1);
  cluster_arrive();
  slot = __shfl_sync(0xffffffffu, slot, 0);
  const int pref = slot;
  if (warp < 4) {
    asm volatile("setmaxnreg.dec.sync.aligned.u32 40;");
    if (warp == 1 + 4 * rank) {
      unsigned taken = threadIdx.x == 32;
#pragma unroll 1
      for (int n = 0; n < NSLOT; n++) {
        asm volatile("{\n.reg .pred p;\nsetp.ne.b32 p, %0, 0;\n@p atom.relaxed.gpu.global.exch.b32 %0, [%1], 1;\n}\n" : "+r"(taken) : "l"(CLAIMP(slot)) : "memory");
        if (!__any_sync(0xffffffffu, taken)) break;
        slot = slot == NSLOT - 1 ? 0 : slot + 1;
      }
    }
    cluster_wait();
    if (threadIdx.x == 32) {
      send_both(sb + SM_BAR + B_SLOT * 8, (V_SLOT - B_SLOT) * 8 + rank * 4, slot | pref << 8);
    }
    if (warp == 2) {
#pragma unroll 1
      for (int kk = 0; kk < 4; kk++) {
        const int g0 = 2 + 3 * kk;
        const uint32_t fb = sb + SM_BAR + (B_FULL + g0) * 8;
        if (elect()) {
          FTSW(kk);
          mbar_expect_tx(fb, 3 * GR);
          tma2d(sb + g0 * GR, &p.c, kk * 64, (KV_ROW(pref & 7, 0) + rank) * 128, fb);
          tma3d_mc(sb + (g0 + 1 + rank) * GR, rank ? &p.wuv : &p.wuk, 0, kk * 64, ((pref & 56) >> 1) + 2 * KV_HEAD(pref & 7, 0), fb);
        }
        if (kk < 3) {
          uint32_t c0, c1;
          asm volatile("mov.u32 %0, %clock;" : "=r"(c0));
          do asm volatile("mov.u32 %0, %clock;" : "=r"(c1)); while (c1 - c0 < (kk ? X_D2 : X_DELAY));
        }
      }
      FTSW(4);
      prefetch_tm(&p.x); prefetch_tm(&p.wq);
    }
  }
  int grp, idx, lb;
  int cn, cch, cstep;
  bool spare, redo;
  auto get_slot = [&]() {
    mbar_wait(sb + SM_BAR + B_SLOT * 8, 0);
    const uint32_t sv0 = __shfl_sync(0xffffffffu, lds32(sb + SM_BAR + V_SLOT * 8), 0), sv1 = __shfl_sync(0xffffffffu, lds32(sb + SM_BAR + V_SLOT * 8 + 4), 0);
    grp = (sv0 & 255) >> 3; idx = sv0 & 7; lb = (sv0 & 255) * 2 + rank;
    spare = grp == 8; redo = spare || sv0 != sv1;
    cn = CN_SPARE; cch = spare ? lb - NMAIN : 4 * CN_SPARE + 4 * lb; cstep = spare ? 4 : 1;
    if (FINE_MODE != 7) TS(0);
  };
  auto get_ticket = [&]() {
    mbar_wait(sb + SM_BAR + B_TICK * 8, 0);
    const int tk = __shfl_sync(0xffffffffu, lds32(sb + SM_BAR + V_TICK * 8), 0);
    cn = tk < NTICK ? 5 : 4;
    return 4 * NMAIN - 4 * lb - 4 + 2 * tk + rank;
  };

  if (wgi == 0) {
    asm volatile("setmaxnreg.dec.sync.aligned.u32 40;");
    const int lane = threadIdx.x & 31;
    cluster_arrive();
    get_slot();
    uint32_t pe = 0;
    auto acquire = [&](int g, int n, uint32_t m) {
      int i = g;
#pragma unroll 1
      do mbar_wait1(sb + SM_BAR + (B_EMPTY + i) * 8, (pe >> i) & 1); while (++i < g + n);
      pe ^= m << g;
    };
    if (warp == 3) {
      if (!spare) {
        const int s0 = lb * 16;
#pragma unroll 1
        for (int cg = 0; cg < 16; cg++) {
          if (cg == 3 || cg == 10) {
#pragma unroll 1
            for (int n = 0; n < 20 && !__any_sync(0xffffffffu, mbar_try(sb + SM_BAR + B_SLOT * 8, cg == 3)); n++);
          } else if (cg < 3) __nanosleep(US0);
          if (cg == TKCG && lane == rank * 32) send_both(sb + SM_BAR + B_TICK * 8, (V_TICK - B_TICK) * 8, atomicInc(FLAG(F_TICK), 0x7fffffffu));
          const int ch = cg * 64 + 2 * lane;
          const uint32_t* kp = reinterpret_cast<const uint32_t*>(p.ak + (size_t)s0 * DM + ch);
          const uint32_t* vp = reinterpret_cast<const uint32_t*>(p.av + (size_t)s0 * DM + ch);
          const uint4 sw = __ldg(reinterpret_cast<const uint4*>(p.shk + ch * 4));
          uint32_t k3 = 0, k2 = 0, k1 = 0, k0 = 0, up = 0;
          if (lb > 0) { k3 = ldg_stream(kp - 4 * 512); k2 = ldg_stream(kp - 3 * 512); k1 = ldg_stream(kp - 2 * 512); k0 = ldg_stream(kp - 512); up = ldg_stream(vp - 512); }
          const uint32_t w0 = __byte_perm(sw.x, sw.z, 0x5410), w1 = __byte_perm(sw.x, sw.z, 0x7632);
          const uint32_t w2 = __byte_perm(sw.y, sw.w, 0x5410), w3 = __byte_perm(sw.y, sw.w, 0x7632);
          up = hmul2(hfma2(k0, w0, hfma2(k1, w1, hfma2(k2, w2, hmul2(k3, w3)))), up);
#pragma unroll 1
          for (int hb = 0; hb < 2; hb++) {
            uint32_t kk[8], u[8];
#pragma unroll
            for (int r = 0; r < 8; r++) { kk[r] = ldg_stream(kp + r * 512); u[r] = ldg_stream(vp + r * 512); }
#pragma unroll
            for (int r = 0; r < 8; r++) {
              k3 = k2; k2 = k1; k1 = k0; k0 = kk[r];
              u[r] = hmul2(hfma2(k0, w0, hfma2(k1, w1, hfma2(k2, w2, hmul2(k3, w3)))), u[r]);
            }
            if (lane == 0) asm volatile("cp.async.bulk.wait_group.read 0;" ::: "memory");
            __syncwarp();
            const uint32_t dst = sb + SM_UST + lane * 32 + ((lane & 4) << 2);
#pragma unroll
            for (int cc = 0; cc < 2; cc++) {
              const uint32_t sel = cc ? 0x7632 : 0x5410;
              asm volatile("st.shared.v4.b32 [%0], {%1,%2,%3,%4};" ::"r"(dst + cc * 1024), "r"(__byte_perm(u[6], u[5], sel)), "r"(__byte_perm(u[4], u[3], sel)),
                           "r"(__byte_perm(u[2], u[1], sel)), "r"(__byte_perm(u[0], up, sel)) : "memory");
              asm volatile("st.shared.v4.b32 [%0], {%1,%2,%3,%4};" ::"r"((dst ^ 16) + cc * 1024), "r"(__byte_perm(u[7], u[6], sel)), "r"(__byte_perm(u[5], u[4], sel)),
                           "r"(__byte_perm(u[3], u[2], sel)), "r"(__byte_perm(u[1], u[0], sel)) : "memory");
            }
            fence_async_smem();
            __syncwarp();
            if (lane == 0) {
              asm volatile("cp.async.bulk.tensor.3d.global.shared::cta.bulk_group [%0, {%2, %3, %4}], [%1];\ncp.async.bulk.commit_group;"
                           ::"l"(&p.w), "r"(sb + SM_UST), "r"(WZ / 2 + lb * 16 + (hb ^ 1) * (WPL / 2)), "r"(cg * 32), "r"(0) : "memory");
            }
            up = u[7];
            kp += 8 * 512; vp += 8 * 512;
          }
          if ((cg & (cg + 1)) == 0 && lane == 0) {
            asm volatile("cp.async.bulk.wait_group 0;" ::: "memory");
            fence_release();
            flag_add(FLAG(F_U + 32 - __clz(cg)));
          }
          TSW(10 + cg);
        }
        prefetch_tm(&p.wo); prefetch_tm(&p.x3); prefetch_tm(&p.y3); prefetch_tm(&p.out);
        if (P3PF) {
          const int rt = 2 * grp + rank;
          unsigned v;
          asm volatile("ld.acquire.gpu.global.u32 %0, [%1];" : "=r"(v) : "l"(FLAG(F_CTX + rt * 2)) : "memory");
#pragma unroll 1
          for (int kb = P3PF0; kb < P3PF0 + P3PF; kb++) {
            const uint8_t* a = lane < 16 ? g_cimg + (unsigned)((rt * 64 + kb) * GR + (idx * 16 + lane) * 128) : (const uint8_t*)p.wop + (unsigned)(kb * 64 * DM * 2 + (lb * 8 + (lane & 7)) * 128);
            if (lane < 24 && v == 32) asm volatile("prefetch.global.L2 [%0];" ::"l"(a));
          }
        }
      } else {
#pragma unroll 1
        for (int i = 0, g = 2; i < 32; i++) {
          acquire(g, 2, 3);
          if (elect()) {
            const uint32_t fb = sb + SM_BAR + (B_FULL + g) * 8;
            if (i == 0) { mbar_expect_tx(fb - 8, 2048); bulk_g2s(sb + GR, p.gate_w, 2048, fb - 8); }
            mbar_expect_tx(fb, 2 * GR);
            tma3d(sb + g * GR, &p.x3, 0, (lb - NMAIN) * 512 + (i >> 3) * 128, (i & 7) * 2, fb);
          }
          g = g == NGR - 2 ? 2 : g + 2;
        }
        bar_arrive(5, 64);
      }
      unsigned long long t0, t1;
      asm volatile("mov.u64 %0, %globaltimer;" : "=l"(t0));
      auto check = [&]() {
        asm volatile("mov.u64 %0, %globaltimer;" : "=l"(t1));
        if (t1 - t0 > 2000000000ull) __trap();
      };
      if (!spare) {
        unsigned v;
        do {
          __nanosleep(PSL);
          check();
          asm volatile("ld.acquire.gpu.global.u32 %0, [%1];" : "=r"(v) : "l"(FLAG(lane & 1 ? F_Y + idx : F_GATE)) : "memory");
        } while (__any_sync(0xffffffffu, v < (lane & 1 ? 128 : 32)));
        __syncwarp();
        if (lane == 0) mbar_arrive(sb + SM_BAR + B_SLOT * 8);
      }
      if (lane == 0) {
        while (!mbar_try(sb + SM_BAR + B_DONE * 8, 0)) check();
      }
    } else if (warp != 0) {
      const int w = warp - 1;
      int ne = 12 + (CN_SPARE + 1 - w) / 2, c5 = 0;
      uint32_t p0 = 0;
      int cg = 2 + w, ch = cch + w * cstep;
#pragma unroll 1
      for (int e = spare ? 12 : 0; e < ne; e++) {
        const int rnd = e >= 6, k = e - 6 * rnd, rt = k == 4 ? idx : 15 - idx;
        uint8_t* dst = k < 4 ? g_kv + (size_t)(((k & 1) * 16 + 2 * grp + KV_HEAD(idx, k >> 1)) * 16 + KV_ROW(idx, k >> 1) + rank) * 32768 + w * 8192
                     : k < 6 ? g_cimg + (size_t)(rt * 32 + 16 * rnd + 2 * grp + rank) * 32768 + (w ^ (k & 1)) * 8192
                             : reinterpret_cast<uint8_t*>(g_yT + (size_t)ch * SEQ);
        const uint32_t src = sb + w * 8192 + (k == 4 ? 2 * GR : 0);
        if (e == 11) { c5 = get_ticket(); ne = 12 + ((cn + 1 - w) >> 1); }
        if (e == 6) flag_wait(FLAG(F_AD + grp), 32);
        mbar_wait1(sb + SM_BAR + (B_EV + (k == 4 ? 2 : 0) + w) * 8, k == 4 ? rnd : p0);
        if (k != 4) p0 ^= 1;
        if (lane < 4 && k >= 6 && (!spare || e < ne - 6)) mbar_arrive_cluster(sb + SM_BAR + (B_EMPTY + cg) * 8, lane & 1);
        fence_async_smem();
        if (elect()) {
          const uint32_t cs = k >= 6 ? 4096 : 1024;
#pragma unroll 1
          for (uint32_t i = 0; i < (k >= 6 ? 4096 : 16384); i += cs) {
            const uint32_t o = i + (i & 8192);
            asm volatile("cp.async.bulk.global.shared::cta.bulk_group [%0], [%1], %2;" ::"l"(dst + o), "r"(src + o), "r"(cs) : "memory");
            asm volatile("cp.async.bulk.commit_group;\ncp.async.bulk.wait_group.read 1;" ::: "memory");
          }
          asm volatile("cp.async.bulk.wait_group 0;" ::: "memory");
          if (k != 4) mbar_arrive(sb + SM_BAR + (B_FREE + w) * 8);
        }
        __syncwarp();
        if (lane < (k == 4 ? 4 : e == 11 || (e == ne - 1 && !spare) ? 2 : 0))
          mbar_arrive_cluster(sb + SM_BAR + (B_EMPTY + (k == 4 ? 2 : e == 11) + (lane >> 1)) * 8, lane & 1);
        if (k >= 3) {
          fence_release();
          const unsigned fl = k == 3 ? F_KV + rnd * 8 + grp : k < 6 ? F_CTX + rt * 2 + rnd : F_Y + ((unsigned)ch >> 7);
          if (lane <= (e == 5)) flag_add(FLAG(lane ? F_AD + grp : fl));
        }
        if (k >= 6) { cg = conv_next(cg, spare); ch += 2 * cstep + (k == 7 ? c5 : 0); }
      }
      if (lane == 0) mbar_arrive(sb + SM_BAR + B_DONE * 8);
    } else {
#pragma unroll 1
      for (int rnd = 0; rnd < (spare ? 0 : 2); rnd++) {
        const int hp = 16 * rnd + 2 * grp, head = hp + rank;
#pragma unroll 1
        for (int kk = rnd || redo ? 0 : 4; kk < 32; kk++) {
          const int g0 = 2 + 3 * (kk & 3);
          acquire(g0, kk < 4 ? 3 : 1, 7);
          if (elect()) {
            const uint32_t fb = sb + SM_BAR + (B_FULL + g0) * 8;
            mbar_expect_tx(fb, 3 * GR);
            if (kk < 16) {
              tma2d(sb + g0 * GR, &p.c, (kk & 7) * 64, (KV_ROW(idx, kk >> 3) + rank) * 128, fb);
              tma3d_mc(sb + (g0 + 1 + rank) * GR, rank ? &p.wuv : &p.wuk, 0, (kk & 7) * 64, (hp + KV_HEAD(idx, kk >> 3)) * 2, fb);
            } else {
              tma2d_mc(sb + (g0 + rank) * GR, &p.x, (kk - 16) * 64, (rank ? 15 - idx : idx) * 128, fb);
              tma3d(sb + (g0 + 2) * GR, &p.wq, 0, (kk - 16) * 64, head * 2, fb);
            }
          }
        }
        flag_wait(FLAG(F_KV + rnd * 8 + grp), 32);
        fence_async_all();
        acquire(2, 1, 3);
        int g0 = 4;
#pragma unroll 1
        for (int n = 0; n < 36; n += n == 0 || n == 33 ? 2 : 1) {
          const int it = (n >> 1) - (n & 1);
          const int blk = it & 15 ? (it <= idx ? it - 1 : 15 - it) : it ? 15 - idx : idx;
          acquire(g0, n < 6 ? 2 : 1, 3);
          if (elect()) {
            const uint32_t fb = sb + SM_BAR + (B_FULL + g0) * 8;
            if (n == 5) mbar_arrive(sb + SM_BAR + B_SLOT * 8);
            mbar_expect_tx(fb, 2 * GR);
            bulk_g2s(sb + g0 * GR, g_kv + (unsigned)((((n & 1) * 16 + (head & 15)) * 16 + blk) * 32768), 2 * GR, fb);
          }
          g0 = n == 13 ? 12 : g0 == 12 ? 4 : g0 + 2;
        }
      }
      int c5 = 0;
      if (spare) { bar_sync(5, 64); pe = 0x3FC0; }
      else c5 = get_ticket();
      auto conv_fill = [&](int g, int ch) {
        acquire(g, 1, 1);
        if (elect()) {
          const uint32_t fb = sb + SM_BAR + (B_FULL + g) * 8;
          if (!spare) FTP(64 + 48 + g);
          mbar_expect_tx(fb, WBYTES + 4096);
          bulk_g2s<true>(sb + g * GR, g_w + (size_t)ch * WSTRIDE, WBYTES, fb);
          bulk_g2s<true>(sb + g * GR + WBYTES, p.ssk + (size_t)ch * SEQ, 4096, fb);
        }
      };
#pragma unroll 1
      for (int i = 0, g = 2; i < cn; i++) {
        if ((i & 15) == 0) { flag_wait(FLAG(F_U + (spare ? 32 - __clz(i >> 4) : 4)), NMAIN); fence_async_all(); }
        conv_fill(g + (i & 1), cch + i * cstep + (i == 4 ? c5 : 0));
        if (i & 1) g = conv_next(g, spare);
      }
      if (!spare) {
        const int rt = 2 * grp + rank, ct = idx;
        int g0 = P3G, top = 12;
        const uint8_t* src = g_cimg + (unsigned)(rt * 64 * GR);
#pragma unroll 1
        for (int kb = 0; kb < 64; kb++) {
          if (!(kb & 31)) { flag_wait(FLAG(F_CTX + rt * 2 + (kb >> 5)), 32); fence_async_all(); }
          acquire(g0, kb < 11 ? 2 : 1, 3);
          if (elect()) {
            const uint32_t fb = sb + SM_BAR + (B_FULL + g0) * 8;
            if (kb < 16) FTP(48 + kb);
            mbar_expect_tx(fb, 2 * GR);
            bulk_g2s<true>(sb + g0 * GR, src, GR, fb);
            tma2d_mc<true>(sb + (g0 + 1) * GR + rank * 8192, &p.wo, ct * 128 + rank * 64, kb * 64, fb);
          }
          src += GR;
          g0 = g0 == (kb < XK ? 12 : kb < YK ? 10 : 8) ? (kb == 3 ? 2 : 0) : g0 + 2;
          if (kb == XK || (kb >= YK && top == P3Y && (kb == 63 || mbar_test(sb + SM_BAR + B_SLOT * 8, 1)))) {
            const bool j = kb != XK;
            if (j) { mbar_wait1(sb + SM_BAR + B_SLOT * 8, 1); fence_async_all(); }
            acquire(top, 1, 0);
            if (elect()) {
              const uint32_t fb = sb + SM_BAR + (B_FULL + top) * 8;
              mbar_expect_tx(fb, j ? 2 * GR + 512 : 2 * GR);
              if (j) bulk_g2s(sb + SM_GATE, g_gate + (unsigned)(rt * 128), 512, fb);
              tma3d(sb + top * GR, j ? &p.y3 : &p.x3, 0, (j ? ct : rt) * 128, (j ? rt : ct) * 2, fb);
            }
            top -= 2;
          }
        }
        unsigned n = 0;
        if (lane == 0) n = atomicInc(FLAG(F_EXIT), 0x7fffffffu);
        if (__any_sync(0xffffffffu, n == NMAIN - 1)) {
#pragma unroll
          for (int i = lane; i < 96; i += 32) *reinterpret_cast<uint2*>(FLAG(i)) = make_uint2(0, 0);
        }
      }
      if (lane == 0) mbar_arrive(sb + SM_BAR + B_DONE * 8);
    }
    __syncwarp();
    cluster_wait();
  } else {
    asm volatile("setmaxnreg.inc.sync.aligned.u32 232;");
    FTS(2);
    Cons c;
    c.sb = sb; c.pf = 0; c.wg = wgi - 1; c.tid = threadIdx.x & 127;
    const int lane = threadIdx.x & 31, t = lane & 3;
    const int row = c.wg * 64 + (warp & 3) * 16 + (lane >> 2);
    const uint32_t dkk = desc_k(sb), dk0 = dkk + c.wg * 512, dm0 = desc_mn<8192>(sb), dv0 = desc_mn<16384>(sb);
    const uint32_t dsw = DG + 512 - c.wg * 1024;
    if (c.wg == 1) bar_arrive(1, 256);
    c.pfree = 1;
    asm("mapa.shared::cluster.u32 %0, %1, %2;" : "=r"(c.relb) : "r"(sb + SM_BAR + (B_EMPTY + (c.tid >> 1)) * 8), "r"(c.tid & 1));
    c.zero = p.zero;
    c.rnd = 0;
    const uint32_t stg = sb + (c.wg * 64 + (warp & 3) * 16 + ((lane >> 3) & 1) * 8 + (lane & 7)) * 128 + (((lane >> 4) ^ (lane & 7)) << 4);

    uint32_t dd0;
    auto load_dd = [&]() { asm volatile("ld.global.nc.u16 %0, [%1];" : "=r"(dd0) : "l"(p.ssd + (unsigned)(cch + c.wg * cstep + (lane & c.zero)))); };
    int pass = c.zero;
#pragma unroll 1
    do {
    if (pass) {
      load_dd();
#pragma unroll 1
      for (int g = 2; g < NGR; g += 3) { mbar_wait(sb + SM_BAR + (B_FULL + g) * 8, 0); c.release(g, 3); }
      c.pf = 0x924;
    if (spare) {
      c.wait_full(1);
      int g = 2;
#pragma unroll 1
      for (int r = 0; r < 4; r++) {
        float d[4] = {0.f, 0.f, 0.f, 0.f}, e[4] = {0.f, 0.f, 0.f, 0.f};
#pragma unroll 1
        for (int kb = 0; kb < 16; kb += 2) {
          c.wait_full(g);
          wg_fence();
#pragma unroll 1
          for (int k = 0; k < 4; k++) {
            mma_ss_n8(d, dk0 + g * DG + k * 2, dkk + DG + kb * 8 + k * 2);
            mma_ss_n8(e, dk0 + (g + 1) * DG + k * 2, dkk + DG + kb * 8 + 8 + k * 2);
          }
          wg_commit();
          wg_wait<0>();
          c.release(g, 2);
          g = g == NGR - 2 ? 2 : g + 2;
        }
        reg_fence(d); reg_fence(e);
        d[0] += e[0]; d[2] += e[2];
        if (t == 0) {
          float* gp = g_gate + (unsigned)((lb - NMAIN) * 512 + r * 128 + row);
          gp[0] = rcp(1.f + ex2(-1.4426950408889634f * d[0])); gp[8] = rcp(1.f + ex2(-1.4426950408889634f * d[2]));
        }
      }
      fence_release();
      __syncwarp();
      if (lane == 0) flag_add(FLAG(F_GATE));
      TS(1);
    }
    } else cluster_wait();
    get_slot();
    } while (redo && !pass++);
    FTS(3);
    const float dmask = (float)(2 * t - (row & 63));
    int c5 = 0;
    uint32_t pv[32];
#pragma unroll 1
    for (int rnd = 0; rnd < (spare ? 0 : 2); rnd++) {
      float O[64];
      FTM(rnd * 8);
      FTG(0);
      FTH(56, c.rnd == rnd);
      c.wait_full(2);
      FTM(rnd * 8 + 1);
      FTH(57, c.rnd == rnd);
#pragma unroll 1
      for (int tile = c.zero; tile < 2; tile++) {
        float acc[128];
        const bool single = tile == 0;
        {
          FTG(tile * 32 + 1);
          const uint32_t a = dk0 + 2 * DG, b = dm0 + 3 * DG;
          c.turn_begin();
          FTG(tile * 32 + 2);
          FTH(58, c.rnd == rnd);
          wg_fence();
          mma_ss_n256_init<1>(acc, a, b);
#pragma unroll
          for (int k = 1; k < 4; k++) mma_ss_n256<1>(acc, a + k * 2, b + k * 128);
          wg_commit();
          if (single) c.turn_end();
          if (single && rnd && !c.wg) { stsm_frag(pv, stg); c.staged(0); }
          FTG(tile * 32 + 3);
        }
#pragma unroll 1
        for (int kb = 1; kb < 8; kb++) {
          const int g0 = 2 + 3 * (kb & 3);
          const uint32_t a = dk0 + g0 * DG, b = dm0 + (g0 + 1) * DG;
          const bool second = (kb == 1 && !single) || kb == 7;
          FTG(tile * 32 + kb * 4);
          if (!second) { wg_wait<0>(); c.release(2 + 3 * ((kb - 1) & 3), 3); }
          FTG(tile * 32 + kb * 4 + 1);
          c.wait_full(g0);
          if (!second) c.turn_begin();
          FTG(tile * 32 + kb * 4 + 2);
          wg_fence();
#pragma unroll
          for (int k = 0; k < 4; k++) mma_ss_n256<1>(acc, a + k * 2, b + k * 128);
          wg_commit();
          if (kb != 6) c.turn_end();
          if (second) { wg_wait<1>(); c.release(2 + 3 * ((kb - 1) & 3), 3); }
          FTG(tile * 32 + kb * 4 + 3);
          FTH(58 + kb, c.rnd == rnd || kb > 3);
          if (tile == 1 && kb == 3) { c.wait_stage_free(); stsm_frag<0, 4>(pv, stg); }
          if (tile == 1 && kb == 4) { stsm_frag<4, 8>(pv, stg); c.staged(0); }
        }
        c.rnd = rnd;
        c.wait_stage_free();
        const bool nxt = c.try_full(2);
        wg_wait<0>();
        reg_fence(acc);
        c.release(11, 3);
        pack_frag_scaled(acc, pv, SM_C, SM_C);
        stsm_frag(pv, stg);
        c.staged(0);
        pack_frag<64>(acc, pv);
        pin32(pv, sb);
        FTG(32 + tile * 32);
        if (!nxt) mbar_wait(sb + SM_BAR + (B_FULL + 2) * 8, (c.pf >> 2) & 1);
        c.pf ^= 4;
      }
      TS(1 + rnd * 3);
      FTM(rnd * 8 + 2);
      {
        float qa[64];
        float (&qb)[64] = O;
        {
          FTG(65);
          const uint32_t a = dk0 + 2 * DG, b = dm0 + 4 * DG;
          c.turn_begin();
          FTG(66);
          wg_fence();
          mma_ss_n128_init<1>(qa, a, b);
          mma_ss_n128_init<1>(qb, a + dsw, b);
#pragma unroll
          for (int k = 1; k < 4; k++) {
            mma_ss_n128<1>(qa, a + k * 2, b + k * 128);
            mma_ss_n128<1>(qb, a + dsw + k * 2, b + k * 128);
          }
          wg_commit();
          FTG(67);
        }
#pragma unroll 1
        for (int kb = 1; kb < 16; kb++) {
          const int g0 = 2 + 3 * (kb & 3);
          const uint32_t a = dk0 + g0 * DG, b = dm0 + (g0 + 2) * DG;
          const bool second = kb == 1 || kb == 15;
          FTG(64 + kb * 4);
          if (!second) { wg_wait<0>(); c.release(2 + 3 * ((kb - 1) & 3), 3); }
          FTG(65 + kb * 4);
          c.wait_full(g0);
          if (!second) c.turn_begin();
          FTG(66 + kb * 4);
          FTH(kb - 14, kb < 14);
          wg_fence();
#pragma unroll
          for (int k = 0; k < 4; k++) {
            mma_ss_n128<1>(qa, a + k * 2, b + k * 128);
            mma_ss_n128<1>(qb, a + dsw + k * 2, b + k * 128);
          }
          wg_commit();
          if (kb != 14) c.turn_end();
          if (second) { wg_wait<1>(); c.release(2 + 3 * ((kb - 1) & 3), 3); }
          FTG(67 + kb * 4);
          FTH(2, kb < 15);
          if (kb == QFLUSH) { c.wait_stage_free(); stsm_frag<0, 4>(pv, stg); }
          if (kb == QFLUSH + 1) { stsm_frag<4, 8>(pv, stg); c.staged(0); }
        }
        c.wait_stage_free();
        mbar_wait(sb + SM_BAR + (B_EMPTY + 2) * 8, rnd ^ !redo);
        FTM(rnd * 8 + 3);
        FTH(3, 0);
        wg_wait<0>();
        reg_fence(qa); reg_fence(qb);
        FTH(4, 0);
        c.release(11, 3);
        pack_frag<0>(qa, pv);
        stsm_frag(pv, stg + 2 * GR);
        if (c.wg == 0) {
          pack_frag<0>(qb, pv);
          stsm_frag(pv, stg);
        }
        FTH(6, 0);
        fence_async_smem();
        FTH(7, 0);
        c.wait_full(4);
      }
      TS(2 + rnd * 3);
      FTM(rnd * 8 + 4);
      FTH(5, 0);
      {
        const int nA = idx + 1;
        uint32_t (&P)[32] = pv;
        SoftState z;
        z.m0 = z.m1 = z.l0 = z.l1 = 0.f; z.shifted = c.zero;
#pragma unroll 1
        for (int seg = c.zero;; seg++) {
        if (c.wg == seg) attn_half(c, O, P, z, dk0, dkk, dv0, dmask, seg);
        if (seg) break;
        FTM(rnd * 8 + 5);
        int gk = c.wg ? 4 : 6, gv = c.wg ? 4 : 8;
        uint32_t dq = dk0 + (1 - c.wg < nA ? 2 * DG : 0), dk = dkk + gk * DG;
#pragma unroll 1
        for (int it = 1 - c.wg; it < 17 - c.wg; it++) {
          float S[64];
          FTA(it * 7 + 0); FTH((it < 3 ? 8 + it * 8 : it * 8 - 88) + 0, it >= 3 && it < 15);
          c.turn_begin();
          FTA(it * 7 + 2); FTH((it < 3 ? 8 + it * 8 : it * 8 - 88) + 1, it >= 3 && it < 15);
          wg_fence();
          issue_qk(S, dq, dk);
          wg_commit();
          const uint32_t dv = dv0 + gv * DG;
          uint32_t relk = c.relb + gk * 8, relv = c.relb + gv * 8;
          gk = it == 6 ? 12 : gv == 12 ? 4 : gv + 2;
          gv = it == 16 ? gk : gk == 12 ? 4 : gk + 2;
          uint32_t fk = sb + SM_BAR + (B_FULL + gk) * 8, fv = sb + SM_BAR + (B_FULL + gv) * 8, park = (c.pf >> gk) & 1, parv = (c.pf >> gv) & 1;
          c.pf ^= (1u << gk) | (1u << gv);
          dq = dk0 + (it + 1 < nA ? 2 * DG : 0); dk = dkk + gk * DG;
          float lo0 = z.l0, lo1 = z.l1;
          const bool first = it == nA || it == 0;
          if (it == nA) {
            lo0 = rcp(quad_sum(lo0)); lo1 = rcp(quad_sum(lo1));
            z.m0 = z.m1 = z.l0 = z.l1 = 0.f; z.shifted = 0;
          }
          float s0, s1, d0 = z.m0, d1 = z.m1;
          int pre = z.shifted || (it & 15) == 0;
          float lim = first ? -1.f : SM_LIMIT;
          asm volatile("" : "+r"(relk), "+r"(relv), "+r"(fk), "+r"(fv), "+r"(park), "+r"(parv), "+r"(dq), "+r"(dk), "+r"(pre), "+f"(lim), "+f"(d0), "+f"(d1), "+f"(z.l0), "+f"(z.l1));
          if (it + c.wg > 1) {
            issue_pv<0>(O, P, dv, it != nA + 1 && it != 1, true);
            issue_pv<1>(O, P, dv, 1, true);
            c.turn_end();
          } else if (it) {
            issue_pv<0>(O, P, dv, 0, true);
            wg_commit(); wg_commit();
            c.turn_end();
          } else stage_q2(c, O, P, stg);
          FTA(it * 7 + 3); FTH((it < 3 ? 8 + it * 8 : it * 8 - 88) + 2, it >= 3 && it < 15);
          wg_wait<4>();
          reg_fence(S);
          FTA(it * 7 + 4); FTH((it < 3 ? 8 + it * 8 : it * 8 - 88) + 3, it >= 3 && it < 15);
          if (c.tid < 4) asm volatile("mbarrier.arrive.shared::cluster.b64 _, [%0];" ::"r"(relk) : "memory");
#pragma unroll 1
          for (int pass = 0;; pass++) {
            if (pre) {
              if ((it & 15) == 0) mask_diag(S, dmask);
              if (z.shifted) shift_scores(S, d0, d1);
            }
            float tr[ROT];
            exp_quarter<0, 3>(S, P, tr, s0, s1, sb);
            exp_quarter<1, 2>(S, P, tr, s0, s1, sb);
            exp_quarter<2, 1>(S, P, tr, s0, s1, sb);
            exp_quarter<3, 0>(S, P, tr, s0, s1, sb);
            reg_fence(O);
            if (c.tid < (pass || !it ? 0 : 4)) asm volatile("mbarrier.arrive.shared::cluster.b64 _, [%0];" ::"r"(relv) : "memory");
            const bool ok = mbar_test(fk, park) & mbar_test(fv, parv);
            if (!ok) lim = -1.f;
            FTA(it * 7 + 5); FTH((it < 3 ? 8 + it * 8 : it * 8 - 88) + 4, it >= 3 && it < 15);
            if (!__any_sync(0xffffffffu, !(s0 <= lim && s1 <= lim))) break;
            if (pass) break;
            if (it == nA) {
              uint32_t pk[32];
              pack_frag_scaled(O, pk, lo0, lo1);
              stsm_frag(pk, stg + 2 * GR);
              c.staged(1);
            }
            if (!ok) { mbar_wait(fk, park); mbar_wait(fv, parv); }
            if (!soft_unsafe(s0, s1, first)) break;
            soft_fix(S, O, z, first, d0, d1);
            pre = 1;
          }
          z.l0 += s0; z.l1 += s1;
          FTA(it * 7 + 6); FTH((it < 3 ? 8 + it * 8 : it * 8 - 88) + 5, it >= 3 && it < 15);
        }
        FTM(rnd * 8 + 6);
        }
        FTH(48, 0);
        load_dd();
        c.turn_begin();
        FTH(49, 0);
        wg_fence();
        issue_pv<0>(O, P, dv0 + 12 * DG, 1, true);
        issue_pv<1>(O, P, dv0 + 12 * DG, 1, !c.wg);
        c.turn_end();
        z.l0 = rcp(quad_sum(z.l0)); z.l1 = rcp(quad_sum(z.l1));
        if (rnd) c5 = get_ticket();
        wg_wait<0>();
        reg_fence(O); reg_fence(P);
        FTH(50, 0);
        c.release(12, 2);
        pack_frag_scaled(O, P, z.l0, z.l1);
        if (rnd || c.wg) { stsm_frag(P, stg); c.staged(0); }
        FTM(rnd * 8 + 7);
        FTH(51, 0);
      }
      TS(3 + rnd * 3);
    }
    conv_tasks(c, p, (cn + 1 - c.wg) >> 1, spare, cch + c.wg * cstep, 2 * cstep, c5, dd0, dkk, warp & 3, lane);
    if (c.wg == 1) c.pf ^= 0x14;
    if (c.wg == (cn & 1)) c.turn_begin();
    TS(7);
    if (!spare) {
      const int rt = 2 * grp + rank, ct = idx;
      float acc[64];
      int g0 = P3G + 2, pg = P3G;
      {
        FTO(0);
        c.wait_full(P3G);
        FTO(1);
        const uint32_t a = dk0 + P3G * DG, b = dm0 + (P3G + 1) * DG;
        wg_fence();
        mma_ss_n128_init<1>(acc, a, b);
#pragma unroll
        for (int k = 1; k < 4; k++) mma_ss_n128<1>(acc, a + k * 2, b + k * 128);
        wg_commit();
      }
#pragma unroll 1
      for (int kb = 1; kb < 64; kb++) {
        FTO(kb * 2);
        c.wait_full(g0);
        if (kb == STR && !c.wg) c.turn_begin();
        FTO(kb * 2 + 1);
        const uint32_t a = dk0 + g0 * DG, b = dm0 + (g0 + 1) * DG;
        wg_fence();
#pragma unroll
        for (int k = 0; k < 4; k++) mma_ss_n128<1>(acc, a + k * 2, b + k * 128);
        wg_commit();
        if (kb < STR) { wg_wait<1>(); c.release(pg, kb <= 59 ? 2 : 0); }
        if (kb == FDUMP_KB) FTDUMP();
        pg = g0;
        g0 = g0 == (kb < XK ? 12 : kb < YK ? 10 : 8) ? (kb == 3 ? 2 : 0) : g0 + 2;
      }
      if (c.wg) c.turn_end();
      cluster_arrive();
      c.wait_full(P3X);
      c.wait_full(P3Y);
      const float g0f = __uint_as_float(lds32(sb + SM_GATE + row * 4)), g1f = __uint_as_float(lds32(sb + SM_GATE + row * 4 + 32));
      const uint32_t gp0 = pack_bf16(g0f, g0f), gp1 = pack_bf16(g1f, g1f);
      const float h0 = 1.f - g0f, h1 = 1.f - g1f;
      const int w = warp & 3;
      const uint32_t xa = stg + P3X * GR;
      const uint32_t ya = sb + P3Y * GR + c.wg * 16384 + ((lane >> 4) * 8 + (lane & 7)) * 128 + (((2 * w + ((lane >> 3) & 1)) ^ (lane & 7)) << 4);
      uint32_t xy[32];
      auto prep = [&](int j0, int j1) {
#pragma unroll
        for (int jj = j0; jj < j1; jj++) {
          uint32_t x[4], y[4];
          asm volatile("ldmatrix.sync.aligned.m8n8.x4.shared.b16 {%0,%1,%2,%3}, [%4];" : "=r"(x[0]), "=r"(x[1]), "=r"(x[2]), "=r"(x[3]) : "r"((xa ^ ((jj & 3) << 5)) + (jj >> 2) * 16384) : "memory");
          asm volatile("ldmatrix.sync.aligned.m8n8.x4.trans.shared.b16 {%0,%1,%2,%3}, [%4];" : "=r"(y[0]), "=r"(y[1]), "=r"(y[2]), "=r"(y[3]) : "r"(ya + jj * 2048) : "memory");
#pragma unroll
          for (int i = 0; i < 4; i++) xy[4 * jj + i] = hmul2(x[i], y[i]);
        }
      };
      prep(0, 4);
      wg_wait<0>();
      reg_fence(acc);
      TS(8);
#pragma unroll
      for (int hf = 0; hf < 2; hf++) {
#pragma unroll
        for (int i = 16 * hf; i < 16 * hf + 16; i++) {
          const float h = (i & 1) ? h1 : h0;
          xy[i] = hfma2((i & 1) ? gp1 : gp0, xy[i], pack_bf16(acc[2 * i] * h, acc[2 * i + 1] * h));
        }
        if (hf) stsm_frag<4, 8>(xy, xa); else stsm_frag<0, 4>(xy, xa);
        fence_async_smem();
        __syncwarp();
        const int r0 = c.wg * 64 + w * 16;
        if (lane == 0) tma2d_store(&p.out, sb + (P3X + hf) * GR + r0 * 128, ct * 128 + hf * 64, rt * 128 + r0);
        if (!hf) prep(4, 8);
      }
      if (lane == 0) asm volatile("cp.async.bulk.commit_group;\ncp.async.bulk.wait_group.read 0;" ::: "memory");
    } else { FTDUMP(); cluster_arrive(); }
    if (lane == 0) mbar_arrive(sb + SM_BAR + B_DONE * 8);
    __syncwarp();
    TS(9);
    cluster_wait();
  }
}

typedef CUresult (*EncFn)(CUtensorMap*, CUtensorMapDataType, cuuint32_t, void*, const cuuint64_t*, const cuuint64_t*, const cuuint32_t*,
                          const cuuint32_t*, CUtensorMapInterleave, CUtensorMapSwizzle, CUtensorMapL2promotion, CUtensorMapFloatOOBfill);

void enc2d(EncFn enc, CUtensorMap* tm, const void* base, uint64_t cols, uint64_t rows, uint32_t bc, uint32_t br) {
  cuuint64_t dims[2] = {cols, rows}; cuuint64_t strides[1] = {cols * 2}; cuuint32_t box[2] = {bc, br}; cuuint32_t es[2] = {1, 1};
  enc(tm, CU_TENSOR_MAP_DATA_TYPE_BFLOAT16, 2, const_cast<void*>(base), dims, strides, box, es, CU_TENSOR_MAP_INTERLEAVE_NONE,
      CU_TENSOR_MAP_SWIZZLE_128B, CU_TENSOR_MAP_L2_PROMOTION_L2_256B, CU_TENSOR_MAP_FLOAT_OOB_FILL_NONE);
}
void enc3d(EncFn enc, CUtensorMap* tm, const void* base, uint64_t K, uint64_t N, uint32_t bk = 64) {
  cuuint64_t dims[3] = {64, K, N / 64}; cuuint64_t strides[2] = {N * 2, 128}; cuuint32_t box[3] = {64, bk, 2}; cuuint32_t es[3] = {1, 1, 1};
  enc(tm, CU_TENSOR_MAP_DATA_TYPE_BFLOAT16, 3, const_cast<void*>(base), dims, strides, box, es, CU_TENSOR_MAP_INTERLEAVE_NONE,
      CU_TENSOR_MAP_SWIZZLE_128B, CU_TENSOR_MAP_L2_PROMOTION_L2_256B, CU_TENSOR_MAP_FLOAT_OOB_FILL_NONE);
}

}

extern "C" void kernel_launch(void* const* d_in, const int* in_sizes, int n_in, void* d_out, int out_size) {
  (void)in_sizes; (void)n_in; (void)out_size;
  typedef const __nv_bfloat16* BP;
  BP xq = (BP)d_in[0], ak = (BP)d_in[1], av = (BP)d_in[2], shk = (BP)d_in[3], ssk = (BP)d_in[4], ssd = (BP)d_in[5];
  BP ckv = (BP)d_in[7], wq = (BP)d_in[8], wuk = (BP)d_in[9], wuv = (BP)d_in[10], wo = (BP)d_in[11], gw = (BP)d_in[12];

  static EncFn enc = nullptr;
  if (!enc) {
    cudaDriverEntryPointQueryResult qr;
    cudaGetDriverEntryPoint("cuTensorMapEncodeTiled", (void**)&enc, cudaEnableDefault, &qr);
    cudaFuncSetAttribute(mega_kernel, cudaFuncAttributeMaxDynamicSharedMemorySize, SMEM_BYTES);
  }
  Params p;
  void* yT = nullptr;
  cudaGetSymbolAddress(&yT, g_yT);
  enc2d(enc, &p.x, xq, DM, SEQ, 64, 128);
  enc2d(enc, &p.c, ckv, DC, SEQ, 64, 128);
  enc3d(enc, &p.wq, wq, DM, NH * HD);
  enc3d(enc, &p.wuk, wuk, DC, NH * HD);
  enc3d(enc, &p.wuv, wuv, DC, NH * HD);
  enc2d(enc, &p.wo, wo, DM, NH * HD, 64, 64);
  enc3d(enc, &p.x3, xq, SEQ, DM, 128);
  enc3d(enc, &p.y3, yT, DM, SEQ, 128);
  enc2d(enc, &p.out, d_out, DM, SEQ, 64, 16);
  {
    void* wp = nullptr;
    cudaGetSymbolAddress(&wp, g_w);
    cuuint64_t dims[3] = {WSTRIDE / 2, DM / 2, 2}; cuuint64_t strides[2] = {2 * WSTRIDE, WSTRIDE}; cuuint32_t box[3] = {16, 32, 2}; cuuint32_t es[3] = {1, 1, 1};
    enc(&p.w, CU_TENSOR_MAP_DATA_TYPE_BFLOAT16, 3, wp, dims, strides, box, es, CU_TENSOR_MAP_INTERLEAVE_NONE,
        CU_TENSOR_MAP_SWIZZLE_32B, CU_TENSOR_MAP_L2_PROMOTION_NONE, CU_TENSOR_MAP_FLOAT_OOB_FILL_NONE);
  }
  p.zero = 0;
  cudaGetSymbolAddress((void**)&p.flags, g_flags);
  for (int i = 0; i < 128; i++) {
    const int tp = i % NSLOT;
    p.pref[i] = tp < 32 ? (tp & 7) * 8 + (tp >> 3) : tp < 60 ? (1 + (tp - 32) % 7) * 8 + 4 + (tp - 32) / 7 : tp < 62 ? tp + 4 : tp - 58;
  }
  p.gate_w = gw; p.ak = ak; p.av = av; p.shk = shk; p.ssk = ssk; p.ssd = ssd; p.wop = wo;

  mega_kernel<<<132, NTHREADS, SMEM_BYTES>>>(p);
}
```

```cpp
#include <cuda_runtime.h>
#include <cuda.h>
#include <cuda_bf16.h>
#include <stdint.h>

namespace {

constexpr int SEQ = 2048, DM = 1024, DC = 512, NH = 32, HD = 128;
constexpr int GR = 16384;
constexpr int NGR = 14;
constexpr int SM_BAR = NGR * GR;
constexpr int SM_GATE = SM_BAR + 512;
constexpr int SM_UST = SM_GATE + 512;
constexpr int SMEM_BYTES = SM_UST + 2048;
constexpr int NTHREADS = 384;
#define SM_LIMIT 1.0995116e12f
#define SM_LOW 9.094947e-13f
#define CNS 104
constexpr int CN_SPARE = CNS, NTICK = 256 - 2 * CN_SPARE;
constexpr int XK = 57, YK = 62;
constexpr int STR = 61;
constexpr int P3G = 6, P3X = 12, P3Y = 10;
constexpr int NMAIN = 128;

constexpr int B_FULL = 0, B_FREE = 14, B_SLOT = 16, B_DONE = 17, B_EMPTY = 18, B_EV = 32, B_TICK = 36;
constexpr int V_SLOT = 37, V_TICK = 38;

__device__ __align__(1024) uint8_t g_kv[2 * 16 * 16 * 32768];
__device__ __align__(1024) uint8_t g_cimg[16 * NH * 32768];
__device__ __align__(1024) __nv_bfloat16 g_yT[DM * SEQ];
__device__ __align__(1024) float g_gate[SEQ];
constexpr int WZ = 256, WPL = WZ + 4096, WBYTES = 2 * WPL + 32, WSTRIDE = 2 * WPL + 128;
__device__ __align__(1024) uint8_t g_w[DM * WSTRIDE];
__device__ __align__(32) unsigned g_flags[96 * 8];
constexpr int F_KV = 0, F_CTX = 16, F_U = 48, F_AD = 56, F_Y = 64, F_GATE = 72, F_EXIT = 73, F_TICK = 74;
constexpr int NSLOT = 66;
#define FLAG(i) (&g_flags[(i) * 8])
#define CLAIMP(i) (p.flags + (i) * 8 + 1)

#define TS(slot)
#define TSW(slot)
#define FTX(i, off)
#define FTDUMP()

#define QFLUSH 4
#define TKCG 10
#define PSL 200
#define US0 800
#define EROT 6
#define X_DELAY 900
#define X_D2 600
#define P3PF 10
#define P3PF0 5
#define EXPV 1
#define SUMV 0
#define ROT 8
#define KVARR 1
#define KV_ROW(idx, t) (KVARR ? 8 * (t) + 2 * ((idx) & 3) : 2 * (idx))
#define KV_HEAD(idx, t) (KVARR ? (idx) >> 2 : (t))
#define FINE_MODE 0
#define FDUMP_KB 40
#define FINE_RND 1
#define FTA(i) do { if (FINE_MODE == 0) FTX(i, rnd ^ FINE_RND); } while (0)
#define FTG(i) do { if (FINE_MODE == 1) FTX(i, rnd ^ FINE_RND); } while (0)
#define FTM(i) do { if (FINE_MODE == 4) FTX(i, 0); } while (0)
#define FTC(k) do { if (FINE_MODE == 5) FTX((i & 7) * 8 + (k), (i >> 3) ^ FINE_RND); } while (0)
#define FTH(i, off) do { if (FINE_MODE == 6) FTX(i, (c.rnd ^ FINE_RND) | (off)); } while (0)
#define FTS(i)
#define FTSD(i)
#define FTSW(i)
#define FTP(i)
#define FTO(i) do { if (FINE_MODE == 2) FTX(i, 0); } while (0)

__device__ __forceinline__ uint32_t smem_u32(const void* p) { return (uint32_t)__cvta_generic_to_shared(p); }
__device__ __forceinline__ void mbar_init(uint32_t bar, int cnt) { asm volatile("mbarrier.init.shared::cta.b64 [%0], %1;" ::"r"(bar), "r"(cnt) : "memory"); }
__device__ __forceinline__ void mbar_expect_tx(uint32_t bar, uint32_t bytes) { asm volatile("mbarrier.arrive.expect_tx.shared::cta.b64 _, [%0], %1;" ::"r"(bar), "r"(bytes) : "memory"); }
__device__ __forceinline__ void mbar_arrive(uint32_t bar) { asm volatile("mbarrier.arrive.shared::cta.b64 _, [%0];" ::"r"(bar) : "memory"); }
__device__ __forceinline__ void mbar_arrive_cluster(uint32_t bar, uint32_t cta) {
  asm volatile("{\n.reg .b32 r;\nmapa.shared::cluster.u32 r, %0, %1;\nmbarrier.arrive.shared::cluster.b64 _, [r];\n}\n" ::"r"(bar), "r"(cta) : "memory");
}
__device__ __forceinline__ void send_both(uint32_t bar, uint32_t off, uint32_t v) {
#pragma unroll
  for (int r = 0; r < 2; r++)
    asm volatile("{\n.reg .b32 a, b;\nmapa.shared::cluster.u32 a, %0, %1;\nadd.u32 b, a, %3;\nst.async.shared::cluster.mbarrier::complete_tx::bytes.u32 [b], %2, [a];\n}\n"
                 ::"r"(bar), "r"(r), "r"(v), "r"(off) : "memory");
}
__device__ __forceinline__ bool mbar_try(uint32_t bar, uint32_t parity) {
  uint32_t ok;
  asm volatile("{\n.reg .pred p;\nmbarrier.try_wait.parity.shared::cta.b64 p, [%1], %2, 20000;\nselp.u32 %0, 1, 0, p;\n}\n" : "=r"(ok) : "r"(bar), "r"(parity) : "memory");
  return ok;
}
__device__ __forceinline__ bool mbar_test(uint32_t bar, uint32_t parity) {
  uint32_t ok;
  asm volatile("{\n.reg .pred p;\nmbarrier.test_wait.parity.shared::cta.b64 p, [%1], %2;\nselp.u32 %0, 1, 0, p;\n}\n" : "=r"(ok) : "r"(bar), "r"(parity) : "memory");
  return ok;
}
__device__ __forceinline__ void mbar_wait(uint32_t bar, uint32_t parity) {
  asm volatile("{\n.reg .pred p;\nWAIT_LOOP:\nbar.warp.sync -1;\nmbarrier.try_wait.parity.shared::cta.b64 p, [%0], %1;\n@!p bra WAIT_LOOP;\n}\n" ::"r"(bar), "r"(parity) : "memory");
}
__device__ __forceinline__ void mbar_wait1(uint32_t bar, uint32_t parity) {
  asm volatile("{\n.reg .pred p;\nWAIT_LOOP:\nbar.warp.sync -1;\nmbarrier.try_wait.parity.shared::cta.b64 p, [%0], %1, 4000;\n@!p bra WAIT_LOOP;\n}\n" ::"r"(bar), "r"(parity) : "memory");
}
constexpr uint64_t EV_FIRST = 0x12F0000000000000ull;
__device__ __forceinline__ uint32_t ldg_stream(const uint32_t* p) {
  uint32_t r; asm volatile("ld.global.nc.L1::no_allocate.L2::cache_hint.b32 %0, [%1], %2;" : "=r"(r) : "l"(p), "l"(EV_FIRST)); return r;
}
#define TMA_LD "cp.async.bulk.tensor."
#define TMA_MB ".shared::cluster.global.mbarrier::complete_tx::bytes"
__device__ __forceinline__ void tma2d(uint32_t dst, const CUtensorMap* tm, int c0, int c1, uint32_t bar) {
  asm volatile(TMA_LD "2d" TMA_MB " [%0], [%1, {%3, %4}], [%2];" ::"r"(dst), "l"(tm), "r"(bar), "r"(c0), "r"(c1) : "memory");
}
template <bool ONCE = false> __device__ __forceinline__ void tma2d_mc(uint32_t dst, const CUtensorMap* tm, int c0, int c1, uint32_t bar) {
  if (ONCE) asm volatile(TMA_LD "2d" TMA_MB ".multicast::cluster.L2::cache_hint [%0], [%1, {%3, %4}], [%2], %5, %6;"
                         ::"r"(dst), "l"(tm), "r"(bar), "r"(c0), "r"(c1), "h"((uint16_t)3), "l"(EV_FIRST) : "memory");
  else asm volatile(TMA_LD "2d" TMA_MB ".multicast::cluster [%0], [%1, {%3, %4}], [%2], %5;"
                    ::"r"(dst), "l"(tm), "r"(bar), "r"(c0), "r"(c1), "h"((uint16_t)3) : "memory");
}
__device__ __forceinline__ void tma3d(uint32_t dst, const CUtensorMap* tm, int c0, int c1, int c2, uint32_t bar) {
  asm volatile(TMA_LD "3d" TMA_MB " [%0], [%1, {%3, %4, %5}], [%2];" ::"r"(dst), "l"(tm), "r"(bar), "r"(c0), "r"(c1), "r"(c2) : "memory");
}
__device__ __forceinline__ void tma3d_mc(uint32_t dst, const CUtensorMap* tm, int c0, int c1, int c2, uint32_t bar) {
  asm volatile(TMA_LD "3d" TMA_MB ".multicast::cluster [%0], [%1, {%3, %4, %5}], [%2], %6;"
               ::"r"(dst), "l"(tm), "r"(bar), "r"(c0), "r"(c1), "r"(c2), "h"((uint16_t)3) : "memory");
}
template <bool ONCE = false> __device__ __forceinline__ void bulk_g2s(uint32_t dst, const void* src, uint32_t bytes, uint32_t bar) {
  if (ONCE) asm volatile("cp.async.bulk" TMA_MB ".L2::cache_hint [%0], [%1], %2, [%3], %4;" ::"r"(dst), "l"(src), "r"(bytes), "r"(bar), "l"(EV_FIRST) : "memory");
  else asm volatile("cp.async.bulk" TMA_MB " [%0], [%1], %2, [%3];" ::"r"(dst), "l"(src), "r"(bytes), "r"(bar) : "memory");
}
__device__ __forceinline__ void tma2d_store(const CUtensorMap* tm, uint32_t src, int c0, int c1) {
  asm volatile("cp.async.bulk.tensor.2d.global.shared::cta.bulk_group [%0, {%2, %3}], [%1];" ::"l"(tm), "r"(src), "r"(c0), "r"(c1) : "memory");
}
__device__ __forceinline__ void prefetch_tm(const CUtensorMap* tm) { asm volatile("prefetch.tensormap [%0];" ::"l"(tm) : "memory"); }
__device__ __forceinline__ void wg_fence() { asm volatile("wgmma.fence.sync.aligned;" ::: "memory"); }
__device__ __forceinline__ void wg_commit() { asm volatile("wgmma.commit_group.sync.aligned;" ::: "memory"); }
template <int N> __device__ __forceinline__ void wg_wait() { asm volatile("wgmma.wait_group.sync.aligned %0;" ::"n"(N) : "memory"); }
__device__ __forceinline__ void bar_sync(int id, int n) { asm volatile("bar.sync %0, %1;" ::"r"(id), "r"(n) : "memory"); }
__device__ __forceinline__ void bar_arrive(int id, int n) { asm volatile("bar.arrive %0, %1;" ::"r"(id), "r"(n) : "memory"); }
__device__ __forceinline__ void fence_async_smem() { asm volatile("fence.proxy.async.shared::cta;" ::: "memory"); }
__device__ __forceinline__ void fence_async_all() { asm volatile("fence.proxy.async.global;" ::: "memory"); }
__device__ __forceinline__ uint32_t pack_bf16(float lo, float hi) { uint32_t r; asm("cvt.rn.bf16x2.f32 %0, %1, %2;" : "=r"(r) : "f"(hi), "f"(lo)); return r; }
__device__ __forceinline__ float ex2(float x) { float r; asm("ex2.approx.ftz.f32 %0, %1;" : "=f"(r) : "f"(x)); return r; }
__device__ __forceinline__ float rcp(float x) { float r; asm("rcp.approx.ftz.f32 %0, %1;" : "=f"(r) : "f"(x)); return r; }
__device__ __forceinline__ void flag_wait(const unsigned* f, unsigned target) {
  unsigned v;
  do { asm volatile("ld.acquire.gpu.global.u32 %0, [%1];" : "=r"(v) : "l"(f) : "memory"); } while (__any_sync(0xffffffffu, v < target));
}
__device__ __forceinline__ bool elect() {
  uint32_t r;
  asm volatile("{\n.reg .pred p;\nelect.sync _|p, -1;\nselp.u32 %0, 1, 0, p;\n}\n" : "=r"(r));
  return r;
}
__device__ __forceinline__ void fence_release() { asm volatile("fence.release.gpu;" ::: "memory"); }
__device__ __forceinline__ void flag_add(unsigned* f) { asm volatile("red.relaxed.gpu.global.inc.u32 [%0], 0x7fffffff;" ::"l"(f) : "memory"); }
__device__ __forceinline__ void cluster_arrive() { asm volatile("barrier.cluster.arrive.relaxed.aligned;" ::: "memory"); }
__device__ __forceinline__ void cluster_wait() { asm volatile("barrier.cluster.wait.aligned;" ::: "memory"); }
__device__ __forceinline__ uint32_t hmul2(uint32_t a, uint32_t b) { uint32_t r; asm("mul.rn.bf16x2 %0, %1, %2;" : "=r"(r) : "r"(a), "r"(b)); return r; }
__device__ __forceinline__ uint32_t hadd2(uint32_t a, uint32_t b) { uint32_t r; asm("add.rn.bf16x2 %0, %1, %2;" : "=r"(r) : "r"(a), "r"(b)); return r; }
__device__ __forceinline__ uint32_t hfma2(uint32_t a, uint32_t b, uint32_t c) { uint32_t r; asm("fma.rn.bf16x2 %0, %1, %2, %3;" : "=r"(r) : "r"(a), "r"(b), "r"(c)); return r; }
__device__ __forceinline__ uint32_t lds32(uint32_t a) { uint32_t r; asm volatile("ld.shared.b32 %0, [%1];" : "=r"(r) : "r"(a) : "memory"); return r; }
__device__ __forceinline__ uint4 lds128(uint32_t a) { uint4 r; asm volatile("ld.shared.v4.b32 {%0,%1,%2,%3}, [%4];" : "=r"(r.x), "=r"(r.y), "=r"(r.z), "=r"(r.w) : "r"(a) : "memory"); return r; }
__device__ __forceinline__ uint32_t desc_k(uint32_t addr) { return ((addr & 0x3FFFF) >> 4) | (1u << 16); }
template <int LBO> __device__ __forceinline__ uint32_t desc_mn(uint32_t addr) { return ((addr & 0x3FFFF) >> 4) | ((uint32_t)(LBO >> 4) << 16); }
#define DHI "0x40000040"

#define R8(d, o) "+f"(d[o]), "+f"(d[o + 1]), "+f"(d[o + 2]), "+f"(d[o + 3]), "+f"(d[o + 4]), "+f"(d[o + 5]), "+f"(d[o + 6]), "+f"(d[o + 7])
#define R32(d, o) R8(d, o), R8(d, o + 8), R8(d, o + 16), R8(d, o + 24)
#define R64(d, o) R32(d, o), R32(d, o + 32)
#define L64 "%0,%1,%2,%3,%4,%5,%6,%7,%8,%9,%10,%11,%12,%13,%14,%15,%16,%17,%18,%19,%20,%21,%22,%23,%24,%25,%26,%27,%28,%29,%30,%31," \
            "%32,%33,%34,%35,%36,%37,%38,%39,%40,%41,%42,%43,%44,%45,%46,%47,%48,%49,%50,%51,%52,%53,%54,%55,%56,%57,%58,%59,%60,%61,%62,%63"
#define L128 L64 ",%64,%65,%66,%67,%68,%69,%70,%71,%72,%73,%74,%75,%76,%77,%78,%79,%80,%81,%82,%83,%84,%85,%86,%87,%88,%89,%90,%91,%92,%93,%94,%95," \
            "%96,%97,%98,%99,%100,%101,%102,%103,%104,%105,%106,%107,%108,%109,%110,%111,%112,%113,%114,%115,%116,%117,%118,%119,%120,%121,%122,%123,%124,%125,%126,%127"

template <int TB> __device__ __forceinline__ void mma_ss_n128(float (&d)[64], uint32_t da, uint32_t db) {
  asm volatile("{\n.reg .b64 da, db;\nmov.b64 da, {%64, " DHI "};\nmov.b64 db, {%65, " DHI "};\n"
               "wgmma.mma_async.sync.aligned.m64n128k16.f32.bf16.bf16 {" L64 "}, da, db, 1, 1, 1, 0, %66;\n}\n"
               : R64(d, 0) : "r"(da), "r"(db), "n"(TB));
}
template <int TB> __device__ __forceinline__ void mma_rs_n128(float (&d)[64], uint32_t a0, uint32_t a1, uint32_t a2, uint32_t a3, uint32_t db, int sd) {
  asm volatile("{\n.reg .pred p;\n.reg .b64 db;\nsetp.ne.b32 p, %69, 0;\nmov.b64 db, {%68, " DHI "};\n"
               "wgmma.mma_async.sync.aligned.m64n128k16.f32.bf16.bf16 {" L64 "}, {%64,%65,%66,%67}, db, p, 1, 1, %70;\n}\n"
               : R64(d, 0) : "r"(a0), "r"(a1), "r"(a2), "r"(a3), "r"(db), "r"(sd), "n"(TB));
}
template <int TB> __device__ __forceinline__ void mma_ss_n256(float (&d)[128], uint32_t da, uint32_t db) {
  asm volatile("{\n.reg .b64 da, db;\nmov.b64 da, {%128, " DHI "};\nmov.b64 db, {%129, " DHI "};\n"
               "wgmma.mma_async.sync.aligned.m64n256k16.f32.bf16.bf16 {" L128 "}, da, db, 1, 1, 1, 0, %130;\n}\n"
               : R64(d, 0), R64(d, 64) : "r"(da), "r"(db), "n"(TB));
}
#define W8(d, o) "=f"(d[o]), "=f"(d[o + 1]), "=f"(d[o + 2]), "=f"(d[o + 3]), "=f"(d[o + 4]), "=f"(d[o + 5]), "=f"(d[o + 6]), "=f"(d[o + 7])
#define W32(d, o) W8(d, o), W8(d, o + 8), W8(d, o + 16), W8(d, o + 24)
#define W64(d, o) W32(d, o), W32(d, o + 32)
template <int TB> __device__ __forceinline__ void mma_ss_n128_init(float (&d)[64], uint32_t da, uint32_t db) {
  asm volatile("{\n.reg .b64 da, db;\nmov.b64 da, {%64, " DHI "};\nmov.b64 db, {%65, " DHI "};\n"
               "wgmma.mma_async.sync.aligned.m64n128k16.f32.bf16.bf16 {" L64 "}, da, db, 0, 1, 1, 0, %66;\n}\n"
               : W64(d, 0) : "r"(da), "r"(db), "n"(TB));
}
template <int TB> __device__ __forceinline__ void mma_ss_n256_init(float (&d)[128], uint32_t da, uint32_t db) {
  asm volatile("{\n.reg .b64 da, db;\nmov.b64 da, {%128, " DHI "};\nmov.b64 db, {%129, " DHI "};\n"
               "wgmma.mma_async.sync.aligned.m64n256k16.f32.bf16.bf16 {" L128 "}, da, db, 0, 1, 1, 0, %130;\n}\n"
               : W64(d, 0), W64(d, 64) : "r"(da), "r"(db), "n"(TB));
}
#define L32 "%0,%1,%2,%3,%4,%5,%6,%7,%8,%9,%10,%11,%12,%13,%14,%15,%16,%17,%18,%19,%20,%21,%22,%23,%24,%25,%26,%27,%28,%29,%30,%31"
__device__ __forceinline__ void mma_ss_n64(float (&d)[32], uint32_t da, uint32_t db) {
  asm volatile("{\n.reg .b64 da, db;\nmov.b64 da, {%32, " DHI "};\nmov.b64 db, {%33, " DHI "};\n"
               "wgmma.mma_async.sync.aligned.m64n64k16.f32.bf16.bf16 {" L32 "}, da, db, 1, 1, 1, 0, 0;\n}\n"
               : R32(d, 0) : "r"(da), "r"(db));
}
__device__ __forceinline__ void mma_ss_n64_init(float (&d)[32], uint32_t da, uint32_t db) {
  asm volatile("{\n.reg .b64 da, db;\nmov.b64 da, {%32, " DHI "};\nmov.b64 db, {%33, " DHI "};\n"
               "wgmma.mma_async.sync.aligned.m64n64k16.f32.bf16.bf16 {" L32 "}, da, db, 0, 1, 1, 0, 0;\n}\n"
               : W32(d, 0) : "r"(da), "r"(db));
}
#define L16 "%0,%1,%2,%3,%4,%5,%6,%7,%8,%9,%10,%11,%12,%13,%14,%15"
template <int O, bool INIT> __device__ __forceinline__ void mma_rs_n32(float (&d)[128], uint32_t a0, uint32_t a1, uint32_t a2, uint32_t a3, uint32_t db) {
  if (INIT) asm volatile("{\n.reg .b64 db;\nmov.b64 db, {%20, 0x00000008};\n"
               "wgmma.mma_async.sync.aligned.m64n32k16.f32.bf16.bf16 {" L16 "}, {%16,%17,%18,%19}, db, 0, 1, 1, 0;\n}\n"
               : W8(d, O), W8(d, O + 8) : "r"(a0), "r"(a1), "r"(a2), "r"(a3), "r"(db));
  else asm volatile("{\n.reg .b64 db;\nmov.b64 db, {%20, 0x00000008};\n"
               "wgmma.mma_async.sync.aligned.m64n32k16.f32.bf16.bf16 {" L16 "}, {%16,%17,%18,%19}, db, 1, 1, 1, 0;\n}\n"
               : R8(d, O), R8(d, O + 8) : "r"(a0), "r"(a1), "r"(a2), "r"(a3), "r"(db));
}
template <int S, int J> __device__ __forceinline__ void conv_step(float (&d)[128], const uint32_t (&a)[64], uint32_t db) {
  if constexpr (J >= 0 && J >= (S >> 1)) {
    mma_rs_n32<16 * J, S == 0>(d, a[4 * S], a[4 * S + 1], a[4 * S + 2], a[4 * S + 3], db + (uint32_t)((2 * J - S) * 16));
    conv_step<S, J - 1>(d, a, db);
  }
}
__device__ __forceinline__ void mma_ss_n8(float (&d)[4], uint32_t da, uint32_t db) {
  asm volatile("{\n.reg .b64 da, db;\nmov.b64 da, {%4, " DHI "};\nmov.b64 db, {%5, 0x00000008};\n"
               "wgmma.mma_async.sync.aligned.m64n8k16.f32.bf16.bf16 {%0,%1,%2,%3}, da, db, 1, 1, 1, 0, 0;\n}\n"
               : "+f"(d[0]), "+f"(d[1]), "+f"(d[2]), "+f"(d[3]) : "r"(da), "r"(db));
}
template <int N> __device__ __forceinline__ void reg_fence(float (&d)[N]) {
#pragma unroll
  for (int i = 0; i < N; i++) asm volatile("" : "+f"(d[i])::"memory");
}
template <int N> __device__ __forceinline__ void reg_fence(uint32_t (&d)[N]) {
#pragma unroll
  for (int i = 0; i < N; i++) asm volatile("" : "+r"(d[i])::"memory");
}

struct __align__(64) Params {
  unsigned* flags;
  int zero;
  uint8_t pref[128];
  const __nv_bfloat16 *gate_w, *ak, *av, *shk, *ssk, *ssd, *wop;
  CUtensorMap x, c, wq, wuk, wuv, wo, x3, y3, out, w;
};

template <int O, int N, int M> __device__ __forceinline__ void pack_frag(const float (&acc)[N], uint32_t (&pk)[M]) {
#pragma unroll
  for (int i = 0; i < 32; i++) pk[i] = pack_bf16(acc[O + 2 * i], acc[O + 2 * i + 1]);
}
template <int N> __device__ __forceinline__ void pack_frag_scaled(const float (&acc)[N], uint32_t (&pk)[32], float s0, float s1) {
#pragma unroll
  for (int i = 0; i < 32; i++) { const float s = (i & 1) ? s1 : s0; pk[i] = pack_bf16(acc[2 * i] * s, acc[2 * i + 1] * s); }
}
template <int J0 = 0, int J1 = 8, int M> __device__ __forceinline__ void stsm_frag(const uint32_t (&pk)[M], uint32_t a) {
#pragma unroll
  for (int jj = J0; jj < J1; jj++)
    asm volatile("stmatrix.sync.aligned.m8n8.x4.shared.b16 [%0], {%1,%2,%3,%4};" ::"r"((a ^ ((jj & 3) << 5)) + (jj >> 2) * 16384),
                 "r"(pk[4 * jj]), "r"(pk[4 * jj + 1]), "r"(pk[4 * jj + 2]), "r"(pk[4 * jj + 3]) : "memory");
}

struct Cons {
  uint32_t sb;
  uint32_t pf;
  int wg, tid;
  __device__ __forceinline__ void wait_full(int g) { mbar_wait(sb + SM_BAR + (B_FULL + g) * 8, (pf >> g) & 1); pf ^= 1u << g; }
  uint32_t relb;
  __device__ __forceinline__ void release(int g, int n) {
    if (tid < 2 * n) asm volatile("mbarrier.arrive.shared::cluster.b64 _, [%0];" ::"r"(relb + g * 8) : "memory");
  }
  __device__ __forceinline__ void turn_begin() { bar_sync(1 + wg, 256); }
  __device__ __forceinline__ void turn_end() { bar_arrive(2 - wg, 256); }
  __device__ __forceinline__ void staged(int e) { __syncwarp(); if ((tid & 31) == 0) mbar_arrive(sb + SM_BAR + (B_EV + 2 * e + wg) * 8); }
  int zero;
  int rnd;
  uint32_t pfree;
  __device__ __forceinline__ void wait_stage_free() { mbar_wait(sb + SM_BAR + (B_FREE + wg) * 8, pfree); pfree ^= 1; }
  __device__ __forceinline__ bool try_full(int g) { return mbar_test(sb + SM_BAR + (B_FULL + g) * 8, (pf >> g) & 1); }
};

constexpr float SM_C = 0.08838834764831845f * 1.4426950408889634f;
struct SoftState { float m0, m1, l0, l1; int shifted; };
__device__ __forceinline__ void ex2_rot(float& t, float s, uint32_t never_zero) {
  asm("{\n.reg .pred p;\nsetp.ne.u32 p, %2, 0;\n@p ex2.approx.ftz.f32 %0, %1;\n}\n" : "+f"(t) : "f"(s), "r"(never_zero));
}
__device__ __forceinline__ void pin(float a, uint32_t never_zero) {
  asm volatile("{\n.reg .pred p;\nsetp.eq.u32 p, %1, 0;\n@p st.shared.f32 [%1], %0;\n}\n" ::"f"(a), "r"(never_zero) : "memory");
}
template <int O, int N> __device__ __forceinline__ void reg_fence_part(uint32_t (&d)[32]) {
#pragma unroll
  for (int i = O; i < O + N; i++) asm volatile("" : "+r"(d[i])::"memory");
}
template <int Q, int W, int N> __device__ __forceinline__ void exp_quarter(const float (&S)[N], uint32_t (&P)[32], float (&t)[ROT], float& s0, float& s1, uint32_t nz) {
#pragma unroll
  for (int i = 8 * Q; i < 8 * Q + 8; i++) {
    float& a = t[(2 * i) % ROT];
    float& b = t[(2 * i + 1) % ROT];
    if (2 * i < ROT) { a = ex2(S[2 * i]); b = ex2(S[2 * i + 1]); }
    else { ex2_rot(a, S[2 * i], nz); ex2_rot(b, S[2 * i + 1], nz); }
    if (i < 2) { if (i) s1 = a + b; else s0 = a + b; }
    else if (SUMV == 0) { if (i & 1) { s1 += a; s1 += b; } else { s0 += a; s0 += b; } }
    else { if (i & 1) s1 += a + b; else s0 += a + b; }
    if (i == 8 * Q) { pin(EXPV == 1 && Q ? s1 : s0, nz); wg_wait<W>(); reg_fence_part<8 * Q, 8>(P); }
    P[i] = pack_bf16(a, b);
  }
}
template <int N> __device__ __forceinline__ void shift_scores(float (&S)[N], float d0, float d1) {
#pragma unroll
  for (int i = 0; i < N; i++) S[i] -= (i & 2) ? d1 : d0;
}
__device__ __forceinline__ bool soft_high(float s0, float s1, float lim = SM_LIMIT) { return s0 > lim || s1 > lim; }
__device__ __forceinline__ bool soft_unsafe(float s0, float s1, bool first) {
  uint32_t b0 = __ballot_sync(0xffffffffu, s0 >= SM_LOW), b1 = __ballot_sync(0xffffffffu, s1 >= SM_LOW);
  b0 |= b0 >> 1; b0 |= b0 >> 2; b1 |= b1 >> 1; b1 |= b1 >> 2;
  return __any_sync(0xffffffffu, soft_high(s0, s1)) || (first && (b0 & b1 & 0x11111111u) != 0x11111111u);
}
template <int N> __device__ __forceinline__ void soft_fix(const float (&S)[N], float (&O)[64], SoftState& z, bool first, float& d0, float& d1) {
  d0 = d1 = first ? -INFINITY : 0.f;
#pragma unroll
  for (int j = 0; j < N / 4; j++) { d0 = fmaxf(d0, fmaxf(S[4 * j], S[4 * j + 1])); d1 = fmaxf(d1, fmaxf(S[4 * j + 2], S[4 * j + 3])); }
  d0 = fmaxf(d0, __shfl_xor_sync(0xffffffffu, d0, 1)); d1 = fmaxf(d1, __shfl_xor_sync(0xffffffffu, d1, 1));
  d0 = fmaxf(d0, __shfl_xor_sync(0xffffffffu, d0, 2)); d1 = fmaxf(d1, __shfl_xor_sync(0xffffffffu, d1, 2));
  const float sc0 = ex2(-fmaxf(d0, 0.f)), sc1 = ex2(-fmaxf(d1, 0.f));
  z.m0 += d0; z.m1 += d1; z.l0 *= sc0; z.l1 *= sc1; z.shifted = 1;
#pragma unroll
  for (int j = 0; j < 16; j++) { O[4 * j] *= sc0; O[4 * j + 1] *= sc0; O[4 * j + 2] *= sc1; O[4 * j + 3] *= sc1; }
}
template <int M> __device__ __forceinline__ void pin32(const uint32_t (&v)[M], uint32_t never_zero) {
#pragma unroll
  for (int i = 0; i < 32; i += 4)
    asm volatile("{\n.reg .pred p;\nsetp.eq.u32 p, %4, 0;\n@p st.shared.v4.b32 [%4], {%0,%1,%2,%3};\n}\n" ::"r"(v[i]), "r"(v[i + 1]), "r"(v[i + 2]), "r"(v[i + 3]), "r"(never_zero) : "memory");
}
template <int N> __device__ __forceinline__ void mask_diag(float (&S)[N], float nd) {
  asm volatile("" : "+f"(nd));
#pragma unroll
  for (int i = 0; i < 32; i++) {
    const float beyond = __saturatef(nd + (float)(8 * (i >> 2) + (i & 1) - 4 * (i & 2)));
    S[N - 32 + i] = fmaf(beyond, -3.0e38f, S[N - 32 + i]);
  }
}
__device__ __forceinline__ float quad_sum(float v) {
  v += __shfl_xor_sync(0xffffffffu, v, 1);
  v += __shfl_xor_sync(0xffffffffu, v, 2);
  return v;
}
__device__ __forceinline__ void issue_qk(float (&S)[64], uint32_t dq, uint32_t dk) {
  mma_ss_n128_init<0>(S, dq, dk);
#pragma unroll
  for (int s = 1; s < 8; s++) mma_ss_n128<0>(S, dq + (s >> 2) * 1024 + (s & 3) * 2, dk + (s >> 2) * 1024 + (s & 3) * 2);
}
__device__ __forceinline__ void issue_qk(float (&S)[32], uint32_t dq, uint32_t dk) {
  mma_ss_n64_init(S, dq, dk);
#pragma unroll
  for (int s = 1; s < 8; s++) mma_ss_n64(S, dq + (s >> 2) * 1024 + (s & 3) * 2, dk + (s >> 2) * 1024 + (s & 3) * 2);
}
template <int H> __device__ __forceinline__ void issue_pv(float (&O)[64], const uint32_t (&P)[32], uint32_t dv, int acc, bool on) {
  if (on) {
#pragma unroll
    for (int s = 4 * H; s < 4 * H + 4; s++) {
      mma_rs_n128<1>(O, P[4 * s], P[4 * s + 1], P[4 * s + 2], P[4 * s + 3], dv + s * 128, s != 0 ? 1 : acc);
      if (s & 1) wg_commit();
    }
  } else { wg_commit(); wg_commit(); }
}
constexpr uint32_t DG = GR >> 4;
__device__ __forceinline__ void stage_q2(Cons& c, const float (&O)[64], uint32_t (&P)[32], uint32_t stg) {
  wg_commit(); wg_commit(); wg_commit(); wg_commit();
  c.turn_end();
  pack_frag<0>(O, P);
  stsm_frag(P, stg);
  fence_async_smem();
}
__device__ __forceinline__ void attn_half(Cons& c, float (&O)[64], uint32_t (&P)[32], SoftState& z, uint32_t dk0, uint32_t dkk, uint32_t dv0, float dmask, int last) {
  float S[32];
  FTH(8 + last * 32, 0);
  c.turn_begin();
  FTH(9 + last * 32, 0);
  wg_fence();
  issue_qk(S, dk0 + (last ? 0 : 2 * DG), dkk + (last ? 8 : 4) * DG);
  wg_commit();
  issue_pv<0>(O, P, dv0 + 10 * DG, 1, last);
  issue_pv<1>(O, P, dv0 + 10 * DG, 1, last);
  c.turn_end();
  c.wait_full(last ? 12 : 6);
  FTH(10 + last * 32, 0);
  wg_wait<4>();
  reg_fence(S);
  FTH(11 + last * 32, 0);
  c.release(last ? 8 : 4, 2);
  mask_diag(S, dmask);
  float s0, s1, d0 = z.m0, d1 = z.m1;
#pragma unroll 1
  for (int pass = 0;; pass++) {
    if (z.shifted) shift_scores(S, d0, d1);
    float tr[ROT];
    exp_quarter<0, 3>(S, P, tr, s0, s1, c.sb);
    exp_quarter<1, 2>(S, P, tr, s0, s1, c.sb);
    pin(s1, c.sb); wg_wait<0>(); reg_fence_part<16, 16>(P); reg_fence(O);
    if (!soft_unsafe(s0, s1, !last) || pass) break;
    soft_fix(S, O, z, !last, d0, d1);
  }
  FTH(12 + last * 32, 0);
  z.l0 += s0; z.l1 += s1;
  c.release(10, last ? 2 : 0);
  if (!last) c.wait_full(8);
  FTH(13 + last * 32, 0);
}

template <int V> struct IC { static constexpr int value = V; };
__device__ __forceinline__ int conv_next(int g, bool spare) { return g >= NGR - 2 ? g - (NGR - 4) : !spare && g == 4 ? 1 : g + 2; }
__device__ __forceinline__ void conv_final(uint32_t rb, uint32_t yb, bool on) {
  const uint4 q0 = lds128(rb), q1 = lds128(rb + 4096), q2 = lds128(rb + 8192), q3 = lds128(rb + 12288);
  auto fin = [&](uint32_t x0, uint32_t x1, uint32_t x2, uint32_t x3) { return hadd2(hadd2(x0, x1), hadd2(x2, x3)); };
  asm volatile("{\n.reg .pred p;\nsetp.ne.b32 p, %5, 0;\n@p st.shared.v4.b32 [%0], {%1,%2,%3,%4};\n}\n" ::"r"(yb), "r"(fin(q0.x, q1.x, q2.x, q3.x)),
               "r"(fin(q0.y, q1.y, q2.y, q3.y)), "r"(fin(q0.z, q1.z, q2.z, q3.z)), "r"(fin(q0.w, q1.w, q2.w, q3.w)), "r"((int)on) : "memory");
}
__device__ __forceinline__ void conv_tasks(Cons& c, const Params& p, int ntask, bool spare, int ch, int chstep, int c5, uint32_t dd, uint32_t dkk, int w, int lane) {
  const uint32_t sb = c.sb;
  int g = 2 + c.wg;
  uint32_t rb = sb + g * GR;
  const uint32_t yb = sb + c.wg * 8192 + c.tid * 16;
  const int gt = 8 * w + (lane >> 2) + (lane & 3);
  uint32_t a[64], hb;
  auto lda = [&](int s) {
    a[4 * s] = lds32(hb + s * 256); a[4 * s + 1] = lds32(hb + s * 256 + 128);
    a[4 * s + 2] = lds32(hb + s * 256 + 16); a[4 * s + 3] = lds32(hb + s * 256 + 144);
  };
  auto first_a = [&]() {
    hb = sb + g * GR + WBYTES - 28 + gt * 4;
    lda(0); lda(15);
  };
  c.wait_full(g);
  first_a();
#pragma unroll 1
  for (int i = 0; i < ntask; i++) {
    const uint32_t base = sb + g * GR;
    FTC(0);
    lda(1); lda(14);
    a[0] = hadd2(a[0], gt == 7 ? dd : 0u); a[2] = hadd2(a[2], gt == 3 ? dd : 0u);
    float acc[128];
    const uint32_t db = dkk + ((WPL / 16 - 1) << 16) + g * DG + WZ / 16;
    FTC(2);
    c.turn_begin();
    FTC(3);
    auto pair = [&](auto kc) {
      constexpr int k = decltype(kc)::value;
      if (k < 7) wg_fence();
      if (k == 6) c.turn_end();
      conv_step<k, 7>(acc, a, db);
      conv_step<15 - k, 7>(acc, a, db);
      if (k < 6) { lda(k + 2); lda(13 - k); }
      if (k == 0) conv_final(rb, yb, i > 0);
      if (k == 1) {
        conv_final(rb + 2048, yb + 2048, i > 0);
        __syncwarp();
        if (lane == 0 && i > 0) mbar_arrive(sb + SM_BAR + (B_EV + c.wg) * 8);
      }
      if (k == 6) dd = __bfloat16_as_ushort(p.ssd[(ch + chstep + (i == 1 ? c5 : 0)) & (DM - 1)]);
    };
    pair(IC<0>()); pair(IC<1>()); pair(IC<2>()); pair(IC<3>()); pair(IC<4>()); pair(IC<5>()); pair(IC<6>()); pair(IC<7>());
    wg_commit();
    FTC(4);
    g = conv_next(g, spare);
    ch += chstep;
    rb = base + c.tid * 16;
    if (i + 1 < ntask) c.wait_full(g);
    const bool fr = mbar_test(sb + SM_BAR + (B_FREE + c.wg) * 8, c.pfree);
    wg_wait<0>();
    reg_fence(acc);
    reg_fence(a);
    bar_sync(3 + c.wg, 128);
    FTC(5);
    first_a();
    const int tw = (lane & 3) + w;
    const uint32_t xb = base + w * 4096 + tw * 32 + (lane >> 2) * 4;
    [[maybe_unused]] float t0[EROT + 1];
#pragma unroll
    for (int j = 0; j < 32; j++) {
      uint32_t ad = xb + j * 128;
      float v0 = acc[4 * j], v1 = acc[4 * j + 1];
      if (EROT && j > EROT) {
        v0 = t0[j % (EROT + 1)];
        asm("{\n.reg .pred p;\nsetp.ne.u32 p, %3, 0;\n@p add.f32 %0, %1, %2;\n}\n" : "+f"(v0) : "f"(acc[4 * j]), "f"(acc[j > 0 ? 4 * j - 2 : 0]), "r"(sb));
      } else if (j > 0) v0 += acc[j > 0 ? 4 * j - 2 : 0];
      if (j > 0) v1 += acc[j > 0 ? 4 * j - 1 : 0];
      uint32_t v = pack_bf16(v0, v1);
      t0[j % (EROT + 1)] = __uint_as_float(v);
      if (j == 31 && tw >= 4) { v = 0; ad -= 4096; }
      asm volatile("st.shared.b32 [%0], %1;" ::"r"(ad), "r"(v) : "memory");
    }
    if (!fr) c.wait_stage_free(); else c.pfree ^= 1;
    FTC(6);
  }
  bar_sync(3 + c.wg, 128);
  conv_final(rb, yb, true);
  conv_final(rb + 2048, yb + 2048, true);
  c.staged(0);
}

__global__ void __cluster_dims__(2, 1, 1) __launch_bounds__(NTHREADS, 1) mega_kernel(const __grid_constant__ Params p) {
  extern __shared__ __align__(1024) uint8_t smem_raw[];
  FTS(0);
  const uint32_t sb = smem_u32(smem_raw);
  if (threadIdx.x - 64 < 32) { prefetch_tm(&p.c); prefetch_tm(&p.wuk + (blockIdx.x & 1)); }
  const int wgi = __shfl_sync(0xffffffffu, threadIdx.x >> 7, 0);
  const int warp = __shfl_sync(0xffffffffu, threadIdx.x >> 5, 0);
  const uint32_t rank = blockIdx.x & 1;
  int slot;
  {
    uint32_t smid; asm volatile("mov.u32 %0, %smid;" : "=r"(smid));
    slot = p.pref[((smid >> 1) + (threadIdx.x & (smid >> 16))) & 127];
  }
  if (warp >= 3) {
    if (elect()) {
#pragma unroll
      for (int k = 0; k < 4; k++) mbar_init(sb + SM_BAR + ((warp - 3) * 4 + k) * 8, k == 1 && warp == 7 ? 11 : warp < (k ? 7 : 8) ? 1 : 4);
      if (warp == 7) { mbar_init(sb + SM_BAR + B_TICK * 8, 1); mbar_expect_tx(sb + SM_BAR + B_SLOT * 8, 8); mbar_expect_tx(sb + SM_BAR + B_TICK * 8, 4); }
      asm volatile("fence.mbarrier_init.release.cluster;" ::: "memory");
    }
    __syncwarp();
  }
  FTS(1);
  cluster_arrive();
  slot = __shfl_sync(0xffffffffu, slot, 0);
  const int pref = slot;
  if (warp < 4) {
    asm volatile("setmaxnreg.dec.sync.aligned.u32 40;");
    if (warp == 1 + 4 * rank) {
      unsigned taken = threadIdx.x == 32;
#pragma unroll 1
      for (int n = 0; n < NSLOT; n++) {
        asm volatile("{\n.reg .pred p;\nsetp.ne.b32 p, %0, 0;\n@p atom.relaxed.gpu.global.exch.b32 %0, [%1], 1;\n}\n" : "+r"(taken) : "l"(CLAIMP(slot)) : "memory");
        if (!__any_sync(0xffffffffu, taken)) break;
        slot = slot == NSLOT - 1 ? 0 : slot + 1;
      }
    }
    cluster_wait();
    if (threadIdx.x == 32) {
      send_both(sb + SM_BAR + B_SLOT * 8, (V_SLOT - B_SLOT) * 8 + rank * 4, slot | pref << 8);
    }
    if (warp == 2) {
#pragma unroll 1
      for (int kk = 0; kk < 4; kk++) {
        const int g0 = 2 + 3 * kk;
        const uint32_t fb = sb + SM_BAR + (B_FULL + g0) * 8;
        if (elect()) {
          FTSW(kk);
          mbar_expect_tx(fb, 3 * GR);
          tma2d(sb + g0 * GR, &p.c, kk * 64, (KV_ROW(pref & 7, 0) + rank) * 128, fb);
          tma3d_mc(sb + (g0 + 1 + rank) * GR, rank ? &p.wuv : &p.wuk, 0, kk * 64, ((pref & 56) >> 1) + 2 * KV_HEAD(pref & 7, 0), fb);
        }
        if (kk < 3) {
          uint32_t c0, c1;
          asm volatile("mov.u32 %0, %clock;" : "=r"(c0));
          do asm volatile("mov.u32 %0, %clock;" : "=r"(c1)); while (c1 - c0 < (kk ? X_D2 : X_DELAY));
        }
      }
      FTSW(4);
      prefetch_tm(&p.x); prefetch_tm(&p.wq);
    }
  }
  int grp, idx, lb;
  int cn, cch, cstep;
  bool spare, redo;
  auto get_slot = [&]() {
    mbar_wait(sb + SM_BAR + B_SLOT * 8, 0);
    const uint32_t sv0 = __shfl_sync(0xffffffffu, lds32(sb + SM_BAR + V_SLOT * 8), 0), sv1 = __shfl_sync(0xffffffffu, lds32(sb + SM_BAR + V_SLOT * 8 + 4), 0);
    grp = (sv0 & 255) >> 3; idx = sv0 & 7; lb = (sv0 & 255) * 2 + rank;
    spare = grp == 8; redo = spare || sv0 != sv1;
    cn = CN_SPARE; cch = spare ? lb - NMAIN : 4 * CN_SPARE + 4 * lb; cstep = spare ? 4 : 1;
    if (FINE_MODE != 7) TS(0);
  };
  auto get_ticket = [&]() {
    mbar_wait(sb + SM_BAR + B_TICK * 8, 0);
    const int tk = __shfl_sync(0xffffffffu, lds32(sb + SM_BAR + V_TICK * 8), 0);
    cn = tk < NTICK ? 5 : 4;
    return 4 * NMAIN - 4 * lb - 4 + 2 * tk + rank;
  };

  if (wgi == 0) {
    asm volatile("setmaxnreg.dec.sync.aligned.u32 40;");
    const int lane = threadIdx.x & 31;
    cluster_arrive();
    get_slot();
    uint32_t pe = 0;
    auto acquire = [&](int g, int n, uint32_t m) {
      int i = g;
#pragma unroll 1
      do mbar_wait1(sb + SM_BAR + (B_EMPTY + i) * 8, (pe >> i) & 1); while (++i < g + n);
      pe ^= m << g;
    };
    if (warp == 3) {
      if (!spare) {
        const int s0 = lb * 16;
#pragma unroll 1
        for (int cg = 0; cg < 16; cg++) {
          if (cg == 3 || cg == 10) {
#pragma unroll 1
            for (int n = 0; n < 20 && !__any_sync(0xffffffffu, mbar_try(sb + SM_BAR + B_SLOT * 8, cg == 3)); n++);
          } else if (cg < 3) __nanosleep(US0);
          if (cg == TKCG && lane == rank * 32) send_both(sb + SM_BAR + B_TICK * 8, (V_TICK - B_TICK) * 8, atomicInc(FLAG(F_TICK), 0x7fffffffu));
          const int ch = cg * 64 + 2 * lane;
          const uint32_t* kp = reinterpret_cast<const uint32_t*>(p.ak + (size_t)s0 * DM + ch);
          const uint32_t* vp = reinterpret_cast<const uint32_t*>(p.av + (size_t)s0 * DM + ch);
          const uint4 sw = __ldg(reinterpret_cast<const uint4*>(p.shk + ch * 4));
          uint32_t k3 = 0, k2 = 0, k1 = 0, k0 = 0, up = 0;
          if (lb > 0) { k3 = ldg_stream(kp - 4 * 512); k2 = ldg_stream(kp - 3 * 512); k1 = ldg_stream(kp - 2 * 512); k0 = ldg_stream(kp - 512); up = ldg_stream(vp - 512); }
          const uint32_t w0 = __byte_perm(sw.x, sw.z, 0x5410), w1 = __byte_perm(sw.x, sw.z, 0x7632);
          const uint32_t w2 = __byte_perm(sw.y, sw.w, 0x5410), w3 = __byte_perm(sw.y, sw.w, 0x7632);
          up = hmul2(hfma2(k0, w0, hfma2(k1, w1, hfma2(k2, w2, hmul2(k3, w3)))), up);
#pragma unroll 1
          for (int hb = 0; hb < 2; hb++) {
            uint32_t kk[8], u[8];
#pragma unroll
            for (int r = 0; r < 8; r++) { kk[r] = ldg_stream(kp + r * 512); u[r] = ldg_stream(vp + r * 512); }
#pragma unroll
            for (int r = 0; r < 8; r++) {
              k3 = k2; k2 = k1; k1 = k0; k0 = kk[r];
              u[r] = hmul2(hfma2(k0, w0, hfma2(k1, w1, hfma2(k2, w2, hmul2(k3, w3)))), u[r]);
            }
            if (lane == 0) asm volatile("cp.async.bulk.wait_group.read 0;" ::: "memory");
            __syncwarp();
            const uint32_t dst = sb + SM_UST + lane * 32 + ((lane & 4) << 2);
#pragma unroll
            for (int cc = 0; cc < 2; cc++) {
              const uint32_t sel = cc ? 0x7632 : 0x5410;
              asm volatile("st.shared.v4.b32 [%0], {%1,%2,%3,%4};" ::"r"(dst + cc * 1024), "r"(__byte_perm(u[6], u[5], sel)), "r"(__byte_perm(u[4], u[3], sel)),
                           "r"(__byte_perm(u[2], u[1], sel)), "r"(__byte_perm(u[0], up, sel)) : "memory");
              asm volatile("st.shared.v4.b32 [%0], {%1,%2,%3,%4};" ::"r"((dst ^ 16) + cc * 1024), "r"(__byte_perm(u[7], u[6], sel)), "r"(__byte_perm(u[5], u[4], sel)),
                           "r"(__byte_perm(u[3], u[2], sel)), "r"(__byte_perm(u[1], u[0], sel)) : "memory");
            }
            fence_async_smem();
            __syncwarp();
            if (lane == 0) {
              asm volatile("cp.async.bulk.tensor.3d.global.shared::cta.bulk_group [%0, {%2, %3, %4}], [%1];\ncp.async.bulk.commit_group;"
                           ::"l"(&p.w), "r"(sb + SM_UST), "r"(WZ / 2 + lb * 16 + (hb ^ 1) * (WPL / 2)), "r"(cg * 32), "r"(0) : "memory");
            }
            up = u[7];
            kp += 8 * 512; vp += 8 * 512;
          }
          if ((cg & (cg + 1)) == 0 && lane == 0) {
            asm volatile("cp.async.bulk.wait_group 0;" ::: "memory");
            fence_release();
            flag_add(FLAG(F_U + 32 - __clz(cg)));
          }
          TSW(10 + cg);
        }
        prefetch_tm(&p.wo); prefetch_tm(&p.x3); prefetch_tm(&p.y3); prefetch_tm(&p.out);
        if (P3PF) {
          const int rt = 2 * grp + rank;
          unsigned v;
          asm volatile("ld.acquire.gpu.global.u32 %0, [%1];" : "=r"(v) : "l"(FLAG(F_CTX + rt * 2)) : "memory");
#pragma unroll 1
          for (int kb = P3PF0; kb < P3PF0 + P3PF; kb++) {
            const uint8_t* a = lane < 16 ? g_cimg + (unsigned)((rt * 64 + kb) * GR + (idx * 16 + lane) * 128) : (const uint8_t*)p.wop + (unsigned)(kb * 64 * DM * 2 + (lb * 8 + (lane & 7)) * 128);
            if (lane < 24 && v == 32) asm volatile("prefetch.global.L2 [%0];" ::"l"(a));
          }
        }
      } else {
#pragma unroll 1
        for (int i = 0, g = 2; i < 32; i++) {
          acquire(g, 2, 3);
          if (elect()) {
            const uint32_t fb = sb + SM_BAR + (B_FULL + g) * 8;
            if (i == 0) { mbar_expect_tx(fb - 8, 2048); bulk_g2s(sb + GR, p.gate_w, 2048, fb - 8); }
            mbar_expect_tx(fb, 2 * GR);
            tma3d(sb + g * GR, &p.x3, 0, (lb - NMAIN) * 512 + (i >> 3) * 128, (i & 7) * 2, fb);
          }
          g = g == NGR - 2 ? 2 : g + 2;
        }
        bar_arrive(5, 64);
      }
      unsigned long long t0, t1;
      asm volatile("mov.u64 %0, %globaltimer;" : "=l"(t0));
      auto check = [&]() {
        asm volatile("mov.u64 %0, %globaltimer;" : "=l"(t1));
        if (t1 - t0 > 2000000000ull) __trap();
      };
      if (!spare) {
        unsigned v;
        do {
          __nanosleep(PSL);
          check();
          asm volatile("ld.acquire.gpu.global.u32 %0, [%1];" : "=r"(v) : "l"(FLAG(lane & 1 ? F_Y + idx : F_GATE)) : "memory");
        } while (__any_sync(0xffffffffu, v < (lane & 1 ? 128 : 32)));
        __syncwarp();
        if (lane == 0) mbar_arrive(sb + SM_BAR + B_SLOT * 8);
      }
      if (lane == 0) {
        while (!mbar_try(sb + SM_BAR + B_DONE * 8, 0)) check();
      }
    } else if (warp != 0) {
      const int w = warp - 1;
      int ne = 12 + (CN_SPARE + 1 - w) / 2, c5 = 0;
      uint32_t p0 = 0;
      int cg = 2 + w, ch = cch + w * cstep;
#pragma unroll 1
      for (int e = spare ? 12 : 0; e < ne; e++) {
        const int rnd = e >= 6, k = e - 6 * rnd, rt = k == 4 ? idx : 15 - idx;
        uint8_t* dst = k < 4 ? g_kv + (size_t)(((k & 1) * 16 + 2 * grp + KV_HEAD(idx, k >> 1)) * 16 + KV_ROW(idx, k >> 1) + rank) * 32768 + w * 8192
                     : k < 6 ? g_cimg + (size_t)(rt * 32 + 16 * rnd + 2 * grp + rank) * 32768 + (w ^ (k & 1)) * 8192
                             : reinterpret_cast<uint8_t*>(g_yT + (size_t)ch * SEQ);
        const uint32_t src = sb + w * 8192 + (k == 4 ? 2 * GR : 0);
        if (e == 11) { c5 = get_ticket(); ne = 12 + ((cn + 1 - w) >> 1); }
        if (e == 6) flag_wait(FLAG(F_AD + grp), 32);
        mbar_wait1(sb + SM_BAR + (B_EV + (k == 4 ? 2 : 0) + w) * 8, k == 4 ? rnd : p0);
        if (k != 4) p0 ^= 1;
        if (lane < 4 && k >= 6 && (!spare || e < ne - 6)) mbar_arrive_cluster(sb + SM_BAR + (B_EMPTY + cg) * 8, lane & 1);
        fence_async_smem();
        if (elect()) {
          const uint32_t cs = k >= 6 ? 4096 : 1024;
#pragma unroll 1
          for (uint32_t i = 0; i < (k >= 6 ? 4096 : 16384); i += cs) {
            const uint32_t o = i + (i & 8192);
            asm volatile("cp.async.bulk.global.shared::cta.bulk_group [%0], [%1], %2;" ::"l"(dst + o), "r"(src + o), "r"(cs) : "memory");
            asm volatile("cp.async.bulk.commit_group;\ncp.async.bulk.wait_group.read 1;" ::: "memory");
          }
          asm volatile("cp.async.bulk.wait_group 0;" ::: "memory");
          if (k != 4) mbar_arrive(sb + SM_BAR + (B_FREE + w) * 8);
        }
        __syncwarp();
        if (lane < (k == 4 ? 4 : e == 11 || (e == ne - 1 && !spare) ? 2 : 0))
          mbar_arrive_cluster(sb + SM_BAR + (B_EMPTY + (k == 4 ? 2 : e == 11) + (lane >> 1)) * 8, lane & 1);
        if (k >= 3) {
          fence_release();
          const unsigned fl = k == 3 ? F_KV + rnd * 8 + grp : k < 6 ? F_CTX + rt * 2 + rnd : F_Y + ((unsigned)ch >> 7);
          if (lane <= (e == 5)) flag_add(FLAG(lane ? F_AD + grp : fl));
        }
        if (k >= 6) { cg = conv_next(cg, spare); ch += 2 * cstep + (k == 7 ? c5 : 0); }
      }
      if (lane == 0) mbar_arrive(sb + SM_BAR + B_DONE * 8);
    } else {
#pragma unroll 1
      for (int rnd = 0; rnd < (spare ? 0 : 2); rnd++) {
        const int hp = 16 * rnd + 2 * grp, head = hp + rank;
#pragma unroll 1
        for (int kk = rnd || redo ? 0 : 4; kk < 32; kk++) {
          const int g0 = 2 + 3 * (kk & 3);
          acquire(g0, kk < 4 ? 3 : 1, 7);
          if (elect()) {
            const uint32_t fb = sb + SM_BAR + (B_FULL + g0) * 8;
            mbar_expect_tx(fb, 3 * GR);
            if (kk < 16) {
              tma2d(sb + g0 * GR, &p.c, (kk & 7) * 64, (KV_ROW(idx, kk >> 3) + rank) * 128, fb);
              tma3d_mc(sb + (g0 + 1 + rank) * GR, rank ? &p.wuv : &p.wuk, 0, (kk & 7) * 64, (hp + KV_HEAD(idx, kk >> 3)) * 2, fb);
            } else {
              tma2d_mc(sb + (g0 + rank) * GR, &p.x, (kk - 16) * 64, (rank ? 15 - idx : idx) * 128, fb);
              tma3d(sb + (g0 + 2) * GR, &p.wq, 0, (kk - 16) * 64, head * 2, fb);
            }
          }
        }
        flag_wait(FLAG(F_KV + rnd * 8 + grp), 32);
        fence_async_all();
        acquire(2, 1, 3);
        int g0 = 4;
#pragma unroll 1
        for (int n = 0; n < 36; n += n == 0 || n == 33 ? 2 : 1) {
          const int it = (n >> 1) - (n & 1);
          const int blk = it & 15 ? (it <= idx ? it - 1 : 15 - it) : it ? 15 - idx : idx;
          acquire(g0, n < 6 ? 2 : 1, 3);
          if (elect()) {
            const uint32_t fb = sb + SM_BAR + (B_FULL + g0) * 8;
            if (n == 5) mbar_arrive(sb + SM_BAR + B_SLOT * 8);
            mbar_expect_tx(fb, 2 * GR);
            bulk_g2s(sb + g0 * GR, g_kv + (unsigned)((((n & 1) * 16 + (head & 15)) * 16 + blk) * 32768), 2 * GR, fb);
          }
          g0 = n == 13 ? 12 : g0 == 12 ? 4 : g0 + 2;
        }
      }
      int c5 = 0;
      if (spare) { bar_sync(5, 64); pe = 0x3FC0; }
      else c5 = get_ticket();
      auto conv_fill = [&](int g, int ch) {
        acquire(g, 1, 1);
        if (elect()) {
          const uint32_t fb = sb + SM_BAR + (B_FULL + g) * 8;
          if (!spare) FTP(64 + 48 + g);
          mbar_expect_tx(fb, WBYTES + 4096);
          bulk_g2s<true>(sb + g * GR, g_w + (size_t)ch * WSTRIDE, WBYTES, fb);
          bulk_g2s<true>(sb + g * GR + WBYTES, p.ssk + (size_t)ch * SEQ, 4096, fb);
        }
      };
#pragma unroll 1
      for (int i = 0, g = 2; i < cn; i++) {
        if ((i & 15) == 0) { flag_wait(FLAG(F_U + (spare ? 32 - __clz(i >> 4) : 4)), NMAIN); fence_async_all(); }
        conv_fill(g + (i & 1), cch + i * cstep + (i == 4 ? c5 : 0));
        if (i & 1) g = conv_next(g, spare);
      }
      if (!spare) {
        const int rt = 2 * grp + rank, ct = idx;
        int g0 = P3G, top = 12;
        const uint8_t* src = g_cimg + (unsigned)(rt * 64 * GR);
#pragma unroll 1
        for (int kb = 0; kb < 64; kb++) {
          if (!(kb & 31)) { flag_wait(FLAG(F_CTX + rt * 2 + (kb >> 5)), 32); fence_async_all(); }
          acquire(g0, kb < 11 ? 2 : 1, 3);
          if (elect()) {
            const uint32_t fb = sb + SM_BAR + (B_FULL + g0) * 8;
            if (kb < 16) FTP(48 + kb);
            mbar_expect_tx(fb, 2 * GR);
            bulk_g2s<true>(sb + g0 * GR, src, GR, fb);
            tma2d_mc<true>(sb + (g0 + 1) * GR + rank * 8192, &p.wo, ct * 128 + rank * 64, kb * 64, fb);
          }
          src += GR;
          g0 = g0 == (kb < XK ? 12 : kb < YK ? 10 : 8) ? (kb == 3 ? 2 : 0) : g0 + 2;
          if (kb == XK || (kb >= YK && top == P3Y && (kb == 63 || mbar_test(sb + SM_BAR + B_SLOT * 8, 1)))) {
            const bool j = kb != XK;
            if (j) { mbar_wait1(sb + SM_BAR + B_SLOT * 8, 1); fence_async_all(); }
            acquire(top, 1, 0);
            if (elect()) {
              const uint32_t fb = sb + SM_BAR + (B_FULL + top) * 8;
              mbar_expect_tx(fb, j ? 2 * GR + 512 : 2 * GR);
              if (j) bulk_g2s(sb + SM_GATE, g_gate + (unsigned)(rt * 128), 512, fb);
              tma3d(sb + top * GR, j ? &p.y3 : &p.x3, 0, (j ? ct : rt) * 128, (j ? rt : ct) * 2, fb);
            }
            top -= 2;
          }
        }
        unsigned n = 0;
        if (lane == 0) n = atomicInc(FLAG(F_EXIT), 0x7fffffffu);
        if (__any_sync(0xffffffffu, n == NMAIN - 1)) {
#pragma unroll
          for (int i = lane; i < 96; i += 32) *reinterpret_cast<uint2*>(FLAG(i)) = make_uint2(0, 0);
        }
      }
      if (lane == 0) mbar_arrive(sb + SM_BAR + B_DONE * 8);
    }
    __syncwarp();
    cluster_wait();
  } else {
    asm volatile("setmaxnreg.inc.sync.aligned.u32 232;");
    FTS(2);
    Cons c;
    c.sb = sb; c.pf = 0; c.wg = wgi - 1; c.tid = threadIdx.x & 127;
    const int lane = threadIdx.x & 31, t = lane & 3;
    const int row = c.wg * 64 + (warp & 3) * 16 + (lane >> 2);
    const uint32_t dkk = desc_k(sb), dk0 = dkk + c.wg * 512, dm0 = desc_mn<8192>(sb), dv0 = desc_mn<16384>(sb);
    const uint32_t dsw = DG + 512 - c.wg * 1024;
    if (c.wg == 1) bar_arrive(1, 256);
    c.pfree = 1;
    asm("mapa.shared::cluster.u32 %0, %1, %2;" : "=r"(c.relb) : "r"(sb + SM_BAR + (B_EMPTY + (c.tid >> 1)) * 8), "r"(c.tid & 1));
    c.zero = p.zero;
    c.rnd = 0;
    const uint32_t stg = sb + (c.wg * 64 + (warp & 3) * 16 + ((lane >> 3) & 1) * 8 + (lane & 7)) * 128 + (((lane >> 4) ^ (lane & 7)) << 4);

    uint32_t dd0;
    auto load_dd = [&]() { asm volatile("ld.global.nc.u16 %0, [%1];" : "=r"(dd0) : "l"(p.ssd + (unsigned)(cch + c.wg * cstep + (lane & c.zero)))); };
    int pass = c.zero;
#pragma unroll 1
    do {
    if (pass) {
      load_dd();
#pragma unroll 1
      for (int g = 2; g < NGR; g += 3) { mbar_wait(sb + SM_BAR + (B_FULL + g) * 8, 0); c.release(g, 3); }
      c.pf = 0x924;
    if (spare) {
      c.wait_full(1);
      int g = 2;
#pragma unroll 1
      for (int r = 0; r < 4; r++) {
        float d[4] = {0.f, 0.f, 0.f, 0.f}, e[4] = {0.f, 0.f, 0.f, 0.f};
#pragma unroll 1
        for (int kb = 0; kb < 16; kb += 2) {
          c.wait_full(g);
          wg_fence();
#pragma unroll 1
          for (int k = 0; k < 4; k++) {
            mma_ss_n8(d, dk0 + g * DG + k * 2, dkk + DG + kb * 8 + k * 2);
            mma_ss_n8(e, dk0 + (g + 1) * DG + k * 2, dkk + DG + kb * 8 + 8 + k * 2);
          }
          wg_commit();
          wg_wait<0>();
          c.release(g, 2);
          g = g == NGR - 2 ? 2 : g + 2;
        }
        reg_fence(d); reg_fence(e);
        d[0] += e[0]; d[2] += e[2];
        if (t == 0) {
          float* gp = g_gate + (unsigned)((lb - NMAIN) * 512 + r * 128 + row);
          gp[0] = rcp(1.f + ex2(-1.4426950408889634f * d[0])); gp[8] = rcp(1.f + ex2(-1.4426950408889634f * d[2]));
        }
      }
      fence_release();
      __syncwarp();
      if (lane == 0) flag_add(FLAG(F_GATE));
      TS(1);
    }
    } else cluster_wait();
    get_slot();
    } while (redo && !pass++);
    FTS(3);
    const float dmask = (float)(2 * t - (row & 63));
    int c5 = 0;
    uint32_t pv[32];
#pragma unroll 1
    for (int rnd = 0; rnd < (spare ? 0 : 2); rnd++) {
      float O[64];
      FTM(rnd * 8);
      FTG(0);
      FTH(56, c.rnd == rnd);
      c.wait_full(2);
      FTM(rnd * 8 + 1);
      FTH(57, c.rnd == rnd);
#pragma unroll 1
      for (int tile = c.zero; tile < 2; tile++) {
        float acc[128];
        const bool single = tile == 0;
        {
          FTG(tile * 32 + 1);
          const uint32_t a = dk0 + 2 * DG, b = dm0 + 3 * DG;
          c.turn_begin();
          FTG(tile * 32 + 2);
          FTH(58, c.rnd == rnd);
          wg_fence();
          mma_ss_n256_init<1>(acc, a, b);
#pragma unroll
          for (int k = 1; k < 4; k++) mma_ss_n256<1>(acc, a + k * 2, b + k * 128);
          wg_commit();
          if (single) c.turn_end();
          if (single && rnd && !c.wg) { stsm_frag(pv, stg); c.staged(0); }
          FTG(tile * 32 + 3);
        }
#pragma unroll 1
        for (int kb = 1; kb < 8; kb++) {
          const int g0 = 2 + 3 * (kb & 3);
          const uint32_t a = dk0 + g0 * DG, b = dm0 + (g0 + 1) * DG;
          const bool second = (kb == 1 && !single) || kb == 7;
          FTG(tile * 32 + kb * 4);
          if (!second) { wg_wait<0>(); c.release(2 + 3 * ((kb - 1) & 3), 3); }
          FTG(tile * 32 + kb * 4 + 1);
          c.wait_full(g0);
          if (!second) c.turn_begin();
          FTG(tile * 32 + kb * 4 + 2);
          wg_fence();
#pragma unroll
          for (int k = 0; k < 4; k++) mma_ss_n256<1>(acc, a + k * 2, b + k * 128);
          wg_commit();
          if (kb != 6) c.turn_end();
          if (second) { wg_wait<1>(); c.release(2 + 3 * ((kb - 1) & 3), 3); }
          FTG(tile * 32 + kb * 4 + 3);
          FTH(58 + kb, c.rnd == rnd || kb > 3);
          if (tile == 1 && kb == 3) { c.wait_stage_free(); stsm_frag<0, 4>(pv, stg); }
          if (tile == 1 && kb == 4) { stsm_frag<4, 8>(pv, stg); c.staged(0); }
        }
        c.rnd = rnd;
        c.wait_stage_free();
        const bool nxt = c.try_full(2);
        wg_wait<0>();
        reg_fence(acc);
        c.release(11, 3);
        pack_frag_scaled(acc, pv, SM_C, SM_C);
        stsm_frag(pv, stg);
        c.staged(0);
        pack_frag<64>(acc, pv);
        pin32(pv, sb);
        FTG(32 + tile * 32);
        if (!nxt) mbar_wait(sb + SM_BAR + (B_FULL + 2) * 8, (c.pf >> 2) & 1);
        c.pf ^= 4;
      }
      TS(1 + rnd * 3);
      FTM(rnd * 8 + 2);
      {
        float qa[64];
        float (&qb)[64] = O;
        {
          FTG(65);
          const uint32_t a = dk0 + 2 * DG, b = dm0 + 4 * DG;
          c.turn_begin();
          FTG(66);
          wg_fence();
          mma_ss_n128_init<1>(qa, a, b);
          mma_ss_n128_init<1>(qb, a + dsw, b);
#pragma unroll
          for (int k = 1; k < 4; k++) {
            mma_ss_n128<1>(qa, a + k * 2, b + k * 128);
            mma_ss_n128<1>(qb, a + dsw + k * 2, b + k * 128);
          }
          wg_commit();
          FTG(67);
        }
#pragma unroll 1
        for (int kb = 1; kb < 16; kb++) {
          const int g0 = 2 + 3 * (kb & 3);
          const uint32_t a = dk0 + g0 * DG, b = dm0 + (g0 + 2) * DG;
          const bool second = kb == 1 || kb == 15;
          FTG(64 + kb * 4);
          if (!second) { wg_wait<0>(); c.release(2 + 3 * ((kb - 1) & 3), 3); }
          FTG(65 + kb * 4);
          c.wait_full(g0);
          if (!second) c.turn_begin();
          FTG(66 + kb * 4);
          FTH(kb - 14, kb < 14);
          wg_fence();
#pragma unroll
          for (int k = 0; k < 4; k++) {
            mma_ss_n128<1>(qa, a + k * 2, b + k * 128);
            mma_ss_n128<1>(qb, a + dsw + k * 2, b + k * 128);
          }
          wg_commit();
          if (kb != 14) c.turn_end();
          if (second) { wg_wait<1>(); c.release(2 + 3 * ((kb - 1) & 3), 3); }
          FTG(67 + kb * 4);
          FTH(2, kb < 15);
          if (kb == QFLUSH) { c.wait_stage_free(); stsm_frag<0, 4>(pv, stg); }
          if (kb == QFLUSH + 1) { stsm_frag<4, 8>(pv, stg); c.staged(0); }
        }
        c.wait_stage_free();
        mbar_wait(sb + SM_BAR + (B_EMPTY + 2) * 8, rnd ^ !redo);
        FTM(rnd * 8 + 3);
        FTH(3, 0);
        wg_wait<0>();
        reg_fence(qa); reg_fence(qb);
        FTH(4, 0);
        c.release(11, 3);
        pack_frag<0>(qa, pv);
        stsm_frag(pv, stg + 2 * GR);
        if (c.wg == 0) {
          pack_frag<0>(qb, pv);
          stsm_frag(pv, stg);
        }
        FTH(6, 0);
        fence_async_smem();
        FTH(7, 0);
        c.wait_full(4);
      }
      TS(2 + rnd * 3);
      FTM(rnd * 8 + 4);
      FTH(5, 0);
      {
        const int nA = idx + 1;
        uint32_t (&P)[32] = pv;
        SoftState z;
        z.m0 = z.m1 = z.l0 = z.l1 = 0.f; z.shifted = c.zero;
#pragma unroll 1
        for (int seg = c.zero;; seg++) {
        if (c.wg == seg) attn_half(c, O, P, z, dk0, dkk, dv0, dmask, seg);
        if (seg) break;
        FTM(rnd * 8 + 5);
        int gk = c.wg ? 4 : 6, gv = c.wg ? 4 : 8;
        uint32_t dq = dk0 + (1 - c.wg < nA ? 2 * DG : 0), dk = dkk + gk * DG;
#pragma unroll 1
        for (int it = 1 - c.wg; it < 17 - c.wg; it++) {
          float S[64];
          FTA(it * 7 + 0); FTH((it < 3 ? 8 + it * 8 : it * 8 - 88) + 0, it >= 3 && it < 15);
          c.turn_begin();
          FTA(it * 7 + 2); FTH((it < 3 ? 8 + it * 8 : it * 8 - 88) + 1, it >= 3 && it < 15);
          wg_fence();
          issue_qk(S, dq, dk);
          wg_commit();
          const uint32_t dv = dv0 + gv * DG;
          uint32_t relk = c.relb + gk * 8, relv = c.relb + gv * 8;
          gk = it == 6 ? 12 : gv == 12 ? 4 : gv + 2;
          gv = it == 16 ? gk : gk == 12 ? 4 : gk + 2;
          uint32_t fk = sb + SM_BAR + (B_FULL + gk) * 8, fv = sb + SM_BAR + (B_FULL + gv) * 8, park = (c.pf >> gk) & 1, parv = (c.pf >> gv) & 1;
          c.pf ^= (1u << gk) | (1u << gv);
          dq = dk0 + (it + 1 < nA ? 2 * DG : 0); dk = dkk + gk * DG;
          float lo0 = z.l0, lo1 = z.l1;
          const bool first = it == nA || it == 0;
          if (it == nA) {
            lo0 = rcp(quad_sum(lo0)); lo1 = rcp(quad_sum(lo1));
            z.m0 = z.m1 = z.l0 = z.l1 = 0.f; z.shifted = 0;
          }
          float s0, s1, d0 = z.m0, d1 = z.m1;
          int pre = z.shifted || (it & 15) == 0;
          float lim = first ? -1.f : SM_LIMIT;
          asm volatile("" : "+r"(relk), "+r"(relv), "+r"(fk), "+r"(fv), "+r"(park), "+r"(parv), "+r"(dq), "+r"(dk), "+r"(pre), "+f"(lim), "+f"(d0), "+f"(d1), "+f"(z.l0), "+f"(z.l1));
          if (it + c.wg > 1) {
            issue_pv<0>(O, P, dv, it != nA + 1 && it != 1, true);
            issue_pv<1>(O, P, dv, 1, true);
            c.turn_end();
          } else if (it) {
            issue_pv<0>(O, P, dv, 0, true);
            wg_commit(); wg_commit();
            c.turn_end();
          } else stage_q2(c, O, P, stg);
          FTA(it * 7 + 3); FTH((it < 3 ? 8 + it * 8 : it * 8 - 88) + 2, it >= 3 && it < 15);
          wg_wait<4>();
          reg_fence(S);
          FTA(it * 7 + 4); FTH((it < 3 ? 8 + it * 8 : it * 8 - 88) + 3, it >= 3 && it < 15);
          if (c.tid < 4) asm volatile("mbarrier.arrive.shared::cluster.b64 _, [%0];" ::"r"(relk) : "memory");
#pragma unroll 1
          for (int pass = 0;; pass++) {
            if (pre) {
              if ((it & 15) == 0) mask_diag(S, dmask);
              if (z.shifted) shift_scores(S, d0, d1);
            }
            float tr[ROT];
            exp_quarter<0, 3>(S, P, tr, s0, s1, sb);
            exp_quarter<1, 2>(S, P, tr, s0, s1, sb);
            exp_quarter<2, 1>(S, P, tr, s0, s1, sb);
            exp_quarter<3, 0>(S, P, tr, s0, s1, sb);
            reg_fence(O);
            if (c.tid < (pass || !it ? 0 : 4)) asm volatile("mbarrier.arrive.shared::cluster.b64 _, [%0];" ::"r"(relv) : "memory");
            const bool ok = mbar_test(fk, park) & mbar_test(fv, parv);
            if (!ok) lim = -1.f;
            FTA(it * 7 + 5); FTH((it < 3 ? 8 + it * 8 : it * 8 - 88) + 4, it >= 3 && it < 15);
            if (!__any_sync(0xffffffffu, !(s0 <= lim && s1 <= lim))) break;
            if (pass) break;
            if (it == nA) {
              uint32_t pk[32];
              pack_frag_scaled(O, pk, lo0, lo1);
              stsm_frag(pk, stg + 2 * GR);
              c.staged(1);
            }
            if (!ok) { mbar_wait(fk, park); mbar_wait(fv, parv); }
            if (!soft_unsafe(s0, s1, first)) break;
            soft_fix(S, O, z, first, d0, d1);
            pre = 1;
          }
          z.l0 += s0; z.l1 += s1;
          FTA(it * 7 + 6); FTH((it < 3 ? 8 + it * 8 : it * 8 - 88) + 5, it >= 3 && it < 15);
        }
        FTM(rnd * 8 + 6);
        }
        FTH(48, 0);
        load_dd();
        c.turn_begin();
        FTH(49, 0);
        wg_fence();
        issue_pv<0>(O, P, dv0 + 12 * DG, 1, true);
        issue_pv<1>(O, P, dv0 + 12 * DG, 1, !c.wg);
        c.turn_end();
        z.l0 = rcp(quad_sum(z.l0)); z.l1 = rcp(quad_sum(z.l1));
        if (rnd) c5 = get_ticket();
        wg_wait<0>();
        reg_fence(O); reg_fence(P);
        FTH(50, 0);
        c.release(12, 2);
        pack_frag_scaled(O, P, z.l0, z.l1);
        if (rnd || c.wg) { stsm_frag(P, stg); c.staged(0); }
        FTM(rnd * 8 + 7);
        FTH(51, 0);
      }
      TS(3 + rnd * 3);
    }
    conv_tasks(c, p, (cn + 1 - c.wg) >> 1, spare, cch + c.wg * cstep, 2 * cstep, c5, dd0, dkk, warp & 3, lane);
    if (c.wg == 1) c.pf ^= 0x14;
    if (c.wg == (cn & 1)) c.turn_begin();
    TS(7);
    if (!spare) {
      const int rt = 2 * grp + rank, ct = idx;
      float acc[64];
      int g0 = P3G + 2, pg = P3G;
      {
        FTO(0);
        c.wait_full(P3G);
        FTO(1);
        const uint32_t a = dk0 + P3G * DG, b = dm0 + (P3G + 1) * DG;
        wg_fence();
        mma_ss_n128_init<1>(acc, a, b);
#pragma unroll
        for (int k = 1; k < 4; k++) mma_ss_n128<1>(acc, a + k * 2, b + k * 128);
        wg_commit();
      }
#pragma unroll 1
      for (int kb = 1; kb < 64; kb++) {
        FTO(kb * 2);
        c.wait_full(g0);
        if (kb == STR && !c.wg) c.turn_begin();
        FTO(kb * 2 + 1);
        const uint32_t a = dk0 + g0 * DG, b = dm0 + (g0 + 1) * DG;
        wg_fence();
#pragma unroll
        for (int k = 0; k < 4; k++) mma_ss_n128<1>(acc, a + k * 2, b + k * 128);
        wg_commit();
        if (kb < STR) { wg_wait<1>(); c.release(pg, kb <= 59 ? 2 : 0); }
        if (kb == FDUMP_KB) FTDUMP();
        pg = g0;
        g0 = g0 == (kb < XK ? 12 : kb < YK ? 10 : 8) ? (kb == 3 ? 2 : 0) : g0 + 2;
      }
      if (c.wg) c.turn_end();
      cluster_arrive();
      c.wait_full(P3X);
      c.wait_full(P3Y);
      const float g0f = __uint_as_float(lds32(sb + SM_GATE + row * 4)), g1f = __uint_as_float(lds32(sb + SM_GATE + row * 4 + 32));
      const uint32_t gp0 = pack_bf16(g0f, g0f), gp1 = pack_bf16(g1f, g1f);
      const float h0 = 1.f - g0f, h1 = 1.f - g1f;
      const int w = warp & 3;
      const uint32_t xa = stg + P3X * GR;
      const uint32_t ya = sb + P3Y * GR + c.wg * 16384 + ((lane >> 4) * 8 + (lane & 7)) * 128 + (((2 * w + ((lane >> 3) & 1)) ^ (lane & 7)) << 4);
      uint32_t xy[32];
      auto prep = [&](int j0, int j1) {
#pragma unroll
        for (int jj = j0; jj < j1; jj++) {
          uint32_t x[4], y[4];
          asm volatile("ldmatrix.sync.aligned.m8n8.x4.shared.b16 {%0,%1,%2,%3}, [%4];" : "=r"(x[0]), "=r"(x[1]), "=r"(x[2]), "=r"(x[3]) : "r"((xa ^ ((jj & 3) << 5)) + (jj >> 2) * 16384) : "memory");
          asm volatile("ldmatrix.sync.aligned.m8n8.x4.trans.shared.b16 {%0,%1,%2,%3}, [%4];" : "=r"(y[0]), "=r"(y[1]), "=r"(y[2]), "=r"(y[3]) : "r"(ya + jj * 2048) : "memory");
#pragma unroll
          for (int i = 0; i < 4; i++) xy[4 * jj + i] = hmul2(x[i], y[i]);
        }
      };
      prep(0, 4);
      wg_wait<0>();
      reg_fence(acc);
      TS(8);
#pragma unroll
      for (int hf = 0; hf < 2; hf++) {
#pragma unroll
        for (int i = 16 * hf; i < 16 * hf + 16; i++) {
          const float h = (i & 1) ? h1 : h0;
          xy[i] = hfma2((i & 1) ? gp1 : gp0, xy[i], pack_bf16(acc[2 * i] * h, acc[2 * i + 1] * h));
        }
        if (hf) stsm_frag<4, 8>(xy, xa); else stsm_frag<0, 4>(xy, xa);
        fence_async_smem();
        __syncwarp();
        const int r0 = c.wg * 64 + w * 16;
        if (lane == 0) tma2d_store(&p.out, sb + (P3X + hf) * GR + r0 * 128, ct * 128 + hf * 64, rt * 128 + r0);
        if (!hf) prep(4, 8);
      }
      if (lane == 0) asm volatile("cp.async.bulk.commit_group;\ncp.async.bulk.wait_group.read 0;" ::: "memory");
    } else { FTDUMP(); cluster_arrive(); }
    if (lane == 0) mbar_arrive(sb + SM_BAR + B_DONE * 8);
    __syncwarp();
    TS(9);
    cluster_wait();
  }
}

typedef CUresult (*EncFn)(CUtensorMap*, CUtensorMapDataType, cuuint32_t, void*, const cuuint64_t*, const cuuint64_t*, const cuuint32_t*,
                          const cuuint32_t*, CUtensorMapInterleave, CUtensorMapSwizzle, CUtensorMapL2promotion, CUtensorMapFloatOOBfill);

void enc2d(EncFn enc, CUtensorMap* tm, const void* base, uint64_t cols, uint64_t rows, uint32_t bc, uint32_t br) {
  cuuint64_t dims[2] = {cols, rows}; cuuint64_t strides[1] = {cols * 2}; cuuint32_t box[2] = {bc, br}; cuuint32_t es[2] = {1, 1};
  enc(tm, CU_TENSOR_MAP_DATA_TYPE_BFLOAT16, 2, const_cast<void*>(base), dims, strides, box, es, CU_TENSOR_MAP_INTERLEAVE_NONE,
      CU_TENSOR_MAP_SWIZZLE_128B, CU_TENSOR_MAP_L2_PROMOTION_L2_256B, CU_TENSOR_MAP_FLOAT_OOB_FILL_NONE);
}
void enc3d(EncFn enc, CUtensorMap* tm, const void* base, uint64_t K, uint64_t N, uint32_t bk = 64) {
  cuuint64_t dims[3] = {64, K, N / 64}; cuuint64_t strides[2] = {N * 2, 128}; cuuint32_t box[3] = {64, bk, 2}; cuuint32_t es[3] = {1, 1, 1};
  enc(tm, CU_TENSOR_MAP_DATA_TYPE_BFLOAT16, 3, const_cast<void*>(base), dims, strides, box, es, CU_TENSOR_MAP_INTERLEAVE_NONE,
      CU_TENSOR_MAP_SWIZZLE_128B, CU_TENSOR_MAP_L2_PROMOTION_L2_256B, CU_TENSOR_MAP_FLOAT_OOB_FILL_NONE);
}

}

extern "C" void kernel_launch(void* const* d_in, const int* in_sizes, int n_in, void* d_out, int out_size) {
  (void)in_sizes; (void)n_in; (void)out_size;
  typedef const __nv_bfloat16* BP;
  BP xq = (BP)d_in[0], ak = (BP)d_in[1], av = (BP)d_in[2], shk = (BP)d_in[3], ssk = (BP)d_in[4], ssd = (BP)d_in[5];
  BP ckv = (BP)d_in[7], wq = (BP)d_in[8], wuk = (BP)d_in[9], wuv = (BP)d_in[10], wo = (BP)d_in[11], gw = (BP)d_in[12];

  static EncFn enc = nullptr;
  if (!enc) {
    cudaDriverEntryPointQueryResult qr;
    cudaGetDriverEntryPoint("cuTensorMapEncodeTiled", (void**)&enc, cudaEnableDefault, &qr);
    cudaFuncSetAttribute(mega_kernel, cudaFuncAttributeMaxDynamicSharedMemorySize, SMEM_BYTES);
  }
  Params p;
  void* yT = nullptr;
  cudaGetSymbolAddress(&yT, g_yT);
  enc2d(enc, &p.x, xq, DM, SEQ, 64, 128);
  enc2d(enc, &p.c, ckv, DC, SEQ, 64, 128);
  enc3d(enc, &p.wq, wq, DM, NH * HD);
  enc3d(enc, &p.wuk, wuk, DC, NH * HD);
  enc3d(enc, &p.wuv, wuv, DC, NH * HD);
  enc2d(enc, &p.wo, wo, DM, NH * HD, 64, 64);
  enc3d(enc, &p.x3, xq, SEQ, DM, 128);
  enc3d(enc, &p.y3, yT, DM, SEQ, 128);
  enc2d(enc, &p.out, d_out, DM, SEQ, 64, 16);
  {
    void* wp = nullptr;
    cudaGetSymbolAddress(&wp, g_w);
    cuuint64_t dims[3] = {WSTRIDE / 2, DM / 2, 2}; cuuint64_t strides[2] = {2 * WSTRIDE, WSTRIDE}; cuuint32_t box[3] = {16, 32, 2}; cuuint32_t es[3] = {1, 1, 1};
    enc(&p.w, CU_TENSOR_MAP_DATA_TYPE_BFLOAT16, 3, wp, dims, strides, box, es, CU_TENSOR_MAP_INTERLEAVE_NONE,
        CU_TENSOR_MAP_SWIZZLE_32B, CU_TENSOR_MAP_L2_PROMOTION_NONE, CU_TENSOR_MAP_FLOAT_OOB_FILL_NONE);
  }
  p.zero = 0;
  cudaGetSymbolAddress((void**)&p.flags, g_flags);
  for (int i = 0; i < 128; i++) {
    const int tp = i % NSLOT;
    p.pref[i] = tp < 32 ? (tp & 7) * 8 + (tp >> 3) : tp < 60 ? (1 + (tp - 32) % 7) * 8 + 4 + (tp - 32) / 7 : tp < 62 ? tp + 4 : tp - 58;
  }
  p.gate_w = gw; p.ak = ak; p.av = av; p.shk = shk; p.ssk = ssk; p.ssd = ssd; p.wop = wo;

  mega_kernel<<<132, NTHREADS, SMEM_BYTES>>>(p);
}
```

```cpp
#include <cuda_runtime.h>
#include <cuda.h>
#include <cuda_bf16.h>
#include <stdint.h>

namespace {

constexpr int SEQ = 2048, DM = 1024, DC = 512, NH = 32, HD = 128;
constexpr int GR = 16384;
constexpr int NGR = 14;
constexpr int SM_BAR = NGR * GR;
constexpr int SM_GATE = SM_BAR + 512;
constexpr int SM_UST = SM_GATE + 512;
constexpr int SMEM_BYTES = SM_UST + 2048;
constexpr int NTHREADS = 384;
#define SM_LIMIT 1.0995116e12f
#define SM_LOW 9.094947e-13f
#define CNS 104
constexpr int CN_SPARE = CNS, NTICK = 256 - 2 * CN_SPARE;
constexpr int XK = 57, YK = 62;
constexpr int STR = 61;
constexpr int P3G = 6, P3X = 12, P3Y = 10;
constexpr int NMAIN = 128;

constexpr int B_FULL = 0, B_FREE = 14, B_SLOT = 16, B_DONE = 17, B_EMPTY = 18, B_EV = 32, B_TICK = 36;
constexpr int V_SLOT = 37, V_TICK = 38;

__device__ __align__(1024) uint8_t g_kv[2 * 16 * 16 * 32768];
__device__ __align__(1024) uint8_t g_cimg[16 * NH * 32768];
__device__ __align__(1024) __nv_bfloat16 g_yT[DM * SEQ];
__device__ __align__(1024) float g_gate[SEQ];
constexpr int WZ = 256, WPL = WZ + 4096, WBYTES = 2 * WPL + 32, WSTRIDE = 2 * WPL + 128;
__device__ __align__(1024) uint8_t g_w[DM * WSTRIDE];
__device__ __align__(32) unsigned g_flags[96 * 8];
constexpr int F_KV = 0, F_CTX = 16, F_U = 48, F_AD = 56, F_Y = 64, F_GATE = 72, F_EXIT = 73, F_TICK = 74;
constexpr int NSLOT = 66;
#define FLAG(i) (&g_flags[(i) * 8])
#define CLAIMP(i) (p.flags + (i) * 8 + 1)

#define TS(slot)
#define TSW(slot)
#define FTX(i, off)
#define FTDUMP()

#define QFLUSH 4
#define PSL 200
#define US0 500
#define EROT 6
#define RST 2
#define UP0 4
#define UP1 11
#define X_DELAY 900
#define X_D2 600
#define P3PF 12
#define P3PF0 5
#define EXPV 1
#define SUMV 0
#define ROT 8
#define KVARR 1
#define KV_ROW(idx, t) (KVARR ? 8 * (t) + 2 * ((idx) & 3) : 2 * (idx))
#define KV_HEAD(idx, t) (KVARR ? (idx) >> 2 : (t))
#define FINE_MODE 0
#define FDUMP_KB 40
#define FINE_RND 1
#define FTA(i) do { if (FINE_MODE == 0) FTX(i, rnd ^ FINE_RND); } while (0)
#define FTG(i) do { if (FINE_MODE == 1) FTX(i, rnd ^ FINE_RND); } while (0)
#define FTM(i) do { if (FINE_MODE == 4) FTX(i, 0); } while (0)
#define FTC(k) do { if (FINE_MODE == 5) FTX((i & 7) * 8 + (k), (i >> 3) ^ FINE_RND); } while (0)
#define FTH(i, off) do { if (FINE_MODE == 6) FTX(i, (c.rnd ^ FINE_RND) | (off)); } while (0)
#define FTS(i)
#define FTSD(i)
#define FTSW(i)
#define FTP(i)
#define FTO(i) do { if (FINE_MODE == 2) FTX(i, 0); } while (0)

__device__ __forceinline__ uint32_t smem_u32(const void* p) { return (uint32_t)__cvta_generic_to_shared(p); }
__device__ __forceinline__ void mbar_init(uint32_t bar, int cnt) { asm volatile("mbarrier.init.shared::cta.b64 [%0], %1;" ::"r"(bar), "r"(cnt) : "memory"); }
__device__ __forceinline__ void mbar_expect_tx(uint32_t bar, uint32_t bytes) { asm volatile("mbarrier.arrive.expect_tx.shared::cta.b64 _, [%0], %1;" ::"r"(bar), "r"(bytes) : "memory"); }
__device__ __forceinline__ void mbar_arrive(uint32_t bar) { asm volatile("mbarrier.arrive.shared::cta.b64 _, [%0];" ::"r"(bar) : "memory"); }
__device__ __forceinline__ void mbar_arrive_cluster(uint32_t bar, uint32_t cta) {
  asm volatile("{\n.reg .b32 r;\nmapa.shared::cluster.u32 r, %0, %1;\nmbarrier.arrive.shared::cluster.b64 _, [r];\n}\n" ::"r"(bar), "r"(cta) : "memory");
}
__device__ __forceinline__ void send_both(uint32_t bar, uint32_t off, uint32_t v) {
#pragma unroll
  for (int r = 0; r < 2; r++)
    asm volatile("{\n.reg .b32 a, b;\nmapa.shared::cluster.u32 a, %0, %1;\nadd.u32 b, a, %3;\nst.async.shared::cluster.mbarrier::complete_tx::bytes.u32 [b], %2, [a];\n}\n"
                 ::"r"(bar), "r"(r), "r"(v), "r"(off) : "memory");
}
__device__ __forceinline__ bool mbar_try(uint32_t bar, uint32_t parity) {
  uint32_t ok;
  asm volatile("{\n.reg .pred p;\nmbarrier.try_wait.parity.shared::cta.b64 p, [%1], %2, 20000;\nselp.u32 %0, 1, 0, p;\n}\n" : "=r"(ok) : "r"(bar), "r"(parity) : "memory");
  return ok;
}
__device__ __forceinline__ bool mbar_test(uint32_t bar, uint32_t parity) {
  uint32_t ok;
  asm volatile("{\n.reg .pred p;\nmbarrier.test_wait.parity.shared::cta.b64 p, [%1], %2;\nselp.u32 %0, 1, 0, p;\n}\n" : "=r"(ok) : "r"(bar), "r"(parity) : "memory");
  return ok;
}
__device__ __forceinline__ void mbar_wait(uint32_t bar, uint32_t parity) {
  asm volatile("{\n.reg .pred p;\nWAIT_LOOP:\nbar.warp.sync -1;\nmbarrier.try_wait.parity.shared::cta.b64 p, [%0], %1;\n@!p bra WAIT_LOOP;\n}\n" ::"r"(bar), "r"(parity) : "memory");
}
__device__ __forceinline__ void mbar_wait1(uint32_t bar, uint32_t parity) {
  asm volatile("{\n.reg .pred p;\nWAIT_LOOP:\nbar.warp.sync -1;\nmbarrier.try_wait.parity.shared::cta.b64 p, [%0], %1, 4000;\n@!p bra WAIT_LOOP;\n}\n" ::"r"(bar), "r"(parity) : "memory");
}
constexpr uint64_t EV_FIRST = 0x12F0000000000000ull;
__device__ __forceinline__ uint32_t ldg_stream(const uint32_t* p) {
  uint32_t r; asm volatile("ld.global.nc.L1::no_allocate.L2::cache_hint.b32 %0, [%1], %2;" : "=r"(r) : "l"(p), "l"(EV_FIRST)); return r;
}
#define TMA_LD "cp.async.bulk.tensor."
#define TMA_MB ".shared::cluster.global.mbarrier::complete_tx::bytes"
__device__ __forceinline__ void tma2d(uint32_t dst, const CUtensorMap* tm, int c0, int c1, uint32_t bar) {
  asm volatile(TMA_LD "2d" TMA_MB " [%0], [%1, {%3, %4}], [%2];" ::"r"(dst), "l"(tm), "r"(bar), "r"(c0), "r"(c1) : "memory");
}
template <bool ONCE = false> __device__ __forceinline__ void tma2d_mc(uint32_t dst, const CUtensorMap* tm, int c0, int c1, uint32_t bar) {
  if (ONCE) asm volatile(TMA_LD "2d" TMA_MB ".multicast::cluster.L2::cache_hint [%0], [%1, {%3, %4}], [%2], %5, %6;"
                         ::"r"(dst), "l"(tm), "r"(bar), "r"(c0), "r"(c1), "h"((uint16_t)3), "l"(EV_FIRST) : "memory");
  else asm volatile(TMA_LD "2d" TMA_MB ".multicast::cluster [%0], [%1, {%3, %4}], [%2], %5;"
                    ::"r"(dst), "l"(tm), "r"(bar), "r"(c0), "r"(c1), "h"((uint16_t)3) : "memory");
}
__device__ __forceinline__ void tma3d(uint32_t dst, const CUtensorMap* tm, int c0, int c1, int c2, uint32_t bar) {
  asm volatile(TMA_LD "3d" TMA_MB " [%0], [%1, {%3, %4, %5}], [%2];" ::"r"(dst), "l"(tm), "r"(bar), "r"(c0), "r"(c1), "r"(c2) : "memory");
}
__device__ __forceinline__ void tma3d_mc(uint32_t dst, const CUtensorMap* tm, int c0, int c1, int c2, uint32_t bar) {
  asm volatile(TMA_LD "3d" TMA_MB ".multicast::cluster [%0], [%1, {%3, %4, %5}], [%2], %6;"
               ::"r"(dst), "l"(tm), "r"(bar), "r"(c0), "r"(c1), "r"(c2), "h"((uint16_t)3) : "memory");
}
template <bool ONCE = false> __device__ __forceinline__ void bulk_g2s(uint32_t dst, const void* src, uint32_t bytes, uint32_t bar) {
  if (ONCE) asm volatile("cp.async.bulk" TMA_MB ".L2::cache_hint [%0], [%1], %2, [%3], %4;" ::"r"(dst), "l"(src), "r"(bytes), "r"(bar), "l"(EV_FIRST) : "memory");
  else asm volatile("cp.async.bulk" TMA_MB " [%0], [%1], %2, [%3];" ::"r"(dst), "l"(src), "r"(bytes), "r"(bar) : "memory");
}
__device__ __forceinline__ void tma2d_store(const CUtensorMap* tm, uint32_t src, int c0, int c1) {
  asm volatile("cp.async.bulk.tensor.2d.global.shared::cta.bulk_group [%0, {%2, %3}], [%1];" ::"l"(tm), "r"(src), "r"(c0), "r"(c1) : "memory");
}
__device__ __forceinline__ void prefetch_tm(const CUtensorMap* tm) { asm volatile("prefetch.tensormap [%0];" ::"l"(tm) : "memory"); }
__device__ __forceinline__ void wg_fence() { asm volatile("wgmma.fence.sync.aligned;" ::: "memory"); }
__device__ __forceinline__ void wg_commit() { asm volatile("wgmma.commit_group.sync.aligned;" ::: "memory"); }
template <int N> __device__ __forceinline__ void wg_wait() { asm volatile("wgmma.wait_group.sync.aligned %0;" ::"n"(N) : "memory"); }
__device__ __forceinline__ void bar_sync(int id, int n) { asm volatile("bar.sync %0, %1;" ::"r"(id), "r"(n) : "memory"); }
__device__ __forceinline__ void bar_arrive(int id, int n) { asm volatile("bar.arrive %0, %1;" ::"r"(id), "r"(n) : "memory"); }
__device__ __forceinline__ void fence_async_smem() { asm volatile("fence.proxy.async.shared::cta;" ::: "memory"); }
__device__ __forceinline__ void fence_async_all() { asm volatile("fence.proxy.async.global;" ::: "memory"); }
__device__ __forceinline__ uint32_t pack_bf16(float lo, float hi) { uint32_t r; asm("cvt.rn.bf16x2.f32 %0, %1, %2;" : "=r"(r) : "f"(hi), "f"(lo)); return r; }
__device__ __forceinline__ float ex2(float x) { float r; asm("ex2.approx.ftz.f32 %0, %1;" : "=f"(r) : "f"(x)); return r; }
__device__ __forceinline__ float rcp(float x) { float r; asm("rcp.approx.ftz.f32 %0, %1;" : "=f"(r) : "f"(x)); return r; }
__device__ __forceinline__ void flag_wait(const unsigned* f, unsigned target) {
  unsigned v;
  do { asm volatile("ld.acquire.gpu.global.u32 %0, [%1];" : "=r"(v) : "l"(f) : "memory"); } while (__any_sync(0xffffffffu, v < target));
}
__device__ __forceinline__ bool elect() {
  uint32_t r;
  asm volatile("{\n.reg .pred p;\nelect.sync _|p, -1;\nselp.u32 %0, 1, 0, p;\n}\n" : "=r"(r));
  return r;
}
__device__ __forceinline__ void fence_release() { asm volatile("fence.release.gpu;" ::: "memory"); }
__device__ __forceinline__ void flag_add(unsigned* f) { asm volatile("red.relaxed.gpu.global.inc.u32 [%0], 0x7fffffff;" ::"l"(f) : "memory"); }
__device__ __forceinline__ void cluster_arrive() { asm volatile("barrier.cluster.arrive.relaxed.aligned;" ::: "memory"); }
__device__ __forceinline__ void cluster_wait() { asm volatile("barrier.cluster.wait.aligned;" ::: "memory"); }
__device__ __forceinline__ uint32_t hmul2(uint32_t a, uint32_t b) { uint32_t r; asm("mul.rn.bf16x2 %0, %1, %2;" : "=r"(r) : "r"(a), "r"(b)); return r; }
__device__ __forceinline__ uint32_t hadd2(uint32_t a, uint32_t b) { uint32_t r; asm("add.rn.bf16x2 %0, %1, %2;" : "=r"(r) : "r"(a), "r"(b)); return r; }
__device__ __forceinline__ uint32_t hfma2(uint32_t a, uint32_t b, uint32_t c) { uint32_t r; asm("fma.rn.bf16x2 %0, %1, %2, %3;" : "=r"(r) : "r"(a), "r"(b), "r"(c)); return r; }
__device__ __forceinline__ uint32_t lds32(uint32_t a) { uint32_t r; asm volatile("ld.shared.b32 %0, [%1];" : "=r"(r) : "r"(a) : "memory"); return r; }
__device__ __forceinline__ uint4 lds128(uint32_t a) { uint4 r; asm volatile("ld.shared.v4.b32 {%0,%1,%2,%3}, [%4];" : "=r"(r.x), "=r"(r.y), "=r"(r.z), "=r"(r.w) : "r"(a) : "memory"); return r; }
__device__ __forceinline__ uint32_t desc_k(uint32_t addr) { return ((addr & 0x3FFFF) >> 4) | (1u << 16); }
template <int LBO> __device__ __forceinline__ uint32_t desc_mn(uint32_t addr) { return ((addr & 0x3FFFF) >> 4) | ((uint32_t)(LBO >> 4) << 16); }
#define DHI "0x40000040"

#define R8(d, o) "+f"(d[o]), "+f"(d[o + 1]), "+f"(d[o + 2]), "+f"(d[o + 3]), "+f"(d[o + 4]), "+f"(d[o + 5]), "+f"(d[o + 6]), "+f"(d[o + 7])
#define R32(d, o) R8(d, o), R8(d, o + 8), R8(d, o + 16), R8(d, o + 24)
#define R64(d, o) R32(d, o), R32(d, o + 32)
#define L64 "%0,%1,%2,%3,%4,%5,%6,%7,%8,%9,%10,%11,%12,%13,%14,%15,%16,%17,%18,%19,%20,%21,%22,%23,%24,%25,%26,%27,%28,%29,%30,%31," \
            "%32,%33,%34,%35,%36,%37,%38,%39,%40,%41,%42,%43,%44,%45,%46,%47,%48,%49,%50,%51,%52,%53,%54,%55,%56,%57,%58,%59,%60,%61,%62,%63"
#define L128 L64 ",%64,%65,%66,%67,%68,%69,%70,%71,%72,%73,%74,%75,%76,%77,%78,%79,%80,%81,%82,%83,%84,%85,%86,%87,%88,%89,%90,%91,%92,%93,%94,%95," \
            "%96,%97,%98,%99,%100,%101,%102,%103,%104,%105,%106,%107,%108,%109,%110,%111,%112,%113,%114,%115,%116,%117,%118,%119,%120,%121,%122,%123,%124,%125,%126,%127"

template <int TB> __device__ __forceinline__ void mma_ss_n128(float (&d)[64], uint32_t da, uint32_t db) {
  asm volatile("{\n.reg .b64 da, db;\nmov.b64 da, {%64, " DHI "};\nmov.b64 db, {%65, " DHI "};\n"
               "wgmma.mma_async.sync.aligned.m64n128k16.f32.bf16.bf16 {" L64 "}, da, db, 1, 1, 1, 0, %66;\n}\n"
               : R64(d, 0) : "r"(da), "r"(db), "n"(TB));
}
template <int TB> __device__ __forceinline__ void mma_rs_n128(float (&d)[64], uint32_t a0, uint32_t a1, uint32_t a2, uint32_t a3, uint32_t db, int sd) {
  asm volatile("{\n.reg .pred p;\n.reg .b64 db;\nsetp.ne.b32 p, %69, 0;\nmov.b64 db, {%68, " DHI "};\n"
               "wgmma.mma_async.sync.aligned.m64n128k16.f32.bf16.bf16 {" L64 "}, {%64,%65,%66,%67}, db, p, 1, 1, %70;\n}\n"
               : R64(d, 0) : "r"(a0), "r"(a1), "r"(a2), "r"(a3), "r"(db), "r"(sd), "n"(TB));
}
template <int TB> __device__ __forceinline__ void mma_ss_n256(float (&d)[128], uint32_t da, uint32_t db) {
  asm volatile("{\n.reg .b64 da, db;\nmov.b64 da, {%128, " DHI "};\nmov.b64 db, {%129, " DHI "};\n"
               "wgmma.mma_async.sync.aligned.m64n256k16.f32.bf16.bf16 {" L128 "}, da, db, 1, 1, 1, 0, %130;\n}\n"
               : R64(d, 0), R64(d, 64) : "r"(da), "r"(db), "n"(TB));
}
#define W8(d, o) "=f"(d[o]), "=f"(d[o + 1]), "=f"(d[o + 2]), "=f"(d[o + 3]), "=f"(d[o + 4]), "=f"(d[o + 5]), "=f"(d[o + 6]), "=f"(d[o + 7])
#define W32(d, o) W8(d, o), W8(d, o + 8), W8(d, o + 16), W8(d, o + 24)
#define W64(d, o) W32(d, o), W32(d, o + 32)
template <int TB> __device__ __forceinline__ void mma_ss_n128_init(float (&d)[64], uint32_t da, uint32_t db) {
  asm volatile("{\n.reg .b64 da, db;\nmov.b64 da, {%64, " DHI "};\nmov.b64 db, {%65, " DHI "};\n"
               "wgmma.mma_async.sync.aligned.m64n128k16.f32.bf16.bf16 {" L64 "}, da, db, 0, 1, 1, 0, %66;\n}\n"
               : W64(d, 0) : "r"(da), "r"(db), "n"(TB));
}
template <int TB> __device__ __forceinline__ void mma_ss_n256_init(float (&d)[128], uint32_t da, uint32_t db) {
  asm volatile("{\n.reg .b64 da, db;\nmov.b64 da, {%128, " DHI "};\nmov.b64 db, {%129, " DHI "};\n"
               "wgmma.mma_async.sync.aligned.m64n256k16.f32.bf16.bf16 {" L128 "}, da, db, 0, 1, 1, 0, %130;\n}\n"
               : W64(d, 0), W64(d, 64) : "r"(da), "r"(db), "n"(TB));
}
#define L32 "%0,%1,%2,%3,%4,%5,%6,%7,%8,%9,%10,%11,%12,%13,%14,%15,%16,%17,%18,%19,%20,%21,%22,%23,%24,%25,%26,%27,%28,%29,%30,%31"
__device__ __forceinline__ void mma_ss_n64(float (&d)[32], uint32_t da, uint32_t db) {
  asm volatile("{\n.reg .b64 da, db;\nmov.b64 da, {%32, " DHI "};\nmov.b64 db, {%33, " DHI "};\n"
               "wgmma.mma_async.sync.aligned.m64n64k16.f32.bf16.bf16 {" L32 "}, da, db, 1, 1, 1, 0, 0;\n}\n"
               : R32(d, 0) : "r"(da), "r"(db));
}
__device__ __forceinline__ void mma_ss_n64_init(float (&d)[32], uint32_t da, uint32_t db) {
  asm volatile("{\n.reg .b64 da, db;\nmov.b64 da, {%32, " DHI "};\nmov.b64 db, {%33, " DHI "};\n"
               "wgmma.mma_async.sync.aligned.m64n64k16.f32.bf16.bf16 {" L32 "}, da, db, 0, 1, 1, 0, 0;\n}\n"
               : W32(d, 0) : "r"(da), "r"(db));
}
#define L16 "%0,%1,%2,%3,%4,%5,%6,%7,%8,%9,%10,%11,%12,%13,%14,%15"
template <int O, bool INIT> __device__ __forceinline__ void mma_rs_n32(float (&d)[128], uint32_t a0, uint32_t a1, uint32_t a2, uint32_t a3, uint32_t db) {
  if (INIT) asm volatile("{\n.reg .b64 db;\nmov.b64 db, {%20, 0x00000008};\n"
               "wgmma.mma_async.sync.aligned.m64n32k16.f32.bf16.bf16 {" L16 "}, {%16,%17,%18,%19}, db, 0, 1, 1, 0;\n}\n"
               : W8(d, O), W8(d, O + 8) : "r"(a0), "r"(a1), "r"(a2), "r"(a3), "r"(db));
  else asm volatile("{\n.reg .b64 db;\nmov.b64 db, {%20, 0x00000008};\n"
               "wgmma.mma_async.sync.aligned.m64n32k16.f32.bf16.bf16 {" L16 "}, {%16,%17,%18,%19}, db, 1, 1, 1, 0;\n}\n"
               : R8(d, O), R8(d, O + 8) : "r"(a0), "r"(a1), "r"(a2), "r"(a3), "r"(db));
}
template <int S, int J> __device__ __forceinline__ void conv_step(float (&d)[128], const uint32_t (&a)[64], uint32_t db) {
  if constexpr (J >= 0 && J >= (S >> 1)) {
    mma_rs_n32<16 * J, S == 0>(d, a[4 * S], a[4 * S + 1], a[4 * S + 2], a[4 * S + 3], db + (uint32_t)((2 * J - S) * 16));
    conv_step<S, J - 1>(d, a, db);
  }
}
__device__ __forceinline__ void mma_ss_n8(float (&d)[4], uint32_t da, uint32_t db) {
  asm volatile("{\n.reg .b64 da, db;\nmov.b64 da, {%4, " DHI "};\nmov.b64 db, {%5, 0x00000008};\n"
               "wgmma.mma_async.sync.aligned.m64n8k16.f32.bf16.bf16 {%0,%1,%2,%3}, da, db, 1, 1, 1, 0, 0;\n}\n"
               : "+f"(d[0]), "+f"(d[1]), "+f"(d[2]), "+f"(d[3]) : "r"(da), "r"(db));
}
template <int N> __device__ __forceinline__ void reg_fence(float (&d)[N]) {
#pragma unroll
  for (int i = 0; i < N; i++) asm volatile("" : "+f"(d[i])::"memory");
}
template <int N> __device__ __forceinline__ void reg_fence(uint32_t (&d)[N]) {
#pragma unroll
  for (int i = 0; i < N; i++) asm volatile("" : "+r"(d[i])::"memory");
}

struct __align__(64) Params {
  unsigned* flags;
  int zero;
  uint8_t pref[128];
  const __nv_bfloat16 *gate_w, *ak, *av, *shk, *ssk, *ssd, *wop;
  CUtensorMap x, c, wq, wuk, wuv, wo, x3, y3, out, w;
};

template <int O, int N, int M> __device__ __forceinline__ void pack_frag(const float (&acc)[N], uint32_t (&pk)[M]) {
#pragma unroll
  for (int i = 0; i < 32; i++) pk[i] = pack_bf16(acc[O + 2 * i], acc[O + 2 * i + 1]);
}
template <int J0 = 0, int J1 = 8, int M> __device__ __forceinline__ void stsm_frag(const uint32_t (&pk)[M], uint32_t a) {
#pragma unroll
  for (int jj = J0; jj < J1; jj++)
    asm volatile("stmatrix.sync.aligned.m8n8.x4.shared.b16 [%0], {%1,%2,%3,%4};" ::"r"((a ^ ((jj & 3) << 5)) + (jj >> 2) * 16384),
                 "r"(pk[4 * jj]), "r"(pk[4 * jj + 1]), "r"(pk[4 * jj + 2]), "r"(pk[4 * jj + 3]) : "memory");
}

template <int N> __device__ __forceinline__ void store_scaled(const float (&acc)[N], float s0, float s1, uint32_t a, uint32_t never_zero) {
  float t[8];
#pragma unroll
  for (int jj = 0; jj < 8; jj++) {
    float v = acc[8 * jj] * s0;
    if (jj >= RST) {
      v = t[jj - RST];
      asm("{\n.reg .pred p;\nsetp.ne.u32 p, %3, 0;\n@p mul.f32 %0, %1, %2;\n}\n" : "+f"(v) : "f"(acc[8 * jj]), "f"(s0), "r"(never_zero));
    }
    const uint32_t q = pack_bf16(v, acc[8 * jj + 1] * s0);
    t[jj] = __uint_as_float(q);
    asm volatile("stmatrix.sync.aligned.m8n8.x4.shared.b16 [%0], {%1,%2,%3,%4};" ::"r"((a ^ ((jj & 3) << 5)) + (jj >> 2) * 16384), "r"(q),
                 "r"(pack_bf16(acc[8 * jj + 2] * s1, acc[8 * jj + 3] * s1)), "r"(pack_bf16(acc[8 * jj + 4] * s0, acc[8 * jj + 5] * s0)),
                 "r"(pack_bf16(acc[8 * jj + 6] * s1, acc[8 * jj + 7] * s1)) : "memory");
  }
}

struct Cons {
  uint32_t sb;
  uint32_t pf;
  int wg, tid;
  __device__ __forceinline__ void wait_full(int g) { mbar_wait(sb + SM_BAR + (B_FULL + g) * 8, (pf >> g) & 1); pf ^= 1u << g; }
  uint32_t relb;
  __device__ __forceinline__ void release(int g, int n) {
    if (tid < 2 * n) asm volatile("mbarrier.arrive.shared::cluster.b64 _, [%0];" ::"r"(relb + g * 8) : "memory");
  }
  __device__ __forceinline__ void turn_begin() { bar_sync(1 + wg, 256); }
  __device__ __forceinline__ void turn_end() { bar_arrive(2 - wg, 256); }
  __device__ __forceinline__ void staged(int e) { __syncwarp(); if ((tid & 31) == 0) mbar_arrive(sb + SM_BAR + (B_EV + 2 * e + wg) * 8); }
  int zero;
  int rnd;
  uint32_t pfree;
  __device__ __forceinline__ void wait_stage_free() { mbar_wait(sb + SM_BAR + (B_FREE + wg) * 8, pfree); pfree ^= 1; }
  __device__ __forceinline__ bool try_full(int g) { return mbar_test(sb + SM_BAR + (B_FULL + g) * 8, (pf >> g) & 1); }
};

constexpr float SM_C = 0.08838834764831845f * 1.4426950408889634f;
struct SoftState { float m0, m1, l0, l1; int shifted; };
__device__ __forceinline__ void ex2_rot(float& t, float s, uint32_t never_zero) {
  asm("{\n.reg .pred p;\nsetp.ne.u32 p, %2, 0;\n@p ex2.approx.ftz.f32 %0, %1;\n}\n" : "+f"(t) : "f"(s), "r"(never_zero));
}
__device__ __forceinline__ void pin(float a, uint32_t never_zero) {
  asm volatile("{\n.reg .pred p;\nsetp.eq.u32 p, %1, 0;\n@p st.shared.f32 [%1], %0;\n}\n" ::"f"(a), "r"(never_zero) : "memory");
}
template <int O, int N> __device__ __forceinline__ void reg_fence_part(uint32_t (&d)[32]) {
#pragma unroll
  for (int i = O; i < O + N; i++) asm volatile("" : "+r"(d[i])::"memory");
}
template <int Q, int W, int N> __device__ __forceinline__ void exp_quarter(const float (&S)[N], uint32_t (&P)[32], float (&t)[ROT], float& s0, float& s1, uint32_t nz) {
#pragma unroll
  for (int i = 8 * Q; i < 8 * Q + 8; i++) {
    float& a = t[(2 * i) % ROT];
    float& b = t[(2 * i + 1) % ROT];
    if (2 * i < ROT) { a = ex2(S[2 * i]); b = ex2(S[2 * i + 1]); }
    else { ex2_rot(a, S[2 * i], nz); ex2_rot(b, S[2 * i + 1], nz); }
    if (i < 2) { if (i) s1 = a + b; else s0 = a + b; }
    else if (SUMV == 0) { if (i & 1) { s1 += a; s1 += b; } else { s0 += a; s0 += b; } }
    else { if (i & 1) s1 += a + b; else s0 += a + b; }
    if (i == 8 * Q) { pin(EXPV == 1 && Q ? s1 : s0, nz); wg_wait<W>(); reg_fence_part<8 * Q, 8>(P); }
    P[i] = pack_bf16(a, b);
  }
}
template <int N> __device__ __forceinline__ void shift_scores(float (&S)[N], float d0, float d1) {
#pragma unroll
  for (int i = 0; i < N; i++) S[i] -= (i & 2) ? d1 : d0;
}
__device__ __forceinline__ bool soft_high(float s0, float s1, float lim = SM_LIMIT) { return s0 > lim || s1 > lim; }
__device__ __forceinline__ bool soft_unsafe(float s0, float s1, bool first) {
  uint32_t b0 = __ballot_sync(0xffffffffu, s0 >= SM_LOW), b1 = __ballot_sync(0xffffffffu, s1 >= SM_LOW);
  b0 |= b0 >> 1; b0 |= b0 >> 2; b1 |= b1 >> 1; b1 |= b1 >> 2;
  return __any_sync(0xffffffffu, soft_high(s0, s1)) || (first && (b0 & b1 & 0x11111111u) != 0x11111111u);
}
template <int N> __device__ __forceinline__ void soft_fix(const float (&S)[N], float (&O)[64], SoftState& z, bool first, float& d0, float& d1) {
  d0 = d1 = first ? -INFINITY : 0.f;
#pragma unroll
  for (int j = 0; j < N / 4; j++) { d0 = fmaxf(d0, fmaxf(S[4 * j], S[4 * j + 1])); d1 = fmaxf(d1, fmaxf(S[4 * j + 2], S[4 * j + 3])); }
  d0 = fmaxf(d0, __shfl_xor_sync(0xffffffffu, d0, 1)); d1 = fmaxf(d1, __shfl_xor_sync(0xffffffffu, d1, 1));
  d0 = fmaxf(d0, __shfl_xor_sync(0xffffffffu, d0, 2)); d1 = fmaxf(d1, __shfl_xor_sync(0xffffffffu, d1, 2));
  const float sc0 = ex2(-fmaxf(d0, 0.f)), sc1 = ex2(-fmaxf(d1, 0.f));
  z.m0 += d0; z.m1 += d1; z.l0 *= sc0; z.l1 *= sc1; z.shifted = 1;
#pragma unroll
  for (int j = 0; j < 16; j++) { O[4 * j] *= sc0; O[4 * j + 1] *= sc0; O[4 * j + 2] *= sc1; O[4 * j + 3] *= sc1; }
}
template <int N> __device__ __forceinline__ void mask_diag(float (&S)[N], float nd) {
  asm volatile("" : "+f"(nd));
#pragma unroll
  for (int i = 0; i < 32; i++) {
    const float beyond = __saturatef(nd + (float)(8 * (i >> 2) + (i & 1) - 4 * (i & 2)));
    S[N - 32 + i] = fmaf(beyond, -3.0e38f, S[N - 32 + i]);
  }
}
__device__ __forceinline__ float quad_sum(float v) {
  v += __shfl_xor_sync(0xffffffffu, v, 1);
  v += __shfl_xor_sync(0xffffffffu, v, 2);
  return v;
}
__device__ __forceinline__ void issue_qk(float (&S)[64], uint32_t dq, uint32_t dk) {
  mma_ss_n128_init<0>(S, dq, dk);
#pragma unroll
  for (int s = 1; s < 8; s++) mma_ss_n128<0>(S, dq + (s >> 2) * 1024 + (s & 3) * 2, dk + (s >> 2) * 1024 + (s & 3) * 2);
}
__device__ __forceinline__ void issue_qk(float (&S)[32], uint32_t dq, uint32_t dk) {
  mma_ss_n64_init(S, dq, dk);
#pragma unroll
  for (int s = 1; s < 8; s++) mma_ss_n64(S, dq + (s >> 2) * 1024 + (s & 3) * 2, dk + (s >> 2) * 1024 + (s & 3) * 2);
}
template <int H> __device__ __forceinline__ void issue_pv(float (&O)[64], const uint32_t (&P)[32], uint32_t dv, int acc, bool on) {
  if (on) {
#pragma unroll
    for (int s = 4 * H; s < 4 * H + 4; s++) {
      mma_rs_n128<1>(O, P[4 * s], P[4 * s + 1], P[4 * s + 2], P[4 * s + 3], dv + s * 128, s != 0 ? 1 : acc);
      if (s & 1) wg_commit();
    }
  } else { wg_commit(); wg_commit(); }
}
constexpr uint32_t DG = GR >> 4;
__device__ __forceinline__ void stage_q2(Cons& c, const float (&O)[64], uint32_t (&P)[32], uint32_t stg) {
  wg_commit(); wg_commit(); wg_commit(); wg_commit();
  c.turn_end();
  pack_frag<0>(O, P);
  stsm_frag(P, stg);
  fence_async_smem();
}
__device__ __forceinline__ void attn_half(Cons& c, float (&O)[64], uint32_t (&P)[32], SoftState& z, uint32_t dk0, uint32_t dkk, uint32_t dv0, float dmask, int last) {
  float S[32];
  FTH(8 + last * 32, 0);
  c.turn_begin();
  FTH(9 + last * 32, 0);
  wg_fence();
  issue_qk(S, dk0 + (last ? 0 : 2 * DG), dkk + (last ? 8 : 4) * DG);
  wg_commit();
  issue_pv<0>(O, P, dv0 + 10 * DG, 1, last);
  issue_pv<1>(O, P, dv0 + 10 * DG, 1, last);
  c.turn_end();
  c.wait_full(last ? 12 : 6);
  FTH(10 + last * 32, 0);
  wg_wait<4>();
  reg_fence(S);
  FTH(11 + last * 32, 0);
  c.release(last ? 8 : 4, 2);
  mask_diag(S, dmask);
  float s0, s1, d0 = z.m0, d1 = z.m1;
#pragma unroll 1
  for (int pass = 0;; pass++) {
    if (z.shifted) shift_scores(S, d0, d1);
    float tr[ROT];
    exp_quarter<0, 3>(S, P, tr, s0, s1, c.sb);
    exp_quarter<1, 2>(S, P, tr, s0, s1, c.sb);
    pin(s1, c.sb); wg_wait<0>(); reg_fence_part<16, 16>(P); reg_fence(O);
    if (!soft_unsafe(s0, s1, !last) || pass) break;
    soft_fix(S, O, z, !last, d0, d1);
  }
  FTH(12 + last * 32, 0);
  z.l0 += s0; z.l1 += s1;
  c.release(10, last ? 2 : 0);
  if (!last) c.wait_full(8);
  FTH(13 + last * 32, 0);
}

template <int V> struct IC { static constexpr int value = V; };
__device__ __forceinline__ int conv_next(int g, bool spare) { return g >= NGR - 2 ? g - (NGR - 4) : !spare && g == 4 ? 1 : g + 2; }
__device__ __forceinline__ void conv_final(uint32_t rb, uint32_t yb, bool on) {
  const uint4 q0 = lds128(rb), q1 = lds128(rb + 4096), q2 = lds128(rb + 8192), q3 = lds128(rb + 12288);
  auto fin = [&](uint32_t x0, uint32_t x1, uint32_t x2, uint32_t x3) { return hadd2(hadd2(x0, x1), hadd2(x2, x3)); };
  asm volatile("{\n.reg .pred p;\nsetp.ne.b32 p, %5, 0;\n@p st.shared.v4.b32 [%0], {%1,%2,%3,%4};\n}\n" ::"r"(yb), "r"(fin(q0.x, q1.x, q2.x, q3.x)),
               "r"(fin(q0.y, q1.y, q2.y, q3.y)), "r"(fin(q0.z, q1.z, q2.z, q3.z)), "r"(fin(q0.w, q1.w, q2.w, q3.w)), "r"((int)on) : "memory");
}
__device__ __forceinline__ void conv_tasks(Cons& c, const Params& p, int ntask, bool spare, int ch, int chstep, int c5, uint32_t dd, uint32_t dkk, int w, int lane) {
  const uint32_t sb = c.sb;
  int g = 2 + c.wg;
  uint32_t rb = sb + g * GR;
  const uint32_t yb = sb + c.wg * 8192 + c.tid * 16;
  const int gt = 8 * w + (lane >> 2) + (lane & 3);
  uint32_t a[64], hb;
  auto lda = [&](int s) {
    a[4 * s] = lds32(hb + s * 256); a[4 * s + 1] = lds32(hb + s * 256 + 128);
    a[4 * s + 2] = lds32(hb + s * 256 + 16); a[4 * s + 3] = lds32(hb + s * 256 + 144);
  };
  auto first_a = [&]() {
    hb = sb + g * GR + WBYTES - 28 + gt * 4;
    lda(0); lda(15);
  };
  c.wait_full(g);
  first_a();
#pragma unroll 1
  for (int i = 0; i < ntask; i++) {
    const uint32_t base = sb + g * GR;
    FTC(0);
    lda(1); lda(14);
    a[0] = hadd2(a[0], gt == 7 ? dd : 0u); a[2] = hadd2(a[2], gt == 3 ? dd : 0u);
    float acc[128];
    const uint32_t db = dkk + ((WPL / 16 - 1) << 16) + g * DG + WZ / 16;
    FTC(2);
    c.turn_begin();
    FTC(3);
    auto pair = [&](auto kc) {
      constexpr int k = decltype(kc)::value;
      if (k < 7) wg_fence();
      if (k == 6) c.turn_end();
      conv_step<k, 7>(acc, a, db);
      conv_step<15 - k, 7>(acc, a, db);
      if (k < 6) { lda(k + 2); lda(13 - k); }
      if (k == 0) conv_final(rb, yb, i > 0);
      if (k == 1) {
        conv_final(rb + 2048, yb + 2048, i > 0);
        __syncwarp();
        if (lane == 0 && i > 0) mbar_arrive(sb + SM_BAR + (B_EV + c.wg) * 8);
      }
      if (k == 6) dd = __bfloat16_as_ushort(p.ssd[(ch + chstep + (i == 1 ? c5 : 0)) & (DM - 1)]);
    };
    pair(IC<0>()); pair(IC<1>()); pair(IC<2>()); pair(IC<3>()); pair(IC<4>()); pair(IC<5>()); pair(IC<6>()); pair(IC<7>());
    wg_commit();
    FTC(4);
    g = conv_next(g, spare);
    ch += chstep;
    rb = base + c.tid * 16;
    if (i + 1 < ntask) c.wait_full(g);
    const bool fr = mbar_test(sb + SM_BAR + (B_FREE + c.wg) * 8, c.pfree);
    wg_wait<0>();
    reg_fence(acc);
    reg_fence(a);
    bar_sync(3 + c.wg, 128);
    FTC(5);
    first_a();
    const int tw = (lane & 3) + w;
    const uint32_t xb = base + w * 4096 + tw * 32 + (lane >> 2) * 4;
    [[maybe_unused]] float t0[EROT + 1];
#pragma unroll
    for (int j = 0; j < 32; j++) {
      uint32_t ad = xb + j * 128;
      float v0 = acc[4 * j], v1 = acc[4 * j + 1];
      if (EROT && j > EROT) {
        v0 = t0[j % (EROT + 1)];
        asm("{\n.reg .pred p;\nsetp.ne.u32 p, %3, 0;\n@p add.f32 %0, %1, %2;\n}\n" : "+f"(v0) : "f"(acc[4 * j]), "f"(acc[j > 0 ? 4 * j - 2 : 0]), "r"(sb));
      } else if (j > 0) v0 += acc[j > 0 ? 4 * j - 2 : 0];
      if (j > 0) v1 += acc[j > 0 ? 4 * j - 1 : 0];
      uint32_t v = pack_bf16(v0, v1);
      t0[j % (EROT + 1)] = __uint_as_float(v);
      if (j == 31 && tw >= 4) { v = 0; ad -= 4096; }
      asm volatile("st.shared.b32 [%0], %1;" ::"r"(ad), "r"(v) : "memory");
    }
    if (!fr) c.wait_stage_free(); else c.pfree ^= 1;
    FTC(6);
  }
  bar_sync(3 + c.wg, 128);
  conv_final(rb, yb, true);
  conv_final(rb + 2048, yb + 2048, true);
  c.staged(0);
}

__global__ void __cluster_dims__(2, 1, 1) __launch_bounds__(NTHREADS, 1) mega_kernel(const __grid_constant__ Params p) {
  extern __shared__ __align__(1024) uint8_t smem_raw[];
  FTS(0);
  const uint32_t sb = smem_u32(smem_raw);
  if (threadIdx.x - 64 < 32) { prefetch_tm(&p.c); prefetch_tm(&p.wuk + (blockIdx.x & 1)); }
  const int wgi = __shfl_sync(0xffffffffu, threadIdx.x >> 7, 0);
  const int warp = __shfl_sync(0xffffffffu, threadIdx.x >> 5, 0);
  const uint32_t rank = blockIdx.x & 1;
  int slot;
  {
    uint32_t smid; asm volatile("mov.u32 %0, %smid;" : "=r"(smid));
    slot = p.pref[((smid >> 1) + (threadIdx.x & (smid >> 16))) & 127];
  }
  if (warp >= 3) {
    if (elect()) {
#pragma unroll
      for (int k = 0; k < 4; k++) mbar_init(sb + SM_BAR + ((warp - 3) * 4 + k) * 8, k == 1 && warp == 7 ? 11 : warp < (k ? 7 : 8) ? 1 : 4);
      if (warp == 7) { mbar_init(sb + SM_BAR + B_TICK * 8, 1); mbar_expect_tx(sb + SM_BAR + B_SLOT * 8, 8); mbar_expect_tx(sb + SM_BAR + B_TICK * 8, 4); }
      asm volatile("fence.mbarrier_init.release.cluster;" ::: "memory");
    }
    __syncwarp();
  }
  FTS(1);
  cluster_arrive();
  slot = __shfl_sync(0xffffffffu, slot, 0);
  const int pref = slot;
  if (warp < 4) {
    asm volatile("setmaxnreg.dec.sync.aligned.u32 40;");
    if (warp == 1 + 4 * rank) {
      unsigned taken = threadIdx.x == 32;
#pragma unroll 1
      for (int n = 0; n < NSLOT; n++) {
        asm volatile("{\n.reg .pred p;\nsetp.ne.b32 p, %0, 0;\n@p atom.relaxed.gpu.global.exch.b32 %0, [%1], 1;\n}\n" : "+r"(taken) : "l"(CLAIMP(slot)) : "memory");
        if (!__any_sync(0xffffffffu, taken)) break;
        slot = slot == NSLOT - 1 ? 0 : slot + 1;
      }
    }
    cluster_wait();
    if (threadIdx.x == 32) {
      send_both(sb + SM_BAR + B_SLOT * 8, (V_SLOT - B_SLOT) * 8 + rank * 4, slot | pref << 8);
    }
    if (warp == 2) {
#pragma unroll 1
      for (int kk = 0; kk < 4; kk++) {
        const int g0 = 2 + 3 * kk;
        const uint32_t fb = sb + SM_BAR + (B_FULL + g0) * 8;
        if (elect()) {
          FTSW(kk);
          mbar_expect_tx(fb, 3 * GR);
          tma2d(sb + g0 * GR, &p.c, kk * 64, (KV_ROW(pref & 7, 0) + rank) * 128, fb);
          tma3d_mc(sb + (g0 + 1 + rank) * GR, rank ? &p.wuv : &p.wuk, 0, kk * 64, ((pref & 56) >> 1) + 2 * KV_HEAD(pref & 7, 0), fb);
        }
        if (kk < 3) {
          uint32_t c0, c1;
          asm volatile("mov.u32 %0, %clock;" : "=r"(c0));
          do asm volatile("mov.u32 %0, %clock;" : "=r"(c1)); while (c1 - c0 < (kk ? X_D2 : X_DELAY));
        }
      }
      FTSW(4);
      prefetch_tm(&p.x); prefetch_tm(&p.wq);
    }
  }
  int grp, idx, lb;
  int cn, cch, cstep;
  bool spare, redo;
  auto get_slot = [&]() {
    mbar_wait(sb + SM_BAR + B_SLOT * 8, 0);
    const uint32_t sv0 = __shfl_sync(0xffffffffu, lds32(sb + SM_BAR + V_SLOT * 8), 0), sv1 = __shfl_sync(0xffffffffu, lds32(sb + SM_BAR + V_SLOT * 8 + 4), 0);
    grp = (sv0 & 255) >> 3; idx = sv0 & 7; lb = (sv0 & 255) * 2 + rank;
    spare = grp == 8; redo = spare || sv0 != sv1;
    cn = CN_SPARE; cch = spare ? lb - NMAIN : 4 * CN_SPARE + 4 * lb; cstep = spare ? 4 : 1;
    if (FINE_MODE != 7) TS(0);
  };
  auto get_ticket = [&]() {
    mbar_wait(sb + SM_BAR + B_TICK * 8, 0);
    const int tk = __shfl_sync(0xffffffffu, lds32(sb + SM_BAR + V_TICK * 8), 0);
    cn = tk < NTICK ? 5 : 4;
    return 4 * NMAIN - 4 * lb - 4 + 2 * tk + rank;
  };

  if (wgi == 0) {
    asm volatile("setmaxnreg.dec.sync.aligned.u32 40;");
    const int lane = threadIdx.x & 31;
    cluster_arrive();
    get_slot();
    uint32_t pe = 0;
    auto acquire = [&](int g, int n, uint32_t m) {
      int i = g;
#pragma unroll 1
      do mbar_wait1(sb + SM_BAR + (B_EMPTY + i) * 8, (pe >> i) & 1); while (++i < g + n);
      pe ^= m << g;
    };
    if (warp == 3) {
      if (!spare) {
        const int s0 = lb * 16;
#pragma unroll 1
        for (int cg = 0; cg < 16; cg++) {
          if (cg == UP0 || cg == UP1) {
#pragma unroll 1
            for (int n = 0; n < 20 && !__any_sync(0xffffffffu, mbar_try(sb + SM_BAR + B_SLOT * 8, cg == UP0)); n++);
          } else if (cg < UP0) __nanosleep(US0);
          if (cg == UP1 && lane == rank * 32) send_both(sb + SM_BAR + B_TICK * 8, (V_TICK - B_TICK) * 8, atomicInc(FLAG(F_TICK), 0x7fffffffu));
          const int ch = cg * 64 + 2 * lane;
          const uint32_t* kp = reinterpret_cast<const uint32_t*>(p.ak + (size_t)s0 * DM + ch);
          const uint32_t* vp = reinterpret_cast<const uint32_t*>(p.av + (size_t)s0 * DM + ch);
          const uint4 sw = __ldg(reinterpret_cast<const uint4*>(p.shk + ch * 4));
          uint32_t k3 = 0, k2 = 0, k1 = 0, k0 = 0, up = 0;
          if (lb > 0) { k3 = ldg_stream(kp - 4 * 512); k2 = ldg_stream(kp - 3 * 512); k1 = ldg_stream(kp - 2 * 512); k0 = ldg_stream(kp - 512); up = ldg_stream(vp - 512); }
          const uint32_t w0 = __byte_perm(sw.x, sw.z, 0x5410), w1 = __byte_perm(sw.x, sw.z, 0x7632);
          const uint32_t w2 = __byte_perm(sw.y, sw.w, 0x5410), w3 = __byte_perm(sw.y, sw.w, 0x7632);
          up = hmul2(hfma2(k0, w0, hfma2(k1, w1, hfma2(k2, w2, hmul2(k3, w3)))), up);
#pragma unroll 1
          for (int hb = 0; hb < 2; hb++) {
            uint32_t kk[8], u[8];
#pragma unroll
            for (int r = 0; r < 8; r++) { kk[r] = ldg_stream(kp + r * 512); u[r] = ldg_stream(vp + r * 512); }
#pragma unroll
            for (int r = 0; r < 8; r++) {
              k3 = k2; k2 = k1; k1 = k0; k0 = kk[r];
              u[r] = hmul2(hfma2(k0, w0, hfma2(k1, w1, hfma2(k2, w2, hmul2(k3, w3)))), u[r]);
            }
            if (lane == 0) asm volatile("cp.async.bulk.wait_group.read 0;" ::: "memory");
            __syncwarp();
            const uint32_t dst = sb + SM_UST + lane * 32 + ((lane & 4) << 2);
#pragma unroll
            for (int cc = 0; cc < 2; cc++) {
              const uint32_t sel = cc ? 0x7632 : 0x5410;
              asm volatile("st.shared.v4.b32 [%0], {%1,%2,%3,%4};" ::"r"(dst + cc * 1024), "r"(__byte_perm(u[6], u[5], sel)), "r"(__byte_perm(u[4], u[3], sel)),
                           "r"(__byte_perm(u[2], u[1], sel)), "r"(__byte_perm(u[0], up, sel)) : "memory");
              asm volatile("st.shared.v4.b32 [%0], {%1,%2,%3,%4};" ::"r"((dst ^ 16) + cc * 1024), "r"(__byte_perm(u[7], u[6], sel)), "r"(__byte_perm(u[5], u[4], sel)),
                           "r"(__byte_perm(u[3], u[2], sel)), "r"(__byte_perm(u[1], u[0], sel)) : "memory");
            }
            fence_async_smem();
            __syncwarp();
            if (lane == 0) {
              asm volatile("cp.async.bulk.tensor.3d.global.shared::cta.bulk_group [%0, {%2, %3, %4}], [%1];\ncp.async.bulk.commit_group;"
                           ::"l"(&p.w), "r"(sb + SM_UST), "r"(WZ / 2 + lb * 16 + (hb ^ 1) * (WPL / 2)), "r"(cg * 32), "r"(0) : "memory");
            }
            up = u[7];
            kp += 8 * 512; vp += 8 * 512;
          }
          if ((cg & (cg + 1)) == 0 && lane == 0) {
            asm volatile("cp.async.bulk.wait_group 0;" ::: "memory");
            fence_release();
            flag_add(FLAG(F_U + 32 - __clz(cg)));
          }
          TSW(10 + cg);
        }
        prefetch_tm(&p.wo); prefetch_tm(&p.x3); prefetch_tm(&p.y3); prefetch_tm(&p.out);
        if (P3PF) {
          const int rt = 2 * grp + rank;
          unsigned v;
          asm volatile("ld.acquire.gpu.global.u32 %0, [%1];" : "=r"(v) : "l"(FLAG(F_CTX + rt * 2)) : "memory");
#pragma unroll 1
          for (int kb = P3PF0; kb < P3PF0 + P3PF; kb++) {
            const uint8_t* a = lane < 16 ? g_cimg + (unsigned)((rt * 64 + kb) * GR + (idx * 16 + lane) * 128) : (const uint8_t*)p.wop + (unsigned)(kb * 64 * DM * 2 + (lb * 8 + (lane & 7)) * 128);
            if (lane < 24 && v == 32) asm volatile("prefetch.global.L2 [%0];" ::"l"(a));
          }
        }
      } else {
#pragma unroll 1
        for (int i = 0, g = 2; i < 32; i++) {
          acquire(g, 2, 3);
          if (elect()) {
            const uint32_t fb = sb + SM_BAR + (B_FULL + g) * 8;
            if (i == 0) { mbar_expect_tx(fb - 8, 2048); bulk_g2s(sb + GR, p.gate_w, 2048, fb - 8); }
            mbar_expect_tx(fb, 2 * GR);
            tma3d(sb + g * GR, &p.x3, 0, (lb - NMAIN) * 512 + (i >> 3) * 128, (i & 7) * 2, fb);
          }
          g = g == NGR - 2 ? 2 : g + 2;
        }
        bar_arrive(5, 64);
      }
      unsigned long long t0, t1;
      asm volatile("mov.u64 %0, %globaltimer;" : "=l"(t0));
      auto check = [&]() {
        asm volatile("mov.u64 %0, %globaltimer;" : "=l"(t1));
        if (t1 - t0 > 2000000000ull) __trap();
      };
      if (!spare) {
        unsigned v;
        do {
          __nanosleep(PSL);
          check();
          asm volatile("ld.acquire.gpu.global.u32 %0, [%1];" : "=r"(v) : "l"(FLAG(lane & 1 ? F_Y + idx : F_GATE)) : "memory");
        } while (__any_sync(0xffffffffu, v < (lane & 1 ? 128 : 32)));
        __syncwarp();
        if (lane == 0) mbar_arrive(sb + SM_BAR + B_SLOT * 8);
      }
      if (lane == 0) {
        while (!mbar_try(sb + SM_BAR + B_DONE * 8, 0)) check();
      }
    } else if (warp != 0) {
      const int w = warp - 1;
      int ne = 12 + (CN_SPARE + 1 - w) / 2, c5 = 0;
      uint32_t p0 = 0;
      int cg = 2 + w, ch = cch + w * cstep;
#pragma unroll 1
      for (int e = spare ? 12 : 0; e < ne; e++) {
        const int rnd = e >= 6, k = e - 6 * rnd, rt = k == 4 ? idx : 15 - idx;
        uint8_t* dst = k < 4 ? g_kv + (size_t)(((k & 1) * 16 + 2 * grp + KV_HEAD(idx, k >> 1)) * 16 + KV_ROW(idx, k >> 1) + rank) * 32768 + w * 8192
                     : k < 6 ? g_cimg + (size_t)(rt * 32 + 16 * rnd + 2 * grp + rank) * 32768 + (w ^ (k & 1)) * 8192
                             : reinterpret_cast<uint8_t*>(g_yT + (size_t)ch * SEQ);
        const uint32_t src = sb + w * 8192 + (k == 4 ? 2 * GR : 0);
        if (e == 11) { c5 = get_ticket(); ne = 12 + ((cn + 1 - w) >> 1); }
        if (e == 6) flag_wait(FLAG(F_AD + grp), 32);
        mbar_wait1(sb + SM_BAR + (B_EV + (k == 4 ? 2 : 0) + w) * 8, k == 4 ? rnd : p0);
        if (k != 4) p0 ^= 1;
        if (lane < 4 && k >= 6 && (!spare || e < ne - 6)) mbar_arrive_cluster(sb + SM_BAR + (B_EMPTY + cg) * 8, lane & 1);
        fence_async_smem();
        if (elect()) {
          const uint32_t cs = k >= 6 ? 4096 : 1024;
#pragma unroll 1
          for (uint32_t i = 0; i < (k >= 6 ? 4096 : 16384); i += cs) {
            const uint32_t o = i + (i & 8192);
            asm volatile("cp.async.bulk.global.shared::cta.bulk_group [%0], [%1], %2;" ::"l"(dst + o), "r"(src + o), "r"(cs) : "memory");
            asm volatile("cp.async.bulk.commit_group;\ncp.async.bulk.wait_group.read 1;" ::: "memory");
          }
          asm volatile("cp.async.bulk.wait_group 0;" ::: "memory");
          if (k != 4) mbar_arrive(sb + SM_BAR + (B_FREE + w) * 8);
        }
        __syncwarp();
        if (lane < (k == 4 ? 4 : e == 11 || (e == ne - 1 && !spare) ? 2 : 0))
          mbar_arrive_cluster(sb + SM_BAR + (B_EMPTY + (k == 4 ? 2 : e == 11) + (lane >> 1)) * 8, lane & 1);
        if (k >= 3) {
          fence_release();
          const unsigned fl = k == 3 ? F_KV + rnd * 8 + grp : k < 6 ? F_CTX + rt * 2 + rnd : F_Y + ((unsigned)ch >> 7);
          if (lane <= (e == 5)) flag_add(FLAG(lane ? F_AD + grp : fl));
        }
        if (k >= 6) { cg = conv_next(cg, spare); ch += 2 * cstep + (k == 7 ? c5 : 0); }
      }
      if (lane == 0) mbar_arrive(sb + SM_BAR + B_DONE * 8);
    } else {
#pragma unroll 1
      for (int rnd = 0; rnd < (spare ? 0 : 2); rnd++) {
        const int hp = 16 * rnd + 2 * grp, head = hp + rank;
#pragma unroll 1
        for (int kk = rnd || redo ? 0 : 4; kk < 32; kk++) {
          const int g0 = 2 + 3 * (kk & 3);
          acquire(g0, kk < 4 ? 3 : 1, 7);
          if (elect()) {
            const uint32_t fb = sb + SM_BAR + (B_FULL + g0) * 8;
            mbar_expect_tx(fb, 3 * GR);
            if (kk < 16) {
              tma2d(sb + g0 * GR, &p.c, (kk & 7) * 64, (KV_ROW(idx, kk >> 3) + rank) * 128, fb);
              tma3d_mc(sb + (g0 + 1 + rank) * GR, rank ? &p.wuv : &p.wuk, 0, (kk & 7) * 64, (hp + KV_HEAD(idx, kk >> 3)) * 2, fb);
            } else {
              tma2d_mc(sb + (g0 + rank) * GR, &p.x, (kk - 16) * 64, (rank ? 15 - idx : idx) * 128, fb);
              tma3d(sb + (g0 + 2) * GR, &p.wq, 0, (kk - 16) * 64, head * 2, fb);
            }
          }
        }
        flag_wait(FLAG(F_KV + rnd * 8 + grp), 32);
        fence_async_all();
        acquire(2, 1, 3);
        int g0 = 4;
#pragma unroll 1
        for (int n = 0; n < 36; n += n == 0 || n == 33 ? 2 : 1) {
          const int it = (n >> 1) - (n & 1);
          const int blk = it & 15 ? (it <= idx ? it - 1 : 15 - it) : it ? 15 - idx : idx;
          acquire(g0, n < 6 ? 2 : 1, 3);
          if (elect()) {
            const uint32_t fb = sb + SM_BAR + (B_FULL + g0) * 8;
            if (n == 5) mbar_arrive(sb + SM_BAR + B_SLOT * 8);
            mbar_expect_tx(fb, 2 * GR);
            bulk_g2s(sb + g0 * GR, g_kv + (unsigned)((((n & 1) * 16 + (head & 15)) * 16 + blk) * 32768), 2 * GR, fb);
          }
          g0 = n == 13 ? 12 : g0 == 12 ? 4 : g0 + 2;
        }
      }
      int c5 = 0;
      if (spare) { bar_sync(5, 64); pe = 0x3FC0; }
      else c5 = get_ticket();
      auto conv_fill = [&](int g, int ch) {
        acquire(g, 1, 1);
        if (elect()) {
          const uint32_t fb = sb + SM_BAR + (B_FULL + g) * 8;
          if (!spare) FTP(64 + 48 + g);
          mbar_expect_tx(fb, WBYTES + 4096);
          bulk_g2s<true>(sb + g * GR, g_w + (size_t)ch * WSTRIDE, WBYTES, fb);
          bulk_g2s<true>(sb + g * GR + WBYTES, p.ssk + (size_t)ch * SEQ, 4096, fb);
        }
      };
#pragma unroll 1
      for (int i = 0, g = 2; i < cn; i++) {
        if ((i & 15) == 0) { flag_wait(FLAG(F_U + (spare ? 32 - __clz(i >> 4) : 4)), NMAIN); fence_async_all(); }
        conv_fill(g + (i & 1), cch + i * cstep + (i == 4 ? c5 : 0));
        if (i & 1) g = conv_next(g, spare);
      }
      if (!spare) {
        const int rt = 2 * grp + rank, ct = idx;
        int g0 = P3G, top = 12;
        const uint8_t* src = g_cimg + (unsigned)(rt * 64 * GR);
#pragma unroll 1
        for (int kb = 0; kb < 64; kb++) {
          if (!(kb & 31)) { flag_wait(FLAG(F_CTX + rt * 2 + (kb >> 5)), 32); fence_async_all(); }
          acquire(g0, kb < 11 ? 2 : 1, 3);
          if (elect()) {
            const uint32_t fb = sb + SM_BAR + (B_FULL + g0) * 8;
            if (kb < 16) FTP(48 + kb);
            mbar_expect_tx(fb, 2 * GR);
            bulk_g2s<true>(sb + g0 * GR, src, GR, fb);
            tma2d_mc<true>(sb + (g0 + 1) * GR + rank * 8192, &p.wo, ct * 128 + rank * 64, kb * 64, fb);
          }
          src += GR;
          g0 = g0 == (kb < XK ? 12 : kb < YK ? 10 : 8) ? (kb == 3 ? 2 : 0) : g0 + 2;
          if (kb == XK || (kb >= YK && top == P3Y && (kb == 63 || mbar_test(sb + SM_BAR + B_SLOT * 8, 1)))) {
            const bool j = kb != XK;
            if (j) { mbar_wait1(sb + SM_BAR + B_SLOT * 8, 1); fence_async_all(); }
            acquire(top, 1, 0);
            if (elect()) {
              const uint32_t fb = sb + SM_BAR + (B_FULL + top) * 8;
              mbar_expect_tx(fb, j ? 2 * GR + 512 : 2 * GR);
              if (j) bulk_g2s(sb + SM_GATE, g_gate + (unsigned)(rt * 128), 512, fb);
              tma3d(sb + top * GR, j ? &p.y3 : &p.x3, 0, (j ? ct : rt) * 128, (j ? rt : ct) * 2, fb);
            }
            top -= 2;
          }
        }
        unsigned n = 0;
        if (lane == 0) n = atomicInc(FLAG(F_EXIT), 0x7fffffffu);
        if (__any_sync(0xffffffffu, n == NMAIN - 1)) {
#pragma unroll
          for (int i = lane; i < 96; i += 32) *reinterpret_cast<uint2*>(FLAG(i)) = make_uint2(0, 0);
        }
      }
      if (lane == 0) mbar_arrive(sb + SM_BAR + B_DONE * 8);
    }
    __syncwarp();
    cluster_wait();
  } else {
    asm volatile("setmaxnreg.inc.sync.aligned.u32 232;");
    FTS(2);
    Cons c;
    c.sb = sb; c.pf = 0; c.wg = wgi - 1; c.tid = threadIdx.x & 127;
    const int lane = threadIdx.x & 31, t = lane & 3;
    const int row = c.wg * 64 + (warp & 3) * 16 + (lane >> 2);
    const uint32_t dkk = desc_k(sb), dk0 = dkk + c.wg * 512, dm0 = desc_mn<8192>(sb), dv0 = desc_mn<16384>(sb);
    const uint32_t dsw = DG + 512 - c.wg * 1024;
    if (c.wg == 1) bar_arrive(1, 256);
    c.pfree = 1;
    asm("mapa.shared::cluster.u32 %0, %1, %2;" : "=r"(c.relb) : "r"(sb + SM_BAR + (B_EMPTY + (c.tid >> 1)) * 8), "r"(c.tid & 1));
    c.zero = p.zero;
    c.rnd = 0;
    const uint32_t stg = sb + (c.wg * 64 + (warp & 3) * 16 + ((lane >> 3) & 1) * 8 + (lane & 7)) * 128 + (((lane >> 4) ^ (lane & 7)) << 4);

    uint32_t dd0;
    auto load_dd = [&]() { asm volatile("ld.global.nc.u16 %0, [%1];" : "=r"(dd0) : "l"(p.ssd + (unsigned)(cch + c.wg * cstep + (lane & c.zero)))); };
    int pass = c.zero;
#pragma unroll 1
    do {
    if (pass) {
      load_dd();
#pragma unroll 1
      for (int g = 2; g < NGR; g += 3) { mbar_wait(sb + SM_BAR + (B_FULL + g) * 8, 0); c.release(g, 3); }
      c.pf = 0x924;
    if (spare) {
      c.wait_full(1);
      int g = 2;
#pragma unroll 1
      for (int r = 0; r < 4; r++) {
        float d[4] = {0.f, 0.f, 0.f, 0.f}, e[4] = {0.f, 0.f, 0.f, 0.f};
#pragma unroll 1
        for (int kb = 0; kb < 16; kb += 2) {
          c.wait_full(g);
          wg_fence();
#pragma unroll 1
          for (int k = 0; k < 4; k++) {
            mma_ss_n8(d, dk0 + g * DG + k * 2, dkk + DG + kb * 8 + k * 2);
            mma_ss_n8(e, dk0 + (g + 1) * DG + k * 2, dkk + DG + kb * 8 + 8 + k * 2);
          }
          wg_commit();
          wg_wait<0>();
          c.release(g, 2);
          g = g == NGR - 2 ? 2 : g + 2;
        }
        reg_fence(d); reg_fence(e);
        d[0] += e[0]; d[2] += e[2];
        if (t == 0) {
          float* gp = g_gate + (unsigned)((lb - NMAIN) * 512 + r * 128 + row);
          gp[0] = rcp(1.f + ex2(-1.4426950408889634f * d[0])); gp[8] = rcp(1.f + ex2(-1.4426950408889634f * d[2]));
        }
      }
      fence_release();
      __syncwarp();
      if (lane == 0) flag_add(FLAG(F_GATE));
      TS(1);
    }
    } else cluster_wait();
    get_slot();
    } while (redo && !pass++);
    FTS(3);
    const float dmask = (float)(2 * t - (row & 63));
    int c5 = 0;
    uint32_t pv[32];
#pragma unroll 1
    for (int rnd = 0; rnd < (spare ? 0 : 2); rnd++) {
      float O[64];
      FTM(rnd * 8);
      FTG(0);
      FTH(56, c.rnd == rnd);
      c.wait_full(2);
      FTM(rnd * 8 + 1);
      FTH(57, c.rnd == rnd);
#pragma unroll 1
      for (int tile = c.zero; tile < 2; tile++) {
        float acc[128];
        const bool single = tile == 0;
        {
          FTG(tile * 32 + 1);
          const uint32_t a = dk0 + 2 * DG, b = dm0 + 3 * DG;
          c.turn_begin();
          FTG(tile * 32 + 2);
          FTH(58, c.rnd == rnd);
          wg_fence();
          mma_ss_n256_init<1>(acc, a, b);
#pragma unroll
          for (int k = 1; k < 4; k++) mma_ss_n256<1>(acc, a + k * 2, b + k * 128);
          wg_commit();
          if (single) c.turn_end();
          FTG(tile * 32 + 3);
        }
#pragma unroll 1
        for (int kb = 1; kb < 8; kb++) {
          const int g0 = 2 + 3 * (kb & 3);
          const uint32_t a = dk0 + g0 * DG, b = dm0 + (g0 + 1) * DG;
          const bool second = (kb == 1 && !single) || kb == 7;
          FTG(tile * 32 + kb * 4);
          if (!second) { wg_wait<0>(); c.release(2 + 3 * ((kb - 1) & 3), 3); }
          FTG(tile * 32 + kb * 4 + 1);
          c.wait_full(g0);
          if (!second) c.turn_begin();
          FTG(tile * 32 + kb * 4 + 2);
          wg_fence();
#pragma unroll
          for (int k = 0; k < 4; k++) mma_ss_n256<1>(acc, a + k * 2, b + k * 128);
          wg_commit();
          if (kb != 6) c.turn_end();
          if (second) { wg_wait<1>(); c.release(2 + 3 * ((kb - 1) & 3), 3); }
          FTG(tile * 32 + kb * 4 + 3);
          FTH(58 + kb, c.rnd == rnd || kb > 3);
          if (tile == 1 && kb == 3) { c.wait_stage_free(); stsm_frag<0, 4>(pv, stg); }
          if (tile == 1 && kb == 4) { stsm_frag<4, 8>(pv, stg); c.staged(0); }
        }
        c.rnd = rnd;
        c.wait_stage_free();
        const bool nxt = c.try_full(2);
        wg_wait<0>();
        reg_fence(acc);
        c.release(11, 3);
        store_scaled(acc, SM_C, SM_C, stg, sb);
        c.staged(0);
        pack_frag<64>(acc, pv);
        FTG(32 + tile * 32);
        if (!nxt) mbar_wait(sb + SM_BAR + (B_FULL + 2) * 8, (c.pf >> 2) & 1);
        c.pf ^= 4;
      }
      TS(1 + rnd * 3);
      FTM(rnd * 8 + 2);
      {
        float qa[64];
        float (&qb)[64] = O;
        {
          FTG(65);
          const uint32_t a = dk0 + 2 * DG, b = dm0 + 4 * DG;
          c.turn_begin();
          FTG(66);
          wg_fence();
          mma_ss_n128_init<1>(qa, a, b);
          mma_ss_n128_init<1>(qb, a + dsw, b);
#pragma unroll
          for (int k = 1; k < 4; k++) {
            mma_ss_n128<1>(qa, a + k * 2, b + k * 128);
            mma_ss_n128<1>(qb, a + dsw + k * 2, b + k * 128);
          }
          wg_commit();
          FTG(67);
        }
#pragma unroll 1
        for (int kb = 1; kb < 16; kb++) {
          const int g0 = 2 + 3 * (kb & 3);
          const uint32_t a = dk0 + g0 * DG, b = dm0 + (g0 + 2) * DG;
          const bool second = kb == 1 || kb == 15;
          FTG(64 + kb * 4);
          if (!second) { wg_wait<0>(); c.release(2 + 3 * ((kb - 1) & 3), 3); }
          FTG(65 + kb * 4);
          c.wait_full(g0);
          if (!second) c.turn_begin();
          FTG(66 + kb * 4);
          FTH(kb - 14, kb < 14);
          wg_fence();
#pragma unroll
          for (int k = 0; k < 4; k++) {
            mma_ss_n128<1>(qa, a + k * 2, b + k * 128);
            mma_ss_n128<1>(qb, a + dsw + k * 2, b + k * 128);
          }
          wg_commit();
          if (kb != 14) c.turn_end();
          if (second) { wg_wait<1>(); c.release(2 + 3 * ((kb - 1) & 3), 3); }
          FTG(67 + kb * 4);
          FTH(2, kb < 15);
          if (kb == QFLUSH) { c.wait_stage_free(); stsm_frag<0, 4>(pv, stg); }
          if (kb == QFLUSH + 1) { stsm_frag<4, 8>(pv, stg); c.staged(0); }
        }
        c.wait_stage_free();
        mbar_wait(sb + SM_BAR + (B_EMPTY + 2) * 8, rnd ^ !redo);
        FTM(rnd * 8 + 3);
        FTH(3, 0);
        const bool k0 = c.try_full(4);
        wg_wait<0>();
        reg_fence(qa); reg_fence(qb);
        FTH(4, 0);
        c.release(11, 3);
        pack_frag<0>(qa, pv);
        stsm_frag(pv, stg + 2 * GR);
        if (c.wg == 0) {
          pack_frag<0>(qb, pv);
          stsm_frag(pv, stg);
        }
        FTH(6, 0);
        fence_async_smem();
        FTH(7, 0);
        if (!k0) c.wait_full(4); else c.pf ^= 16;
      }
      TS(2 + rnd * 3);
      FTM(rnd * 8 + 4);
      FTH(5, 0);
      {
        const int nA = idx + 1;
        uint32_t (&P)[32] = pv;
        SoftState z;
        z.m0 = z.m1 = z.l0 = z.l1 = 0.f; z.shifted = c.zero;
#pragma unroll 1
        for (int seg = c.zero;; seg++) {
        if (c.wg == seg) attn_half(c, O, P, z, dk0, dkk, dv0, dmask, seg);
        if (seg) break;
        FTM(rnd * 8 + 5);
        int gk = c.wg ? 4 : 6, gv = c.wg ? 4 : 8;
        uint32_t dq = dk0 + (1 - c.wg < nA ? 2 * DG : 0), dk = dkk + gk * DG;
#pragma unroll 1
        for (int it = 1 - c.wg; it < 17 - c.wg; it++) {
          float S[64];
          FTA(it * 7 + 0); FTH((it < 3 ? 8 + it * 8 : it * 8 - 88) + 0, it >= 3 && it < 15);
          c.turn_begin();
          FTA(it * 7 + 2); FTH((it < 3 ? 8 + it * 8 : it * 8 - 88) + 1, it >= 3 && it < 15);
          wg_fence();
          issue_qk(S, dq, dk);
          wg_commit();
          const uint32_t dv = dv0 + gv * DG;
          uint32_t relk = c.relb + gk * 8, relv = c.relb + gv * 8;
          gk = it == 6 ? 12 : gv == 12 ? 4 : gv + 2;
          gv = it == 16 ? gk : gk == 12 ? 4 : gk + 2;
          uint32_t fk = sb + SM_BAR + (B_FULL + gk) * 8, fv = sb + SM_BAR + (B_FULL + gv) * 8, park = (c.pf >> gk) & 1, parv = (c.pf >> gv) & 1;
          c.pf ^= (1u << gk) | (1u << gv);
          dq = dk0 + (it + 1 < nA ? 2 * DG : 0); dk = dkk + gk * DG;
          float lo0 = z.l0, lo1 = z.l1;
          const bool first = it == nA || it == 0;
          if (it == nA) {
            lo0 = rcp(quad_sum(lo0)); lo1 = rcp(quad_sum(lo1));
            z.m0 = z.m1 = z.l0 = z.l1 = 0.f; z.shifted = 0;
          }
          float s0, s1, d0 = z.m0, d1 = z.m1;
          int pre = z.shifted || (it & 15) == 0;
          float lim = first ? -1.f : SM_LIMIT;
          asm volatile("" : "+r"(relk), "+r"(relv), "+r"(fk), "+r"(fv), "+r"(park), "+r"(parv), "+r"(dq), "+r"(dk), "+r"(pre), "+f"(lim), "+f"(d0), "+f"(d1), "+f"(z.l0), "+f"(z.l1));
          if (it + c.wg > 1) {
            issue_pv<0>(O, P, dv, it != nA + 1 && it != 1, true);
            issue_pv<1>(O, P, dv, 1, true);
            c.turn_end();
          } else if (it) {
            issue_pv<0>(O, P, dv, 0, true);
            wg_commit(); wg_commit();
            c.turn_end();
          } else stage_q2(c, O, P, stg);
          FTA(it * 7 + 3); FTH((it < 3 ? 8 + it * 8 : it * 8 - 88) + 2, it >= 3 && it < 15);
          wg_wait<4>();
          reg_fence(S);
          FTA(it * 7 + 4); FTH((it < 3 ? 8 + it * 8 : it * 8 - 88) + 3, it >= 3 && it < 15);
          if (c.tid < 4) asm volatile("mbarrier.arrive.shared::cluster.b64 _, [%0];" ::"r"(relk) : "memory");
#pragma unroll 1
          for (int pass = 0;; pass++) {
            if (pre) {
              if ((it & 15) == 0) mask_diag(S, dmask);
              if (z.shifted) shift_scores(S, d0, d1);
            }
            float tr[ROT];
            exp_quarter<0, 3>(S, P, tr, s0, s1, sb);
            exp_quarter<1, 2>(S, P, tr, s0, s1, sb);
            exp_quarter<2, 1>(S, P, tr, s0, s1, sb);
            exp_quarter<3, 0>(S, P, tr, s0, s1, sb);
            reg_fence(O);
            if (c.tid < (pass || !it ? 0 : 4)) asm volatile("mbarrier.arrive.shared::cluster.b64 _, [%0];" ::"r"(relv) : "memory");
            const bool ok = mbar_test(fk, park) & mbar_test(fv, parv);
            if (!ok) lim = -1.f;
            FTA(it * 7 + 5); FTH((it < 3 ? 8 + it * 8 : it * 8 - 88) + 4, it >= 3 && it < 15);
            if (!__any_sync(0xffffffffu, !(s0 <= lim && s1 <= lim))) break;
            if (pass) break;
            if (it == nA) {
              store_scaled(O, lo0, lo1, stg + 2 * GR, sb);
              c.staged(1);
            }
            if (!ok) { mbar_wait(fk, park); mbar_wait(fv, parv); }
            if (!soft_unsafe(s0, s1, first)) break;
            soft_fix(S, O, z, first, d0, d1);
            pre = 1;
          }
          z.l0 += s0; z.l1 += s1;
          FTA(it * 7 + 6); FTH((it < 3 ? 8 + it * 8 : it * 8 - 88) + 5, it >= 3 && it < 15);
        }
        FTM(rnd * 8 + 6);
        }
        FTH(48, 0);
        load_dd();
        c.turn_begin();
        FTH(49, 0);
        wg_fence();
        issue_pv<0>(O, P, dv0 + 12 * DG, 1, true);
        issue_pv<1>(O, P, dv0 + 12 * DG, 1, !c.wg);
        c.turn_end();
        z.l0 = rcp(quad_sum(z.l0)); z.l1 = rcp(quad_sum(z.l1));
        if (rnd) c5 = get_ticket();
        wg_wait<0>();
        reg_fence(O); reg_fence(P);
        FTH(50, 0);
        c.release(12, 2);
        store_scaled(O, z.l0, z.l1, stg, sb);
        c.staged(0);
        FTM(rnd * 8 + 7);
        FTH(51, 0);
      }
      TS(3 + rnd * 3);
    }
    conv_tasks(c, p, (cn + 1 - c.wg) >> 1, spare, cch + c.wg * cstep, 2 * cstep, c5, dd0, dkk, warp & 3, lane);
    if (c.wg == 1) c.pf ^= 0x14;
    if (c.wg == (cn & 1)) c.turn_begin();
    TS(7);
    if (!spare) {
      const int rt = 2 * grp + rank, ct = idx;
      float acc[64];
      int g0 = P3G + 2, pg = P3G;
      {
        FTO(0);
        c.wait_full(P3G);
        FTO(1);
        const uint32_t a = dk0 + P3G * DG, b = dm0 + (P3G + 1) * DG;
        wg_fence();
        mma_ss_n128_init<1>(acc, a, b);
#pragma unroll
        for (int k = 1; k < 4; k++) mma_ss_n128<1>(acc, a + k * 2, b + k * 128);
        wg_commit();
      }
#pragma unroll 1
      for (int kb = 1; kb < 64; kb++) {
        FTO(kb * 2);
        c.wait_full(g0);
        if (kb == STR && !c.wg) c.turn_begin();
        FTO(kb * 2 + 1);
        const uint32_t a = dk0 + g0 * DG, b = dm0 + (g0 + 1) * DG;
        wg_fence();
#pragma unroll
        for (int k = 0; k < 4; k++) mma_ss_n128<1>(acc, a + k * 2, b + k * 128);
        wg_commit();
        if (kb < STR) { wg_wait<1>(); c.release(pg, kb <= 59 ? 2 : 0); }
        if (kb == FDUMP_KB) FTDUMP();
        pg = g0;
        g0 = g0 == (kb < XK ? 12 : kb < YK ? 10 : 8) ? (kb == 3 ? 2 : 0) : g0 + 2;
      }
      if (c.wg) c.turn_end();
      cluster_arrive();
      c.wait_full(P3X);
      c.wait_full(P3Y);
      const float g0f = __uint_as_float(lds32(sb + SM_GATE + row * 4)), g1f = __uint_as_float(lds32(sb + SM_GATE + row * 4 + 32));
      const uint32_t gp0 = pack_bf16(g0f, g0f), gp1 = pack_bf16(g1f, g1f);
      const float h0 = 1.f - g0f, h1 = 1.f - g1f;
      const int w = warp & 3;
      const uint32_t xa = stg + P3X * GR;
      const uint32_t ya = sb + P3Y * GR + c.wg * 16384 + ((lane >> 4) * 8 + (lane & 7)) * 128 + (((2 * w + ((lane >> 3) & 1)) ^ (lane & 7)) << 4);
      uint32_t xy[32];
      auto prep = [&](int j0, int j1) {
#pragma unroll
        for (int jj = j0; jj < j1; jj++) {
          uint32_t x[4], y[4];
          asm volatile("ldmatrix.sync.aligned.m8n8.x4.shared.b16 {%0,%1,%2,%3}, [%4];" : "=r"(x[0]), "=r"(x[1]), "=r"(x[2]), "=r"(x[3]) : "r"((xa ^ ((jj & 3) << 5)) + (jj >> 2) * 16384) : "memory");
          asm volatile("ldmatrix.sync.aligned.m8n8.x4.trans.shared.b16 {%0,%1,%2,%3}, [%4];" : "=r"(y[0]), "=r"(y[1]), "=r"(y[2]), "=r"(y[3]) : "r"(ya + jj * 2048) : "memory");
#pragma unroll
          for (int i = 0; i < 4; i++) xy[4 * jj + i] = hmul2(x[i], y[i]);
        }
      };
      prep(0, 4);
      wg_wait<0>();
      reg_fence(acc);
      TS(8);
#pragma unroll
      for (int hf = 0; hf < 2; hf++) {
#pragma unroll
        for (int i = 16 * hf; i < 16 * hf + 16; i++) {
          const float h = (i & 1) ? h1 : h0;
          xy[i] = hfma2((i & 1) ? gp1 : gp0, xy[i], pack_bf16(acc[2 * i] * h, acc[2 * i + 1] * h));
        }
        if (hf) stsm_frag<4, 8>(xy, xa); else stsm_frag<0, 4>(xy, xa);
        fence_async_smem();
        __syncwarp();
        const int r0 = c.wg * 64 + w * 16;
        if (lane == 0) tma2d_store(&p.out, sb + (P3X + hf) * GR + r0 * 128, ct * 128 + hf * 64, rt * 128 + r0);
        if (!hf) prep(4, 8);
      }
      if (lane == 0) asm volatile("cp.async.bulk.commit_group;\ncp.async.bulk.wait_group.read 0;" ::: "memory");
    } else { FTDUMP(); cluster_arrive(); }
    if (lane == 0) mbar_arrive(sb + SM_BAR + B_DONE * 8);
    __syncwarp();
    TS(9);
    cluster_wait();
  }
}

typedef CUresult (*EncFn)(CUtensorMap*, CUtensorMapDataType, cuuint32_t, void*, const cuuint64_t*, const cuuint64_t*, const cuuint32_t*,
                          const cuuint32_t*, CUtensorMapInterleave, CUtensorMapSwizzle, CUtensorMapL2promotion, CUtensorMapFloatOOBfill);

void enc2d(EncFn enc, CUtensorMap* tm, const void* base, uint64_t cols, uint64_t rows, uint32_t bc, uint32_t br) {
  cuuint64_t dims[2] = {cols, rows}; cuuint64_t strides[1] = {cols * 2}; cuuint32_t box[2] = {bc, br}; cuuint32_t es[2] = {1, 1};
  enc(tm, CU_TENSOR_MAP_DATA_TYPE_BFLOAT16, 2, const_cast<void*>(base), dims, strides, box, es, CU_TENSOR_MAP_INTERLEAVE_NONE,
      CU_TENSOR_MAP_SWIZZLE_128B, CU_TENSOR_MAP_L2_PROMOTION_L2_256B, CU_TENSOR_MAP_FLOAT_OOB_FILL_NONE);
}
void enc3d(EncFn enc, CUtensorMap* tm, const void* base, uint64_t K, uint64_t N, uint32_t bk = 64) {
  cuuint64_t dims[3] = {64, K, N / 64}; cuuint64_t strides[2] = {N * 2, 128}; cuuint32_t box[3] = {64, bk, 2}; cuuint32_t es[3] = {1, 1, 1};
  enc(tm, CU_TENSOR_MAP_DATA_TYPE_BFLOAT16, 3, const_cast<void*>(base), dims, strides, box, es, CU_TENSOR_MAP_INTERLEAVE_NONE,
      CU_TENSOR_MAP_SWIZZLE_128B, CU_TENSOR_MAP_L2_PROMOTION_L2_256B, CU_TENSOR_MAP_FLOAT_OOB_FILL_NONE);
}

}

extern "C" void kernel_launch(void* const* d_in, const int* in_sizes, int n_in, void* d_out, int out_size) {
  (void)in_sizes; (void)n_in; (void)out_size;
  typedef const __nv_bfloat16* BP;
  BP xq = (BP)d_in[0], ak = (BP)d_in[1], av = (BP)d_in[2], shk = (BP)d_in[3], ssk = (BP)d_in[4], ssd = (BP)d_in[5];
  BP ckv = (BP)d_in[7], wq = (BP)d_in[8], wuk = (BP)d_in[9], wuv = (BP)d_in[10], wo = (BP)d_in[11], gw = (BP)d_in[12];

  static EncFn enc = nullptr;
  if (!enc) {
    cudaDriverEntryPointQueryResult qr;
    cudaGetDriverEntryPoint("cuTensorMapEncodeTiled", (void**)&enc, cudaEnableDefault, &qr);
    cudaFuncSetAttribute(mega_kernel, cudaFuncAttributeMaxDynamicSharedMemorySize, SMEM_BYTES);
  }
  Params p;
  void* yT = nullptr;
  cudaGetSymbolAddress(&yT, g_yT);
  enc2d(enc, &p.x, xq, DM, SEQ, 64, 128);
  enc2d(enc, &p.c, ckv, DC, SEQ, 64, 128);
  enc3d(enc, &p.wq, wq, DM, NH * HD);
  enc3d(enc, &p.wuk, wuk, DC, NH * HD);
  enc3d(enc, &p.wuv, wuv, DC, NH * HD);
  enc2d(enc, &p.wo, wo, DM, NH * HD, 64, 64);
  enc3d(enc, &p.x3, xq, SEQ, DM, 128);
  enc3d(enc, &p.y3, yT, DM, SEQ, 128);
  enc2d(enc, &p.out, d_out, DM, SEQ, 64, 16);
  {
    void* wp = nullptr;
    cudaGetSymbolAddress(&wp, g_w);
    cuuint64_t dims[3] = {WSTRIDE / 2, DM / 2, 2}; cuuint64_t strides[2] = {2 * WSTRIDE, WSTRIDE}; cuuint32_t box[3] = {16, 32, 2}; cuuint32_t es[3] = {1, 1, 1};
    enc(&p.w, CU_TENSOR_MAP_DATA_TYPE_BFLOAT16, 3, wp, dims, strides, box, es, CU_TENSOR_MAP_INTERLEAVE_NONE,
        CU_TENSOR_MAP_SWIZZLE_32B, CU_TENSOR_MAP_L2_PROMOTION_NONE, CU_TENSOR_MAP_FLOAT_OOB_FILL_NONE);
  }
  p.zero = 0;
  cudaGetSymbolAddress((void**)&p.flags, g_flags);
  for (int i = 0; i < 128; i++) {
    const int tp = i % NSLOT;
    p.pref[i] = tp < 32 ? (tp & 7) * 8 + (tp >> 3) : tp < 60 ? (1 + (tp - 32) % 7) * 8 + 4 + (tp - 32) / 7 : tp < 62 ? tp + 4 : tp - 58;
  }
  p.gate_w = gw; p.ak = ak; p.av = av; p.shk = shk; p.ssk = ssk; p.ssd = ssd; p.wop = wo;

  mega_kernel<<<132, NTHREADS, SMEM_BYTES>>>(p);
}
```

```cpp
#include <cuda_runtime.h>
#include <cuda.h>
#include <cuda_bf16.h>
#include <stdint.h>

namespace {

constexpr int SEQ = 2048, DM = 1024, DC = 512, NH = 32, HD = 128;
constexpr int GR = 16384;
constexpr int NGR = 14;
constexpr int SM_BAR = NGR * GR;
constexpr int SM_GATE = SM_BAR + 512;
constexpr int SM_UST = SM_GATE + 512;
constexpr int SMEM_BYTES = SM_UST + 2048;
constexpr int NTHREADS = 384;
#define SM_LIMIT 1.0995116e12f
#define SM_LOW 9.094947e-13f
#define CNS 104
constexpr int CN_SPARE = CNS, NTICK = 256 - 2 * CN_SPARE;
constexpr int XK = 57, YK = 62;
constexpr int STR = 61;
constexpr int P3G = 6, P3X = 12, P3Y = 10;
constexpr int NMAIN = 128;

constexpr int B_FULL = 0, B_FREE = 14, B_SLOT = 16, B_DONE = 17, B_EMPTY = 18, B_EV = 32, B_TICK = 36;
constexpr int V_SLOT = 37, V_TICK = 38;

__device__ __align__(1024) uint8_t g_kv[2 * 16 * 16 * 32768];
__device__ __align__(1024) uint8_t g_cimg[16 * NH * 32768];
__device__ __align__(1024) __nv_bfloat16 g_yT[DM * SEQ];
__device__ __align__(1024) float g_gate[SEQ];
constexpr int WZ = 256, WPL = WZ + 4096, WBYTES = 2 * WPL + 32, WSTRIDE = 2 * WPL + 128;
__device__ __align__(1024) uint8_t g_w[DM * WSTRIDE];
__device__ __align__(32) unsigned g_flags[96 * 8];
constexpr int F_KV = 0, F_CTX = 16, F_U = 48, F_AD = 56, F_Y = 64, F_GATE = 72, F_EXIT = 73, F_TICK = 74;
constexpr int NSLOT = 66;
#define FLAG(i) (&g_flags[(i) * 8])
#define CLAIMP(i) (p.flags + (i) * 8 + 1)

#define TS(slot)
#define TSW(slot)
#define FTX(i, off)
#define FTDUMP()

#define QFLUSH 4
#define PSL 200
#define US0 500
#define EROT 6
#define RST 2
#define UP0 4
#define UP1 11
#define POL 91
#define WG0 4
#define WG1 UP1
#define KVP 3
#define P3O 32
#define X_DELAY 900
#define X_D2 600
#define P3PF 12
#define P3PF0 5
#define EXPV 1
#define SUMV 0
#define ROT 8
#define KVARR 1
#define KV_ROW(idx, t) (KVARR ? 8 * (t) + 2 * ((idx) & 3) : 2 * (idx))
#define KV_HEAD(idx, t) (KVARR ? (idx) >> 2 : (t))
#define FINE_MODE 0
#define FDUMP_KB 40
#define FINE_RND 1
#define FTA(i) do { if (FINE_MODE == 0) FTX(i, rnd ^ FINE_RND); } while (0)
#define FTG(i) do { if (FINE_MODE == 1) FTX(i, rnd ^ FINE_RND); } while (0)
#define FTM(i) do { if (FINE_MODE == 4) FTX(i, 0); } while (0)
#define FTC(k) do { if (FINE_MODE == 5) FTX((i & 7) * 8 + (k), (i >> 3) ^ FINE_RND); } while (0)
#define FTH(i, off) do { if (FINE_MODE == 6) FTX(i, (c.rnd ^ FINE_RND) | (off)); } while (0)
#define FTS(i)
#define FTSD(i)
#define FTSW(i)
#define FTP(i)
#define FTO(i) do { if (FINE_MODE == 2) FTX(i, 0); } while (0)

__device__ __forceinline__ uint32_t smem_u32(const void* p) { return (uint32_t)__cvta_generic_to_shared(p); }
__device__ __forceinline__ void mbar_init(uint32_t bar, int cnt) { asm volatile("mbarrier.init.shared::cta.b64 [%0], %1;" ::"r"(bar), "r"(cnt) : "memory"); }
__device__ __forceinline__ void mbar_expect_tx(uint32_t bar, uint32_t bytes) { asm volatile("mbarrier.arrive.expect_tx.shared::cta.b64 _, [%0], %1;" ::"r"(bar), "r"(bytes) : "memory"); }
__device__ __forceinline__ void mbar_arrive(uint32_t bar) { asm volatile("mbarrier.arrive.shared::cta.b64 _, [%0];" ::"r"(bar) : "memory"); }
__device__ __forceinline__ void mbar_arrive_cluster(uint32_t bar, uint32_t cta) {
  asm volatile("{\n.reg .b32 r;\nmapa.shared::cluster.u32 r, %0, %1;\nmbarrier.arrive.shared::cluster.b64 _, [r];\n}\n" ::"r"(bar), "r"(cta) : "memory");
}
__device__ __forceinline__ void send_both(uint32_t bar, uint32_t off, uint32_t v) {
#pragma unroll
  for (int r = 0; r < 2; r++)
    asm volatile("{\n.reg .b32 a, b;\nmapa.shared::cluster.u32 a, %0, %1;\nadd.u32 b, a, %3;\nst.async.shared::cluster.mbarrier::complete_tx::bytes.u32 [b], %2, [a];\n}\n"
                 ::"r"(bar), "r"(r), "r"(v), "r"(off) : "memory");
}
__device__ __forceinline__ bool mbar_try(uint32_t bar, uint32_t parity) {
  uint32_t ok;
  asm volatile("{\n.reg .pred p;\nmbarrier.try_wait.parity.shared::cta.b64 p, [%1], %2, 20000;\nselp.u32 %0, 1, 0, p;\n}\n" : "=r"(ok) : "r"(bar), "r"(parity) : "memory");
  return ok;
}
__device__ __forceinline__ bool mbar_test(uint32_t bar, uint32_t parity) {
  uint32_t ok;
  asm volatile("{\n.reg .pred p;\nmbarrier.test_wait.parity.shared::cta.b64 p, [%1], %2;\nselp.u32 %0, 1, 0, p;\n}\n" : "=r"(ok) : "r"(bar), "r"(parity) : "memory");
  return ok;
}
__device__ __forceinline__ void mbar_wait(uint32_t bar, uint32_t parity) {
  asm volatile("{\n.reg .pred p;\nWAIT_LOOP:\nbar.warp.sync -1;\nmbarrier.try_wait.parity.shared::cta.b64 p, [%0], %1;\n@!p bra WAIT_LOOP;\n}\n" ::"r"(bar), "r"(parity) : "memory");
}
__device__ __forceinline__ void mbar_wait1(uint32_t bar, uint32_t parity) {
  asm volatile("{\n.reg .pred p;\nWAIT_LOOP:\nbar.warp.sync -1;\nmbarrier.try_wait.parity.shared::cta.b64 p, [%0], %1, 4000;\n@!p bra WAIT_LOOP;\n}\n" ::"r"(bar), "r"(parity) : "memory");
}
constexpr uint64_t EV_NORMAL = 0x1000000000000000ull, EV_FIRST = 0x12F0000000000000ull;
__device__ __forceinline__ uint32_t ldg_stream(const uint32_t* p) {
  uint32_t r; asm volatile("ld.global.nc.L1::no_allocate.L2::cache_hint.b32 %0, [%1], %2;" : "=r"(r) : "l"(p), "l"(EV_FIRST)); return r;
}
#define TMA_LD "cp.async.bulk.tensor."
#define TMA_MB ".shared::cluster.global.mbarrier::complete_tx::bytes"
__device__ __forceinline__ void tma2d(uint32_t dst, const CUtensorMap* tm, int c0, int c1, uint32_t bar) {
  asm volatile(TMA_LD "2d" TMA_MB " [%0], [%1, {%3, %4}], [%2];" ::"r"(dst), "l"(tm), "r"(bar), "r"(c0), "r"(c1) : "memory");
}
template <bool ONCE = false> __device__ __forceinline__ void tma2d_mc(uint32_t dst, const CUtensorMap* tm, int c0, int c1, uint32_t bar) {
  if (ONCE) asm volatile(TMA_LD "2d" TMA_MB ".multicast::cluster.L2::cache_hint [%0], [%1, {%3, %4}], [%2], %5, %6;"
                         ::"r"(dst), "l"(tm), "r"(bar), "r"(c0), "r"(c1), "h"((uint16_t)3), "l"(EV_FIRST) : "memory");
  else asm volatile(TMA_LD "2d" TMA_MB ".multicast::cluster [%0], [%1, {%3, %4}], [%2], %5;"
                    ::"r"(dst), "l"(tm), "r"(bar), "r"(c0), "r"(c1), "h"((uint16_t)3) : "memory");
}
__device__ __forceinline__ void tma2d_p(uint32_t dst, const CUtensorMap* tm, int c0, int c1, uint32_t bar, bool once) {
  asm volatile(TMA_LD "2d" TMA_MB ".L2::cache_hint [%0], [%1, {%3, %4}], [%2], %5;" ::"r"(dst), "l"(tm), "r"(bar), "r"(c0), "r"(c1), "l"(once ? EV_FIRST : EV_NORMAL) : "memory");
}
__device__ __forceinline__ void tma2d_mc_p(uint32_t dst, const CUtensorMap* tm, int c0, int c1, uint32_t bar, bool once) {
  asm volatile(TMA_LD "2d" TMA_MB ".multicast::cluster.L2::cache_hint [%0], [%1, {%3, %4}], [%2], %5, %6;"
               ::"r"(dst), "l"(tm), "r"(bar), "r"(c0), "r"(c1), "h"((uint16_t)3), "l"(once ? EV_FIRST : EV_NORMAL) : "memory");
}
__device__ __forceinline__ void tma3d_mc_p(uint32_t dst, const CUtensorMap* tm, int c0, int c1, int c2, uint32_t bar, bool once) {
  asm volatile(TMA_LD "3d" TMA_MB ".multicast::cluster.L2::cache_hint [%0], [%1, {%3, %4, %5}], [%2], %6, %7;"
               ::"r"(dst), "l"(tm), "r"(bar), "r"(c0), "r"(c1), "r"(c2), "h"((uint16_t)3), "l"(once ? EV_FIRST : EV_NORMAL) : "memory");
}
template <bool ONCE = false> __device__ __forceinline__ void tma3d(uint32_t dst, const CUtensorMap* tm, int c0, int c1, int c2, uint32_t bar) {
  if (ONCE) asm volatile(TMA_LD "3d" TMA_MB ".L2::cache_hint [%0], [%1, {%3, %4, %5}], [%2], %6;" ::"r"(dst), "l"(tm), "r"(bar), "r"(c0), "r"(c1), "r"(c2), "l"(EV_FIRST) : "memory");
  else
  asm volatile(TMA_LD "3d" TMA_MB " [%0], [%1, {%3, %4, %5}], [%2];" ::"r"(dst), "l"(tm), "r"(bar), "r"(c0), "r"(c1), "r"(c2) : "memory");
}
__device__ __forceinline__ void tma3d_mc(uint32_t dst, const CUtensorMap* tm, int c0, int c1, int c2, uint32_t bar) {
  asm volatile(TMA_LD "3d" TMA_MB ".multicast::cluster [%0], [%1, {%3, %4, %5}], [%2], %6;"
               ::"r"(dst), "l"(tm), "r"(bar), "r"(c0), "r"(c1), "r"(c2), "h"((uint16_t)3) : "memory");
}
template <bool ONCE = false> __device__ __forceinline__ void bulk_g2s(uint32_t dst, const void* src, uint32_t bytes, uint32_t bar) {
  if (ONCE) asm volatile("cp.async.bulk" TMA_MB ".L2::cache_hint [%0], [%1], %2, [%3], %4;" ::"r"(dst), "l"(src), "r"(bytes), "r"(bar), "l"(EV_FIRST) : "memory");
  else asm volatile("cp.async.bulk" TMA_MB " [%0], [%1], %2, [%3];" ::"r"(dst), "l"(src), "r"(bytes), "r"(bar) : "memory");
}
__device__ __forceinline__ void tma2d_store(const CUtensorMap* tm, uint32_t src, int c0, int c1) {
  if (POL & 256) asm volatile("cp.async.bulk.tensor.2d.global.shared::cta.bulk_group.L2::cache_hint [%0, {%2, %3}], [%1], %4;" ::"l"(tm), "r"(src), "r"(c0), "r"(c1), "l"(EV_FIRST) : "memory");
  else asm volatile("cp.async.bulk.tensor.2d.global.shared::cta.bulk_group [%0, {%2, %3}], [%1];" ::"l"(tm), "r"(src), "r"(c0), "r"(c1) : "memory");
}
__device__ __forceinline__ void prefetch_tm(const CUtensorMap* tm) { asm volatile("prefetch.tensormap [%0];" ::"l"(tm) : "memory"); }
__device__ __forceinline__ void wg_fence() { asm volatile("wgmma.fence.sync.aligned;" ::: "memory"); }
__device__ __forceinline__ void wg_commit() { asm volatile("wgmma.commit_group.sync.aligned;" ::: "memory"); }
template <int N> __device__ __forceinline__ void wg_wait() { asm volatile("wgmma.wait_group.sync.aligned %0;" ::"n"(N) : "memory"); }
__device__ __forceinline__ void bar_sync(int id, int n) { asm volatile("bar.sync %0, %1;" ::"r"(id), "r"(n) : "memory"); }
__device__ __forceinline__ void bar_arrive(int id, int n) { asm volatile("bar.arrive %0, %1;" ::"r"(id), "r"(n) : "memory"); }
__device__ __forceinline__ void fence_async_smem() { asm volatile("fence.proxy.async.shared::cta;" ::: "memory"); }
__device__ __forceinline__ void fence_async_all() { asm volatile("fence.proxy.async.global;" ::: "memory"); }
__device__ __forceinline__ uint32_t pack_bf16(float lo, float hi) { uint32_t r; asm("cvt.rn.bf16x2.f32 %0, %1, %2;" : "=r"(r) : "f"(hi), "f"(lo)); return r; }
__device__ __forceinline__ float ex2(float x) { float r; asm("ex2.approx.ftz.f32 %0, %1;" : "=f"(r) : "f"(x)); return r; }
__device__ __forceinline__ float rcp(float x) { float r; asm("rcp.approx.ftz.f32 %0, %1;" : "=f"(r) : "f"(x)); return r; }
__device__ __forceinline__ void flag_wait(const unsigned* f, unsigned target) {
  unsigned v;
  do { asm volatile("ld.acquire.gpu.global.u32 %0, [%1];" : "=r"(v) : "l"(f) : "memory"); } while (__any_sync(0xffffffffu, v < target));
}
__device__ __forceinline__ bool elect() {
  uint32_t r;
  asm volatile("{\n.reg .pred p;\nelect.sync _|p, -1;\nselp.u32 %0, 1, 0, p;\n}\n" : "=r"(r));
  return r;
}
__device__ __forceinline__ void fence_release() { asm volatile("fence.release.gpu;" ::: "memory"); }
__device__ __forceinline__ void flag_add(unsigned* f) { asm volatile("red.relaxed.gpu.global.inc.u32 [%0], 0x7fffffff;" ::"l"(f) : "memory"); }
__device__ __forceinline__ void cluster_arrive() { asm volatile("barrier.cluster.arrive.relaxed.aligned;" ::: "memory"); }
__device__ __forceinline__ void cluster_wait() { asm volatile("barrier.cluster.wait.aligned;" ::: "memory"); }
__device__ __forceinline__ uint32_t hmul2(uint32_t a, uint32_t b) { uint32_t r; asm("mul.rn.bf16x2 %0, %1, %2;" : "=r"(r) : "r"(a), "r"(b)); return r; }
__device__ __forceinline__ uint32_t hadd2(uint32_t a, uint32_t b) { uint32_t r; asm("add.rn.bf16x2 %0, %1, %2;" : "=r"(r) : "r"(a), "r"(b)); return r; }
__device__ __forceinline__ uint32_t hfma2(uint32_t a, uint32_t b, uint32_t c) { uint32_t r; asm("fma.rn.bf16x2 %0, %1, %2, %3;" : "=r"(r) : "r"(a), "r"(b), "r"(c)); return r; }
__device__ __forceinline__ uint32_t lds32(uint32_t a) { uint32_t r; asm volatile("ld.shared.b32 %0, [%1];" : "=r"(r) : "r"(a) : "memory"); return r; }
__device__ __forceinline__ uint4 lds128(uint32_t a) { uint4 r; asm volatile("ld.shared.v4.b32 {%0,%1,%2,%3}, [%4];" : "=r"(r.x), "=r"(r.y), "=r"(r.z), "=r"(r.w) : "r"(a) : "memory"); return r; }
__device__ __forceinline__ uint32_t desc_k(uint32_t addr) { return ((addr & 0x3FFFF) >> 4) | (1u << 16); }
template <int LBO> __device__ __forceinline__ uint32_t desc_mn(uint32_t addr) { return ((addr & 0x3FFFF) >> 4) | ((uint32_t)(LBO >> 4) << 16); }
#define DHI "0x40000040"

#define R8(d, o) "+f"(d[o]), "+f"(d[o + 1]), "+f"(d[o + 2]), "+f"(d[o + 3]), "+f"(d[o + 4]), "+f"(d[o + 5]), "+f"(d[o + 6]), "+f"(d[o + 7])
#define R32(d, o) R8(d, o), R8(d, o + 8), R8(d, o + 16), R8(d, o + 24)
#define R64(d, o) R32(d, o), R32(d, o + 32)
#define L64 "%0,%1,%2,%3,%4,%5,%6,%7,%8,%9,%10,%11,%12,%13,%14,%15,%16,%17,%18,%19,%20,%21,%22,%23,%24,%25,%26,%27,%28,%29,%30,%31," \
            "%32,%33,%34,%35,%36,%37,%38,%39,%40,%41,%42,%43,%44,%45,%46,%47,%48,%49,%50,%51,%52,%53,%54,%55,%56,%57,%58,%59,%60,%61,%62,%63"
#define L128 L64 ",%64,%65,%66,%67,%68,%69,%70,%71,%72,%73,%74,%75,%76,%77,%78,%79,%80,%81,%82,%83,%84,%85,%86,%87,%88,%89,%90,%91,%92,%93,%94,%95," \
            "%96,%97,%98,%99,%100,%101,%102,%103,%104,%105,%106,%107,%108,%109,%110,%111,%112,%113,%114,%115,%116,%117,%118,%119,%120,%121,%122,%123,%124,%125,%126,%127"

template <int TB> __device__ __forceinline__ void mma_ss_n128(float (&d)[64], uint32_t da, uint32_t db) {
  asm volatile("{\n.reg .b64 da, db;\nmov.b64 da, {%64, " DHI "};\nmov.b64 db, {%65, " DHI "};\n"
               "wgmma.mma_async.sync.aligned.m64n128k16.f32.bf16.bf16 {" L64 "}, da, db, 1, 1, 1, 0, %66;\n}\n"
               : R64(d, 0) : "r"(da), "r"(db), "n"(TB));
}
template <int TB> __device__ __forceinline__ void mma_rs_n128(float (&d)[64], uint32_t a0, uint32_t a1, uint32_t a2, uint32_t a3, uint32_t db, int sd) {
  asm volatile("{\n.reg .pred p;\n.reg .b64 db;\nsetp.ne.b32 p, %69, 0;\nmov.b64 db, {%68, " DHI "};\n"
               "wgmma.mma_async.sync.aligned.m64n128k16.f32.bf16.bf16 {" L64 "}, {%64,%65,%66,%67}, db, p, 1, 1, %70;\n}\n"
               : R64(d, 0) : "r"(a0), "r"(a1), "r"(a2), "r"(a3), "r"(db), "r"(sd), "n"(TB));
}
template <int TB> __device__ __forceinline__ void mma_ss_n256(float (&d)[128], uint32_t da, uint32_t db) {
  asm volatile("{\n.reg .b64 da, db;\nmov.b64 da, {%128, " DHI "};\nmov.b64 db, {%129, " DHI "};\n"
               "wgmma.mma_async.sync.aligned.m64n256k16.f32.bf16.bf16 {" L128 "}, da, db, 1, 1, 1, 0, %130;\n}\n"
               : R64(d, 0), R64(d, 64) : "r"(da), "r"(db), "n"(TB));
}
#define W8(d, o) "=f"(d[o]), "=f"(d[o + 1]), "=f"(d[o + 2]), "=f"(d[o + 3]), "=f"(d[o + 4]), "=f"(d[o + 5]), "=f"(d[o + 6]), "=f"(d[o + 7])
#define W32(d, o) W8(d, o), W8(d, o + 8), W8(d, o + 16), W8(d, o + 24)
#define W64(d, o) W32(d, o), W32(d, o + 32)
template <int TB> __device__ __forceinline__ void mma_ss_n128_init(float (&d)[64], uint32_t da, uint32_t db) {
  asm volatile("{\n.reg .b64 da, db;\nmov.b64 da, {%64, " DHI "};\nmov.b64 db, {%65, " DHI "};\n"
               "wgmma.mma_async.sync.aligned.m64n128k16.f32.bf16.bf16 {" L64 "}, da, db, 0, 1, 1, 0, %66;\n}\n"
               : W64(d, 0) : "r"(da), "r"(db), "n"(TB));
}
template <int TB> __device__ __forceinline__ void mma_ss_n256_init(float (&d)[128], uint32_t da, uint32_t db) {
  asm volatile("{\n.reg .b64 da, db;\nmov.b64 da, {%128, " DHI "};\nmov.b64 db, {%129, " DHI "};\n"
               "wgmma.mma_async.sync.aligned.m64n256k16.f32.bf16.bf16 {" L128 "}, da, db, 0, 1, 1, 0, %130;\n}\n"
               : W64(d, 0), W64(d, 64) : "r"(da), "r"(db), "n"(TB));
}
#define L32 "%0,%1,%2,%3,%4,%5,%6,%7,%8,%9,%10,%11,%12,%13,%14,%15,%16,%17,%18,%19,%20,%21,%22,%23,%24,%25,%26,%27,%28,%29,%30,%31"
__device__ __forceinline__ void mma_ss_n64(float (&d)[32], uint32_t da, uint32_t db) {
  asm volatile("{\n.reg .b64 da, db;\nmov.b64 da, {%32, " DHI "};\nmov.b64 db, {%33, " DHI "};\n"
               "wgmma.mma_async.sync.aligned.m64n64k16.f32.bf16.bf16 {" L32 "}, da, db, 1, 1, 1, 0, 0;\n}\n"
               : R32(d, 0) : "r"(da), "r"(db));
}
__device__ __forceinline__ void mma_ss_n64_init(float (&d)[32], uint32_t da, uint32_t db) {
  asm volatile("{\n.reg .b64 da, db;\nmov.b64 da, {%32, " DHI "};\nmov.b64 db, {%33, " DHI "};\n"
               "wgmma.mma_async.sync.aligned.m64n64k16.f32.bf16.bf16 {" L32 "}, da, db, 0, 1, 1, 0, 0;\n}\n"
               : W32(d, 0) : "r"(da), "r"(db));
}
#define L16 "%0,%1,%2,%3,%4,%5,%6,%7,%8,%9,%10,%11,%12,%13,%14,%15"
template <int O, bool INIT> __device__ __forceinline__ void mma_rs_n32(float (&d)[128], uint32_t a0, uint32_t a1, uint32_t a2, uint32_t a3, uint32_t db) {
  if (INIT) asm volatile("{\n.reg .b64 db;\nmov.b64 db, {%20, 0x00000008};\n"
               "wgmma.mma_async.sync.aligned.m64n32k16.f32.bf16.bf16 {" L16 "}, {%16,%17,%18,%19}, db, 0, 1, 1, 0;\n}\n"
               : W8(d, O), W8(d, O + 8) : "r"(a0), "r"(a1), "r"(a2), "r"(a3), "r"(db));
  else asm volatile("{\n.reg .b64 db;\nmov.b64 db, {%20, 0x00000008};\n"
               "wgmma.mma_async.sync.aligned.m64n32k16.f32.bf16.bf16 {" L16 "}, {%16,%17,%18,%19}, db, 1, 1, 1, 0;\n}\n"
               : R8(d, O), R8(d, O + 8) : "r"(a0), "r"(a1), "r"(a2), "r"(a3), "r"(db));
}
template <int S, int J> __device__ __forceinline__ void conv_step(float (&d)[128], const uint32_t (&a)[64], uint32_t db) {
  if constexpr (J >= 0 && J >= (S >> 1)) {
    mma_rs_n32<16 * J, S == 0>(d, a[4 * S], a[4 * S + 1], a[4 * S + 2], a[4 * S + 3], db + (uint32_t)((2 * J - S) * 16));
    conv_step<S, J - 1>(d, a, db);
  }
}
__device__ __forceinline__ void mma_ss_n8(float (&d)[4], uint32_t da, uint32_t db) {
  asm volatile("{\n.reg .b64 da, db;\nmov.b64 da, {%4, " DHI "};\nmov.b64 db, {%5, 0x00000008};\n"
               "wgmma.mma_async.sync.aligned.m64n8k16.f32.bf16.bf16 {%0,%1,%2,%3}, da, db, 1, 1, 1, 0, 0;\n}\n"
               : "+f"(d[0]), "+f"(d[1]), "+f"(d[2]), "+f"(d[3]) : "r"(da), "r"(db));
}
template <int N> __device__ __forceinline__ void reg_fence(float (&d)[N]) {
#pragma unroll
  for (int i = 0; i < N; i++) asm volatile("" : "+f"(d[i])::"memory");
}
template <int N> __device__ __forceinline__ void reg_fence(uint32_t (&d)[N]) {
#pragma unroll
  for (int i = 0; i < N; i++) asm volatile("" : "+r"(d[i])::"memory");
}

struct __align__(64) Params {
  unsigned* flags;
  int zero;
  uint8_t pref[128];
  const __nv_bfloat16 *gate_w, *ak, *av, *shk, *ssk, *ssd, *wop;
  CUtensorMap x, c, wq, wuk, wuv, wo, x3, y3, out, w;
};

template <int O, int N, int M> __device__ __forceinline__ void pack_frag(const float (&acc)[N], uint32_t (&pk)[M]) {
#pragma unroll
  for (int i = 0; i < 32; i++) pk[i] = pack_bf16(acc[O + 2 * i], acc[O + 2 * i + 1]);
}
template <int J0 = 0, int J1 = 8, int M> __device__ __forceinline__ void stsm_frag(const uint32_t (&pk)[M], uint32_t a) {
#pragma unroll
  for (int jj = J0; jj < J1; jj++)
    asm volatile("stmatrix.sync.aligned.m8n8.x4.shared.b16 [%0], {%1,%2,%3,%4};" ::"r"((a ^ ((jj & 3) << 5)) + (jj >> 2) * 16384),
                 "r"(pk[4 * jj]), "r"(pk[4 * jj + 1]), "r"(pk[4 * jj + 2]), "r"(pk[4 * jj + 3]) : "memory");
}

template <int N> __device__ __forceinline__ void store_scaled(const float (&acc)[N], float s0, float s1, uint32_t a, uint32_t never_zero) {
  float t[8];
#pragma unroll
  for (int jj = 0; jj < 8; jj++) {
    float v = acc[8 * jj] * s0;
    if (jj >= RST) {
      v = t[jj - RST];
      asm("{\n.reg .pred p;\nsetp.ne.u32 p, %3, 0;\n@p mul.f32 %0, %1, %2;\n}\n" : "+f"(v) : "f"(acc[8 * jj]), "f"(s0), "r"(never_zero));
    }
    const uint32_t q = pack_bf16(v, acc[8 * jj + 1] * s0);
    t[jj] = __uint_as_float(q);
    asm volatile("stmatrix.sync.aligned.m8n8.x4.shared.b16 [%0], {%1,%2,%3,%4};" ::"r"((a ^ ((jj & 3) << 5)) + (jj >> 2) * 16384), "r"(q),
                 "r"(pack_bf16(acc[8 * jj + 2] * s1, acc[8 * jj + 3] * s1)), "r"(pack_bf16(acc[8 * jj + 4] * s0, acc[8 * jj + 5] * s0)),
                 "r"(pack_bf16(acc[8 * jj + 6] * s1, acc[8 * jj + 7] * s1)) : "memory");
  }
}

struct Cons {
  uint32_t sb;
  uint32_t pf;
  int wg, tid;
  __device__ __forceinline__ void wait_full(int g) { mbar_wait(sb + SM_BAR + (B_FULL + g) * 8, (pf >> g) & 1); pf ^= 1u << g; }
  uint32_t relb;
  __device__ __forceinline__ void release(int g, int n) {
    if (tid < 2 * n) asm volatile("mbarrier.arrive.shared::cluster.b64 _, [%0];" ::"r"(relb + g * 8) : "memory");
  }
  __device__ __forceinline__ void turn_begin() { bar_sync(1 + wg, 256); }
  __device__ __forceinline__ void turn_end() { bar_arrive(2 - wg, 256); }
  __device__ __forceinline__ void staged(int e) { __syncwarp(); if ((tid & 31) == 0) mbar_arrive(sb + SM_BAR + (B_EV + 2 * e + wg) * 8); }
  int zero;
  int rnd;
  uint32_t pfree;
  __device__ __forceinline__ void wait_stage_free() { mbar_wait(sb + SM_BAR + (B_FREE + wg) * 8, pfree); pfree ^= 1; }
  __device__ __forceinline__ bool try_full(int g) { return mbar_test(sb + SM_BAR + (B_FULL + g) * 8, (pf >> g) & 1); }
};

constexpr float SM_C = 0.08838834764831845f * 1.4426950408889634f;
struct SoftState { float m0, m1, l0, l1; int shifted; };
__device__ __forceinline__ void ex2_rot(float& t, float s, uint32_t never_zero) {
  asm("{\n.reg .pred p;\nsetp.ne.u32 p, %2, 0;\n@p ex2.approx.ftz.f32 %0, %1;\n}\n" : "+f"(t) : "f"(s), "r"(never_zero));
}
__device__ __forceinline__ void pin(float a, uint32_t never_zero) {
  asm volatile("{\n.reg .pred p;\nsetp.eq.u32 p, %1, 0;\n@p st.shared.f32 [%1], %0;\n}\n" ::"f"(a), "r"(never_zero) : "memory");
}
template <int O, int N> __device__ __forceinline__ void reg_fence_part(uint32_t (&d)[32]) {
#pragma unroll
  for (int i = O; i < O + N; i++) asm volatile("" : "+r"(d[i])::"memory");
}
template <int Q, int W, int N> __device__ __forceinline__ void exp_quarter(const float (&S)[N], uint32_t (&P)[32], float (&t)[ROT], float& s0, float& s1, uint32_t nz) {
#pragma unroll
  for (int i = 8 * Q; i < 8 * Q + 8; i++) {
    float& a = t[(2 * i) % ROT];
    float& b = t[(2 * i + 1) % ROT];
    if (2 * i < ROT) { a = ex2(S[2 * i]); b = ex2(S[2 * i + 1]); }
    else { ex2_rot(a, S[2 * i], nz); ex2_rot(b, S[2 * i + 1], nz); }
    if (i < 2) { if (i) s1 = a + b; else s0 = a + b; }
    else if (SUMV == 0) { if (i & 1) { s1 += a; s1 += b; } else { s0 += a; s0 += b; } }
    else { if (i & 1) s1 += a + b; else s0 += a + b; }
    if (i == 8 * Q) { pin(EXPV == 1 && Q ? s1 : s0, nz); wg_wait<W>(); reg_fence_part<8 * Q, 8>(P); }
    P[i] = pack_bf16(a, b);
  }
}
template <int N> __device__ __forceinline__ void shift_scores(float (&S)[N], float d0, float d1) {
#pragma unroll
  for (int i = 0; i < N; i++) S[i] -= (i & 2) ? d1 : d0;
}
__device__ __forceinline__ bool soft_high(float s0, float s1, float lim = SM_LIMIT) { return s0 > lim || s1 > lim; }
__device__ __forceinline__ bool soft_unsafe(float s0, float s1, bool first) {
  uint32_t b0 = __ballot_sync(0xffffffffu, s0 >= SM_LOW), b1 = __ballot_sync(0xffffffffu, s1 >= SM_LOW);
  b0 |= b0 >> 1; b0 |= b0 >> 2; b1 |= b1 >> 1; b1 |= b1 >> 2;
  return __any_sync(0xffffffffu, soft_high(s0, s1)) || (first && (b0 & b1 & 0x11111111u) != 0x11111111u);
}
template <int N> __device__ __forceinline__ void soft_fix(const float (&S)[N], float (&O)[64], SoftState& z, bool first, float& d0, float& d1) {
  d0 = d1 = first ? -INFINITY : 0.f;
#pragma unroll
  for (int j = 0; j < N / 4; j++) { d0 = fmaxf(d0, fmaxf(S[4 * j], S[4 * j + 1])); d1 = fmaxf(d1, fmaxf(S[4 * j + 2], S[4 * j + 3])); }
  d0 = fmaxf(d0, __shfl_xor_sync(0xffffffffu, d0, 1)); d1 = fmaxf(d1, __shfl_xor_sync(0xffffffffu, d1, 1));
  d0 = fmaxf(d0, __shfl_xor_sync(0xffffffffu, d0, 2)); d1 = fmaxf(d1, __shfl_xor_sync(0xffffffffu, d1, 2));
  const float sc0 = ex2(-fmaxf(d0, 0.f)), sc1 = ex2(-fmaxf(d1, 0.f));
  z.m0 += d0; z.m1 += d1; z.l0 *= sc0; z.l1 *= sc1; z.shifted = 1;
#pragma unroll
  for (int j = 0; j < 16; j++) { O[4 * j] *= sc0; O[4 * j + 1] *= sc0; O[4 * j + 2] *= sc1; O[4 * j + 3] *= sc1; }
}
template <int N> __device__ __forceinline__ void mask_diag(float (&S)[N], float nd) {
  asm volatile("" : "+f"(nd));
#pragma unroll
  for (int i = 0; i < 32; i++) {
    const float beyond = __saturatef(nd + (float)(8 * (i >> 2) + (i & 1) - 4 * (i & 2)));
    S[N - 32 + i] = fmaf(beyond, -3.0e38f, S[N - 32 + i]);
  }
}
__device__ __forceinline__ float quad_sum(float v) {
  v += __shfl_xor_sync(0xffffffffu, v, 1);
  v += __shfl_xor_sync(0xffffffffu, v, 2);
  return v;
}
__device__ __forceinline__ void issue_qk(float (&S)[64], uint32_t dq, uint32_t dk) {
  mma_ss_n128_init<0>(S, dq, dk);
#pragma unroll
  for (int s = 1; s < 8; s++) mma_ss_n128<0>(S, dq + (s >> 2) * 1024 + (s & 3) * 2, dk + (s >> 2) * 1024 + (s & 3) * 2);
}
__device__ __forceinline__ void issue_qk(float (&S)[32], uint32_t dq, uint32_t dk) {
  mma_ss_n64_init(S, dq, dk);
#pragma unroll
  for (int s = 1; s < 8; s++) mma_ss_n64(S, dq + (s >> 2) * 1024 + (s & 3) * 2, dk + (s >> 2) * 1024 + (s & 3) * 2);
}
template <int H> __device__ __forceinline__ void issue_pv(float (&O)[64], const uint32_t (&P)[32], uint32_t dv, int acc, bool on) {
  if (on) {
#pragma unroll
    for (int s = 4 * H; s < 4 * H + 4; s++) {
      mma_rs_n128<1>(O, P[4 * s], P[4 * s + 1], P[4 * s + 2], P[4 * s + 3], dv + s * 128, s != 0 ? 1 : acc);
      if (s & 1) wg_commit();
    }
  } else { wg_commit(); wg_commit(); }
}
constexpr uint32_t DG = GR >> 4;
__device__ __forceinline__ void stage_q2(Cons& c, const float (&O)[64], uint32_t (&P)[32], uint32_t stg) {
  wg_commit(); wg_commit(); wg_commit(); wg_commit();
  c.turn_end();
  pack_frag<0>(O, P);
  stsm_frag(P, stg);
  fence_async_smem();
}
__device__ __forceinline__ void attn_half(Cons& c, float (&O)[64], uint32_t (&P)[32], SoftState& z, uint32_t dk0, uint32_t dkk, uint32_t dv0, float dmask, int last) {
  float S[32];
  FTH(8 + last * 32, 0);
  c.turn_begin();
  FTH(9 + last * 32, 0);
  wg_fence();
  issue_qk(S, dk0 + (last ? 0 : 2 * DG), dkk + (last ? 8 : 4) * DG);
  wg_commit();
  issue_pv<0>(O, P, dv0 + 10 * DG, 1, last);
  issue_pv<1>(O, P, dv0 + 10 * DG, 1, last);
  c.turn_end();
  c.wait_full(last ? 12 : 6);
  FTH(10 + last * 32, 0);
  wg_wait<4>();
  reg_fence(S);
  FTH(11 + last * 32, 0);
  c.release(last ? 8 : 4, 2);
  mask_diag(S, dmask);
  float s0, s1, d0 = z.m0, d1 = z.m1;
#pragma unroll 1
  for (int pass = 0;; pass++) {
    if (z.shifted) shift_scores(S, d0, d1);
    float tr[ROT];
    exp_quarter<0, 3>(S, P, tr, s0, s1, c.sb);
    exp_quarter<1, 2>(S, P, tr, s0, s1, c.sb);
    pin(s1, c.sb); wg_wait<0>(); reg_fence_part<16, 16>(P); reg_fence(O);
    if (!soft_unsafe(s0, s1, !last) || pass) break;
    soft_fix(S, O, z, !last, d0, d1);
  }
  FTH(12 + last * 32, 0);
  z.l0 += s0; z.l1 += s1;
  c.release(10, last ? 2 : 0);
  if (!last) c.wait_full(8);
  FTH(13 + last * 32, 0);
}

template <int V> struct IC { static constexpr int value = V; };
__device__ __forceinline__ int conv_next(int g, bool spare) { return g >= NGR - 2 ? g - (NGR - 4) : !spare && g == 4 ? 1 : g + 2; }
__device__ __forceinline__ void conv_final(uint32_t rb, uint32_t yb, bool on) {
  const uint4 q0 = lds128(rb), q1 = lds128(rb + 4096), q2 = lds128(rb + 8192), q3 = lds128(rb + 12288);
  auto fin = [&](uint32_t x0, uint32_t x1, uint32_t x2, uint32_t x3) { return hadd2(hadd2(x0, x1), hadd2(x2, x3)); };
  asm volatile("{\n.reg .pred p;\nsetp.ne.b32 p, %5, 0;\n@p st.shared.v4.b32 [%0], {%1,%2,%3,%4};\n}\n" ::"r"(yb), "r"(fin(q0.x, q1.x, q2.x, q3.x)),
               "r"(fin(q0.y, q1.y, q2.y, q3.y)), "r"(fin(q0.z, q1.z, q2.z, q3.z)), "r"(fin(q0.w, q1.w, q2.w, q3.w)), "r"((int)on) : "memory");
}
__device__ __forceinline__ void conv_tasks(Cons& c, const Params& p, int ntask, bool spare, int ch, int chstep, int c5, uint32_t dd, uint32_t dkk, int w, int lane) {
  const uint32_t sb = c.sb;
  int g = 2 + c.wg;
  uint32_t rb = sb + g * GR;
  const uint32_t yb = sb + c.wg * 8192 + c.tid * 16;
  const int gt = 8 * w + (lane >> 2) + (lane & 3);
  uint32_t a[64], hb;
  auto lda = [&](int s) {
    a[4 * s] = lds32(hb + s * 256); a[4 * s + 1] = lds32(hb + s * 256 + 128);
    a[4 * s + 2] = lds32(hb + s * 256 + 16); a[4 * s + 3] = lds32(hb + s * 256 + 144);
  };
  auto first_a = [&]() {
    hb = sb + g * GR + WBYTES - 28 + gt * 4;
    lda(0); lda(15);
  };
  c.wait_full(g);
  first_a();
#pragma unroll 1
  for (int i = 0; i < ntask; i++) {
    const uint32_t base = sb + g * GR;
    FTC(0);
    lda(1); lda(14);
    a[0] = hadd2(a[0], gt == 7 ? dd : 0u); a[2] = hadd2(a[2], gt == 3 ? dd : 0u);
    float acc[128];
    const uint32_t db = dkk + ((WPL / 16 - 1) << 16) + g * DG + WZ / 16;
    FTC(2);
    c.turn_begin();
    FTC(3);
    auto pair = [&](auto kc) {
      constexpr int k = decltype(kc)::value;
      if (k < 7) wg_fence();
      if (k == 6) c.turn_end();
      conv_step<k, 7>(acc, a, db);
      conv_step<15 - k, 7>(acc, a, db);
      if (k < 6) { lda(k + 2); lda(13 - k); }
      if (k == 0) conv_final(rb, yb, i > 0);
      if (k == 1) {
        conv_final(rb + 2048, yb + 2048, i > 0);
        __syncwarp();
        if (lane == 0 && i > 0) mbar_arrive(sb + SM_BAR + (B_EV + c.wg) * 8);
      }
      if (k == 6) dd = __bfloat16_as_ushort(p.ssd[(ch + chstep + (i == 1 ? c5 : 0)) & (DM - 1)]);
    };
    pair(IC<0>()); pair(IC<1>()); pair(IC<2>()); pair(IC<3>()); pair(IC<4>()); pair(IC<5>()); pair(IC<6>()); pair(IC<7>());
    wg_commit();
    FTC(4);
    g = conv_next(g, spare);
    ch += chstep;
    rb = base + c.tid * 16;
    if (i + 1 < ntask) c.wait_full(g);
    const bool fr = mbar_test(sb + SM_BAR + (B_FREE + c.wg) * 8, c.pfree);
    wg_wait<0>();
    reg_fence(acc);
    reg_fence(a);
    bar_sync(3 + c.wg, 128);
    FTC(5);
    first_a();
    const int tw = (lane & 3) + w;
    const uint32_t xb = base + w * 4096 + tw * 32 + (lane >> 2) * 4;
    [[maybe_unused]] float t0[EROT + 1];
#pragma unroll
    for (int j = 0; j < 32; j++) {
      uint32_t ad = xb + j * 128;
      float v0 = acc[4 * j], v1 = acc[4 * j + 1];
      if (EROT && j > EROT) {
        v0 = t0[j % (EROT + 1)];
        asm("{\n.reg .pred p;\nsetp.ne.u32 p, %3, 0;\n@p add.f32 %0, %1, %2;\n}\n" : "+f"(v0) : "f"(acc[4 * j]), "f"(acc[j > 0 ? 4 * j - 2 : 0]), "r"(sb));
      } else if (j > 0) v0 += acc[j > 0 ? 4 * j - 2 : 0];
      if (j > 0) v1 += acc[j > 0 ? 4 * j - 1 : 0];
      uint32_t v = pack_bf16(v0, v1);
      t0[j % (EROT + 1)] = __uint_as_float(v);
      if (j == 31 && tw >= 4) { v = 0; ad -= 4096; }
      asm volatile("st.shared.b32 [%0], %1;" ::"r"(ad), "r"(v) : "memory");
    }
    if (!fr) c.wait_stage_free(); else c.pfree ^= 1;
    FTC(6);
  }
  bar_sync(3 + c.wg, 128);
  conv_final(rb, yb, true);
  conv_final(rb + 2048, yb + 2048, true);
  c.staged(0);
}

__global__ void __cluster_dims__(2, 1, 1) __launch_bounds__(NTHREADS, 1) mega_kernel(const __grid_constant__ Params p) {
  extern __shared__ __align__(1024) uint8_t smem_raw[];
  FTS(0);
  const uint32_t sb = smem_u32(smem_raw);
  if (threadIdx.x - 64 < 32) { prefetch_tm(&p.c); prefetch_tm(&p.wuk + (blockIdx.x & 1)); }
  const int wgi = __shfl_sync(0xffffffffu, threadIdx.x >> 7, 0);
  const int warp = __shfl_sync(0xffffffffu, threadIdx.x >> 5, 0);
  const uint32_t rank = blockIdx.x & 1;
  int slot;
  {
    uint32_t smid; asm volatile("mov.u32 %0, %smid;" : "=r"(smid));
    slot = p.pref[((smid >> 1) + (threadIdx.x & (smid >> 16))) & 127];
  }
  if (warp >= 3) {
    if (elect()) {
#pragma unroll
      for (int k = 0; k < 4; k++) mbar_init(sb + SM_BAR + ((warp - 3) * 4 + k) * 8, k == 1 && warp == 7 ? 11 : warp < (k ? 7 : 8) ? 1 : 4);
      if (warp == 7) { mbar_init(sb + SM_BAR + B_TICK * 8, 1); mbar_expect_tx(sb + SM_BAR + B_SLOT * 8, 8); mbar_expect_tx(sb + SM_BAR + B_TICK * 8, 4); }
      asm volatile("fence.mbarrier_init.release.cluster;" ::: "memory");
    }
    __syncwarp();
  }
  FTS(1);
  cluster_arrive();
  slot = __shfl_sync(0xffffffffu, slot, 0);
  const int pref = slot;
  if (warp < 4) {
    asm volatile("setmaxnreg.dec.sync.aligned.u32 40;");
    if (warp == 1 + 4 * rank) {
      unsigned taken = threadIdx.x == 32;
#pragma unroll 1
      for (int n = 0; n < NSLOT; n++) {
        asm volatile("{\n.reg .pred p;\nsetp.ne.b32 p, %0, 0;\n@p atom.relaxed.gpu.global.exch.b32 %0, [%1], 1;\n}\n" : "+r"(taken) : "l"(CLAIMP(slot)) : "memory");
        if (!__any_sync(0xffffffffu, taken)) break;
        slot = slot == NSLOT - 1 ? 0 : slot + 1;
      }
    }
    cluster_wait();
    if (threadIdx.x == 32) {
      send_both(sb + SM_BAR + B_SLOT * 8, (V_SLOT - B_SLOT) * 8 + rank * 4, slot | pref << 8);
    }
    if (warp == 2) {
#pragma unroll 1
      for (int kk = 0; kk < 4; kk++) {
        const int g0 = 2 + 3 * kk;
        const uint32_t fb = sb + SM_BAR + (B_FULL + g0) * 8;
        if (elect()) {
          FTSW(kk);
          mbar_expect_tx(fb, 3 * GR);
          tma2d(sb + g0 * GR, &p.c, kk * 64, (KV_ROW(pref & 7, 0) + rank) * 128, fb);
          tma3d_mc(sb + (g0 + 1 + rank) * GR, rank ? &p.wuv : &p.wuk, 0, kk * 64, ((pref & 56) >> 1) + 2 * KV_HEAD(pref & 7, 0), fb);
        }
        if (kk < 3) {
          uint32_t c0, c1;
          asm volatile("mov.u32 %0, %clock;" : "=r"(c0));
          do asm volatile("mov.u32 %0, %clock;" : "=r"(c1)); while (c1 - c0 < (kk ? X_D2 : X_DELAY));
        }
      }
      FTSW(4);
      prefetch_tm(&p.x); prefetch_tm(&p.wq);
    }
  }
  int grp, idx, lb;
  int cn, cch, cstep;
  bool spare, redo;
  auto get_slot = [&]() {
    mbar_wait(sb + SM_BAR + B_SLOT * 8, 0);
    const uint32_t sv0 = __shfl_sync(0xffffffffu, lds32(sb + SM_BAR + V_SLOT * 8), 0), sv1 = __shfl_sync(0xffffffffu, lds32(sb + SM_BAR + V_SLOT * 8 + 4), 0);
    grp = (sv0 & 255) >> 3; idx = sv0 & 7; lb = (sv0 & 255) * 2 + rank;
    spare = grp == 8; redo = spare || sv0 != sv1;
    cn = CN_SPARE; cch = spare ? lb - NMAIN : 4 * CN_SPARE + 4 * lb; cstep = spare ? 4 : 1;
    if (FINE_MODE != 7) TS(0);
  };
  auto get_ticket = [&]() {
    mbar_wait(sb + SM_BAR + B_TICK * 8, 0);
    const int tk = __shfl_sync(0xffffffffu, lds32(sb + SM_BAR + V_TICK * 8), 0);
    cn = tk < NTICK ? 5 : 4;
    return 4 * NMAIN - 4 * lb - 4 + 2 * tk + rank;
  };

  if (wgi == 0) {
    asm volatile("setmaxnreg.dec.sync.aligned.u32 40;");
    const int lane = threadIdx.x & 31;
    cluster_arrive();
    get_slot();
    uint32_t pe = 0;
    auto acquire = [&](int g, int n, uint32_t m) {
      int i = g;
#pragma unroll 1
      do mbar_wait1(sb + SM_BAR + (B_EMPTY + i) * 8, (pe >> i) & 1); while (++i < g + n);
      pe ^= m << g;
    };
    if (warp == 3) {
      if (!spare) {
        const int s0 = lb * 16;
#pragma unroll 1
        for (int cg = 0; cg < 16; cg++) {
          if (cg == UP0 || cg == UP1) {
#pragma unroll 1
            for (int n = 0; n < 20 && !__any_sync(0xffffffffu, mbar_try(sb + SM_BAR + B_SLOT * 8, cg == UP0)); n++);
          } else if (cg < UP0) __nanosleep(US0);
          if (cg == UP1 && lane == rank * 32) send_both(sb + SM_BAR + B_TICK * 8, (V_TICK - B_TICK) * 8, atomicInc(FLAG(F_TICK), 0x7fffffffu));
          const int ch = cg * 64 + 2 * lane;
          const uint32_t* kp = reinterpret_cast<const uint32_t*>(p.ak + (size_t)s0 * DM + ch);
          const uint32_t* vp = reinterpret_cast<const uint32_t*>(p.av + (size_t)s0 * DM + ch);
          const uint4 sw = __ldg(reinterpret_cast<const uint4*>(p.shk + ch * 4));
          uint32_t k3 = 0, k2 = 0, k1 = 0, k0 = 0, up = 0;
          if (lb > 0) { k3 = ldg_stream(kp - 4 * 512); k2 = ldg_stream(kp - 3 * 512); k1 = ldg_stream(kp - 2 * 512); k0 = ldg_stream(kp - 512); up = ldg_stream(vp - 512); }
          const uint32_t w0 = __byte_perm(sw.x, sw.z, 0x5410), w1 = __byte_perm(sw.x, sw.z, 0x7632);
          const uint32_t w2 = __byte_perm(sw.y, sw.w, 0x5410), w3 = __byte_perm(sw.y, sw.w, 0x7632);
          up = hmul2(hfma2(k0, w0, hfma2(k1, w1, hfma2(k2, w2, hmul2(k3, w3)))), up);
#pragma unroll 1
          for (int hb = 0; hb < 2; hb++) {
            uint32_t kk[8], u[8];
#pragma unroll
            for (int r = 0; r < 8; r++) { kk[r] = ldg_stream(kp + r * 512); u[r] = ldg_stream(vp + r * 512); }
#pragma unroll
            for (int r = 0; r < 8; r++) {
              k3 = k2; k2 = k1; k1 = k0; k0 = kk[r];
              u[r] = hmul2(hfma2(k0, w0, hfma2(k1, w1, hfma2(k2, w2, hmul2(k3, w3)))), u[r]);
            }
            if (lane == 0) asm volatile("cp.async.bulk.wait_group.read 0;" ::: "memory");
            __syncwarp();
            const uint32_t dst = sb + SM_UST + lane * 32 + ((lane & 4) << 2);
#pragma unroll
            for (int cc = 0; cc < 2; cc++) {
              const uint32_t sel = cc ? 0x7632 : 0x5410;
              asm volatile("st.shared.v4.b32 [%0], {%1,%2,%3,%4};" ::"r"(dst + cc * 1024), "r"(__byte_perm(u[6], u[5], sel)), "r"(__byte_perm(u[4], u[3], sel)),
                           "r"(__byte_perm(u[2], u[1], sel)), "r"(__byte_perm(u[0], up, sel)) : "memory");
              asm volatile("st.shared.v4.b32 [%0], {%1,%2,%3,%4};" ::"r"((dst ^ 16) + cc * 1024), "r"(__byte_perm(u[7], u[6], sel)), "r"(__byte_perm(u[5], u[4], sel)),
                           "r"(__byte_perm(u[3], u[2], sel)), "r"(__byte_perm(u[1], u[0], sel)) : "memory");
            }
            fence_async_smem();
            __syncwarp();
            if (lane == 0) {
              if (POL & 64) asm volatile("cp.async.bulk.tensor.3d.global.shared::cta.bulk_group.L2::cache_hint [%0, {%2, %3, %4}], [%1], %5;\ncp.async.bulk.commit_group;"
                           ::"l"(&p.w), "r"(sb + SM_UST), "r"(WZ / 2 + lb * 16 + (hb ^ 1) * (WPL / 2)), "r"(cg * 32), "r"(0), "l"(cg >= WG0 && cg < WG1 ? EV_FIRST : EV_NORMAL) : "memory");
              else
              asm volatile("cp.async.bulk.tensor.3d.global.shared::cta.bulk_group [%0, {%2, %3, %4}], [%1];\ncp.async.bulk.commit_group;"
                           ::"l"(&p.w), "r"(sb + SM_UST), "r"(WZ / 2 + lb * 16 + (hb ^ 1) * (WPL / 2)), "r"(cg * 32), "r"(0) : "memory");
            }
            up = u[7];
            kp += 8 * 512; vp += 8 * 512;
          }
          if ((cg & (cg + 1)) == 0 && lane == 0) {
            asm volatile("cp.async.bulk.wait_group 0;" ::: "memory");
            fence_release();
            flag_add(FLAG(F_U + 32 - __clz(cg)));
          }
          TSW(10 + cg);
        }
        prefetch_tm(&p.wo); prefetch_tm(&p.x3); prefetch_tm(&p.y3); prefetch_tm(&p.out);
        if (P3PF) {
          const int rt = 2 * grp + rank;
          unsigned v;
          asm volatile("ld.acquire.gpu.global.u32 %0, [%1];" : "=r"(v) : "l"(FLAG(F_CTX + rt * 2)) : "memory");
#pragma unroll 1
          for (int kb = P3PF0; kb < P3PF0 + P3PF; kb++) {
            const uint8_t* a = lane < 16 ? g_cimg + (unsigned)((rt * 64 + kb) * GR + (idx * 16 + lane) * 128) : (const uint8_t*)p.wop + (unsigned)((kb ^ P3O) * 64 * DM * 2 + (lb * 8 + (lane & 7)) * 128);
            if (lane < 24 && (P3O ? lane >= 16 : v == 32)) asm volatile("prefetch.global.L2 [%0];" ::"l"(a));
          }
        }
      } else {
#pragma unroll 1
        for (int i = 0, g = 2; i < 32; i++) {
          acquire(g, 2, 3);
          if (elect()) {
            const uint32_t fb = sb + SM_BAR + (B_FULL + g) * 8;
            if (i == 0) { mbar_expect_tx(fb - 8, 2048); bulk_g2s(sb + GR, p.gate_w, 2048, fb - 8); }
            mbar_expect_tx(fb, 2 * GR);
            tma3d(sb + g * GR, &p.x3, 0, (lb - NMAIN) * 512 + (i >> 3) * 128, (i & 7) * 2, fb);
          }
          g = g == NGR - 2 ? 2 : g + 2;
        }
        bar_arrive(5, 64);
      }
      unsigned long long t0, t1;
      asm volatile("mov.u64 %0, %globaltimer;" : "=l"(t0));
      auto check = [&]() {
        asm volatile("mov.u64 %0, %globaltimer;" : "=l"(t1));
        if (t1 - t0 > 2000000000ull) __trap();
      };
      if (!spare) {
        unsigned v;
        do {
          __nanosleep(PSL);
          check();
          asm volatile("ld.acquire.gpu.global.u32 %0, [%1];" : "=r"(v) : "l"(FLAG(lane & 1 ? F_Y + idx : F_GATE)) : "memory");
        } while (__any_sync(0xffffffffu, v < (lane & 1 ? 128 : 32)));
        __syncwarp();
        if (lane == 0) mbar_arrive(sb + SM_BAR + B_SLOT * 8);
      }
      if (lane == 0) {
        while (!mbar_try(sb + SM_BAR + B_DONE * 8, 0)) check();
      }
    } else if (warp != 0) {
      const int w = warp - 1;
      int ne = 12 + (CN_SPARE + 1 - w) / 2, c5 = 0;
      uint32_t p0 = 0;
      int cg = 2 + w, ch = cch + w * cstep;
#pragma unroll 1
      for (int e = spare ? 12 : 0; e < ne; e++) {
        const int rnd = e >= 6, k = e - 6 * rnd, rt = k == 4 ? idx : 15 - idx;
        uint8_t* dst = k < 4 ? g_kv + (size_t)(((k & 1) * 16 + 2 * grp + KV_HEAD(idx, k >> 1)) * 16 + KV_ROW(idx, k >> 1) + rank) * 32768 + w * 8192
                     : k < 6 ? g_cimg + (size_t)(rt * 32 + 16 * rnd + 2 * grp + rank) * 32768 + (w ^ (k & 1)) * 8192
                             : reinterpret_cast<uint8_t*>(g_yT + (size_t)ch * SEQ);
        const uint32_t src = sb + w * 8192 + (k == 4 ? 2 * GR : 0);
        if (e == 11) { c5 = get_ticket(); ne = 12 + ((cn + 1 - w) >> 1); }
        if (e == 6) flag_wait(FLAG(F_AD + grp), 32);
        mbar_wait1(sb + SM_BAR + (B_EV + (k == 4 ? 2 : 0) + w) * 8, k == 4 ? rnd : p0);
        if (k != 4) p0 ^= 1;
        if (lane < 4 && k >= 6 && (!spare || e < ne - 6)) mbar_arrive_cluster(sb + SM_BAR + (B_EMPTY + cg) * 8, lane & 1);
        fence_async_smem();
        if (elect()) {
          const uint32_t cs = k >= 6 ? 4096 : 1024;
#pragma unroll 1
          for (uint32_t i = 0; i < (k >= 6 ? 4096 : 16384); i += cs) {
            const uint32_t o = i + (i & 8192);
            if (POL & (8 | 16 | 32)) asm volatile("cp.async.bulk.global.shared::cta.bulk_group.L2::cache_hint [%0], [%1], %2, %3;" ::"l"(dst + o), "r"(src + o), "r"(cs),
                "l"(((POL & 8) && (e == 4 || e == 5)) || ((POL & 16) && spare) || ((POL & 32) && (e == 10 || e == 11)) ? EV_FIRST : EV_NORMAL) : "memory");
            else
            asm volatile("cp.async.bulk.global.shared::cta.bulk_group [%0], [%1], %2;" ::"l"(dst + o), "r"(src + o), "r"(cs) : "memory");
            asm volatile("cp.async.bulk.commit_group;\ncp.async.bulk.wait_group.read 1;" ::: "memory");
          }
          asm volatile("cp.async.bulk.wait_group 0;" ::: "memory");
          if (k != 4) mbar_arrive(sb + SM_BAR + (B_FREE + w) * 8);
        }
        __syncwarp();
        if (lane < (k == 4 ? 4 : e == 11 || (e == ne - 1 && !spare) ? 2 : 0))
          mbar_arrive_cluster(sb + SM_BAR + (B_EMPTY + (k == 4 ? 2 : e == 11) + (lane >> 1)) * 8, lane & 1);
        if (k >= 3) {
          fence_release();
          const unsigned fl = k == 3 ? F_KV + rnd * 8 + grp : k < 6 ? F_CTX + rt * 2 + rnd : F_Y + ((unsigned)ch >> 7);
          if (lane <= (e == 5)) flag_add(FLAG(lane ? F_AD + grp : fl));
        }
        if (k >= 6) { cg = conv_next(cg, spare); ch += 2 * cstep + (k == 7 ? c5 : 0); }
      }
      if (lane == 0) mbar_arrive(sb + SM_BAR + B_DONE * 8);
    } else {
#pragma unroll 1
      for (int rnd = 0; rnd < (spare ? 0 : 2); rnd++) {
        const int hp = 16 * rnd + 2 * grp, head = hp + rank;
#pragma unroll 1
        for (int kk = rnd || redo ? 0 : 4; kk < 32; kk++) {
          const int g0 = 2 + 3 * (kk & 3);
          acquire(g0, kk < 4 ? 3 : 1, 7);
          if (elect()) {
            const uint32_t fb = sb + SM_BAR + (B_FULL + g0) * 8;
            mbar_expect_tx(fb, 3 * GR);
            if (kk < 16) {
              if (POL & 1) tma2d_p(sb + g0 * GR, &p.c, (kk & 7) * 64, (KV_ROW(idx, kk >> 3) + rank) * 128, fb, rnd);
              else tma2d(sb + g0 * GR, &p.c, (kk & 7) * 64, (KV_ROW(idx, kk >> 3) + rank) * 128, fb);
              if (POL & 2) tma3d_mc_p(sb + (g0 + 1 + rank) * GR, rank ? &p.wuv : &p.wuk, 0, (kk & 7) * 64, (hp + KV_HEAD(idx, kk >> 3)) * 2, fb, (POL & 512) || kk >= 8);
              else tma3d_mc(sb + (g0 + 1 + rank) * GR, rank ? &p.wuv : &p.wuk, 0, (kk & 7) * 64, (hp + KV_HEAD(idx, kk >> 3)) * 2, fb);
            } else {
              if (POL & 4) tma2d_mc_p(sb + (g0 + rank) * GR, &p.x, (kk - 16) * 64, (rank ? 15 - idx : idx) * 128, fb, (POL & 1024) || rnd);
              else tma2d_mc(sb + (g0 + rank) * GR, &p.x, (kk - 16) * 64, (rank ? 15 - idx : idx) * 128, fb);
              tma3d<true>(sb + (g0 + 2) * GR, &p.wq, 0, (kk - 16) * 64, head * 2, fb);
            }
          }
        }
        flag_wait(FLAG(F_KV + rnd * 8 + grp), 32);
        fence_async_all();
        acquire(2, 1, 3);
        int g0 = 4;
#pragma unroll 1
        for (int n = 0; n < 36; n += n == 0 || n == 33 ? 2 : 1) {
          const int it = (n >> 1) - (n & 1);
          const int blk = it & 15 ? (it <= idx ? it - 1 : 15 - it) : it ? 15 - idx : idx;
          acquire(g0, n < 6 ? 2 : 1, 3);
          if (elect()) {
            const uint32_t fb = sb + SM_BAR + (B_FULL + g0) * 8;
            if (n == 5) mbar_arrive(sb + SM_BAR + B_SLOT * 8);
            mbar_expect_tx(fb, 2 * GR);
            if (KVP) asm volatile("cp.async.bulk" TMA_MB ".L2::cache_hint [%0], [%1], %2, [%3], %4;" ::"r"(sb + g0 * GR), "l"(g_kv + (unsigned)((((n & 1) * 16 + (head & 15)) * 16 + blk) * 32768)),
                                  "r"(2 * GR), "r"(fb), "l"(it >= 8 && ((KVP >> rnd) & 1) ? EV_FIRST : EV_NORMAL) : "memory");
            else
            bulk_g2s(sb + g0 * GR, g_kv + (unsigned)((((n & 1) * 16 + (head & 15)) * 16 + blk) * 32768), 2 * GR, fb);
          }
          g0 = n == 13 ? 12 : g0 == 12 ? 4 : g0 + 2;
        }
      }
      int c5 = 0;
      if (spare) { bar_sync(5, 64); pe = 0x3FC0; }
      else c5 = get_ticket();
      auto conv_fill = [&](int g, int ch) {
        acquire(g, 1, 1);
        if (elect()) {
          const uint32_t fb = sb + SM_BAR + (B_FULL + g) * 8;
          if (!spare) FTP(64 + 48 + g);
          mbar_expect_tx(fb, WBYTES + 4096);
          bulk_g2s<true>(sb + g * GR, g_w + (size_t)ch * WSTRIDE, WBYTES, fb);
          bulk_g2s<true>(sb + g * GR + WBYTES, p.ssk + (size_t)ch * SEQ, 4096, fb);
        }
      };
#pragma unroll 1
      for (int i = 0, g = 2; i < cn; i++) {
        if ((i & 15) == 0) { flag_wait(FLAG(F_U + (spare ? 32 - __clz(i >> 4) : 4)), NMAIN); fence_async_all(); }
        conv_fill(g + (i & 1), cch + i * cstep + (i == 4 ? c5 : 0));
        if (i & 1) g = conv_next(g, spare);
      }
      if (!spare) {
        const int rt = 2 * grp + rank, ct = idx;
        int g0 = P3G, top = 12;
        const uint8_t* src = g_cimg + (unsigned)((rt * 64 + P3O) * GR);
#pragma unroll 1
        for (int kb = 0; kb < 64; kb++) {
          if (!(kb & 31)) { flag_wait(FLAG(F_CTX + rt * 2 + ((kb ^ P3O) >> 5)), 32); fence_async_all(); if (P3O && kb) src -= 64 * GR; }
          acquire(g0, kb < 11 ? 2 : 1, 3);
          if (elect()) {
            const uint32_t fb = sb + SM_BAR + (B_FULL + g0) * 8;
            if (kb < 16) FTP(48 + kb);
            mbar_expect_tx(fb, 2 * GR);
            bulk_g2s<true>(sb + g0 * GR, src, GR, fb);
            tma2d_mc<true>(sb + (g0 + 1) * GR + rank * 8192, &p.wo, ct * 128 + rank * 64, (kb ^ P3O) * 64, fb);
          }
          src += GR;
          g0 = g0 == (kb < XK ? 12 : kb < YK ? 10 : 8) ? (kb == 3 ? 2 : 0) : g0 + 2;
          if (kb == XK || (kb >= YK && top == P3Y && (kb == 63 || mbar_test(sb + SM_BAR + B_SLOT * 8, 1)))) {
            const bool j = kb != XK;
            if (j) { mbar_wait1(sb + SM_BAR + B_SLOT * 8, 1); fence_async_all(); }
            acquire(top, 1, 0);
            if (elect()) {
              const uint32_t fb = sb + SM_BAR + (B_FULL + top) * 8;
              mbar_expect_tx(fb, j ? 2 * GR + 512 : 2 * GR);
              if (j) bulk_g2s(sb + SM_GATE, g_gate + (unsigned)(rt * 128), 512, fb);
              tma3d<(POL & 128) != 0>(sb + top * GR, j ? &p.y3 : &p.x3, 0, (j ? ct : rt) * 128, (j ? rt : ct) * 2, fb);
            }
            top -= 2;
          }
        }
        unsigned n = 0;
        if (lane == 0) n = atomicInc(FLAG(F_EXIT), 0x7fffffffu);
        if (__any_sync(0xffffffffu, n == NMAIN - 1)) {
#pragma unroll
          for (int i = lane; i < 96; i += 32) *reinterpret_cast<uint2*>(FLAG(i)) = make_uint2(0, 0);
        }
      }
      if (lane == 0) mbar_arrive(sb + SM_BAR + B_DONE * 8);
    }
    __syncwarp();
    cluster_wait();
  } else {
    asm volatile("setmaxnreg.inc.sync.aligned.u32 232;");
    FTS(2);
    Cons c;
    c.sb = sb; c.pf = 0; c.wg = wgi - 1; c.tid = threadIdx.x & 127;
    const int lane = threadIdx.x & 31, t = lane & 3;
    const int row = c.wg * 64 + (warp & 3) * 16 + (lane >> 2);
    const uint32_t dkk = desc_k(sb), dk0 = dkk + c.wg * 512, dm0 = desc_mn<8192>(sb), dv0 = desc_mn<16384>(sb);
    const uint32_t dsw = DG + 512 - c.wg * 1024;
    if (c.wg == 1) bar_arrive(1, 256);
    c.pfree = 1;
    asm("mapa.shared::cluster.u32 %0, %1, %2;" : "=r"(c.relb) : "r"(sb + SM_BAR + (B_EMPTY + (c.tid >> 1)) * 8), "r"(c.tid & 1));
    c.zero = p.zero;
    c.rnd = 0;
    const uint32_t stg = sb + (c.wg * 64 + (warp & 3) * 16 + ((lane >> 3) & 1) * 8 + (lane & 7)) * 128 + (((lane >> 4) ^ (lane & 7)) << 4);

    uint32_t dd0;
    auto load_dd = [&]() { asm volatile("ld.global.nc.u16 %0, [%1];" : "=r"(dd0) : "l"(p.ssd + (unsigned)(cch + c.wg * cstep + (lane & c.zero)))); };
    int pass = c.zero;
#pragma unroll 1
    do {
    if (pass) {
      load_dd();
#pragma unroll 1
      for (int g = 2; g < NGR; g += 3) { mbar_wait(sb + SM_BAR + (B_FULL + g) * 8, 0); c.release(g, 3); }
      c.pf = 0x924;
    if (spare) {
      c.wait_full(1);
      int g = 2;
#pragma unroll 1
      for (int r = 0; r < 4; r++) {
        float d[4] = {0.f, 0.f, 0.f, 0.f}, e[4] = {0.f, 0.f, 0.f, 0.f};
#pragma unroll 1
        for (int kb = 0; kb < 16; kb += 2) {
          c.wait_full(g);
          wg_fence();
#pragma unroll 1
          for (int k = 0; k < 4; k++) {
            mma_ss_n8(d, dk0 + g * DG + k * 2, dkk + DG + kb * 8 + k * 2);
            mma_ss_n8(e, dk0 + (g + 1) * DG + k * 2, dkk + DG + kb * 8 + 8 + k * 2);
          }
          wg_commit();
          wg_wait<0>();
          c.release(g, 2);
          g = g == NGR - 2 ? 2 : g + 2;
        }
        reg_fence(d); reg_fence(e);
        d[0] += e[0]; d[2] += e[2];
        if (t == 0) {
          float* gp = g_gate + (unsigned)((lb - NMAIN) * 512 + r * 128 + row);
          gp[0] = rcp(1.f + ex2(-1.4426950408889634f * d[0])); gp[8] = rcp(1.f + ex2(-1.4426950408889634f * d[2]));
        }
      }
      fence_release();
      __syncwarp();
      if (lane == 0) flag_add(FLAG(F_GATE));
      TS(1);
    }
    } else cluster_wait();
    get_slot();
    } while (redo && !pass++);
    FTS(3);
    const float dmask = (float)(2 * t - (row & 63));
    int c5 = 0;
    uint32_t pv[32];
#pragma unroll 1
    for (int rnd = 0; rnd < (spare ? 0 : 2); rnd++) {
      float O[64];
      FTM(rnd * 8);
      FTG(0);
      FTH(56, c.rnd == rnd);
      c.wait_full(2);
      FTM(rnd * 8 + 1);
      FTH(57, c.rnd == rnd);
#pragma unroll 1
      for (int tile = c.zero; tile < 2; tile++) {
        float acc[128];
        const bool single = tile == 0;
        {
          FTG(tile * 32 + 1);
          const uint32_t a = dk0 + 2 * DG, b = dm0 + 3 * DG;
          c.turn_begin();
          FTG(tile * 32 + 2);
          FTH(58, c.rnd == rnd);
          wg_fence();
          mma_ss_n256_init<1>(acc, a, b);
#pragma unroll
          for (int k = 1; k < 4; k++) mma_ss_n256<1>(acc, a + k * 2, b + k * 128);
          wg_commit();
          if (single) c.turn_end();
          FTG(tile * 32 + 3);
        }
#pragma unroll 1
        for (int kb = 1; kb < 8; kb++) {
          const int g0 = 2 + 3 * (kb & 3);
          const uint32_t a = dk0 + g0 * DG, b = dm0 + (g0 + 1) * DG;
          const bool second = (kb == 1 && !single) || kb == 7;
          FTG(tile * 32 + kb * 4);
          if (!second) { wg_wait<0>(); c.release(2 + 3 * ((kb - 1) & 3), 3); }
          FTG(tile * 32 + kb * 4 + 1);
          c.wait_full(g0);
          if (!second) c.turn_begin();
          FTG(tile * 32 + kb * 4 + 2);
          wg_fence();
#pragma unroll
          for (int k = 0; k < 4; k++) mma_ss_n256<1>(acc, a + k * 2, b + k * 128);
          wg_commit();
          if (kb != 6) c.turn_end();
          if (second) { wg_wait<1>(); c.release(2 + 3 * ((kb - 1) & 3), 3); }
          FTG(tile * 32 + kb * 4 + 3);
          FTH(58 + kb, c.rnd == rnd || kb > 3);
          if (tile == 1 && kb == 3) { c.wait_stage_free(); stsm_frag<0, 4>(pv, stg); }
          if (tile == 1 && kb == 4) { stsm_frag<4, 8>(pv, stg); c.staged(0); }
        }
        c.rnd = rnd;
        c.wait_stage_free();
        const bool nxt = c.try_full(2);
        wg_wait<0>();
        reg_fence(acc);
        c.release(11, 3);
        store_scaled(acc, SM_C, SM_C, stg, sb);
        c.staged(0);
        pack_frag<64>(acc, pv);
        FTG(32 + tile * 32);
        if (!nxt) mbar_wait(sb + SM_BAR + (B_FULL + 2) * 8, (c.pf >> 2) & 1);
        c.pf ^= 4;
      }
      TS(1 + rnd * 3);
      FTM(rnd * 8 + 2);
      {
        float qa[64];
        float (&qb)[64] = O;
        {
          FTG(65);
          const uint32_t a = dk0 + 2 * DG, b = dm0 + 4 * DG;
          c.turn_begin();
          FTG(66);
          wg_fence();
          mma_ss_n128_init<1>(qa, a, b);
          mma_ss_n128_init<1>(qb, a + dsw, b);
#pragma unroll
          for (int k = 1; k < 4; k++) {
            mma_ss_n128<1>(qa, a + k * 2, b + k * 128);
            mma_ss_n128<1>(qb, a + dsw + k * 2, b + k * 128);
          }
          wg_commit();
          FTG(67);
        }
#pragma unroll 1
        for (int kb = 1; kb < 16; kb++) {
          const int g0 = 2 + 3 * (kb & 3);
          const uint32_t a = dk0 + g0 * DG, b = dm0 + (g0 + 2) * DG;
          const bool second = kb == 1 || kb == 15;
          FTG(64 + kb * 4);
          if (!second) { wg_wait<0>(); c.release(2 + 3 * ((kb - 1) & 3), 3); }
          FTG(65 + kb * 4);
          c.wait_full(g0);
          if (!second) c.turn_begin();
          FTG(66 + kb * 4);
          FTH(kb - 14, kb < 14);
          wg_fence();
#pragma unroll
          for (int k = 0; k < 4; k++) {
            mma_ss_n128<1>(qa, a + k * 2, b + k * 128);
            mma_ss_n128<1>(qb, a + dsw + k * 2, b + k * 128);
          }
          wg_commit();
          if (kb != 14) c.turn_end();
          if (second) { wg_wait<1>(); c.release(2 + 3 * ((kb - 1) & 3), 3); }
          FTG(67 + kb * 4);
          FTH(2, kb < 15);
          if (kb == QFLUSH) { c.wait_stage_free(); stsm_frag<0, 4>(pv, stg); }
          if (kb == QFLUSH + 1) { stsm_frag<4, 8>(pv, stg); c.staged(0); }
        }
        c.wait_stage_free();
        mbar_wait(sb + SM_BAR + (B_EMPTY + 2) * 8, rnd ^ !redo);
        FTM(rnd * 8 + 3);
        FTH(3, 0);
        const bool k0 = c.try_full(4);
        wg_wait<0>();
        reg_fence(qa); reg_fence(qb);
        FTH(4, 0);
        c.release(11, 3);
        pack_frag<0>(qa, pv);
        stsm_frag(pv, stg + 2 * GR);
        if (c.wg == 0) {
          pack_frag<0>(qb, pv);
          stsm_frag(pv, stg);
        }
        FTH(6, 0);
        fence_async_smem();
        FTH(7, 0);
        if (!k0) c.wait_full(4); else c.pf ^= 16;
      }
      TS(2 + rnd * 3);
      FTM(rnd * 8 + 4);
      FTH(5, 0);
      {
        const int nA = idx + 1;
        uint32_t (&P)[32] = pv;
        SoftState z;
        z.m0 = z.m1 = z.l0 = z.l1 = 0.f; z.shifted = c.zero;
#pragma unroll 1
        for (int seg = c.zero;; seg++) {
        if (c.wg == seg) attn_half(c, O, P, z, dk0, dkk, dv0, dmask, seg);
        if (seg) break;
        FTM(rnd * 8 + 5);
        int gk = c.wg ? 4 : 6, gv = c.wg ? 4 : 8;
        uint32_t dq = dk0 + (1 - c.wg < nA ? 2 * DG : 0), dk = dkk + gk * DG;
#pragma unroll 1
        for (int it = 1 - c.wg; it < 17 - c.wg; it++) {
          float S[64];
          FTA(it * 7 + 0); FTH((it < 3 ? 8 + it * 8 : it * 8 - 88) + 0, it >= 3 && it < 15);
          c.turn_begin();
          FTA(it * 7 + 2); FTH((it < 3 ? 8 + it * 8 : it * 8 - 88) + 1, it >= 3 && it < 15);
          wg_fence();
          issue_qk(S, dq, dk);
          wg_commit();
          const uint32_t dv = dv0 + gv * DG;
          uint32_t relk = c.relb + gk * 8, relv = c.relb + gv * 8;
          gk = it == 6 ? 12 : gv == 12 ? 4 : gv + 2;
          gv = it == 16 ? gk : gk == 12 ? 4 : gk + 2;
          uint32_t fk = sb + SM_BAR + (B_FULL + gk) * 8, fv = sb + SM_BAR + (B_FULL + gv) * 8, park = (c.pf >> gk) & 1, parv = (c.pf >> gv) & 1;
          c.pf ^= (1u << gk) | (1u << gv);
          dq = dk0 + (it + 1 < nA ? 2 * DG : 0); dk = dkk + gk * DG;
          float lo0 = z.l0, lo1 = z.l1;
          const bool first = it == nA || it == 0;
          if (it == nA) {
            lo0 = rcp(quad_sum(lo0)); lo1 = rcp(quad_sum(lo1));
            z.m0 = z.m1 = z.l0 = z.l1 = 0.f; z.shifted = 0;
          }
          float s0, s1, d0 = z.m0, d1 = z.m1;
          int pre = z.shifted || (it & 15) == 0;
          float lim = first ? -1.f : SM_LIMIT;
          asm volatile("" : "+r"(relk), "+r"(relv), "+r"(fk), "+r"(fv), "+r"(park), "+r"(parv), "+r"(dq), "+r"(dk), "+r"(pre), "+f"(lim), "+f"(d0), "+f"(d1), "+f"(z.l0), "+f"(z.l1));
          if (it + c.wg > 1) {
            issue_pv<0>(O, P, dv, it != nA + 1 && it != 1, true);
            issue_pv<1>(O, P, dv, 1, true);
            c.turn_end();
          } else if (it) {
            issue_pv<0>(O, P, dv, 0, true);
            wg_commit(); wg_commit();
            c.turn_end();
          } else stage_q2(c, O, P, stg);
          FTA(it * 7 + 3); FTH((it < 3 ? 8 + it * 8 : it * 8 - 88) + 2, it >= 3 && it < 15);
          wg_wait<4>();
          reg_fence(S);
          FTA(it * 7 + 4); FTH((it < 3 ? 8 + it * 8 : it * 8 - 88) + 3, it >= 3 && it < 15);
          if (c.tid < 4) asm volatile("mbarrier.arrive.shared::cluster.b64 _, [%0];" ::"r"(relk) : "memory");
#pragma unroll 1
          for (int pass = 0;; pass++) {
            if (pre) {
              if ((it & 15) == 0) mask_diag(S, dmask);
              if (z.shifted) shift_scores(S, d0, d1);
            }
            float tr[ROT];
            exp_quarter<0, 3>(S, P, tr, s0, s1, sb);
            exp_quarter<1, 2>(S, P, tr, s0, s1, sb);
            exp_quarter<2, 1>(S, P, tr, s0, s1, sb);
            exp_quarter<3, 0>(S, P, tr, s0, s1, sb);
            reg_fence(O);
            if (c.tid < (pass || !it ? 0 : 4)) asm volatile("mbarrier.arrive.shared::cluster.b64 _, [%0];" ::"r"(relv) : "memory");
            const bool ok = mbar_test(fk, park) & mbar_test(fv, parv);
            if (!ok) lim = -1.f;
            FTA(it * 7 + 5); FTH((it < 3 ? 8 + it * 8 : it * 8 - 88) + 4, it >= 3 && it < 15);
            if (!__any_sync(0xffffffffu, !(s0 <= lim && s1 <= lim))) break;
            if (pass) break;
            if (it == nA) {
              store_scaled(O, lo0, lo1, stg + 2 * GR, sb);
              c.staged(1);
            }
            if (!ok) { mbar_wait(fk, park); mbar_wait(fv, parv); }
            if (!soft_unsafe(s0, s1, first)) break;
            soft_fix(S, O, z, first, d0, d1);
            pre = 1;
          }
          z.l0 += s0; z.l1 += s1;
          FTA(it * 7 + 6); FTH((it < 3 ? 8 + it * 8 : it * 8 - 88) + 5, it >= 3 && it < 15);
        }
        FTM(rnd * 8 + 6);
        }
        FTH(48, 0);
        load_dd();
        c.turn_begin();
        FTH(49, 0);
        wg_fence();
        issue_pv<0>(O, P, dv0 + 12 * DG, 1, true);
        issue_pv<1>(O, P, dv0 + 12 * DG, 1, !c.wg);
        c.turn_end();
        z.l0 = rcp(quad_sum(z.l0)); z.l1 = rcp(quad_sum(z.l1));
        if (rnd) c5 = get_ticket();
        wg_wait<0>();
        reg_fence(O); reg_fence(P);
        FTH(50, 0);
        c.release(12, 2);
        store_scaled(O, z.l0, z.l1, stg, sb);
        c.staged(0);
        FTM(rnd * 8 + 7);
        FTH(51, 0);
      }
      TS(3 + rnd * 3);
    }
    conv_tasks(c, p, (cn + 1 - c.wg) >> 1, spare, cch + c.wg * cstep, 2 * cstep, c5, dd0, dkk, warp & 3, lane);
    if (c.wg == 1) c.pf ^= 0x14;
    if (c.wg == (cn & 1)) c.turn_begin();
    TS(7);
    if (!spare) {
      const int rt = 2 * grp + rank, ct = idx;
      float acc[64];
      int g0 = P3G + 2, pg = P3G;
      {
        FTO(0);
        c.wait_full(P3G);
        FTO(1);
        const uint32_t a = dk0 + P3G * DG, b = dm0 + (P3G + 1) * DG;
        wg_fence();
        mma_ss_n128_init<1>(acc, a, b);
#pragma unroll
        for (int k = 1; k < 4; k++) mma_ss_n128<1>(acc, a + k * 2, b + k * 128);
        wg_commit();
      }
#pragma unroll 1
      for (int kb = 1; kb < 64; kb++) {
        FTO(kb * 2);
        c.wait_full(g0);
        if (kb == STR && !c.wg) c.turn_begin();
        FTO(kb * 2 + 1);
        const uint32_t a = dk0 + g0 * DG, b = dm0 + (g0 + 1) * DG;
        wg_fence();
#pragma unroll
        for (int k = 0; k < 4; k++) mma_ss_n128<1>(acc, a + k * 2, b + k * 128);
        wg_commit();
        if (kb < STR) { wg_wait<1>(); c.release(pg, kb <= 59 ? 2 : 0); }
        if (kb == FDUMP_KB) FTDUMP();
        pg = g0;
        g0 = g0 == (kb < XK ? 12 : kb < YK ? 10 : 8) ? (kb == 3 ? 2 : 0) : g0 + 2;
      }
      if (c.wg) c.turn_end();
      cluster_arrive();
      c.wait_full(P3X);
      c.wait_full(P3Y);
      const float g0f = __uint_as_float(lds32(sb + SM_GATE + row * 4)), g1f = __uint_as_float(lds32(sb + SM_GATE + row * 4 + 32));
      const uint32_t gp0 = pack_bf16(g0f, g0f), gp1 = pack_bf16(g1f, g1f);
      const float h0 = 1.f - g0f, h1 = 1.f - g1f;
      const int w = warp & 3;
      const uint32_t xa = stg + P3X * GR;
      const uint32_t ya = sb + P3Y * GR + c.wg * 16384 + ((lane >> 4) * 8 + (lane & 7)) * 128 + (((2 * w + ((lane >> 3) & 1)) ^ (lane & 7)) << 4);
      uint32_t xy[32];
      auto prep = [&](int j0, int j1) {
#pragma unroll
        for (int jj = j0; jj < j1; jj++) {
          uint32_t x[4], y[4];
          asm volatile("ldmatrix.sync.aligned.m8n8.x4.shared.b16 {%0,%1,%2,%3}, [%4];" : "=r"(x[0]), "=r"(x[1]), "=r"(x[2]), "=r"(x[3]) : "r"((xa ^ ((jj & 3) << 5)) + (jj >> 2) * 16384) : "memory");
          asm volatile("ldmatrix.sync.aligned.m8n8.x4.trans.shared.b16 {%0,%1,%2,%3}, [%4];" : "=r"(y[0]), "=r"(y[1]), "=r"(y[2]), "=r"(y[3]) : "r"(ya + jj * 2048) : "memory");
#pragma unroll
          for (int i = 0; i < 4; i++) xy[4 * jj + i] = hmul2(x[i], y[i]);
        }
      };
      prep(0, 4);
      wg_wait<0>();
      reg_fence(acc);
      TS(8);
#pragma unroll
      for (int hf = 0; hf < 2; hf++) {
#pragma unroll
        for (int i = 16 * hf; i < 16 * hf + 16; i++) {
          const float h = (i & 1) ? h1 : h0;
          xy[i] = hfma2((i & 1) ? gp1 : gp0, xy[i], pack_bf16(acc[2 * i] * h, acc[2 * i + 1] * h));
        }
        if (hf) stsm_frag<4, 8>(xy, xa); else stsm_frag<0, 4>(xy, xa);
        fence_async_smem();
        __syncwarp();
        const int r0 = c.wg * 64 + w * 16;
        if (lane == 0) tma2d_store(&p.out, sb + (P3X + hf) * GR + r0 * 128, ct * 128 + hf * 64, rt * 128 + r0);
        if (!hf) prep(4, 8);
      }
      if (lane == 0) asm volatile("cp.async.bulk.commit_group;\ncp.async.bulk.wait_group.read 0;" ::: "memory");
    } else { FTDUMP(); cluster_arrive(); }
    if (lane == 0) mbar_arrive(sb + SM_BAR + B_DONE * 8);
    __syncwarp();
    TS(9);
    cluster_wait();
  }
}

typedef CUresult (*EncFn)(CUtensorMap*, CUtensorMapDataType, cuuint32_t, void*, const cuuint64_t*, const cuuint64_t*, const cuuint32_t*,
                          const cuuint32_t*, CUtensorMapInterleave, CUtensorMapSwizzle, CUtensorMapL2promotion, CUtensorMapFloatOOBfill);

void enc2d(EncFn enc, CUtensorMap* tm, const void* base, uint64_t cols, uint64_t rows, uint32_t bc, uint32_t br) {
  cuuint64_t dims[2] = {cols, rows}; cuuint64_t strides[1] = {cols * 2}; cuuint32_t box[2] = {bc, br}; cuuint32_t es[2] = {1, 1};
  enc(tm, CU_TENSOR_MAP_DATA_TYPE_BFLOAT16, 2, const_cast<void*>(base), dims, strides, box, es, CU_TENSOR_MAP_INTERLEAVE_NONE,
      CU_TENSOR_MAP_SWIZZLE_128B, CU_TENSOR_MAP_L2_PROMOTION_L2_256B, CU_TENSOR_MAP_FLOAT_OOB_FILL_NONE);
}
void enc3d(EncFn enc, CUtensorMap* tm, const void* base, uint64_t K, uint64_t N, uint32_t bk = 64) {
  cuuint64_t dims[3] = {64, K, N / 64}; cuuint64_t strides[2] = {N * 2, 128}; cuuint32_t box[3] = {64, bk, 2}; cuuint32_t es[3] = {1, 1, 1};
  enc(tm, CU_TENSOR_MAP_DATA_TYPE_BFLOAT16, 3, const_cast<void*>(base), dims, strides, box, es, CU_TENSOR_MAP_INTERLEAVE_NONE,
      CU_TENSOR_MAP_SWIZZLE_128B, CU_TENSOR_MAP_L2_PROMOTION_L2_256B, CU_TENSOR_MAP_FLOAT_OOB_FILL_NONE);
}

}

extern "C" void kernel_launch(void* const* d_in, const int* in_sizes, int n_in, void* d_out, int out_size) {
  (void)in_sizes; (void)n_in; (void)out_size;
  typedef const __nv_bfloat16* BP;
  BP xq = (BP)d_in[0], ak = (BP)d_in[1], av = (BP)d_in[2], shk = (BP)d_in[3], ssk = (BP)d_in[4], ssd = (BP)d_in[5];
  BP ckv = (BP)d_in[7], wq = (BP)d_in[8], wuk = (BP)d_in[9], wuv = (BP)d_in[10], wo = (BP)d_in[11], gw = (BP)d_in[12];

  static EncFn enc = nullptr;
  if (!enc) {
    cudaDriverEntryPointQueryResult qr;
    cudaGetDriverEntryPoint("cuTensorMapEncodeTiled", (void**)&enc, cudaEnableDefault, &qr);
    cudaFuncSetAttribute(mega_kernel, cudaFuncAttributeMaxDynamicSharedMemorySize, SMEM_BYTES);
  }
  Params p;
  void* yT = nullptr;
  cudaGetSymbolAddress(&yT, g_yT);
  enc2d(enc, &p.x, xq, DM, SEQ, 64, 128);
  enc2d(enc, &p.c, ckv, DC, SEQ, 64, 128);
  enc3d(enc, &p.wq, wq, DM, NH * HD);
  enc3d(enc, &p.wuk, wuk, DC, NH * HD);
  enc3d(enc, &p.wuv, wuv, DC, NH * HD);
  enc2d(enc, &p.wo, wo, DM, NH * HD, 64, 64);
  enc3d(enc, &p.x3, xq, SEQ, DM, 128);
  enc3d(enc, &p.y3, yT, DM, SEQ, 128);
  enc2d(enc, &p.out, d_out, DM, SEQ, 64, 16);
  {
    void* wp = nullptr;
    cudaGetSymbolAddress(&wp, g_w);
    cuuint64_t dims[3] = {WSTRIDE / 2, DM / 2, 2}; cuuint64_t strides[2] = {2 * WSTRIDE, WSTRIDE}; cuuint32_t box[3] = {16, 32, 2}; cuuint32_t es[3] = {1, 1, 1};
    enc(&p.w, CU_TENSOR_MAP_DATA_TYPE_BFLOAT16, 3, wp, dims, strides, box, es, CU_TENSOR_MAP_INTERLEAVE_NONE,
        CU_TENSOR_MAP_SWIZZLE_32B, CU_TENSOR_MAP_L2_PROMOTION_NONE, CU_TENSOR_MAP_FLOAT_OOB_FILL_NONE);
  }
  p.zero = 0;
  cudaGetSymbolAddress((void**)&p.flags, g_flags);
  for (int i = 0; i < 128; i++) {
    const int tp = i % NSLOT;
    p.pref[i] = tp < 32 ? (tp & 7) * 8 + (tp >> 3) : tp < 60 ? (1 + (tp - 32) % 7) * 8 + 4 + (tp - 32) / 7 : tp < 62 ? tp + 4 : tp - 58;
  }
  p.gate_w = gw; p.ak = ak; p.av = av; p.shk = shk; p.ssk = ssk; p.ssd = ssd; p.wop = wo;

  mega_kernel<<<132, NTHREADS, SMEM_BYTES>>>(p);
}
```

```cpp
#include <cuda_runtime.h>
#include <cuda.h>
#include <cuda_bf16.h>
#include <stdint.h>

namespace {

constexpr int SEQ = 2048, DM = 1024, DC = 512, NH = 32, HD = 128;
constexpr int GR = 16384;
constexpr int NGR = 14;
constexpr int SM_BAR = NGR * GR;
constexpr int SM_GATE = SM_BAR + 512;
constexpr int SM_UST = SM_GATE + 512;
constexpr int SMEM_BYTES = SM_UST + 2048;
constexpr int NTHREADS = 384;
#define SM_LIMIT 1.0995116e12f
#define SM_LOW 9.094947e-13f
#define CNS 106
constexpr int CN_SPARE = CNS, NTICK = 256 - 2 * CN_SPARE;
constexpr int XK = 57, YK = 62;
constexpr int STR = 61;
constexpr int P3G = 6, P3X = 12, P3Y = 10;
constexpr int NMAIN = 128;

constexpr int B_FULL = 0, B_FREE = 14, B_SLOT = 16, B_DONE = 17, B_EMPTY = 18, B_EV = 32, B_TICK = 36;
constexpr int V_SLOT = 37, V_TICK = 38;

__device__ __align__(1024) uint8_t g_kv[2 * 16 * 16 * 32768];
__device__ __align__(1024) uint8_t g_cimg[16 * NH * 32768];
__device__ __align__(1024) __nv_bfloat16 g_yT[DM * SEQ];
__device__ __align__(1024) float g_gate[SEQ];
constexpr int WZ = 256, WPL = WZ + 4096, WBYTES = 2 * WPL + 32, WSTRIDE = 2 * WPL + 128;
__device__ __align__(1024) uint8_t g_w[DM * WSTRIDE];
__device__ __align__(32) unsigned g_flags[96 * 8];
constexpr int F_KV = 0, F_CTX = 16, F_U = 48, F_AD = 56, F_Y = 64, F_GATE = 72, F_EXIT = 73, F_TICK = 74;
constexpr int NSLOT = 66;
#define FLAG(i) (&g_flags[(i) * 8])
#define CLAIMP(i) (p.flags + (i) * 8 + 1)

#define TS(slot)
#define TSW(slot)
#define FTX(i, off)
#define FTDUMP()

#define QFLUSH 4
#define PSL 200
#define US0 500
#define EROT 6
#define RST 2
#define UP0 4
#define UP1 11
#define X_DELAY 900
#define X_D2 600
#define EXPV 1
#define SUMV 0
#define ROT 8
#define KVARR 1
#define KV_ROW(idx, t) (KVARR ? 8 * (t) + 2 * ((idx) & 3) : 2 * (idx))
#define KV_HEAD(idx, t) (KVARR ? (idx) >> 2 : (t))
#define FINE_MODE 0
#define FDUMP_KB 40
#define FINE_RND 1
#define FTA(i) do { if (FINE_MODE == 0) FTX(i, rnd ^ FINE_RND); } while (0)
#define FTG(i) do { if (FINE_MODE == 1) FTX(i, rnd ^ FINE_RND); } while (0)
#define FTM(i) do { if (FINE_MODE == 4) FTX(i, 0); } while (0)
#define FTC(k) do { if (FINE_MODE == 5) FTX((i & 7) * 8 + (k), (i >> 3) ^ FINE_RND); } while (0)
#define FTH(i, off) do { if (FINE_MODE == 6) FTX(i, (c.rnd ^ FINE_RND) | (off)); } while (0)
#define FTS(i)
#define FTSD(i)
#define FTSW(i)
#define FTP(i)
#define FTO(i) do { if (FINE_MODE == 2) FTX(i, 0); } while (0)

__device__ __forceinline__ uint32_t smem_u32(const void* p) { return (uint32_t)__cvta_generic_to_shared(p); }
__device__ __forceinline__ void mbar_init(uint32_t bar, int cnt) { asm volatile("mbarrier.init.shared::cta.b64 [%0], %1;" ::"r"(bar), "r"(cnt) : "memory"); }
__device__ __forceinline__ void mbar_expect_tx(uint32_t bar, uint32_t bytes) { asm volatile("mbarrier.arrive.expect_tx.shared::cta.b64 _, [%0], %1;" ::"r"(bar), "r"(bytes) : "memory"); }
__device__ __forceinline__ void mbar_arrive(uint32_t bar) { asm volatile("mbarrier.arrive.shared::cta.b64 _, [%0];" ::"r"(bar) : "memory"); }
__device__ __forceinline__ void mbar_arrive_cluster(uint32_t bar, uint32_t cta) {
  asm volatile("{\n.reg .b32 r;\nmapa.shared::cluster.u32 r, %0, %1;\nmbarrier.arrive.shared::cluster.b64 _, [r];\n}\n" ::"r"(bar), "r"(cta) : "memory");
}
__device__ __forceinline__ void send_both(uint32_t bar, uint32_t off, uint32_t v) {
#pragma unroll
  for (int r = 0; r < 2; r++)
    asm volatile("{\n.reg .b32 a, b;\nmapa.shared::cluster.u32 a, %0, %1;\nadd.u32 b, a, %3;\nst.async.shared::cluster.mbarrier::complete_tx::bytes.u32 [b], %2, [a];\n}\n"
                 ::"r"(bar), "r"(r), "r"(v), "r"(off) : "memory");
}
__device__ __forceinline__ bool mbar_try(uint32_t bar, uint32_t parity) {
  uint32_t ok;
  asm volatile("{\n.reg .pred p;\nmbarrier.try_wait.parity.shared::cta.b64 p, [%1], %2, 20000;\nselp.u32 %0, 1, 0, p;\n}\n" : "=r"(ok) : "r"(bar), "r"(parity) : "memory");
  return ok;
}
__device__ __forceinline__ bool mbar_test(uint32_t bar, uint32_t parity) {
  uint32_t ok;
  asm volatile("{\n.reg .pred p;\nmbarrier.test_wait.parity.shared::cta.b64 p, [%1], %2;\nselp.u32 %0, 1, 0, p;\n}\n" : "=r"(ok) : "r"(bar), "r"(parity) : "memory");
  return ok;
}
__device__ __forceinline__ void mbar_wait(uint32_t bar, uint32_t parity) {
  asm volatile("{\n.reg .pred p;\nWAIT_LOOP:\nbar.warp.sync -1;\nmbarrier.try_wait.parity.shared::cta.b64 p, [%0], %1;\n@!p bra WAIT_LOOP;\n}\n" ::"r"(bar), "r"(parity) : "memory");
}
__device__ __forceinline__ void mbar_wait1(uint32_t bar, uint32_t parity) {
  asm volatile("{\n.reg .pred p;\nWAIT_LOOP:\nbar.warp.sync -1;\nmbarrier.try_wait.parity.shared::cta.b64 p, [%0], %1, 4000;\n@!p bra WAIT_LOOP;\n}\n" ::"r"(bar), "r"(parity) : "memory");
}
constexpr uint64_t EV_NORMAL = 0x1000000000000000ull, EV_FIRST = 0x12F0000000000000ull;
__device__ __forceinline__ uint32_t ldg_stream(const uint32_t* p) {
  uint32_t r; asm volatile("ld.global.nc.L1::no_allocate.L2::cache_hint.b32 %0, [%1], %2;" : "=r"(r) : "l"(p), "l"(EV_FIRST)); return r;
}
#define TMA_LD "cp.async.bulk.tensor."
#define TMA_MB ".shared::cluster.global.mbarrier::complete_tx::bytes"
__device__ __forceinline__ void tma2d(uint32_t dst, const CUtensorMap* tm, int c0, int c1, uint32_t bar) {
  asm volatile(TMA_LD "2d" TMA_MB " [%0], [%1, {%3, %4}], [%2];" ::"r"(dst), "l"(tm), "r"(bar), "r"(c0), "r"(c1) : "memory");
}
template <bool ONCE = false> __device__ __forceinline__ void tma2d_mc(uint32_t dst, const CUtensorMap* tm, int c0, int c1, uint32_t bar) {
  if (ONCE) asm volatile(TMA_LD "2d" TMA_MB ".multicast::cluster.L2::cache_hint [%0], [%1, {%3, %4}], [%2], %5, %6;"
                         ::"r"(dst), "l"(tm), "r"(bar), "r"(c0), "r"(c1), "h"((uint16_t)3), "l"(EV_FIRST) : "memory");
  else asm volatile(TMA_LD "2d" TMA_MB ".multicast::cluster [%0], [%1, {%3, %4}], [%2], %5;"
                    ::"r"(dst), "l"(tm), "r"(bar), "r"(c0), "r"(c1), "h"((uint16_t)3) : "memory");
}
__device__ __forceinline__ void tma2d_p(uint32_t dst, const CUtensorMap* tm, int c0, int c1, uint32_t bar, bool once) {
  asm volatile(TMA_LD "2d" TMA_MB ".L2::cache_hint [%0], [%1, {%3, %4}], [%2], %5;" ::"r"(dst), "l"(tm), "r"(bar), "r"(c0), "r"(c1), "l"(once ? EV_FIRST : EV_NORMAL) : "memory");
}
__device__ __forceinline__ void tma3d_mc_p(uint32_t dst, const CUtensorMap* tm, int c0, int c1, int c2, uint32_t bar, bool once) {
  asm volatile(TMA_LD "3d" TMA_MB ".multicast::cluster.L2::cache_hint [%0], [%1, {%3, %4, %5}], [%2], %6, %7;"
               ::"r"(dst), "l"(tm), "r"(bar), "r"(c0), "r"(c1), "r"(c2), "h"((uint16_t)3), "l"(once ? EV_FIRST : EV_NORMAL) : "memory");
}
template <bool ONCE = false> __device__ __forceinline__ void tma3d(uint32_t dst, const CUtensorMap* tm, int c0, int c1, int c2, uint32_t bar) {
  if (ONCE) asm volatile(TMA_LD "3d" TMA_MB ".L2::cache_hint [%0], [%1, {%3, %4, %5}], [%2], %6;" ::"r"(dst), "l"(tm), "r"(bar), "r"(c0), "r"(c1), "r"(c2), "l"(EV_FIRST) : "memory");
  else
  asm volatile(TMA_LD "3d" TMA_MB " [%0], [%1, {%3, %4, %5}], [%2];" ::"r"(dst), "l"(tm), "r"(bar), "r"(c0), "r"(c1), "r"(c2) : "memory");
}
__device__ __forceinline__ void tma3d_mc(uint32_t dst, const CUtensorMap* tm, int c0, int c1, int c2, uint32_t bar) {
  asm volatile(TMA_LD "3d" TMA_MB ".multicast::cluster [%0], [%1, {%3, %4, %5}], [%2], %6;"
               ::"r"(dst), "l"(tm), "r"(bar), "r"(c0), "r"(c1), "r"(c2), "h"((uint16_t)3) : "memory");
}
template <bool ONCE = false> __device__ __forceinline__ void bulk_g2s(uint32_t dst, const void* src, uint32_t bytes, uint32_t bar) {
  if (ONCE) asm volatile("cp.async.bulk" TMA_MB ".L2::cache_hint [%0], [%1], %2, [%3], %4;" ::"r"(dst), "l"(src), "r"(bytes), "r"(bar), "l"(EV_FIRST) : "memory");
  else asm volatile("cp.async.bulk" TMA_MB " [%0], [%1], %2, [%3];" ::"r"(dst), "l"(src), "r"(bytes), "r"(bar) : "memory");
}
__device__ __forceinline__ void tma2d_store(const CUtensorMap* tm, uint32_t src, int c0, int c1) {
  asm volatile("cp.async.bulk.tensor.2d.global.shared::cta.bulk_group [%0, {%2, %3}], [%1];" ::"l"(tm), "r"(src), "r"(c0), "r"(c1) : "memory");
}
__device__ __forceinline__ void prefetch_tm(const CUtensorMap* tm) { asm volatile("prefetch.tensormap [%0];" ::"l"(tm) : "memory"); }
__device__ __forceinline__ void wg_fence() { asm volatile("wgmma.fence.sync.aligned;" ::: "memory"); }
__device__ __forceinline__ void wg_commit() { asm volatile("wgmma.commit_group.sync.aligned;" ::: "memory"); }
template <int N> __device__ __forceinline__ void wg_wait() { asm volatile("wgmma.wait_group.sync.aligned %0;" ::"n"(N) : "memory"); }
__device__ __forceinline__ void bar_sync(int id, int n) { asm volatile("bar.sync %0, %1;" ::"r"(id), "r"(n) : "memory"); }
__device__ __forceinline__ void bar_arrive(int id, int n) { asm volatile("bar.arrive %0, %1;" ::"r"(id), "r"(n) : "memory"); }
__device__ __forceinline__ void fence_async_smem() { asm volatile("fence.proxy.async.shared::cta;" ::: "memory"); }
__device__ __forceinline__ void fence_async_all() { asm volatile("fence.proxy.async.global;" ::: "memory"); }
__device__ __forceinline__ uint32_t pack_bf16(float lo, float hi) { uint32_t r; asm("cvt.rn.bf16x2.f32 %0, %1, %2;" : "=r"(r) : "f"(hi), "f"(lo)); return r; }
__device__ __forceinline__ float ex2(float x) { float r; asm("ex2.approx.ftz.f32 %0, %1;" : "=f"(r) : "f"(x)); return r; }
__device__ __forceinline__ float rcp(float x) { float r; asm("rcp.approx.ftz.f32 %0, %1;" : "=f"(r) : "f"(x)); return r; }
__device__ __forceinline__ void flag_wait(const unsigned* f, unsigned target) {
  unsigned v;
  do { asm volatile("ld.acquire.gpu.global.u32 %0, [%1];" : "=r"(v) : "l"(f) : "memory"); } while (__any_sync(0xffffffffu, v < target));
}
__device__ __forceinline__ bool elect() {
  uint32_t r;
  asm volatile("{\n.reg .pred p;\nelect.sync _|p, -1;\nselp.u32 %0, 1, 0, p;\n}\n" : "=r"(r));
  return r;
}
__device__ __forceinline__ void fence_release() { asm volatile("fence.release.gpu;" ::: "memory"); }
__device__ __forceinline__ void flag_add(unsigned* f) { asm volatile("red.relaxed.gpu.global.inc.u32 [%0], 0x7fffffff;" ::"l"(f) : "memory"); }
__device__ __forceinline__ void cluster_arrive() { asm volatile("barrier.cluster.arrive.relaxed.aligned;" ::: "memory"); }
__device__ __forceinline__ void cluster_wait() { asm volatile("barrier.cluster.wait.aligned;" ::: "memory"); }
__device__ __forceinline__ uint32_t hmul2(uint32_t a, uint32_t b) { uint32_t r; asm("mul.rn.bf16x2 %0, %1, %2;" : "=r"(r) : "r"(a), "r"(b)); return r; }
__device__ __forceinline__ uint32_t hadd2(uint32_t a, uint32_t b) { uint32_t r; asm("add.rn.bf16x2 %0, %1, %2;" : "=r"(r) : "r"(a), "r"(b)); return r; }
__device__ __forceinline__ uint32_t hfma2(uint32_t a, uint32_t b, uint32_t c) { uint32_t r; asm("fma.rn.bf16x2 %0, %1, %2, %3;" : "=r"(r) : "r"(a), "r"(b), "r"(c)); return r; }
__device__ __forceinline__ uint32_t lds32(uint32_t a) { uint32_t r; asm volatile("ld.shared.b32 %0, [%1];" : "=r"(r) : "r"(a) : "memory"); return r; }
__device__ __forceinline__ uint4 lds128(uint32_t a) { uint4 r; asm volatile("ld.shared.v4.b32 {%0,%1,%2,%3}, [%4];" : "=r"(r.x), "=r"(r.y), "=r"(r.z), "=r"(r.w) : "r"(a) : "memory"); return r; }
__device__ __forceinline__ uint32_t desc_k(uint32_t addr) { return ((addr & 0x3FFFF) >> 4) | (1u << 16); }
template <int LBO> __device__ __forceinline__ uint32_t desc_mn(uint32_t addr) { return ((addr & 0x3FFFF) >> 4) | ((uint32_t)(LBO >> 4) << 16); }
#define DHI "0x40000040"

#define R8(d, o) "+f"(d[o]), "+f"(d[o + 1]), "+f"(d[o + 2]), "+f"(d[o + 3]), "+f"(d[o + 4]), "+f"(d[o + 5]), "+f"(d[o + 6]), "+f"(d[o + 7])
#define R32(d, o) R8(d, o), R8(d, o + 8), R8(d, o + 16), R8(d, o + 24)
#define R64(d, o) R32(d, o), R32(d, o + 32)
#define L64 "%0,%1,%2,%3,%4,%5,%6,%7,%8,%9,%10,%11,%12,%13,%14,%15,%16,%17,%18,%19,%20,%21,%22,%23,%24,%25,%26,%27,%28,%29,%30,%31," \
            "%32,%33,%34,%35,%36,%37,%38,%39,%40,%41,%42,%43,%44,%45,%46,%47,%48,%49,%50,%51,%52,%53,%54,%55,%56,%57,%58,%59,%60,%61,%62,%63"
#define L128 L64 ",%64,%65,%66,%67,%68,%69,%70,%71,%72,%73,%74,%75,%76,%77,%78,%79,%80,%81,%82,%83,%84,%85,%86,%87,%88,%89,%90,%91,%92,%93,%94,%95," \
            "%96,%97,%98,%99,%100,%101,%102,%103,%104,%105,%106,%107,%108,%109,%110,%111,%112,%113,%114,%115,%116,%117,%118,%119,%120,%121,%122,%123,%124,%125,%126,%127"

template <int TB> __device__ __forceinline__ void mma_ss_n128(float (&d)[64], uint32_t da, uint32_t db) {
  asm volatile("{\n.reg .b64 da, db;\nmov.b64 da, {%64, " DHI "};\nmov.b64 db, {%65, " DHI "};\n"
               "wgmma.mma_async.sync.aligned.m64n128k16.f32.bf16.bf16 {" L64 "}, da, db, 1, 1, 1, 0, %66;\n}\n"
               : R64(d, 0) : "r"(da), "r"(db), "n"(TB));
}
template <int TB> __device__ __forceinline__ void mma_rs_n128(float (&d)[64], uint32_t a0, uint32_t a1, uint32_t a2, uint32_t a3, uint32_t db, int sd) {
  asm volatile("{\n.reg .pred p;\n.reg .b64 db;\nsetp.ne.b32 p, %69, 0;\nmov.b64 db, {%68, " DHI "};\n"
               "wgmma.mma_async.sync.aligned.m64n128k16.f32.bf16.bf16 {" L64 "}, {%64,%65,%66,%67}, db, p, 1, 1, %70;\n}\n"
               : R64(d, 0) : "r"(a0), "r"(a1), "r"(a2), "r"(a3), "r"(db), "r"(sd), "n"(TB));
}
template <int TB> __device__ __forceinline__ void mma_ss_n256(float (&d)[128], uint32_t da, uint32_t db) {
  asm volatile("{\n.reg .b64 da, db;\nmov.b64 da, {%128, " DHI "};\nmov.b64 db, {%129, " DHI "};\n"
               "wgmma.mma_async.sync.aligned.m64n256k16.f32.bf16.bf16 {" L128 "}, da, db, 1, 1, 1, 0, %130;\n}\n"
               : R64(d, 0), R64(d, 64) : "r"(da), "r"(db), "n"(TB));
}
#define W8(d, o) "=f"(d[o]), "=f"(d[o + 1]), "=f"(d[o + 2]), "=f"(d[o + 3]), "=f"(d[o + 4]), "=f"(d[o + 5]), "=f"(d[o + 6]), "=f"(d[o + 7])
#define W32(d, o) W8(d, o), W8(d, o + 8), W8(d, o + 16), W8(d, o + 24)
#define W64(d, o) W32(d, o), W32(d, o + 32)
template <int TB> __device__ __forceinline__ void mma_ss_n128_init(float (&d)[64], uint32_t da, uint32_t db) {
  asm volatile("{\n.reg .b64 da, db;\nmov.b64 da, {%64, " DHI "};\nmov.b64 db, {%65, " DHI "};\n"
               "wgmma.mma_async.sync.aligned.m64n128k16.f32.bf16.bf16 {" L64 "}, da, db, 0, 1, 1, 0, %66;\n}\n"
               : W64(d, 0) : "r"(da), "r"(db), "n"(TB));
}
template <int TB> __device__ __forceinline__ void mma_ss_n256_init(float (&d)[128], uint32_t da, uint32_t db) {
  asm volatile("{\n.reg .b64 da, db;\nmov.b64 da, {%128, " DHI "};\nmov.b64 db, {%129, " DHI "};\n"
               "wgmma.mma_async.sync.aligned.m64n256k16.f32.bf16.bf16 {" L128 "}, da, db, 0, 1, 1, 0, %130;\n}\n"
               : W64(d, 0), W64(d, 64) : "r"(da), "r"(db), "n"(TB));
}
#define L32 "%0,%1,%2,%3,%4,%5,%6,%7,%8,%9,%10,%11,%12,%13,%14,%15,%16,%17,%18,%19,%20,%21,%22,%23,%24,%25,%26,%27,%28,%29,%30,%31"
__device__ __forceinline__ void mma_ss_n64(float (&d)[32], uint32_t da, uint32_t db) {
  asm volatile("{\n.reg .b64 da, db;\nmov.b64 da, {%32, " DHI "};\nmov.b64 db, {%33, " DHI "};\n"
               "wgmma.mma_async.sync.aligned.m64n64k16.f32.bf16.bf16 {" L32 "}, da, db, 1, 1, 1, 0, 0;\n}\n"
               : R32(d, 0) : "r"(da), "r"(db));
}
__device__ __forceinline__ void mma_ss_n64_init(float (&d)[32], uint32_t da, uint32_t db) {
  asm volatile("{\n.reg .b64 da, db;\nmov.b64 da, {%32, " DHI "};\nmov.b64 db, {%33, " DHI "};\n"
               "wgmma.mma_async.sync.aligned.m64n64k16.f32.bf16.bf16 {" L32 "}, da, db, 0, 1, 1, 0, 0;\n}\n"
               : W32(d, 0) : "r"(da), "r"(db));
}
#define L16 "%0,%1,%2,%3,%4,%5,%6,%7,%8,%9,%10,%11,%12,%13,%14,%15"
template <int O, bool INIT> __device__ __forceinline__ void mma_rs_n32(float (&d)[128], uint32_t a0, uint32_t a1, uint32_t a2, uint32_t a3, uint32_t db) {
  if (INIT) asm volatile("{\n.reg .b64 db;\nmov.b64 db, {%20, 0x00000008};\n"
               "wgmma.mma_async.sync.aligned.m64n32k16.f32.bf16.bf16 {" L16 "}, {%16,%17,%18,%19}, db, 0, 1, 1, 0;\n}\n"
               : W8(d, O), W8(d, O + 8) : "r"(a0), "r"(a1), "r"(a2), "r"(a3), "r"(db));
  else asm volatile("{\n.reg .b64 db;\nmov.b64 db, {%20, 0x00000008};\n"
               "wgmma.mma_async.sync.aligned.m64n32k16.f32.bf16.bf16 {" L16 "}, {%16,%17,%18,%19}, db, 1, 1, 1, 0;\n}\n"
               : R8(d, O), R8(d, O + 8) : "r"(a0), "r"(a1), "r"(a2), "r"(a3), "r"(db));
}
template <int S, int J> __device__ __forceinline__ void conv_step(float (&d)[128], const uint32_t (&a)[64], uint32_t db) {
  if constexpr (J >= 0 && J >= (S >> 1)) {
    mma_rs_n32<16 * J, S == 0>(d, a[4 * S], a[4 * S + 1], a[4 * S + 2], a[4 * S + 3], db + (uint32_t)((2 * J - S) * 16));
    conv_step<S, J - 1>(d, a, db);
  }
}
__device__ __forceinline__ void mma_ss_n8(float (&d)[4], uint32_t da, uint32_t db) {
  asm volatile("{\n.reg .b64 da, db;\nmov.b64 da, {%4, " DHI "};\nmov.b64 db, {%5, 0x00000008};\n"
               "wgmma.mma_async.sync.aligned.m64n8k16.f32.bf16.bf16 {%0,%1,%2,%3}, da, db, 1, 1, 1, 0, 0;\n}\n"
               : "+f"(d[0]), "+f"(d[1]), "+f"(d[2]), "+f"(d[3]) : "r"(da), "r"(db));
}
template <int N> __device__ __forceinline__ void reg_fence(float (&d)[N]) {
#pragma unroll
  for (int i = 0; i < N; i++) asm volatile("" : "+f"(d[i])::"memory");
}
template <int N> __device__ __forceinline__ void reg_fence(uint32_t (&d)[N]) {
#pragma unroll
  for (int i = 0; i < N; i++) asm volatile("" : "+r"(d[i])::"memory");
}

struct __align__(64) Params {
  unsigned* flags;
  int zero;
  uint8_t pref[128];
  const __nv_bfloat16 *gate_w, *ak, *av, *shk, *ssk, *ssd;
  CUtensorMap x, c, wq, wuk, wuv, wo, x3, y3, out, w;
};

template <int O, int N, int M> __device__ __forceinline__ void pack_frag(const float (&acc)[N], uint32_t (&pk)[M]) {
#pragma unroll
  for (int i = 0; i < 32; i++) pk[i] = pack_bf16(acc[O + 2 * i], acc[O + 2 * i + 1]);
}
template <int J0 = 0, int J1 = 8, int M> __device__ __forceinline__ void stsm_frag(const uint32_t (&pk)[M], uint32_t a) {
#pragma unroll
  for (int jj = J0; jj < J1; jj++)
    asm volatile("stmatrix.sync.aligned.m8n8.x4.shared.b16 [%0], {%1,%2,%3,%4};" ::"r"((a ^ ((jj & 3) << 5)) + (jj >> 2) * 16384),
                 "r"(pk[4 * jj]), "r"(pk[4 * jj + 1]), "r"(pk[4 * jj + 2]), "r"(pk[4 * jj + 3]) : "memory");
}

template <int N> __device__ __forceinline__ void store_scaled(const float (&acc)[N], float s0, float s1, uint32_t a, uint32_t never_zero) {
  float t[8];
#pragma unroll
  for (int jj = 0; jj < 8; jj++) {
    float v = acc[8 * jj] * s0;
    if (jj >= RST) {
      v = t[jj - RST];
      asm("{\n.reg .pred p;\nsetp.ne.u32 p, %3, 0;\n@p mul.f32 %0, %1, %2;\n}\n" : "+f"(v) : "f"(acc[8 * jj]), "f"(s0), "r"(never_zero));
    }
    const uint32_t q = pack_bf16(v, acc[8 * jj + 1] * s0);
    t[jj] = __uint_as_float(q);
    asm volatile("stmatrix.sync.aligned.m8n8.x4.shared.b16 [%0], {%1,%2,%3,%4};" ::"r"((a ^ ((jj & 3) << 5)) + (jj >> 2) * 16384), "r"(q),
                 "r"(pack_bf16(acc[8 * jj + 2] * s1, acc[8 * jj + 3] * s1)), "r"(pack_bf16(acc[8 * jj + 4] * s0, acc[8 * jj + 5] * s0)),
                 "r"(pack_bf16(acc[8 * jj + 6] * s1, acc[8 * jj + 7] * s1)) : "memory");
  }
}

struct Cons {
  uint32_t sb;
  uint32_t pf;
  int wg, tid;
  __device__ __forceinline__ void wait_full(int g) { mbar_wait(sb + SM_BAR + (B_FULL + g) * 8, (pf >> g) & 1); pf ^= 1u << g; }
  uint32_t relb;
  __device__ __forceinline__ void release(int g, int n) {
    if (tid < 2 * n) asm volatile("mbarrier.arrive.shared::cluster.b64 _, [%0];" ::"r"(relb + g * 8) : "memory");
  }
  __device__ __forceinline__ void turn_begin() { bar_sync(1 + wg, 256); }
  __device__ __forceinline__ void turn_end() { bar_arrive(2 - wg, 256); }
  __device__ __forceinline__ void staged(int e) { __syncwarp(); if ((tid & 31) == 0) mbar_arrive(sb + SM_BAR + (B_EV + 2 * e + wg) * 8); }
  int zero;
  int rnd;
  uint32_t pfree;
  __device__ __forceinline__ void wait_stage_free() { mbar_wait(sb + SM_BAR + (B_FREE + wg) * 8, pfree); pfree ^= 1; }
  __device__ __forceinline__ bool try_full(int g) { return mbar_test(sb + SM_BAR + (B_FULL + g) * 8, (pf >> g) & 1); }
};

constexpr float SM_C = 0.08838834764831845f * 1.4426950408889634f;
struct SoftState { float m0, m1, l0, l1; int shifted; };
__device__ __forceinline__ void ex2_rot(float& t, float s, uint32_t never_zero) {
  asm("{\n.reg .pred p;\nsetp.ne.u32 p, %2, 0;\n@p ex2.approx.ftz.f32 %0, %1;\n}\n" : "+f"(t) : "f"(s), "r"(never_zero));
}
__device__ __forceinline__ void pin(float a, uint32_t never_zero) {
  asm volatile("{\n.reg .pred p;\nsetp.eq.u32 p, %1, 0;\n@p st.shared.f32 [%1], %0;\n}\n" ::"f"(a), "r"(never_zero) : "memory");
}
template <int O, int N> __device__ __forceinline__ void reg_fence_part(uint32_t (&d)[32]) {
#pragma unroll
  for (int i = O; i < O + N; i++) asm volatile("" : "+r"(d[i])::"memory");
}
template <int Q, int W, int N> __device__ __forceinline__ void exp_quarter(const float (&S)[N], uint32_t (&P)[32], float (&t)[ROT], float& s0, float& s1, uint32_t nz) {
#pragma unroll
  for (int i = 8 * Q; i < 8 * Q + 8; i++) {
    float& a = t[(2 * i) % ROT];
    float& b = t[(2 * i + 1) % ROT];
    if (2 * i < ROT) { a = ex2(S[2 * i]); b = ex2(S[2 * i + 1]); }
    else { ex2_rot(a, S[2 * i], nz); ex2_rot(b, S[2 * i + 1], nz); }
    if (i < 2) { if (i) s1 = a + b; else s0 = a + b; }
    else if (SUMV == 0) { if (i & 1) { s1 += a; s1 += b; } else { s0 += a; s0 += b; } }
    else { if (i & 1) s1 += a + b; else s0 += a + b; }
    if (i == 8 * Q) { pin(EXPV == 1 && Q ? s1 : s0, nz); wg_wait<W>(); reg_fence_part<8 * Q, 8>(P); }
    P[i] = pack_bf16(a, b);
  }
}
template <int N> __device__ __forceinline__ void shift_scores(float (&S)[N], float d0, float d1) {
#pragma unroll
  for (int i = 0; i < N; i++) S[i] -= (i & 2) ? d1 : d0;
}
__device__ __forceinline__ bool soft_high(float s0, float s1, float lim = SM_LIMIT) { return s0 > lim || s1 > lim; }
__device__ __forceinline__ bool soft_unsafe(float s0, float s1, bool first) {
  uint32_t b0 = __ballot_sync(0xffffffffu, s0 >= SM_LOW), b1 = __ballot_sync(0xffffffffu, s1 >= SM_LOW);
  b0 |= b0 >> 1; b0 |= b0 >> 2; b1 |= b1 >> 1; b1 |= b1 >> 2;
  return __any_sync(0xffffffffu, soft_high(s0, s1)) || (first && (b0 & b1 & 0x11111111u) != 0x11111111u);
}
template <int N> __device__ __forceinline__ void soft_fix(const float (&S)[N], float (&O)[64], SoftState& z, bool first, float& d0, float& d1) {
  d0 = d1 = first ? -INFINITY : 0.f;
#pragma unroll
  for (int j = 0; j < N / 4; j++) { d0 = fmaxf(d0, fmaxf(S[4 * j], S[4 * j + 1])); d1 = fmaxf(d1, fmaxf(S[4 * j + 2], S[4 * j + 3])); }
  d0 = fmaxf(d0, __shfl_xor_sync(0xffffffffu, d0, 1)); d1 = fmaxf(d1, __shfl_xor_sync(0xffffffffu, d1, 1));
  d0 = fmaxf(d0, __shfl_xor_sync(0xffffffffu, d0, 2)); d1 = fmaxf(d1, __shfl_xor_sync(0xffffffffu, d1, 2));
  const float sc0 = ex2(-fmaxf(d0, 0.f)), sc1 = ex2(-fmaxf(d1, 0.f));
  z.m0 += d0; z.m1 += d1; z.l0 *= sc0; z.l1 *= sc1; z.shifted = 1;
#pragma unroll
  for (int j = 0; j < 16; j++) { O[4 * j] *= sc0; O[4 * j + 1] *= sc0; O[4 * j + 2] *= sc1; O[4 * j + 3] *= sc1; }
}
template <int N> __device__ __forceinline__ void mask_diag(float (&S)[N], float nd) {
  asm volatile("" : "+f"(nd));
#pragma unroll
  for (int i = 0; i < 32; i++) {
    const float beyond = __saturatef(nd + (float)(8 * (i >> 2) + (i & 1) - 4 * (i & 2)));
    S[N - 32 + i] = fmaf(beyond, -3.0e38f, S[N - 32 + i]);
  }
}
__device__ __forceinline__ float quad_sum(float v) {
  v += __shfl_xor_sync(0xffffffffu, v, 1);
  v += __shfl_xor_sync(0xffffffffu, v, 2);
  return v;
}
__device__ __forceinline__ void issue_qk(float (&S)[64], uint32_t dq, uint32_t dk) {
  mma_ss_n128_init<0>(S, dq, dk);
#pragma unroll
  for (int s = 1; s < 8; s++) mma_ss_n128<0>(S, dq + (s >> 2) * 1024 + (s & 3) * 2, dk + (s >> 2) * 1024 + (s & 3) * 2);
}
__device__ __forceinline__ void issue_qk(float (&S)[32], uint32_t dq, uint32_t dk) {
  mma_ss_n64_init(S, dq, dk);
#pragma unroll
  for (int s = 1; s < 8; s++) mma_ss_n64(S, dq + (s >> 2) * 1024 + (s & 3) * 2, dk + (s >> 2) * 1024 + (s & 3) * 2);
}
template <int H> __device__ __forceinline__ void issue_pv(float (&O)[64], const uint32_t (&P)[32], uint32_t dv, int acc, bool on) {
  if (on) {
#pragma unroll
    for (int s = 4 * H; s < 4 * H + 4; s++) {
      mma_rs_n128<1>(O, P[4 * s], P[4 * s + 1], P[4 * s + 2], P[4 * s + 3], dv + s * 128, s != 0 ? 1 : acc);
      if (s & 1) wg_commit();
    }
  } else { wg_commit(); wg_commit(); }
}
constexpr uint32_t DG = GR >> 4;
__device__ __forceinline__ void stage_q2(Cons& c, const float (&O)[64], uint32_t (&P)[32], uint32_t stg) {
  wg_commit(); wg_commit(); wg_commit(); wg_commit();
  c.turn_end();
  pack_frag<0>(O, P);
  stsm_frag(P, stg);
  fence_async_smem();
}
__device__ __forceinline__ void attn_half(Cons& c, float (&O)[64], uint32_t (&P)[32], SoftState& z, uint32_t dk0, uint32_t dkk, uint32_t dv0, float dmask, int last) {
  float S[32];
  FTH(8 + last * 32, 0);
  c.turn_begin();
  FTH(9 + last * 32, 0);
  wg_fence();
  issue_qk(S, dk0 + (last ? 0 : 2 * DG), dkk + (last ? 8 : 4) * DG);
  wg_commit();
  issue_pv<0>(O, P, dv0 + 10 * DG, 1, last);
  issue_pv<1>(O, P, dv0 + 10 * DG, 1, last);
  c.turn_end();
  c.wait_full(last ? 12 : 6);
  FTH(10 + last * 32, 0);
  wg_wait<4>();
  reg_fence(S);
  FTH(11 + last * 32, 0);
  c.release(last ? 8 : 4, 2);
  mask_diag(S, dmask);
  float s0, s1, d0 = z.m0, d1 = z.m1;
#pragma unroll 1
  for (int pass = 0;; pass++) {
    if (z.shifted) shift_scores(S, d0, d1);
    float tr[ROT];
    exp_quarter<0, 3>(S, P, tr, s0, s1, c.sb);
    exp_quarter<1, 2>(S, P, tr, s0, s1, c.sb);
    pin(s1, c.sb); wg_wait<0>(); reg_fence_part<16, 16>(P); reg_fence(O);
    if (!soft_unsafe(s0, s1, !last) || pass) break;
    soft_fix(S, O, z, !last, d0, d1);
  }
  FTH(12 + last * 32, 0);
  z.l0 += s0; z.l1 += s1;
  c.release(10, last ? 2 : 0);
  if (!last) c.wait_full(8);
  FTH(13 + last * 32, 0);
}

template <int V> struct IC { static constexpr int value = V; };
__device__ __forceinline__ int conv_next(int g, bool spare) { return g >= NGR - 2 ? g - (NGR - 4) : !spare && g == 4 ? 1 : g + 2; }
__device__ __forceinline__ void conv_final(uint32_t rb, uint32_t yb, bool on) {
  const uint4 q0 = lds128(rb), q1 = lds128(rb + 4096), q2 = lds128(rb + 8192), q3 = lds128(rb + 12288);
  auto fin = [&](uint32_t x0, uint32_t x1, uint32_t x2, uint32_t x3) { return hadd2(hadd2(x0, x1), hadd2(x2, x3)); };
  asm volatile("{\n.reg .pred p;\nsetp.ne.b32 p, %5, 0;\n@p st.shared.v4.b32 [%0], {%1,%2,%3,%4};\n}\n" ::"r"(yb), "r"(fin(q0.x, q1.x, q2.x, q3.x)),
               "r"(fin(q0.y, q1.y, q2.y, q3.y)), "r"(fin(q0.z, q1.z, q2.z, q3.z)), "r"(fin(q0.w, q1.w, q2.w, q3.w)), "r"((int)on) : "memory");
}
__device__ __forceinline__ void conv_tasks(Cons& c, const Params& p, int ntask, bool spare, int ch, int chstep, int c5, uint32_t dd, uint32_t dkk, int w, int lane) {
  const uint32_t sb = c.sb;
  int g = 2 + c.wg;
  uint32_t rb = sb + g * GR;
  const uint32_t yb = sb + c.wg * 8192 + c.tid * 16;
  const int gt = 8 * w + (lane >> 2) + (lane & 3);
  uint32_t a[64], hb;
  auto lda = [&](int s) {
    a[4 * s] = lds32(hb + s * 256); a[4 * s + 1] = lds32(hb + s * 256 + 128);
    a[4 * s + 2] = lds32(hb + s * 256 + 16); a[4 * s + 3] = lds32(hb + s * 256 + 144);
  };
  auto first_a = [&]() {
    hb = sb + g * GR + WBYTES - 28 + gt * 4;
    lda(0); lda(15);
  };
  c.wait_full(g);
  first_a();
#pragma unroll 1
  for (int i = 0; i < ntask; i++) {
    const uint32_t base = sb + g * GR;
    FTC(0);
    lda(1); lda(14);
    a[0] = hadd2(a[0], gt == 7 ? dd : 0u); a[2] = hadd2(a[2], gt == 3 ? dd : 0u);
    float acc[128];
    const uint32_t db = dkk + ((WPL / 16 - 1) << 16) + g * DG + WZ / 16;
    FTC(2);
    c.turn_begin();
    FTC(3);
    auto pair = [&](auto kc) {
      constexpr int k = decltype(kc)::value;
      if (k < 7) wg_fence();
      if (k == 6) c.turn_end();
      conv_step<k, 7>(acc, a, db);
      conv_step<15 - k, 7>(acc, a, db);
      if (k < 6) { lda(k + 2); lda(13 - k); }
      if (k == 0) conv_final(rb, yb, i > 0);
      if (k == 1) {
        conv_final(rb + 2048, yb + 2048, i > 0);
        __syncwarp();
        if (lane == 0 && i > 0) mbar_arrive(sb + SM_BAR + (B_EV + c.wg) * 8);
      }
      if (k == 6) dd = __bfloat16_as_ushort(p.ssd[(ch + chstep + (i == 1 ? c5 : 0)) & (DM - 1)]);
    };
    pair(IC<0>()); pair(IC<1>()); pair(IC<2>()); pair(IC<3>()); pair(IC<4>()); pair(IC<5>()); pair(IC<6>()); pair(IC<7>());
    wg_commit();
    FTC(4);
    g = conv_next(g, spare);
    ch += chstep;
    rb = base + c.tid * 16;
    if (i + 1 < ntask) c.wait_full(g);
    const bool fr = mbar_test(sb + SM_BAR + (B_FREE + c.wg) * 8, c.pfree);
    wg_wait<0>();
    reg_fence(acc);
    reg_fence(a);
    bar_sync(3 + c.wg, 128);
    FTC(5);
    first_a();
    const int tw = (lane & 3) + w;
    const uint32_t xb = base + w * 4096 + tw * 32 + (lane >> 2) * 4;
    [[maybe_unused]] float t0[EROT + 1];
#pragma unroll
    for (int j = 0; j < 32; j++) {
      uint32_t ad = xb + j * 128;
      float v0 = acc[4 * j], v1 = acc[4 * j + 1];
      if (EROT && j > EROT) {
        v0 = t0[j % (EROT + 1)];
        asm("{\n.reg .pred p;\nsetp.ne.u32 p, %3, 0;\n@p add.f32 %0, %1, %2;\n}\n" : "+f"(v0) : "f"(acc[4 * j]), "f"(acc[j > 0 ? 4 * j - 2 : 0]), "r"(sb));
      } else if (j > 0) v0 += acc[j > 0 ? 4 * j - 2 : 0];
      if (j > 0) v1 += acc[j > 0 ? 4 * j - 1 : 0];
      uint32_t v = pack_bf16(v0, v1);
      t0[j % (EROT + 1)] = __uint_as_float(v);
      if (j == 31 && tw >= 4) { v = 0; ad -= 4096; }
      asm volatile("st.shared.b32 [%0], %1;" ::"r"(ad), "r"(v) : "memory");
    }
    if (!fr) c.wait_stage_free(); else c.pfree ^= 1;
    FTC(6);
  }
  bar_sync(3 + c.wg, 128);
  conv_final(rb, yb, true);
  conv_final(rb + 2048, yb + 2048, true);
  c.staged(0);
}

__global__ void __cluster_dims__(2, 1, 1) __launch_bounds__(NTHREADS, 1) mega_kernel(const __grid_constant__ Params p) {
  extern __shared__ __align__(1024) uint8_t smem_raw[];
  FTS(0);
  const uint32_t sb = smem_u32(smem_raw);
  if (threadIdx.x - 64 < 32) { prefetch_tm(&p.c); prefetch_tm(&p.wuk + (blockIdx.x & 1)); }
  const int wgi = __shfl_sync(0xffffffffu, threadIdx.x >> 7, 0);
  const int warp = __shfl_sync(0xffffffffu, threadIdx.x >> 5, 0);
  const uint32_t rank = blockIdx.x & 1;
  int slot;
  {
    uint32_t smid; asm volatile("mov.u32 %0, %smid;" : "=r"(smid));
    slot = p.pref[((smid >> 1) + (threadIdx.x & (smid >> 16))) & 127];
  }
  if (warp >= 3) {
    if (elect()) {
#pragma unroll
      for (int k = 0; k < 4; k++) mbar_init(sb + SM_BAR + ((warp - 3) * 4 + k) * 8, k == 1 && warp == 7 ? 11 : warp < (k ? 7 : 8) ? 1 : 4);
      if (warp == 7) { mbar_init(sb + SM_BAR + B_TICK * 8, 1); mbar_expect_tx(sb + SM_BAR + B_SLOT * 8, 8); mbar_expect_tx(sb + SM_BAR + B_TICK * 8, 4); }
      asm volatile("fence.mbarrier_init.release.cluster;" ::: "memory");
    }
    __syncwarp();
  }
  FTS(1);
  cluster_arrive();
  slot = __shfl_sync(0xffffffffu, slot, 0);
  const int pref = slot;
  if (warp < 4) {
    asm volatile("setmaxnreg.dec.sync.aligned.u32 40;");
    if (warp == 1 + 4 * rank) {
      unsigned taken = threadIdx.x == 32;
#pragma unroll 1
      for (int n = 0; n < NSLOT; n++) {
        asm volatile("{\n.reg .pred p;\nsetp.ne.b32 p, %0, 0;\n@p atom.relaxed.gpu.global.exch.b32 %0, [%1], 1;\n}\n" : "+r"(taken) : "l"(CLAIMP(slot)) : "memory");
        if (!__any_sync(0xffffffffu, taken)) break;
        slot = slot == NSLOT - 1 ? 0 : slot + 1;
      }
    }
    cluster_wait();
    if (threadIdx.x == 32) {
      send_both(sb + SM_BAR + B_SLOT * 8, (V_SLOT - B_SLOT) * 8 + rank * 4, slot | pref << 8);
    }
    if (warp == 2) {
#pragma unroll 1
      for (int kk = 0; kk < 4; kk++) {
        const int g0 = 2 + 3 * kk;
        const uint32_t fb = sb + SM_BAR + (B_FULL + g0) * 8;
        if (elect()) {
          FTSW(kk);
          mbar_expect_tx(fb, 3 * GR);
          tma2d(sb + g0 * GR, &p.c, kk * 64, (KV_ROW(pref & 7, 0) + rank) * 128, fb);
          tma3d_mc(sb + (g0 + 1 + rank) * GR, rank ? &p.wuv : &p.wuk, 0, kk * 64, ((pref & 56) >> 1) + 2 * KV_HEAD(pref & 7, 0), fb);
        }
        if (kk < 3) {
          uint32_t c0, c1;
          asm volatile("mov.u32 %0, %clock;" : "=r"(c0));
          do asm volatile("mov.u32 %0, %clock;" : "=r"(c1)); while (c1 - c0 < (kk ? X_D2 : X_DELAY));
        }
      }
      FTSW(4);
      prefetch_tm(&p.x); prefetch_tm(&p.wq);
    }
  }
  int grp, idx, lb;
  int cn, cch, cstep;
  bool spare, redo;
  auto get_slot = [&]() {
    mbar_wait(sb + SM_BAR + B_SLOT * 8, 0);
    const uint32_t sv0 = __shfl_sync(0xffffffffu, lds32(sb + SM_BAR + V_SLOT * 8), 0), sv1 = __shfl_sync(0xffffffffu, lds32(sb + SM_BAR + V_SLOT * 8 + 4), 0);
    grp = (sv0 & 255) >> 3; idx = sv0 & 7; lb = (sv0 & 255) * 2 + rank;
    spare = grp == 8; redo = spare || sv0 != sv1;
    cn = CN_SPARE; cch = spare ? lb - NMAIN : 4 * CN_SPARE + 4 * lb; cstep = spare ? 4 : 1;
    if (FINE_MODE != 7) TS(0);
  };
  auto get_ticket = [&]() {
    mbar_wait(sb + SM_BAR + B_TICK * 8, 0);
    const int tk = __shfl_sync(0xffffffffu, lds32(sb + SM_BAR + V_TICK * 8), 0);
    cn = tk < NTICK ? 5 : 4;
    return 4 * NMAIN - 4 * lb - 4 + 2 * tk + rank;
  };

  if (wgi == 0) {
    asm volatile("setmaxnreg.dec.sync.aligned.u32 40;");
    const int lane = threadIdx.x & 31;
    cluster_arrive();
    get_slot();
    uint32_t pe = 0;
    auto acquire = [&](int g, int n, uint32_t m) {
      int i = g;
#pragma unroll 1
      do mbar_wait1(sb + SM_BAR + (B_EMPTY + i) * 8, (pe >> i) & 1); while (++i < g + n);
      pe ^= m << g;
    };
    if (warp == 3) {
      if (!spare) {
        const int s0 = lb * 16;
#pragma unroll 1
        for (int cg = 0; cg < 16; cg++) {
          if (cg == UP0 || cg == UP1) {
#pragma unroll 1
            for (int n = 0; n < 20 && !__any_sync(0xffffffffu, mbar_try(sb + SM_BAR + B_SLOT * 8, cg == UP0)); n++);
          } else if (cg < UP0) __nanosleep(US0);
          if (cg == UP1 && lane == rank * 32) send_both(sb + SM_BAR + B_TICK * 8, (V_TICK - B_TICK) * 8, atomicInc(FLAG(F_TICK), 0x7fffffffu));
          const int ch = cg * 64 + 2 * lane;
          const uint32_t* kp = reinterpret_cast<const uint32_t*>(p.ak + (size_t)s0 * DM + ch);
          const uint32_t* vp = reinterpret_cast<const uint32_t*>(p.av + (size_t)s0 * DM + ch);
          const uint4 sw = __ldg(reinterpret_cast<const uint4*>(p.shk + ch * 4));
          uint32_t k3 = 0, k2 = 0, k1 = 0, k0 = 0, up = 0;
          if (lb > 0) { k3 = ldg_stream(kp - 4 * 512); k2 = ldg_stream(kp - 3 * 512); k1 = ldg_stream(kp - 2 * 512); k0 = ldg_stream(kp - 512); up = ldg_stream(vp - 512); }
          const uint32_t w0 = __byte_perm(sw.x, sw.z, 0x5410), w1 = __byte_perm(sw.x, sw.z, 0x7632);
          const uint32_t w2 = __byte_perm(sw.y, sw.w, 0x5410), w3 = __byte_perm(sw.y, sw.w, 0x7632);
          up = hmul2(hfma2(k0, w0, hfma2(k1, w1, hfma2(k2, w2, hmul2(k3, w3)))), up);
#pragma unroll 1
          for (int hb = 0; hb < 2; hb++) {
            uint32_t kk[8], u[8];
#pragma unroll
            for (int r = 0; r < 8; r++) { kk[r] = ldg_stream(kp + r * 512); u[r] = ldg_stream(vp + r * 512); }
#pragma unroll
            for (int r = 0; r < 8; r++) {
              k3 = k2; k2 = k1; k1 = k0; k0 = kk[r];
              u[r] = hmul2(hfma2(k0, w0, hfma2(k1, w1, hfma2(k2, w2, hmul2(k3, w3)))), u[r]);
            }
            if (lane == 0) asm volatile("cp.async.bulk.wait_group.read 0;" ::: "memory");
            __syncwarp();
            const uint32_t dst = sb + SM_UST + lane * 32 + ((lane & 4) << 2);
#pragma unroll
            for (int cc = 0; cc < 2; cc++) {
              const uint32_t sel = cc ? 0x7632 : 0x5410;
              asm volatile("st.shared.v4.b32 [%0], {%1,%2,%3,%4};" ::"r"(dst + cc * 1024), "r"(__byte_perm(u[6], u[5], sel)), "r"(__byte_perm(u[4], u[3], sel)),
                           "r"(__byte_perm(u[2], u[1], sel)), "r"(__byte_perm(u[0], up, sel)) : "memory");
              asm volatile("st.shared.v4.b32 [%0], {%1,%2,%3,%4};" ::"r"((dst ^ 16) + cc * 1024), "r"(__byte_perm(u[7], u[6], sel)), "r"(__byte_perm(u[5], u[4], sel)),
                           "r"(__byte_perm(u[3], u[2], sel)), "r"(__byte_perm(u[1], u[0], sel)) : "memory");
            }
            fence_async_smem();
            __syncwarp();
            if (lane == 0) {
              asm volatile("cp.async.bulk.tensor.3d.global.shared::cta.bulk_group.L2::cache_hint [%0, {%2, %3, %4}], [%1], %5;\ncp.async.bulk.commit_group;"
                           ::"l"(&p.w), "r"(sb + SM_UST), "r"(WZ / 2 + lb * 16 + (hb ^ 1) * (WPL / 2)), "r"(cg * 32), "r"(0), "l"(cg >= UP0 && cg < UP1 ? EV_FIRST : EV_NORMAL) : "memory");
            }
            up = u[7];
            kp += 8 * 512; vp += 8 * 512;
          }
          if ((cg & (cg + 1)) == 0 && lane == 0) {
            asm volatile("cp.async.bulk.wait_group 0;" ::: "memory");
            fence_release();
            flag_add(FLAG(F_U + 32 - __clz(cg)));
          }
          TSW(10 + cg);
        }
        prefetch_tm(&p.wo); prefetch_tm(&p.x3); prefetch_tm(&p.y3); prefetch_tm(&p.out);
      } else {
#pragma unroll 1
        for (int i = 0, g = 2; i < 32; i++) {
          acquire(g, 2, 3);
          if (elect()) {
            const uint32_t fb = sb + SM_BAR + (B_FULL + g) * 8;
            if (i == 0) { mbar_expect_tx(fb - 8, 2048); bulk_g2s(sb + GR, p.gate_w, 2048, fb - 8); }
            mbar_expect_tx(fb, 2 * GR);
            tma3d(sb + g * GR, &p.x3, 0, (lb - NMAIN) * 512 + (i >> 3) * 128, (i & 7) * 2, fb);
          }
          g = g == NGR - 2 ? 2 : g + 2;
        }
        bar_arrive(5, 64);
      }
      unsigned long long t0, t1;
      asm volatile("mov.u64 %0, %globaltimer;" : "=l"(t0));
      auto check = [&]() {
        asm volatile("mov.u64 %0, %globaltimer;" : "=l"(t1));
        if (t1 - t0 > 2000000000ull) __trap();
      };
      if (!spare) {
        unsigned v;
        do {
          __nanosleep(PSL);
          check();
          asm volatile("ld.acquire.gpu.global.u32 %0, [%1];" : "=r"(v) : "l"(FLAG(lane & 1 ? F_Y + idx : F_GATE)) : "memory");
        } while (__any_sync(0xffffffffu, v < (lane & 1 ? 128 : 32)));
        __syncwarp();
        if (lane == 0) mbar_arrive(sb + SM_BAR + B_SLOT * 8);
      }
      if (lane == 0) {
        while (!mbar_try(sb + SM_BAR + B_DONE * 8, 0)) check();
      }
    } else if (warp != 0) {
      const int w = warp - 1;
      int ne = 12 + (CN_SPARE + 1 - w) / 2, c5 = 0;
      uint32_t p0 = 0;
      int cg = 2 + w, ch = cch + w * cstep;
#pragma unroll 1
      for (int e = spare ? 12 : 0; e < ne; e++) {
        const int rnd = e >= 6, k = e - 6 * rnd, rt = k == 4 ? idx : 15 - idx;
        uint8_t* dst = k < 4 ? g_kv + (size_t)(((k & 1) * 16 + 2 * grp + KV_HEAD(idx, k >> 1)) * 16 + KV_ROW(idx, k >> 1) + rank) * 32768 + w * 8192
                     : k < 6 ? g_cimg + (size_t)(rt * 32 + 16 * rnd + 2 * grp + rank) * 32768 + (w ^ (k & 1)) * 8192
                             : reinterpret_cast<uint8_t*>(g_yT + (size_t)ch * SEQ);
        const uint32_t src = sb + w * 8192 + (k == 4 ? 2 * GR : 0);
        if (e == 11) { c5 = get_ticket(); ne = 12 + ((cn + 1 - w) >> 1); }
        if (e == 6) flag_wait(FLAG(F_AD + grp), 32);
        mbar_wait1(sb + SM_BAR + (B_EV + (k == 4 ? 2 : 0) + w) * 8, k == 4 ? rnd : p0);
        if (k != 4) p0 ^= 1;
        if (lane < 4 && k >= 6 && (!spare || e < ne - 6)) mbar_arrive_cluster(sb + SM_BAR + (B_EMPTY + cg) * 8, lane & 1);
        fence_async_smem();
        if (elect()) {
          const uint32_t cs = k >= 6 ? 4096 : 1024;
#pragma unroll 1
          for (uint32_t i = 0; i < (k >= 6 ? 4096 : 16384); i += cs) {
            const uint32_t o = i + (i & 8192);
            asm volatile("cp.async.bulk.global.shared::cta.bulk_group.L2::cache_hint [%0], [%1], %2, %3;" ::"l"(dst + o), "r"(src + o), "r"(cs),
                         "l"(e == 4 || e == 5 || spare ? EV_FIRST : EV_NORMAL) : "memory");
            asm volatile("cp.async.bulk.commit_group;\ncp.async.bulk.wait_group.read 1;" ::: "memory");
          }
          asm volatile("cp.async.bulk.wait_group 0;" ::: "memory");
          if (k != 4) mbar_arrive(sb + SM_BAR + (B_FREE + w) * 8);
        }
        __syncwarp();
        if (lane < (k == 4 ? 4 : e == 11 || (e == ne - 1 && !spare) ? 2 : 0))
          mbar_arrive_cluster(sb + SM_BAR + (B_EMPTY + (k == 4 ? 2 : e == 11) + (lane >> 1)) * 8, lane & 1);
        if (k >= 3) {
          fence_release();
          const unsigned fl = k == 3 ? F_KV + rnd * 8 + grp : k < 6 ? F_CTX + rt * 2 + rnd : F_Y + ((unsigned)ch >> 7);
          if (lane <= (e == 5)) flag_add(FLAG(lane ? F_AD + grp : fl));
        }
        if (k >= 6) { cg = conv_next(cg, spare); ch += 2 * cstep + (k == 7 ? c5 : 0); }
      }
      if (lane == 0) mbar_arrive(sb + SM_BAR + B_DONE * 8);
    } else {
#pragma unroll 1
      for (int rnd = 0; rnd < (spare ? 0 : 2); rnd++) {
        const int hp = 16 * rnd + 2 * grp, head = hp + rank;
#pragma unroll 1
        for (int kk = rnd || redo ? 0 : 4; kk < 32; kk++) {
          const int g0 = 2 + 3 * (kk & 3);
          acquire(g0, kk < 4 ? 3 : 1, 7);
          if (elect()) {
            const uint32_t fb = sb + SM_BAR + (B_FULL + g0) * 8;
            mbar_expect_tx(fb, 3 * GR);
            if (kk < 16) {
              tma2d_p(sb + g0 * GR, &p.c, (kk & 7) * 64, (KV_ROW(idx, kk >> 3) + rank) * 128, fb, rnd);
              tma3d_mc_p(sb + (g0 + 1 + rank) * GR, rank ? &p.wuv : &p.wuk, 0, (kk & 7) * 64, (hp + KV_HEAD(idx, kk >> 3)) * 2, fb, kk >= 8);
            } else {
              tma2d_mc(sb + (g0 + rank) * GR, &p.x, (kk - 16) * 64, (rank ? 15 - idx : idx) * 128, fb);
              tma3d<true>(sb + (g0 + 2) * GR, &p.wq, 0, (kk - 16) * 64, head * 2, fb);
            }
          }
        }
        flag_wait(FLAG(F_KV + rnd * 8 + grp), 32);
        fence_async_all();
        acquire(2, 1, 3);
        int g0 = 4;
#pragma unroll 1
        for (int n = 0; n < 36; n += n == 0 || n == 33 ? 2 : 1) {
          const int it = (n >> 1) - (n & 1);
          const int blk = it & 15 ? (it <= idx ? it - 1 : 15 - it) : it ? 15 - idx : idx;
          acquire(g0, n < 6 ? 2 : 1, 3);
          if (elect()) {
            const uint32_t fb = sb + SM_BAR + (B_FULL + g0) * 8;
            if (n == 5) mbar_arrive(sb + SM_BAR + B_SLOT * 8);
            mbar_expect_tx(fb, 2 * GR);
            asm volatile("cp.async.bulk" TMA_MB ".L2::cache_hint [%0], [%1], %2, [%3], %4;" ::"r"(sb + g0 * GR), "l"(g_kv + (unsigned)((((n & 1) * 16 + (head & 15)) * 16 + blk) * 32768)),
                         "r"(2 * GR), "r"(fb), "l"(it >= 8 ? EV_FIRST : EV_NORMAL) : "memory");
          }
          g0 = n == 13 ? 12 : g0 == 12 ? 4 : g0 + 2;
        }
      }
      int c5 = 0;
      if (spare) { bar_sync(5, 64); pe = 0x3FC0; }
      else c5 = get_ticket();
      auto conv_fill = [&](int g, int ch) {
        acquire(g, 1, 1);
        if (elect()) {
          const uint32_t fb = sb + SM_BAR + (B_FULL + g) * 8;
          if (!spare) FTP(64 + 48 + g);
          mbar_expect_tx(fb, WBYTES + 4096);
          bulk_g2s<true>(sb + g * GR, g_w + (size_t)ch * WSTRIDE, WBYTES, fb);
          bulk_g2s<true>(sb + g * GR + WBYTES, p.ssk + (size_t)ch * SEQ, 4096, fb);
        }
      };
#pragma unroll 1
      for (int i = 0, g = 2; i < cn; i++) {
        if ((i & 15) == 0) { flag_wait(FLAG(F_U + (spare ? 32 - __clz(i >> 4) : 4)), NMAIN); fence_async_all(); }
        conv_fill(g + (i & 1), cch + i * cstep + (i == 4 ? c5 : 0));
        if (i & 1) g = conv_next(g, spare);
      }
      if (!spare) {
        const int rt = 2 * grp + rank, ct = idx;
        int g0 = P3G, top = 12;
        const uint8_t* src = g_cimg + (unsigned)((rt * 64 + 32) * GR);
#pragma unroll 1
        for (int kb = 0; kb < 64; kb++) {
          if (!(kb & 31)) { flag_wait(FLAG(F_CTX + rt * 2 + ((kb ^ 32) >> 5)), 32); fence_async_all(); if (kb) src -= 64 * GR; }
          acquire(g0, kb < 11 ? 2 : 1, 3);
          if (elect()) {
            const uint32_t fb = sb + SM_BAR + (B_FULL + g0) * 8;
            if (kb < 16) FTP(48 + kb);
            mbar_expect_tx(fb, 2 * GR);
            bulk_g2s<true>(sb + g0 * GR, src, GR, fb);
            tma2d_mc<true>(sb + (g0 + 1) * GR + rank * 8192, &p.wo, ct * 128 + rank * 64, (kb ^ 32) * 64, fb);
          }
          src += GR;
          g0 = g0 == (kb < XK ? 12 : kb < YK ? 10 : 8) ? (kb == 3 ? 2 : 0) : g0 + 2;
          if (kb == XK || (kb >= YK && top == P3Y && (kb == 63 || mbar_test(sb + SM_BAR + B_SLOT * 8, 1)))) {
            const bool j = kb != XK;
            if (j) { mbar_wait1(sb + SM_BAR + B_SLOT * 8, 1); fence_async_all(); }
            acquire(top, 1, 0);
            if (elect()) {
              const uint32_t fb = sb + SM_BAR + (B_FULL + top) * 8;
              mbar_expect_tx(fb, j ? 2 * GR + 512 : 2 * GR);
              if (j) bulk_g2s(sb + SM_GATE, g_gate + (unsigned)(rt * 128), 512, fb);
              tma3d(sb + top * GR, j ? &p.y3 : &p.x3, 0, (j ? ct : rt) * 128, (j ? rt : ct) * 2, fb);
            }
            top -= 2;
          }
        }
        unsigned n = 0;
        if (lane == 0) n = atomicInc(FLAG(F_EXIT), 0x7fffffffu);
        if (__any_sync(0xffffffffu, n == NMAIN - 1)) {
#pragma unroll
          for (int i = lane; i < 96; i += 32) *reinterpret_cast<uint2*>(FLAG(i)) = make_uint2(0, 0);
        }
      }
      if (lane == 0) mbar_arrive(sb + SM_BAR + B_DONE * 8);
    }
    __syncwarp();
    cluster_wait();
  } else {
    asm volatile("setmaxnreg.inc.sync.aligned.u32 232;");
    FTS(2);
    Cons c;
    c.sb = sb; c.pf = 0; c.wg = wgi - 1; c.tid = threadIdx.x & 127;
    const int lane = threadIdx.x & 31, t = lane & 3;
    const int row = c.wg * 64 + (warp & 3) * 16 + (lane >> 2);
    const uint32_t dkk = desc_k(sb), dk0 = dkk + c.wg * 512, dm0 = desc_mn<8192>(sb), dv0 = desc_mn<16384>(sb);
    const uint32_t dsw = DG + 512 - c.wg * 1024;
    if (c.wg == 1) bar_arrive(1, 256);
    c.pfree = 1;
    asm("mapa.shared::cluster.u32 %0, %1, %2;" : "=r"(c.relb) : "r"(sb + SM_BAR + (B_EMPTY + (c.tid >> 1)) * 8), "r"(c.tid & 1));
    c.zero = p.zero;
    c.rnd = 0;
    const uint32_t stg = sb + (c.wg * 64 + (warp & 3) * 16 + ((lane >> 3) & 1) * 8 + (lane & 7)) * 128 + (((lane >> 4) ^ (lane & 7)) << 4);

    uint32_t dd0;
    auto load_dd = [&]() { asm volatile("ld.global.nc.u16 %0, [%1];" : "=r"(dd0) : "l"(p.ssd + (unsigned)(cch + c.wg * cstep + (lane & c.zero)))); };
    int pass = c.zero;
#pragma unroll 1
    do {
    if (pass) {
      load_dd();
#pragma unroll 1
      for (int g = 2; g < NGR; g += 3) { mbar_wait(sb + SM_BAR + (B_FULL + g) * 8, 0); c.release(g, 3); }
      c.pf = 0x924;
    if (spare) {
      c.wait_full(1);
      int g = 2;
#pragma unroll 1
      for (int r = 0; r < 4; r++) {
        float d[4] = {0.f, 0.f, 0.f, 0.f}, e[4] = {0.f, 0.f, 0.f, 0.f};
#pragma unroll 1
        for (int kb = 0; kb < 16; kb += 2) {
          c.wait_full(g);
          wg_fence();
#pragma unroll 1
          for (int k = 0; k < 4; k++) {
            mma_ss_n8(d, dk0 + g * DG + k * 2, dkk + DG + kb * 8 + k * 2);
            mma_ss_n8(e, dk0 + (g + 1) * DG + k * 2, dkk + DG + kb * 8 + 8 + k * 2);
          }
          wg_commit();
          wg_wait<0>();
          c.release(g, 2);
          g = g == NGR - 2 ? 2 : g + 2;
        }
        reg_fence(d); reg_fence(e);
        d[0] += e[0]; d[2] += e[2];
        if (t == 0) {
          float* gp = g_gate + (unsigned)((lb - NMAIN) * 512 + r * 128 + row);
          gp[0] = rcp(1.f + ex2(-1.4426950408889634f * d[0])); gp[8] = rcp(1.f + ex2(-1.4426950408889634f * d[2]));
        }
      }
      fence_release();
      __syncwarp();
      if (lane == 0) flag_add(FLAG(F_GATE));
      TS(1);
    }
    } else cluster_wait();
    get_slot();
    } while (redo && !pass++);
    FTS(3);
    const float dmask = (float)(2 * t - (row & 63));
    int c5 = 0;
    uint32_t pv[32];
#pragma unroll 1
    for (int rnd = 0; rnd < (spare ? 0 : 2); rnd++) {
      float O[64];
      FTM(rnd * 8);
      FTG(0);
      FTH(56, c.rnd == rnd);
      c.wait_full(2);
      FTM(rnd * 8 + 1);
      FTH(57, c.rnd == rnd);
#pragma unroll 1
      for (int tile = c.zero; tile < 2; tile++) {
        float acc[128];
        const bool single = tile == 0;
        {
          FTG(tile * 32 + 1);
          const uint32_t a = dk0 + 2 * DG, b = dm0 + 3 * DG;
          c.turn_begin();
          FTG(tile * 32 + 2);
          FTH(58, c.rnd == rnd);
          wg_fence();
          mma_ss_n256_init<1>(acc, a, b);
#pragma unroll
          for (int k = 1; k < 4; k++) mma_ss_n256<1>(acc, a + k * 2, b + k * 128);
          wg_commit();
          if (single) c.turn_end();
          FTG(tile * 32 + 3);
        }
#pragma unroll 1
        for (int kb = 1; kb < 8; kb++) {
          const int g0 = 2 + 3 * (kb & 3);
          const uint32_t a = dk0 + g0 * DG, b = dm0 + (g0 + 1) * DG;
          const bool second = (kb == 1 && !single) || kb == 7;
          FTG(tile * 32 + kb * 4);
          if (!second) { wg_wait<0>(); c.release(2 + 3 * ((kb - 1) & 3), 3); }
          FTG(tile * 32 + kb * 4 + 1);
          c.wait_full(g0);
          if (!second) c.turn_begin();
          FTG(tile * 32 + kb * 4 + 2);
          wg_fence();
#pragma unroll
          for (int k = 0; k < 4; k++) mma_ss_n256<1>(acc, a + k * 2, b + k * 128);
          wg_commit();
          if (kb != 6) c.turn_end();
          if (second) { wg_wait<1>(); c.release(2 + 3 * ((kb - 1) & 3), 3); }
          FTG(tile * 32 + kb * 4 + 3);
          FTH(58 + kb, c.rnd == rnd || kb > 3);
          if (tile == 1 && kb == 3) { c.wait_stage_free(); stsm_frag<0, 4>(pv, stg); }
          if (tile == 1 && kb == 4) { stsm_frag<4, 8>(pv, stg); c.staged(0); }
        }
        c.rnd = rnd;
        c.wait_stage_free();
        const bool nxt = c.try_full(2);
        wg_wait<0>();
        reg_fence(acc);
        c.release(11, 3);
        store_scaled(acc, SM_C, SM_C, stg, sb);
        c.staged(0);
        pack_frag<64>(acc, pv);
        FTG(32 + tile * 32);
        if (!nxt) mbar_wait(sb + SM_BAR + (B_FULL + 2) * 8, (c.pf >> 2) & 1);
        c.pf ^= 4;
      }
      TS(1 + rnd * 3);
      FTM(rnd * 8 + 2);
      {
        float qa[64];
        float (&qb)[64] = O;
        {
          FTG(65);
          const uint32_t a = dk0 + 2 * DG, b = dm0 + 4 * DG;
          c.turn_begin();
          FTG(66);
          wg_fence();
          mma_ss_n128_init<1>(qa, a, b);
          mma_ss_n128_init<1>(qb, a + dsw, b);
#pragma unroll
          for (int k = 1; k < 4; k++) {
            mma_ss_n128<1>(qa, a + k * 2, b + k * 128);
            mma_ss_n128<1>(qb, a + dsw + k * 2, b + k * 128);
          }
          wg_commit();
          FTG(67);
        }
#pragma unroll 1
        for (int kb = 1; kb < 16; kb++) {
          const int g0 = 2 + 3 * (kb & 3);
          const uint32_t a = dk0 + g0 * DG, b = dm0 + (g0 + 2) * DG;
          const bool second = kb == 1 || kb == 15;
          FTG(64 + kb * 4);
          if (!second) { wg_wait<0>(); c.release(2 + 3 * ((kb - 1) & 3), 3); }
          FTG(65 + kb * 4);
          c.wait_full(g0);
          if (!second) c.turn_begin();
          FTG(66 + kb * 4);
          FTH(kb - 14, kb < 14);
          wg_fence();
#pragma unroll
          for (int k = 0; k < 4; k++) {
            mma_ss_n128<1>(qa, a + k * 2, b + k * 128);
            mma_ss_n128<1>(qb, a + dsw + k * 2, b + k * 128);
          }
          wg_commit();
          if (kb != 14) c.turn_end();
          if (second) { wg_wait<1>(); c.release(2 + 3 * ((kb - 1) & 3), 3); }
          FTG(67 + kb * 4);
          FTH(2, kb < 15);
          if (kb == QFLUSH) { c.wait_stage_free(); stsm_frag<0, 4>(pv, stg); }
          if (kb == QFLUSH + 1) { stsm_frag<4, 8>(pv, stg); c.staged(0); }
        }
        c.wait_stage_free();
        mbar_wait(sb + SM_BAR + (B_EMPTY + 2) * 8, rnd ^ !redo);
        FTM(rnd * 8 + 3);
        FTH(3, 0);
        const bool k0 = c.try_full(4);
        wg_wait<0>();
        reg_fence(qa); reg_fence(qb);
        FTH(4, 0);
        c.release(11, 3);
        pack_frag<0>(qa, pv);
        stsm_frag(pv, stg + 2 * GR);
        if (c.wg == 0) {
          pack_frag<0>(qb, pv);
          stsm_frag(pv, stg);
        }
        FTH(6, 0);
        fence_async_smem();
        FTH(7, 0);
        if (!k0) c.wait_full(4); else c.pf ^= 16;
      }
      TS(2 + rnd * 3);
      FTM(rnd * 8 + 4);
      FTH(5, 0);
      {
        const int nA = idx + 1;
        uint32_t (&P)[32] = pv;
        SoftState z;
        z.m0 = z.m1 = z.l0 = z.l1 = 0.f; z.shifted = c.zero;
#pragma unroll 1
        for (int seg = c.zero;; seg++) {
        if (c.wg == seg) attn_half(c, O, P, z, dk0, dkk, dv0, dmask, seg);
        if (seg) break;
        FTM(rnd * 8 + 5);
        int gk = c.wg ? 4 : 6, gv = c.wg ? 4 : 8;
        uint32_t dq = dk0 + (1 - c.wg < nA ? 2 * DG : 0), dk = dkk + gk * DG;
#pragma unroll 1
        for (int it = 1 - c.wg; it < 17 - c.wg; it++) {
          float S[64];
          FTA(it * 7 + 0); FTH((it < 3 ? 8 + it * 8 : it * 8 - 88) + 0, it >= 3 && it < 15);
          c.turn_begin();
          FTA(it * 7 + 2); FTH((it < 3 ? 8 + it * 8 : it * 8 - 88) + 1, it >= 3 && it < 15);
          wg_fence();
          issue_qk(S, dq, dk);
          wg_commit();
          const uint32_t dv = dv0 + gv * DG;
          uint32_t relk = c.relb + gk * 8, relv = c.relb + gv * 8;
          gk = it == 6 ? 12 : gv == 12 ? 4 : gv + 2;
          gv = it == 16 ? gk : gk == 12 ? 4 : gk + 2;
          uint32_t fk = sb + SM_BAR + (B_FULL + gk) * 8, fv = sb + SM_BAR + (B_FULL + gv) * 8, park = (c.pf >> gk) & 1, parv = (c.pf >> gv) & 1;
          c.pf ^= (1u << gk) | (1u << gv);
          dq = dk0 + (it + 1 < nA ? 2 * DG : 0); dk = dkk + gk * DG;
          float lo0 = z.l0, lo1 = z.l1;
          const bool first = it == nA || it == 0;
          if (it == nA) {
            lo0 = rcp(quad_sum(lo0)); lo1 = rcp(quad_sum(lo1));
            z.m0 = z.m1 = z.l0 = z.l1 = 0.f; z.shifted = 0;
          }
          float s0, s1, d0 = z.m0, d1 = z.m1;
          int pre = z.shifted || (it & 15) == 0;
          float lim = first ? -1.f : SM_LIMIT;
          asm volatile("" : "+r"(relk), "+r"(relv), "+r"(fk), "+r"(fv), "+r"(park), "+r"(parv), "+r"(dq), "+r"(dk), "+r"(pre), "+f"(lim), "+f"(d0), "+f"(d1), "+f"(z.l0), "+f"(z.l1));
          if (it + c.wg > 1) {
            issue_pv<0>(O, P, dv, it != nA + 1 && it != 1, true);
            issue_pv<1>(O, P, dv, 1, true);
            c.turn_end();
          } else if (it) {
            issue_pv<0>(O, P, dv, 0, true);
            wg_commit(); wg_commit();
            c.turn_end();
          } else stage_q2(c, O, P, stg);
          FTA(it * 7 + 3); FTH((it < 3 ? 8 + it * 8 : it * 8 - 88) + 2, it >= 3 && it < 15);
          wg_wait<4>();
          reg_fence(S);
          FTA(it * 7 + 4); FTH((it < 3 ? 8 + it * 8 : it * 8 - 88) + 3, it >= 3 && it < 15);
          if (c.tid < 4) asm volatile("mbarrier.arrive.shared::cluster.b64 _, [%0];" ::"r"(relk) : "memory");
#pragma unroll 1
          for (int pass = 0;; pass++) {
            if (pre) {
              if ((it & 15) == 0) mask_diag(S, dmask);
              if (z.shifted) shift_scores(S, d0, d1);
            }
            float tr[ROT];
            exp_quarter<0, 3>(S, P, tr, s0, s1, sb);
            exp_quarter<1, 2>(S, P, tr, s0, s1, sb);
            exp_quarter<2, 1>(S, P, tr, s0, s1, sb);
            exp_quarter<3, 0>(S, P, tr, s0, s1, sb);
            reg_fence(O);
            if (c.tid < (pass || !it ? 0 : 4)) asm volatile("mbarrier.arrive.shared::cluster.b64 _, [%0];" ::"r"(relv) : "memory");
            const bool ok = mbar_test(fk, park) & mbar_test(fv, parv);
            if (!ok) lim = -1.f;
            FTA(it * 7 + 5); FTH((it < 3 ? 8 + it * 8 : it * 8 - 88) + 4, it >= 3 && it < 15);
            if (!__any_sync(0xffffffffu, !(s0 <= lim && s1 <= lim))) break;
            if (pass) break;
            if (it == nA) {
              store_scaled(O, lo0, lo1, stg + 2 * GR, sb);
              c.staged(1);
            }
            if (!ok) { mbar_wait(fk, park); mbar_wait(fv, parv); }
            if (!soft_unsafe(s0, s1, first)) break;
            soft_fix(S, O, z, first, d0, d1);
            pre = 1;
          }
          z.l0 += s0; z.l1 += s1;
          FTA(it * 7 + 6); FTH((it < 3 ? 8 + it * 8 : it * 8 - 88) + 5, it >= 3 && it < 15);
        }
        FTM(rnd * 8 + 6);
        }
        FTH(48, 0);
        load_dd();
        c.turn_begin();
        FTH(49, 0);
        wg_fence();
        issue_pv<0>(O, P, dv0 + 12 * DG, 1, true);
        issue_pv<1>(O, P, dv0 + 12 * DG, 1, !c.wg);
        c.turn_end();
        z.l0 = rcp(quad_sum(z.l0)); z.l1 = rcp(quad_sum(z.l1));
        if (rnd) c5 = get_ticket();
        wg_wait<0>();
        reg_fence(O); reg_fence(P);
        FTH(50, 0);
        c.release(12, 2);
        store_scaled(O, z.l0, z.l1, stg, sb);
        c.staged(0);
        FTM(rnd * 8 + 7);
        FTH(51, 0);
      }
      TS(3 + rnd * 3);
    }
    conv_tasks(c, p, (cn + 1 - c.wg) >> 1, spare, cch + c.wg * cstep, 2 * cstep, c5, dd0, dkk, warp & 3, lane);
    if (c.wg == 1) c.pf ^= 0x14;
    if (c.wg == (cn & 1)) c.turn_begin();
    TS(7);
    if (!spare) {
      const int rt = 2 * grp + rank, ct = idx;
      float acc[64];
      int g0 = P3G + 2, pg = P3G;
      {
        FTO(0);
        c.wait_full(P3G);
        FTO(1);
        const uint32_t a = dk0 + P3G * DG, b = dm0 + (P3G + 1) * DG;
        wg_fence();
        mma_ss_n128_init<1>(acc, a, b);
#pragma unroll
        for (int k = 1; k < 4; k++) mma_ss_n128<1>(acc, a + k * 2, b + k * 128);
        wg_commit();
      }
#pragma unroll 1
      for (int kb = 1; kb < 64; kb++) {
        FTO(kb * 2);
        c.wait_full(g0);
        if (kb == STR && !c.wg) c.turn_begin();
        FTO(kb * 2 + 1);
        const uint32_t a = dk0 + g0 * DG, b = dm0 + (g0 + 1) * DG;
        wg_fence();
#pragma unroll
        for (int k = 0; k < 4; k++) mma_ss_n128<1>(acc, a + k * 2, b + k * 128);
        wg_commit();
        if (kb < STR) { wg_wait<1>(); c.release(pg, kb <= 59 ? 2 : 0); }
        if (kb == FDUMP_KB) FTDUMP();
        pg = g0;
        g0 = g0 == (kb < XK ? 12 : kb < YK ? 10 : 8) ? (kb == 3 ? 2 : 0) : g0 + 2;
      }
      if (c.wg) c.turn_end();
      cluster_arrive();
      c.wait_full(P3X);
      c.wait_full(P3Y);
      const float g0f = __uint_as_float(lds32(sb + SM_GATE + row * 4)), g1f = __uint_as_float(lds32(sb + SM_GATE + row * 4 + 32));
      const uint32_t gp0 = pack_bf16(g0f, g0f), gp1 = pack_bf16(g1f, g1f);
      const float h0 = 1.f - g0f, h1 = 1.f - g1f;
      const int w = warp & 3;
      const uint32_t xa = stg + P3X * GR;
      const uint32_t ya = sb + P3Y * GR + c.wg * 16384 + ((lane >> 4) * 8 + (lane & 7)) * 128 + (((2 * w + ((lane >> 3) & 1)) ^ (lane & 7)) << 4);
      uint32_t xy[32];
      auto prep = [&](int j0, int j1) {
#pragma unroll
        for (int jj = j0; jj < j1; jj++) {
          uint32_t x[4], y[4];
          asm volatile("ldmatrix.sync.aligned.m8n8.x4.shared.b16 {%0,%1,%2,%3}, [%4];" : "=r"(x[0]), "=r"(x[1]), "=r"(x[2]), "=r"(x[3]) : "r"((xa ^ ((jj & 3) << 5)) + (jj >> 2) * 16384) : "memory");
          asm volatile("ldmatrix.sync.aligned.m8n8.x4.trans.shared.b16 {%0,%1,%2,%3}, [%4];" : "=r"(y[0]), "=r"(y[1]), "=r"(y[2]), "=r"(y[3]) : "r"(ya + jj * 2048) : "memory");
#pragma unroll
          for (int i = 0; i < 4; i++) xy[4 * jj + i] = hmul2(x[i], y[i]);
        }
      };
      prep(0, 4);
      wg_wait<0>();
      reg_fence(acc);
      TS(8);
#pragma unroll
      for (int hf = 0; hf < 2; hf++) {
#pragma unroll
        for (int i = 16 * hf; i < 16 * hf + 16; i++) {
          const float h = (i & 1) ? h1 : h0;
          xy[i] = hfma2((i & 1) ? gp1 : gp0, xy[i], pack_bf16(acc[2 * i] * h, acc[2 * i + 1] * h));
        }
        if (hf) stsm_frag<4, 8>(xy, xa); else stsm_frag<0, 4>(xy, xa);
        fence_async_smem();
        __syncwarp();
        const int r0 = c.wg * 64 + w * 16;
        if (lane == 0) tma2d_store(&p.out, sb + (P3X + hf) * GR + r0 * 128, ct * 128 + hf * 64, rt * 128 + r0);
        if (!hf) prep(4, 8);
      }
      if (lane == 0) asm volatile("cp.async.bulk.commit_group;\ncp.async.bulk.wait_group.read 0;" ::: "memory");
    } else { FTDUMP(); cluster_arrive(); }
    if (lane == 0) mbar_arrive(sb + SM_BAR + B_DONE * 8);
    __syncwarp();
    TS(9);
    cluster_wait();
  }
}

typedef CUresult (*EncFn)(CUtensorMap*, CUtensorMapDataType, cuuint32_t, void*, const cuuint64_t*, const cuuint64_t*, const cuuint32_t*,
                          const cuuint32_t*, CUtensorMapInterleave, CUtensorMapSwizzle, CUtensorMapL2promotion, CUtensorMapFloatOOBfill);

void enc2d(EncFn enc, CUtensorMap* tm, const void* base, uint64_t cols, uint64_t rows, uint32_t bc, uint32_t br) {
  cuuint64_t dims[2] = {cols, rows}; cuuint64_t strides[1] = {cols * 2}; cuuint32_t box[2] = {bc, br}; cuuint32_t es[2] = {1, 1};
  enc(tm, CU_TENSOR_MAP_DATA_TYPE_BFLOAT16, 2, const_cast<void*>(base), dims, strides, box, es, CU_TENSOR_MAP_INTERLEAVE_NONE,
      CU_TENSOR_MAP_SWIZZLE_128B, CU_TENSOR_MAP_L2_PROMOTION_L2_256B, CU_TENSOR_MAP_FLOAT_OOB_FILL_NONE);
}
void enc3d(EncFn enc, CUtensorMap* tm, const void* base, uint64_t K, uint64_t N, uint32_t bk = 64) {
  cuuint64_t dims[3] = {64, K, N / 64}; cuuint64_t strides[2] = {N * 2, 128}; cuuint32_t box[3] = {64, bk, 2}; cuuint32_t es[3] = {1, 1, 1};
  enc(tm, CU_TENSOR_MAP_DATA_TYPE_BFLOAT16, 3, const_cast<void*>(base), dims, strides, box, es, CU_TENSOR_MAP_INTERLEAVE_NONE,
      CU_TENSOR_MAP_SWIZZLE_128B, CU_TENSOR_MAP_L2_PROMOTION_L2_256B, CU_TENSOR_MAP_FLOAT_OOB_FILL_NONE);
}

}

extern "C" void kernel_launch(void* const* d_in, const int* in_sizes, int n_in, void* d_out, int out_size) {
  (void)in_sizes; (void)n_in; (void)out_size;
  typedef const __nv_bfloat16* BP;
  BP xq = (BP)d_in[0], ak = (BP)d_in[1], av = (BP)d_in[2], shk = (BP)d_in[3], ssk = (BP)d_in[4], ssd = (BP)d_in[5];
  BP ckv = (BP)d_in[7], wq = (BP)d_in[8], wuk = (BP)d_in[9], wuv = (BP)d_in[10], wo = (BP)d_in[11], gw = (BP)d_in[12];

  static EncFn enc = nullptr;
  if (!enc) {
    cudaDriverEntryPointQueryResult qr;
    cudaGetDriverEntryPoint("cuTensorMapEncodeTiled", (void**)&enc, cudaEnableDefault, &qr);
    cudaFuncSetAttribute(mega_kernel, cudaFuncAttributeMaxDynamicSharedMemorySize, SMEM_BYTES);
  }
  Params p;
  void* yT = nullptr;
  cudaGetSymbolAddress(&yT, g_yT);
  enc2d(enc, &p.x, xq, DM, SEQ, 64, 128);
  enc2d(enc, &p.c, ckv, DC, SEQ, 64, 128);
  enc3d(enc, &p.wq, wq, DM, NH * HD);
  enc3d(enc, &p.wuk, wuk, DC, NH * HD);
  enc3d(enc, &p.wuv, wuv, DC, NH * HD);
  enc2d(enc, &p.wo, wo, DM, NH * HD, 64, 64);
  enc3d(enc, &p.x3, xq, SEQ, DM, 128);
  enc3d(enc, &p.y3, yT, DM, SEQ, 128);
  enc2d(enc, &p.out, d_out, DM, SEQ, 64, 16);
  {
    void* wp = nullptr;
    cudaGetSymbolAddress(&wp, g_w);
    cuuint64_t dims[3] = {WSTRIDE / 2, DM / 2, 2}; cuuint64_t strides[2] = {2 * WSTRIDE, WSTRIDE}; cuuint32_t box[3] = {16, 32, 2}; cuuint32_t es[3] = {1, 1, 1};
    enc(&p.w, CU_TENSOR_MAP_DATA_TYPE_BFLOAT16, 3, wp, dims, strides, box, es, CU_TENSOR_MAP_INTERLEAVE_NONE,
        CU_TENSOR_MAP_SWIZZLE_32B, CU_TENSOR_MAP_L2_PROMOTION_NONE, CU_TENSOR_MAP_FLOAT_OOB_FILL_NONE);
  }
  p.zero = 0;
  cudaGetSymbolAddress((void**)&p.flags, g_flags);
  for (int i = 0; i < 128; i++) {
    const int tp = i % NSLOT;
    p.pref[i] = tp < 32 ? (tp & 7) * 8 + (tp >> 3) : tp < 60 ? (1 + (tp - 32) % 7) * 8 + 4 + (tp - 32) / 7 : tp < 62 ? tp + 4 : tp - 58;
  }
  p.gate_w = gw; p.ak = ak; p.av = av; p.shk = shk; p.ssk = ssk; p.ssd = ssd;

  mega_kernel<<<132, NTHREADS, SMEM_BYTES>>>(p);
}
```

```cpp
#include <cuda_runtime.h>
#include <cuda.h>
#include <cuda_bf16.h>
#include <stdint.h>

namespace {

constexpr int SEQ = 2048, DM = 1024, DC = 512, NH = 32, HD = 128;
constexpr int GR = 16384;
constexpr int NGR = 14;
constexpr int SM_BAR = NGR * GR;
constexpr int SM_GATE = SM_BAR + 512;
constexpr int SM_UST = SM_GATE + 512;
constexpr int SMEM_BYTES = SM_UST + 2048;
constexpr int NTHREADS = 384;
#define SM_LIMIT 1.0995116e12f
#define SM_LOW 9.094947e-13f
#define CNS 106
constexpr int CN_SPARE = CNS, NTICK = 256 - 2 * CN_SPARE;
constexpr int XK = 57, YK = 62;
constexpr int STR = 61;
constexpr int P3G = 6, P3X = 12, P3Y = 10;
constexpr int NMAIN = 128;

constexpr int B_FULL = 0, B_FREE = 14, B_SLOT = 16, B_DONE = 17, B_EMPTY = 18, B_EV = 32, B_TICK = 36;
constexpr int V_SLOT = 37, V_TICK = 38;

__device__ __align__(1024) uint8_t g_kv[2 * 16 * 16 * 32768];
__device__ __align__(1024) uint8_t g_cimg[16 * NH * 32768];
__device__ __align__(1024) float g_gate[SEQ];
constexpr int WZ = 256, WPL = WZ + 4096, WBYTES = 2 * WPL + 32, WSTRIDE = 2 * WPL + 128;
__device__ __align__(1024) uint8_t g_w[DM * WSTRIDE];
__device__ __align__(32) unsigned g_flags[96 * 8];
constexpr int F_KV = 0, F_CTX = 16, F_U = 48, F_AD = 56, F_Y = 64, F_GATE = 72, F_EXIT = 73, F_TICK = 74;
constexpr int NSLOT = 66;
#define FLAG(i) (&g_flags[(i) * 8])
#define CLAIMP(i) (p.flags + (i) * 8 + 1)

#define TS(slot)
#define TSW(slot)
#define FTX(i, off)
#define FTDUMP()

#define QFLUSH 4
#define PSL 200
#define US0 500
#define EROT 6
#define RST 2
#define UP0 4
#define UP1 11
#define X_DELAY 900
#define X_D2 600
#define ROT 8
#define KVARR 1
#define KV_ROW(idx, t) (KVARR ? 8 * (t) + 2 * ((idx) & 3) : 2 * (idx))
#define KV_HEAD(idx, t) (KVARR ? (idx) >> 2 : (t))
#define FINE_MODE 0
#define FDUMP_KB 40
#define FINE_RND 1
#define FTA(i) do { if (FINE_MODE == 0) FTX(i, rnd ^ FINE_RND); } while (0)
#define FTG(i) do { if (FINE_MODE == 1) FTX(i, rnd ^ FINE_RND); } while (0)
#define FTM(i) do { if (FINE_MODE == 4) FTX(i, 0); } while (0)
#define FTC(k) do { if (FINE_MODE == 5) FTX((i & 7) * 8 + (k), (i >> 3) ^ FINE_RND); } while (0)
#define FTH(i, off) do { if (FINE_MODE == 6) FTX(i, (c.rnd ^ FINE_RND) | (off)); } while (0)
#define FTS(i)
#define FTSD(i)
#define FTSW(i)
#define FTP(i)
#define FTO(i) do { if (FINE_MODE == 2) FTX(i, 0); } while (0)

__device__ __forceinline__ uint32_t smem_u32(const void* p) { return (uint32_t)__cvta_generic_to_shared(p); }
__device__ __forceinline__ void mbar_init(uint32_t bar, int cnt) { asm volatile("mbarrier.init.shared::cta.b64 [%0], %1;" ::"r"(bar), "r"(cnt) : "memory"); }
__device__ __forceinline__ void mbar_expect_tx(uint32_t bar, uint32_t bytes) { asm volatile("mbarrier.arrive.expect_tx.shared::cta.b64 _, [%0], %1;" ::"r"(bar), "r"(bytes) : "memory"); }
__device__ __forceinline__ void mbar_arrive(uint32_t bar) { asm volatile("mbarrier.arrive.shared::cta.b64 _, [%0];" ::"r"(bar) : "memory"); }
__device__ __forceinline__ void mbar_arrive_cluster(uint32_t bar, uint32_t cta) {
  asm volatile("{\n.reg .b32 r;\nmapa.shared::cluster.u32 r, %0, %1;\nmbarrier.arrive.shared::cluster.b64 _, [r];\n}\n" ::"r"(bar), "r"(cta) : "memory");
}
__device__ __forceinline__ void send_both(uint32_t bar, uint32_t off, uint32_t v) {
#pragma unroll
  for (int r = 0; r < 2; r++)
    asm volatile("{\n.reg .b32 a, b;\nmapa.shared::cluster.u32 a, %0, %1;\nadd.u32 b, a, %3;\nst.async.shared::cluster.mbarrier::complete_tx::bytes.u32 [b], %2, [a];\n}\n"
                 ::"r"(bar), "r"(r), "r"(v), "r"(off) : "memory");
}
__device__ __forceinline__ bool mbar_try(uint32_t bar, uint32_t parity) {
  uint32_t ok;
  asm volatile("{\n.reg .pred p;\nmbarrier.try_wait.parity.shared::cta.b64 p, [%1], %2, 20000;\nselp.u32 %0, 1, 0, p;\n}\n" : "=r"(ok) : "r"(bar), "r"(parity) : "memory");
  return ok;
}
__device__ __forceinline__ bool mbar_test(uint32_t bar, uint32_t parity) {
  uint32_t ok;
  asm volatile("{\n.reg .pred p;\nmbarrier.test_wait.parity.shared::cta.b64 p, [%1], %2;\nselp.u32 %0, 1, 0, p;\n}\n" : "=r"(ok) : "r"(bar), "r"(parity) : "memory");
  return ok;
}
__device__ __forceinline__ void mbar_wait(uint32_t bar, uint32_t parity) {
  asm volatile("{\n.reg .pred p;\nWAIT_LOOP:\nbar.warp.sync -1;\nmbarrier.try_wait.parity.shared::cta.b64 p, [%0], %1;\n@!p bra WAIT_LOOP;\n}\n" ::"r"(bar), "r"(parity) : "memory");
}
__device__ __forceinline__ void mbar_wait1(uint32_t bar, uint32_t parity) {
  asm volatile("{\n.reg .pred p;\nWAIT_LOOP:\nbar.warp.sync -1;\nmbarrier.try_wait.parity.shared::cta.b64 p, [%0], %1, 4000;\n@!p bra WAIT_LOOP;\n}\n" ::"r"(bar), "r"(parity) : "memory");
}
constexpr uint64_t EV_NORMAL = 0x1000000000000000ull, EV_FIRST = 0x12F0000000000000ull;
__device__ __forceinline__ uint32_t ldg_stream(const uint32_t* p) {
  uint32_t r; asm volatile("ld.global.nc.L1::no_allocate.L2::cache_hint.b32 %0, [%1], %2;" : "=r"(r) : "l"(p), "l"(EV_FIRST)); return r;
}
#define TMA_LD "cp.async.bulk.tensor."
#define TMA_MB ".shared::cluster.global.mbarrier::complete_tx::bytes"
__device__ __forceinline__ void tma2d(uint32_t dst, const CUtensorMap* tm, int c0, int c1, uint32_t bar) {
  asm volatile(TMA_LD "2d" TMA_MB " [%0], [%1, {%3, %4}], [%2];" ::"r"(dst), "l"(tm), "r"(bar), "r"(c0), "r"(c1) : "memory");
}
template <bool ONCE = false> __device__ __forceinline__ void tma2d_mc(uint32_t dst, const CUtensorMap* tm, int c0, int c1, uint32_t bar) {
  if (ONCE) asm volatile(TMA_LD "2d" TMA_MB ".multicast::cluster.L2::cache_hint [%0], [%1, {%3, %4}], [%2], %5, %6;"
                         ::"r"(dst), "l"(tm), "r"(bar), "r"(c0), "r"(c1), "h"((uint16_t)3), "l"(EV_FIRST) : "memory");
  else asm volatile(TMA_LD "2d" TMA_MB ".multicast::cluster [%0], [%1, {%3, %4}], [%2], %5;"
                    ::"r"(dst), "l"(tm), "r"(bar), "r"(c0), "r"(c1), "h"((uint16_t)3) : "memory");
}
__device__ __forceinline__ void tma2d_p(uint32_t dst, const CUtensorMap* tm, int c0, int c1, uint32_t bar, bool once) {
  asm volatile(TMA_LD "2d" TMA_MB ".L2::cache_hint [%0], [%1, {%3, %4}], [%2], %5;" ::"r"(dst), "l"(tm), "r"(bar), "r"(c0), "r"(c1), "l"(once ? EV_FIRST : EV_NORMAL) : "memory");
}
__device__ __forceinline__ void tma3d_mc_p(uint32_t dst, const CUtensorMap* tm, int c0, int c1, int c2, uint32_t bar, bool once) {
  asm volatile(TMA_LD "3d" TMA_MB ".multicast::cluster.L2::cache_hint [%0], [%1, {%3, %4, %5}], [%2], %6, %7;"
               ::"r"(dst), "l"(tm), "r"(bar), "r"(c0), "r"(c1), "r"(c2), "h"((uint16_t)3), "l"(once ? EV_FIRST : EV_NORMAL) : "memory");
}
template <bool ONCE = false> __device__ __forceinline__ void tma3d(uint32_t dst, const CUtensorMap* tm, int c0, int c1, int c2, uint32_t bar) {
  if (ONCE) asm volatile(TMA_LD "3d" TMA_MB ".L2::cache_hint [%0], [%1, {%3, %4, %5}], [%2], %6;" ::"r"(dst), "l"(tm), "r"(bar), "r"(c0), "r"(c1), "r"(c2), "l"(EV_FIRST) : "memory");
  else
  asm volatile(TMA_LD "3d" TMA_MB " [%0], [%1, {%3, %4, %5}], [%2];" ::"r"(dst), "l"(tm), "r"(bar), "r"(c0), "r"(c1), "r"(c2) : "memory");
}
__device__ __forceinline__ void tma3d_mc(uint32_t dst, const CUtensorMap* tm, int c0, int c1, int c2, uint32_t bar) {
  asm volatile(TMA_LD "3d" TMA_MB ".multicast::cluster [%0], [%1, {%3, %4, %5}], [%2], %6;"
               ::"r"(dst), "l"(tm), "r"(bar), "r"(c0), "r"(c1), "r"(c2), "h"((uint16_t)3) : "memory");
}
template <bool ONCE = false> __device__ __forceinline__ void bulk_g2s(uint32_t dst, const void* src, uint32_t bytes, uint32_t bar) {
  if (ONCE) asm volatile("cp.async.bulk" TMA_MB ".L2::cache_hint [%0], [%1], %2, [%3], %4;" ::"r"(dst), "l"(src), "r"(bytes), "r"(bar), "l"(EV_FIRST) : "memory");
  else asm volatile("cp.async.bulk" TMA_MB " [%0], [%1], %2, [%3];" ::"r"(dst), "l"(src), "r"(bytes), "r"(bar) : "memory");
}
__device__ __forceinline__ void tma2d_store(const CUtensorMap* tm, uint32_t src, int c0, int c1) {
  asm volatile("cp.async.bulk.tensor.2d.global.shared::cta.bulk_group [%0, {%2, %3}], [%1];" ::"l"(tm), "r"(src), "r"(c0), "r"(c1) : "memory");
}
__device__ __forceinline__ void prefetch_tm(const CUtensorMap* tm) { asm volatile("prefetch.tensormap [%0];" ::"l"(tm) : "memory"); }
__device__ __forceinline__ void wg_fence() { asm volatile("wgmma.fence.sync.aligned;" ::: "memory"); }
__device__ __forceinline__ void wg_commit() { asm volatile("wgmma.commit_group.sync.aligned;" ::: "memory"); }
template <int N> __device__ __forceinline__ void wg_wait() { asm volatile("wgmma.wait_group.sync.aligned %0;" ::"n"(N) : "memory"); }
__device__ __forceinline__ void bar_sync(int id, int n) { asm volatile("bar.sync %0, %1;" ::"r"(id), "r"(n) : "memory"); }
__device__ __forceinline__ void bar_arrive(int id, int n) { asm volatile("bar.arrive %0, %1;" ::"r"(id), "r"(n) : "memory"); }
__device__ __forceinline__ void fence_async_smem() { asm volatile("fence.proxy.async.shared::cta;" ::: "memory"); }
__device__ __forceinline__ void fence_async_all() { asm volatile("fence.proxy.async.global;" ::: "memory"); }
__device__ __forceinline__ uint32_t pack_bf16(float lo, float hi) { uint32_t r; asm("cvt.rn.bf16x2.f32 %0, %1, %2;" : "=r"(r) : "f"(hi), "f"(lo)); return r; }
__device__ __forceinline__ float ex2(float x) { float r; asm("ex2.approx.ftz.f32 %0, %1;" : "=f"(r) : "f"(x)); return r; }
__device__ __forceinline__ float rcp(float x) { float r; asm("rcp.approx.ftz.f32 %0, %1;" : "=f"(r) : "f"(x)); return r; }
__device__ __forceinline__ void flag_wait(const unsigned* f, unsigned target) {
  unsigned v;
  do { asm volatile("ld.acquire.gpu.global.u32 %0, [%1];" : "=r"(v) : "l"(f) : "memory"); } while (__any_sync(0xffffffffu, v < target));
}
__device__ __forceinline__ bool elect() {
  uint32_t r;
  asm volatile("{\n.reg .pred p;\nelect.sync _|p, -1;\nselp.u32 %0, 1, 0, p;\n}\n" : "=r"(r));
  return r;
}
__device__ __forceinline__ void fence_release() { asm volatile("fence.release.gpu;" ::: "memory"); }
__device__ __forceinline__ void flag_add(unsigned* f) { asm volatile("red.relaxed.gpu.global.inc.u32 [%0], 0x7fffffff;" ::"l"(f) : "memory"); }
__device__ __forceinline__ void cluster_arrive() { asm volatile("barrier.cluster.arrive.relaxed.aligned;" ::: "memory"); }
__device__ __forceinline__ void cluster_wait() { asm volatile("barrier.cluster.wait.aligned;" ::: "memory"); }
__device__ __forceinline__ uint32_t hmul2(uint32_t a, uint32_t b) { uint32_t r; asm("mul.rn.bf16x2 %0, %1, %2;" : "=r"(r) : "r"(a), "r"(b)); return r; }
__device__ __forceinline__ uint32_t hadd2(uint32_t a, uint32_t b) { uint32_t r; asm("add.rn.bf16x2 %0, %1, %2;" : "=r"(r) : "r"(a), "r"(b)); return r; }
__device__ __forceinline__ uint32_t hfma2(uint32_t a, uint32_t b, uint32_t c) { uint32_t r; asm("fma.rn.bf16x2 %0, %1, %2, %3;" : "=r"(r) : "r"(a), "r"(b), "r"(c)); return r; }
__device__ __forceinline__ uint32_t lds32(uint32_t a) { uint32_t r; asm volatile("ld.shared.b32 %0, [%1];" : "=r"(r) : "r"(a) : "memory"); return r; }
__device__ __forceinline__ uint4 lds128(uint32_t a) { uint4 r; asm volatile("ld.shared.v4.b32 {%0,%1,%2,%3}, [%4];" : "=r"(r.x), "=r"(r.y), "=r"(r.z), "=r"(r.w) : "r"(a) : "memory"); return r; }
__device__ __forceinline__ uint32_t desc_k(uint32_t addr) { return ((addr & 0x3FFFF) >> 4) | (1u << 16); }
template <int LBO> __device__ __forceinline__ uint32_t desc_mn(uint32_t addr) { return ((addr & 0x3FFFF) >> 4) | ((uint32_t)(LBO >> 4) << 16); }
#define DHI "0x40000040"

#define R8(d, o) "+f"(d[o]), "+f"(d[o + 1]), "+f"(d[o + 2]), "+f"(d[o + 3]), "+f"(d[o + 4]), "+f"(d[o + 5]), "+f"(d[o + 6]), "+f"(d[o + 7])
#define R32(d, o) R8(d, o), R8(d, o + 8), R8(d, o + 16), R8(d, o + 24)
#define R64(d, o) R32(d, o), R32(d, o + 32)
#define L64 "%0,%1,%2,%3,%4,%5,%6,%7,%8,%9,%10,%11,%12,%13,%14,%15,%16,%17,%18,%19,%20,%21,%22,%23,%24,%25,%26,%27,%28,%29,%30,%31," \
            "%32,%33,%34,%35,%36,%37,%38,%39,%40,%41,%42,%43,%44,%45,%46,%47,%48,%49,%50,%51,%52,%53,%54,%55,%56,%57,%58,%59,%60,%61,%62,%63"
#define L128 L64 ",%64,%65,%66,%67,%68,%69,%70,%71,%72,%73,%74,%75,%76,%77,%78,%79,%80,%81,%82,%83,%84,%85,%86,%87,%88,%89,%90,%91,%92,%93,%94,%95," \
            "%96,%97,%98,%99,%100,%101,%102,%103,%104,%105,%106,%107,%108,%109,%110,%111,%112,%113,%114,%115,%116,%117,%118,%119,%120,%121,%122,%123,%124,%125,%126,%127"

template <int TB> __device__ __forceinline__ void mma_ss_n128(float (&d)[64], uint32_t da, uint32_t db) {
  asm volatile("{\n.reg .b64 da, db;\nmov.b64 da, {%64, " DHI "};\nmov.b64 db, {%65, " DHI "};\n"
               "wgmma.mma_async.sync.aligned.m64n128k16.f32.bf16.bf16 {" L64 "}, da, db, 1, 1, 1, 0, %66;\n}\n"
               : R64(d, 0) : "r"(da), "r"(db), "n"(TB));
}
template <int TB> __device__ __forceinline__ void mma_rs_n128(float (&d)[64], uint32_t a0, uint32_t a1, uint32_t a2, uint32_t a3, uint32_t db, int sd) {
  asm volatile("{\n.reg .pred p;\n.reg .b64 db;\nsetp.ne.b32 p, %69, 0;\nmov.b64 db, {%68, " DHI "};\n"
               "wgmma.mma_async.sync.aligned.m64n128k16.f32.bf16.bf16 {" L64 "}, {%64,%65,%66,%67}, db, p, 1, 1, %70;\n}\n"
               : R64(d, 0) : "r"(a0), "r"(a1), "r"(a2), "r"(a3), "r"(db), "r"(sd), "n"(TB));
}
template <int TB> __device__ __forceinline__ void mma_ss_n256(float (&d)[128], uint32_t da, uint32_t db) {
  asm volatile("{\n.reg .b64 da, db;\nmov.b64 da, {%128, " DHI "};\nmov.b64 db, {%129, " DHI "};\n"
               "wgmma.mma_async.sync.aligned.m64n256k16.f32.bf16.bf16 {" L128 "}, da, db, 1, 1, 1, 0, %130;\n}\n"
               : R64(d, 0), R64(d, 64) : "r"(da), "r"(db), "n"(TB));
}
#define W8(d, o) "=f"(d[o]), "=f"(d[o + 1]), "=f"(d[o + 2]), "=f"(d[o + 3]), "=f"(d[o + 4]), "=f"(d[o + 5]), "=f"(d[o + 6]), "=f"(d[o + 7])
#define W32(d, o) W8(d, o), W8(d, o + 8), W8(d, o + 16), W8(d, o + 24)
#define W64(d, o) W32(d, o), W32(d, o + 32)
template <int TB> __device__ __forceinline__ void mma_ss_n128_init(float (&d)[64], uint32_t da, uint32_t db) {
  asm volatile("{\n.reg .b64 da, db;\nmov.b64 da, {%64, " DHI "};\nmov.b64 db, {%65, " DHI "};\n"
               "wgmma.mma_async.sync.aligned.m64n128k16.f32.bf16.bf16 {" L64 "}, da, db, 0, 1, 1, 0, %66;\n}\n"
               : W64(d, 0) : "r"(da), "r"(db), "n"(TB));
}
template <int TB> __device__ __forceinline__ void mma_ss_n256_init(float (&d)[128], uint32_t da, uint32_t db) {
  asm volatile("{\n.reg .b64 da, db;\nmov.b64 da, {%128, " DHI "};\nmov.b64 db, {%129, " DHI "};\n"
               "wgmma.mma_async.sync.aligned.m64n256k16.f32.bf16.bf16 {" L128 "}, da, db, 0, 1, 1, 0, %130;\n}\n"
               : W64(d, 0), W64(d, 64) : "r"(da), "r"(db), "n"(TB));
}
#define L32 "%0,%1,%2,%3,%4,%5,%6,%7,%8,%9,%10,%11,%12,%13,%14,%15,%16,%17,%18,%19,%20,%21,%22,%23,%24,%25,%26,%27,%28,%29,%30,%31"
__device__ __forceinline__ void mma_ss_n64(float (&d)[32], uint32_t da, uint32_t db) {
  asm volatile("{\n.reg .b64 da, db;\nmov.b64 da, {%32, " DHI "};\nmov.b64 db, {%33, " DHI "};\n"
               "wgmma.mma_async.sync.aligned.m64n64k16.f32.bf16.bf16 {" L32 "}, da, db, 1, 1, 1, 0, 0;\n}\n"
               : R32(d, 0) : "r"(da), "r"(db));
}
__device__ __forceinline__ void mma_ss_n64_init(float (&d)[32], uint32_t da, uint32_t db) {
  asm volatile("{\n.reg .b64 da, db;\nmov.b64 da, {%32, " DHI "};\nmov.b64 db, {%33, " DHI "};\n"
               "wgmma.mma_async.sync.aligned.m64n64k16.f32.bf16.bf16 {" L32 "}, da, db, 0, 1, 1, 0, 0;\n}\n"
               : W32(d, 0) : "r"(da), "r"(db));
}
#define L16 "%0,%1,%2,%3,%4,%5,%6,%7,%8,%9,%10,%11,%12,%13,%14,%15"
template <int O, bool INIT> __device__ __forceinline__ void mma_rs_n32(float (&d)[128], uint32_t a0, uint32_t a1, uint32_t a2, uint32_t a3, uint32_t db) {
  if (INIT) asm volatile("{\n.reg .b64 db;\nmov.b64 db, {%20, 0x00000008};\n"
               "wgmma.mma_async.sync.aligned.m64n32k16.f32.bf16.bf16 {" L16 "}, {%16,%17,%18,%19}, db, 0, 1, 1, 0;\n}\n"
               : W8(d, O), W8(d, O + 8) : "r"(a0), "r"(a1), "r"(a2), "r"(a3), "r"(db));
  else asm volatile("{\n.reg .b64 db;\nmov.b64 db, {%20, 0x00000008};\n"
               "wgmma.mma_async.sync.aligned.m64n32k16.f32.bf16.bf16 {" L16 "}, {%16,%17,%18,%19}, db, 1, 1, 1, 0;\n}\n"
               : R8(d, O), R8(d, O + 8) : "r"(a0), "r"(a1), "r"(a2), "r"(a3), "r"(db));
}
template <int S, int J> __device__ __forceinline__ void conv_step(float (&d)[128], const uint32_t (&a)[64], uint32_t db) {
  if constexpr (J >= 0 && J >= (S >> 1)) {
    mma_rs_n32<16 * J, S == 0>(d, a[4 * S], a[4 * S + 1], a[4 * S + 2], a[4 * S + 3], db + (uint32_t)((2 * J - S) * 16));
    conv_step<S, J - 1>(d, a, db);
  }
}
__device__ __forceinline__ void mma_ss_n8(float (&d)[4], uint32_t da, uint32_t db) {
  asm volatile("{\n.reg .b64 da, db;\nmov.b64 da, {%4, " DHI "};\nmov.b64 db, {%5, 0x00000008};\n"
               "wgmma.mma_async.sync.aligned.m64n8k16.f32.bf16.bf16 {%0,%1,%2,%3}, da, db, 1, 1, 1, 0, 0;\n}\n"
               : "+f"(d[0]), "+f"(d[1]), "+f"(d[2]), "+f"(d[3]) : "r"(da), "r"(db));
}
template <int N> __device__ __forceinline__ void reg_fence(float (&d)[N]) {
#pragma unroll
  for (int i = 0; i < N; i++) asm volatile("" : "+f"(d[i])::"memory");
}
template <int N> __device__ __forceinline__ void reg_fence(uint32_t (&d)[N]) {
#pragma unroll
  for (int i = 0; i < N; i++) asm volatile("" : "+r"(d[i])::"memory");
}

struct __align__(64) Params {
  unsigned* flags;
  int zero;
  uint8_t pref[128];
  const __nv_bfloat16 *gate_w, *ak, *av, *shk, *ssk, *ssd;
  CUtensorMap x, c, wq, wuk, wuv, wo, x3, y3, out, w;
};

template <int O, int N, int M> __device__ __forceinline__ void pack_frag(const float (&acc)[N], uint32_t (&pk)[M]) {
#pragma unroll
  for (int i = 0; i < 32; i++) pk[i] = pack_bf16(acc[O + 2 * i], acc[O + 2 * i + 1]);
}
template <int J0 = 0, int J1 = 8, int M> __device__ __forceinline__ void stsm_frag(const uint32_t (&pk)[M], uint32_t a) {
#pragma unroll
  for (int jj = J0; jj < J1; jj++)
    asm volatile("stmatrix.sync.aligned.m8n8.x4.shared.b16 [%0], {%1,%2,%3,%4};" ::"r"((a ^ ((jj & 3) << 5)) + (jj >> 2) * 16384),
                 "r"(pk[4 * jj]), "r"(pk[4 * jj + 1]), "r"(pk[4 * jj + 2]), "r"(pk[4 * jj + 3]) : "memory");
}

template <int N> __device__ __forceinline__ void store_scaled(const float (&acc)[N], float s0, float s1, uint32_t a, uint32_t never_zero) {
  float t[8];
#pragma unroll
  for (int jj = 0; jj < 8; jj++) {
    float v = acc[8 * jj] * s0;
    if (jj >= RST) {
      v = t[jj - RST];
      asm("{\n.reg .pred p;\nsetp.ne.u32 p, %3, 0;\n@p mul.f32 %0, %1, %2;\n}\n" : "+f"(v) : "f"(acc[8 * jj]), "f"(s0), "r"(never_zero));
    }
    const uint32_t q = pack_bf16(v, acc[8 * jj + 1] * s0);
    t[jj] = __uint_as_float(q);
    asm volatile("stmatrix.sync.aligned.m8n8.x4.shared.b16 [%0], {%1,%2,%3,%4};" ::"r"((a ^ ((jj & 3) << 5)) + (jj >> 2) * 16384), "r"(q),
                 "r"(pack_bf16(acc[8 * jj + 2] * s1, acc[8 * jj + 3] * s1)), "r"(pack_bf16(acc[8 * jj + 4] * s0, acc[8 * jj + 5] * s0)),
                 "r"(pack_bf16(acc[8 * jj + 6] * s1, acc[8 * jj + 7] * s1)) : "memory");
  }
}

struct Cons {
  uint32_t sb;
  uint32_t pf;
  int wg, tid;
  __device__ __forceinline__ void wait_full(int g) { mbar_wait(sb + SM_BAR + (B_FULL + g) * 8, (pf >> g) & 1); pf ^= 1u << g; }
  uint32_t relb;
  __device__ __forceinline__ void release(int g, int n) {
    if (tid < 2 * n) asm volatile("mbarrier.arrive.shared::cluster.b64 _, [%0];" ::"r"(relb + g * 8) : "memory");
  }
  __device__ __forceinline__ void turn_begin() { bar_sync(1 + wg, 256); }
  __device__ __forceinline__ void turn_end() { bar_arrive(2 - wg, 256); }
  __device__ __forceinline__ void staged(int e) { __syncwarp(); if ((tid & 31) == 0) mbar_arrive(sb + SM_BAR + (B_EV + 2 * e + wg) * 8); }
  int zero;
  int rnd;
  uint32_t pfree;
  __device__ __forceinline__ void wait_stage_free() { mbar_wait(sb + SM_BAR + (B_FREE + wg) * 8, pfree); pfree ^= 1; }
  __device__ __forceinline__ bool try_full(int g) { return mbar_test(sb + SM_BAR + (B_FULL + g) * 8, (pf >> g) & 1); }
};

constexpr float SM_C = 0.08838834764831845f * 1.4426950408889634f;
struct SoftState { float m0, m1, l0, l1; int shifted; };
__device__ __forceinline__ void ex2_rot(float& t, float s, uint32_t never_zero) {
  asm("{\n.reg .pred p;\nsetp.ne.u32 p, %2, 0;\n@p ex2.approx.ftz.f32 %0, %1;\n}\n" : "+f"(t) : "f"(s), "r"(never_zero));
}
__device__ __forceinline__ void pin(float a, uint32_t never_zero) {
  asm volatile("{\n.reg .pred p;\nsetp.eq.u32 p, %1, 0;\n@p st.shared.f32 [%1], %0;\n}\n" ::"f"(a), "r"(never_zero) : "memory");
}
template <int O, int N> __device__ __forceinline__ void reg_fence_part(uint32_t (&d)[32]) {
#pragma unroll
  for (int i = O; i < O + N; i++) asm volatile("" : "+r"(d[i])::"memory");
}
template <int Q, int W, int N> __device__ __forceinline__ void exp_quarter(const float (&S)[N], uint32_t (&P)[32], float (&t)[ROT], float& s0, float& s1, uint32_t nz) {
#pragma unroll
  for (int i = 8 * Q; i < 8 * Q + 8; i++) {
    float& a = t[(2 * i) % ROT];
    float& b = t[(2 * i + 1) % ROT];
    if (2 * i < ROT) { a = ex2(S[2 * i]); b = ex2(S[2 * i + 1]); }
    else { ex2_rot(a, S[2 * i], nz); ex2_rot(b, S[2 * i + 1], nz); }
    if (i < 2) { if (i) s1 = a + b; else s0 = a + b; }
    else if (i & 1) { s1 += a; s1 += b; } else { s0 += a; s0 += b; }
    if (i == 8 * Q) { pin(Q ? s1 : s0, nz); wg_wait<W>(); reg_fence_part<8 * Q, 8>(P); }
    P[i] = pack_bf16(a, b);
  }
}
template <int N> __device__ __forceinline__ void shift_scores(float (&S)[N], float d0, float d1) {
#pragma unroll
  for (int i = 0; i < N; i++) S[i] -= (i & 2) ? d1 : d0;
}
__device__ __forceinline__ bool soft_high(float s0, float s1, float lim = SM_LIMIT) { return s0 > lim || s1 > lim; }
__device__ __forceinline__ bool soft_unsafe(float s0, float s1, bool first) {
  uint32_t b0 = __ballot_sync(0xffffffffu, s0 >= SM_LOW), b1 = __ballot_sync(0xffffffffu, s1 >= SM_LOW);
  b0 |= b0 >> 1; b0 |= b0 >> 2; b1 |= b1 >> 1; b1 |= b1 >> 2;
  return __any_sync(0xffffffffu, soft_high(s0, s1)) || (first && (b0 & b1 & 0x11111111u) != 0x11111111u);
}
template <int N> __device__ __forceinline__ void soft_fix(const float (&S)[N], float (&O)[64], SoftState& z, bool first, float& d0, float& d1) {
  d0 = d1 = first ? -INFINITY : 0.f;
#pragma unroll
  for (int j = 0; j < N / 4; j++) { d0 = fmaxf(d0, fmaxf(S[4 * j], S[4 * j + 1])); d1 = fmaxf(d1, fmaxf(S[4 * j + 2], S[4 * j + 3])); }
  d0 = fmaxf(d0, __shfl_xor_sync(0xffffffffu, d0, 1)); d1 = fmaxf(d1, __shfl_xor_sync(0xffffffffu, d1, 1));
  d0 = fmaxf(d0, __shfl_xor_sync(0xffffffffu, d0, 2)); d1 = fmaxf(d1, __shfl_xor_sync(0xffffffffu, d1, 2));
  const float sc0 = ex2(-fmaxf(d0, 0.f)), sc1 = ex2(-fmaxf(d1, 0.f));
  z.m0 += d0; z.m1 += d1; z.l0 *= sc0; z.l1 *= sc1; z.shifted = 1;
#pragma unroll
  for (int j = 0; j < 16; j++) { O[4 * j] *= sc0; O[4 * j + 1] *= sc0; O[4 * j + 2] *= sc1; O[4 * j + 3] *= sc1; }
}
template <int N> __device__ __forceinline__ void mask_diag(float (&S)[N], float nd) {
  asm volatile("" : "+f"(nd));
#pragma unroll
  for (int i = 0; i < 32; i++) {
    const float beyond = __saturatef(nd + (float)(8 * (i >> 2) + (i & 1) - 4 * (i & 2)));
    S[N - 32 + i] = fmaf(beyond, -3.0e38f, S[N - 32 + i]);
  }
}
__device__ __forceinline__ float quad_sum(float v) {
  v += __shfl_xor_sync(0xffffffffu, v, 1);
  v += __shfl_xor_sync(0xffffffffu, v, 2);
  return v;
}
__device__ __forceinline__ void issue_qk(float (&S)[64], uint32_t dq, uint32_t dk) {
  mma_ss_n128_init<0>(S, dq, dk);
#pragma unroll
  for (int s = 1; s < 8; s++) mma_ss_n128<0>(S, dq + (s >> 2) * 1024 + (s & 3) * 2, dk + (s >> 2) * 1024 + (s & 3) * 2);
}
__device__ __forceinline__ void issue_qk(float (&S)[32], uint32_t dq, uint32_t dk) {
  mma_ss_n64_init(S, dq, dk);
#pragma unroll
  for (int s = 1; s < 8; s++) mma_ss_n64(S, dq + (s >> 2) * 1024 + (s & 3) * 2, dk + (s >> 2) * 1024 + (s & 3) * 2);
}
template <int H> __device__ __forceinline__ void issue_pv(float (&O)[64], const uint32_t (&P)[32], uint32_t dv, int acc, bool on) {
  if (on) {
#pragma unroll
    for (int s = 4 * H; s < 4 * H + 4; s++) {
      mma_rs_n128<1>(O, P[4 * s], P[4 * s + 1], P[4 * s + 2], P[4 * s + 3], dv + s * 128, s != 0 ? 1 : acc);
      if (s & 1) wg_commit();
    }
  } else { wg_commit(); wg_commit(); }
}
constexpr uint32_t DG = GR >> 4;
__device__ __forceinline__ void stage_q2(Cons& c, const float (&O)[64], uint32_t (&P)[32], uint32_t stg) {
  wg_commit(); wg_commit(); wg_commit(); wg_commit();
  c.turn_end();
  pack_frag<0>(O, P);
  stsm_frag(P, stg);
  fence_async_smem();
}
__device__ __forceinline__ void attn_half(Cons& c, float (&O)[64], uint32_t (&P)[32], SoftState& z, uint32_t dk0, uint32_t dkk, uint32_t dv0, float dmask, int last) {
  float S[32];
  FTH(8 + last * 32, 0);
  c.turn_begin();
  FTH(9 + last * 32, 0);
  wg_fence();
  issue_qk(S, dk0 + (last ? 0 : 2 * DG), dkk + (last ? 8 : 4) * DG);
  wg_commit();
  issue_pv<0>(O, P, dv0 + 10 * DG, 1, last);
  issue_pv<1>(O, P, dv0 + 10 * DG, 1, last);
  c.turn_end();
  c.wait_full(last ? 12 : 6);
  FTH(10 + last * 32, 0);
  wg_wait<4>();
  reg_fence(S);
  FTH(11 + last * 32, 0);
  c.release(last ? 8 : 4, 2);
  mask_diag(S, dmask);
  float s0, s1, d0 = z.m0, d1 = z.m1;
#pragma unroll 1
  for (int pass = 0;; pass++) {
    if (z.shifted) shift_scores(S, d0, d1);
    float tr[ROT];
    exp_quarter<0, 3>(S, P, tr, s0, s1, c.sb);
    exp_quarter<1, 2>(S, P, tr, s0, s1, c.sb);
    pin(s1, c.sb); wg_wait<0>(); reg_fence_part<16, 16>(P); reg_fence(O);
    if (!soft_unsafe(s0, s1, !last) || pass) break;
    soft_fix(S, O, z, !last, d0, d1);
  }
  FTH(12 + last * 32, 0);
  z.l0 += s0; z.l1 += s1;
  c.release(10, last ? 2 : 0);
  if (!last) c.wait_full(8);
  FTH(13 + last * 32, 0);
}

template <int V> struct IC { static constexpr int value = V; };
__device__ __forceinline__ int conv_next(int g, bool spare) { return g >= NGR - 2 ? g - (NGR - 4) : !spare && g == 4 ? 1 : g + 2; }
__device__ __forceinline__ void conv_final(uint32_t rb, uint32_t yb, bool on) {
  const uint4 q0 = lds128(rb), q1 = lds128(rb + 4096), q2 = lds128(rb + 8192), q3 = lds128(rb + 12288);
  auto fin = [&](uint32_t x0, uint32_t x1, uint32_t x2, uint32_t x3) { return hadd2(hadd2(x0, x1), hadd2(x2, x3)); };
  asm volatile("{\n.reg .pred p;\nsetp.ne.b32 p, %5, 0;\n@p st.shared.v4.b32 [%0], {%1,%2,%3,%4};\n}\n" ::"r"(yb), "r"(fin(q0.x, q1.x, q2.x, q3.x)),
               "r"(fin(q0.y, q1.y, q2.y, q3.y)), "r"(fin(q0.z, q1.z, q2.z, q3.z)), "r"(fin(q0.w, q1.w, q2.w, q3.w)), "r"((int)on) : "memory");
}
__device__ __forceinline__ void conv_tasks(Cons& c, const Params& p, int ntask, bool spare, int ch, int chstep, int c5, uint32_t dd, uint32_t dkk, int w, int lane) {
  const uint32_t sb = c.sb;
  int g = 2 + c.wg;
  uint32_t rb = sb + g * GR;
  const uint32_t yb = sb + c.wg * 8192 + c.tid * 16;
  const int gt = 8 * w + (lane >> 2) + (lane & 3);
  uint32_t a[64], hb;
  auto lda = [&](int s) {
    a[4 * s] = lds32(hb + s * 256); a[4 * s + 1] = lds32(hb + s * 256 + 128);
    a[4 * s + 2] = lds32(hb + s * 256 + 16); a[4 * s + 3] = lds32(hb + s * 256 + 144);
  };
  auto first_a = [&]() {
    hb = sb + g * GR + WBYTES - 28 + gt * 4;
    lda(0); lda(15);
  };
  c.wait_full(g);
  first_a();
#pragma unroll 1
  for (int i = 0; i < ntask; i++) {
    const uint32_t base = sb + g * GR;
    FTC(0);
    lda(1); lda(14);
    a[0] = hadd2(a[0], gt == 7 ? dd : 0u); a[2] = hadd2(a[2], gt == 3 ? dd : 0u);
    float acc[128];
    const uint32_t db = dkk + ((WPL / 16 - 1) << 16) + g * DG + WZ / 16;
    FTC(2);
    c.turn_begin();
    FTC(3);
    auto pair = [&](auto kc) {
      constexpr int k = decltype(kc)::value;
      if (k < 7) wg_fence();
      if (k == 6) c.turn_end();
      conv_step<k, 7>(acc, a, db);
      conv_step<15 - k, 7>(acc, a, db);
      if (k < 6) { lda(k + 2); lda(13 - k); }
      if (k == 0) conv_final(rb, yb, i > 0);
      if (k == 1) {
        conv_final(rb + 2048, yb + 2048, i > 0);
        __syncwarp();
        if (lane == 0 && i > 0) mbar_arrive(sb + SM_BAR + (B_EV + c.wg) * 8);
      }
      if (k == 6) dd = __bfloat16_as_ushort(p.ssd[(ch + chstep + (i == 1 ? c5 : 0)) & (DM - 1)]);
    };
    pair(IC<0>()); pair(IC<1>()); pair(IC<2>()); pair(IC<3>()); pair(IC<4>()); pair(IC<5>()); pair(IC<6>()); pair(IC<7>());
    wg_commit();
    FTC(4);
    g = conv_next(g, spare);
    ch += chstep;
    rb = base + c.tid * 16;
    if (i + 1 < ntask) c.wait_full(g);
    const bool fr = mbar_test(sb + SM_BAR + (B_FREE + c.wg) * 8, c.pfree);
    wg_wait<0>();
    reg_fence(acc);
    reg_fence(a);
    bar_sync(3 + c.wg, 128);
    FTC(5);
    first_a();
    const int tw = (lane & 3) + w;
    const uint32_t xb = base + w * 4096 + tw * 32 + (lane >> 2) * 4;
    [[maybe_unused]] float t0[EROT + 1];
#pragma unroll
    for (int j = 0; j < 32; j++) {
      uint32_t ad = xb + j * 128;
      float v0 = acc[4 * j], v1 = acc[4 * j + 1];
      if (EROT && j > EROT) {
        v0 = t0[j % (EROT + 1)];
        asm("{\n.reg .pred p;\nsetp.ne.u32 p, %3, 0;\n@p add.f32 %0, %1, %2;\n}\n" : "+f"(v0) : "f"(acc[4 * j]), "f"(acc[j > 0 ? 4 * j - 2 : 0]), "r"(sb));
      } else if (j > 0) v0 += acc[j > 0 ? 4 * j - 2 : 0];
      if (j > 0) v1 += acc[j > 0 ? 4 * j - 1 : 0];
      uint32_t v = pack_bf16(v0, v1);
      t0[j % (EROT + 1)] = __uint_as_float(v);
      if (j == 31 && tw >= 4) { v = 0; ad -= 4096; }
      asm volatile("st.shared.b32 [%0], %1;" ::"r"(ad), "r"(v) : "memory");
    }
    if (!fr) c.wait_stage_free(); else c.pfree ^= 1;
    FTC(6);
  }
  bar_sync(3 + c.wg, 128);
  conv_final(rb, yb, true);
  conv_final(rb + 2048, yb + 2048, true);
  c.staged(0);
}

__global__ void __cluster_dims__(2, 1, 1) __launch_bounds__(NTHREADS, 1) mega_kernel(const __grid_constant__ Params p) {
  extern __shared__ __align__(1024) uint8_t smem_raw[];
  FTS(0);
  const uint32_t sb = smem_u32(smem_raw);
  if (threadIdx.x - 64 < 32) { prefetch_tm(&p.c); prefetch_tm(&p.wuk + (blockIdx.x & 1)); }
  const int wgi = __shfl_sync(0xffffffffu, threadIdx.x >> 7, 0);
  const int warp = __shfl_sync(0xffffffffu, threadIdx.x >> 5, 0);
  const uint32_t rank = blockIdx.x & 1;
  int slot;
  {
    uint32_t smid; asm volatile("mov.u32 %0, %smid;" : "=r"(smid));
    slot = p.pref[((smid >> 1) + (threadIdx.x & (smid >> 16))) & 127];
  }
  if (warp >= 3) {
    if (elect()) {
#pragma unroll
      for (int k = 0; k < 4; k++) mbar_init(sb + SM_BAR + ((warp - 3) * 4 + k) * 8, k == 1 && warp == 7 ? 11 : warp < (k ? 7 : 8) ? 1 : 4);
      if (warp == 7) { mbar_init(sb + SM_BAR + B_TICK * 8, 1); mbar_expect_tx(sb + SM_BAR + B_SLOT * 8, 8); mbar_expect_tx(sb + SM_BAR + B_TICK * 8, 4); }
      asm volatile("fence.mbarrier_init.release.cluster;" ::: "memory");
    }
    __syncwarp();
  }
  FTS(1);
  cluster_arrive();
  slot = __shfl_sync(0xffffffffu, slot, 0);
  const int pref = slot;
  if (warp < 4) {
    asm volatile("setmaxnreg.dec.sync.aligned.u32 40;");
    if (warp == 1 + 4 * rank) {
      unsigned taken = threadIdx.x == 32;
#pragma unroll 1
      for (int n = 0; n < NSLOT; n++) {
        asm volatile("{\n.reg .pred p;\nsetp.ne.b32 p, %0, 0;\n@p atom.relaxed.gpu.global.exch.b32 %0, [%1], 1;\n}\n" : "+r"(taken) : "l"(CLAIMP(slot)) : "memory");
        if (!__any_sync(0xffffffffu, taken)) break;
        slot = slot == NSLOT - 1 ? 0 : slot + 1;
      }
    }
    cluster_wait();
    if (threadIdx.x == 32) {
      send_both(sb + SM_BAR + B_SLOT * 8, (V_SLOT - B_SLOT) * 8 + rank * 4, slot | pref << 8);
    }
    if (warp == 2) {
#pragma unroll 1
      for (int kk = 0; kk < 4; kk++) {
        const int g0 = 2 + 3 * kk;
        const uint32_t fb = sb + SM_BAR + (B_FULL + g0) * 8;
        if (elect()) {
          FTSW(kk);
          mbar_expect_tx(fb, 3 * GR);
          tma2d(sb + g0 * GR, &p.c, kk * 64, (KV_ROW(pref & 7, 0) + rank) * 128, fb);
          tma3d_mc(sb + (g0 + 1 + rank) * GR, rank ? &p.wuv : &p.wuk, 0, kk * 64, ((pref & 56) >> 1) + 2 * KV_HEAD(pref & 7, 0), fb);
        }
        if (kk < 3) {
          uint32_t c0, c1;
          asm volatile("mov.u32 %0, %clock;" : "=r"(c0));
          do asm volatile("mov.u32 %0, %clock;" : "=r"(c1)); while (c1 - c0 < (kk ? X_D2 : X_DELAY));
        }
      }
      FTSW(4);
      prefetch_tm(&p.x); prefetch_tm(&p.wq);
    }
  }
  int grp, idx, lb;
  int cn, cch, cstep;
  bool spare, redo;
  auto get_slot = [&]() {
    mbar_wait(sb + SM_BAR + B_SLOT * 8, 0);
    const uint32_t sv0 = __shfl_sync(0xffffffffu, lds32(sb + SM_BAR + V_SLOT * 8), 0), sv1 = __shfl_sync(0xffffffffu, lds32(sb + SM_BAR + V_SLOT * 8 + 4), 0);
    grp = (sv0 & 255) >> 3; idx = sv0 & 7; lb = (sv0 & 255) * 2 + rank;
    spare = grp == 8; redo = spare || sv0 != sv1;
    cn = CN_SPARE; cch = spare ? lb - NMAIN : 4 * CN_SPARE + 4 * lb; cstep = spare ? 4 : 1;
    if (FINE_MODE != 7) TS(0);
  };
  auto get_ticket = [&]() {
    mbar_wait(sb + SM_BAR + B_TICK * 8, 0);
    const int tk = __shfl_sync(0xffffffffu, lds32(sb + SM_BAR + V_TICK * 8), 0);
    cn = tk < NTICK ? 5 : 4;
    return 4 * NMAIN - 4 * lb - 4 + 2 * tk + rank;
  };

  if (wgi == 0) {
    asm volatile("setmaxnreg.dec.sync.aligned.u32 40;");
    const int lane = threadIdx.x & 31;
    cluster_arrive();
    get_slot();
    uint32_t pe = 0;
    auto acquire = [&](int g, int n, uint32_t m) {
      int i = g;
#pragma unroll 1
      do mbar_wait1(sb + SM_BAR + (B_EMPTY + i) * 8, (pe >> i) & 1); while (++i < g + n);
      pe ^= m << g;
    };
    if (warp == 3) {
      if (!spare) {
        const int s0 = lb * 16;
#pragma unroll 1
        for (int cg = 0; cg < 16; cg++) {
          if (cg == UP0 || cg == UP1) {
#pragma unroll 1
            for (int n = 0; n < 20 && !__any_sync(0xffffffffu, mbar_try(sb + SM_BAR + B_SLOT * 8, cg == UP0)); n++);
          } else if (cg < UP0) __nanosleep(US0);
          if (cg == UP1 && lane == rank * 32) send_both(sb + SM_BAR + B_TICK * 8, (V_TICK - B_TICK) * 8, atomicInc(FLAG(F_TICK), 0x7fffffffu));
          const int ch = cg * 64 + 2 * lane;
          const uint32_t* kp = reinterpret_cast<const uint32_t*>(p.ak + (size_t)s0 * DM + ch);
          const uint32_t* vp = reinterpret_cast<const uint32_t*>(p.av + (size_t)s0 * DM + ch);
          const uint4 sw = __ldg(reinterpret_cast<const uint4*>(p.shk + ch * 4));
          uint32_t k3 = 0, k2 = 0, k1 = 0, k0 = 0, up = 0;
          if (lb > 0) { k3 = ldg_stream(kp - 4 * 512); k2 = ldg_stream(kp - 3 * 512); k1 = ldg_stream(kp - 2 * 512); k0 = ldg_stream(kp - 512); up = ldg_stream(vp - 512); }
          const uint32_t w0 = __byte_perm(sw.x, sw.z, 0x5410), w1 = __byte_perm(sw.x, sw.z, 0x7632);
          const uint32_t w2 = __byte_perm(sw.y, sw.w, 0x5410), w3 = __byte_perm(sw.y, sw.w, 0x7632);
          up = hmul2(hfma2(k0, w0, hfma2(k1, w1, hfma2(k2, w2, hmul2(k3, w3)))), up);
#pragma unroll 1
          for (int hb = 0; hb < 2; hb++) {
            uint32_t kk[8], u[8];
#pragma unroll
            for (int r = 0; r < 8; r++) { kk[r] = ldg_stream(kp + r * 512); u[r] = ldg_stream(vp + r * 512); }
#pragma unroll
            for (int r = 0; r < 8; r++) {
              k3 = k2; k2 = k1; k1 = k0; k0 = kk[r];
              u[r] = hmul2(hfma2(k0, w0, hfma2(k1, w1, hfma2(k2, w2, hmul2(k3, w3)))), u[r]);
            }
            if (lane == 0) asm volatile("cp.async.bulk.wait_group.read 0;" ::: "memory");
            __syncwarp();
            const uint32_t dst = sb + SM_UST + lane * 32 + ((lane & 4) << 2);
#pragma unroll
            for (int cc = 0; cc < 2; cc++) {
              const uint32_t sel = cc ? 0x7632 : 0x5410;
              asm volatile("st.shared.v4.b32 [%0], {%1,%2,%3,%4};" ::"r"(dst + cc * 1024), "r"(__byte_perm(u[6], u[5], sel)), "r"(__byte_perm(u[4], u[3], sel)),
                           "r"(__byte_perm(u[2], u[1], sel)), "r"(__byte_perm(u[0], up, sel)) : "memory");
              asm volatile("st.shared.v4.b32 [%0], {%1,%2,%3,%4};" ::"r"((dst ^ 16) + cc * 1024), "r"(__byte_perm(u[7], u[6], sel)), "r"(__byte_perm(u[5], u[4], sel)),
                           "r"(__byte_perm(u[3], u[2], sel)), "r"(__byte_perm(u[1], u[0], sel)) : "memory");
            }
            fence_async_smem();
            __syncwarp();
            if (lane == 0) {
              asm volatile("cp.async.bulk.tensor.3d.global.shared::cta.bulk_group.L2::cache_hint [%0, {%2, %3, %4}], [%1], %5;\ncp.async.bulk.commit_group;"
                           ::"l"(&p.w), "r"(sb + SM_UST), "r"(WZ / 2 + lb * 16 + (hb ^ 1) * (WPL / 2)), "r"(cg * 32), "r"(0), "l"(cg >= UP0 && cg < UP1 ? EV_FIRST : EV_NORMAL) : "memory");
            }
            up = u[7];
            kp += 8 * 512; vp += 8 * 512;
          }
          if ((cg & (cg + 1)) == 0 && lane == 0) {
            asm volatile("cp.async.bulk.wait_group 0;" ::: "memory");
            fence_release();
            flag_add(FLAG(F_U + 32 - __clz(cg)));
          }
          TSW(10 + cg);
        }
        prefetch_tm(&p.wo); prefetch_tm(&p.x3); prefetch_tm(&p.y3); prefetch_tm(&p.out);
      } else {
#pragma unroll 1
        for (int i = 0, g = 2; i < 32; i++) {
          acquire(g, 2, 3);
          if (elect()) {
            const uint32_t fb = sb + SM_BAR + (B_FULL + g) * 8;
            if (i == 0) { mbar_expect_tx(fb - 8, 2048); bulk_g2s(sb + GR, p.gate_w, 2048, fb - 8); }
            mbar_expect_tx(fb, 2 * GR);
            tma3d(sb + g * GR, &p.x3, 0, (lb - NMAIN) * 512 + (i >> 3) * 128, (i & 7) * 2, fb);
          }
          g = g == NGR - 2 ? 2 : g + 2;
        }
        bar_arrive(5, 64);
      }
      unsigned long long t0, t1;
      asm volatile("mov.u64 %0, %globaltimer;" : "=l"(t0));
      auto check = [&]() {
        asm volatile("mov.u64 %0, %globaltimer;" : "=l"(t1));
        if (t1 - t0 > 2000000000ull) __trap();
      };
      if (!spare) {
        unsigned v;
        do {
          __nanosleep(PSL);
          check();
          asm volatile("ld.acquire.gpu.global.u32 %0, [%1];" : "=r"(v) : "l"(FLAG(lane & 1 ? F_Y + idx : F_GATE)) : "memory");
        } while (__any_sync(0xffffffffu, v < (lane & 1 ? 128 : 32)));
        __syncwarp();
        if (lane == 0) mbar_arrive(sb + SM_BAR + B_SLOT * 8);
      }
      if (lane == 0) {
        while (!mbar_try(sb + SM_BAR + B_DONE * 8, 0)) check();
      }
    } else if (warp != 0) {
      const int w = warp - 1;
      int ne = 12 + (CN_SPARE + 1 - w) / 2, c5 = 0;
      uint32_t p0 = 0;
      int cg = 2 + w, ch = cch + w * cstep;
#pragma unroll 1
      for (int e = spare ? 12 : 0; e < ne; e++) {
        const int rnd = e >= 6, k = e - 6 * rnd, rt = k == 4 ? idx : 15 - idx;
        uint8_t* dst = k < 4 ? g_kv + (size_t)(((k & 1) * 16 + 2 * grp + KV_HEAD(idx, k >> 1)) * 16 + KV_ROW(idx, k >> 1) + rank) * 32768 + w * 8192
                     : k < 6 ? g_cimg + (size_t)(rt * 32 + 16 * rnd + 2 * grp + rank) * 32768 + (w ^ (k & 1)) * 8192
                             : g_w + (size_t)ch * WSTRIDE + WZ;
        const uint32_t src = sb + w * 8192 + (k == 4 ? 2 * GR : 0);
        if (e == 11) { c5 = get_ticket(); ne = 12 + ((cn + 1 - w) >> 1); }
        if (e == 6) flag_wait(FLAG(F_AD + grp), 32);
        mbar_wait1(sb + SM_BAR + (B_EV + (k == 4 ? 2 : 0) + w) * 8, k == 4 ? rnd : p0);
        if (k != 4) p0 ^= 1;
        if (lane < 4 && k >= 6 && (!spare || e < ne - 6)) mbar_arrive_cluster(sb + SM_BAR + (B_EMPTY + cg) * 8, lane & 1);
        fence_async_smem();
        if (elect()) {
          const uint32_t cs = k >= 6 ? 4096 : 1024;
#pragma unroll 1
          for (uint32_t i = 0; i < (k >= 6 ? 4096 : 16384); i += cs) {
            const uint32_t o = i + (i & 8192);
            asm volatile("cp.async.bulk.global.shared::cta.bulk_group.L2::cache_hint [%0], [%1], %2, %3;" ::"l"(dst + o), "r"(src + o), "r"(cs),
                         "l"(e == 4 || e == 5 || spare ? EV_FIRST : EV_NORMAL) : "memory");
            asm volatile("cp.async.bulk.commit_group;\ncp.async.bulk.wait_group.read 1;" ::: "memory");
          }
          asm volatile("cp.async.bulk.wait_group 0;" ::: "memory");
          if (k != 4) mbar_arrive(sb + SM_BAR + (B_FREE + w) * 8);
        }
        __syncwarp();
        if (lane < (k == 4 ? 4 : e == 11 || (e == ne - 1 && !spare) ? 2 : 0))
          mbar_arrive_cluster(sb + SM_BAR + (B_EMPTY + (k == 4 ? 2 : e == 11) + (lane >> 1)) * 8, lane & 1);
        if (k >= 3) {
          fence_release();
          const unsigned fl = k == 3 ? F_KV + rnd * 8 + grp : k < 6 ? F_CTX + rt * 2 + rnd : F_Y + ((unsigned)ch >> 7);
          if (lane <= (e == 5)) flag_add(FLAG(lane ? F_AD + grp : fl));
        }
        if (k >= 6) { cg = conv_next(cg, spare); ch += 2 * cstep + (k == 7 ? c5 : 0); }
      }
      if (lane == 0) mbar_arrive(sb + SM_BAR + B_DONE * 8);
    } else {
#pragma unroll 1
      for (int rnd = 0; rnd < (spare ? 0 : 2); rnd++) {
        const int hp = 16 * rnd + 2 * grp, head = hp + rank;
#pragma unroll 1
        for (int kk = rnd || redo ? 0 : 4; kk < 32; kk++) {
          const int g0 = 2 + 3 * (kk & 3);
          acquire(g0, kk < 4 ? 3 : 1, 7);
          if (elect()) {
            const uint32_t fb = sb + SM_BAR + (B_FULL + g0) * 8;
            mbar_expect_tx(fb, 3 * GR);
            if (kk < 16) {
              tma2d_p(sb + g0 * GR, &p.c, (kk & 7) * 64, (KV_ROW(idx, kk >> 3) + rank) * 128, fb, rnd);
              tma3d_mc_p(sb + (g0 + 1 + rank) * GR, rank ? &p.wuv : &p.wuk, 0, (kk & 7) * 64, (hp + KV_HEAD(idx, kk >> 3)) * 2, fb, kk >= 8);
            } else {
              tma2d_mc(sb + (g0 + rank) * GR, &p.x, (kk - 16) * 64, (rank ? 15 - idx : idx) * 128, fb);
              tma3d<true>(sb + (g0 + 2) * GR, &p.wq, 0, (kk - 16) * 64, head * 2, fb);
            }
          }
        }
        flag_wait(FLAG(F_KV + rnd * 8 + grp), 32);
        fence_async_all();
        acquire(2, 1, 3);
        int g0 = 4;
#pragma unroll 1
        for (int n = 0; n < 36; n += n == 0 || n == 33 ? 2 : 1) {
          const int it = (n >> 1) - (n & 1);
          const int blk = it & 15 ? (it <= idx ? it - 1 : 15 - it) : it ? 15 - idx : idx;
          acquire(g0, n < 6 ? 2 : 1, 3);
          if (elect()) {
            const uint32_t fb = sb + SM_BAR + (B_FULL + g0) * 8;
            if (n == 5) mbar_arrive(sb + SM_BAR + B_SLOT * 8);
            mbar_expect_tx(fb, 2 * GR);
            asm volatile("cp.async.bulk" TMA_MB ".L2::cache_hint [%0], [%1], %2, [%3], %4;" ::"r"(sb + g0 * GR), "l"(g_kv + (unsigned)((((n & 1) * 16 + (head & 15)) * 16 + blk) * 32768)),
                         "r"(2 * GR), "r"(fb), "l"(it >= 8 ? EV_FIRST : EV_NORMAL) : "memory");
          }
          g0 = n == 13 ? 12 : g0 == 12 ? 4 : g0 + 2;
        }
      }
      int c5 = 0;
      if (spare) { bar_sync(5, 64); pe = 0x3FC0; }
      else c5 = get_ticket();
      auto conv_fill = [&](int g, int ch) {
        acquire(g, 1, 1);
        if (elect()) {
          const uint32_t fb = sb + SM_BAR + (B_FULL + g) * 8;
          if (!spare) FTP(64 + 48 + g);
          mbar_expect_tx(fb, WBYTES + 4096);
          bulk_g2s<true>(sb + g * GR, g_w + (size_t)ch * WSTRIDE, WBYTES, fb);
          bulk_g2s<true>(sb + g * GR + WBYTES, p.ssk + (size_t)ch * SEQ, 4096, fb);
        }
      };
#pragma unroll 1
      for (int i = 0, g = 2; i < cn; i++) {
        if ((i & 15) == 0) { flag_wait(FLAG(F_U + (spare ? 32 - __clz(i >> 4) : 4)), NMAIN); fence_async_all(); }
        conv_fill(g + (i & 1), cch + i * cstep + (i == 4 ? c5 : 0));
        if (i & 1) g = conv_next(g, spare);
      }
      if (!spare) {
        const int rt = 2 * grp + rank, ct = idx;
        int g0 = P3G, top = 12;
        const uint8_t* src = g_cimg + (unsigned)((rt * 64 + 32) * GR);
#pragma unroll 1
        for (int kb = 0; kb < 64; kb++) {
          if (!(kb & 31)) { flag_wait(FLAG(F_CTX + rt * 2 + ((kb ^ 32) >> 5)), 32); fence_async_all(); if (kb) src -= 64 * GR; }
          acquire(g0, kb < 11 ? 2 : 1, 3);
          if (elect()) {
            const uint32_t fb = sb + SM_BAR + (B_FULL + g0) * 8;
            if (kb < 16) FTP(48 + kb);
            mbar_expect_tx(fb, 2 * GR);
            bulk_g2s<true>(sb + g0 * GR, src, GR, fb);
            tma2d_mc<true>(sb + (g0 + 1) * GR + rank * 8192, &p.wo, ct * 128 + rank * 64, (kb ^ 32) * 64, fb);
          }
          src += GR;
          g0 = g0 == (kb < XK ? 12 : kb < YK ? 10 : 8) ? (kb == 3 ? 2 : 0) : g0 + 2;
          if (kb == XK || (kb >= YK && top == P3Y && (kb == 63 || mbar_test(sb + SM_BAR + B_SLOT * 8, 1)))) {
            const bool j = kb != XK;
            if (j) { mbar_wait1(sb + SM_BAR + B_SLOT * 8, 1); fence_async_all(); }
            acquire(top, 1, 0);
            if (elect()) {
              const uint32_t fb = sb + SM_BAR + (B_FULL + top) * 8;
              mbar_expect_tx(fb, j ? 2 * GR + 512 : 2 * GR);
              if (j) bulk_g2s(sb + SM_GATE, g_gate + (unsigned)(rt * 128), 512, fb);
              tma3d(sb + top * GR, j ? &p.y3 : &p.x3, 0, (j ? ct : rt) * 128, (j ? rt : ct) * 2, fb);
            }
            top -= 2;
          }
        }
        unsigned n = 0;
        if (lane == 0) n = atomicInc(FLAG(F_EXIT), 0x7fffffffu);
        if (__any_sync(0xffffffffu, n == NMAIN - 1)) {
#pragma unroll
          for (int i = lane; i < 96; i += 32) *reinterpret_cast<uint2*>(FLAG(i)) = make_uint2(0, 0);
        }
      }
      if (lane == 0) mbar_arrive(sb + SM_BAR + B_DONE * 8);
    }
    __syncwarp();
    cluster_wait();
  } else {
    asm volatile("setmaxnreg.inc.sync.aligned.u32 232;");
    FTS(2);
    Cons c;
    c.sb = sb; c.pf = 0; c.wg = wgi - 1; c.tid = threadIdx.x & 127;
    const int lane = threadIdx.x & 31, t = lane & 3;
    const int row = c.wg * 64 + (warp & 3) * 16 + (lane >> 2);
    const uint32_t dkk = desc_k(sb), dk0 = dkk + c.wg * 512, dm0 = desc_mn<8192>(sb), dv0 = desc_mn<16384>(sb);
    const uint32_t dsw = DG + 512 - c.wg * 1024;
    if (c.wg == 1) bar_arrive(1, 256);
    c.pfree = 1;
    asm("mapa.shared::cluster.u32 %0, %1, %2;" : "=r"(c.relb) : "r"(sb + SM_BAR + (B_EMPTY + (c.tid >> 1)) * 8), "r"(c.tid & 1));
    c.zero = p.zero;
    c.rnd = 0;
    const uint32_t stg = sb + (c.wg * 64 + (warp & 3) * 16 + ((lane >> 3) & 1) * 8 + (lane & 7)) * 128 + (((lane >> 4) ^ (lane & 7)) << 4);

    uint32_t dd0;
    auto load_dd = [&]() { asm volatile("ld.global.nc.u16 %0, [%1];" : "=r"(dd0) : "l"(p.ssd + (unsigned)(cch + c.wg * cstep + (lane & c.zero)))); };
    int pass = c.zero;
#pragma unroll 1
    do {
    if (pass) {
      load_dd();
#pragma unroll 1
      for (int g = 2; g < NGR; g += 3) { mbar_wait(sb + SM_BAR + (B_FULL + g) * 8, 0); c.release(g, 3); }
      c.pf = 0x924;
    if (spare) {
      c.wait_full(1);
      int g = 2;
#pragma unroll 1
      for (int r = 0; r < 4; r++) {
        float d[4] = {0.f, 0.f, 0.f, 0.f}, e[4] = {0.f, 0.f, 0.f, 0.f};
#pragma unroll 1
        for (int kb = 0; kb < 16; kb += 2) {
          c.wait_full(g);
          wg_fence();
#pragma unroll 1
          for (int k = 0; k < 4; k++) {
            mma_ss_n8(d, dk0 + g * DG + k * 2, dkk + DG + kb * 8 + k * 2);
            mma_ss_n8(e, dk0 + (g + 1) * DG + k * 2, dkk + DG + kb * 8 + 8 + k * 2);
          }
          wg_commit();
          wg_wait<0>();
          c.release(g, 2);
          g = g == NGR - 2 ? 2 : g + 2;
        }
        reg_fence(d); reg_fence(e);
        d[0] += e[0]; d[2] += e[2];
        if (t == 0) {
          float* gp = g_gate + (unsigned)((lb - NMAIN) * 512 + r * 128 + row);
          gp[0] = rcp(1.f + ex2(-1.4426950408889634f * d[0])); gp[8] = rcp(1.f + ex2(-1.4426950408889634f * d[2]));
        }
      }
      fence_release();
      __syncwarp();
      if (lane == 0) flag_add(FLAG(F_GATE));
      TS(1);
    }
    } else cluster_wait();
    get_slot();
    } while (redo && !pass++);
    FTS(3);
    const float dmask = (float)(2 * t - (row & 63));
    int c5 = 0;
    uint32_t pv[32];
#pragma unroll 1
    for (int rnd = 0; rnd < (spare ? 0 : 2); rnd++) {
      float O[64];
      FTM(rnd * 8);
      FTG(0);
      FTH(56, c.rnd == rnd);
      c.wait_full(2);
      FTM(rnd * 8 + 1);
      FTH(57, c.rnd == rnd);
#pragma unroll 1
      for (int tile = c.zero; tile < 2; tile++) {
        float acc[128];
        const bool single = tile == 0;
        {
          FTG(tile * 32 + 1);
          const uint32_t a = dk0 + 2 * DG, b = dm0 + 3 * DG;
          c.turn_begin();
          FTG(tile * 32 + 2);
          FTH(58, c.rnd == rnd);
          wg_fence();
          mma_ss_n256_init<1>(acc, a, b);
#pragma unroll
          for (int k = 1; k < 4; k++) mma_ss_n256<1>(acc, a + k * 2, b + k * 128);
          wg_commit();
          if (single) c.turn_end();
          FTG(tile * 32 + 3);
        }
#pragma unroll 1
        for (int kb = 1; kb < 8; kb++) {
          const int g0 = 2 + 3 * (kb & 3);
          const uint32_t a = dk0 + g0 * DG, b = dm0 + (g0 + 1) * DG;
          const bool second = (kb == 1 && !single) || kb == 7;
          FTG(tile * 32 + kb * 4);
          if (!second) { wg_wait<0>(); c.release(2 + 3 * ((kb - 1) & 3), 3); }
          FTG(tile * 32 + kb * 4 + 1);
          c.wait_full(g0);
          if (!second) c.turn_begin();
          FTG(tile * 32 + kb * 4 + 2);
          wg_fence();
#pragma unroll
          for (int k = 0; k < 4; k++) mma_ss_n256<1>(acc, a + k * 2, b + k * 128);
          wg_commit();
          if (kb != 6) c.turn_end();
          if (second) { wg_wait<1>(); c.release(2 + 3 * ((kb - 1) & 3), 3); }
          FTG(tile * 32 + kb * 4 + 3);
          FTH(58 + kb, c.rnd == rnd || kb > 3);
          if (tile == 1 && kb == 3) { c.wait_stage_free(); stsm_frag<0, 4>(pv, stg); }
          if (tile == 1 && kb == 4) { stsm_frag<4, 8>(pv, stg); c.staged(0); }
        }
        c.rnd = rnd;
        c.wait_stage_free();
        const bool nxt = c.try_full(2);
        wg_wait<0>();
        reg_fence(acc);
        c.release(11, 3);
        store_scaled(acc, SM_C, SM_C, stg, sb);
        c.staged(0);
        pack_frag<64>(acc, pv);
        FTG(32 + tile * 32);
        if (!nxt) mbar_wait(sb + SM_BAR + (B_FULL + 2) * 8, (c.pf >> 2) & 1);
        c.pf ^= 4;
      }
      TS(1 + rnd * 3);
      FTM(rnd * 8 + 2);
      {
        float qa[64];
        float (&qb)[64] = O;
        {
          FTG(65);
          const uint32_t a = dk0 + 2 * DG, b = dm0 + 4 * DG;
          c.turn_begin();
          FTG(66);
          wg_fence();
          mma_ss_n128_init<1>(qa, a, b);
          mma_ss_n128_init<1>(qb, a + dsw, b);
#pragma unroll
          for (int k = 1; k < 4; k++) {
            mma_ss_n128<1>(qa, a + k * 2, b + k * 128);
            mma_ss_n128<1>(qb, a + dsw + k * 2, b + k * 128);
          }
          wg_commit();
          FTG(67);
        }
#pragma unroll 1
        for (int kb = 1; kb < 16; kb++) {
          const int g0 = 2 + 3 * (kb & 3);
          const uint32_t a = dk0 + g0 * DG, b = dm0 + (g0 + 2) * DG;
          const bool second = kb == 1 || kb == 15;
          FTG(64 + kb * 4);
          if (!second) { wg_wait<0>(); c.release(2 + 3 * ((kb - 1) & 3), 3); }
          FTG(65 + kb * 4);
          c.wait_full(g0);
          if (!second) c.turn_begin();
          FTG(66 + kb * 4);
          FTH(kb - 14, kb < 14);
          wg_fence();
#pragma unroll
          for (int k = 0; k < 4; k++) {
            mma_ss_n128<1>(qa, a + k * 2, b + k * 128);
            mma_ss_n128<1>(qb, a + dsw + k * 2, b + k * 128);
          }
          wg_commit();
          if (kb != 14) c.turn_end();
          if (second) { wg_wait<1>(); c.release(2 + 3 * ((kb - 1) & 3), 3); }
          FTG(67 + kb * 4);
          FTH(2, kb < 15);
          if (kb == QFLUSH) { c.wait_stage_free(); stsm_frag<0, 4>(pv, stg); }
          if (kb == QFLUSH + 1) { stsm_frag<4, 8>(pv, stg); c.staged(0); }
        }
        c.wait_stage_free();
        mbar_wait(sb + SM_BAR + (B_EMPTY + 2) * 8, rnd ^ !redo);
        FTM(rnd * 8 + 3);
        FTH(3, 0);
        const bool k0 = c.try_full(4);
        wg_wait<0>();
        reg_fence(qa); reg_fence(qb);
        FTH(4, 0);
        c.release(11, 3);
        pack_frag<0>(qa, pv);
        stsm_frag(pv, stg + 2 * GR);
        if (c.wg == 0) {
          pack_frag<0>(qb, pv);
          stsm_frag(pv, stg);
        }
        FTH(6, 0);
        fence_async_smem();
        FTH(7, 0);
        if (!k0) c.wait_full(4); else c.pf ^= 16;
      }
      TS(2 + rnd * 3);
      FTM(rnd * 8 + 4);
      FTH(5, 0);
      {
        const int nA = idx + 1;
        uint32_t (&P)[32] = pv;
        SoftState z;
        z.m0 = z.m1 = z.l0 = z.l1 = 0.f; z.shifted = c.zero;
#pragma unroll 1
        for (int seg = c.zero;; seg++) {
        if (c.wg == seg) attn_half(c, O, P, z, dk0, dkk, dv0, dmask, seg);
        if (seg) break;
        FTM(rnd * 8 + 5);
        int gk = c.wg ? 4 : 6, gv = c.wg ? 4 : 8;
        uint32_t dq = dk0 + (1 - c.wg < nA ? 2 * DG : 0), dk = dkk + gk * DG;
#pragma unroll 1
        for (int it = 1 - c.wg; it < 17 - c.wg; it++) {
          float S[64];
          FTA(it * 7 + 0); FTH((it < 3 ? 8 + it * 8 : it * 8 - 88) + 0, it >= 3 && it < 15);
          c.turn_begin();
          FTA(it * 7 + 2); FTH((it < 3 ? 8 + it * 8 : it * 8 - 88) + 1, it >= 3 && it < 15);
          wg_fence();
          issue_qk(S, dq, dk);
          wg_commit();
          const uint32_t dv = dv0 + gv * DG;
          uint32_t relk = c.relb + gk * 8, relv = c.relb + gv * 8;
          gk = it == 6 ? 12 : gv == 12 ? 4 : gv + 2;
          gv = it == 16 ? gk : gk == 12 ? 4 : gk + 2;
          uint32_t fk = sb + SM_BAR + (B_FULL + gk) * 8, fv = sb + SM_BAR + (B_FULL + gv) * 8, park = (c.pf >> gk) & 1, parv = (c.pf >> gv) & 1;
          c.pf ^= (1u << gk) | (1u << gv);
          dq = dk0 + (it + 1 < nA ? 2 * DG : 0); dk = dkk + gk * DG;
          float lo0 = z.l0, lo1 = z.l1;
          const bool first = it == nA || it == 0;
          if (it == nA) {
            lo0 = rcp(quad_sum(lo0)); lo1 = rcp(quad_sum(lo1));
            z.m0 = z.m1 = z.l0 = z.l1 = 0.f; z.shifted = 0;
          }
          float s0, s1, d0 = z.m0, d1 = z.m1;
          int pre = z.shifted || (it & 15) == 0;
          float lim = first ? -1.f : SM_LIMIT;
          asm volatile("" : "+r"(relk), "+r"(relv), "+r"(fk), "+r"(fv), "+r"(park), "+r"(parv), "+r"(dq), "+r"(dk), "+r"(pre), "+f"(lim), "+f"(d0), "+f"(d1), "+f"(z.l0), "+f"(z.l1));
          if (it + c.wg > 1) {
            issue_pv<0>(O, P, dv, it != nA + 1 && it != 1, true);
            issue_pv<1>(O, P, dv, 1, true);
            c.turn_end();
          } else if (it) {
            issue_pv<0>(O, P, dv, 0, true);
            wg_commit(); wg_commit();
            c.turn_end();
          } else stage_q2(c, O, P, stg);
          FTA(it * 7 + 3); FTH((it < 3 ? 8 + it * 8 : it * 8 - 88) + 2, it >= 3 && it < 15);
          wg_wait<4>();
          reg_fence(S);
          FTA(it * 7 + 4); FTH((it < 3 ? 8 + it * 8 : it * 8 - 88) + 3, it >= 3 && it < 15);
          if (c.tid < 4) asm volatile("mbarrier.arrive.shared::cluster.b64 _, [%0];" ::"r"(relk) : "memory");
#pragma unroll 1
          for (int pass = 0;; pass++) {
            if (pre) {
              if ((it & 15) == 0) mask_diag(S, dmask);
              if (z.shifted) shift_scores(S, d0, d1);
            }
            float tr[ROT];
            exp_quarter<0, 3>(S, P, tr, s0, s1, sb);
            exp_quarter<1, 2>(S, P, tr, s0, s1, sb);
            exp_quarter<2, 1>(S, P, tr, s0, s1, sb);
            exp_quarter<3, 0>(S, P, tr, s0, s1, sb);
            reg_fence(O);
            if (c.tid < (pass || !it ? 0 : 4)) asm volatile("mbarrier.arrive.shared::cluster.b64 _, [%0];" ::"r"(relv) : "memory");
            const bool ok = mbar_test(fk, park) & mbar_test(fv, parv);
            if (!ok) lim = -1.f;
            FTA(it * 7 + 5); FTH((it < 3 ? 8 + it * 8 : it * 8 - 88) + 4, it >= 3 && it < 15);
            if (!__any_sync(0xffffffffu, !(s0 <= lim && s1 <= lim))) break;
            if (pass) break;
            if (it == nA) {
              store_scaled(O, lo0, lo1, stg + 2 * GR, sb);
              c.staged(1);
            }
            if (!ok) { mbar_wait(fk, park); mbar_wait(fv, parv); }
            if (!soft_unsafe(s0, s1, first)) break;
            soft_fix(S, O, z, first, d0, d1);
            pre = 1;
          }
          z.l0 += s0; z.l1 += s1;
          FTA(it * 7 + 6); FTH((it < 3 ? 8 + it * 8 : it * 8 - 88) + 5, it >= 3 && it < 15);
        }
        FTM(rnd * 8 + 6);
        }
        FTH(48, 0);
        load_dd();
        c.turn_begin();
        FTH(49, 0);
        wg_fence();
        issue_pv<0>(O, P, dv0 + 12 * DG, 1, true);
        issue_pv<1>(O, P, dv0 + 12 * DG, 1, !c.wg);
        c.turn_end();
        z.l0 = rcp(quad_sum(z.l0)); z.l1 = rcp(quad_sum(z.l1));
        if (rnd) c5 = get_ticket();
        wg_wait<0>();
        reg_fence(O); reg_fence(P);
        FTH(50, 0);
        c.release(12, 2);
        store_scaled(O, z.l0, z.l1, stg, sb);
        c.staged(0);
        FTM(rnd * 8 + 7);
        FTH(51, 0);
      }
      TS(3 + rnd * 3);
    }
    conv_tasks(c, p, (cn + 1 - c.wg) >> 1, spare, cch + c.wg * cstep, 2 * cstep, c5, dd0, dkk, warp & 3, lane);
    if (c.wg == 1) c.pf ^= 0x14;
    if (c.wg == (cn & 1)) c.turn_begin();
    TS(7);
    if (!spare) {
      const int rt = 2 * grp + rank, ct = idx;
      float acc[64];
      int g0 = P3G + 2, pg = P3G;
      {
        FTO(0);
        c.wait_full(P3G);
        FTO(1);
        const uint32_t a = dk0 + P3G * DG, b = dm0 + (P3G + 1) * DG;
        wg_fence();
        mma_ss_n128_init<1>(acc, a, b);
#pragma unroll
        for (int k = 1; k < 4; k++) mma_ss_n128<1>(acc, a + k * 2, b + k * 128);
        wg_commit();
      }
#pragma unroll 1
      for (int kb = 1; kb < 64; kb++) {
        FTO(kb * 2);
        c.wait_full(g0);
        if (kb == STR && !c.wg) c.turn_begin();
        FTO(kb * 2 + 1);
        const uint32_t a = dk0 + g0 * DG, b = dm0 + (g0 + 1) * DG;
        wg_fence();
#pragma unroll
        for (int k = 0; k < 4; k++) mma_ss_n128<1>(acc, a + k * 2, b + k * 128);
        wg_commit();
        if (kb < STR) { wg_wait<1>(); c.release(pg, kb <= 59 ? 2 : 0); }
        if (kb == FDUMP_KB) FTDUMP();
        pg = g0;
        g0 = g0 == (kb < XK ? 12 : kb < YK ? 10 : 8) ? (kb == 3 ? 2 : 0) : g0 + 2;
      }
      if (c.wg) c.turn_end();
      cluster_arrive();
      c.wait_full(P3X);
      c.wait_full(P3Y);
      const float g0f = __uint_as_float(lds32(sb + SM_GATE + row * 4)), g1f = __uint_as_float(lds32(sb + SM_GATE + row * 4 + 32));
      const uint32_t gp0 = pack_bf16(g0f, g0f), gp1 = pack_bf16(g1f, g1f);
      const float h0 = 1.f - g0f, h1 = 1.f - g1f;
      const int w = warp & 3;
      const uint32_t xa = stg + P3X * GR;
      const uint32_t ya = sb + P3Y * GR + c.wg * 16384 + ((lane >> 4) * 8 + (lane & 7)) * 128 + (((2 * w + ((lane >> 3) & 1)) ^ (lane & 7)) << 4);
      uint32_t xy[32];
      auto prep = [&](int j0, int j1) {
#pragma unroll
        for (int jj = j0; jj < j1; jj++) {
          uint32_t x[4], y[4];
          asm volatile("ldmatrix.sync.aligned.m8n8.x4.shared.b16 {%0,%1,%2,%3}, [%4];" : "=r"(x[0]), "=r"(x[1]), "=r"(x[2]), "=r"(x[3]) : "r"((xa ^ ((jj & 3) << 5)) + (jj >> 2) * 16384) : "memory");
          asm volatile("ldmatrix.sync.aligned.m8n8.x4.trans.shared.b16 {%0,%1,%2,%3}, [%4];" : "=r"(y[0]), "=r"(y[1]), "=r"(y[2]), "=r"(y[3]) : "r"(ya + jj * 2048) : "memory");
#pragma unroll
          for (int i = 0; i < 4; i++) xy[4 * jj + i] = hmul2(x[i], y[i]);
        }
      };
      prep(0, 4);
      wg_wait<0>();
      reg_fence(acc);
      TS(8);
#pragma unroll
      for (int hf = 0; hf < 2; hf++) {
#pragma unroll
        for (int i = 16 * hf; i < 16 * hf + 16; i++) {
          const float h = (i & 1) ? h1 : h0;
          xy[i] = hfma2((i & 1) ? gp1 : gp0, xy[i], pack_bf16(acc[2 * i] * h, acc[2 * i + 1] * h));
        }
        if (hf) stsm_frag<4, 8>(xy, xa); else stsm_frag<0, 4>(xy, xa);
        fence_async_smem();
        __syncwarp();
        const int r0 = c.wg * 64 + w * 16;
        if (lane == 0) tma2d_store(&p.out, sb + (P3X + hf) * GR + r0 * 128, ct * 128 + hf * 64, rt * 128 + r0);
        if (!hf) prep(4, 8);
      }
      if (lane == 0) asm volatile("cp.async.bulk.commit_group;\ncp.async.bulk.wait_group.read 0;" ::: "memory");
    } else { FTDUMP(); cluster_arrive(); }
    if (lane == 0) mbar_arrive(sb + SM_BAR + B_DONE * 8);
    __syncwarp();
    TS(9);
    cluster_wait();
  }
}

typedef CUresult (*EncFn)(CUtensorMap*, CUtensorMapDataType, cuuint32_t, void*, const cuuint64_t*, const cuuint64_t*, const cuuint32_t*,
                          const cuuint32_t*, CUtensorMapInterleave, CUtensorMapSwizzle, CUtensorMapL2promotion, CUtensorMapFloatOOBfill);

void enc2d(EncFn enc, CUtensorMap* tm, const void* base, uint64_t cols, uint64_t rows, uint32_t bc, uint32_t br) {
  cuuint64_t dims[2] = {cols, rows}; cuuint64_t strides[1] = {cols * 2}; cuuint32_t box[2] = {bc, br}; cuuint32_t es[2] = {1, 1};
  enc(tm, CU_TENSOR_MAP_DATA_TYPE_BFLOAT16, 2, const_cast<void*>(base), dims, strides, box, es, CU_TENSOR_MAP_INTERLEAVE_NONE,
      CU_TENSOR_MAP_SWIZZLE_128B, CU_TENSOR_MAP_L2_PROMOTION_L2_256B, CU_TENSOR_MAP_FLOAT_OOB_FILL_NONE);
}
void enc3d(EncFn enc, CUtensorMap* tm, const void* base, uint64_t K, uint64_t N, uint32_t bk = 64, uint64_t pitch = 0) {
  cuuint64_t dims[3] = {64, K, N / 64}; cuuint64_t strides[2] = {pitch ? pitch : N * 2, 128}; cuuint32_t box[3] = {64, bk, 2}; cuuint32_t es[3] = {1, 1, 1};
  enc(tm, CU_TENSOR_MAP_DATA_TYPE_BFLOAT16, 3, const_cast<void*>(base), dims, strides, box, es, CU_TENSOR_MAP_INTERLEAVE_NONE,
      CU_TENSOR_MAP_SWIZZLE_128B, CU_TENSOR_MAP_L2_PROMOTION_L2_256B, CU_TENSOR_MAP_FLOAT_OOB_FILL_NONE);
}

}

extern "C" void kernel_launch(void* const* d_in, const int* in_sizes, int n_in, void* d_out, int out_size) {
  (void)in_sizes; (void)n_in; (void)out_size;
  typedef const __nv_bfloat16* BP;
  BP xq = (BP)d_in[0], ak = (BP)d_in[1], av = (BP)d_in[2], shk = (BP)d_in[3], ssk = (BP)d_in[4], ssd = (BP)d_in[5];
  BP ckv = (BP)d_in[7], wq = (BP)d_in[8], wuk = (BP)d_in[9], wuv = (BP)d_in[10], wo = (BP)d_in[11], gw = (BP)d_in[12];

  static EncFn enc = nullptr;
  if (!enc) {
    cudaDriverEntryPointQueryResult qr;
    cudaGetDriverEntryPoint("cuTensorMapEncodeTiled", (void**)&enc, cudaEnableDefault, &qr);
    cudaFuncSetAttribute(mega_kernel, cudaFuncAttributeMaxDynamicSharedMemorySize, SMEM_BYTES);
  }
  Params p;
  enc2d(enc, &p.x, xq, DM, SEQ, 64, 128);
  enc2d(enc, &p.c, ckv, DC, SEQ, 64, 128);
  enc3d(enc, &p.wq, wq, DM, NH * HD);
  enc3d(enc, &p.wuk, wuk, DC, NH * HD);
  enc3d(enc, &p.wuv, wuv, DC, NH * HD);
  enc2d(enc, &p.wo, wo, DM, NH * HD, 64, 64);
  enc3d(enc, &p.x3, xq, SEQ, DM, 128);
  enc2d(enc, &p.out, d_out, DM, SEQ, 64, 16);
  {
    void* wp = nullptr;
    cudaGetSymbolAddress(&wp, g_w);
    enc3d(enc, &p.y3, (uint8_t*)wp + WZ, DM, SEQ, 128, WSTRIDE);
    cuuint64_t dims[3] = {WSTRIDE / 2, DM / 2, 2}; cuuint64_t strides[2] = {2 * WSTRIDE, WSTRIDE}; cuuint32_t box[3] = {16, 32, 2}; cuuint32_t es[3] = {1, 1, 1};
    enc(&p.w, CU_TENSOR_MAP_DATA_TYPE_BFLOAT16, 3, wp, dims, strides, box, es, CU_TENSOR_MAP_INTERLEAVE_NONE,
        CU_TENSOR_MAP_SWIZZLE_32B, CU_TENSOR_MAP_L2_PROMOTION_NONE, CU_TENSOR_MAP_FLOAT_OOB_FILL_NONE);
  }
  p.zero = 0;
  cudaGetSymbolAddress((void**)&p.flags, g_flags);
  for (int i = 0; i < 128; i++) {
    const int tp = i % NSLOT;
    p.pref[i] = tp < 32 ? (tp & 7) * 8 + (tp >> 3) : tp < 60 ? (1 + (tp - 32) % 7) * 8 + 4 + (tp - 32) / 7 : tp < 62 ? tp + 4 : tp - 58;
  }
  p.gate_w = gw; p.ak = ak; p.av = av; p.shk = shk; p.ssk = ssk; p.ssd = ssd;

  mega_kernel<<<132, NTHREADS, SMEM_BYTES>>>(p);
}
```

```cpp
#include <cuda_runtime.h>
#include <cuda.h>
#include <cuda_bf16.h>
#include <stdint.h>

namespace {

constexpr int SEQ = 2048, DM = 1024, DC = 512, NH = 32, HD = 128;
constexpr int GR = 16384;
constexpr int NGR = 14;
constexpr int SM_BAR = NGR * GR;
constexpr int SM_GATE = SM_BAR + 512;
constexpr int SM_UST = SM_GATE + 512;
constexpr int SMEM_BYTES = SM_UST + 2048;
constexpr int NTHREADS = 384;
#define SM_LIMIT 1.0995116e12f
#define SM_LOW 9.094947e-13f
#define CNS 106
constexpr int CN_SPARE = CNS, NTICK = 256 - 2 * CN_SPARE;
constexpr int XK = 57, YK = 62;
constexpr int STR = 61;
constexpr int P3G = 6, P3X = 12, P3Y = 10;
constexpr int NMAIN = 128;

constexpr int B_FULL = 0, B_FREE = 14, B_SLOT = 16, B_DONE = 17, B_EMPTY = 18, B_EV = 32, B_TICK = 36;
constexpr int V_SLOT = 37, V_TICK = 38;

__device__ __align__(1024) uint8_t g_kv[2 * 16 * 16 * 32768];
__device__ __align__(1024) uint8_t g_cimg[16 * NH * 32768];
__device__ __align__(1024) float g_gate[SEQ];
constexpr int WZ = 256, WPL = WZ + 4096, WBYTES = 2 * WPL + 32, WSTRIDE = 2 * WPL + 128;
__device__ __align__(1024) uint8_t g_w[DM * WSTRIDE];
__device__ __align__(32) unsigned g_flags[96 * 8];
constexpr int F_KV = 0, F_CTX = 16, F_U = 48, F_AD = 56, F_Y = 64, F_GATE = 72, F_EXIT = 73, F_TICK = 74;
constexpr int NSLOT = 66;
#define FLAG(i) (&g_flags[(i) * 8])
#define CLAIMP(i) (p.flags + (i) * 8 + 1)

#define TS(slot)
#define TSW(slot)
#define FTX(i, off)
#define FTDUMP()

#define QFLUSH 3
#define PSL 200
#define US0 500
#define EROT 6
#define RST 2
#define UP0 4
#define UP1 11
#define X_DELAY 1100
#define X_D2 500
#define ROT 8
#define KVARR 1
#define KV_ROW(idx, t) (KVARR ? 8 * (t) + 2 * ((idx) & 3) : 2 * (idx))
#define KV_HEAD(idx, t) (KVARR ? (idx) >> 2 : (t))
#define FINE_MODE 0
#define FDUMP_KB 40
#define FINE_RND 1
#define FTA(i) do { if (FINE_MODE == 0) FTX(i, rnd ^ FINE_RND); } while (0)
#define FTB(i) do { if (FINE_MODE == 8) FTX(c.rnd * 32 + (i), 0); } while (0)
#define FTG(i) do { if (FINE_MODE == 1) FTX(i, rnd ^ FINE_RND); } while (0)
#define FTM(i) do { if (FINE_MODE == 4) FTX(i, 0); } while (0)
#define FTC(k) do { if (FINE_MODE == 5) FTX((i & 7) * 8 + (k), (i >> 3) ^ FINE_RND); } while (0)
#define FTH(i, off) do { if (FINE_MODE == 6) FTX(i, (c.rnd ^ FINE_RND) | (off)); } while (0)
#define FTS(i)
#define FTSD(i)
#define FTSW(i)
#define FTP(i)
#define FTO(i) do { if (FINE_MODE == 2) FTX(i, 0); } while (0)

__device__ __forceinline__ uint32_t smem_u32(const void* p) { return (uint32_t)__cvta_generic_to_shared(p); }
__device__ __forceinline__ void mbar_init(uint32_t bar, int cnt) { asm volatile("mbarrier.init.shared::cta.b64 [%0], %1;" ::"r"(bar), "r"(cnt) : "memory"); }
__device__ __forceinline__ void mbar_expect_tx(uint32_t bar, uint32_t bytes) { asm volatile("mbarrier.arrive.expect_tx.shared::cta.b64 _, [%0], %1;" ::"r"(bar), "r"(bytes) : "memory"); }
__device__ __forceinline__ void mbar_arrive(uint32_t bar) { asm volatile("mbarrier.arrive.shared::cta.b64 _, [%0];" ::"r"(bar) : "memory"); }
__device__ __forceinline__ void mbar_arrive_cluster(uint32_t bar, uint32_t cta) {
  asm volatile("{\n.reg .b32 r;\nmapa.shared::cluster.u32 r, %0, %1;\nmbarrier.arrive.shared::cluster.b64 _, [r];\n}\n" ::"r"(bar), "r"(cta) : "memory");
}
__device__ __forceinline__ void send_both(uint32_t bar, uint32_t off, uint32_t v) {
#pragma unroll
  for (int r = 0; r < 2; r++)
    asm volatile("{\n.reg .b32 a, b;\nmapa.shared::cluster.u32 a, %0, %1;\nadd.u32 b, a, %3;\nst.async.shared::cluster.mbarrier::complete_tx::bytes.u32 [b], %2, [a];\n}\n"
                 ::"r"(bar), "r"(r), "r"(v), "r"(off) : "memory");
}
__device__ __forceinline__ bool mbar_try(uint32_t bar, uint32_t parity) {
  uint32_t ok;
  asm volatile("{\n.reg .pred p;\nmbarrier.try_wait.parity.shared::cta.b64 p, [%1], %2, 20000;\nselp.u32 %0, 1, 0, p;\n}\n" : "=r"(ok) : "r"(bar), "r"(parity) : "memory");
  return ok;
}
__device__ __forceinline__ bool mbar_test(uint32_t bar, uint32_t parity) {
  uint32_t ok;
  asm volatile("{\n.reg .pred p;\nmbarrier.test_wait.parity.shared::cta.b64 p, [%1], %2;\nselp.u32 %0, 1, 0, p;\n}\n" : "=r"(ok) : "r"(bar), "r"(parity) : "memory");
  return ok;
}
__device__ __forceinline__ void mbar_wait(uint32_t bar, uint32_t parity) {
  asm volatile("{\n.reg .pred p;\nWAIT_LOOP:\nbar.warp.sync -1;\nmbarrier.try_wait.parity.shared::cta.b64 p, [%0], %1;\n@!p bra WAIT_LOOP;\n}\n" ::"r"(bar), "r"(parity) : "memory");
}
__device__ __forceinline__ void mbar_wait1(uint32_t bar, uint32_t parity) {
  asm volatile("{\n.reg .pred p;\nWAIT_LOOP:\nbar.warp.sync -1;\nmbarrier.try_wait.parity.shared::cta.b64 p, [%0], %1, 4000;\n@!p bra WAIT_LOOP;\n}\n" ::"r"(bar), "r"(parity) : "memory");
}
constexpr uint64_t EV_NORMAL = 0x1000000000000000ull, EV_FIRST = 0x12F0000000000000ull;
__device__ __forceinline__ uint32_t ldg_stream(const uint32_t* p) {
  uint32_t r; asm volatile("ld.global.nc.L1::no_allocate.L2::cache_hint.b32 %0, [%1], %2;" : "=r"(r) : "l"(p), "l"(EV_FIRST)); return r;
}
#define TMA_LD "cp.async.bulk.tensor."
#define TMA_MB ".shared::cluster.global.mbarrier::complete_tx::bytes"
__device__ __forceinline__ void tma2d(uint32_t dst, const CUtensorMap* tm, int c0, int c1, uint32_t bar) {
  asm volatile(TMA_LD "2d" TMA_MB " [%0], [%1, {%3, %4}], [%2];" ::"r"(dst), "l"(tm), "r"(bar), "r"(c0), "r"(c1) : "memory");
}
template <bool ONCE = false> __device__ __forceinline__ void tma2d_mc(uint32_t dst, const CUtensorMap* tm, int c0, int c1, uint32_t bar) {
  if (ONCE) asm volatile(TMA_LD "2d" TMA_MB ".multicast::cluster.L2::cache_hint [%0], [%1, {%3, %4}], [%2], %5, %6;"
                         ::"r"(dst), "l"(tm), "r"(bar), "r"(c0), "r"(c1), "h"((uint16_t)3), "l"(EV_FIRST) : "memory");
  else asm volatile(TMA_LD "2d" TMA_MB ".multicast::cluster [%0], [%1, {%3, %4}], [%2], %5;"
                    ::"r"(dst), "l"(tm), "r"(bar), "r"(c0), "r"(c1), "h"((uint16_t)3) : "memory");
}
__device__ __forceinline__ void tma2d_p(uint32_t dst, const CUtensorMap* tm, int c0, int c1, uint32_t bar, bool once) {
  asm volatile(TMA_LD "2d" TMA_MB ".L2::cache_hint [%0], [%1, {%3, %4}], [%2], %5;" ::"r"(dst), "l"(tm), "r"(bar), "r"(c0), "r"(c1), "l"(once ? EV_FIRST : EV_NORMAL) : "memory");
}
__device__ __forceinline__ void tma3d_mc_p(uint32_t dst, const CUtensorMap* tm, int c0, int c1, int c2, uint32_t bar, bool once) {
  asm volatile(TMA_LD "3d" TMA_MB ".multicast::cluster.L2::cache_hint [%0], [%1, {%3, %4, %5}], [%2], %6, %7;"
               ::"r"(dst), "l"(tm), "r"(bar), "r"(c0), "r"(c1), "r"(c2), "h"((uint16_t)3), "l"(once ? EV_FIRST : EV_NORMAL) : "memory");
}
template <bool ONCE = false> __device__ __forceinline__ void tma3d(uint32_t dst, const CUtensorMap* tm, int c0, int c1, int c2, uint32_t bar) {
  if (ONCE) asm volatile(TMA_LD "3d" TMA_MB ".L2::cache_hint [%0], [%1, {%3, %4, %5}], [%2], %6;" ::"r"(dst), "l"(tm), "r"(bar), "r"(c0), "r"(c1), "r"(c2), "l"(EV_FIRST) : "memory");
  else
  asm volatile(TMA_LD "3d" TMA_MB " [%0], [%1, {%3, %4, %5}], [%2];" ::"r"(dst), "l"(tm), "r"(bar), "r"(c0), "r"(c1), "r"(c2) : "memory");
}
__device__ __forceinline__ void tma3d_mc(uint32_t dst, const CUtensorMap* tm, int c0, int c1, int c2, uint32_t bar) {
  asm volatile(TMA_LD "3d" TMA_MB ".multicast::cluster [%0], [%1, {%3, %4, %5}], [%2], %6;"
               ::"r"(dst), "l"(tm), "r"(bar), "r"(c0), "r"(c1), "r"(c2), "h"((uint16_t)3) : "memory");
}
template <bool ONCE = false> __device__ __forceinline__ void bulk_g2s(uint32_t dst, const void* src, uint32_t bytes, uint32_t bar) {
  if (ONCE) asm volatile("cp.async.bulk" TMA_MB ".L2::cache_hint [%0], [%1], %2, [%3], %4;" ::"r"(dst), "l"(src), "r"(bytes), "r"(bar), "l"(EV_FIRST) : "memory");
  else asm volatile("cp.async.bulk" TMA_MB " [%0], [%1], %2, [%3];" ::"r"(dst), "l"(src), "r"(bytes), "r"(bar) : "memory");
}
__device__ __forceinline__ void tma2d_store(const CUtensorMap* tm, uint32_t src, int c0, int c1) {
  asm volatile("cp.async.bulk.tensor.2d.global.shared::cta.bulk_group [%0, {%2, %3}], [%1];" ::"l"(tm), "r"(src), "r"(c0), "r"(c1) : "memory");
}
__device__ __forceinline__ void prefetch_tm(const CUtensorMap* tm) { asm volatile("prefetch.tensormap [%0];" ::"l"(tm) : "memory"); }
__device__ __forceinline__ void wg_fence() { asm volatile("wgmma.fence.sync.aligned;" ::: "memory"); }
__device__ __forceinline__ void wg_commit() { asm volatile("wgmma.commit_group.sync.aligned;" ::: "memory"); }
template <int N> __device__ __forceinline__ void wg_wait() { asm volatile("wgmma.wait_group.sync.aligned %0;" ::"n"(N) : "memory"); }
__device__ __forceinline__ void bar_sync(int id, int n) { asm volatile("bar.sync %0, %1;" ::"r"(id), "r"(n) : "memory"); }
__device__ __forceinline__ void bar_arrive(int id, int n) { asm volatile("bar.arrive %0, %1;" ::"r"(id), "r"(n) : "memory"); }
__device__ __forceinline__ void fence_async_smem() { asm volatile("fence.proxy.async.shared::cta;" ::: "memory"); }
__device__ __forceinline__ void fence_async_all() { asm volatile("fence.proxy.async.global;" ::: "memory"); }
__device__ __forceinline__ uint32_t pack_bf16(float lo, float hi) { uint32_t r; asm("cvt.rn.bf16x2.f32 %0, %1, %2;" : "=r"(r) : "f"(hi), "f"(lo)); return r; }
__device__ __forceinline__ float ex2(float x) { float r; asm("ex2.approx.ftz.f32 %0, %1;" : "=f"(r) : "f"(x)); return r; }
__device__ __forceinline__ float rcp(float x) { float r; asm("rcp.approx.ftz.f32 %0, %1;" : "=f"(r) : "f"(x)); return r; }
__device__ __forceinline__ void flag_wait(const unsigned* f, unsigned target) {
  unsigned v;
  do { asm volatile("ld.acquire.gpu.global.u32 %0, [%1];" : "=r"(v) : "l"(f) : "memory"); } while (__any_sync(0xffffffffu, v < target));
}
__device__ __forceinline__ bool elect() {
  uint32_t r;
  asm volatile("{\n.reg .pred p;\nelect.sync _|p, -1;\nselp.u32 %0, 1, 0, p;\n}\n" : "=r"(r));
  return r;
}
__device__ __forceinline__ void fence_release() { asm volatile("fence.release.gpu;" ::: "memory"); }
__device__ __forceinline__ void flag_add(unsigned* f) { asm volatile("red.relaxed.gpu.global.inc.u32 [%0], 0x7fffffff;" ::"l"(f) : "memory"); }
__device__ __forceinline__ void cluster_arrive() { asm volatile("barrier.cluster.arrive.relaxed.aligned;" ::: "memory"); }
__device__ __forceinline__ void cluster_wait() { asm volatile("barrier.cluster.wait.aligned;" ::: "memory"); }
__device__ __forceinline__ uint32_t hmul2(uint32_t a, uint32_t b) { uint32_t r; asm("mul.rn.bf16x2 %0, %1, %2;" : "=r"(r) : "r"(a), "r"(b)); return r; }
__device__ __forceinline__ uint32_t hadd2(uint32_t a, uint32_t b) { uint32_t r; asm("add.rn.bf16x2 %0, %1, %2;" : "=r"(r) : "r"(a), "r"(b)); return r; }
__device__ __forceinline__ uint32_t hfma2(uint32_t a, uint32_t b, uint32_t c) { uint32_t r; asm("fma.rn.bf16x2 %0, %1, %2, %3;" : "=r"(r) : "r"(a), "r"(b), "r"(c)); return r; }
__device__ __forceinline__ uint32_t lds32(uint32_t a) { uint32_t r; asm volatile("ld.shared.b32 %0, [%1];" : "=r"(r) : "r"(a) : "memory"); return r; }
__device__ __forceinline__ uint4 lds128(uint32_t a) { uint4 r; asm volatile("ld.shared.v4.b32 {%0,%1,%2,%3}, [%4];" : "=r"(r.x), "=r"(r.y), "=r"(r.z), "=r"(r.w) : "r"(a) : "memory"); return r; }
__device__ __forceinline__ uint32_t desc_k(uint32_t addr) { return ((addr & 0x3FFFF) >> 4) | (1u << 16); }
template <int LBO> __device__ __forceinline__ uint32_t desc_mn(uint32_t addr) { return ((addr & 0x3FFFF) >> 4) | ((uint32_t)(LBO >> 4) << 16); }
#define DHI "0x40000040"

#define R8(d, o) "+f"(d[o]), "+f"(d[o + 1]), "+f"(d[o + 2]), "+f"(d[o + 3]), "+f"(d[o + 4]), "+f"(d[o + 5]), "+f"(d[o + 6]), "+f"(d[o + 7])
#define R32(d, o) R8(d, o), R8(d, o + 8), R8(d, o + 16), R8(d, o + 24)
#define R64(d, o) R32(d, o), R32(d, o + 32)
#define L64 "%0,%1,%2,%3,%4,%5,%6,%7,%8,%9,%10,%11,%12,%13,%14,%15,%16,%17,%18,%19,%20,%21,%22,%23,%24,%25,%26,%27,%28,%29,%30,%31," \
            "%32,%33,%34,%35,%36,%37,%38,%39,%40,%41,%42,%43,%44,%45,%46,%47,%48,%49,%50,%51,%52,%53,%54,%55,%56,%57,%58,%59,%60,%61,%62,%63"
#define L128 L64 ",%64,%65,%66,%67,%68,%69,%70,%71,%72,%73,%74,%75,%76,%77,%78,%79,%80,%81,%82,%83,%84,%85,%86,%87,%88,%89,%90,%91,%92,%93,%94,%95," \
            "%96,%97,%98,%99,%100,%101,%102,%103,%104,%105,%106,%107,%108,%109,%110,%111,%112,%113,%114,%115,%116,%117,%118,%119,%120,%121,%122,%123,%124,%125,%126,%127"

template <int TB> __device__ __forceinline__ void mma_ss_n128(float (&d)[64], uint32_t da, uint32_t db) {
  asm volatile("{\n.reg .b64 da, db;\nmov.b64 da, {%64, " DHI "};\nmov.b64 db, {%65, " DHI "};\n"
               "wgmma.mma_async.sync.aligned.m64n128k16.f32.bf16.bf16 {" L64 "}, da, db, 1, 1, 1, 0, %66;\n}\n"
               : R64(d, 0) : "r"(da), "r"(db), "n"(TB));
}
template <int TB> __device__ __forceinline__ void mma_rs_n128(float (&d)[64], uint32_t a0, uint32_t a1, uint32_t a2, uint32_t a3, uint32_t db, int sd) {
  asm volatile("{\n.reg .pred p;\n.reg .b64 db;\nsetp.ne.b32 p, %69, 0;\nmov.b64 db, {%68, " DHI "};\n"
               "wgmma.mma_async.sync.aligned.m64n128k16.f32.bf16.bf16 {" L64 "}, {%64,%65,%66,%67}, db, p, 1, 1, %70;\n}\n"
               : R64(d, 0) : "r"(a0), "r"(a1), "r"(a2), "r"(a3), "r"(db), "r"(sd), "n"(TB));
}
template <int TB> __device__ __forceinline__ void mma_ss_n256(float (&d)[128], uint32_t da, uint32_t db) {
  asm volatile("{\n.reg .b64 da, db;\nmov.b64 da, {%128, " DHI "};\nmov.b64 db, {%129, " DHI "};\n"
               "wgmma.mma_async.sync.aligned.m64n256k16.f32.bf16.bf16 {" L128 "}, da, db, 1, 1, 1, 0, %130;\n}\n"
               : R64(d, 0), R64(d, 64) : "r"(da), "r"(db), "n"(TB));
}
#define W8(d, o) "=f"(d[o]), "=f"(d[o + 1]), "=f"(d[o + 2]), "=f"(d[o + 3]), "=f"(d[o + 4]), "=f"(d[o + 5]), "=f"(d[o + 6]), "=f"(d[o + 7])
#define W32(d, o) W8(d, o), W8(d, o + 8), W8(d, o + 16), W8(d, o + 24)
#define W64(d, o) W32(d, o), W32(d, o + 32)
template <int TB> __device__ __forceinline__ void mma_ss_n128_init(float (&d)[64], uint32_t da, uint32_t db) {
  asm volatile("{\n.reg .b64 da, db;\nmov.b64 da, {%64, " DHI "};\nmov.b64 db, {%65, " DHI "};\n"
               "wgmma.mma_async.sync.aligned.m64n128k16.f32.bf16.bf16 {" L64 "}, da, db, 0, 1, 1, 0, %66;\n}\n"
               : W64(d, 0) : "r"(da), "r"(db), "n"(TB));
}
template <int TB> __device__ __forceinline__ void mma_ss_n256_init(float (&d)[128], uint32_t da, uint32_t db) {
  asm volatile("{\n.reg .b64 da, db;\nmov.b64 da, {%128, " DHI "};\nmov.b64 db, {%129, " DHI "};\n"
               "wgmma.mma_async.sync.aligned.m64n256k16.f32.bf16.bf16 {" L128 "}, da, db, 0, 1, 1, 0, %130;\n}\n"
               : W64(d, 0), W64(d, 64) : "r"(da), "r"(db), "n"(TB));
}
#define L32 "%0,%1,%2,%3,%4,%5,%6,%7,%8,%9,%10,%11,%12,%13,%14,%15,%16,%17,%18,%19,%20,%21,%22,%23,%24,%25,%26,%27,%28,%29,%30,%31"
__device__ __forceinline__ void mma_ss_n64(float (&d)[32], uint32_t da, uint32_t db) {
  asm volatile("{\n.reg .b64 da, db;\nmov.b64 da, {%32, " DHI "};\nmov.b64 db, {%33, " DHI "};\n"
               "wgmma.mma_async.sync.aligned.m64n64k16.f32.bf16.bf16 {" L32 "}, da, db, 1, 1, 1, 0, 0;\n}\n"
               : R32(d, 0) : "r"(da), "r"(db));
}
__device__ __forceinline__ void mma_ss_n64_init(float (&d)[32], uint32_t da, uint32_t db) {
  asm volatile("{\n.reg .b64 da, db;\nmov.b64 da, {%32, " DHI "};\nmov.b64 db, {%33, " DHI "};\n"
               "wgmma.mma_async.sync.aligned.m64n64k16.f32.bf16.bf16 {" L32 "}, da, db, 0, 1, 1, 0, 0;\n}\n"
               : W32(d, 0) : "r"(da), "r"(db));
}
#define L16 "%0,%1,%2,%3,%4,%5,%6,%7,%8,%9,%10,%11,%12,%13,%14,%15"
template <int O, bool INIT> __device__ __forceinline__ void mma_rs_n32(float (&d)[128], uint32_t a0, uint32_t a1, uint32_t a2, uint32_t a3, uint32_t db) {
  if (INIT) asm volatile("{\n.reg .b64 db;\nmov.b64 db, {%20, 0x00000008};\n"
               "wgmma.mma_async.sync.aligned.m64n32k16.f32.bf16.bf16 {" L16 "}, {%16,%17,%18,%19}, db, 0, 1, 1, 0;\n}\n"
               : W8(d, O), W8(d, O + 8) : "r"(a0), "r"(a1), "r"(a2), "r"(a3), "r"(db));
  else asm volatile("{\n.reg .b64 db;\nmov.b64 db, {%20, 0x00000008};\n"
               "wgmma.mma_async.sync.aligned.m64n32k16.f32.bf16.bf16 {" L16 "}, {%16,%17,%18,%19}, db, 1, 1, 1, 0;\n}\n"
               : R8(d, O), R8(d, O + 8) : "r"(a0), "r"(a1), "r"(a2), "r"(a3), "r"(db));
}
template <int S, int J> __device__ __forceinline__ void conv_step(float (&d)[128], const uint32_t (&a)[64], uint32_t db) {
  if constexpr (J >= 0 && J >= (S >> 1)) {
    mma_rs_n32<16 * J, S == 0>(d, a[4 * S], a[4 * S + 1], a[4 * S + 2], a[4 * S + 3], db + (uint32_t)((2 * J - S) * 16));
    conv_step<S, J - 1>(d, a, db);
  }
}
__device__ __forceinline__ void mma_ss_n8(float (&d)[4], uint32_t da, uint32_t db) {
  asm volatile("{\n.reg .b64 da, db;\nmov.b64 da, {%4, " DHI "};\nmov.b64 db, {%5, 0x00000008};\n"
               "wgmma.mma_async.sync.aligned.m64n8k16.f32.bf16.bf16 {%0,%1,%2,%3}, da, db, 1, 1, 1, 0, 0;\n}\n"
               : "+f"(d[0]), "+f"(d[1]), "+f"(d[2]), "+f"(d[3]) : "r"(da), "r"(db));
}
template <int N> __device__ __forceinline__ void reg_fence(float (&d)[N]) {
#pragma unroll
  for (int i = 0; i < N; i++) asm volatile("" : "+f"(d[i])::"memory");
}
template <int N> __device__ __forceinline__ void reg_fence(uint32_t (&d)[N]) {
#pragma unroll
  for (int i = 0; i < N; i++) asm volatile("" : "+r"(d[i])::"memory");
}

struct __align__(64) Params {
  unsigned* flags;
  int zero;
  uint8_t pref[128];
  const __nv_bfloat16 *gate_w, *ak, *av, *shk, *ssk, *ssd;
  CUtensorMap x, c, wq, wuk, wuv, wo, x3, y3, out, w;
};

template <int O, int N, int M> __device__ __forceinline__ void pack_frag(const float (&acc)[N], uint32_t (&pk)[M]) {
#pragma unroll
  for (int i = 0; i < 32; i++) pk[i] = pack_bf16(acc[O + 2 * i], acc[O + 2 * i + 1]);
}
template <int J0 = 0, int J1 = 8, int M> __device__ __forceinline__ void stsm_frag(const uint32_t (&pk)[M], uint32_t a) {
#pragma unroll
  for (int jj = J0; jj < J1; jj++)
    asm volatile("stmatrix.sync.aligned.m8n8.x4.shared.b16 [%0], {%1,%2,%3,%4};" ::"r"((a ^ ((jj & 3) << 5)) + (jj >> 2) * 16384),
                 "r"(pk[4 * jj]), "r"(pk[4 * jj + 1]), "r"(pk[4 * jj + 2]), "r"(pk[4 * jj + 3]) : "memory");
}

template <int N> __device__ __forceinline__ void store_scaled(const float (&acc)[N], float s0, float s1, uint32_t a, uint32_t never_zero) {
  float t[8];
#pragma unroll
  for (int jj = 0; jj < 8; jj++) {
    float v = acc[8 * jj] * s0;
    if (jj >= RST) {
      v = t[jj - RST];
      asm("{\n.reg .pred p;\nsetp.ne.u32 p, %3, 0;\n@p mul.f32 %0, %1, %2;\n}\n" : "+f"(v) : "f"(acc[8 * jj]), "f"(s0), "r"(never_zero));
    }
    const uint32_t q = pack_bf16(v, acc[8 * jj + 1] * s0);
    t[jj] = __uint_as_float(q);
    asm volatile("stmatrix.sync.aligned.m8n8.x4.shared.b16 [%0], {%1,%2,%3,%4};" ::"r"((a ^ ((jj & 3) << 5)) + (jj >> 2) * 16384), "r"(q),
                 "r"(pack_bf16(acc[8 * jj + 2] * s1, acc[8 * jj + 3] * s1)), "r"(pack_bf16(acc[8 * jj + 4] * s0, acc[8 * jj + 5] * s0)),
                 "r"(pack_bf16(acc[8 * jj + 6] * s1, acc[8 * jj + 7] * s1)) : "memory");
  }
}

struct Cons {
  uint32_t sb;
  uint32_t pf;
  int wg, tid;
  __device__ __forceinline__ void wait_full(int g) { mbar_wait(sb + SM_BAR + (B_FULL + g) * 8, (pf >> g) & 1); pf ^= 1u << g; }
  uint32_t relb;
  __device__ __forceinline__ void release(int g, int n) {
    if (tid < 2 * n) asm volatile("mbarrier.arrive.shared::cluster.b64 _, [%0];" ::"r"(relb + g * 8) : "memory");
  }
  __device__ __forceinline__ void turn_begin() { bar_sync(1 + wg, 256); }
  __device__ __forceinline__ void turn_end() { bar_arrive(2 - wg, 256); }
  __device__ __forceinline__ void staged(int e) { __syncwarp(); if ((tid & 31) == 0) mbar_arrive(sb + SM_BAR + (B_EV + 2 * e + wg) * 8); }
  int zero;
  int rnd;
  uint32_t pfree;
  __device__ __forceinline__ void wait_stage_free() { mbar_wait(sb + SM_BAR + (B_FREE + wg) * 8, pfree); pfree ^= 1; }
  __device__ __forceinline__ bool try_full(int g) { return mbar_test(sb + SM_BAR + (B_FULL + g) * 8, (pf >> g) & 1); }
};

constexpr float SM_C = 0.08838834764831845f * 1.4426950408889634f;
struct SoftState { float m0, m1, l0, l1; int shifted; };
__device__ __forceinline__ void ex2_rot(float& t, float s, uint32_t never_zero) {
  asm("{\n.reg .pred p;\nsetp.ne.u32 p, %2, 0;\n@p ex2.approx.ftz.f32 %0, %1;\n}\n" : "+f"(t) : "f"(s), "r"(never_zero));
}
__device__ __forceinline__ void pin(float a, uint32_t never_zero) {
  asm volatile("{\n.reg .pred p;\nsetp.eq.u32 p, %1, 0;\n@p st.shared.f32 [%1], %0;\n}\n" ::"f"(a), "r"(never_zero) : "memory");
}
template <int O, int N> __device__ __forceinline__ void reg_fence_part(uint32_t (&d)[32]) {
#pragma unroll
  for (int i = O; i < O + N; i++) asm volatile("" : "+r"(d[i])::"memory");
}
template <int Q, int W, int N> __device__ __forceinline__ void exp_quarter(const float (&S)[N], uint32_t (&P)[32], float (&t)[ROT], float& s0, float& s1, uint32_t nz) {
#pragma unroll
  for (int i = 8 * Q; i < 8 * Q + 8; i++) {
    float& a = t[(2 * i) % ROT];
    float& b = t[(2 * i + 1) % ROT];
    if (2 * i < ROT) { a = ex2(S[2 * i]); b = ex2(S[2 * i + 1]); }
    else { ex2_rot(a, S[2 * i], nz); ex2_rot(b, S[2 * i + 1], nz); }
    if (i < 2) { if (i) s1 = a + b; else s0 = a + b; }
    else if (i & 1) { s1 += a; s1 += b; } else { s0 += a; s0 += b; }
    if (i == 8 * Q) { pin(Q ? s1 : s0, nz); wg_wait<W>(); reg_fence_part<8 * Q, 8>(P); }
    P[i] = pack_bf16(a, b);
  }
}
template <int N> __device__ __forceinline__ void shift_scores(float (&S)[N], float d0, float d1) {
#pragma unroll
  for (int i = 0; i < N; i++) S[i] -= (i & 2) ? d1 : d0;
}
__device__ __forceinline__ bool soft_high(float s0, float s1, float lim = SM_LIMIT) { return s0 > lim || s1 > lim; }
__device__ __forceinline__ bool soft_unsafe(float s0, float s1, bool first) {
  uint32_t b0 = __ballot_sync(0xffffffffu, s0 >= SM_LOW), b1 = __ballot_sync(0xffffffffu, s1 >= SM_LOW);
  b0 |= b0 >> 1; b0 |= b0 >> 2; b1 |= b1 >> 1; b1 |= b1 >> 2;
  return __any_sync(0xffffffffu, soft_high(s0, s1)) || (first && (b0 & b1 & 0x11111111u) != 0x11111111u);
}
template <int N> __device__ __forceinline__ void soft_fix(const float (&S)[N], float (&O)[64], SoftState& z, bool first, float& d0, float& d1) {
  d0 = d1 = first ? -INFINITY : 0.f;
#pragma unroll
  for (int j = 0; j < N / 4; j++) { d0 = fmaxf(d0, fmaxf(S[4 * j], S[4 * j + 1])); d1 = fmaxf(d1, fmaxf(S[4 * j + 2], S[4 * j + 3])); }
  d0 = fmaxf(d0, __shfl_xor_sync(0xffffffffu, d0, 1)); d1 = fmaxf(d1, __shfl_xor_sync(0xffffffffu, d1, 1));
  d0 = fmaxf(d0, __shfl_xor_sync(0xffffffffu, d0, 2)); d1 = fmaxf(d1, __shfl_xor_sync(0xffffffffu, d1, 2));
  const float sc0 = ex2(-fmaxf(d0, 0.f)), sc1 = ex2(-fmaxf(d1, 0.f));
  z.m0 += d0; z.m1 += d1; z.l0 *= sc0; z.l1 *= sc1; z.shifted = 1;
#pragma unroll
  for (int j = 0; j < 16; j++) { O[4 * j] *= sc0; O[4 * j + 1] *= sc0; O[4 * j + 2] *= sc1; O[4 * j + 3] *= sc1; }
}
template <int N> __device__ __forceinline__ void mask_diag(float (&S)[N], float nd) {
  asm volatile("" : "+f"(nd));
#pragma unroll
  for (int i = 0; i < 32; i++) {
    const float beyond = __saturatef(nd + (float)(8 * (i >> 2) + (i & 1) - 4 * (i & 2)));
    S[N - 32 + i] = fmaf(beyond, -3.0e38f, S[N - 32 + i]);
  }
}
__device__ __forceinline__ float quad_sum(float v) {
  v += __shfl_xor_sync(0xffffffffu, v, 1);
  v += __shfl_xor_sync(0xffffffffu, v, 2);
  return v;
}
__device__ __forceinline__ void issue_qk(float (&S)[64], uint32_t dq, uint32_t dk) {
  mma_ss_n128_init<0>(S, dq, dk);
#pragma unroll
  for (int s = 1; s < 8; s++) mma_ss_n128<0>(S, dq + (s >> 2) * 1024 + (s & 3) * 2, dk + (s >> 2) * 1024 + (s & 3) * 2);
}
__device__ __forceinline__ void issue_qk(float (&S)[32], uint32_t dq, uint32_t dk) {
  mma_ss_n64_init(S, dq, dk);
#pragma unroll
  for (int s = 1; s < 8; s++) mma_ss_n64(S, dq + (s >> 2) * 1024 + (s & 3) * 2, dk + (s >> 2) * 1024 + (s & 3) * 2);
}
template <int H> __device__ __forceinline__ void issue_pv(float (&O)[64], const uint32_t (&P)[32], uint32_t dv, int acc, bool on) {
  if (on) {
#pragma unroll
    for (int s = 4 * H; s < 4 * H + 4; s++) {
      mma_rs_n128<1>(O, P[4 * s], P[4 * s + 1], P[4 * s + 2], P[4 * s + 3], dv + s * 128, s != 0 ? 1 : acc);
      if (s & 1) wg_commit();
    }
  } else { wg_commit(); wg_commit(); }
}
constexpr uint32_t DG = GR >> 4;
__device__ __forceinline__ void stage_q2(Cons& c, const float (&O)[64], uint32_t (&P)[32], uint32_t stg) {
  wg_commit(); wg_commit(); wg_commit(); wg_commit();
  c.turn_end();
  pack_frag<0>(O, P);
  stsm_frag(P, stg);
}
__device__ __forceinline__ void attn_half(Cons& c, float (&O)[64], uint32_t (&P)[32], SoftState& z, uint32_t dk0, uint32_t dkk, uint32_t dv0, float dmask, int last) {
  float S[32];
  FTH(8 + last * 32, 0);
  c.turn_begin();
  FTH(9 + last * 32, 0);
  wg_fence();
  issue_qk(S, dk0 + (last ? 0 : 2 * DG), dkk + (last ? 8 : 4) * DG);
  wg_commit();
  issue_pv<0>(O, P, dv0 + 10 * DG, 1, last);
  issue_pv<1>(O, P, dv0 + 10 * DG, 1, last);
  c.turn_end();
  c.wait_full(last ? 12 : 6);
  FTH(10 + last * 32, 0);
  wg_wait<4>();
  reg_fence(S);
  FTH(11 + last * 32, 0);
  c.release(last ? 8 : 4, 2);
  mask_diag(S, dmask);
  float s0, s1, d0 = z.m0, d1 = z.m1;
#pragma unroll 1
  for (int pass = 0;; pass++) {
    if (z.shifted) shift_scores(S, d0, d1);
    float tr[ROT];
    exp_quarter<0, 3>(S, P, tr, s0, s1, c.sb);
    exp_quarter<1, 2>(S, P, tr, s0, s1, c.sb);
    pin(s1, c.sb); wg_wait<0>(); reg_fence_part<16, 16>(P); reg_fence(O);
    if (!soft_unsafe(s0, s1, !last) || pass) break;
    soft_fix(S, O, z, !last, d0, d1);
  }
  FTH(12 + last * 32, 0);
  if (!last) FTB(2);
  z.l0 += s0; z.l1 += s1;
  c.release(10, last ? 2 : 0);
  if (!last) c.wait_full(8);
  FTH(13 + last * 32, 0);
  if (!last) FTB(3);
}

template <int V> struct IC { static constexpr int value = V; };
__device__ __forceinline__ int conv_next(int g, bool spare) { return g >= NGR - 2 ? g - (NGR - 4) : !spare && g == 4 ? 1 : g + 2; }
__device__ __forceinline__ void conv_final(uint32_t rb, uint32_t yb, bool on) {
  const uint4 q0 = lds128(rb), q1 = lds128(rb + 4096), q2 = lds128(rb + 8192), q3 = lds128(rb + 12288);
  auto fin = [&](uint32_t x0, uint32_t x1, uint32_t x2, uint32_t x3) { return hadd2(hadd2(x0, x1), hadd2(x2, x3)); };
  asm volatile("{\n.reg .pred p;\nsetp.ne.b32 p, %5, 0;\n@p st.shared.v4.b32 [%0], {%1,%2,%3,%4};\n}\n" ::"r"(yb), "r"(fin(q0.x, q1.x, q2.x, q3.x)),
               "r"(fin(q0.y, q1.y, q2.y, q3.y)), "r"(fin(q0.z, q1.z, q2.z, q3.z)), "r"(fin(q0.w, q1.w, q2.w, q3.w)), "r"((int)on) : "memory");
}
__device__ __forceinline__ void conv_tasks(Cons& c, const Params& p, int ntask, bool spare, int ch, int chstep, int c5, uint32_t dd, uint32_t dkk, int w, int lane) {
  const uint32_t sb = c.sb;
  int g = 2 + c.wg;
  uint32_t rb = sb + g * GR;
  const uint32_t yb = sb + c.wg * 8192 + c.tid * 16;
  const int gt = 8 * w + (lane >> 2) + (lane & 3);
  uint32_t a[64], hb;
  auto lda = [&](int s) {
    a[4 * s] = lds32(hb + s * 256); a[4 * s + 1] = lds32(hb + s * 256 + 128);
    a[4 * s + 2] = lds32(hb + s * 256 + 16); a[4 * s + 3] = lds32(hb + s * 256 + 144);
  };
  auto first_a = [&]() {
    hb = sb + g * GR + WBYTES - 28 + gt * 4;
    lda(0); lda(15);
  };
  c.wait_full(g);
  first_a();
#pragma unroll 1
  for (int i = 0; i < ntask; i++) {
    const uint32_t base = sb + g * GR;
    FTC(0);
    lda(1); lda(14);
    a[0] = hadd2(a[0], gt == 7 ? dd : 0u); a[2] = hadd2(a[2], gt == 3 ? dd : 0u);
    float acc[128];
    const uint32_t db = dkk + ((WPL / 16 - 1) << 16) + g * DG + WZ / 16;
    FTC(2);
    c.turn_begin();
    FTC(3);
    auto pair = [&](auto kc) {
      constexpr int k = decltype(kc)::value;
      if (k < 7) wg_fence();
      if (k == 6) c.turn_end();
      conv_step<k, 7>(acc, a, db);
      conv_step<15 - k, 7>(acc, a, db);
      if (k < 6) { lda(k + 2); lda(13 - k); }
      if (k == 0) conv_final(rb, yb, i > 0);
      if (k == 1) {
        conv_final(rb + 2048, yb + 2048, i > 0);
        __syncwarp();
        if (lane == 0 && i > 0) mbar_arrive(sb + SM_BAR + (B_EV + c.wg) * 8);
      }
      if (k == 6) dd = __bfloat16_as_ushort(p.ssd[(ch + chstep + (i == 1 ? c5 : 0)) & (DM - 1)]);
    };
    pair(IC<0>()); pair(IC<1>()); pair(IC<2>()); pair(IC<3>()); pair(IC<4>()); pair(IC<5>()); pair(IC<6>()); pair(IC<7>());
    wg_commit();
    FTC(4);
    g = conv_next(g, spare);
    ch += chstep;
    rb = base + c.tid * 16;
    if (i + 1 < ntask) c.wait_full(g);
    const bool fr = mbar_test(sb + SM_BAR + (B_FREE + c.wg) * 8, c.pfree);
    wg_wait<0>();
    reg_fence(acc);
    reg_fence(a);
    bar_sync(3 + c.wg, 128);
    FTC(5);
    first_a();
    const int tw = (lane & 3) + w;
    const uint32_t xb = base + w * 4096 + tw * 32 + (lane >> 2) * 4;
    [[maybe_unused]] float t0[EROT + 1];
#pragma unroll
    for (int j = 0; j < 32; j++) {
      uint32_t ad = xb + j * 128;
      float v0 = acc[4 * j], v1 = acc[4 * j + 1];
      if (EROT && j > EROT) {
        v0 = t0[j % (EROT + 1)];
        asm("{\n.reg .pred p;\nsetp.ne.u32 p, %3, 0;\n@p add.f32 %0, %1, %2;\n}\n" : "+f"(v0) : "f"(acc[4 * j]), "f"(acc[j > 0 ? 4 * j - 2 : 0]), "r"(sb));
      } else if (j > 0) v0 += acc[j > 0 ? 4 * j - 2 : 0];
      if (j > 0) v1 += acc[j > 0 ? 4 * j - 1 : 0];
      uint32_t v = pack_bf16(v0, v1);
      t0[j % (EROT + 1)] = __uint_as_float(v);
      if (j == 31 && tw >= 4) { v = 0; ad -= 4096; }
      asm volatile("st.shared.b32 [%0], %1;" ::"r"(ad), "r"(v) : "memory");
    }
    if (!fr) c.wait_stage_free(); else c.pfree ^= 1;
    FTC(6);
  }
  bar_sync(3 + c.wg, 128);
  conv_final(rb, yb, true);
  conv_final(rb + 2048, yb + 2048, true);
  c.staged(0);
}

__global__ void __cluster_dims__(2, 1, 1) __launch_bounds__(NTHREADS, 1) mega_kernel(const __grid_constant__ Params p) {
  extern __shared__ __align__(1024) uint8_t smem_raw[];
  FTS(0);
  const uint32_t sb = smem_u32(smem_raw);
  if (threadIdx.x - 64 < 32) { prefetch_tm(&p.c); prefetch_tm(&p.wuk + (blockIdx.x & 1)); }
  const int wgi = __shfl_sync(0xffffffffu, threadIdx.x >> 7, 0);
  const int warp = __shfl_sync(0xffffffffu, threadIdx.x >> 5, 0);
  const uint32_t rank = blockIdx.x & 1;
  int slot;
  {
    uint32_t smid; asm volatile("mov.u32 %0, %smid;" : "=r"(smid));
    slot = p.pref[((smid >> 1) + (threadIdx.x & (smid >> 16))) & 127];
  }
  if (warp >= 3) {
    if (elect()) {
#pragma unroll
      for (int k = 0; k < 4; k++) mbar_init(sb + SM_BAR + ((warp - 3) * 4 + k) * 8, k == 1 && warp == 7 ? 11 : warp < (k ? 7 : 8) ? 1 : 4);
      if (warp == 7) { mbar_init(sb + SM_BAR + B_TICK * 8, 1); mbar_expect_tx(sb + SM_BAR + B_SLOT * 8, 8); mbar_expect_tx(sb + SM_BAR + B_TICK * 8, 4); }
      asm volatile("fence.mbarrier_init.release.cluster;" ::: "memory");
    }
    __syncwarp();
  }
  FTS(1);
  cluster_arrive();
  slot = __shfl_sync(0xffffffffu, slot, 0);
  const int pref = slot;
  if (warp < 4) {
    asm volatile("setmaxnreg.dec.sync.aligned.u32 40;");
    if (warp == 1 + 4 * rank) {
      unsigned taken = threadIdx.x == 32;
#pragma unroll 1
      for (int n = 0; n < NSLOT; n++) {
        asm volatile("{\n.reg .pred p;\nsetp.ne.b32 p, %0, 0;\n@p atom.relaxed.gpu.global.exch.b32 %0, [%1], 1;\n}\n" : "+r"(taken) : "l"(CLAIMP(slot)) : "memory");
        if (!__any_sync(0xffffffffu, taken)) break;
        slot = slot == NSLOT - 1 ? 0 : slot + 1;
      }
    }
    cluster_wait();
    if (threadIdx.x == 32) {
      send_both(sb + SM_BAR + B_SLOT * 8, (V_SLOT - B_SLOT) * 8 + rank * 4, slot | pref << 8);
    }
    if (warp == 2) {
#pragma unroll 1
      for (int kk = 0; kk < 4; kk++) {
        const int g0 = 2 + 3 * kk;
        const uint32_t fb = sb + SM_BAR + (B_FULL + g0) * 8;
        if (elect()) {
          FTSW(kk);
          mbar_expect_tx(fb, 3 * GR);
          tma2d(sb + g0 * GR, &p.c, kk * 64, (KV_ROW(pref & 7, 0) + rank) * 128, fb);
          tma3d_mc(sb + (g0 + 1 + rank) * GR, rank ? &p.wuv : &p.wuk, 0, kk * 64, ((pref & 56) >> 1) + 2 * KV_HEAD(pref & 7, 0), fb);
        }
        if (kk < 3) {
          uint32_t c0, c1;
          asm volatile("mov.u32 %0, %clock;" : "=r"(c0));
          do asm volatile("mov.u32 %0, %clock;" : "=r"(c1)); while (c1 - c0 < (kk ? X_D2 : X_DELAY));
        }
      }
      FTSW(4);
      prefetch_tm(&p.x); prefetch_tm(&p.wq);
    }
  }
  int grp, idx, lb;
  int cn, cch, cstep;
  bool spare, redo;
  auto get_slot = [&]() {
    mbar_wait(sb + SM_BAR + B_SLOT * 8, 0);
    const uint32_t sv0 = __shfl_sync(0xffffffffu, lds32(sb + SM_BAR + V_SLOT * 8), 0), sv1 = __shfl_sync(0xffffffffu, lds32(sb + SM_BAR + V_SLOT * 8 + 4), 0);
    grp = (sv0 & 255) >> 3; idx = sv0 & 7; lb = (sv0 & 255) * 2 + rank;
    spare = grp == 8; redo = spare || sv0 != sv1;
    cn = CN_SPARE; cch = spare ? lb - NMAIN : 4 * CN_SPARE + 4 * lb; cstep = spare ? 4 : 1;
    if (FINE_MODE != 7) TS(0);
  };
  auto get_ticket = [&]() {
    mbar_wait(sb + SM_BAR + B_TICK * 8, 0);
    const int tk = __shfl_sync(0xffffffffu, lds32(sb + SM_BAR + V_TICK * 8), 0);
    cn = tk < NTICK ? 5 : 4;
    return 4 * NMAIN - 4 * lb - 4 + 2 * tk + rank;
  };

  if (wgi == 0) {
    asm volatile("setmaxnreg.dec.sync.aligned.u32 40;");
    const int lane = threadIdx.x & 31;
    cluster_arrive();
    get_slot();
    uint32_t pe = 0;
    auto acquire = [&](int g, int n, uint32_t m) {
      int i = g;
#pragma unroll 1
      do mbar_wait1(sb + SM_BAR + (B_EMPTY + i) * 8, (pe >> i) & 1); while (++i < g + n);
      pe ^= m << g;
    };
    if (warp == 3) {
      if (!spare) {
        const int s0 = lb * 16;
#pragma unroll 1
        for (int cg = 0; cg < 16; cg++) {
          if (cg == UP0 || cg == UP1) {
#pragma unroll 1
            for (int n = 0; n < 20 && !__any_sync(0xffffffffu, mbar_try(sb + SM_BAR + B_SLOT * 8, cg == UP0)); n++);
          } else if (cg < UP0) __nanosleep(US0);
          if (cg == UP1 && lane == rank * 32) send_both(sb + SM_BAR + B_TICK * 8, (V_TICK - B_TICK) * 8, atomicInc(FLAG(F_TICK), 0x7fffffffu));
          const int ch = cg * 64 + 2 * lane;
          const uint32_t* kp = reinterpret_cast<const uint32_t*>(p.ak + (size_t)s0 * DM + ch);
          const uint32_t* vp = reinterpret_cast<const uint32_t*>(p.av + (size_t)s0 * DM + ch);
          const uint4 sw = __ldg(reinterpret_cast<const uint4*>(p.shk + ch * 4));
          uint32_t k3 = 0, k2 = 0, k1 = 0, k0 = 0, up = 0;
          if (lb > 0) { k3 = ldg_stream(kp - 4 * 512); k2 = ldg_stream(kp - 3 * 512); k1 = ldg_stream(kp - 2 * 512); k0 = ldg_stream(kp - 512); up = ldg_stream(vp - 512); }
          const uint32_t w0 = __byte_perm(sw.x, sw.z, 0x5410), w1 = __byte_perm(sw.x, sw.z, 0x7632);
          const uint32_t w2 = __byte_perm(sw.y, sw.w, 0x5410), w3 = __byte_perm(sw.y, sw.w, 0x7632);
          up = hmul2(hfma2(k0, w0, hfma2(k1, w1, hfma2(k2, w2, hmul2(k3, w3)))), up);
#pragma unroll 1
          for (int hb = 0; hb < 2; hb++) {
            uint32_t kk[8], u[8];
#pragma unroll
            for (int r = 0; r < 8; r++) { kk[r] = ldg_stream(kp + r * 512); u[r] = ldg_stream(vp + r * 512); }
#pragma unroll
            for (int r = 0; r < 8; r++) {
              k3 = k2; k2 = k1; k1 = k0; k0 = kk[r];
              u[r] = hmul2(hfma2(k0, w0, hfma2(k1, w1, hfma2(k2, w2, hmul2(k3, w3)))), u[r]);
            }
            if (lane == 0) asm volatile("cp.async.bulk.wait_group.read 0;" ::: "memory");
            __syncwarp();
            const uint32_t dst = sb + SM_UST + lane * 32 + ((lane & 4) << 2);
#pragma unroll
            for (int cc = 0; cc < 2; cc++) {
              const uint32_t sel = cc ? 0x7632 : 0x5410;
              asm volatile("st.shared.v4.b32 [%0], {%1,%2,%3,%4};" ::"r"(dst + cc * 1024), "r"(__byte_perm(u[6], u[5], sel)), "r"(__byte_perm(u[4], u[3], sel)),
                           "r"(__byte_perm(u[2], u[1], sel)), "r"(__byte_perm(u[0], up, sel)) : "memory");
              asm volatile("st.shared.v4.b32 [%0], {%1,%2,%3,%4};" ::"r"((dst ^ 16) + cc * 1024), "r"(__byte_perm(u[7], u[6], sel)), "r"(__byte_perm(u[5], u[4], sel)),
                           "r"(__byte_perm(u[3], u[2], sel)), "r"(__byte_perm(u[1], u[0], sel)) : "memory");
            }
            fence_async_smem();
            __syncwarp();
            if (lane == 0) {
              asm volatile("cp.async.bulk.tensor.3d.global.shared::cta.bulk_group.L2::cache_hint [%0, {%2, %3, %4}], [%1], %5;\ncp.async.bulk.commit_group;"
                           ::"l"(&p.w), "r"(sb + SM_UST), "r"(WZ / 2 + lb * 16 + (hb ^ 1) * (WPL / 2)), "r"(cg * 32), "r"(0), "l"(cg >= UP0 && cg < UP1 ? EV_FIRST : EV_NORMAL) : "memory");
            }
            up = u[7];
            kp += 8 * 512; vp += 8 * 512;
          }
          if ((cg & (cg + 1)) == 0 && lane == 0) {
            asm volatile("cp.async.bulk.wait_group 0;" ::: "memory");
            fence_release();
            flag_add(FLAG(F_U + 32 - __clz(cg)));
          }
          TSW(10 + cg);
        }
        prefetch_tm(&p.wo); prefetch_tm(&p.x3); prefetch_tm(&p.y3); prefetch_tm(&p.out);
      } else {
#pragma unroll 1
        for (int i = 0, g = 2; i < 32; i++) {
          acquire(g, 2, 3);
          if (elect()) {
            const uint32_t fb = sb + SM_BAR + (B_FULL + g) * 8;
            if (i == 0) { mbar_expect_tx(fb - 8, 2048); bulk_g2s(sb + GR, p.gate_w, 2048, fb - 8); }
            mbar_expect_tx(fb, 2 * GR);
            tma3d(sb + g * GR, &p.x3, 0, (lb - NMAIN) * 512 + (i >> 3) * 128, (i & 7) * 2, fb);
          }
          g = g == NGR - 2 ? 2 : g + 2;
        }
        bar_arrive(5, 64);
      }
      unsigned long long t0, t1;
      asm volatile("mov.u64 %0, %globaltimer;" : "=l"(t0));
      auto check = [&]() {
        asm volatile("mov.u64 %0, %globaltimer;" : "=l"(t1));
        if (t1 - t0 > 2000000000ull) __trap();
      };
      if (!spare) {
        unsigned v;
        do {
          __nanosleep(PSL);
          check();
          asm volatile("ld.acquire.gpu.global.u32 %0, [%1];" : "=r"(v) : "l"(FLAG(lane & 1 ? F_Y + idx : F_GATE)) : "memory");
        } while (__any_sync(0xffffffffu, v < (lane & 1 ? 128 : 32)));
        __syncwarp();
        if (lane == 0) mbar_arrive(sb + SM_BAR + B_SLOT * 8);
      }
      if (lane == 0) {
        while (!mbar_try(sb + SM_BAR + B_DONE * 8, 0)) check();
      }
    } else if (warp != 0) {
      const int w = warp - 1;
      int ne = 12 + (CN_SPARE + 1 - w) / 2, c5 = 0;
      uint32_t p0 = 0;
      int cg = 2 + w, ch = cch + w * cstep;
#pragma unroll 1
      for (int e = spare ? 12 : 0; e < ne; e++) {
        const int rnd = e >= 6, k = e - 6 * rnd, rt = k == 4 ? idx : 15 - idx;
        uint8_t* dst = k < 4 ? g_kv + (size_t)(((k & 1) * 16 + 2 * grp + KV_HEAD(idx, k >> 1)) * 16 + KV_ROW(idx, k >> 1) + rank) * 32768 + w * 8192
                     : k < 6 ? g_cimg + (size_t)(rt * 32 + 16 * rnd + 2 * grp + rank) * 32768 + (w ^ (k & 1)) * 8192
                             : g_w + (size_t)ch * WSTRIDE + WZ;
        const uint32_t src = sb + w * 8192 + (k == 4 ? 2 * GR : 0);
        if (e == 11) { c5 = get_ticket(); ne = 12 + ((cn + 1 - w) >> 1); }
        if (e == 6) flag_wait(FLAG(F_AD + grp), 32);
        mbar_wait1(sb + SM_BAR + (B_EV + (k == 4 ? 2 : 0) + w) * 8, k == 4 ? rnd : p0);
        if (k != 4) p0 ^= 1;
        if (lane < 4 && k >= 6 && (!spare || e < ne - 6)) mbar_arrive_cluster(sb + SM_BAR + (B_EMPTY + cg) * 8, lane & 1);
        fence_async_smem();
        if (elect()) {
          const uint32_t cs = k >= 6 ? 4096 : 1024;
#pragma unroll 1
          for (uint32_t i = 0; i < (k >= 6 ? 4096 : 16384); i += cs) {
            const uint32_t o = i + (i & 8192);
            asm volatile("cp.async.bulk.global.shared::cta.bulk_group.L2::cache_hint [%0], [%1], %2, %3;" ::"l"(dst + o), "r"(src + o), "r"(cs),
                         "l"(e == 4 || e == 5 || spare ? EV_FIRST : EV_NORMAL) : "memory");
            asm volatile("cp.async.bulk.commit_group;\ncp.async.bulk.wait_group.read 1;" ::: "memory");
          }
          asm volatile("cp.async.bulk.wait_group 0;" ::: "memory");
          if (k != 4) mbar_arrive(sb + SM_BAR + (B_FREE + w) * 8);
        }
        __syncwarp();
        if (lane < (k == 4 ? 4 : e == 11 || (e == ne - 1 && !spare) ? 2 : 0))
          mbar_arrive_cluster(sb + SM_BAR + (B_EMPTY + (k == 4 ? 2 : e == 11) + (lane >> 1)) * 8, lane & 1);
        if (k >= 3) {
          fence_release();
          const unsigned fl = k == 3 ? F_KV + rnd * 8 + grp : k < 6 ? F_CTX + rt * 2 + rnd : F_Y + ((unsigned)ch >> 7);
          if (lane <= (e == 5)) flag_add(FLAG(lane ? F_AD + grp : fl));
        }
        if (k >= 6) { cg = conv_next(cg, spare); ch += 2 * cstep + (k == 7 ? c5 : 0); }
      }
      if (lane == 0) mbar_arrive(sb + SM_BAR + B_DONE * 8);
    } else {
#pragma unroll 1
      for (int rnd = 0; rnd < (spare ? 0 : 2); rnd++) {
        const int hp = 16 * rnd + 2 * grp, head = hp + rank;
#pragma unroll 1
        for (int kk = rnd || redo ? 0 : 4; kk < 32; kk++) {
          const int g0 = 2 + 3 * (kk & 3);
          acquire(g0, kk < 4 ? 3 : 1, 7);
          if (elect()) {
            const uint32_t fb = sb + SM_BAR + (B_FULL + g0) * 8;
            mbar_expect_tx(fb, 3 * GR);
            if (kk < 16) {
              tma2d_p(sb + g0 * GR, &p.c, (kk & 7) * 64, (KV_ROW(idx, kk >> 3) + rank) * 128, fb, rnd);
              tma3d_mc_p(sb + (g0 + 1 + rank) * GR, rank ? &p.wuv : &p.wuk, 0, (kk & 7) * 64, (hp + KV_HEAD(idx, kk >> 3)) * 2, fb, kk >= 8);
            } else {
              tma2d_mc(sb + (g0 + rank) * GR, &p.x, (kk - 16) * 64, (rank ? 15 - idx : idx) * 128, fb);
              tma3d<true>(sb + (g0 + 2) * GR, &p.wq, 0, (kk - 16) * 64, head * 2, fb);
            }
          }
        }
        flag_wait(FLAG(F_KV + rnd * 8 + grp), 32);
        fence_async_all();
        acquire(2, 1, 3);
        int g0 = 4;
#pragma unroll 1
        for (int n = 0; n < 36; n += n == 0 || n == 33 ? 2 : 1) {
          const int it = (n >> 1) - (n & 1);
          const int blk = it & 15 ? (it <= idx ? it - 1 : 15 - it) : it ? 15 - idx : idx;
          acquire(g0, n < 6 ? 2 : 1, 3);
          if (elect()) {
            const uint32_t fb = sb + SM_BAR + (B_FULL + g0) * 8;
            if (FINE_MODE == 8 && n < 8) FTP(rnd * 32 + 24 + n);
            if (n == 5) mbar_arrive(sb + SM_BAR + B_SLOT * 8);
            mbar_expect_tx(fb, 2 * GR);
            asm volatile("cp.async.bulk" TMA_MB ".L2::cache_hint [%0], [%1], %2, [%3], %4;" ::"r"(sb + g0 * GR), "l"(g_kv + (unsigned)((((n & 1) * 16 + (head & 15)) * 16 + blk) * 32768)),
                         "r"(2 * GR), "r"(fb), "l"(it >= 8 ? EV_FIRST : EV_NORMAL) : "memory");
          }
          g0 = n == 13 ? 12 : g0 == 12 ? 4 : g0 + 2;
        }
      }
      int c5 = 0;
      if (spare) { bar_sync(5, 64); pe = 0x3FC0; }
      else c5 = get_ticket();
      auto conv_fill = [&](int g, int ch) {
        acquire(g, 1, 1);
        if (elect()) {
          const uint32_t fb = sb + SM_BAR + (B_FULL + g) * 8;
          if (FINE_MODE == 2 && !spare) FTP(64 + 48 + g);
          mbar_expect_tx(fb, WBYTES + 4096);
          bulk_g2s<true>(sb + g * GR, g_w + (size_t)ch * WSTRIDE, WBYTES, fb);
          bulk_g2s<true>(sb + g * GR + WBYTES, p.ssk + (size_t)ch * SEQ, 4096, fb);
        }
      };
#pragma unroll 1
      for (int i = 0, g = 2; i < cn; i++) {
        if ((i & 15) == 0) { flag_wait(FLAG(F_U + (spare ? 32 - __clz(i >> 4) : 4)), NMAIN); fence_async_all(); }
        conv_fill(g + (i & 1), cch + i * cstep + (i == 4 ? c5 : 0));
        if (i & 1) g = conv_next(g, spare);
      }
      if (!spare) {
        const int rt = 2 * grp + rank, ct = idx;
        int g0 = P3G, top = 12;
        const uint8_t* src = g_cimg + (unsigned)((rt * 64 + 32) * GR);
#pragma unroll 1
        for (int kb = 0; kb < 64; kb++) {
          if (!(kb & 31)) { flag_wait(FLAG(F_CTX + rt * 2 + ((kb ^ 32) >> 5)), 32); fence_async_all(); if (kb) src -= 64 * GR; }
          acquire(g0, kb < 11 ? 2 : 1, 3);
          if (elect()) {
            const uint32_t fb = sb + SM_BAR + (B_FULL + g0) * 8;
            if (FINE_MODE == 2 && kb < 16) FTP(48 + kb);
            mbar_expect_tx(fb, 2 * GR);
            bulk_g2s<true>(sb + g0 * GR, src, GR, fb);
            tma2d_mc<true>(sb + (g0 + 1) * GR + rank * 8192, &p.wo, ct * 128 + rank * 64, (kb ^ 32) * 64, fb);
          }
          src += GR;
          g0 = g0 == (kb < XK ? 12 : kb < YK ? 10 : 8) ? (kb == 3 ? 2 : 0) : g0 + 2;
          if (kb == XK || (kb >= YK && top == P3Y && (kb == 63 || mbar_test(sb + SM_BAR + B_SLOT * 8, 1)))) {
            const bool j = kb != XK;
            if (j) { mbar_wait1(sb + SM_BAR + B_SLOT * 8, 1); fence_async_all(); }
            acquire(top, 1, 0);
            if (elect()) {
              const uint32_t fb = sb + SM_BAR + (B_FULL + top) * 8;
              mbar_expect_tx(fb, j ? 2 * GR + 512 : 2 * GR);
              if (j) bulk_g2s(sb + SM_GATE, g_gate + (unsigned)(rt * 128), 512, fb);
              tma3d(sb + top * GR, j ? &p.y3 : &p.x3, 0, (j ? ct : rt) * 128, (j ? rt : ct) * 2, fb);
            }
            top -= 2;
          }
        }
        unsigned n = 0;
        if (lane == 0) n = atomicInc(FLAG(F_EXIT), 0x7fffffffu);
        if (__any_sync(0xffffffffu, n == NMAIN - 1)) {
#pragma unroll
          for (int i = lane; i < 96; i += 32) *reinterpret_cast<uint2*>(FLAG(i)) = make_uint2(0, 0);
        }
      }
      if (lane == 0) mbar_arrive(sb + SM_BAR + B_DONE * 8);
    }
    __syncwarp();
    cluster_wait();
  } else {
    asm volatile("setmaxnreg.inc.sync.aligned.u32 232;");
    FTS(2);
    Cons c;
    c.sb = sb; c.pf = 0; c.wg = wgi - 1; c.tid = threadIdx.x & 127;
    const int lane = threadIdx.x & 31, t = lane & 3;
    const int row = c.wg * 64 + (warp & 3) * 16 + (lane >> 2);
    const uint32_t dkk = desc_k(sb), dk0 = dkk + c.wg * 512, dm0 = desc_mn<8192>(sb), dv0 = desc_mn<16384>(sb);
    const uint32_t dsw = DG + 512 - c.wg * 1024;
    if (c.wg == 1) bar_arrive(1, 256);
    c.pfree = 1;
    asm("mapa.shared::cluster.u32 %0, %1, %2;" : "=r"(c.relb) : "r"(sb + SM_BAR + (B_EMPTY + (c.tid >> 1)) * 8), "r"(c.tid & 1));
    c.zero = p.zero;
    c.rnd = 0;
    const uint32_t stg = sb + (c.wg * 64 + (warp & 3) * 16 + ((lane >> 3) & 1) * 8 + (lane & 7)) * 128 + (((lane >> 4) ^ (lane & 7)) << 4);

    uint32_t dd0;
    auto load_dd = [&]() { asm volatile("ld.global.nc.u16 %0, [%1];" : "=r"(dd0) : "l"(p.ssd + (unsigned)(cch + c.wg * cstep + (lane & c.zero)))); };
    int pass = c.zero;
#pragma unroll 1
    do {
    if (pass) {
      load_dd();
#pragma unroll 1
      for (int g = 2; g < NGR; g += 3) { mbar_wait(sb + SM_BAR + (B_FULL + g) * 8, 0); c.release(g, 3); }
      c.pf = 0x924;
    if (spare) {
      c.wait_full(1);
      int g = 2;
#pragma unroll 1
      for (int r = 0; r < 4; r++) {
        float d[4] = {0.f, 0.f, 0.f, 0.f}, e[4] = {0.f, 0.f, 0.f, 0.f};
#pragma unroll 1
        for (int kb = 0; kb < 16; kb += 2) {
          c.wait_full(g);
          wg_fence();
#pragma unroll 1
          for (int k = 0; k < 4; k++) {
            mma_ss_n8(d, dk0 + g * DG + k * 2, dkk + DG + kb * 8 + k * 2);
            mma_ss_n8(e, dk0 + (g + 1) * DG + k * 2, dkk + DG + kb * 8 + 8 + k * 2);
          }
          wg_commit();
          wg_wait<0>();
          c.release(g, 2);
          g = g == NGR - 2 ? 2 : g + 2;
        }
        reg_fence(d); reg_fence(e);
        d[0] += e[0]; d[2] += e[2];
        if (t == 0) {
          float* gp = g_gate + (unsigned)((lb - NMAIN) * 512 + r * 128 + row);
          gp[0] = rcp(1.f + ex2(-1.4426950408889634f * d[0])); gp[8] = rcp(1.f + ex2(-1.4426950408889634f * d[2]));
        }
      }
      fence_release();
      __syncwarp();
      if (lane == 0) flag_add(FLAG(F_GATE));
      TS(1);
    }
    } else cluster_wait();
    get_slot();
    } while (redo && !pass++);
    FTS(3);
    const float dmask = (float)(2 * t - (row & 63));
    int c5 = 0;
    uint32_t pv[32];
#pragma unroll 1
    for (int rnd = 0; rnd < (spare ? 0 : 2); rnd++) {
      float O[64];
      FTM(rnd * 8);
      FTG(0);
      FTH(56, c.rnd == rnd);
      c.wait_full(2);
      FTM(rnd * 8 + 1);
      FTH(57, c.rnd == rnd);
#pragma unroll 1
      for (int tile = c.zero; tile < 2; tile++) {
        float acc[128];
        const bool single = tile == 0;
        {
          FTG(tile * 32 + 1);
          const uint32_t a = dk0 + 2 * DG, b = dm0 + 3 * DG;
          c.turn_begin();
          FTG(tile * 32 + 2);
          FTH(58, c.rnd == rnd);
          wg_fence();
          mma_ss_n256_init<1>(acc, a, b);
#pragma unroll
          for (int k = 1; k < 4; k++) mma_ss_n256<1>(acc, a + k * 2, b + k * 128);
          wg_commit();
          if (single) c.turn_end();
          FTG(tile * 32 + 3);
        }
#pragma unroll 1
        for (int kb = 1; kb < 8; kb++) {
          const int g0 = 2 + 3 * (kb & 3);
          const uint32_t a = dk0 + g0 * DG, b = dm0 + (g0 + 1) * DG;
          const bool second = (kb == 1 && !single) || kb == 7;
          FTG(tile * 32 + kb * 4);
          if (!second) { wg_wait<0>(); c.release(2 + 3 * ((kb - 1) & 3), 3); }
          FTG(tile * 32 + kb * 4 + 1);
          c.wait_full(g0);
          if (!second) c.turn_begin();
          FTG(tile * 32 + kb * 4 + 2);
          wg_fence();
#pragma unroll
          for (int k = 0; k < 4; k++) mma_ss_n256<1>(acc, a + k * 2, b + k * 128);
          wg_commit();
          if (kb != 6) c.turn_end();
          if (second) { wg_wait<1>(); c.release(2 + 3 * ((kb - 1) & 3), 3); }
          FTG(tile * 32 + kb * 4 + 3);
          FTH(58 + kb, c.rnd == rnd || kb > 3);
          if (tile == 1 && kb == 3) { c.wait_stage_free(); stsm_frag<0, 4>(pv, stg); }
          if (tile == 1 && kb == 4) { stsm_frag<4, 8>(pv, stg); c.staged(0); }
        }
        c.rnd = rnd;
        c.wait_stage_free();
        const bool nxt = c.try_full(2);
        wg_wait<0>();
        reg_fence(acc);
        c.release(11, 3);
        store_scaled(acc, SM_C, SM_C, stg, sb);
        c.staged(0);
        pack_frag<64>(acc, pv);
        FTG(32 + tile * 32);
        if (!nxt) mbar_wait(sb + SM_BAR + (B_FULL + 2) * 8, (c.pf >> 2) & 1);
        c.pf ^= 4;
      }
      TS(1 + rnd * 3);
      FTM(rnd * 8 + 2);
      {
        float qa[64];
        float (&qb)[64] = O;
        {
          FTG(65);
          const uint32_t a = dk0 + 2 * DG, b = dm0 + 4 * DG;
          c.turn_begin();
          FTG(66);
          wg_fence();
          mma_ss_n128_init<1>(qa, a, b);
          mma_ss_n128_init<1>(qb, a + dsw, b);
#pragma unroll
          for (int k = 1; k < 4; k++) {
            mma_ss_n128<1>(qa, a + k * 2, b + k * 128);
            mma_ss_n128<1>(qb, a + dsw + k * 2, b + k * 128);
          }
          wg_commit();
          FTG(67);
        }
#pragma unroll 1
        for (int kb = 1; kb < 16; kb++) {
          const int g0 = 2 + 3 * (kb & 3);
          const uint32_t a = dk0 + g0 * DG, b = dm0 + (g0 + 2) * DG;
          const bool second = kb == 1 || kb == 15;
          FTG(64 + kb * 4);
          if (!second) { wg_wait<0>(); c.release(2 + 3 * ((kb - 1) & 3), 3); }
          FTG(65 + kb * 4);
          c.wait_full(g0);
          if (!second) c.turn_begin();
          FTG(66 + kb * 4);
          FTH(kb - 14, kb < 14);
          wg_fence();
#pragma unroll
          for (int k = 0; k < 4; k++) {
            mma_ss_n128<1>(qa, a + k * 2, b + k * 128);
            mma_ss_n128<1>(qb, a + dsw + k * 2, b + k * 128);
          }
          wg_commit();
          if (kb != 14) c.turn_end();
          if (second) { wg_wait<1>(); c.release(2 + 3 * ((kb - 1) & 3), 3); }
          FTG(67 + kb * 4);
          FTH(2, kb < 15);
          if (kb == 13) FTB(0);
          if (kb == QFLUSH) { c.wait_stage_free(); stsm_frag<0, 4>(pv, stg); }
          if (kb == QFLUSH + 1) { stsm_frag<4, 8>(pv, stg); c.staged(0); }
        }
        c.wait_stage_free();
        mbar_wait(sb + SM_BAR + (B_EMPTY + 2) * 8, rnd ^ !redo);
        FTM(rnd * 8 + 3);
        FTH(3, 0);
        const bool k0 = c.try_full(4);
        wg_wait<0>();
        reg_fence(qa); reg_fence(qb);
        FTH(4, 0);
        if (c.wg) FTB(1);
        c.release(11, 3);
        pack_frag<0>(qa, pv);
        stsm_frag(pv, stg + 2 * GR);
        if (c.wg == 0) {
          pack_frag<0>(qb, pv);
          stsm_frag(pv, stg);
        }
        FTH(6, 0);
        fence_async_smem();
        FTH(7, 0);
        if (!c.wg) FTB(4);
        if (!k0) c.wait_full(4); else c.pf ^= 16;
      }
      TS(2 + rnd * 3);
      FTM(rnd * 8 + 4);
      FTH(5, 0);
      if (!c.wg) FTB(1);
      {
        const int nA = idx + 1;
        uint32_t (&P)[32] = pv;
        SoftState z;
        z.m0 = z.m1 = z.l0 = z.l1 = 0.f; z.shifted = c.zero;
#pragma unroll 1
        for (int seg = c.zero;; seg++) {
        if (c.wg == seg) attn_half(c, O, P, z, dk0, dkk, dv0, dmask, seg);
        if (seg) break;
        FTM(rnd * 8 + 5);
        int gk = c.wg ? 4 : 6, gv = c.wg ? 4 : 8;
        uint32_t dq = dk0 + (1 - c.wg < nA ? 2 * DG : 0), dk = dkk + gk * DG;
#pragma unroll 1
        for (int it = 1 - c.wg; it < 17 - c.wg; it++) {
          float S[64];
          FTA(it * 7 + 0); FTH((it < 3 ? 8 + it * 8 : it * 8 - 88) + 0, it >= 3 && it < 15);
          c.turn_begin();
          FTA(it * 7 + 2); FTH((it < 3 ? 8 + it * 8 : it * 8 - 88) + 1, it >= 3 && it < 15);
          wg_fence();
          issue_qk(S, dq, dk);
          wg_commit();
          FTB(4 + it);
          const uint32_t dv = dv0 + gv * DG;
          uint32_t relk = c.relb + gk * 8, relv = c.relb + gv * 8;
          gk = it == 6 ? 12 : gv == 12 ? 4 : gv + 2;
          gv = it == 16 ? gk : gk == 12 ? 4 : gk + 2;
          uint32_t fk = sb + SM_BAR + (B_FULL + gk) * 8, fv = sb + SM_BAR + (B_FULL + gv) * 8, park = (c.pf >> gk) & 1, parv = (c.pf >> gv) & 1;
          c.pf ^= (1u << gk) | (1u << gv);
          dq = dk0 + (it + 1 < nA ? 2 * DG : 0); dk = dkk + gk * DG;
          float lo0 = z.l0, lo1 = z.l1;
          const bool first = it == nA || it == 0;
          if (it == nA) {
            lo0 = rcp(quad_sum(lo0)); lo1 = rcp(quad_sum(lo1));
            z.m0 = z.m1 = z.l0 = z.l1 = 0.f; z.shifted = 0;
          }
          float s0, s1, d0 = z.m0, d1 = z.m1;
          int pre = z.shifted || (it & 15) == 0;
          float lim = first ? -1.f : SM_LIMIT;
          asm volatile("" : "+r"(relk), "+r"(relv), "+r"(fk), "+r"(fv), "+r"(park), "+r"(parv), "+r"(dq), "+r"(dk), "+r"(pre), "+f"(lim), "+f"(d0), "+f"(d1), "+f"(z.l0), "+f"(z.l1));
          if (it + c.wg > 1) {
            issue_pv<0>(O, P, dv, it != nA + 1 && it != 1, true);
            issue_pv<1>(O, P, dv, 1, true);
            c.turn_end();
          } else if (it) {
            issue_pv<0>(O, P, dv, 0, true);
            wg_commit(); wg_commit();
            c.turn_end();
          } else stage_q2(c, O, P, stg);
          FTA(it * 7 + 3); FTH((it < 3 ? 8 + it * 8 : it * 8 - 88) + 2, it >= 3 && it < 15);
          wg_wait<4>();
          reg_fence(S);
          FTA(it * 7 + 4); FTH((it < 3 ? 8 + it * 8 : it * 8 - 88) + 3, it >= 3 && it < 15);
          if (c.tid < 4) asm volatile("mbarrier.arrive.shared::cluster.b64 _, [%0];" ::"r"(relk) : "memory");
#pragma unroll 1
          for (int pass = 0;; pass++) {
            if (pre) {
              if ((it & 15) == 0) mask_diag(S, dmask);
              if (z.shifted) shift_scores(S, d0, d1);
            }
            float tr[ROT];
            exp_quarter<0, 3>(S, P, tr, s0, s1, sb);
            exp_quarter<1, 2>(S, P, tr, s0, s1, sb);
            exp_quarter<2, 1>(S, P, tr, s0, s1, sb);
            exp_quarter<3, 0>(S, P, tr, s0, s1, sb);
            reg_fence(O);
            if (c.tid < (pass || !it ? 0 : 4)) asm volatile("mbarrier.arrive.shared::cluster.b64 _, [%0];" ::"r"(relv) : "memory");
            const bool ok = mbar_test(fk, park) & mbar_test(fv, parv);
            if (!ok) lim = -1.f;
            FTA(it * 7 + 5); FTH((it < 3 ? 8 + it * 8 : it * 8 - 88) + 4, it >= 3 && it < 15);
            if (!__any_sync(0xffffffffu, !(s0 <= lim && s1 <= lim))) break;
            if (pass) break;
            if (it == nA) {
              store_scaled(O, lo0, lo1, stg + 2 * GR, sb);
              c.staged(1);
            }
            if (!it) fence_async_smem();
            if (!it) FTB(2);
            if (!ok) { mbar_wait(fk, park); mbar_wait(fv, parv); }
            if (!it) FTB(3);
            if (!soft_unsafe(s0, s1, first)) break;
            soft_fix(S, O, z, first, d0, d1);
            pre = 1;
          }
          z.l0 += s0; z.l1 += s1;
          FTA(it * 7 + 6); FTH((it < 3 ? 8 + it * 8 : it * 8 - 88) + 5, it >= 3 && it < 15);
        }
        FTM(rnd * 8 + 6);
        }
        FTH(48, 0);
        load_dd();
        c.turn_begin();
        FTH(49, 0);
        wg_fence();
        issue_pv<0>(O, P, dv0 + 12 * DG, 1, true);
        issue_pv<1>(O, P, dv0 + 12 * DG, 1, !c.wg);
        c.turn_end();
        z.l0 = rcp(quad_sum(z.l0)); z.l1 = rcp(quad_sum(z.l1));
        if (rnd) c5 = get_ticket();
        wg_wait<0>();
        reg_fence(O); reg_fence(P);
        FTH(50, 0);
        c.release(12, 2);
        store_scaled(O, z.l0, z.l1, stg, sb);
        c.staged(0);
        FTM(rnd * 8 + 7);
        FTH(51, 0);
      }
      TS(3 + rnd * 3);
    }
    conv_tasks(c, p, (cn + 1 - c.wg) >> 1, spare, cch + c.wg * cstep, 2 * cstep, c5, dd0, dkk, warp & 3, lane);
    if (c.wg == 1) c.pf ^= 0x14;
    if (c.wg == (cn & 1)) c.turn_begin();
    TS(7);
    if (!spare) {
      const int rt = 2 * grp + rank, ct = idx;
      float acc[64];
      int g0 = P3G + 2, pg = P3G;
      {
        FTO(0);
        c.wait_full(P3G);
        FTO(1);
        const uint32_t a = dk0 + P3G * DG, b = dm0 + (P3G + 1) * DG;
        wg_fence();
        mma_ss_n128_init<1>(acc, a, b);
#pragma unroll
        for (int k = 1; k < 4; k++) mma_ss_n128<1>(acc, a + k * 2, b + k * 128);
        wg_commit();
      }
#pragma unroll 1
      for (int kb = 1; kb < 64; kb++) {
        FTO(kb * 2);
        c.wait_full(g0);
        if (kb == STR && !c.wg) c.turn_begin();
        FTO(kb * 2 + 1);
        const uint32_t a = dk0 + g0 * DG, b = dm0 + (g0 + 1) * DG;
        wg_fence();
#pragma unroll
        for (int k = 0; k < 4; k++) mma_ss_n128<1>(acc, a + k * 2, b + k * 128);
        wg_commit();
        if (kb < STR) { wg_wait<1>(); c.release(pg, kb <= 59 ? 2 : 0); }
        if (kb == FDUMP_KB) FTDUMP();
        pg = g0;
        g0 = g0 == (kb < XK ? 12 : kb < YK ? 10 : 8) ? (kb == 3 ? 2 : 0) : g0 + 2;
      }
      if (c.wg) c.turn_end();
      cluster_arrive();
      c.wait_full(P3X);
      c.wait_full(P3Y);
      const float g0f = __uint_as_float(lds32(sb + SM_GATE + row * 4)), g1f = __uint_as_float(lds32(sb + SM_GATE + row * 4 + 32));
      const uint32_t gp0 = pack_bf16(g0f, g0f), gp1 = pack_bf16(g1f, g1f);
      const float h0 = 1.f - g0f, h1 = 1.f - g1f;
      const int w = warp & 3;
      const uint32_t xa = stg + P3X * GR;
      const uint32_t ya = sb + P3Y * GR + c.wg * 16384 + ((lane >> 4) * 8 + (lane & 7)) * 128 + (((2 * w + ((lane >> 3) & 1)) ^ (lane & 7)) << 4);
      uint32_t xy[32];
      auto prep = [&](int j0, int j1) {
#pragma unroll
        for (int jj = j0; jj < j1; jj++) {
          uint32_t x[4], y[4];
          asm volatile("ldmatrix.sync.aligned.m8n8.x4.shared.b16 {%0,%1,%2,%3}, [%4];" : "=r"(x[0]), "=r"(x[1]), "=r"(x[2]), "=r"(x[3]) : "r"((xa ^ ((jj & 3) << 5)) + (jj >> 2) * 16384) : "memory");
          asm volatile("ldmatrix.sync.aligned.m8n8.x4.trans.shared.b16 {%0,%1,%2,%3}, [%4];" : "=r"(y[0]), "=r"(y[1]), "=r"(y[2]), "=r"(y[3]) : "r"(ya + jj * 2048) : "memory");
#pragma unroll
          for (int i = 0; i < 4; i++) xy[4 * jj + i] = hmul2(x[i], y[i]);
        }
      };
      prep(0, 4);
      wg_wait<0>();
      reg_fence(acc);
      TS(8);
#pragma unroll
      for (int hf = 0; hf < 2; hf++) {
#pragma unroll
        for (int i = 16 * hf; i < 16 * hf + 16; i++) {
          const float h = (i & 1) ? h1 : h0;
          xy[i] = hfma2((i & 1) ? gp1 : gp0, xy[i], pack_bf16(acc[2 * i] * h, acc[2 * i + 1] * h));
        }
        if (hf) stsm_frag<4, 8>(xy, xa); else stsm_frag<0, 4>(xy, xa);
        fence_async_smem();
        __syncwarp();
        const int r0 = c.wg * 64 + w * 16;
        if (lane == 0) tma2d_store(&p.out, sb + (P3X + hf) * GR + r0 * 128, ct * 128 + hf * 64, rt * 128 + r0);
        if (!hf) prep(4, 8);
      }
      if (lane == 0) asm volatile("cp.async.bulk.commit_group;\ncp.async.bulk.wait_group.read 0;" ::: "memory");
    } else { FTDUMP(); cluster_arrive(); }
    if (lane == 0) mbar_arrive(sb + SM_BAR + B_DONE * 8);
    __syncwarp();
    TS(9);
    cluster_wait();
  }
}

typedef CUresult (*EncFn)(CUtensorMap*, CUtensorMapDataType, cuuint32_t, void*, const cuuint64_t*, const cuuint64_t*, const cuuint32_t*,
                          const cuuint32_t*, CUtensorMapInterleave, CUtensorMapSwizzle, CUtensorMapL2promotion, CUtensorMapFloatOOBfill);

void enc2d(EncFn enc, CUtensorMap* tm, const void* base, uint64_t cols, uint64_t rows, uint32_t bc, uint32_t br) {
  cuuint64_t dims[2] = {cols, rows}; cuuint64_t strides[1] = {cols * 2}; cuuint32_t box[2] = {bc, br}; cuuint32_t es[2] = {1, 1};
  enc(tm, CU_TENSOR_MAP_DATA_TYPE_BFLOAT16, 2, const_cast<void*>(base), dims, strides, box, es, CU_TENSOR_MAP_INTERLEAVE_NONE,
      CU_TENSOR_MAP_SWIZZLE_128B, CU_TENSOR_MAP_L2_PROMOTION_L2_256B, CU_TENSOR_MAP_FLOAT_OOB_FILL_NONE);
}
void enc3d(EncFn enc, CUtensorMap* tm, const void* base, uint64_t K, uint64_t N, uint32_t bk = 64, uint64_t pitch = 0) {
  cuuint64_t dims[3] = {64, K, N / 64}; cuuint64_t strides[2] = {pitch ? pitch : N * 2, 128}; cuuint32_t box[3] = {64, bk, 2}; cuuint32_t es[3] = {1, 1, 1};
  enc(tm, CU_TENSOR_MAP_DATA_TYPE_BFLOAT16, 3, const_cast<void*>(base), dims, strides, box, es, CU_TENSOR_MAP_INTERLEAVE_NONE,
      CU_TENSOR_MAP_SWIZZLE_128B, CU_TENSOR_MAP_L2_PROMOTION_L2_256B, CU_TENSOR_MAP_FLOAT_OOB_FILL_NONE);
}

}

extern "C" void kernel_launch(void* const* d_in, const int* in_sizes, int n_in, void* d_out, int out_size) {
  (void)in_sizes; (void)n_in; (void)out_size;
  typedef const __nv_bfloat16* BP;
  BP xq = (BP)d_in[0], ak = (BP)d_in[1], av = (BP)d_in[2], shk = (BP)d_in[3], ssk = (BP)d_in[4], ssd = (BP)d_in[5];
  BP ckv = (BP)d_in[7], wq = (BP)d_in[8], wuk = (BP)d_in[9], wuv = (BP)d_in[10], wo = (BP)d_in[11], gw = (BP)d_in[12];

  static EncFn enc = nullptr;
  if (!enc) {
    cudaDriverEntryPointQueryResult qr;
    cudaGetDriverEntryPoint("cuTensorMapEncodeTiled", (void**)&enc, cudaEnableDefault, &qr);
    cudaFuncSetAttribute(mega_kernel, cudaFuncAttributeMaxDynamicSharedMemorySize, SMEM_BYTES);
  }
  Params p;
  enc2d(enc, &p.x, xq, DM, SEQ, 64, 128);
  enc2d(enc, &p.c, ckv, DC, SEQ, 64, 128);
  enc3d(enc, &p.wq, wq, DM, NH * HD);
  enc3d(enc, &p.wuk, wuk, DC, NH * HD);
  enc3d(enc, &p.wuv, wuv, DC, NH * HD);
  enc2d(enc, &p.wo, wo, DM, NH * HD, 64, 64);
  enc3d(enc, &p.x3, xq, SEQ, DM, 128);
  enc2d(enc, &p.out, d_out, DM, SEQ, 64, 16);
  {
    void* wp = nullptr;
    cudaGetSymbolAddress(&wp, g_w);
    enc3d(enc, &p.y3, (uint8_t*)wp + WZ, DM, SEQ, 128, WSTRIDE);
    cuuint64_t dims[3] = {WSTRIDE / 2, DM / 2, 2}; cuuint64_t strides[2] = {2 * WSTRIDE, WSTRIDE}; cuuint32_t box[3] = {16, 32, 2}; cuuint32_t es[3] = {1, 1, 1};
    enc(&p.w, CU_TENSOR_MAP_DATA_TYPE_BFLOAT16, 3, wp, dims, strides, box, es, CU_TENSOR_MAP_INTERLEAVE_NONE,
        CU_TENSOR_MAP_SWIZZLE_32B, CU_TENSOR_MAP_L2_PROMOTION_NONE, CU_TENSOR_MAP_FLOAT_OOB_FILL_NONE);
  }
  p.zero = 0;
  cudaGetSymbolAddress((void**)&p.flags, g_flags);
  for (int i = 0; i < 128; i++) {
    const int tp = i % NSLOT;
    p.pref[i] = tp < 32 ? (tp & 7) * 8 + (tp >> 3) : tp < 60 ? (1 + (tp - 32) % 7) * 8 + 4 + (tp - 32) / 7 : tp < 62 ? tp + 4 : tp - 58;
  }
  p.gate_w = gw; p.ak = ak; p.av = av; p.shk = shk; p.ssk = ssk; p.ssd = ssd;

  mega_kernel<<<132, NTHREADS, SMEM_BYTES>>>(p);
}
```

```cpp
#include <cuda_runtime.h>
#include <cuda.h>
#include <cuda_bf16.h>
#include <stdint.h>

namespace {

constexpr int SEQ = 2048, DM = 1024, DC = 512, NH = 32, HD = 128;
constexpr int GR = 16384;
constexpr int NGR = 14;
constexpr int SM_BAR = NGR * GR;
constexpr int SM_GATE = SM_BAR + 512;
constexpr int SM_UST = SM_GATE + 512;
constexpr int SMEM_BYTES = SM_UST + 2048;
constexpr int NTHREADS = 384;
#define SM_LIMIT 1.0995116e12f
#define SM_LOW 9.094947e-13f
#define CNS 106
constexpr int CN_SPARE = CNS, NTICK = 256 - 2 * CN_SPARE;
constexpr int XK = 57, YK = 62;
constexpr int STR = 61;
constexpr int P3G = 6, P3X = 12, P3Y = 10;
constexpr int NMAIN = 128;

constexpr int B_FULL = 0, B_FREE = 14, B_SLOT = 16, B_DONE = 17, B_EMPTY = 18, B_EV = 32, B_TICK = 36;
constexpr int V_SLOT = 37, V_TICK = 38;

__device__ __align__(1024) uint8_t g_kv[2 * 16 * 16 * 32768];
__device__ __align__(1024) uint8_t g_cimg[16 * NH * 32768];
__device__ __align__(1024) float g_gate[SEQ];
constexpr int WZ = 256, WPL = WZ + 4096, WBYTES = 2 * WPL + 32, WSTRIDE = 2 * WPL + 128;
__device__ __align__(1024) uint8_t g_w[DM * WSTRIDE];
__device__ __align__(32) unsigned g_flags[96 * 8];
constexpr int F_KV = 0, F_CTX = 16, F_U = 48, F_AD = 56, F_Y = 64, F_GATE = 72, F_EXIT = 73, F_TICK = 74;
constexpr int NSLOT = 66;
#define FLAG(i) (&g_flags[(i) * 8])
#define CLAIMP(i) (p.flags + (i) * 8 + 1)

#define TS(slot)
#define TSW(slot)
#define FTX(i, off)
#define FTDUMP()

#define QFLUSH 3
#define PSL 200
#define US0 500
#define EROT 6
#define RST 2
#define UP0 4
#define UP1 11
#define X_DELAY 1100
#define X_D2 500
#define ROT 8
#define KVARR 1
#define KV_ROW(idx, t) (KVARR ? 8 * (t) + 2 * ((idx) & 3) : 2 * (idx))
#define KV_HEAD(idx, t) (KVARR ? (idx) >> 2 : (t))
#define FINE_MODE 0
#define FDUMP_KB 40
#define FINE_RND 1
#define FTA(i) do { if (FINE_MODE == 0) FTX(i, rnd ^ FINE_RND); } while (0)
#define FTB(i) do { if (FINE_MODE == 8) FTX(c.rnd * 32 + (i), 0); } while (0)
#define FTG(i) do { if (FINE_MODE == 1) FTX(i, rnd ^ FINE_RND); } while (0)
#define FTM(i) do { if (FINE_MODE == 4) FTX(i, 0); } while (0)
#define FTC(k) do { if (FINE_MODE == 5) FTX((i & 7) * 8 + (k), (i >> 3) ^ FINE_RND); } while (0)
#define FTH(i, off) do { if (FINE_MODE == 6) FTX(i, (c.rnd ^ FINE_RND) | (off)); } while (0)
#define FTS(i)
#define FTSD(i)
#define FTSW(i)
#define FTP(i)
#define FTO(i) do { if (FINE_MODE == 2) FTX(i, 0); } while (0)

__device__ __forceinline__ uint32_t smem_u32(const void* p) { return (uint32_t)__cvta_generic_to_shared(p); }
__device__ __forceinline__ void mbar_init(uint32_t bar, int cnt) { asm volatile("mbarrier.init.shared::cta.b64 [%0], %1;" ::"r"(bar), "r"(cnt) : "memory"); }
__device__ __forceinline__ void mbar_expect_tx(uint32_t bar, uint32_t bytes) { asm volatile("mbarrier.arrive.expect_tx.shared::cta.b64 _, [%0], %1;" ::"r"(bar), "r"(bytes) : "memory"); }
__device__ __forceinline__ void mbar_arrive(uint32_t bar) { asm volatile("mbarrier.arrive.shared::cta.b64 _, [%0];" ::"r"(bar) : "memory"); }
__device__ __forceinline__ void mbar_arrive_cluster(uint32_t bar, uint32_t cta) {
  asm volatile("{\n.reg .b32 r;\nmapa.shared::cluster.u32 r, %0, %1;\nmbarrier.arrive.shared::cluster.b64 _, [r];\n}\n" ::"r"(bar), "r"(cta) : "memory");
}
__device__ __forceinline__ void send_both(uint32_t bar, uint32_t off, uint32_t v) {
#pragma unroll
  for (int r = 0; r < 2; r++)
    asm volatile("{\n.reg .b32 a, b;\nmapa.shared::cluster.u32 a, %0, %1;\nadd.u32 b, a, %3;\nst.async.shared::cluster.mbarrier::complete_tx::bytes.u32 [b], %2, [a];\n}\n"
                 ::"r"(bar), "r"(r), "r"(v), "r"(off) : "memory");
}
__device__ __forceinline__ bool mbar_try(uint32_t bar, uint32_t parity) {
  uint32_t ok;
  asm volatile("{\n.reg .pred p;\nmbarrier.try_wait.parity.shared::cta.b64 p, [%1], %2, 20000;\nselp.u32 %0, 1, 0, p;\n}\n" : "=r"(ok) : "r"(bar), "r"(parity) : "memory");
  return ok;
}
__device__ __forceinline__ bool mbar_test(uint32_t bar, uint32_t parity) {
  uint32_t ok;
  asm volatile("{\n.reg .pred p;\nmbarrier.test_wait.parity.shared::cta.b64 p, [%1], %2;\nselp.u32 %0, 1, 0, p;\n}\n" : "=r"(ok) : "r"(bar), "r"(parity) : "memory");
  return ok;
}
__device__ __forceinline__ void mbar_wait(uint32_t bar, uint32_t parity) {
  asm volatile("{\n.reg .pred p;\nWAIT_LOOP:\nbar.warp.sync -1;\nmbarrier.try_wait.parity.shared::cta.b64 p, [%0], %1;\n@!p bra WAIT_LOOP;\n}\n" ::"r"(bar), "r"(parity) : "memory");
}
__device__ __forceinline__ void mbar_wait1(uint32_t bar, uint32_t parity) {
  asm volatile("{\n.reg .pred p;\nWAIT_LOOP:\nbar.warp.sync -1;\nmbarrier.try_wait.parity.shared::cta.b64 p, [%0], %1, 4000;\n@!p bra WAIT_LOOP;\n}\n" ::"r"(bar), "r"(parity) : "memory");
}
constexpr uint64_t EV_NORMAL = 0x1000000000000000ull, EV_FIRST = 0x12F0000000000000ull;
__device__ __forceinline__ uint32_t ldg_stream(const uint32_t* p) {
  uint32_t r; asm volatile("ld.global.nc.L1::no_allocate.L2::cache_hint.b32 %0, [%1], %2;" : "=r"(r) : "l"(p), "l"(EV_FIRST)); return r;
}
#define TMA_LD "cp.async.bulk.tensor."
#define TMA_MB ".shared::cluster.global.mbarrier::complete_tx::bytes"
__device__ __forceinline__ void tma2d(uint32_t dst, const CUtensorMap* tm, int c0, int c1, uint32_t bar) {
  asm volatile(TMA_LD "2d" TMA_MB " [%0], [%1, {%3, %4}], [%2];" ::"r"(dst), "l"(tm), "r"(bar), "r"(c0), "r"(c1) : "memory");
}
template <bool ONCE = false> __device__ __forceinline__ void tma2d_mc(uint32_t dst, const CUtensorMap* tm, int c0, int c1, uint32_t bar) {
  if (ONCE) asm volatile(TMA_LD "2d" TMA_MB ".multicast::cluster.L2::cache_hint [%0], [%1, {%3, %4}], [%2], %5, %6;"
                         ::"r"(dst), "l"(tm), "r"(bar), "r"(c0), "r"(c1), "h"((uint16_t)3), "l"(EV_FIRST) : "memory");
  else asm volatile(TMA_LD "2d" TMA_MB ".multicast::cluster [%0], [%1, {%3, %4}], [%2], %5;"
                    ::"r"(dst), "l"(tm), "r"(bar), "r"(c0), "r"(c1), "h"((uint16_t)3) : "memory");
}
__device__ __forceinline__ void tma2d_p(uint32_t dst, const CUtensorMap* tm, int c0, int c1, uint32_t bar, bool once) {
  asm volatile(TMA_LD "2d" TMA_MB ".L2::cache_hint [%0], [%1, {%3, %4}], [%2], %5;" ::"r"(dst), "l"(tm), "r"(bar), "r"(c0), "r"(c1), "l"(once ? EV_FIRST : EV_NORMAL) : "memory");
}
__device__ __forceinline__ void tma3d_mc_p(uint32_t dst, const CUtensorMap* tm, int c0, int c1, int c2, uint32_t bar, bool once) {
  asm volatile(TMA_LD "3d" TMA_MB ".multicast::cluster.L2::cache_hint [%0], [%1, {%3, %4, %5}], [%2], %6, %7;"
               ::"r"(dst), "l"(tm), "r"(bar), "r"(c0), "r"(c1), "r"(c2), "h"((uint16_t)3), "l"(once ? EV_FIRST : EV_NORMAL) : "memory");
}
template <bool ONCE = false> __device__ __forceinline__ void tma3d(uint32_t dst, const CUtensorMap* tm, int c0, int c1, int c2, uint32_t bar) {
  if (ONCE) asm volatile(TMA_LD "3d" TMA_MB ".L2::cache_hint [%0], [%1, {%3, %4, %5}], [%2], %6;" ::"r"(dst), "l"(tm), "r"(bar), "r"(c0), "r"(c1), "r"(c2), "l"(EV_FIRST) : "memory");
  else
  asm volatile(TMA_LD "3d" TMA_MB " [%0], [%1, {%3, %4, %5}], [%2];" ::"r"(dst), "l"(tm), "r"(bar), "r"(c0), "r"(c1), "r"(c2) : "memory");
}
__device__ __forceinline__ void tma3d_mc(uint32_t dst, const CUtensorMap* tm, int c0, int c1, int c2, uint32_t bar) {
  asm volatile(TMA_LD "3d" TMA_MB ".multicast::cluster [%0], [%1, {%3, %4, %5}], [%2], %6;"
               ::"r"(dst), "l"(tm), "r"(bar), "r"(c0), "r"(c1), "r"(c2), "h"((uint16_t)3) : "memory");
}
template <bool ONCE = false> __device__ __forceinline__ void bulk_g2s(uint32_t dst, const void* src, uint32_t bytes, uint32_t bar) {
  if (ONCE) asm volatile("cp.async.bulk" TMA_MB ".L2::cache_hint [%0], [%1], %2, [%3], %4;" ::"r"(dst), "l"(src), "r"(bytes), "r"(bar), "l"(EV_FIRST) : "memory");
  else asm volatile("cp.async.bulk" TMA_MB " [%0], [%1], %2, [%3];" ::"r"(dst), "l"(src), "r"(bytes), "r"(bar) : "memory");
}
__device__ __forceinline__ void tma2d_store(const CUtensorMap* tm, uint32_t src, int c0, int c1) {
  asm volatile("cp.async.bulk.tensor.2d.global.shared::cta.bulk_group [%0, {%2, %3}], [%1];" ::"l"(tm), "r"(src), "r"(c0), "r"(c1) : "memory");
}
__device__ __forceinline__ void prefetch_tm(const CUtensorMap* tm) { asm volatile("prefetch.tensormap [%0];" ::"l"(tm) : "memory"); }
__device__ __forceinline__ void wg_fence() { asm volatile("wgmma.fence.sync.aligned;" ::: "memory"); }
__device__ __forceinline__ void wg_commit() { asm volatile("wgmma.commit_group.sync.aligned;" ::: "memory"); }
template <int N> __device__ __forceinline__ void wg_wait() { asm volatile("wgmma.wait_group.sync.aligned %0;" ::"n"(N) : "memory"); }
__device__ __forceinline__ void bar_sync(int id, int n) { asm volatile("bar.sync %0, %1;" ::"r"(id), "r"(n) : "memory"); }
__device__ __forceinline__ void bar_arrive(int id, int n) { asm volatile("bar.arrive %0, %1;" ::"r"(id), "r"(n) : "memory"); }
__device__ __forceinline__ void fence_async_smem() { asm volatile("fence.proxy.async.shared::cta;" ::: "memory"); }
__device__ __forceinline__ void fence_async_all() { asm volatile("fence.proxy.async.global;" ::: "memory"); }
__device__ __forceinline__ uint32_t pack_bf16(float lo, float hi) { uint32_t r; asm("cvt.rn.bf16x2.f32 %0, %1, %2;" : "=r"(r) : "f"(hi), "f"(lo)); return r; }
__device__ __forceinline__ float ex2(float x) { float r; asm("ex2.approx.ftz.f32 %0, %1;" : "=f"(r) : "f"(x)); return r; }
__device__ __forceinline__ float rcp(float x) { float r; asm("rcp.approx.ftz.f32 %0, %1;" : "=f"(r) : "f"(x)); return r; }
__device__ __forceinline__ void flag_wait(const unsigned* f, unsigned target) {
  unsigned v;
  do { asm volatile("ld.acquire.gpu.global.u32 %0, [%1];" : "=r"(v) : "l"(f) : "memory"); } while (__any_sync(0xffffffffu, v < target));
}
__device__ __forceinline__ bool elect() {
  uint32_t r;
  asm volatile("{\n.reg .pred p;\nelect.sync _|p, -1;\nselp.u32 %0, 1, 0, p;\n}\n" : "=r"(r));
  return r;
}
__device__ __forceinline__ void fence_release() { asm volatile("fence.release.gpu;" ::: "memory"); }
__device__ __forceinline__ void flag_add(unsigned* f) { asm volatile("red.relaxed.gpu.global.inc.u32 [%0], 0x7fffffff;" ::"l"(f) : "memory"); }
__device__ __forceinline__ void cluster_arrive() { asm volatile("barrier.cluster.arrive.relaxed.aligned;" ::: "memory"); }
__device__ __forceinline__ void cluster_wait() { asm volatile("barrier.cluster.wait.aligned;" ::: "memory"); }
__device__ __forceinline__ uint32_t hmul2(uint32_t a, uint32_t b) { uint32_t r; asm("mul.rn.bf16x2 %0, %1, %2;" : "=r"(r) : "r"(a), "r"(b)); return r; }
__device__ __forceinline__ uint32_t hadd2(uint32_t a, uint32_t b) { uint32_t r; asm("add.rn.bf16x2 %0, %1, %2;" : "=r"(r) : "r"(a), "r"(b)); return r; }
__device__ __forceinline__ uint32_t hfma2(uint32_t a, uint32_t b, uint32_t c) { uint32_t r; asm("fma.rn.bf16x2 %0, %1, %2, %3;" : "=r"(r) : "r"(a), "r"(b), "r"(c)); return r; }
__device__ __forceinline__ uint32_t lds32(uint32_t a) { uint32_t r; asm volatile("ld.shared.b32 %0, [%1];" : "=r"(r) : "r"(a) : "memory"); return r; }
__device__ __forceinline__ uint4 lds128(uint32_t a) { uint4 r; asm volatile("ld.shared.v4.b32 {%0,%1,%2,%3}, [%4];" : "=r"(r.x), "=r"(r.y), "=r"(r.z), "=r"(r.w) : "r"(a) : "memory"); return r; }
__device__ __forceinline__ uint32_t desc_k(uint32_t addr) { return ((addr & 0x3FFFF) >> 4) | (1u << 16); }
template <int LBO> __device__ __forceinline__ uint32_t desc_mn(uint32_t addr) { return ((addr & 0x3FFFF) >> 4) | ((uint32_t)(LBO >> 4) << 16); }
#define DHI "0x40000040"

#define R8(d, o) "+f"(d[o]), "+f"(d[o + 1]), "+f"(d[o + 2]), "+f"(d[o + 3]), "+f"(d[o + 4]), "+f"(d[o + 5]), "+f"(d[o + 6]), "+f"(d[o + 7])
#define R32(d, o) R8(d, o), R8(d, o + 8), R8(d, o + 16), R8(d, o + 24)
#define R64(d, o) R32(d, o), R32(d, o + 32)
#define L64 "%0,%1,%2,%3,%4,%5,%6,%7,%8,%9,%10,%11,%12,%13,%14,%15,%16,%17,%18,%19,%20,%21,%22,%23,%24,%25,%26,%27,%28,%29,%30,%31," \
            "%32,%33,%34,%35,%36,%37,%38,%39,%40,%41,%42,%43,%44,%45,%46,%47,%48,%49,%50,%51,%52,%53,%54,%55,%56,%57,%58,%59,%60,%61,%62,%63"
#define L128 L64 ",%64,%65,%66,%67,%68,%69,%70,%71,%72,%73,%74,%75,%76,%77,%78,%79,%80,%81,%82,%83,%84,%85,%86,%87,%88,%89,%90,%91,%92,%93,%94,%95," \
            "%96,%97,%98,%99,%100,%101,%102,%103,%104,%105,%106,%107,%108,%109,%110,%111,%112,%113,%114,%115,%116,%117,%118,%119,%120,%121,%122,%123,%124,%125,%126,%127"

template <int TB> __device__ __forceinline__ void mma_ss_n128(float (&d)[64], uint32_t da, uint32_t db) {
  asm volatile("{\n.reg .b64 da, db;\nmov.b64 da, {%64, " DHI "};\nmov.b64 db, {%65, " DHI "};\n"
               "wgmma.mma_async.sync.aligned.m64n128k16.f32.bf16.bf16 {" L64 "}, da, db, 1, 1, 1, 0, %66;\n}\n"
               : R64(d, 0) : "r"(da), "r"(db), "n"(TB));
}
template <int TB> __device__ __forceinline__ void mma_rs_n128(float (&d)[64], uint32_t a0, uint32_t a1, uint32_t a2, uint32_t a3, uint32_t db, int sd) {
  asm volatile("{\n.reg .pred p;\n.reg .b64 db;\nsetp.ne.b32 p, %69, 0;\nmov.b64 db, {%68, " DHI "};\n"
               "wgmma.mma_async.sync.aligned.m64n128k16.f32.bf16.bf16 {" L64 "}, {%64,%65,%66,%67}, db, p, 1, 1, %70;\n}\n"
               : R64(d, 0) : "r"(a0), "r"(a1), "r"(a2), "r"(a3), "r"(db), "r"(sd), "n"(TB));
}
template <int TB> __device__ __forceinline__ void mma_ss_n256(float (&d)[128], uint32_t da, uint32_t db) {
  asm volatile("{\n.reg .b64 da, db;\nmov.b64 da, {%128, " DHI "};\nmov.b64 db, {%129, " DHI "};\n"
               "wgmma.mma_async.sync.aligned.m64n256k16.f32.bf16.bf16 {" L128 "}, da, db, 1, 1, 1, 0, %130;\n}\n"
               : R64(d, 0), R64(d, 64) : "r"(da), "r"(db), "n"(TB));
}
#define W8(d, o) "=f"(d[o]), "=f"(d[o + 1]), "=f"(d[o + 2]), "=f"(d[o + 3]), "=f"(d[o + 4]), "=f"(d[o + 5]), "=f"(d[o + 6]), "=f"(d[o + 7])
#define W32(d, o) W8(d, o), W8(d, o + 8), W8(d, o + 16), W8(d, o + 24)
#define W64(d, o) W32(d, o), W32(d, o + 32)
template <int TB> __device__ __forceinline__ void mma_ss_n128_init(float (&d)[64], uint32_t da, uint32_t db) {
  asm volatile("{\n.reg .b64 da, db;\nmov.b64 da, {%64, " DHI "};\nmov.b64 db, {%65, " DHI "};\n"
               "wgmma.mma_async.sync.aligned.m64n128k16.f32.bf16.bf16 {" L64 "}, da, db, 0, 1, 1, 0, %66;\n}\n"
               : W64(d, 0) : "r"(da), "r"(db), "n"(TB));
}
template <int TB> __device__ __forceinline__ void mma_rs_n128_init(float (&d)[64], uint32_t a0, uint32_t a1, uint32_t a2, uint32_t a3, uint32_t db) {
  asm volatile("{\n.reg .b64 db;\nmov.b64 db, {%68, " DHI "};\n"
               "wgmma.mma_async.sync.aligned.m64n128k16.f32.bf16.bf16 {" L64 "}, {%64,%65,%66,%67}, db, 0, 1, 1, %69;\n}\n"
               : W64(d, 0) : "r"(a0), "r"(a1), "r"(a2), "r"(a3), "r"(db), "n"(TB));
}
template <int TB> __device__ __forceinline__ void mma_ss_n256_init(float (&d)[128], uint32_t da, uint32_t db) {
  asm volatile("{\n.reg .b64 da, db;\nmov.b64 da, {%128, " DHI "};\nmov.b64 db, {%129, " DHI "};\n"
               "wgmma.mma_async.sync.aligned.m64n256k16.f32.bf16.bf16 {" L128 "}, da, db, 0, 1, 1, 0, %130;\n}\n"
               : W64(d, 0), W64(d, 64) : "r"(da), "r"(db), "n"(TB));
}
#define L32 "%0,%1,%2,%3,%4,%5,%6,%7,%8,%9,%10,%11,%12,%13,%14,%15,%16,%17,%18,%19,%20,%21,%22,%23,%24,%25,%26,%27,%28,%29,%30,%31"
template <bool INIT> __device__ __forceinline__ void mma_rs_n64(float (&d)[32], uint32_t a0, uint32_t a1, uint32_t a2, uint32_t a3, uint32_t db) {
  if (INIT) asm volatile("{\n.reg .b64 db;\nmov.b64 db, {%36, " DHI "};\n"
               "wgmma.mma_async.sync.aligned.m64n64k16.f32.bf16.bf16 {" L32 "}, {%32,%33,%34,%35}, db, 0, 1, 1, 0;\n}\n"
               : W32(d, 0) : "r"(a0), "r"(a1), "r"(a2), "r"(a3), "r"(db));
  else asm volatile("{\n.reg .b64 db;\nmov.b64 db, {%36, " DHI "};\n"
               "wgmma.mma_async.sync.aligned.m64n64k16.f32.bf16.bf16 {" L32 "}, {%32,%33,%34,%35}, db, 1, 1, 1, 0;\n}\n"
               : R32(d, 0) : "r"(a0), "r"(a1), "r"(a2), "r"(a3), "r"(db));
}
#define L16 "%0,%1,%2,%3,%4,%5,%6,%7,%8,%9,%10,%11,%12,%13,%14,%15"
template <int O, bool INIT> __device__ __forceinline__ void mma_rs_n32(float (&d)[128], uint32_t a0, uint32_t a1, uint32_t a2, uint32_t a3, uint32_t db) {
  if (INIT) asm volatile("{\n.reg .b64 db;\nmov.b64 db, {%20, 0x00000008};\n"
               "wgmma.mma_async.sync.aligned.m64n32k16.f32.bf16.bf16 {" L16 "}, {%16,%17,%18,%19}, db, 0, 1, 1, 0;\n}\n"
               : W8(d, O), W8(d, O + 8) : "r"(a0), "r"(a1), "r"(a2), "r"(a3), "r"(db));
  else asm volatile("{\n.reg .b64 db;\nmov.b64 db, {%20, 0x00000008};\n"
               "wgmma.mma_async.sync.aligned.m64n32k16.f32.bf16.bf16 {" L16 "}, {%16,%17,%18,%19}, db, 1, 1, 1, 0;\n}\n"
               : R8(d, O), R8(d, O + 8) : "r"(a0), "r"(a1), "r"(a2), "r"(a3), "r"(db));
}
template <int S, int J> __device__ __forceinline__ void conv_step(float (&d)[128], const uint32_t (&a)[64], uint32_t db) {
  if constexpr (J >= 0 && J >= (S >> 1)) {
    mma_rs_n32<16 * J, S == 0>(d, a[4 * S], a[4 * S + 1], a[4 * S + 2], a[4 * S + 3], db + (uint32_t)((2 * J - S) * 16));
    conv_step<S, J - 1>(d, a, db);
  }
}
__device__ __forceinline__ void mma_ss_n8(float (&d)[4], uint32_t da, uint32_t db) {
  asm volatile("{\n.reg .b64 da, db;\nmov.b64 da, {%4, " DHI "};\nmov.b64 db, {%5, 0x00000008};\n"
               "wgmma.mma_async.sync.aligned.m64n8k16.f32.bf16.bf16 {%0,%1,%2,%3}, da, db, 1, 1, 1, 0, 0;\n}\n"
               : "+f"(d[0]), "+f"(d[1]), "+f"(d[2]), "+f"(d[3]) : "r"(da), "r"(db));
}
template <int N> __device__ __forceinline__ void reg_fence(float (&d)[N]) {
#pragma unroll
  for (int i = 0; i < N; i++) asm volatile("" : "+f"(d[i])::"memory");
}
template <int N> __device__ __forceinline__ void reg_fence(uint32_t (&d)[N]) {
#pragma unroll
  for (int i = 0; i < N; i++) asm volatile("" : "+r"(d[i])::"memory");
}

struct __align__(64) Params {
  unsigned* flags;
  int zero;
  uint8_t pref[128];
  const __nv_bfloat16 *gate_w, *ak, *av, *shk, *ssk, *ssd;
  CUtensorMap x, c, wq, wuk, wuv, wo, x3, y3, out, w;
};

template <int O, int N, int M> __device__ __forceinline__ void pack_frag(const float (&acc)[N], uint32_t (&pk)[M]) {
#pragma unroll
  for (int i = 0; i < 32; i++) pk[i] = pack_bf16(acc[O + 2 * i], acc[O + 2 * i + 1]);
}
template <int J0 = 0, int J1 = 8, int M> __device__ __forceinline__ void stsm_frag(const uint32_t (&pk)[M], uint32_t a) {
#pragma unroll
  for (int jj = J0; jj < J1; jj++)
    asm volatile("stmatrix.sync.aligned.m8n8.x4.shared.b16 [%0], {%1,%2,%3,%4};" ::"r"((a ^ ((jj & 3) << 5)) + (jj >> 2) * 16384),
                 "r"(pk[4 * jj]), "r"(pk[4 * jj + 1]), "r"(pk[4 * jj + 2]), "r"(pk[4 * jj + 3]) : "memory");
}

template <int N> __device__ __forceinline__ void store_scaled(const float (&acc)[N], float s0, float s1, uint32_t a, uint32_t never_zero) {
  float t[8];
#pragma unroll
  for (int jj = 0; jj < 8; jj++) {
    float v = acc[8 * jj] * s0;
    if (jj >= RST) {
      v = t[jj - RST];
      asm("{\n.reg .pred p;\nsetp.ne.u32 p, %3, 0;\n@p mul.f32 %0, %1, %2;\n}\n" : "+f"(v) : "f"(acc[8 * jj]), "f"(s0), "r"(never_zero));
    }
    const uint32_t q = pack_bf16(v, acc[8 * jj + 1] * s0);
    t[jj] = __uint_as_float(q);
    asm volatile("stmatrix.sync.aligned.m8n8.x4.shared.b16 [%0], {%1,%2,%3,%4};" ::"r"((a ^ ((jj & 3) << 5)) + (jj >> 2) * 16384), "r"(q),
                 "r"(pack_bf16(acc[8 * jj + 2] * s1, acc[8 * jj + 3] * s1)), "r"(pack_bf16(acc[8 * jj + 4] * s0, acc[8 * jj + 5] * s0)),
                 "r"(pack_bf16(acc[8 * jj + 6] * s1, acc[8 * jj + 7] * s1)) : "memory");
  }
}

struct Cons {
  uint32_t sb;
  uint32_t pf;
  int wg, tid;
  __device__ __forceinline__ void wait_full(int g) { mbar_wait(sb + SM_BAR + (B_FULL + g) * 8, (pf >> g) & 1); pf ^= 1u << g; }
  uint32_t relb;
  __device__ __forceinline__ void release(int g, int n) {
    if (tid < 2 * n) asm volatile("mbarrier.arrive.shared::cluster.b64 _, [%0];" ::"r"(relb + g * 8) : "memory");
  }
  __device__ __forceinline__ void turn_begin() { bar_sync(1 + wg, 256); }
  __device__ __forceinline__ void turn_end() { bar_arrive(2 - wg, 256); }
  __device__ __forceinline__ void staged(int e) { __syncwarp(); if ((tid & 31) == 0) mbar_arrive(sb + SM_BAR + (B_EV + 2 * e + wg) * 8); }
  int zero;
  int rnd;
  uint32_t pfree;
  __device__ __forceinline__ void wait_stage_free() { mbar_wait(sb + SM_BAR + (B_FREE + wg) * 8, pfree); pfree ^= 1; }
  __device__ __forceinline__ bool try_full(int g) { return mbar_test(sb + SM_BAR + (B_FULL + g) * 8, (pf >> g) & 1); }
};

constexpr float SM_C = 0.08838834764831845f * 1.4426950408889634f;
struct SoftState { float m0, m1, l0, l1; int shifted; };
__device__ __forceinline__ void ex2_rot(float& t, float s, uint32_t never_zero) {
  asm("{\n.reg .pred p;\nsetp.ne.u32 p, %2, 0;\n@p ex2.approx.ftz.f32 %0, %1;\n}\n" : "+f"(t) : "f"(s), "r"(never_zero));
}
__device__ __forceinline__ void pin(float a, uint32_t never_zero) {
  asm volatile("{\n.reg .pred p;\nsetp.eq.u32 p, %1, 0;\n@p st.shared.f32 [%1], %0;\n}\n" ::"f"(a), "r"(never_zero) : "memory");
}
template <int O, int N> __device__ __forceinline__ void reg_fence_part(uint32_t (&d)[32]) {
#pragma unroll
  for (int i = O; i < O + N; i++) asm volatile("" : "+r"(d[i])::"memory");
}
template <int Q, int W, int N> __device__ __forceinline__ void exp_quarter(const float (&S)[N], uint32_t (&P)[32], float (&t)[ROT], float& s0, float& s1, uint32_t nz) {
#pragma unroll
  for (int i = 8 * Q; i < 8 * Q + 8; i++) {
    float& a = t[(2 * i) % ROT];
    float& b = t[(2 * i + 1) % ROT];
    if (2 * i < ROT) { a = ex2(S[2 * i]); b = ex2(S[2 * i + 1]); }
    else { ex2_rot(a, S[2 * i], nz); ex2_rot(b, S[2 * i + 1], nz); }
    if (i < 2) { if (i) s1 = a + b; else s0 = a + b; }
    else if (i & 1) { s1 += a; s1 += b; } else { s0 += a; s0 += b; }
    if (i == 8 * Q) { pin(Q ? s1 : s0, nz); wg_wait<W>(); reg_fence_part<8 * Q, 8>(P); }
    P[i] = pack_bf16(a, b);
  }
}
template <int N> __device__ __forceinline__ void shift_scores(float (&S)[N], float d0, float d1) {
#pragma unroll
  for (int i = 0; i < N; i++) S[i] -= (i & 2) ? d1 : d0;
}
__device__ __forceinline__ bool soft_high(float s0, float s1, float lim = SM_LIMIT) { return s0 > lim || s1 > lim; }
__device__ __forceinline__ bool soft_unsafe(float s0, float s1, bool first) {
  uint32_t b0 = __ballot_sync(0xffffffffu, s0 >= SM_LOW), b1 = __ballot_sync(0xffffffffu, s1 >= SM_LOW);
  b0 |= b0 >> 1; b0 |= b0 >> 2; b1 |= b1 >> 1; b1 |= b1 >> 2;
  return __any_sync(0xffffffffu, soft_high(s0, s1)) || (first && (b0 & b1 & 0x11111111u) != 0x11111111u);
}
template <int N> __device__ __forceinline__ void soft_fix(const float (&S)[N], float (&O)[64], SoftState& z, bool first, float& d0, float& d1) {
  d0 = d1 = first ? -INFINITY : 0.f;
#pragma unroll
  for (int j = 0; j < N / 4; j++) { d0 = fmaxf(d0, fmaxf(S[4 * j], S[4 * j + 1])); d1 = fmaxf(d1, fmaxf(S[4 * j + 2], S[4 * j + 3])); }
  d0 = fmaxf(d0, __shfl_xor_sync(0xffffffffu, d0, 1)); d1 = fmaxf(d1, __shfl_xor_sync(0xffffffffu, d1, 1));
  d0 = fmaxf(d0, __shfl_xor_sync(0xffffffffu, d0, 2)); d1 = fmaxf(d1, __shfl_xor_sync(0xffffffffu, d1, 2));
  const float sc0 = ex2(-fmaxf(d0, 0.f)), sc1 = ex2(-fmaxf(d1, 0.f));
  z.m0 += d0; z.m1 += d1; z.l0 *= sc0; z.l1 *= sc1; z.shifted = 1;
#pragma unroll
  for (int j = 0; j < 16; j++) { O[4 * j] *= sc0; O[4 * j + 1] *= sc0; O[4 * j + 2] *= sc1; O[4 * j + 3] *= sc1; }
}
template <int N> __device__ __forceinline__ void mask_diag(float (&S)[N], float nd) {
  asm volatile("" : "+f"(nd));
#pragma unroll
  for (int i = 0; i < 32; i++) {
    const float beyond = __saturatef(nd + (float)(8 * (i >> 2) + (i & 1) - 4 * (i & 2)));
    S[N - 32 + i] = fmaf(beyond, -3.0e38f, S[N - 32 + i]);
  }
}
__device__ __forceinline__ float quad_sum(float v) {
  v += __shfl_xor_sync(0xffffffffu, v, 1);
  v += __shfl_xor_sync(0xffffffffu, v, 2);
  return v;
}
__device__ __forceinline__ void issue_qk(float (&S)[64], const uint32_t (&Q)[32], uint32_t dk) {
  mma_rs_n128_init<0>(S, Q[0], Q[1], Q[2], Q[3], dk);
#pragma unroll
  for (int s = 1; s < 8; s++) mma_rs_n128<0>(S, Q[4 * s], Q[4 * s + 1], Q[4 * s + 2], Q[4 * s + 3], dk + (s >> 2) * 1024 + (s & 3) * 2, 1);
}
__device__ __forceinline__ void issue_qk(float (&S)[32], const uint32_t (&Q)[32], uint32_t dk) {
  mma_rs_n64<true>(S, Q[0], Q[1], Q[2], Q[3], dk);
#pragma unroll
  for (int s = 1; s < 8; s++) mma_rs_n64<false>(S, Q[4 * s], Q[4 * s + 1], Q[4 * s + 2], Q[4 * s + 3], dk + (s >> 2) * 1024 + (s & 3) * 2);
}
__device__ __forceinline__ void load_q(uint32_t (&Q)[32], uint32_t a) {
  __syncwarp();
#pragma unroll
  for (int jj = 0; jj < 8; jj++)
    asm volatile("ldmatrix.sync.aligned.m8n8.x4.shared.b16 {%0,%1,%2,%3}, [%4];" : "=r"(Q[4 * jj]), "=r"(Q[4 * jj + 1]), "=r"(Q[4 * jj + 2]), "=r"(Q[4 * jj + 3])
                 : "r"((a ^ ((jj & 3) << 5)) + (jj >> 2) * 16384) : "memory");
}
template <int H> __device__ __forceinline__ void issue_pv(float (&O)[64], const uint32_t (&P)[32], uint32_t dv, int acc, bool on) {
  if (on) {
#pragma unroll
    for (int s = 4 * H; s < 4 * H + 4; s++) {
      mma_rs_n128<1>(O, P[4 * s], P[4 * s + 1], P[4 * s + 2], P[4 * s + 3], dv + s * 128, s != 0 ? 1 : acc);
      if (s & 1) wg_commit();
    }
  } else { wg_commit(); wg_commit(); }
}
constexpr uint32_t DG = GR >> 4;
__device__ __forceinline__ void stage_q2(Cons& c, const float (&O)[64], uint32_t (&P)[32], uint32_t stg) {
  wg_commit(); wg_commit(); wg_commit(); wg_commit();
  c.turn_end();
  pack_frag<0>(O, P);
  stsm_frag(P, stg);
}
__device__ __forceinline__ void attn_half(Cons& c, float (&O)[64], uint32_t (&P)[32], uint32_t (&Q)[32], bool nextq, uint32_t stg, SoftState& z, uint32_t dkk, uint32_t dv0, float dmask, int last) {
  float S[32];
  FTH(8 + last * 32, 0);
  c.turn_begin();
  FTH(9 + last * 32, 0);
  wg_fence();
  issue_qk(S, Q, dkk + (last ? 8 : 2) * DG);
  wg_commit();
  issue_pv<0>(O, P, dv0 + 10 * DG, 1, last);
  issue_pv<1>(O, P, dv0 + 10 * DG, 1, last);
  c.turn_end();
  c.wait_full(last ? 12 : 4);
  FTH(10 + last * 32, 0);
  wg_wait<4>();
  reg_fence(S);
  FTH(11 + last * 32, 0);
  c.release(last ? 8 : 2, 2);
  reg_fence(Q);
  if (nextq) load_q(Q, stg);
  if (last) bar_sync(6, 256);
  mask_diag(S, dmask);
  float s0, s1, d0 = z.m0, d1 = z.m1;
#pragma unroll 1
  for (int pass = 0;; pass++) {
    if (z.shifted) shift_scores(S, d0, d1);
    float tr[ROT];
    exp_quarter<0, 3>(S, P, tr, s0, s1, c.sb);
    exp_quarter<1, 2>(S, P, tr, s0, s1, c.sb);
    pin(s1, c.sb); wg_wait<0>(); reg_fence_part<16, 16>(P); reg_fence(O);
    if (!soft_unsafe(s0, s1, !last) || pass) break;
    soft_fix(S, O, z, !last, d0, d1);
  }
  FTH(12 + last * 32, 0);
  if (!last) FTB(2);
  z.l0 += s0; z.l1 += s1;
  c.release(10, last ? 2 : 0);
  if (!last) c.wait_full(6);
  FTH(13 + last * 32, 0);
  if (!last) FTB(3);
}

template <int V> struct IC { static constexpr int value = V; };
__device__ __forceinline__ int conv_next(int g, bool spare) { return g >= NGR - 2 ? g - (NGR - 4) : !spare && g == 4 ? 1 : g + 2; }
__device__ __forceinline__ void conv_final(uint32_t rb, uint32_t yb, bool on) {
  const uint4 q0 = lds128(rb), q1 = lds128(rb + 4096), q2 = lds128(rb + 8192), q3 = lds128(rb + 12288);
  auto fin = [&](uint32_t x0, uint32_t x1, uint32_t x2, uint32_t x3) { return hadd2(hadd2(x0, x1), hadd2(x2, x3)); };
  asm volatile("{\n.reg .pred p;\nsetp.ne.b32 p, %5, 0;\n@p st.shared.v4.b32 [%0], {%1,%2,%3,%4};\n}\n" ::"r"(yb), "r"(fin(q0.x, q1.x, q2.x, q3.x)),
               "r"(fin(q0.y, q1.y, q2.y, q3.y)), "r"(fin(q0.z, q1.z, q2.z, q3.z)), "r"(fin(q0.w, q1.w, q2.w, q3.w)), "r"((int)on) : "memory");
}
__device__ __forceinline__ void conv_tasks(Cons& c, const Params& p, int ntask, bool spare, int ch, int chstep, int c5, uint32_t dd, uint32_t dkk, int w, int lane) {
  const uint32_t sb = c.sb;
  int g = 2 + c.wg;
  uint32_t rb = sb + g * GR;
  const uint32_t yb = sb + c.wg * 8192 + c.tid * 16;
  const int gt = 8 * w + (lane >> 2) + (lane & 3);
  uint32_t a[64], hb;
  auto lda = [&](int s) {
    a[4 * s] = lds32(hb + s * 256); a[4 * s + 1] = lds32(hb + s * 256 + 128);
    a[4 * s + 2] = lds32(hb + s * 256 + 16); a[4 * s + 3] = lds32(hb + s * 256 + 144);
  };
  auto first_a = [&]() {
    hb = sb + g * GR + WBYTES - 28 + gt * 4;
    lda(0); lda(15);
  };
  c.wait_full(g);
  first_a();
#pragma unroll 1
  for (int i = 0; i < ntask; i++) {
    const uint32_t base = sb + g * GR;
    FTC(0);
    lda(1); lda(14);
    a[0] = hadd2(a[0], gt == 7 ? dd : 0u); a[2] = hadd2(a[2], gt == 3 ? dd : 0u);
    float acc[128];
    const uint32_t db = dkk + ((WPL / 16 - 1) << 16) + g * DG + WZ / 16;
    FTC(2);
    c.turn_begin();
    FTC(3);
    auto pair = [&](auto kc) {
      constexpr int k = decltype(kc)::value;
      if (k < 7) wg_fence();
      if (k == 6) c.turn_end();
      conv_step<k, 7>(acc, a, db);
      conv_step<15 - k, 7>(acc, a, db);
      if (k < 6) { lda(k + 2); lda(13 - k); }
      if (k == 0) conv_final(rb, yb, i > 0);
      if (k == 1) {
        conv_final(rb + 2048, yb + 2048, i > 0);
        __syncwarp();
        if (lane == 0 && i > 0) mbar_arrive(sb + SM_BAR + (B_EV + c.wg) * 8);
      }
      if (k == 6) dd = __bfloat16_as_ushort(p.ssd[(ch + chstep + (i == 1 ? c5 : 0)) & (DM - 1)]);
    };
    pair(IC<0>()); pair(IC<1>()); pair(IC<2>()); pair(IC<3>()); pair(IC<4>()); pair(IC<5>()); pair(IC<6>()); pair(IC<7>());
    wg_commit();
    FTC(4);
    g = conv_next(g, spare);
    ch += chstep;
    rb = base + c.tid * 16;
    if (i + 1 < ntask) c.wait_full(g);
    const bool fr = mbar_test(sb + SM_BAR + (B_FREE + c.wg) * 8, c.pfree);
    wg_wait<0>();
    reg_fence(acc);
    reg_fence(a);
    bar_sync(3 + c.wg, 128);
    FTC(5);
    first_a();
    const int tw = (lane & 3) + w;
    const uint32_t xb = base + w * 4096 + tw * 32 + (lane >> 2) * 4;
    [[maybe_unused]] float t0[EROT + 1];
#pragma unroll
    for (int j = 0; j < 32; j++) {
      uint32_t ad = xb + j * 128;
      float v0 = acc[4 * j], v1 = acc[4 * j + 1];
      if (EROT && j > EROT) {
        v0 = t0[j % (EROT + 1)];
        asm("{\n.reg .pred p;\nsetp.ne.u32 p, %3, 0;\n@p add.f32 %0, %1, %2;\n}\n" : "+f"(v0) : "f"(acc[4 * j]), "f"(acc[j > 0 ? 4 * j - 2 : 0]), "r"(sb));
      } else if (j > 0) v0 += acc[j > 0 ? 4 * j - 2 : 0];
      if (j > 0) v1 += acc[j > 0 ? 4 * j - 1 : 0];
      uint32_t v = pack_bf16(v0, v1);
      t0[j % (EROT + 1)] = __uint_as_float(v);
      if (j == 31 && tw >= 4) { v = 0; ad -= 4096; }
      asm volatile("st.shared.b32 [%0], %1;" ::"r"(ad), "r"(v) : "memory");
    }
    if (!fr) c.wait_stage_free(); else c.pfree ^= 1;
    FTC(6);
  }
  bar_sync(3 + c.wg, 128);
  conv_final(rb, yb, true);
  conv_final(rb + 2048, yb + 2048, true);
  c.staged(0);
}

__global__ void __cluster_dims__(2, 1, 1) __launch_bounds__(NTHREADS, 1) mega_kernel(const __grid_constant__ Params p) {
  extern __shared__ __align__(1024) uint8_t smem_raw[];
  FTS(0);
  const uint32_t sb = smem_u32(smem_raw);
  if (threadIdx.x - 64 < 32) { prefetch_tm(&p.c); prefetch_tm(&p.wuk + (blockIdx.x & 1)); }
  const int wgi = __shfl_sync(0xffffffffu, threadIdx.x >> 7, 0);
  const int warp = __shfl_sync(0xffffffffu, threadIdx.x >> 5, 0);
  const uint32_t rank = blockIdx.x & 1;
  int slot;
  {
    uint32_t smid; asm volatile("mov.u32 %0, %smid;" : "=r"(smid));
    slot = p.pref[((smid >> 1) + (threadIdx.x & (smid >> 16))) & 127];
  }
  if (warp >= 3) {
    if (elect()) {
#pragma unroll
      for (int k = 0; k < 4; k++) mbar_init(sb + SM_BAR + ((warp - 3) * 4 + k) * 8, k == 1 && warp == 7 ? 11 : warp < (k ? 7 : 8) ? 1 : 4);
      if (warp == 7) { mbar_init(sb + SM_BAR + B_TICK * 8, 1); mbar_expect_tx(sb + SM_BAR + B_SLOT * 8, 8); mbar_expect_tx(sb + SM_BAR + B_TICK * 8, 4); }
      asm volatile("fence.mbarrier_init.release.cluster;" ::: "memory");
    }
    __syncwarp();
  }
  FTS(1);
  cluster_arrive();
  slot = __shfl_sync(0xffffffffu, slot, 0);
  const int pref = slot;
  if (warp < 4) {
    asm volatile("setmaxnreg.dec.sync.aligned.u32 40;");
    if (warp == 1 + 4 * rank) {
      unsigned taken = threadIdx.x == 32;
#pragma unroll 1
      for (int n = 0; n < NSLOT; n++) {
        asm volatile("{\n.reg .pred p;\nsetp.ne.b32 p, %0, 0;\n@p atom.relaxed.gpu.global.exch.b32 %0, [%1], 1;\n}\n" : "+r"(taken) : "l"(CLAIMP(slot)) : "memory");
        if (!__any_sync(0xffffffffu, taken)) break;
        slot = slot == NSLOT - 1 ? 0 : slot + 1;
      }
    }
    cluster_wait();
    if (threadIdx.x == 32) {
      send_both(sb + SM_BAR + B_SLOT * 8, (V_SLOT - B_SLOT) * 8 + rank * 4, slot | pref << 8);
    }
    if (warp == 2) {
#pragma unroll 1
      for (int kk = 0; kk < 4; kk++) {
        const int g0 = 2 + 3 * kk;
        const uint32_t fb = sb + SM_BAR + (B_FULL + g0) * 8;
        if (elect()) {
          FTSW(kk);
          mbar_expect_tx(fb, 3 * GR);
          tma2d(sb + g0 * GR, &p.c, kk * 64, (KV_ROW(pref & 7, 0) + rank) * 128, fb);
          tma3d_mc(sb + (g0 + 1 + rank) * GR, rank ? &p.wuv : &p.wuk, 0, kk * 64, ((pref & 56) >> 1) + 2 * KV_HEAD(pref & 7, 0), fb);
        }
        if (kk < 3) {
          uint32_t c0, c1;
          asm volatile("mov.u32 %0, %clock;" : "=r"(c0));
          do asm volatile("mov.u32 %0, %clock;" : "=r"(c1)); while (c1 - c0 < (kk ? X_D2 : X_DELAY));
        }
      }
      FTSW(4);
      prefetch_tm(&p.x); prefetch_tm(&p.wq);
    }
  }
  int grp, idx, lb;
  int cn, cch, cstep;
  bool spare, redo;
  auto get_slot = [&]() {
    mbar_wait(sb + SM_BAR + B_SLOT * 8, 0);
    const uint32_t sv0 = __shfl_sync(0xffffffffu, lds32(sb + SM_BAR + V_SLOT * 8), 0), sv1 = __shfl_sync(0xffffffffu, lds32(sb + SM_BAR + V_SLOT * 8 + 4), 0);
    grp = (sv0 & 255) >> 3; idx = sv0 & 7; lb = (sv0 & 255) * 2 + rank;
    spare = grp == 8; redo = spare || sv0 != sv1;
    cn = CN_SPARE; cch = spare ? lb - NMAIN : 4 * CN_SPARE + 4 * lb; cstep = spare ? 4 : 1;
    if (FINE_MODE != 7) TS(0);
  };
  auto get_ticket = [&]() {
    mbar_wait(sb + SM_BAR + B_TICK * 8, 0);
    const int tk = __shfl_sync(0xffffffffu, lds32(sb + SM_BAR + V_TICK * 8), 0);
    cn = tk < NTICK ? 5 : 4;
    return 4 * NMAIN - 4 * lb - 4 + 2 * tk + rank;
  };

  if (wgi == 0) {
    asm volatile("setmaxnreg.dec.sync.aligned.u32 40;");
    const int lane = threadIdx.x & 31;
    cluster_arrive();
    get_slot();
    uint32_t pe = 0;
    auto acquire = [&](int g, int n, uint32_t m) {
      int i = g;
#pragma unroll 1
      do mbar_wait1(sb + SM_BAR + (B_EMPTY + i) * 8, (pe >> i) & 1); while (++i < g + n);
      pe ^= m << g;
    };
    if (warp == 3) {
      if (!spare) {
        const int s0 = lb * 16;
#pragma unroll 1
        for (int cg = 0; cg < 16; cg++) {
          if (cg == UP0 || cg == UP1) {
#pragma unroll 1
            for (int n = 0; n < 20 && !__any_sync(0xffffffffu, mbar_try(sb + SM_BAR + B_SLOT * 8, cg == UP0)); n++);
          } else if (cg < UP0) __nanosleep(US0);
          if (cg == UP1 && lane == rank * 32) send_both(sb + SM_BAR + B_TICK * 8, (V_TICK - B_TICK) * 8, atomicInc(FLAG(F_TICK), 0x7fffffffu));
          const int ch = cg * 64 + 2 * lane;
          const uint32_t* kp = reinterpret_cast<const uint32_t*>(p.ak + (size_t)s0 * DM + ch);
          const uint32_t* vp = reinterpret_cast<const uint32_t*>(p.av + (size_t)s0 * DM + ch);
          const uint4 sw = __ldg(reinterpret_cast<const uint4*>(p.shk + ch * 4));
          uint32_t k3 = 0, k2 = 0, k1 = 0, k0 = 0, up = 0;
          if (lb > 0) { k3 = ldg_stream(kp - 4 * 512); k2 = ldg_stream(kp - 3 * 512); k1 = ldg_stream(kp - 2 * 512); k0 = ldg_stream(kp - 512); up = ldg_stream(vp - 512); }
          const uint32_t w0 = __byte_perm(sw.x, sw.z, 0x5410), w1 = __byte_perm(sw.x, sw.z, 0x7632);
          const uint32_t w2 = __byte_perm(sw.y, sw.w, 0x5410), w3 = __byte_perm(sw.y, sw.w, 0x7632);
          up = hmul2(hfma2(k0, w0, hfma2(k1, w1, hfma2(k2, w2, hmul2(k3, w3)))), up);
#pragma unroll 1
          for (int hb = 0; hb < 2; hb++) {
            uint32_t kk[8], u[8];
#pragma unroll
            for (int r = 0; r < 8; r++) { kk[r] = ldg_stream(kp + r * 512); u[r] = ldg_stream(vp + r * 512); }
#pragma unroll
            for (int r = 0; r < 8; r++) {
              k3 = k2; k2 = k1; k1 = k0; k0 = kk[r];
              u[r] = hmul2(hfma2(k0, w0, hfma2(k1, w1, hfma2(k2, w2, hmul2(k3, w3)))), u[r]);
            }
            if (lane == 0) asm volatile("cp.async.bulk.wait_group.read 0;" ::: "memory");
            __syncwarp();
            const uint32_t dst = sb + SM_UST + lane * 32 + ((lane & 4) << 2);
#pragma unroll
            for (int cc = 0; cc < 2; cc++) {
              const uint32_t sel = cc ? 0x7632 : 0x5410;
              asm volatile("st.shared.v4.b32 [%0], {%1,%2,%3,%4};" ::"r"(dst + cc * 1024), "r"(__byte_perm(u[6], u[5], sel)), "r"(__byte_perm(u[4], u[3], sel)),
                           "r"(__byte_perm(u[2], u[1], sel)), "r"(__byte_perm(u[0], up, sel)) : "memory");
              asm volatile("st.shared.v4.b32 [%0], {%1,%2,%3,%4};" ::"r"((dst ^ 16) + cc * 1024), "r"(__byte_perm(u[7], u[6], sel)), "r"(__byte_perm(u[5], u[4], sel)),
                           "r"(__byte_perm(u[3], u[2], sel)), "r"(__byte_perm(u[1], u[0], sel)) : "memory");
            }
            fence_async_smem();
            __syncwarp();
            if (lane == 0) {
              asm volatile("cp.async.bulk.tensor.3d.global.shared::cta.bulk_group.L2::cache_hint [%0, {%2, %3, %4}], [%1], %5;\ncp.async.bulk.commit_group;"
                           ::"l"(&p.w), "r"(sb + SM_UST), "r"(WZ / 2 + lb * 16 + (hb ^ 1) * (WPL / 2)), "r"(cg * 32), "r"(0), "l"(cg >= UP0 && cg < UP1 ? EV_FIRST : EV_NORMAL) : "memory");
            }
            up = u[7];
            kp += 8 * 512; vp += 8 * 512;
          }
          if ((cg & (cg + 1)) == 0 && lane == 0) {
            asm volatile("cp.async.bulk.wait_group 0;" ::: "memory");
            fence_release();
            flag_add(FLAG(F_U + 32 - __clz(cg)));
          }
          TSW(10 + cg);
        }
        prefetch_tm(&p.wo); prefetch_tm(&p.x3); prefetch_tm(&p.y3); prefetch_tm(&p.out);
      } else {
#pragma unroll 1
        for (int i = 0, g = 2; i < 32; i++) {
          acquire(g, 2, 3);
          if (elect()) {
            const uint32_t fb = sb + SM_BAR + (B_FULL + g) * 8;
            if (i == 0) { mbar_expect_tx(fb - 8, 2048); bulk_g2s(sb + GR, p.gate_w, 2048, fb - 8); }
            mbar_expect_tx(fb, 2 * GR);
            tma3d(sb + g * GR, &p.x3, 0, (lb - NMAIN) * 512 + (i >> 3) * 128, (i & 7) * 2, fb);
          }
          g = g == NGR - 2 ? 2 : g + 2;
        }
        bar_arrive(5, 64);
      }
      unsigned long long t0, t1;
      asm volatile("mov.u64 %0, %globaltimer;" : "=l"(t0));
      auto check = [&]() {
        asm volatile("mov.u64 %0, %globaltimer;" : "=l"(t1));
        if (t1 - t0 > 2000000000ull) __trap();
      };
      if (!spare) {
        unsigned v;
        do {
          __nanosleep(PSL);
          check();
          asm volatile("ld.acquire.gpu.global.u32 %0, [%1];" : "=r"(v) : "l"(FLAG(lane & 1 ? F_Y + idx : F_GATE)) : "memory");
        } while (__any_sync(0xffffffffu, v < (lane & 1 ? 128 : 32)));
        __syncwarp();
        if (lane == 0) mbar_arrive(sb + SM_BAR + B_SLOT * 8);
      }
      if (lane == 0) {
        while (!mbar_try(sb + SM_BAR + B_DONE * 8, 0)) check();
      }
    } else if (warp != 0) {
      const int w = warp - 1;
      int ne = 12 + (CN_SPARE + 1 - w) / 2, c5 = 0;
      int cg = 2 + w, ch = cch + w * cstep;
#pragma unroll 1
      for (int e = spare ? 12 : 0; e < ne; e++) {
        const int rnd = e >= 6, k = e - 6 * rnd, rt = k == 4 ? idx : 15 - idx;
        uint8_t* dst = k < 4 ? g_kv + (size_t)(((k & 1) * 16 + 2 * grp + KV_HEAD(idx, k >> 1)) * 16 + KV_ROW(idx, k >> 1) + rank) * 32768 + w * 8192
                     : k < 6 ? g_cimg + (size_t)(rt * 32 + 16 * rnd + 2 * grp + rank) * 32768 + (w ^ (k & 1)) * 8192
                             : g_w + (size_t)ch * WSTRIDE + WZ;
        const uint32_t src = sb + w * 8192;
        if (e == 11) { c5 = get_ticket(); ne = 12 + ((cn + 1 - w) >> 1); }
        if (e == 6) flag_wait(FLAG(F_AD + grp), 32);
        mbar_wait1(sb + SM_BAR + (B_EV + w) * 8, e & 1);
        if (lane < 4 && k >= 6 && (!spare || e < ne - 6)) mbar_arrive_cluster(sb + SM_BAR + (B_EMPTY + cg) * 8, lane & 1);
        fence_async_smem();
        if (elect()) {
          const uint32_t cs = k >= 6 ? 4096 : 1024;
#pragma unroll 1
          for (uint32_t i = 0; i < (k >= 6 ? 4096 : 16384); i += cs) {
            const uint32_t o = i + (i & 8192);
            asm volatile("cp.async.bulk.global.shared::cta.bulk_group.L2::cache_hint [%0], [%1], %2, %3;" ::"l"(dst + o), "r"(src + o), "r"(cs),
                         "l"(e == 4 || e == 5 || spare ? EV_FIRST : EV_NORMAL) : "memory");
            asm volatile("cp.async.bulk.commit_group;\ncp.async.bulk.wait_group.read 1;" ::: "memory");
          }
          asm volatile("cp.async.bulk.wait_group 0;" ::: "memory");
          mbar_arrive(sb + SM_BAR + (B_FREE + w) * 8);
        }
        __syncwarp();
        if (lane < (e == 11 || (e == ne - 1 && !spare) ? 2 : 0)) mbar_arrive_cluster(sb + SM_BAR + (B_EMPTY + (e == 11)) * 8, lane);
        if (k >= 3) {
          fence_release();
          const unsigned fl = k == 3 ? F_KV + rnd * 8 + grp : k < 6 ? F_CTX + rt * 2 + rnd : F_Y + ((unsigned)ch >> 7);
          if (lane <= (e == 5)) flag_add(FLAG(lane ? F_AD + grp : fl));
        }
        if (k >= 6) { cg = conv_next(cg, spare); ch += 2 * cstep + (k == 7 ? c5 : 0); }
      }
      if (lane == 0) mbar_arrive(sb + SM_BAR + B_DONE * 8);
    } else {
#pragma unroll 1
      for (int rnd = 0; rnd < (spare ? 0 : 2); rnd++) {
        const int hp = 16 * rnd + 2 * grp, head = hp + rank;
#pragma unroll 1
        for (int kk = rnd || redo ? 0 : 4; kk < 32; kk++) {
          const int g0 = 2 + 3 * (kk & 3);
          acquire(g0, kk < 4 ? 3 : 1, 7);
          if (elect()) {
            const uint32_t fb = sb + SM_BAR + (B_FULL + g0) * 8;
            mbar_expect_tx(fb, 3 * GR);
            if (kk < 16) {
              tma2d_p(sb + g0 * GR, &p.c, (kk & 7) * 64, (KV_ROW(idx, kk >> 3) + rank) * 128, fb, rnd);
              tma3d_mc_p(sb + (g0 + 1 + rank) * GR, rank ? &p.wuv : &p.wuk, 0, (kk & 7) * 64, (hp + KV_HEAD(idx, kk >> 3)) * 2, fb, kk >= 8);
            } else {
              tma2d_mc(sb + (g0 + rank) * GR, &p.x, (kk - 16) * 64, (rank ? 15 - idx : idx) * 128, fb);
              tma3d<true>(sb + (g0 + 2) * GR, &p.wq, 0, (kk - 16) * 64, head * 2, fb);
            }
          }
        }
        flag_wait(FLAG(F_KV + rnd * 8 + grp), 32);
        fence_async_all();
        int g0 = 2;
#pragma unroll 1
        for (int n = 0; n < 36; n += n == 0 || n == 33 ? 2 : 1) {
          const int it = (n >> 1) - (n & 1);
          const int blk = it & 15 ? (it <= idx ? it - 1 : 15 - it) : it ? 15 - idx : idx;
          acquire(g0, n < 7 ? 2 : 1, 3);
          if (elect()) {
            const uint32_t fb = sb + SM_BAR + (B_FULL + g0) * 8;
            if (FINE_MODE == 8 && n < 8) FTP(rnd * 32 + 24 + n);
            if (n == 5) mbar_arrive(sb + SM_BAR + B_SLOT * 8);
            mbar_expect_tx(fb, 2 * GR);
            asm volatile("cp.async.bulk" TMA_MB ".L2::cache_hint [%0], [%1], %2, [%3], %4;" ::"r"(sb + g0 * GR), "l"(g_kv + (unsigned)((((n & 1) * 16 + (head & 15)) * 16 + blk) * 32768)),
                         "r"(2 * GR), "r"(fb), "l"(it >= 8 ? EV_FIRST : EV_NORMAL) : "memory");
          }
          g0 = g0 == 12 ? 2 : g0 + (n == 13 || n == 19 ? 4 : 2);
        }
      }
      int c5 = 0;
      if (spare) { bar_sync(5, 64); pe = 0x3FC0; }
      else c5 = get_ticket();
      auto conv_fill = [&](int g, int ch) {
        acquire(g, 1, 1);
        if (elect()) {
          const uint32_t fb = sb + SM_BAR + (B_FULL + g) * 8;
          if (FINE_MODE == 2 && !spare) FTP(64 + 48 + g);
          mbar_expect_tx(fb, WBYTES + 4096);
          bulk_g2s<true>(sb + g * GR, g_w + (size_t)ch * WSTRIDE, WBYTES, fb);
          bulk_g2s<true>(sb + g * GR + WBYTES, p.ssk + (size_t)ch * SEQ, 4096, fb);
        }
      };
#pragma unroll 1
      for (int i = 0, g = 2; i < cn; i++) {
        if ((i & 15) == 0) { flag_wait(FLAG(F_U + (spare ? 32 - __clz(i >> 4) : 4)), NMAIN); fence_async_all(); }
        conv_fill(g + (i & 1), cch + i * cstep + (i == 4 ? c5 : 0));
        if (i & 1) g = conv_next(g, spare);
      }
      if (!spare) {
        const int rt = 2 * grp + rank, ct = idx;
        int g0 = P3G, top = 12;
        const uint8_t* src = g_cimg + (unsigned)((rt * 64 + 32) * GR);
#pragma unroll 1
        for (int kb = 0; kb < 64; kb++) {
          if (!(kb & 31)) { flag_wait(FLAG(F_CTX + rt * 2 + ((kb ^ 32) >> 5)), 32); fence_async_all(); if (kb) src -= 64 * GR; }
          acquire(g0, kb < 11 ? 2 : 1, 3);
          if (elect()) {
            const uint32_t fb = sb + SM_BAR + (B_FULL + g0) * 8;
            if (FINE_MODE == 2 && kb < 16) FTP(48 + kb);
            mbar_expect_tx(fb, 2 * GR);
            bulk_g2s<true>(sb + g0 * GR, src, GR, fb);
            tma2d_mc<true>(sb + (g0 + 1) * GR + rank * 8192, &p.wo, ct * 128 + rank * 64, (kb ^ 32) * 64, fb);
          }
          src += GR;
          g0 = g0 == (kb < XK ? 12 : kb < YK ? 10 : 8) ? (kb == 3 ? 2 : 0) : g0 + 2;
          if (kb == XK || (kb >= YK && top == P3Y && (kb == 63 || mbar_test(sb + SM_BAR + B_SLOT * 8, 1)))) {
            const bool j = kb != XK;
            if (j) { mbar_wait1(sb + SM_BAR + B_SLOT * 8, 1); fence_async_all(); }
            acquire(top, 1, 0);
            if (elect()) {
              const uint32_t fb = sb + SM_BAR + (B_FULL + top) * 8;
              mbar_expect_tx(fb, j ? 2 * GR + 512 : 2 * GR);
              if (j) bulk_g2s(sb + SM_GATE, g_gate + (unsigned)(rt * 128), 512, fb);
              tma3d(sb + top * GR, j ? &p.y3 : &p.x3, 0, (j ? ct : rt) * 128, (j ? rt : ct) * 2, fb);
            }
            top -= 2;
          }
        }
        unsigned n = 0;
        if (lane == 0) n = atomicInc(FLAG(F_EXIT), 0x7fffffffu);
        if (__any_sync(0xffffffffu, n == NMAIN - 1)) {
#pragma unroll
          for (int i = lane; i < 96; i += 32) *reinterpret_cast<uint2*>(FLAG(i)) = make_uint2(0, 0);
        }
      }
      if (lane == 0) mbar_arrive(sb + SM_BAR + B_DONE * 8);
    }
    __syncwarp();
    cluster_wait();
  } else {
    asm volatile("setmaxnreg.inc.sync.aligned.u32 232;");
    FTS(2);
    Cons c;
    c.sb = sb; c.pf = 0; c.wg = wgi - 1; c.tid = threadIdx.x & 127;
    const int lane = threadIdx.x & 31, t = lane & 3;
    const int row = c.wg * 64 + (warp & 3) * 16 + (lane >> 2);
    const uint32_t dkk = desc_k(sb), dk0 = dkk + c.wg * 512, dm0 = desc_mn<8192>(sb), dv0 = desc_mn<16384>(sb);
    const uint32_t dsw = DG + 512 - c.wg * 1024;
    if (c.wg == 1) bar_arrive(1, 256);
    c.pfree = 1;
    asm("mapa.shared::cluster.u32 %0, %1, %2;" : "=r"(c.relb) : "r"(sb + SM_BAR + (B_EMPTY + (c.tid >> 1)) * 8), "r"(c.tid & 1));
    c.zero = p.zero;
    c.rnd = 0;
    const uint32_t stg = sb + (c.wg * 64 + (warp & 3) * 16 + ((lane >> 3) & 1) * 8 + (lane & 7)) * 128 + (((lane >> 4) ^ (lane & 7)) << 4);

    uint32_t dd0;
    auto load_dd = [&]() { asm volatile("ld.global.nc.u16 %0, [%1];" : "=r"(dd0) : "l"(p.ssd + (unsigned)(cch + c.wg * cstep + (lane & c.zero)))); };
    int pass = c.zero;
#pragma unroll 1
    do {
    if (pass) {
      load_dd();
#pragma unroll 1
      for (int g = 2; g < NGR; g += 3) { mbar_wait(sb + SM_BAR + (B_FULL + g) * 8, 0); c.release(g, 3); }
      c.pf = 0x924;
    if (spare) {
      c.wait_full(1);
      int g = 2;
#pragma unroll 1
      for (int r = 0; r < 4; r++) {
        float d[4] = {0.f, 0.f, 0.f, 0.f}, e[4] = {0.f, 0.f, 0.f, 0.f};
#pragma unroll 1
        for (int kb = 0; kb < 16; kb += 2) {
          c.wait_full(g);
          wg_fence();
#pragma unroll 1
          for (int k = 0; k < 4; k++) {
            mma_ss_n8(d, dk0 + g * DG + k * 2, dkk + DG + kb * 8 + k * 2);
            mma_ss_n8(e, dk0 + (g + 1) * DG + k * 2, dkk + DG + kb * 8 + 8 + k * 2);
          }
          wg_commit();
          wg_wait<0>();
          c.release(g, 2);
          g = g == NGR - 2 ? 2 : g + 2;
        }
        reg_fence(d); reg_fence(e);
        d[0] += e[0]; d[2] += e[2];
        if (t == 0) {
          float* gp = g_gate + (unsigned)((lb - NMAIN) * 512 + r * 128 + row);
          gp[0] = rcp(1.f + ex2(-1.4426950408889634f * d[0])); gp[8] = rcp(1.f + ex2(-1.4426950408889634f * d[2]));
        }
      }
      fence_release();
      __syncwarp();
      if (lane == 0) flag_add(FLAG(F_GATE));
      TS(1);
    }
    } else cluster_wait();
    get_slot();
    } while (redo && !pass++);
    FTS(3);
    const float dmask = (float)(2 * t - (row & 63));
    int c5 = 0;
    uint32_t pv[32];
#pragma unroll 1
    for (int rnd = 0; rnd < (spare ? 0 : 2); rnd++) {
      float O[64];
      uint32_t Q[32];
      FTM(rnd * 8);
      FTG(0);
      FTH(56, c.rnd == rnd);
      c.wait_full(2);
      FTM(rnd * 8 + 1);
      FTH(57, c.rnd == rnd);
#pragma unroll 1
      for (int tile = c.zero; tile < 2; tile++) {
        float acc[128];
        const bool single = tile == 0;
        {
          FTG(tile * 32 + 1);
          const uint32_t a = dk0 + 2 * DG, b = dm0 + 3 * DG;
          c.turn_begin();
          FTG(tile * 32 + 2);
          FTH(58, c.rnd == rnd);
          wg_fence();
          mma_ss_n256_init<1>(acc, a, b);
#pragma unroll
          for (int k = 1; k < 4; k++) mma_ss_n256<1>(acc, a + k * 2, b + k * 128);
          wg_commit();
          if (single) c.turn_end();
          FTG(tile * 32 + 3);
        }
#pragma unroll 1
        for (int kb = 1; kb < 8; kb++) {
          const int g0 = 2 + 3 * (kb & 3);
          const uint32_t a = dk0 + g0 * DG, b = dm0 + (g0 + 1) * DG;
          const bool second = (kb == 1 && !single) || kb == 7;
          FTG(tile * 32 + kb * 4);
          if (!second) { wg_wait<0>(); c.release(2 + 3 * ((kb - 1) & 3), 3); }
          FTG(tile * 32 + kb * 4 + 1);
          c.wait_full(g0);
          if (!second) c.turn_begin();
          FTG(tile * 32 + kb * 4 + 2);
          wg_fence();
#pragma unroll
          for (int k = 0; k < 4; k++) mma_ss_n256<1>(acc, a + k * 2, b + k * 128);
          wg_commit();
          if (kb != 6) c.turn_end();
          if (second) { wg_wait<1>(); c.release(2 + 3 * ((kb - 1) & 3), 3); }
          FTG(tile * 32 + kb * 4 + 3);
          FTH(58 + kb, c.rnd == rnd || kb > 3);
          if (tile == 1 && kb == 3) { c.wait_stage_free(); stsm_frag<0, 4>(pv, stg); }
          if (tile == 1 && kb == 4) { stsm_frag<4, 8>(pv, stg); c.staged(0); }
        }
        c.rnd = rnd;
        c.wait_stage_free();
        const bool nxt = c.try_full(2);
        wg_wait<0>();
        reg_fence(acc);
        c.release(11, 3);
        store_scaled(acc, SM_C, SM_C, stg, sb);
        c.staged(0);
        pack_frag<64>(acc, pv);
        FTG(32 + tile * 32);
        if (!nxt) mbar_wait(sb + SM_BAR + (B_FULL + 2) * 8, (c.pf >> 2) & 1);
        c.pf ^= 4;
      }
      TS(1 + rnd * 3);
      FTM(rnd * 8 + 2);
      {
        float qa[64];
        float (&qb)[64] = O;
        {
          FTG(65);
          const uint32_t a = dk0 + 2 * DG, b = dm0 + 4 * DG;
          c.turn_begin();
          FTG(66);
          wg_fence();
          mma_ss_n128_init<1>(qa, a, b);
          mma_ss_n128_init<1>(qb, a + dsw, b);
#pragma unroll
          for (int k = 1; k < 4; k++) {
            mma_ss_n128<1>(qa, a + k * 2, b + k * 128);
            mma_ss_n128<1>(qb, a + dsw + k * 2, b + k * 128);
          }
          wg_commit();
          FTG(67);
        }
#pragma unroll 1
        for (int kb = 1; kb < 16; kb++) {
          const int g0 = 2 + 3 * (kb & 3);
          const uint32_t a = dk0 + g0 * DG, b = dm0 + (g0 + 2) * DG;
          const bool second = kb == 1 || kb == 15;
          FTG(64 + kb * 4);
          if (!second) { wg_wait<0>(); c.release(2 + 3 * ((kb - 1) & 3), 3); }
          FTG(65 + kb * 4);
          c.wait_full(g0);
          if (!second) c.turn_begin();
          FTG(66 + kb * 4);
          FTH(kb - 14, kb < 14);
          wg_fence();
#pragma unroll
          for (int k = 0; k < 4; k++) {
            mma_ss_n128<1>(qa, a + k * 2, b + k * 128);
            mma_ss_n128<1>(qb, a + dsw + k * 2, b + k * 128);
          }
          wg_commit();
          if (kb != 14) c.turn_end();
          if (second) { wg_wait<1>(); c.release(2 + 3 * ((kb - 1) & 3), 3); }
          FTG(67 + kb * 4);
          FTH(2, kb < 15);
          if (kb == 13) FTB(0);
          if (kb == QFLUSH) { c.wait_stage_free(); stsm_frag<0, 4>(pv, stg); }
          if (kb == QFLUSH + 1) { stsm_frag<4, 8>(pv, stg); c.staged(0); }
        }
        c.wait_stage_free();
        FTM(rnd * 8 + 3);
        FTH(3, 0);
        const bool k0 = c.try_full(2);
        wg_wait<0>();
        reg_fence(qa); reg_fence(qb);
        FTH(4, 0);
        if (c.wg) FTB(1);
        c.release(11, 3);
        pack_frag<0>(qa, Q);
        if (c.wg == 0) {
          pack_frag<0>(qb, pv);
          stsm_frag(pv, stg);
        }
        if (!k0) c.wait_full(2); else c.pf ^= 4;
      }
      TS(2 + rnd * 3);
      FTM(rnd * 8 + 4);
      FTH(5, 0);
      if (!c.wg) FTB(1);
      {
        const int nA = idx + 1;
        uint32_t (&P)[32] = pv;
        SoftState z;
        z.m0 = z.m1 = z.l0 = z.l1 = 0.f; z.shifted = c.zero;
#pragma unroll 1
        for (int seg = c.zero;; seg++) {
        if (c.wg == seg) attn_half(c, O, P, Q, nA == 1 && !seg, stg, z, dkk, dv0, dmask, seg);
        if (seg) break;
        FTM(rnd * 8 + 5);
        int gk = c.wg ? 2 : 4, gv = c.wg ? 2 : 6;
        uint32_t dk = dkk + gk * DG;
#pragma unroll 1
        for (int it = 1 - c.wg; it < 17 - c.wg; it++) {
          float S[64];
          FTA(it * 7 + 0); FTH((it < 3 ? 8 + it * 8 : it * 8 - 88) + 0, it >= 3 && it < 15);
          c.turn_begin();
          FTA(it * 7 + 2); FTH((it < 3 ? 8 + it * 8 : it * 8 - 88) + 1, it >= 3 && it < 15);
          wg_fence();
          issue_qk(S, Q, dk);
          wg_commit();
          FTB(4 + it);
          const uint32_t dv = dv0 + gv * DG;
          uint32_t relk = c.relb + gk * 8, relv = c.relb + gv * 8;
          gk = gv == 12 ? 2 : gv + (it == 6 || it == 9 ? 4 : 2);
          gv = it == 16 ? gk : gk == 12 ? 2 : gk + 2;
          uint32_t fk = sb + SM_BAR + (B_FULL + gk) * 8, fv = sb + SM_BAR + (B_FULL + gv) * 8, park = (c.pf >> gk) & 1, parv = (c.pf >> gv) & 1;
          c.pf ^= (1u << gk) | (1u << gv);
          dk = dkk + gk * DG;
          float lo0 = z.l0, lo1 = z.l1;
          const bool first = it == nA || it == 0;
          if (it == nA) {
            lo0 = rcp(quad_sum(lo0)); lo1 = rcp(quad_sum(lo1));
            z.m0 = z.m1 = z.l0 = z.l1 = 0.f; z.shifted = 0;
          }
          float s0, s1, d0 = z.m0, d1 = z.m1;
          int pre = z.shifted || (it & 15) == 0 || it + 1 == nA;
          float lim = first ? -1.f : SM_LIMIT;
          asm volatile("" : "+r"(relk), "+r"(relv), "+r"(fk), "+r"(fv), "+r"(park), "+r"(parv), "+r"(dk), "+r"(pre), "+f"(lim), "+f"(d0), "+f"(d1), "+f"(z.l0), "+f"(z.l1));
          if (it + c.wg > 1) {
            issue_pv<0>(O, P, dv, it != nA + 1 && it != 1, true);
            issue_pv<1>(O, P, dv, 1, true);
            c.turn_end();
          } else if (it) {
            issue_pv<0>(O, P, dv, 0, true);
            wg_commit(); wg_commit();
            c.turn_end();
            bar_sync(6, 256);
          } else stage_q2(c, O, P, stg);
          FTA(it * 7 + 3); FTH((it < 3 ? 8 + it * 8 : it * 8 - 88) + 2, it >= 3 && it < 15);
          wg_wait<4>();
          reg_fence(S); reg_fence(Q);
          FTA(it * 7 + 4); FTH((it < 3 ? 8 + it * 8 : it * 8 - 88) + 3, it >= 3 && it < 15);
          if (c.tid < 4) asm volatile("mbarrier.arrive.shared::cluster.b64 _, [%0];" ::"r"(relk) : "memory");
#pragma unroll 1
          for (int pass = 0;; pass++) {
            if (pre) {
              if (it + 1 == nA) load_q(Q, stg);
              if ((it & 15) == 0) mask_diag(S, dmask);
              if (z.shifted) shift_scores(S, d0, d1);
            }
            float tr[ROT];
            exp_quarter<0, 3>(S, P, tr, s0, s1, sb);
            exp_quarter<1, 2>(S, P, tr, s0, s1, sb);
            exp_quarter<2, 1>(S, P, tr, s0, s1, sb);
            exp_quarter<3, 0>(S, P, tr, s0, s1, sb);
            reg_fence(O);
            if (c.tid < (pass || !it ? 0 : 4)) asm volatile("mbarrier.arrive.shared::cluster.b64 _, [%0];" ::"r"(relv) : "memory");
            const bool ok = mbar_test(fk, park) & mbar_test(fv, parv);
            if (!ok) lim = -1.f;
            FTA(it * 7 + 5); FTH((it < 3 ? 8 + it * 8 : it * 8 - 88) + 4, it >= 3 && it < 15);
            if (!__any_sync(0xffffffffu, !(s0 <= lim && s1 <= lim))) break;
            if (pass) break;
            if (it == nA) {
              store_scaled(O, lo0, lo1, stg, sb);
              c.staged(0);
            }
            if (!it) bar_arrive(6, 256);
            if (!it) FTB(2);
            if (!ok) { mbar_wait(fk, park); mbar_wait(fv, parv); }
            if (!it) FTB(3);
            if (!soft_unsafe(s0, s1, first)) break;
            soft_fix(S, O, z, first, d0, d1);
            pre = 1;
          }
          z.l0 += s0; z.l1 += s1;
          FTA(it * 7 + 6); FTH((it < 3 ? 8 + it * 8 : it * 8 - 88) + 5, it >= 3 && it < 15);
        }
        if (!c.wg) bar_arrive(6, 256);
        FTM(rnd * 8 + 6);
        }
        FTH(48, 0);
        load_dd();
        c.turn_begin();
        FTH(49, 0);
        wg_fence();
        issue_pv<0>(O, P, dv0 + 12 * DG, 1, true);
        issue_pv<1>(O, P, dv0 + 12 * DG, 1, !c.wg);
        c.turn_end();
        z.l0 = rcp(quad_sum(z.l0)); z.l1 = rcp(quad_sum(z.l1));
        c.wait_stage_free();
        if (rnd) c5 = get_ticket();
        wg_wait<0>();
        reg_fence(O); reg_fence(P);
        FTH(50, 0);
        c.release(12, 2);
        store_scaled(O, z.l0, z.l1, stg, sb);
        c.staged(0);
        FTM(rnd * 8 + 7);
        FTH(51, 0);
      }
      TS(3 + rnd * 3);
    }
    conv_tasks(c, p, (cn + 1 - c.wg) >> 1, spare, cch + c.wg * cstep, 2 * cstep, c5, dd0, dkk, warp & 3, lane);
    if (c.wg == 1) c.pf ^= 0x14;
    if (c.wg == (cn & 1)) c.turn_begin();
    TS(7);
    if (!spare) {
      const int rt = 2 * grp + rank, ct = idx;
      float acc[64];
      int g0 = P3G + 2, pg = P3G;
      {
        FTO(0);
        c.wait_full(P3G);
        FTO(1);
        const uint32_t a = dk0 + P3G * DG, b = dm0 + (P3G + 1) * DG;
        wg_fence();
        mma_ss_n128_init<1>(acc, a, b);
#pragma unroll
        for (int k = 1; k < 4; k++) mma_ss_n128<1>(acc, a + k * 2, b + k * 128);
        wg_commit();
      }
#pragma unroll 1
      for (int kb = 1; kb < 64; kb++) {
        FTO(kb * 2);
        c.wait_full(g0);
        if (kb == STR && !c.wg) c.turn_begin();
        FTO(kb * 2 + 1);
        const uint32_t a = dk0 + g0 * DG, b = dm0 + (g0 + 1) * DG;
        wg_fence();
#pragma unroll
        for (int k = 0; k < 4; k++) mma_ss_n128<1>(acc, a + k * 2, b + k * 128);
        wg_commit();
        if (kb < STR) { wg_wait<1>(); c.release(pg, kb <= 59 ? 2 : 0); }
        if (kb == FDUMP_KB) FTDUMP();
        pg = g0;
        g0 = g0 == (kb < XK ? 12 : kb < YK ? 10 : 8) ? (kb == 3 ? 2 : 0) : g0 + 2;
      }
      if (c.wg) c.turn_end();
      cluster_arrive();
      c.wait_full(P3X);
      c.wait_full(P3Y);
      const float g0f = __uint_as_float(lds32(sb + SM_GATE + row * 4)), g1f = __uint_as_float(lds32(sb + SM_GATE + row * 4 + 32));
      const uint32_t gp0 = pack_bf16(g0f, g0f), gp1 = pack_bf16(g1f, g1f);
      const float h0 = 1.f - g0f, h1 = 1.f - g1f;
      const int w = warp & 3;
      const uint32_t xa = stg + P3X * GR;
      const uint32_t ya = sb + P3Y * GR + c.wg * 16384 + ((lane >> 4) * 8 + (lane & 7)) * 128 + (((2 * w + ((lane >> 3) & 1)) ^ (lane & 7)) << 4);
      uint32_t xy[32];
      auto prep = [&](int j0, int j1) {
#pragma unroll
        for (int jj = j0; jj < j1; jj++) {
          uint32_t x[4], y[4];
          asm volatile("ldmatrix.sync.aligned.m8n8.x4.shared.b16 {%0,%1,%2,%3}, [%4];" : "=r"(x[0]), "=r"(x[1]), "=r"(x[2]), "=r"(x[3]) : "r"((xa ^ ((jj & 3) << 5)) + (jj >> 2) * 16384) : "memory");
          asm volatile("ldmatrix.sync.aligned.m8n8.x4.trans.shared.b16 {%0,%1,%2,%3}, [%4];" : "=r"(y[0]), "=r"(y[1]), "=r"(y[2]), "=r"(y[3]) : "r"(ya + jj * 2048) : "memory");
#pragma unroll
          for (int i = 0; i < 4; i++) xy[4 * jj + i] = hmul2(x[i], y[i]);
        }
      };
      prep(0, 4);
      wg_wait<0>();
      reg_fence(acc);
      TS(8);
#pragma unroll
      for (int hf = 0; hf < 2; hf++) {
#pragma unroll
        for (int i = 16 * hf; i < 16 * hf + 16; i++) {
          const float h = (i & 1) ? h1 : h0;
          xy[i] = hfma2((i & 1) ? gp1 : gp0, xy[i], pack_bf16(acc[2 * i] * h, acc[2 * i + 1] * h));
        }
        if (hf) stsm_frag<4, 8>(xy, xa); else stsm_frag<0, 4>(xy, xa);
        fence_async_smem();
        __syncwarp();
        const int r0 = c.wg * 64 + w * 16;
        if (lane == 0) tma2d_store(&p.out, sb + (P3X + hf) * GR + r0 * 128, ct * 128 + hf * 64, rt * 128 + r0);
        if (!hf) prep(4, 8);
      }
      if (lane == 0) asm volatile("cp.async.bulk.commit_group;\ncp.async.bulk.wait_group.read 0;" ::: "memory");
    } else { FTDUMP(); cluster_arrive(); }
    if (lane == 0) mbar_arrive(sb + SM_BAR + B_DONE * 8);
    __syncwarp();
    TS(9);
    cluster_wait();
  }
}

typedef CUresult (*EncFn)(CUtensorMap*, CUtensorMapDataType, cuuint32_t, void*, const cuuint64_t*, const cuuint64_t*, const cuuint32_t*,
                          const cuuint32_t*, CUtensorMapInterleave, CUtensorMapSwizzle, CUtensorMapL2promotion, CUtensorMapFloatOOBfill);

void enc2d(EncFn enc, CUtensorMap* tm, const void* base, uint64_t cols, uint64_t rows, uint32_t bc, uint32_t br) {
  cuuint64_t dims[2] = {cols, rows}; cuuint64_t strides[1] = {cols * 2}; cuuint32_t box[2] = {bc, br}; cuuint32_t es[2] = {1, 1};
  enc(tm, CU_TENSOR_MAP_DATA_TYPE_BFLOAT16, 2, const_cast<void*>(base), dims, strides, box, es, CU_TENSOR_MAP_INTERLEAVE_NONE,
      CU_TENSOR_MAP_SWIZZLE_128B, CU_TENSOR_MAP_L2_PROMOTION_L2_256B, CU_TENSOR_MAP_FLOAT_OOB_FILL_NONE);
}
void enc3d(EncFn enc, CUtensorMap* tm, const void* base, uint64_t K, uint64_t N, uint32_t bk = 64, uint64_t pitch = 0) {
  cuuint64_t dims[3] = {64, K, N / 64}; cuuint64_t strides[2] = {pitch ? pitch : N * 2, 128}; cuuint32_t box[3] = {64, bk, 2}; cuuint32_t es[3] = {1, 1, 1};
  enc(tm, CU_TENSOR_MAP_DATA_TYPE_BFLOAT16, 3, const_cast<void*>(base), dims, strides, box, es, CU_TENSOR_MAP_INTERLEAVE_NONE,
      CU_TENSOR_MAP_SWIZZLE_128B, CU_TENSOR_MAP_L2_PROMOTION_L2_256B, CU_TENSOR_MAP_FLOAT_OOB_FILL_NONE);
}

}

extern "C" void kernel_launch(void* const* d_in, const int* in_sizes, int n_in, void* d_out, int out_size) {
  (void)in_sizes; (void)n_in; (void)out_size;
  typedef const __nv_bfloat16* BP;
  BP xq = (BP)d_in[0], ak = (BP)d_in[1], av = (BP)d_in[2], shk = (BP)d_in[3], ssk = (BP)d_in[4], ssd = (BP)d_in[5];
  BP ckv = (BP)d_in[7], wq = (BP)d_in[8], wuk = (BP)d_in[9], wuv = (BP)d_in[10], wo = (BP)d_in[11], gw = (BP)d_in[12];

  static EncFn enc = nullptr;
  if (!enc) {
    cudaDriverEntryPointQueryResult qr;
    cudaGetDriverEntryPoint("cuTensorMapEncodeTiled", (void**)&enc, cudaEnableDefault, &qr);
    cudaFuncSetAttribute(mega_kernel, cudaFuncAttributeMaxDynamicSharedMemorySize, SMEM_BYTES);
  }
  Params p;
  enc2d(enc, &p.x, xq, DM, SEQ, 64, 128);
  enc2d(enc, &p.c, ckv, DC, SEQ, 64, 128);
  enc3d(enc, &p.wq, wq, DM, NH * HD);
  enc3d(enc, &p.wuk, wuk, DC, NH * HD);
  enc3d(enc, &p.wuv, wuv, DC, NH * HD);
  enc2d(enc, &p.wo, wo, DM, NH * HD, 64, 64);
  enc3d(enc, &p.x3, xq, SEQ, DM, 128);
  enc2d(enc, &p.out, d_out, DM, SEQ, 64, 16);
  {
    void* wp = nullptr;
    cudaGetSymbolAddress(&wp, g_w);
    enc3d(enc, &p.y3, (uint8_t*)wp + WZ, DM, SEQ, 128, WSTRIDE);
    cuuint64_t dims[3] = {WSTRIDE / 2, DM / 2, 2}; cuuint64_t strides[2] = {2 * WSTRIDE, WSTRIDE}; cuuint32_t box[3] = {16, 32, 2}; cuuint32_t es[3] = {1, 1, 1};
    enc(&p.w, CU_TENSOR_MAP_DATA_TYPE_BFLOAT16, 3, wp, dims, strides, box, es, CU_TENSOR_MAP_INTERLEAVE_NONE,
        CU_TENSOR_MAP_SWIZZLE_32B, CU_TENSOR_MAP_L2_PROMOTION_NONE, CU_TENSOR_MAP_FLOAT_OOB_FILL_NONE);
  }
  p.zero = 0;
  cudaGetSymbolAddress((void**)&p.flags, g_flags);
  for (int i = 0; i < 128; i++) {
    const int tp = i % NSLOT;
    p.pref[i] = tp < 32 ? (tp & 7) * 8 + (tp >> 3) : tp < 60 ? (1 + (tp - 32) % 7) * 8 + 4 + (tp - 32) / 7 : tp < 62 ? tp + 4 : tp - 58;
  }
  p.gate_w = gw; p.ak = ak; p.av = av; p.shk = shk; p.ssk = ssk; p.ssd = ssd;

  mega_kernel<<<132, NTHREADS, SMEM_BYTES>>>(p);
}
```

```cpp
#include <cuda_runtime.h>
#include <cuda.h>
#include <cuda_bf16.h>
#include <stdint.h>

namespace {

constexpr int SEQ = 2048, DM = 1024, DC = 512, NH = 32, HD = 128;
constexpr int GR = 16384;
constexpr int NGR = 14;
constexpr int SM_BAR = NGR * GR;
constexpr int SM_GATE = SM_BAR + 512;
constexpr int SM_UST = SM_GATE + 512;
constexpr int SMEM_BYTES = SM_UST + 2048;
constexpr int NTHREADS = 384;
constexpr float SM_LIMIT = 1.0995116e12f;
constexpr float SM_LOW = 9.094947e-13f;
constexpr int CNS = 106;
constexpr int CN_SPARE = CNS, NTICK = 256 - 2 * CN_SPARE;
constexpr int XK = 57, YK = 62;
constexpr int STR = 61;
constexpr int P3G = 6, P3X = 12, P3Y = 10;
constexpr int NMAIN = 128;

constexpr int B_FULL = 0, B_FREE = 14, B_SLOT = 16, B_DONE = 17, B_EMPTY = 18, B_EV = 32, B_TICK = 36;
constexpr int V_SLOT = 37, V_TICK = 38;

__device__ __align__(1024) uint8_t g_kv[2 * 16 * 16 * 32768];
__device__ __align__(1024) uint8_t g_cimg[16 * NH * 32768];
__device__ __align__(1024) float g_gate[SEQ];
constexpr int WZ = 256, WPL = WZ + 4096, WBYTES = 2 * WPL + 32, WSTRIDE = 2 * WPL + 128;
__device__ __align__(1024) uint8_t g_w[DM * WSTRIDE];
__device__ __align__(32) unsigned g_flags[96 * 8];
constexpr int F_KV = 0, F_CTX = 16, F_U = 48, F_AD = 56, F_Y = 64, F_GATE = 72, F_EXIT = 73, F_TICK = 74;
constexpr int NSLOT = 66;
#define FLAG(i) (&g_flags[(i) * 8])
#define CLAIMP(i) (p.flags + (i) * 8 + 1)

constexpr int QFLUSH = 3;
constexpr int PSL = 200;
constexpr int US0 = 500;
constexpr int EROT = 6;
constexpr int RST = 2;
constexpr int UP0 = 4;
constexpr int UP1 = 11;
constexpr int X_DELAY = 1100;
constexpr int X_D2 = 500;
constexpr int ROT = 8;
#define KV_ROW(idx, t) (8 * (t) + 2 * ((idx) & 3))
#define KV_HEAD(idx, t) ((idx) >> 2)

__device__ __forceinline__ uint32_t smem_u32(const void* p) { return (uint32_t)__cvta_generic_to_shared(p); }
__device__ __forceinline__ void mbar_init(uint32_t bar, int cnt) { asm volatile("mbarrier.init.shared::cta.b64 [%0], %1;" ::"r"(bar), "r"(cnt) : "memory"); }
__device__ __forceinline__ void mbar_expect_tx(uint32_t bar, uint32_t bytes) { asm volatile("mbarrier.arrive.expect_tx.shared::cta.b64 _, [%0], %1;" ::"r"(bar), "r"(bytes) : "memory"); }
__device__ __forceinline__ void mbar_arrive(uint32_t bar) { asm volatile("mbarrier.arrive.shared::cta.b64 _, [%0];" ::"r"(bar) : "memory"); }
__device__ __forceinline__ void mbar_arrive_cluster(uint32_t bar, uint32_t cta) {
  asm volatile("{\n.reg .b32 r;\nmapa.shared::cluster.u32 r, %0, %1;\nmbarrier.arrive.shared::cluster.b64 _, [r];\n}\n" ::"r"(bar), "r"(cta) : "memory");
}
__device__ __forceinline__ void send_both(uint32_t bar, uint32_t off, uint32_t v) {
#pragma unroll
  for (int r = 0; r < 2; r++)
    asm volatile("{\n.reg .b32 a, b;\nmapa.shared::cluster.u32 a, %0, %1;\nadd.u32 b, a, %3;\nst.async.shared::cluster.mbarrier::complete_tx::bytes.u32 [b], %2, [a];\n}\n"
                 ::"r"(bar), "r"(r), "r"(v), "r"(off) : "memory");
}
__device__ __forceinline__ bool mbar_try(uint32_t bar, uint32_t parity) {
  uint32_t ok;
  asm volatile("{\n.reg .pred p;\nmbarrier.try_wait.parity.shared::cta.b64 p, [%1], %2, 20000;\nselp.u32 %0, 1, 0, p;\n}\n" : "=r"(ok) : "r"(bar), "r"(parity) : "memory");
  return ok;
}
__device__ __forceinline__ bool mbar_test(uint32_t bar, uint32_t parity) {
  uint32_t ok;
  asm volatile("{\n.reg .pred p;\nmbarrier.test_wait.parity.shared::cta.b64 p, [%1], %2;\nselp.u32 %0, 1, 0, p;\n}\n" : "=r"(ok) : "r"(bar), "r"(parity) : "memory");
  return ok;
}
__device__ __forceinline__ void mbar_wait(uint32_t bar, uint32_t parity) {
  asm volatile("{\n.reg .pred p;\nWAIT_LOOP:\nbar.warp.sync -1;\nmbarrier.try_wait.parity.shared::cta.b64 p, [%0], %1;\n@!p bra WAIT_LOOP;\n}\n" ::"r"(bar), "r"(parity) : "memory");
}
__device__ __forceinline__ void mbar_wait1(uint32_t bar, uint32_t parity) {
  asm volatile("{\n.reg .pred p;\nWAIT_LOOP:\nbar.warp.sync -1;\nmbarrier.try_wait.parity.shared::cta.b64 p, [%0], %1, 4000;\n@!p bra WAIT_LOOP;\n}\n" ::"r"(bar), "r"(parity) : "memory");
}
constexpr uint64_t EV_NORMAL = 0x1000000000000000ull, EV_FIRST = 0x12F0000000000000ull;
__device__ __forceinline__ uint32_t ldg_stream(const uint32_t* p) {
  uint32_t r; asm volatile("ld.global.nc.L1::no_allocate.L2::cache_hint.b32 %0, [%1], %2;" : "=r"(r) : "l"(p), "l"(EV_FIRST)); return r;
}
#define TMA_LD "cp.async.bulk.tensor."
#define TMA_MB ".shared::cluster.global.mbarrier::complete_tx::bytes"
__device__ __forceinline__ void tma2d(uint32_t dst, const CUtensorMap* tm, int c0, int c1, uint32_t bar) {
  asm volatile(TMA_LD "2d" TMA_MB " [%0], [%1, {%3, %4}], [%2];" ::"r"(dst), "l"(tm), "r"(bar), "r"(c0), "r"(c1) : "memory");
}
template <bool ONCE = false> __device__ __forceinline__ void tma2d_mc(uint32_t dst, const CUtensorMap* tm, int c0, int c1, uint32_t bar) {
  if (ONCE) asm volatile(TMA_LD "2d" TMA_MB ".multicast::cluster.L2::cache_hint [%0], [%1, {%3, %4}], [%2], %5, %6;"
                         ::"r"(dst), "l"(tm), "r"(bar), "r"(c0), "r"(c1), "h"((uint16_t)3), "l"(EV_FIRST) : "memory");
  else asm volatile(TMA_LD "2d" TMA_MB ".multicast::cluster [%0], [%1, {%3, %4}], [%2], %5;"
                    ::"r"(dst), "l"(tm), "r"(bar), "r"(c0), "r"(c1), "h"((uint16_t)3) : "memory");
}
__device__ __forceinline__ void tma2d_p(uint32_t dst, const CUtensorMap* tm, int c0, int c1, uint32_t bar, bool once) {
  asm volatile(TMA_LD "2d" TMA_MB ".L2::cache_hint [%0], [%1, {%3, %4}], [%2], %5;" ::"r"(dst), "l"(tm), "r"(bar), "r"(c0), "r"(c1), "l"(once ? EV_FIRST : EV_NORMAL) : "memory");
}
__device__ __forceinline__ void tma3d_mc_p(uint32_t dst, const CUtensorMap* tm, int c0, int c1, int c2, uint32_t bar, bool once) {
  asm volatile(TMA_LD "3d" TMA_MB ".multicast::cluster.L2::cache_hint [%0], [%1, {%3, %4, %5}], [%2], %6, %7;"
               ::"r"(dst), "l"(tm), "r"(bar), "r"(c0), "r"(c1), "r"(c2), "h"((uint16_t)3), "l"(once ? EV_FIRST : EV_NORMAL) : "memory");
}
template <bool ONCE = false> __device__ __forceinline__ void tma3d(uint32_t dst, const CUtensorMap* tm, int c0, int c1, int c2, uint32_t bar) {
  if (ONCE) asm volatile(TMA_LD "3d" TMA_MB ".L2::cache_hint [%0], [%1, {%3, %4, %5}], [%2], %6;" ::"r"(dst), "l"(tm), "r"(bar), "r"(c0), "r"(c1), "r"(c2), "l"(EV_FIRST) : "memory");
  else
  asm volatile(TMA_LD "3d" TMA_MB " [%0], [%1, {%3, %4, %5}], [%2];" ::"r"(dst), "l"(tm), "r"(bar), "r"(c0), "r"(c1), "r"(c2) : "memory");
}
__device__ __forceinline__ void tma3d_mc(uint32_t dst, const CUtensorMap* tm, int c0, int c1, int c2, uint32_t bar) {
  asm volatile(TMA_LD "3d" TMA_MB ".multicast::cluster [%0], [%1, {%3, %4, %5}], [%2], %6;"
               ::"r"(dst), "l"(tm), "r"(bar), "r"(c0), "r"(c1), "r"(c2), "h"((uint16_t)3) : "memory");
}
template <bool ONCE = false> __device__ __forceinline__ void bulk_g2s(uint32_t dst, const void* src, uint32_t bytes, uint32_t bar) {
  if (ONCE) asm volatile("cp.async.bulk" TMA_MB ".L2::cache_hint [%0], [%1], %2, [%3], %4;" ::"r"(dst), "l"(src), "r"(bytes), "r"(bar), "l"(EV_FIRST) : "memory");
  else asm volatile("cp.async.bulk" TMA_MB " [%0], [%1], %2, [%3];" ::"r"(dst), "l"(src), "r"(bytes), "r"(bar) : "memory");
}
__device__ __forceinline__ void tma2d_store(const CUtensorMap* tm, uint32_t src, int c0, int c1) {
  asm volatile("cp.async.bulk.tensor.2d.global.shared::cta.bulk_group [%0, {%2, %3}], [%1];" ::"l"(tm), "r"(src), "r"(c0), "r"(c1) : "memory");
}
__device__ __forceinline__ void prefetch_tm(const CUtensorMap* tm) { asm volatile("prefetch.tensormap [%0];" ::"l"(tm) : "memory"); }
__device__ __forceinline__ void wg_fence() { asm volatile("wgmma.fence.sync.aligned;" ::: "memory"); }
__device__ __forceinline__ void wg_commit() { asm volatile("wgmma.commit_group.sync.aligned;" ::: "memory"); }
template <int N> __device__ __forceinline__ void wg_wait() { asm volatile("wgmma.wait_group.sync.aligned %0;" ::"n"(N) : "memory"); }
__device__ __forceinline__ void bar_sync(int id, int n) { asm volatile("bar.sync %0, %1;" ::"r"(id), "r"(n) : "memory"); }
__device__ __forceinline__ void bar_arrive(int id, int n) { asm volatile("bar.arrive %0, %1;" ::"r"(id), "r"(n) : "memory"); }
__device__ __forceinline__ void fence_async_smem() { asm volatile("fence.proxy.async.shared::cta;" ::: "memory"); }
__device__ __forceinline__ void fence_async_all() { asm volatile("fence.proxy.async.global;" ::: "memory"); }
__device__ __forceinline__ uint32_t pack_bf16(float lo, float hi) { uint32_t r; asm("cvt.rn.bf16x2.f32 %0, %1, %2;" : "=r"(r) : "f"(hi), "f"(lo)); return r; }
__device__ __forceinline__ float ex2(float x) { float r; asm("ex2.approx.ftz.f32 %0, %1;" : "=f"(r) : "f"(x)); return r; }
__device__ __forceinline__ float rcp(float x) { float r; asm("rcp.approx.ftz.f32 %0, %1;" : "=f"(r) : "f"(x)); return r; }
__device__ __forceinline__ void flag_wait(const unsigned* f, unsigned target) {
  unsigned v;
  do { asm volatile("ld.acquire.gpu.global.u32 %0, [%1];" : "=r"(v) : "l"(f) : "memory"); } while (__any_sync(0xffffffffu, v < target));
}
__device__ __forceinline__ bool elect() {
  uint32_t r;
  asm volatile("{\n.reg .pred p;\nelect.sync _|p, -1;\nselp.u32 %0, 1, 0, p;\n}\n" : "=r"(r));
  return r;
}
__device__ __forceinline__ void fence_release() { asm volatile("fence.release.gpu;" ::: "memory"); }
__device__ __forceinline__ void flag_add(unsigned* f) { asm volatile("red.relaxed.gpu.global.inc.u32 [%0], 0x7fffffff;" ::"l"(f) : "memory"); }
__device__ __forceinline__ void cluster_arrive() { asm volatile("barrier.cluster.arrive.relaxed.aligned;" ::: "memory"); }
__device__ __forceinline__ void cluster_wait() { asm volatile("barrier.cluster.wait.aligned;" ::: "memory"); }
__device__ __forceinline__ uint32_t hmul2(uint32_t a, uint32_t b) { uint32_t r; asm("mul.rn.bf16x2 %0, %1, %2;" : "=r"(r) : "r"(a), "r"(b)); return r; }
__device__ __forceinline__ uint32_t hadd2(uint32_t a, uint32_t b) { uint32_t r; asm("add.rn.bf16x2 %0, %1, %2;" : "=r"(r) : "r"(a), "r"(b)); return r; }
__device__ __forceinline__ uint32_t hfma2(uint32_t a, uint32_t b, uint32_t c) { uint32_t r; asm("fma.rn.bf16x2 %0, %1, %2, %3;" : "=r"(r) : "r"(a), "r"(b), "r"(c)); return r; }
__device__ __forceinline__ uint32_t lds32(uint32_t a) { uint32_t r; asm volatile("ld.shared.b32 %0, [%1];" : "=r"(r) : "r"(a) : "memory"); return r; }
__device__ __forceinline__ uint4 lds128(uint32_t a) { uint4 r; asm volatile("ld.shared.v4.b32 {%0,%1,%2,%3}, [%4];" : "=r"(r.x), "=r"(r.y), "=r"(r.z), "=r"(r.w) : "r"(a) : "memory"); return r; }
__device__ __forceinline__ uint32_t desc_k(uint32_t addr) { return ((addr & 0x3FFFF) >> 4) | (1u << 16); }
template <int LBO> __device__ __forceinline__ uint32_t desc_mn(uint32_t addr) { return ((addr & 0x3FFFF) >> 4) | ((uint32_t)(LBO >> 4) << 16); }
#define DHI "0x40000040"

#define R8(d, o) "+f"(d[o]), "+f"(d[o + 1]), "+f"(d[o + 2]), "+f"(d[o + 3]), "+f"(d[o + 4]), "+f"(d[o + 5]), "+f"(d[o + 6]), "+f"(d[o + 7])
#define R32(d, o) R8(d, o), R8(d, o + 8), R8(d, o + 16), R8(d, o + 24)
#define R64(d, o) R32(d, o), R32(d, o + 32)
#define L64 "%0,%1,%2,%3,%4,%5,%6,%7,%8,%9,%10,%11,%12,%13,%14,%15,%16,%17,%18,%19,%20,%21,%22,%23,%24,%25,%26,%27,%28,%29,%30,%31," \
            "%32,%33,%34,%35,%36,%37,%38,%39,%40,%41,%42,%43,%44,%45,%46,%47,%48,%49,%50,%51,%52,%53,%54,%55,%56,%57,%58,%59,%60,%61,%62,%63"
#define L128 L64 ",%64,%65,%66,%67,%68,%69,%70,%71,%72,%73,%74,%75,%76,%77,%78,%79,%80,%81,%82,%83,%84,%85,%86,%87,%88,%89,%90,%91,%92,%93,%94,%95," \
            "%96,%97,%98,%99,%100,%101,%102,%103,%104,%105,%106,%107,%108,%109,%110,%111,%112,%113,%114,%115,%116,%117,%118,%119,%120,%121,%122,%123,%124,%125,%126,%127"

template <int TB> __device__ __forceinline__ void mma_ss_n128(float (&d)[64], uint32_t da, uint32_t db) {
  asm volatile("{\n.reg .b64 da, db;\nmov.b64 da, {%64, " DHI "};\nmov.b64 db, {%65, " DHI "};\n"
               "wgmma.mma_async.sync.aligned.m64n128k16.f32.bf16.bf16 {" L64 "}, da, db, 1, 1, 1, 0, %66;\n}\n"
               : R64(d, 0) : "r"(da), "r"(db), "n"(TB));
}
template <int TB> __device__ __forceinline__ void mma_rs_n128(float (&d)[64], uint32_t a0, uint32_t a1, uint32_t a2, uint32_t a3, uint32_t db, int sd) {
  asm volatile("{\n.reg .pred p;\n.reg .b64 db;\nsetp.ne.b32 p, %69, 0;\nmov.b64 db, {%68, " DHI "};\n"
               "wgmma.mma_async.sync.aligned.m64n128k16.f32.bf16.bf16 {" L64 "}, {%64,%65,%66,%67}, db, p, 1, 1, %70;\n}\n"
               : R64(d, 0) : "r"(a0), "r"(a1), "r"(a2), "r"(a3), "r"(db), "r"(sd), "n"(TB));
}
template <int TB> __device__ __forceinline__ void mma_ss_n256(float (&d)[128], uint32_t da, uint32_t db) {
  asm volatile("{\n.reg .b64 da, db;\nmov.b64 da, {%128, " DHI "};\nmov.b64 db, {%129, " DHI "};\n"
               "wgmma.mma_async.sync.aligned.m64n256k16.f32.bf16.bf16 {" L128 "}, da, db, 1, 1, 1, 0, %130;\n}\n"
               : R64(d, 0), R64(d, 64) : "r"(da), "r"(db), "n"(TB));
}
#define W8(d, o) "=f"(d[o]), "=f"(d[o + 1]), "=f"(d[o + 2]), "=f"(d[o + 3]), "=f"(d[o + 4]), "=f"(d[o + 5]), "=f"(d[o + 6]), "=f"(d[o + 7])
#define W32(d, o) W8(d, o), W8(d, o + 8), W8(d, o + 16), W8(d, o + 24)
#define W64(d, o) W32(d, o), W32(d, o + 32)
template <int TB> __device__ __forceinline__ void mma_ss_n128_init(float (&d)[64], uint32_t da, uint32_t db) {
  asm volatile("{\n.reg .b64 da, db;\nmov.b64 da, {%64, " DHI "};\nmov.b64 db, {%65, " DHI "};\n"
               "wgmma.mma_async.sync.aligned.m64n128k16.f32.bf16.bf16 {" L64 "}, da, db, 0, 1, 1, 0, %66;\n}\n"
               : W64(d, 0) : "r"(da), "r"(db), "n"(TB));
}
template <int TB> __device__ __forceinline__ void mma_rs_n128_init(float (&d)[64], uint32_t a0, uint32_t a1, uint32_t a2, uint32_t a3, uint32_t db) {
  asm volatile("{\n.reg .b64 db;\nmov.b64 db, {%68, " DHI "};\n"
               "wgmma.mma_async.sync.aligned.m64n128k16.f32.bf16.bf16 {" L64 "}, {%64,%65,%66,%67}, db, 0, 1, 1, %69;\n}\n"
               : W64(d, 0) : "r"(a0), "r"(a1), "r"(a2), "r"(a3), "r"(db), "n"(TB));
}
template <int TB> __device__ __forceinline__ void mma_ss_n256_init(float (&d)[128], uint32_t da, uint32_t db) {
  asm volatile("{\n.reg .b64 da, db;\nmov.b64 da, {%128, " DHI "};\nmov.b64 db, {%129, " DHI "};\n"
               "wgmma.mma_async.sync.aligned.m64n256k16.f32.bf16.bf16 {" L128 "}, da, db, 0, 1, 1, 0, %130;\n}\n"
               : W64(d, 0), W64(d, 64) : "r"(da), "r"(db), "n"(TB));
}
#define L32 "%0,%1,%2,%3,%4,%5,%6,%7,%8,%9,%10,%11,%12,%13,%14,%15,%16,%17,%18,%19,%20,%21,%22,%23,%24,%25,%26,%27,%28,%29,%30,%31"
template <bool INIT> __device__ __forceinline__ void mma_rs_n64(float (&d)[32], uint32_t a0, uint32_t a1, uint32_t a2, uint32_t a3, uint32_t db) {
  if (INIT) asm volatile("{\n.reg .b64 db;\nmov.b64 db, {%36, " DHI "};\n"
               "wgmma.mma_async.sync.aligned.m64n64k16.f32.bf16.bf16 {" L32 "}, {%32,%33,%34,%35}, db, 0, 1, 1, 0;\n}\n"
               : W32(d, 0) : "r"(a0), "r"(a1), "r"(a2), "r"(a3), "r"(db));
  else asm volatile("{\n.reg .b64 db;\nmov.b64 db, {%36, " DHI "};\n"
               "wgmma.mma_async.sync.aligned.m64n64k16.f32.bf16.bf16 {" L32 "}, {%32,%33,%34,%35}, db, 1, 1, 1, 0;\n}\n"
               : R32(d, 0) : "r"(a0), "r"(a1), "r"(a2), "r"(a3), "r"(db));
}
#define L16 "%0,%1,%2,%3,%4,%5,%6,%7,%8,%9,%10,%11,%12,%13,%14,%15"
template <int O, bool INIT> __device__ __forceinline__ void mma_rs_n32(float (&d)[128], uint32_t a0, uint32_t a1, uint32_t a2, uint32_t a3, uint32_t db) {
  if (INIT) asm volatile("{\n.reg .b64 db;\nmov.b64 db, {%20, 0x00000008};\n"
               "wgmma.mma_async.sync.aligned.m64n32k16.f32.bf16.bf16 {" L16 "}, {%16,%17,%18,%19}, db, 0, 1, 1, 0;\n}\n"
               : W8(d, O), W8(d, O + 8) : "r"(a0), "r"(a1), "r"(a2), "r"(a3), "r"(db));
  else asm volatile("{\n.reg .b64 db;\nmov.b64 db, {%20, 0x00000008};\n"
               "wgmma.mma_async.sync.aligned.m64n32k16.f32.bf16.bf16 {" L16 "}, {%16,%17,%18,%19}, db, 1, 1, 1, 0;\n}\n"
               : R8(d, O), R8(d, O + 8) : "r"(a0), "r"(a1), "r"(a2), "r"(a3), "r"(db));
}
template <int S, int J> __device__ __forceinline__ void conv_step(float (&d)[128], const uint32_t (&a)[64], uint32_t db) {
  if constexpr (J >= 0 && J >= (S >> 1)) {
    mma_rs_n32<16 * J, S == 0>(d, a[4 * S], a[4 * S + 1], a[4 * S + 2], a[4 * S + 3], db + (uint32_t)((2 * J - S) * 16));
    conv_step<S, J - 1>(d, a, db);
  }
}
__device__ __forceinline__ void mma_ss_n8(float (&d)[4], uint32_t da, uint32_t db) {
  asm volatile("{\n.reg .b64 da, db;\nmov.b64 da, {%4, " DHI "};\nmov.b64 db, {%5, 0x00000008};\n"
               "wgmma.mma_async.sync.aligned.m64n8k16.f32.bf16.bf16 {%0,%1,%2,%3}, da, db, 1, 1, 1, 0, 0;\n}\n"
               : "+f"(d[0]), "+f"(d[1]), "+f"(d[2]), "+f"(d[3]) : "r"(da), "r"(db));
}
template <int N> __device__ __forceinline__ void reg_fence(float (&d)[N]) {
#pragma unroll
  for (int i = 0; i < N; i++) asm volatile("" : "+f"(d[i])::"memory");
}
template <int N> __device__ __forceinline__ void reg_fence(uint32_t (&d)[N]) {
#pragma unroll
  for (int i = 0; i < N; i++) asm volatile("" : "+r"(d[i])::"memory");
}

struct __align__(64) Params {
  unsigned* flags;
  int zero;
  uint8_t pref[128];
  const __nv_bfloat16 *gate_w, *ak, *av, *shk, *ssk, *ssd;
  CUtensorMap x, c, wq, wuk, wuv, wo, x3, y3, out, w;
};

template <int O, int N, int M> __device__ __forceinline__ void pack_frag(const float (&acc)[N], uint32_t (&pk)[M]) {
#pragma unroll
  for (int i = 0; i < 32; i++) pk[i] = pack_bf16(acc[O + 2 * i], acc[O + 2 * i + 1]);
}
template <int J0 = 0, int J1 = 8, int M> __device__ __forceinline__ void stsm_frag(const uint32_t (&pk)[M], uint32_t a) {
#pragma unroll
  for (int jj = J0; jj < J1; jj++)
    asm volatile("stmatrix.sync.aligned.m8n8.x4.shared.b16 [%0], {%1,%2,%3,%4};" ::"r"((a ^ ((jj & 3) << 5)) + (jj >> 2) * 16384),
                 "r"(pk[4 * jj]), "r"(pk[4 * jj + 1]), "r"(pk[4 * jj + 2]), "r"(pk[4 * jj + 3]) : "memory");
}

template <int N> __device__ __forceinline__ void store_scaled(const float (&acc)[N], float s0, float s1, uint32_t a, uint32_t never_zero) {
  float t[8];
#pragma unroll
  for (int jj = 0; jj < 8; jj++) {
    float v = acc[8 * jj] * s0;
    if (jj >= RST) {
      v = t[jj - RST];
      asm("{\n.reg .pred p;\nsetp.ne.u32 p, %3, 0;\n@p mul.f32 %0, %1, %2;\n}\n" : "+f"(v) : "f"(acc[8 * jj]), "f"(s0), "r"(never_zero));
    }
    const uint32_t q = pack_bf16(v, acc[8 * jj + 1] * s0);
    t[jj] = __uint_as_float(q);
    asm volatile("stmatrix.sync.aligned.m8n8.x4.shared.b16 [%0], {%1,%2,%3,%4};" ::"r"((a ^ ((jj & 3) << 5)) + (jj >> 2) * 16384), "r"(q),
                 "r"(pack_bf16(acc[8 * jj + 2] * s1, acc[8 * jj + 3] * s1)), "r"(pack_bf16(acc[8 * jj + 4] * s0, acc[8 * jj + 5] * s0)),
                 "r"(pack_bf16(acc[8 * jj + 6] * s1, acc[8 * jj + 7] * s1)) : "memory");
  }
}

struct Cons {
  uint32_t sb;
  uint32_t pf;
  int wg, tid;
  __device__ __forceinline__ void wait_full(int g) { mbar_wait(sb + SM_BAR + (B_FULL + g) * 8, (pf >> g) & 1); pf ^= 1u << g; }
  uint32_t relb;
  __device__ __forceinline__ void release(int g, int n) {
    if (tid < 2 * n) asm volatile("mbarrier.arrive.shared::cluster.b64 _, [%0];" ::"r"(relb + g * 8) : "memory");
  }
  __device__ __forceinline__ void turn_begin() { bar_sync(1 + wg, 256); }
  __device__ __forceinline__ void turn_end() { bar_arrive(2 - wg, 256); }
  __device__ __forceinline__ void staged() { __syncwarp(); if ((tid & 31) == 0) mbar_arrive(sb + SM_BAR + (B_EV + wg) * 8); }
  int zero;
  uint32_t pfree;
  __device__ __forceinline__ void wait_stage_free() { mbar_wait(sb + SM_BAR + (B_FREE + wg) * 8, pfree); pfree ^= 1; }
  __device__ __forceinline__ bool try_full(int g) { return mbar_test(sb + SM_BAR + (B_FULL + g) * 8, (pf >> g) & 1); }
};

constexpr float SM_C = 0.08838834764831845f * 1.4426950408889634f;
struct SoftState { float m0, m1, l0, l1; int shifted; };
__device__ __forceinline__ void ex2_rot(float& t, float s, uint32_t never_zero) {
  asm("{\n.reg .pred p;\nsetp.ne.u32 p, %2, 0;\n@p ex2.approx.ftz.f32 %0, %1;\n}\n" : "+f"(t) : "f"(s), "r"(never_zero));
}
__device__ __forceinline__ void pin(float a, uint32_t never_zero) {
  asm volatile("{\n.reg .pred p;\nsetp.eq.u32 p, %1, 0;\n@p st.shared.f32 [%1], %0;\n}\n" ::"f"(a), "r"(never_zero) : "memory");
}
template <int O, int N> __device__ __forceinline__ void reg_fence_part(uint32_t (&d)[32]) {
#pragma unroll
  for (int i = O; i < O + N; i++) asm volatile("" : "+r"(d[i])::"memory");
}
template <int Q, int W, int N> __device__ __forceinline__ void exp_quarter(const float (&S)[N], uint32_t (&P)[32], float (&t)[ROT], float& s0, float& s1, uint32_t nz) {
#pragma unroll
  for (int i = 8 * Q; i < 8 * Q + 8; i++) {
    float& a = t[(2 * i) % ROT];
    float& b = t[(2 * i + 1) % ROT];
    if (2 * i < ROT) { a = ex2(S[2 * i]); b = ex2(S[2 * i + 1]); }
    else { ex2_rot(a, S[2 * i], nz); ex2_rot(b, S[2 * i + 1], nz); }
    if (i < 2) { if (i) s1 = a + b; else s0 = a + b; }
    else if (i & 1) { s1 += a; s1 += b; } else { s0 += a; s0 += b; }
    if (i == 8 * Q) { pin(Q ? s1 : s0, nz); wg_wait<W>(); reg_fence_part<8 * Q, 8>(P); }
    P[i] = pack_bf16(a, b);
  }
}
template <int N> __device__ __forceinline__ void shift_scores(float (&S)[N], float d0, float d1) {
#pragma unroll
  for (int i = 0; i < N; i++) S[i] -= (i & 2) ? d1 : d0;
}
__device__ __forceinline__ bool soft_high(float s0, float s1, float lim = SM_LIMIT) { return s0 > lim || s1 > lim; }
__device__ __forceinline__ bool soft_unsafe(float s0, float s1, bool first) {
  uint32_t b0 = __ballot_sync(0xffffffffu, s0 >= SM_LOW), b1 = __ballot_sync(0xffffffffu, s1 >= SM_LOW);
  b0 |= b0 >> 1; b0 |= b0 >> 2; b1 |= b1 >> 1; b1 |= b1 >> 2;
  return __any_sync(0xffffffffu, soft_high(s0, s1)) || (first && (b0 & b1 & 0x11111111u) != 0x11111111u);
}
template <int N> __device__ __forceinline__ void soft_fix(const float (&S)[N], float (&O)[64], SoftState& z, bool first, float& d0, float& d1) {
  d0 = d1 = first ? -INFINITY : 0.f;
#pragma unroll
  for (int j = 0; j < N / 4; j++) { d0 = fmaxf(d0, fmaxf(S[4 * j], S[4 * j + 1])); d1 = fmaxf(d1, fmaxf(S[4 * j + 2], S[4 * j + 3])); }
  d0 = fmaxf(d0, __shfl_xor_sync(0xffffffffu, d0, 1)); d1 = fmaxf(d1, __shfl_xor_sync(0xffffffffu, d1, 1));
  d0 = fmaxf(d0, __shfl_xor_sync(0xffffffffu, d0, 2)); d1 = fmaxf(d1, __shfl_xor_sync(0xffffffffu, d1, 2));
  const float sc0 = ex2(-fmaxf(d0, 0.f)), sc1 = ex2(-fmaxf(d1, 0.f));
  z.m0 += d0; z.m1 += d1; z.l0 *= sc0; z.l1 *= sc1; z.shifted = 1;
#pragma unroll
  for (int j = 0; j < 16; j++) { O[4 * j] *= sc0; O[4 * j + 1] *= sc0; O[4 * j + 2] *= sc1; O[4 * j + 3] *= sc1; }
}
template <int N> __device__ __forceinline__ void mask_diag(float (&S)[N], float nd) {
  asm volatile("" : "+f"(nd));
#pragma unroll
  for (int i = 0; i < 32; i++) {
    const float beyond = __saturatef(nd + (float)(8 * (i >> 2) + (i & 1) - 4 * (i & 2)));
    S[N - 32 + i] = fmaf(beyond, -3.0e38f, S[N - 32 + i]);
  }
}
__device__ __forceinline__ float quad_sum(float v) {
  v += __shfl_xor_sync(0xffffffffu, v, 1);
  v += __shfl_xor_sync(0xffffffffu, v, 2);
  return v;
}
__device__ __forceinline__ void issue_qk(float (&S)[64], const uint32_t (&Q)[32], uint32_t dk) {
  mma_rs_n128_init<0>(S, Q[0], Q[1], Q[2], Q[3], dk);
#pragma unroll
  for (int s = 1; s < 8; s++) mma_rs_n128<0>(S, Q[4 * s], Q[4 * s + 1], Q[4 * s + 2], Q[4 * s + 3], dk + (s >> 2) * 1024 + (s & 3) * 2, 1);
}
__device__ __forceinline__ void issue_qk(float (&S)[32], const uint32_t (&Q)[32], uint32_t dk) {
  mma_rs_n64<true>(S, Q[0], Q[1], Q[2], Q[3], dk);
#pragma unroll
  for (int s = 1; s < 8; s++) mma_rs_n64<false>(S, Q[4 * s], Q[4 * s + 1], Q[4 * s + 2], Q[4 * s + 3], dk + (s >> 2) * 1024 + (s & 3) * 2);
}
__device__ __forceinline__ void load_q(uint32_t (&Q)[32], uint32_t a) {
  __syncwarp();
#pragma unroll
  for (int jj = 0; jj < 8; jj++)
    asm volatile("ldmatrix.sync.aligned.m8n8.x4.shared.b16 {%0,%1,%2,%3}, [%4];" : "=r"(Q[4 * jj]), "=r"(Q[4 * jj + 1]), "=r"(Q[4 * jj + 2]), "=r"(Q[4 * jj + 3])
                 : "r"((a ^ ((jj & 3) << 5)) + (jj >> 2) * 16384) : "memory");
}
template <int H> __device__ __forceinline__ void issue_pv(float (&O)[64], const uint32_t (&P)[32], uint32_t dv, int acc, bool on) {
  if (on) {
#pragma unroll
    for (int s = 4 * H; s < 4 * H + 4; s++) {
      mma_rs_n128<1>(O, P[4 * s], P[4 * s + 1], P[4 * s + 2], P[4 * s + 3], dv + s * 128, s != 0 ? 1 : acc);
      if (s & 1) wg_commit();
    }
  } else { wg_commit(); wg_commit(); }
}
constexpr uint32_t DG = GR >> 4;
__device__ __forceinline__ void stage_q2(Cons& c, const float (&O)[64], uint32_t (&P)[32], uint32_t stg) {
  wg_commit(); wg_commit(); wg_commit(); wg_commit();
  c.turn_end();
  pack_frag<0>(O, P);
  stsm_frag(P, stg);
}
__device__ __forceinline__ void attn_half(Cons& c, float (&O)[64], uint32_t (&P)[32], uint32_t (&Q)[32], bool nextq, uint32_t stg, SoftState& z, uint32_t dkk, uint32_t dv0, float dmask, int last) {
  float S[32];
  c.turn_begin();
  wg_fence();
  issue_qk(S, Q, dkk + (last ? 8 : 2) * DG);
  wg_commit();
  issue_pv<0>(O, P, dv0 + 10 * DG, 1, last);
  issue_pv<1>(O, P, dv0 + 10 * DG, 1, last);
  c.turn_end();
  c.wait_full(last ? 12 : 4);
  wg_wait<4>();
  reg_fence(S);
  c.release(last ? 8 : 2, 2);
  reg_fence(Q);
  if (nextq) load_q(Q, stg);
  if (last) bar_sync(6, 256);
  mask_diag(S, dmask);
  float s0, s1, d0 = z.m0, d1 = z.m1;
#pragma unroll 1
  for (int pass = 0;; pass++) {
    if (z.shifted) shift_scores(S, d0, d1);
    float tr[ROT];
    exp_quarter<0, 3>(S, P, tr, s0, s1, c.sb);
    exp_quarter<1, 2>(S, P, tr, s0, s1, c.sb);
    pin(s1, c.sb); wg_wait<0>(); reg_fence_part<16, 16>(P); reg_fence(O);
    if (!soft_unsafe(s0, s1, !last) || pass) break;
    soft_fix(S, O, z, !last, d0, d1);
  }
  z.l0 += s0; z.l1 += s1;
  c.release(10, last ? 2 : 0);
  if (!last) c.wait_full(6);
}

template <int V> struct IC { static constexpr int value = V; };
__device__ __forceinline__ int conv_next(int g, bool spare) { return g >= NGR - 2 ? g - (NGR - 4) : !spare && g == 4 ? 1 : g + 2; }
__device__ __forceinline__ void conv_final(uint32_t rb, uint32_t yb, bool on) {
  const uint4 q0 = lds128(rb), q1 = lds128(rb + 4096), q2 = lds128(rb + 8192), q3 = lds128(rb + 12288);
  auto fin = [&](uint32_t x0, uint32_t x1, uint32_t x2, uint32_t x3) { return hadd2(hadd2(x0, x1), hadd2(x2, x3)); };
  asm volatile("{\n.reg .pred p;\nsetp.ne.b32 p, %5, 0;\n@p st.shared.v4.b32 [%0], {%1,%2,%3,%4};\n}\n" ::"r"(yb), "r"(fin(q0.x, q1.x, q2.x, q3.x)),
               "r"(fin(q0.y, q1.y, q2.y, q3.y)), "r"(fin(q0.z, q1.z, q2.z, q3.z)), "r"(fin(q0.w, q1.w, q2.w, q3.w)), "r"((int)on) : "memory");
}
__device__ __forceinline__ void conv_tasks(Cons& c, const Params& p, int ntask, bool spare, int ch, int chstep, int c5, uint32_t dd, uint32_t dkk, int w, int lane) {
  const uint32_t sb = c.sb;
  int g = 2 + c.wg;
  uint32_t rb = sb + g * GR;
  const uint32_t yb = sb + c.wg * 8192 + c.tid * 16;
  const int gt = 8 * w + (lane >> 2) + (lane & 3);
  uint32_t a[64], hb;
  auto lda = [&](int s) {
    a[4 * s] = lds32(hb + s * 256); a[4 * s + 1] = lds32(hb + s * 256 + 128);
    a[4 * s + 2] = lds32(hb + s * 256 + 16); a[4 * s + 3] = lds32(hb + s * 256 + 144);
  };
  auto first_a = [&]() {
    hb = sb + g * GR + WBYTES - 28 + gt * 4;
    lda(0); lda(15);
  };
  c.wait_full(g);
  first_a();
#pragma unroll 1
  for (int i = 0; i < ntask; i++) {
    const uint32_t base = sb + g * GR;
    lda(1); lda(14);
    a[0] = hadd2(a[0], gt == 7 ? dd : 0u); a[2] = hadd2(a[2], gt == 3 ? dd : 0u);
    float acc[128];
    const uint32_t db = dkk + ((WPL / 16 - 1) << 16) + g * DG + WZ / 16;
    c.turn_begin();
    auto pair = [&](auto kc) {
      constexpr int k = decltype(kc)::value;
      if (k < 7) wg_fence();
      if (k == 6) c.turn_end();
      conv_step<k, 7>(acc, a, db);
      conv_step<15 - k, 7>(acc, a, db);
      if (k < 6) { lda(k + 2); lda(13 - k); }
      if (k == 0) conv_final(rb, yb, i > 0);
      if (k == 1) {
        conv_final(rb + 2048, yb + 2048, i > 0);
        __syncwarp();
        if (lane == 0 && i > 0) mbar_arrive(sb + SM_BAR + (B_EV + c.wg) * 8);
      }
      if (k == 6) dd = __bfloat16_as_ushort(p.ssd[(ch + chstep + (i == 1 ? c5 : 0)) & (DM - 1)]);
    };
    pair(IC<0>()); pair(IC<1>()); pair(IC<2>()); pair(IC<3>()); pair(IC<4>()); pair(IC<5>()); pair(IC<6>()); pair(IC<7>());
    wg_commit();
    g = conv_next(g, spare);
    ch += chstep;
    rb = base + c.tid * 16;
    if (i + 1 < ntask) c.wait_full(g);
    const bool fr = mbar_test(sb + SM_BAR + (B_FREE + c.wg) * 8, c.pfree);
    wg_wait<0>();
    reg_fence(acc);
    reg_fence(a);
    bar_sync(3 + c.wg, 128);
    first_a();
    const int tw = (lane & 3) + w;
    const uint32_t xb = base + w * 4096 + tw * 32 + (lane >> 2) * 4;
    [[maybe_unused]] float t0[EROT + 1];
#pragma unroll
    for (int j = 0; j < 32; j++) {
      uint32_t ad = xb + j * 128;
      float v0 = acc[4 * j], v1 = acc[4 * j + 1];
      if (EROT && j > EROT) {
        v0 = t0[j % (EROT + 1)];
        asm("{\n.reg .pred p;\nsetp.ne.u32 p, %3, 0;\n@p add.f32 %0, %1, %2;\n}\n" : "+f"(v0) : "f"(acc[4 * j]), "f"(acc[j > 0 ? 4 * j - 2 : 0]), "r"(sb));
      } else if (j > 0) v0 += acc[j > 0 ? 4 * j - 2 : 0];
      if (j > 0) v1 += acc[j > 0 ? 4 * j - 1 : 0];
      uint32_t v = pack_bf16(v0, v1);
      t0[j % (EROT + 1)] = __uint_as_float(v);
      if (j == 31 && tw >= 4) { v = 0; ad -= 4096; }
      asm volatile("st.shared.b32 [%0], %1;" ::"r"(ad), "r"(v) : "memory");
    }
    if (!fr) c.wait_stage_free(); else c.pfree ^= 1;
  }
  bar_sync(3 + c.wg, 128);
  conv_final(rb, yb, true);
  conv_final(rb + 2048, yb + 2048, true);
  c.staged();
}

__global__ void __cluster_dims__(2, 1, 1) __launch_bounds__(NTHREADS, 1) mega_kernel(const __grid_constant__ Params p) {
  extern __shared__ __align__(1024) uint8_t smem_raw[];
  const uint32_t sb = smem_u32(smem_raw);
  if (threadIdx.x - 64 < 32) { prefetch_tm(&p.c); prefetch_tm(&p.wuk + (blockIdx.x & 1)); }
  const int wgi = __shfl_sync(0xffffffffu, threadIdx.x >> 7, 0);
  const int warp = __shfl_sync(0xffffffffu, threadIdx.x >> 5, 0);
  const uint32_t rank = blockIdx.x & 1;
  int slot;
  {
    uint32_t smid; asm volatile("mov.u32 %0, %smid;" : "=r"(smid));
    slot = p.pref[((smid >> 1) + (threadIdx.x & (smid >> 16))) & 127];
  }
  if (warp >= 3) {
    if (elect()) {
#pragma unroll
      for (int k = 0; k < 4; k++) mbar_init(sb + SM_BAR + ((warp - 3) * 4 + k) * 8, k == 1 && warp == 7 ? 11 : warp < (k ? 7 : 8) ? 1 : 4);
      if (warp == 7) { mbar_init(sb + SM_BAR + B_TICK * 8, 1); mbar_expect_tx(sb + SM_BAR + B_SLOT * 8, 8); mbar_expect_tx(sb + SM_BAR + B_TICK * 8, 4); }
      asm volatile("fence.mbarrier_init.release.cluster;" ::: "memory");
    }
    __syncwarp();
  }
  cluster_arrive();
  slot = __shfl_sync(0xffffffffu, slot, 0);
  const int pref = slot;
  if (warp < 4) {
    asm volatile("setmaxnreg.dec.sync.aligned.u32 40;");
    if (warp == 1 + 4 * rank) {
      unsigned taken = threadIdx.x == 32;
#pragma unroll 1
      for (int n = 0; n < NSLOT; n++) {
        asm volatile("{\n.reg .pred p;\nsetp.ne.b32 p, %0, 0;\n@p atom.relaxed.gpu.global.exch.b32 %0, [%1], 1;\n}\n" : "+r"(taken) : "l"(CLAIMP(slot)) : "memory");
        if (!__any_sync(0xffffffffu, taken)) break;
        slot = slot == NSLOT - 1 ? 0 : slot + 1;
      }
    }
    cluster_wait();
    if (threadIdx.x == 32) {
      send_both(sb + SM_BAR + B_SLOT * 8, (V_SLOT - B_SLOT) * 8 + rank * 4, slot | pref << 8);
    }
    if (warp == 2) {
#pragma unroll 1
      for (int kk = 0; kk < 4; kk++) {
        const int g0 = 2 + 3 * kk;
        const uint32_t fb = sb + SM_BAR + (B_FULL + g0) * 8;
        if (elect()) {
          mbar_expect_tx(fb, 3 * GR);
          tma2d(sb + g0 * GR, &p.c, kk * 64, (KV_ROW(pref & 7, 0) + rank) * 128, fb);
          tma3d_mc(sb + (g0 + 1 + rank) * GR, rank ? &p.wuv : &p.wuk, 0, kk * 64, ((pref & 56) >> 1) + 2 * KV_HEAD(pref & 7, 0), fb);
        }
        if (kk < 3) {
          uint32_t c0, c1;
          asm volatile("mov.u32 %0, %clock;" : "=r"(c0));
          do asm volatile("mov.u32 %0, %clock;" : "=r"(c1)); while (c1 - c0 < (kk ? X_D2 : X_DELAY));
        }
      }
      prefetch_tm(&p.x); prefetch_tm(&p.wq);
    }
  }
  int grp, idx, lb;
  int cn, cch, cstep;
  bool spare, redo;
  auto get_slot = [&]() {
    mbar_wait(sb + SM_BAR + B_SLOT * 8, 0);
    const uint32_t sv0 = __shfl_sync(0xffffffffu, lds32(sb + SM_BAR + V_SLOT * 8), 0), sv1 = __shfl_sync(0xffffffffu, lds32(sb + SM_BAR + V_SLOT * 8 + 4), 0);
    grp = (sv0 & 255) >> 3; idx = sv0 & 7; lb = (sv0 & 255) * 2 + rank;
    spare = grp == 8; redo = spare || sv0 != sv1;
    cn = CN_SPARE; cch = spare ? lb - NMAIN : 4 * CN_SPARE + 4 * lb; cstep = spare ? 4 : 1;
  };
  auto get_ticket = [&]() {
    mbar_wait(sb + SM_BAR + B_TICK * 8, 0);
    const int tk = __shfl_sync(0xffffffffu, lds32(sb + SM_BAR + V_TICK * 8), 0);
    cn = tk < NTICK ? 5 : 4;
    return 4 * NMAIN - 4 * lb - 4 + 2 * tk + rank;
  };

  if (wgi == 0) {
    asm volatile("setmaxnreg.dec.sync.aligned.u32 40;");
    const int lane = threadIdx.x & 31;
    cluster_arrive();
    get_slot();
    uint32_t pe = 0;
    auto acquire = [&](int g, int n, uint32_t m) {
      int i = g;
#pragma unroll 1
      do mbar_wait1(sb + SM_BAR + (B_EMPTY + i) * 8, (pe >> i) & 1); while (++i < g + n);
      pe ^= m << g;
    };
    if (warp == 3) {
      if (!spare) {
        const int s0 = lb * 16;
#pragma unroll 1
        for (int cg = 0; cg < 16; cg++) {
          if (cg == UP0 || cg == UP1) {
#pragma unroll 1
            for (int n = 0; n < 20 && !__any_sync(0xffffffffu, mbar_try(sb + SM_BAR + B_SLOT * 8, cg == UP0)); n++);
          } else if (cg < UP0) __nanosleep(US0);
          if (cg == UP1 && lane == rank * 32) send_both(sb + SM_BAR + B_TICK * 8, (V_TICK - B_TICK) * 8, atomicInc(FLAG(F_TICK), 0x7fffffffu));
          const int ch = cg * 64 + 2 * lane;
          const uint32_t* kp = reinterpret_cast<const uint32_t*>(p.ak + (size_t)s0 * DM + ch);
          const uint32_t* vp = reinterpret_cast<const uint32_t*>(p.av + (size_t)s0 * DM + ch);
          const uint4 sw = __ldg(reinterpret_cast<const uint4*>(p.shk + ch * 4));
          uint32_t k3 = 0, k2 = 0, k1 = 0, k0 = 0, up = 0;
          if (lb > 0) { k3 = ldg_stream(kp - 4 * 512); k2 = ldg_stream(kp - 3 * 512); k1 = ldg_stream(kp - 2 * 512); k0 = ldg_stream(kp - 512); up = ldg_stream(vp - 512); }
          const uint32_t w0 = __byte_perm(sw.x, sw.z, 0x5410), w1 = __byte_perm(sw.x, sw.z, 0x7632);
          const uint32_t w2 = __byte_perm(sw.y, sw.w, 0x5410), w3 = __byte_perm(sw.y, sw.w, 0x7632);
          up = hmul2(hfma2(k0, w0, hfma2(k1, w1, hfma2(k2, w2, hmul2(k3, w3)))), up);
#pragma unroll 1
          for (int hb = 0; hb < 2; hb++) {
            uint32_t kk[8], u[8];
#pragma unroll
            for (int r = 0; r < 8; r++) { kk[r] = ldg_stream(kp + r * 512); u[r] = ldg_stream(vp + r * 512); }
#pragma unroll
            for (int r = 0; r < 8; r++) {
              k3 = k2; k2 = k1; k1 = k0; k0 = kk[r];
              u[r] = hmul2(hfma2(k0, w0, hfma2(k1, w1, hfma2(k2, w2, hmul2(k3, w3)))), u[r]);
            }
            if (lane == 0) asm volatile("cp.async.bulk.wait_group.read 0;" ::: "memory");
            __syncwarp();
            const uint32_t dst = sb + SM_UST + lane * 32 + ((lane & 4) << 2);
#pragma unroll
            for (int cc = 0; cc < 2; cc++) {
              const uint32_t sel = cc ? 0x7632 : 0x5410;
              asm volatile("st.shared.v4.b32 [%0], {%1,%2,%3,%4};" ::"r"(dst + cc * 1024), "r"(__byte_perm(u[6], u[5], sel)), "r"(__byte_perm(u[4], u[3], sel)),
                           "r"(__byte_perm(u[2], u[1], sel)), "r"(__byte_perm(u[0], up, sel)) : "memory");
              asm volatile("st.shared.v4.b32 [%0], {%1,%2,%3,%4};" ::"r"((dst ^ 16) + cc * 1024), "r"(__byte_perm(u[7], u[6], sel)), "r"(__byte_perm(u[5], u[4], sel)),
                           "r"(__byte_perm(u[3], u[2], sel)), "r"(__byte_perm(u[1], u[0], sel)) : "memory");
            }
            fence_async_smem();
            __syncwarp();
            if (lane == 0) {
              asm volatile("cp.async.bulk.tensor.3d.global.shared::cta.bulk_group.L2::cache_hint [%0, {%2, %3, %4}], [%1], %5;\ncp.async.bulk.commit_group;"
                           ::"l"(&p.w), "r"(sb + SM_UST), "r"(WZ / 2 + lb * 16 + (hb ^ 1) * (WPL / 2)), "r"(cg * 32), "r"(0), "l"(cg >= UP0 && cg < UP1 ? EV_FIRST : EV_NORMAL) : "memory");
            }
            up = u[7];
            kp += 8 * 512; vp += 8 * 512;
          }
          if ((cg & (cg + 1)) == 0 && lane == 0) {
            asm volatile("cp.async.bulk.wait_group 0;" ::: "memory");
            fence_release();
            flag_add(FLAG(F_U + 32 - __clz(cg)));
          }
        }
        prefetch_tm(&p.wo); prefetch_tm(&p.x3); prefetch_tm(&p.y3); prefetch_tm(&p.out);
      } else {
#pragma unroll 1
        for (int i = 0, g = 2; i < 32; i++) {
          acquire(g, 2, 3);
          if (elect()) {
            const uint32_t fb = sb + SM_BAR + (B_FULL + g) * 8;
            if (i == 0) { mbar_expect_tx(fb - 8, 2048); bulk_g2s(sb + GR, p.gate_w, 2048, fb - 8); }
            mbar_expect_tx(fb, 2 * GR);
            tma3d(sb + g * GR, &p.x3, 0, (lb - NMAIN) * 512 + (i >> 3) * 128, (i & 7) * 2, fb);
          }
          g = g == NGR - 2 ? 2 : g + 2;
        }
        bar_arrive(5, 64);
      }
      unsigned long long t0, t1;
      asm volatile("mov.u64 %0, %globaltimer;" : "=l"(t0));
      auto check = [&]() {
        asm volatile("mov.u64 %0, %globaltimer;" : "=l"(t1));
        if (t1 - t0 > 2000000000ull) __trap();
      };
      if (!spare) {
        unsigned v;
        do {
          __nanosleep(PSL);
          check();
          asm volatile("ld.acquire.gpu.global.u32 %0, [%1];" : "=r"(v) : "l"(FLAG(lane & 1 ? F_Y + idx : F_GATE)) : "memory");
        } while (__any_sync(0xffffffffu, v < (lane & 1 ? 128 : 32)));
        __syncwarp();
        if (lane == 0) mbar_arrive(sb + SM_BAR + B_SLOT * 8);
      }
      if (lane == 0) {
        while (!mbar_try(sb + SM_BAR + B_DONE * 8, 0)) check();
      }
    } else if (warp != 0) {
      const int w = warp - 1;
      int ne = 12 + (CN_SPARE + 1 - w) / 2, c5 = 0;
      int cg = 2 + w, ch = cch + w * cstep;
#pragma unroll 1
      for (int e = spare ? 12 : 0; e < ne; e++) {
        const int rnd = e >= 6, k = e - 6 * rnd, rt = k == 4 ? idx : 15 - idx;
        uint8_t* dst = k < 4 ? g_kv + (size_t)(((k & 1) * 16 + 2 * grp + KV_HEAD(idx, k >> 1)) * 16 + KV_ROW(idx, k >> 1) + rank) * 32768 + w * 8192
                     : k < 6 ? g_cimg + (size_t)(rt * 32 + 16 * rnd + 2 * grp + rank) * 32768 + (w ^ (k & 1)) * 8192
                             : g_w + (size_t)ch * WSTRIDE + WZ;
        const uint32_t src = sb + w * 8192;
        if (e == 11) { c5 = get_ticket(); ne = 12 + ((cn + 1 - w) >> 1); }
        if (e == 6) flag_wait(FLAG(F_AD + grp), 32);
        mbar_wait1(sb + SM_BAR + (B_EV + w) * 8, e & 1);
        if (lane < 4 && k >= 6 && (!spare || e < ne - 6)) mbar_arrive_cluster(sb + SM_BAR + (B_EMPTY + cg) * 8, lane & 1);
        fence_async_smem();
        if (elect()) {
          const uint32_t cs = k >= 6 ? 4096 : 1024;
#pragma unroll 1
          for (uint32_t i = 0; i < (k >= 6 ? 4096 : 16384); i += cs) {
            const uint32_t o = i + (i & 8192);
            asm volatile("cp.async.bulk.global.shared::cta.bulk_group.L2::cache_hint [%0], [%1], %2, %3;" ::"l"(dst + o), "r"(src + o), "r"(cs),
                         "l"(e == 4 || e == 5 || spare ? EV_FIRST : EV_NORMAL) : "memory");
            asm volatile("cp.async.bulk.commit_group;\ncp.async.bulk.wait_group.read 1;" ::: "memory");
          }
          asm volatile("cp.async.bulk.wait_group 0;" ::: "memory");
          mbar_arrive(sb + SM_BAR + (B_FREE + w) * 8);
        }
        __syncwarp();
        if (lane < (e == 11 || (e == ne - 1 && !spare) ? 2 : 0)) mbar_arrive_cluster(sb + SM_BAR + (B_EMPTY + (e == 11)) * 8, lane);
        if (k >= 3) {
          fence_release();
          const unsigned fl = k == 3 ? F_KV + rnd * 8 + grp : k < 6 ? F_CTX + rt * 2 + rnd : F_Y + ((unsigned)ch >> 7);
          if (lane <= (e == 5)) flag_add(FLAG(lane ? F_AD + grp : fl));
        }
        if (k >= 6) { cg = conv_next(cg, spare); ch += 2 * cstep + (k == 7 ? c5 : 0); }
      }
      if (lane == 0) mbar_arrive(sb + SM_BAR + B_DONE * 8);
    } else {
#pragma unroll 1
      for (int rnd = 0; rnd < (spare ? 0 : 2); rnd++) {
        const int hp = 16 * rnd + 2 * grp, head = hp + rank;
#pragma unroll 1
        for (int kk = rnd || redo ? 0 : 4; kk < 32; kk++) {
          const int g0 = 2 + 3 * (kk & 3);
          acquire(g0, kk < 4 ? 3 : 1, 7);
          if (elect()) {
            const uint32_t fb = sb + SM_BAR + (B_FULL + g0) * 8;
            mbar_expect_tx(fb, 3 * GR);
            if (kk < 16) {
              tma2d_p(sb + g0 * GR, &p.c, (kk & 7) * 64, (KV_ROW(idx, kk >> 3) + rank) * 128, fb, rnd);
              tma3d_mc_p(sb + (g0 + 1 + rank) * GR, rank ? &p.wuv : &p.wuk, 0, (kk & 7) * 64, (hp + KV_HEAD(idx, kk >> 3)) * 2, fb, kk >= 8);
            } else {
              tma2d_mc(sb + (g0 + rank) * GR, &p.x, (kk - 16) * 64, (rank ? 15 - idx : idx) * 128, fb);
              tma3d<true>(sb + (g0 + 2) * GR, &p.wq, 0, (kk - 16) * 64, head * 2, fb);
            }
          }
        }
        flag_wait(FLAG(F_KV + rnd * 8 + grp), 32);
        fence_async_all();
        int g0 = 2;
#pragma unroll 1
        for (int n = 0; n < 36; n += n == 0 || n == 33 ? 2 : 1) {
          const int it = (n >> 1) - (n & 1);
          const int blk = it & 15 ? (it <= idx ? it - 1 : 15 - it) : it ? 15 - idx : idx;
          acquire(g0, n < 7 ? 2 : 1, 3);
          if (elect()) {
            const uint32_t fb = sb + SM_BAR + (B_FULL + g0) * 8;
            if (n == 5) mbar_arrive(sb + SM_BAR + B_SLOT * 8);
            mbar_expect_tx(fb, 2 * GR);
            asm volatile("cp.async.bulk" TMA_MB ".L2::cache_hint [%0], [%1], %2, [%3], %4;" ::"r"(sb + g0 * GR), "l"(g_kv + (unsigned)((((n & 1) * 16 + (head & 15)) * 16 + blk) * 32768)),
                         "r"(2 * GR), "r"(fb), "l"(it >= 8 ? EV_FIRST : EV_NORMAL) : "memory");
          }
          g0 = g0 == 12 ? 2 : g0 + (n == 13 || n == 19 ? 4 : 2);
        }
      }
      int c5 = 0;
      if (spare) { bar_sync(5, 64); pe = 0x3FC0; }
      else c5 = get_ticket();
      auto conv_fill = [&](int g, int ch) {
        acquire(g, 1, 1);
        if (elect()) {
          const uint32_t fb = sb + SM_BAR + (B_FULL + g) * 8;
          mbar_expect_tx(fb, WBYTES + 4096);
          bulk_g2s<true>(sb + g * GR, g_w + (size_t)ch * WSTRIDE, WBYTES, fb);
          bulk_g2s<true>(sb + g * GR + WBYTES, p.ssk + (size_t)ch * SEQ, 4096, fb);
        }
      };
#pragma unroll 1
      for (int i = 0, g = 2; i < cn; i++) {
        if ((i & 15) == 0) { flag_wait(FLAG(F_U + (spare ? 32 - __clz(i >> 4) : 4)), NMAIN); fence_async_all(); }
        conv_fill(g + (i & 1), cch + i * cstep + (i == 4 ? c5 : 0));
        if (i & 1) g = conv_next(g, spare);
      }
      if (!spare) {
        const int rt = 2 * grp + rank, ct = idx;
        int g0 = P3G, top = 12;
        const uint8_t* src = g_cimg + (unsigned)((rt * 64 + 32) * GR);
#pragma unroll 1
        for (int kb = 0; kb < 64; kb++) {
          if (!(kb & 31)) { flag_wait(FLAG(F_CTX + rt * 2 + ((kb ^ 32) >> 5)), 32); fence_async_all(); if (kb) src -= 64 * GR; }
          acquire(g0, kb < 11 ? 2 : 1, 3);
          if (elect()) {
            const uint32_t fb = sb + SM_BAR + (B_FULL + g0) * 8;
            mbar_expect_tx(fb, 2 * GR);
            bulk_g2s<true>(sb + g0 * GR, src, GR, fb);
            tma2d_mc<true>(sb + (g0 + 1) * GR + rank * 8192, &p.wo, ct * 128 + rank * 64, (kb ^ 32) * 64, fb);
          }
          src += GR;
          g0 = g0 == (kb < XK ? 12 : kb < YK ? 10 : 8) ? (kb == 3 ? 2 : 0) : g0 + 2;
          if (kb == XK || (kb >= YK && top == P3Y && (kb == 63 || mbar_test(sb + SM_BAR + B_SLOT * 8, 1)))) {
            const bool j = kb != XK;
            if (j) { mbar_wait1(sb + SM_BAR + B_SLOT * 8, 1); fence_async_all(); }
            acquire(top, 1, 0);
            if (elect()) {
              const uint32_t fb = sb + SM_BAR + (B_FULL + top) * 8;
              mbar_expect_tx(fb, j ? 2 * GR + 512 : 2 * GR);
              if (j) bulk_g2s(sb + SM_GATE, g_gate + (unsigned)(rt * 128), 512, fb);
              tma3d(sb + top * GR, j ? &p.y3 : &p.x3, 0, (j ? ct : rt) * 128, (j ? rt : ct) * 2, fb);
            }
            top -= 2;
          }
        }
        unsigned n = 0;
        if (lane == 0) n = atomicInc(FLAG(F_EXIT), 0x7fffffffu);
        if (__any_sync(0xffffffffu, n == NMAIN - 1)) {
#pragma unroll
          for (int i = lane; i < 96; i += 32) *reinterpret_cast<uint2*>(FLAG(i)) = make_uint2(0, 0);
        }
      }
      if (lane == 0) mbar_arrive(sb + SM_BAR + B_DONE * 8);
    }
    __syncwarp();
    cluster_wait();
  } else {
    asm volatile("setmaxnreg.inc.sync.aligned.u32 232;");
    Cons c;
    c.sb = sb; c.pf = 0; c.wg = wgi - 1; c.tid = threadIdx.x & 127;
    const int lane = threadIdx.x & 31, t = lane & 3;
    const int row = c.wg * 64 + (warp & 3) * 16 + (lane >> 2);
    const uint32_t dkk = desc_k(sb), dk0 = dkk + c.wg * 512, dm0 = desc_mn<8192>(sb), dv0 = desc_mn<16384>(sb);
    const uint32_t dsw = DG + 512 - c.wg * 1024;
    if (c.wg == 1) bar_arrive(1, 256);
    c.pfree = 1;
    asm("mapa.shared::cluster.u32 %0, %1, %2;" : "=r"(c.relb) : "r"(sb + SM_BAR + (B_EMPTY + (c.tid >> 1)) * 8), "r"(c.tid & 1));
    c.zero = p.zero;
    const uint32_t stg = sb + (c.wg * 64 + (warp & 3) * 16 + ((lane >> 3) & 1) * 8 + (lane & 7)) * 128 + (((lane >> 4) ^ (lane & 7)) << 4);

    uint32_t dd0;
    auto load_dd = [&]() { asm volatile("ld.global.nc.u16 %0, [%1];" : "=r"(dd0) : "l"(p.ssd + (unsigned)(cch + c.wg * cstep + (lane & c.zero)))); };
    int pass = c.zero;
#pragma unroll 1
    do {
    if (pass) {
      load_dd();
#pragma unroll 1
      for (int g = 2; g < NGR; g += 3) { mbar_wait(sb + SM_BAR + (B_FULL + g) * 8, 0); c.release(g, 3); }
      c.pf = 0x924;
    if (spare) {
      c.wait_full(1);
      int g = 2;
#pragma unroll 1
      for (int r = 0; r < 4; r++) {
        float d[4] = {0.f, 0.f, 0.f, 0.f}, e[4] = {0.f, 0.f, 0.f, 0.f};
#pragma unroll 1
        for (int kb = 0; kb < 16; kb += 2) {
          c.wait_full(g);
          wg_fence();
#pragma unroll 1
          for (int k = 0; k < 4; k++) {
            mma_ss_n8(d, dk0 + g * DG + k * 2, dkk + DG + kb * 8 + k * 2);
            mma_ss_n8(e, dk0 + (g + 1) * DG + k * 2, dkk + DG + kb * 8 + 8 + k * 2);
          }
          wg_commit();
          wg_wait<0>();
          c.release(g, 2);
          g = g == NGR - 2 ? 2 : g + 2;
        }
        reg_fence(d); reg_fence(e);
        d[0] += e[0]; d[2] += e[2];
        if (t == 0) {
          float* gp = g_gate + (unsigned)((lb - NMAIN) * 512 + r * 128 + row);
          gp[0] = rcp(1.f + ex2(-1.4426950408889634f * d[0])); gp[8] = rcp(1.f + ex2(-1.4426950408889634f * d[2]));
        }
      }
      fence_release();
      __syncwarp();
      if (lane == 0) flag_add(FLAG(F_GATE));
    }
    } else cluster_wait();
    get_slot();
    } while (redo && !pass++);
    const float dmask = (float)(2 * t - (row & 63));
    int c5 = 0;
    uint32_t pv[32];
#pragma unroll 1
    for (int rnd = 0; rnd < (spare ? 0 : 2); rnd++) {
      float O[64];
      uint32_t Q[32];
      c.wait_full(2);
#pragma unroll 1
      for (int tile = c.zero; tile < 2; tile++) {
        float acc[128];
        const bool single = tile == 0;
        {
          const uint32_t a = dk0 + 2 * DG, b = dm0 + 3 * DG;
          c.turn_begin();
          wg_fence();
          mma_ss_n256_init<1>(acc, a, b);
#pragma unroll
          for (int k = 1; k < 4; k++) mma_ss_n256<1>(acc, a + k * 2, b + k * 128);
          wg_commit();
          if (single) c.turn_end();
        }
#pragma unroll 1
        for (int kb = 1; kb < 8; kb++) {
          const int g0 = 2 + 3 * (kb & 3);
          const uint32_t a = dk0 + g0 * DG, b = dm0 + (g0 + 1) * DG;
          const bool second = (kb == 1 && !single) || kb == 7;
          if (!second) { wg_wait<0>(); c.release(2 + 3 * ((kb - 1) & 3), 3); }
          c.wait_full(g0);
          if (!second) c.turn_begin();
          wg_fence();
#pragma unroll
          for (int k = 0; k < 4; k++) mma_ss_n256<1>(acc, a + k * 2, b + k * 128);
          wg_commit();
          if (kb != 6) c.turn_end();
          if (second) { wg_wait<1>(); c.release(2 + 3 * ((kb - 1) & 3), 3); }
          if (tile == 1 && kb == 3) { c.wait_stage_free(); stsm_frag<0, 4>(pv, stg); }
          if (tile == 1 && kb == 4) { stsm_frag<4, 8>(pv, stg); c.staged(); }
        }
        c.wait_stage_free();
        const bool nxt = c.try_full(2);
        wg_wait<0>();
        reg_fence(acc);
        c.release(11, 3);
        store_scaled(acc, SM_C, SM_C, stg, sb);
        c.staged();
        pack_frag<64>(acc, pv);
        if (!nxt) mbar_wait(sb + SM_BAR + (B_FULL + 2) * 8, (c.pf >> 2) & 1);
        c.pf ^= 4;
      }
      {
        float qa[64];
        float (&qb)[64] = O;
        {
          const uint32_t a = dk0 + 2 * DG, b = dm0 + 4 * DG;
          c.turn_begin();
          wg_fence();
          mma_ss_n128_init<1>(qa, a, b);
          mma_ss_n128_init<1>(qb, a + dsw, b);
#pragma unroll
          for (int k = 1; k < 4; k++) {
            mma_ss_n128<1>(qa, a + k * 2, b + k * 128);
            mma_ss_n128<1>(qb, a + dsw + k * 2, b + k * 128);
          }
          wg_commit();
        }
#pragma unroll 1
        for (int kb = 1; kb < 16; kb++) {
          const int g0 = 2 + 3 * (kb & 3);
          const uint32_t a = dk0 + g0 * DG, b = dm0 + (g0 + 2) * DG;
          const bool second = kb == 1 || kb == 15;
          if (!second) { wg_wait<0>(); c.release(2 + 3 * ((kb - 1) & 3), 3); }
          c.wait_full(g0);
          if (!second) c.turn_begin();
          wg_fence();
#pragma unroll
          for (int k = 0; k < 4; k++) {
            mma_ss_n128<1>(qa, a + k * 2, b + k * 128);
            mma_ss_n128<1>(qb, a + dsw + k * 2, b + k * 128);
          }
          wg_commit();
          if (kb != 14) c.turn_end();
          if (second) { wg_wait<1>(); c.release(2 + 3 * ((kb - 1) & 3), 3); }
          if (kb == QFLUSH) { c.wait_stage_free(); stsm_frag<0, 4>(pv, stg); }
          if (kb == QFLUSH + 1) { stsm_frag<4, 8>(pv, stg); c.staged(); }
        }
        c.wait_stage_free();
        const bool k0 = c.try_full(2);
        wg_wait<0>();
        reg_fence(qa); reg_fence(qb);
        c.release(11, 3);
        pack_frag<0>(qa, Q);
        if (c.wg == 0) {
          pack_frag<0>(qb, pv);
          stsm_frag(pv, stg);
        }
        if (!k0) c.wait_full(2); else c.pf ^= 4;
      }
      {
        const int nA = idx + 1;
        uint32_t (&P)[32] = pv;
        SoftState z;
        z.m0 = z.m1 = z.l0 = z.l1 = 0.f; z.shifted = c.zero;
#pragma unroll 1
        for (int seg = c.zero;; seg++) {
        if (c.wg == seg) attn_half(c, O, P, Q, nA == 1 && !seg, stg, z, dkk, dv0, dmask, seg);
        if (seg) break;
        int gk = c.wg ? 2 : 4, gv = c.wg ? 2 : 6;
        uint32_t dk = dkk + gk * DG;
#pragma unroll 1
        for (int it = 1 - c.wg; it < 17 - c.wg; it++) {
          float S[64];
          c.turn_begin();
          wg_fence();
          issue_qk(S, Q, dk);
          wg_commit();
          const uint32_t dv = dv0 + gv * DG;
          uint32_t relk = c.relb + gk * 8, relv = c.relb + gv * 8;
          gk = gv == 12 ? 2 : gv + (it == 6 || it == 9 ? 4 : 2);
          gv = it == 16 ? gk : gk == 12 ? 2 : gk + 2;
          uint32_t fk = sb + SM_BAR + (B_FULL + gk) * 8, fv = sb + SM_BAR + (B_FULL + gv) * 8, park = (c.pf >> gk) & 1, parv = (c.pf >> gv) & 1;
          c.pf ^= (1u << gk) | (1u << gv);
          dk = dkk + gk * DG;
          float lo0 = z.l0, lo1 = z.l1;
          const bool first = it == nA || it == 0;
          if (it == nA) {
            lo0 = rcp(quad_sum(lo0)); lo1 = rcp(quad_sum(lo1));
            z.m0 = z.m1 = z.l0 = z.l1 = 0.f; z.shifted = 0;
          }
          float s0, s1, d0 = z.m0, d1 = z.m1;
          int pre = z.shifted || (it & 15) == 0 || it + 1 == nA;
          float lim = first ? -1.f : SM_LIMIT;
          asm volatile("" : "+r"(relk), "+r"(relv), "+r"(fk), "+r"(fv), "+r"(park), "+r"(parv), "+r"(dk), "+r"(pre), "+f"(lim), "+f"(d0), "+f"(d1), "+f"(z.l0), "+f"(z.l1));
          if (it + c.wg > 1) {
            issue_pv<0>(O, P, dv, it != nA + 1 && it != 1, true);
            issue_pv<1>(O, P, dv, 1, true);
            c.turn_end();
          } else if (it) {
            issue_pv<0>(O, P, dv, 0, true);
            wg_commit(); wg_commit();
            c.turn_end();
            bar_sync(6, 256);
          } else stage_q2(c, O, P, stg);
          wg_wait<4>();
          reg_fence(S); reg_fence(Q);
          if (c.tid < 4) asm volatile("mbarrier.arrive.shared::cluster.b64 _, [%0];" ::"r"(relk) : "memory");
#pragma unroll 1
          for (int pass = 0;; pass++) {
            if (pre) {
              if (it + 1 == nA) load_q(Q, stg);
              if ((it & 15) == 0) mask_diag(S, dmask);
              if (z.shifted) shift_scores(S, d0, d1);
            }
            float tr[ROT];
            exp_quarter<0, 3>(S, P, tr, s0, s1, sb);
            exp_quarter<1, 2>(S, P, tr, s0, s1, sb);
            exp_quarter<2, 1>(S, P, tr, s0, s1, sb);
            exp_quarter<3, 0>(S, P, tr, s0, s1, sb);
            reg_fence(O);
            if (c.tid < (pass || !it ? 0 : 4)) asm volatile("mbarrier.arrive.shared::cluster.b64 _, [%0];" ::"r"(relv) : "memory");
            const bool ok = mbar_test(fk, park) & mbar_test(fv, parv);
            if (!ok) lim = -1.f;
            if (!__any_sync(0xffffffffu, !(s0 <= lim && s1 <= lim))) break;
            if (pass) break;
            if (it == nA) {
              store_scaled(O, lo0, lo1, stg, sb);
              c.staged();
            }
            if (!it) bar_arrive(6, 256);
            if (!ok) { mbar_wait(fk, park); mbar_wait(fv, parv); }
            if (!soft_unsafe(s0, s1, first)) break;
            soft_fix(S, O, z, first, d0, d1);
            pre = 1;
          }
          z.l0 += s0; z.l1 += s1;
        }
        if (!c.wg) bar_arrive(6, 256);
        }
        load_dd();
        c.turn_begin();
        wg_fence();
        issue_pv<0>(O, P, dv0 + 12 * DG, 1, true);
        issue_pv<1>(O, P, dv0 + 12 * DG, 1, !c.wg);
        c.turn_end();
        z.l0 = rcp(quad_sum(z.l0)); z.l1 = rcp(quad_sum(z.l1));
        c.wait_stage_free();
        if (rnd) c5 = get_ticket();
        wg_wait<0>();
        reg_fence(O); reg_fence(P);
        c.release(12, 2);
        store_scaled(O, z.l0, z.l1, stg, sb);
        c.staged();
      }
    }
    conv_tasks(c, p, (cn + 1 - c.wg) >> 1, spare, cch + c.wg * cstep, 2 * cstep, c5, dd0, dkk, warp & 3, lane);
    if (c.wg == 1) c.pf ^= 0x14;
    if (c.wg == (cn & 1)) c.turn_begin();
    if (!spare) {
      const int rt = 2 * grp + rank, ct = idx;
      float acc[64];
      int g0 = P3G + 2, pg = P3G;
      {
        c.wait_full(P3G);
        const uint32_t a = dk0 + P3G * DG, b = dm0 + (P3G + 1) * DG;
        wg_fence();
        mma_ss_n128_init<1>(acc, a, b);
#pragma unroll
        for (int k = 1; k < 4; k++) mma_ss_n128<1>(acc, a + k * 2, b + k * 128);
        wg_commit();
      }
#pragma unroll 1
      for (int kb = 1; kb < 64; kb++) {
        c.wait_full(g0);
        if (kb == STR && !c.wg) c.turn_begin();
        const uint32_t a = dk0 + g0 * DG, b = dm0 + (g0 + 1) * DG;
        wg_fence();
#pragma unroll
        for (int k = 0; k < 4; k++) mma_ss_n128<1>(acc, a + k * 2, b + k * 128);
        wg_commit();
        if (kb < STR) { wg_wait<1>(); c.release(pg, kb <= 59 ? 2 : 0); }
        pg = g0;
        g0 = g0 == (kb < XK ? 12 : kb < YK ? 10 : 8) ? (kb == 3 ? 2 : 0) : g0 + 2;
      }
      if (c.wg) c.turn_end();
      cluster_arrive();
      c.wait_full(P3X);
      c.wait_full(P3Y);
      const float g0f = __uint_as_float(lds32(sb + SM_GATE + row * 4)), g1f = __uint_as_float(lds32(sb + SM_GATE + row * 4 + 32));
      const uint32_t gp0 = pack_bf16(g0f, g0f), gp1 = pack_bf16(g1f, g1f);
      const float h0 = 1.f - g0f, h1 = 1.f - g1f;
      const int w = warp & 3;
      const uint32_t xa = stg + P3X * GR;
      const uint32_t ya = sb + P3Y * GR + c.wg * 16384 + ((lane >> 4) * 8 + (lane & 7)) * 128 + (((2 * w + ((lane >> 3) & 1)) ^ (lane & 7)) << 4);
      uint32_t xy[32];
      auto prep = [&](int j0, int j1) {
#pragma unroll
        for (int jj = j0; jj < j1; jj++) {
          uint32_t x[4], y[4];
          asm volatile("ldmatrix.sync.aligned.m8n8.x4.shared.b16 {%0,%1,%2,%3}, [%4];" : "=r"(x[0]), "=r"(x[1]), "=r"(x[2]), "=r"(x[3]) : "r"((xa ^ ((jj & 3) << 5)) + (jj >> 2) * 16384) : "memory");
          asm volatile("ldmatrix.sync.aligned.m8n8.x4.trans.shared.b16 {%0,%1,%2,%3}, [%4];" : "=r"(y[0]), "=r"(y[1]), "=r"(y[2]), "=r"(y[3]) : "r"(ya + jj * 2048) : "memory");
#pragma unroll
          for (int i = 0; i < 4; i++) xy[4 * jj + i] = hmul2(x[i], y[i]);
        }
      };
      prep(0, 4);
      wg_wait<0>();
      reg_fence(acc);
#pragma unroll
      for (int hf = 0; hf < 2; hf++) {
#pragma unroll
        for (int i = 16 * hf; i < 16 * hf + 16; i++) {
          const float h = (i & 1) ? h1 : h0;
          xy[i] = hfma2((i & 1) ? gp1 : gp0, xy[i], pack_bf16(acc[2 * i] * h, acc[2 * i + 1] * h));
        }
        if (hf) stsm_frag<4, 8>(xy, xa); else stsm_frag<0, 4>(xy, xa);
        fence_async_smem();
        __syncwarp();
        const int r0 = c.wg * 64 + w * 16;
        if (lane == 0) tma2d_store(&p.out, sb + (P3X + hf) * GR + r0 * 128, ct * 128 + hf * 64, rt * 128 + r0);
        if (!hf) prep(4, 8);
      }
      if (lane == 0) asm volatile("cp.async.bulk.commit_group;\ncp.async.bulk.wait_group.read 0;" ::: "memory");
    } else { cluster_arrive(); }
    if (lane == 0) mbar_arrive(sb + SM_BAR + B_DONE * 8);
    __syncwarp();
    cluster_wait();
  }
}

typedef CUresult (*EncFn)(CUtensorMap*, CUtensorMapDataType, cuuint32_t, void*, const cuuint64_t*, const cuuint64_t*, const cuuint32_t*,
                          const cuuint32_t*, CUtensorMapInterleave, CUtensorMapSwizzle, CUtensorMapL2promotion, CUtensorMapFloatOOBfill);

void enc2d(EncFn enc, CUtensorMap* tm, const void* base, uint64_t cols, uint64_t rows, uint32_t bc, uint32_t br) {
  cuuint64_t dims[2] = {cols, rows}; cuuint64_t strides[1] = {cols * 2}; cuuint32_t box[2] = {bc, br}; cuuint32_t es[2] = {1, 1};
  enc(tm, CU_TENSOR_MAP_DATA_TYPE_BFLOAT16, 2, const_cast<void*>(base), dims, strides, box, es, CU_TENSOR_MAP_INTERLEAVE_NONE,
      CU_TENSOR_MAP_SWIZZLE_128B, CU_TENSOR_MAP_L2_PROMOTION_L2_256B, CU_TENSOR_MAP_FLOAT_OOB_FILL_NONE);
}
void enc3d(EncFn enc, CUtensorMap* tm, const void* base, uint64_t K, uint64_t N, uint32_t bk = 64, uint64_t pitch = 0) {
  cuuint64_t dims[3] = {64, K, N / 64}; cuuint64_t strides[2] = {pitch ? pitch : N * 2, 128}; cuuint32_t box[3] = {64, bk, 2}; cuuint32_t es[3] = {1, 1, 1};
  enc(tm, CU_TENSOR_MAP_DATA_TYPE_BFLOAT16, 3, const_cast<void*>(base), dims, strides, box, es, CU_TENSOR_MAP_INTERLEAVE_NONE,
      CU_TENSOR_MAP_SWIZZLE_128B, CU_TENSOR_MAP_L2_PROMOTION_L2_256B, CU_TENSOR_MAP_FLOAT_OOB_FILL_NONE);
}

}

extern "C" void kernel_launch(void* const* d_in, const int* in_sizes, int n_in, void* d_out, int out_size) {
  (void)in_sizes; (void)n_in; (void)out_size;
  typedef const __nv_bfloat16* BP;
  BP xq = (BP)d_in[0], ak = (BP)d_in[1], av = (BP)d_in[2], shk = (BP)d_in[3], ssk = (BP)d_in[4], ssd = (BP)d_in[5];
  BP ckv = (BP)d_in[7], wq = (BP)d_in[8], wuk = (BP)d_in[9], wuv = (BP)d_in[10], wo = (BP)d_in[11], gw = (BP)d_in[12];

  static EncFn enc = nullptr;
  if (!enc) {
    cudaDriverEntryPointQueryResult qr;
    cudaGetDriverEntryPoint("cuTensorMapEncodeTiled", (void**)&enc, cudaEnableDefault, &qr);
    cudaFuncSetAttribute(mega_kernel, cudaFuncAttributeMaxDynamicSharedMemorySize, SMEM_BYTES);
  }
  Params p;
  enc2d(enc, &p.x, xq, DM, SEQ, 64, 128);
  enc2d(enc, &p.c, ckv, DC, SEQ, 64, 128);
  enc3d(enc, &p.wq, wq, DM, NH * HD);
  enc3d(enc, &p.wuk, wuk, DC, NH * HD);
  enc3d(enc, &p.wuv, wuv, DC, NH * HD);
  enc2d(enc, &p.wo, wo, DM, NH * HD, 64, 64);
  enc3d(enc, &p.x3, xq, SEQ, DM, 128);
  enc2d(enc, &p.out, d_out, DM, SEQ, 64, 16);
  {
    void* wp = nullptr;
    cudaGetSymbolAddress(&wp, g_w);
    enc3d(enc, &p.y3, (uint8_t*)wp + WZ, DM, SEQ, 128, WSTRIDE);
    cuuint64_t dims[3] = {WSTRIDE / 2, DM / 2, 2}; cuuint64_t strides[2] = {2 * WSTRIDE, WSTRIDE}; cuuint32_t box[3] = {16, 32, 2}; cuuint32_t es[3] = {1, 1, 1};
    enc(&p.w, CU_TENSOR_MAP_DATA_TYPE_BFLOAT16, 3, wp, dims, strides, box, es, CU_TENSOR_MAP_INTERLEAVE_NONE,
        CU_TENSOR_MAP_SWIZZLE_32B, CU_TENSOR_MAP_L2_PROMOTION_NONE, CU_TENSOR_MAP_FLOAT_OOB_FILL_NONE);
  }
  p.zero = 0;
  cudaGetSymbolAddress((void**)&p.flags, g_flags);
  for (int i = 0; i < 128; i++) {
    const int tp = i % NSLOT;
    p.pref[i] = tp < 32 ? (tp & 7) * 8 + (tp >> 3) : tp < 60 ? (1 + (tp - 32) % 7) * 8 + 4 + (tp - 32) / 7 : tp < 62 ? tp + 4 : tp - 58;
  }
  p.gate_w = gw; p.ak = ak; p.av = av; p.shk = shk; p.ssk = ssk; p.ssd = ssd;

  mega_kernel<<<132, NTHREADS, SMEM_BYTES>>>(p);
}
```

```cpp
#include <cuda_runtime.h>
#include <cuda.h>
#include <cuda_bf16.h>
#include <stdint.h>

namespace {

constexpr int SEQ = 2048, DM = 1024, DC = 512, NH = 32, HD = 128;
constexpr int GR = 16384;
constexpr int NGR = 14;
constexpr int SM_BAR = NGR * GR;
constexpr int SM_GATE = SM_BAR + 512;
constexpr int SM_UST = SM_GATE + 512;
constexpr int SMEM_BYTES = SM_UST + 2048;
constexpr int NTHREADS = 384;
constexpr float SM_LIMIT = 1.0995116e12f;
constexpr float SM_LOW = 9.094947e-13f;
constexpr int CNS = 106;
constexpr int CN_SPARE = CNS, NTICK = 256 - 2 * CN_SPARE;
constexpr int XK = 57, YK = 62;
constexpr int STR = 61;
constexpr int P3G = 6, P3X = 12, P3Y = 10;
constexpr int NMAIN = 128;

constexpr int B_FULL = 0, B_FREE = 14, B_SLOT = 16, B_DONE = 17, B_EMPTY = 18, B_EV = 32, B_TICK = 36;
constexpr int V_SLOT = 37, V_TICK = 38;

__device__ __align__(1024) uint8_t g_kv[2 * 16 * 16 * 32768];
__device__ __align__(1024) uint8_t g_cimg[16 * NH * 32768];
__device__ __align__(1024) float g_gate[SEQ];
constexpr int WZ = 256, WPL = WZ + 4096, WBYTES = 2 * WPL + 32, WSTRIDE = 2 * WPL + 128;
__device__ __align__(1024) uint8_t g_w[DM * WSTRIDE];
__device__ __align__(32) unsigned g_flags[96 * 8];
constexpr int F_KV = 0, F_CTX = 16, F_U = 48, F_AD = 56, F_Y = 64, F_GATE = 72, F_EXIT = 73, F_TICK = 74;
constexpr int NSLOT = 66;
#define FLAG(i) (&g_flags[(i) * 8])
#define CLAIMP(i) (p.flags + (i) * 8 + 1)

constexpr int QFLUSH = 3;
constexpr int PSL = 200;
constexpr int US0 = 500;
constexpr int EROT = 6;
constexpr int RST = 2;
constexpr int UP0 = 4;
constexpr int UP1 = 11;
constexpr int X_DELAY = 1100;
constexpr int X_D2 = 500;
constexpr int ROT = 8;
#define KV_ROW(idx, t) (8 * (t) + 2 * ((idx) & 3))
#define KV_HEAD(idx, t) ((idx) >> 2)

__device__ __forceinline__ uint32_t smem_u32(const void* p) { return (uint32_t)__cvta_generic_to_shared(p); }
__device__ __forceinline__ void mbar_init(uint32_t bar, int cnt) { asm volatile("mbarrier.init.shared::cta.b64 [%0], %1;" ::"r"(bar), "r"(cnt) : "memory"); }
__device__ __forceinline__ void mbar_expect_tx(uint32_t bar, uint32_t bytes) { asm volatile("mbarrier.arrive.expect_tx.shared::cta.b64 _, [%0], %1;" ::"r"(bar), "r"(bytes) : "memory"); }
__device__ __forceinline__ void mbar_arrive(uint32_t bar) { asm volatile("mbarrier.arrive.shared::cta.b64 _, [%0];" ::"r"(bar) : "memory"); }
__device__ __forceinline__ void mbar_arrive_cluster(uint32_t bar, uint32_t cta) {
  asm volatile("{\n.reg .b32 r;\nmapa.shared::cluster.u32 r, %0, %1;\nmbarrier.arrive.shared::cluster.b64 _, [r];\n}\n" ::"r"(bar), "r"(cta) : "memory");
}
__device__ __forceinline__ void send_both(uint32_t bar, uint32_t off, uint32_t v) {
#pragma unroll
  for (int r = 0; r < 2; r++)
    asm volatile("{\n.reg .b32 a, b;\nmapa.shared::cluster.u32 a, %0, %1;\nadd.u32 b, a, %3;\nst.async.shared::cluster.mbarrier::complete_tx::bytes.u32 [b], %2, [a];\n}\n"
                 ::"r"(bar), "r"(r), "r"(v), "r"(off) : "memory");
}
__device__ __forceinline__ bool mbar_try(uint32_t bar, uint32_t parity) {
  uint32_t ok;
  asm volatile("{\n.reg .pred p;\nmbarrier.try_wait.parity.shared::cta.b64 p, [%1], %2, 20000;\nselp.u32 %0, 1, 0, p;\n}\n" : "=r"(ok) : "r"(bar), "r"(parity) : "memory");
  return ok;
}
__device__ __forceinline__ bool mbar_test(uint32_t bar, uint32_t parity) {
  uint32_t ok;
  asm volatile("{\n.reg .pred p;\nmbarrier.test_wait.parity.shared::cta.b64 p, [%1], %2;\nselp.u32 %0, 1, 0, p;\n}\n" : "=r"(ok) : "r"(bar), "r"(parity) : "memory");
  return ok;
}
__device__ __forceinline__ void mbar_wait(uint32_t bar, uint32_t parity) {
  asm volatile("{\n.reg .pred p;\nWAIT_LOOP:\nbar.warp.sync -1;\nmbarrier.try_wait.parity.shared::cta.b64 p, [%0], %1;\n@!p bra WAIT_LOOP;\n}\n" ::"r"(bar), "r"(parity) : "memory");
}
__device__ __forceinline__ void mbar_wait1(uint32_t bar, uint32_t parity) {
  asm volatile("{\n.reg .pred p;\nWAIT_LOOP:\nbar.warp.sync -1;\nmbarrier.try_wait.parity.shared::cta.b64 p, [%0], %1, 4000;\n@!p bra WAIT_LOOP;\n}\n" ::"r"(bar), "r"(parity) : "memory");
}
constexpr uint64_t EV_NORMAL = 0x1000000000000000ull, EV_FIRST = 0x12F0000000000000ull;
__device__ __forceinline__ uint32_t ldg_stream(const uint32_t* p) {
  uint32_t r; asm volatile("ld.global.nc.L1::no_allocate.L2::cache_hint.b32 %0, [%1], %2;" : "=r"(r) : "l"(p), "l"(EV_FIRST)); return r;
}
#define TMA_LD "cp.async.bulk.tensor."
#define TMA_MB ".shared::cluster.global.mbarrier::complete_tx::bytes"
__device__ __forceinline__ void tma2d(uint32_t dst, const CUtensorMap* tm, int c0, int c1, uint32_t bar) {
  asm volatile(TMA_LD "2d" TMA_MB " [%0], [%1, {%3, %4}], [%2];" ::"r"(dst), "l"(tm), "r"(bar), "r"(c0), "r"(c1) : "memory");
}
template <bool ONCE = false> __device__ __forceinline__ void tma2d_mc(uint32_t dst, const CUtensorMap* tm, int c0, int c1, uint32_t bar) {
  if (ONCE) asm volatile(TMA_LD "2d" TMA_MB ".multicast::cluster.L2::cache_hint [%0], [%1, {%3, %4}], [%2], %5, %6;"
                         ::"r"(dst), "l"(tm), "r"(bar), "r"(c0), "r"(c1), "h"((uint16_t)3), "l"(EV_FIRST) : "memory");
  else asm volatile(TMA_LD "2d" TMA_MB ".multicast::cluster [%0], [%1, {%3, %4}], [%2], %5;"
                    ::"r"(dst), "l"(tm), "r"(bar), "r"(c0), "r"(c1), "h"((uint16_t)3) : "memory");
}
__device__ __forceinline__ void tma2d_p(uint32_t dst, const CUtensorMap* tm, int c0, int c1, uint32_t bar, bool once) {
  asm volatile(TMA_LD "2d" TMA_MB ".L2::cache_hint [%0], [%1, {%3, %4}], [%2], %5;" ::"r"(dst), "l"(tm), "r"(bar), "r"(c0), "r"(c1), "l"(once ? EV_FIRST : EV_NORMAL) : "memory");
}
__device__ __forceinline__ void tma3d_mc_p(uint32_t dst, const CUtensorMap* tm, int c0, int c1, int c2, uint32_t bar, bool once) {
  asm volatile(TMA_LD "3d" TMA_MB ".multicast::cluster.L2::cache_hint [%0], [%1, {%3, %4, %5}], [%2], %6, %7;"
               ::"r"(dst), "l"(tm), "r"(bar), "r"(c0), "r"(c1), "r"(c2), "h"((uint16_t)3), "l"(once ? EV_FIRST : EV_NORMAL) : "memory");
}
template <bool ONCE = false> __device__ __forceinline__ void tma3d(uint32_t dst, const CUtensorMap* tm, int c0, int c1, int c2, uint32_t bar) {
  if (ONCE) asm volatile(TMA_LD "3d" TMA_MB ".L2::cache_hint [%0], [%1, {%3, %4, %5}], [%2], %6;" ::"r"(dst), "l"(tm), "r"(bar), "r"(c0), "r"(c1), "r"(c2), "l"(EV_FIRST) : "memory");
  else
  asm volatile(TMA_LD "3d" TMA_MB " [%0], [%1, {%3, %4, %5}], [%2];" ::"r"(dst), "l"(tm), "r"(bar), "r"(c0), "r"(c1), "r"(c2) : "memory");
}
__device__ __forceinline__ void tma3d_mc(uint32_t dst, const CUtensorMap* tm, int c0, int c1, int c2, uint32_t bar) {
  asm volatile(TMA_LD "3d" TMA_MB ".multicast::cluster [%0], [%1, {%3, %4, %5}], [%2], %6;"
               ::"r"(dst), "l"(tm), "r"(bar), "r"(c0), "r"(c1), "r"(c2), "h"((uint16_t)3) : "memory");
}
template <bool ONCE = false> __device__ __forceinline__ void bulk_g2s(uint32_t dst, const void* src, uint32_t bytes, uint32_t bar) {
  if (ONCE) asm volatile("cp.async.bulk" TMA_MB ".L2::cache_hint [%0], [%1], %2, [%3], %4;" ::"r"(dst), "l"(src), "r"(bytes), "r"(bar), "l"(EV_FIRST) : "memory");
  else asm volatile("cp.async.bulk" TMA_MB " [%0], [%1], %2, [%3];" ::"r"(dst), "l"(src), "r"(bytes), "r"(bar) : "memory");
}
__device__ __forceinline__ void tma2d_store(const CUtensorMap* tm, uint32_t src, int c0, int c1) {
  asm volatile("cp.async.bulk.tensor.2d.global.shared::cta.bulk_group [%0, {%2, %3}], [%1];" ::"l"(tm), "r"(src), "r"(c0), "r"(c1) : "memory");
}
__device__ __forceinline__ void prefetch_tm(const CUtensorMap* tm) { asm volatile("prefetch.tensormap [%0];" ::"l"(tm) : "memory"); }
__device__ __forceinline__ void wg_fence() { asm volatile("wgmma.fence.sync.aligned;" ::: "memory"); }
__device__ __forceinline__ void wg_commit() { asm volatile("wgmma.commit_group.sync.aligned;" ::: "memory"); }
template <int N> __device__ __forceinline__ void wg_wait() { asm volatile("wgmma.wait_group.sync.aligned %0;" ::"n"(N) : "memory"); }
__device__ __forceinline__ void bar_sync(int id, int n) { asm volatile("bar.sync %0, %1;" ::"r"(id), "r"(n) : "memory"); }
__device__ __forceinline__ void bar_arrive(int id, int n) { asm volatile("bar.arrive %0, %1;" ::"r"(id), "r"(n) : "memory"); }
__device__ __forceinline__ void fence_async_smem() { asm volatile("fence.proxy.async.shared::cta;" ::: "memory"); }
__device__ __forceinline__ void fence_async_all() { asm volatile("fence.proxy.async.global;" ::: "memory"); }
__device__ __forceinline__ uint32_t pack_bf16(float lo, float hi) { uint32_t r; asm("cvt.rn.bf16x2.f32 %0, %1, %2;" : "=r"(r) : "f"(hi), "f"(lo)); return r; }
__device__ __forceinline__ float ex2(float x) { float r; asm("ex2.approx.ftz.f32 %0, %1;" : "=f"(r) : "f"(x)); return r; }
__device__ __forceinline__ float rcp(float x) { float r; asm("rcp.approx.ftz.f32 %0, %1;" : "=f"(r) : "f"(x)); return r; }
__device__ __forceinline__ void flag_wait(const unsigned* f, unsigned target) {
  unsigned v;
  do { asm volatile("ld.acquire.gpu.global.u32 %0, [%1];" : "=r"(v) : "l"(f) : "memory"); } while (__any_sync(0xffffffffu, v < target));
}
__device__ __forceinline__ bool elect() {
  uint32_t r;
  asm volatile("{\n.reg .pred p;\nelect.sync _|p, -1;\nselp.u32 %0, 1, 0, p;\n}\n" : "=r"(r));
  return r;
}
__device__ __forceinline__ void fence_release() { asm volatile("fence.release.gpu;" ::: "memory"); }
__device__ __forceinline__ void flag_add(unsigned* f) { asm volatile("red.relaxed.gpu.global.inc.u32 [%0], 0x7fffffff;" ::"l"(f) : "memory"); }
__device__ __forceinline__ void cluster_arrive() { asm volatile("barrier.cluster.arrive.relaxed.aligned;" ::: "memory"); }
__device__ __forceinline__ void cluster_wait() { asm volatile("barrier.cluster.wait.aligned;" ::: "memory"); }
__device__ __forceinline__ uint32_t hmul2(uint32_t a, uint32_t b) { uint32_t r; asm("mul.rn.bf16x2 %0, %1, %2;" : "=r"(r) : "r"(a), "r"(b)); return r; }
__device__ __forceinline__ uint32_t hadd2(uint32_t a, uint32_t b) { uint32_t r; asm("add.rn.bf16x2 %0, %1, %2;" : "=r"(r) : "r"(a), "r"(b)); return r; }
__device__ __forceinline__ uint32_t hfma2(uint32_t a, uint32_t b, uint32_t c) { uint32_t r; asm("fma.rn.bf16x2 %0, %1, %2, %3;" : "=r"(r) : "r"(a), "r"(b), "r"(c)); return r; }
__device__ __forceinline__ uint32_t lds32(uint32_t a) { uint32_t r; asm volatile("ld.shared.b32 %0, [%1];" : "=r"(r) : "r"(a) : "memory"); return r; }
__device__ __forceinline__ uint4 lds128(uint32_t a) { uint4 r; asm volatile("ld.shared.v4.b32 {%0,%1,%2,%3}, [%4];" : "=r"(r.x), "=r"(r.y), "=r"(r.z), "=r"(r.w) : "r"(a) : "memory"); return r; }
__device__ __forceinline__ uint32_t desc_k(uint32_t addr) { return ((addr & 0x3FFFF) >> 4) | (1u << 16); }
template <int LBO> __device__ __forceinline__ uint32_t desc_mn(uint32_t addr) { return ((addr & 0x3FFFF) >> 4) | ((uint32_t)(LBO >> 4) << 16); }
#define DHI "0x40000040"

#define R8(d, o) "+f"(d[o]), "+f"(d[o + 1]), "+f"(d[o + 2]), "+f"(d[o + 3]), "+f"(d[o + 4]), "+f"(d[o + 5]), "+f"(d[o + 6]), "+f"(d[o + 7])
#define R32(d, o) R8(d, o), R8(d, o + 8), R8(d, o + 16), R8(d, o + 24)
#define R64(d, o) R32(d, o), R32(d, o + 32)
#define L64 "%0,%1,%2,%3,%4,%5,%6,%7,%8,%9,%10,%11,%12,%13,%14,%15,%16,%17,%18,%19,%20,%21,%22,%23,%24,%25,%26,%27,%28,%29,%30,%31," \
            "%32,%33,%34,%35,%36,%37,%38,%39,%40,%41,%42,%43,%44,%45,%46,%47,%48,%49,%50,%51,%52,%53,%54,%55,%56,%57,%58,%59,%60,%61,%62,%63"
#define L128 L64 ",%64,%65,%66,%67,%68,%69,%70,%71,%72,%73,%74,%75,%76,%77,%78,%79,%80,%81,%82,%83,%84,%85,%86,%87,%88,%89,%90,%91,%92,%93,%94,%95," \
            "%96,%97,%98,%99,%100,%101,%102,%103,%104,%105,%106,%107,%108,%109,%110,%111,%112,%113,%114,%115,%116,%117,%118,%119,%120,%121,%122,%123,%124,%125,%126,%127"

template <int TB> __device__ __forceinline__ void mma_ss_n128(float (&d)[64], uint32_t da, uint32_t db) {
  asm volatile("{\n.reg .b64 da, db;\nmov.b64 da, {%64, " DHI "};\nmov.b64 db, {%65, " DHI "};\n"
               "wgmma.mma_async.sync.aligned.m64n128k16.f32.bf16.bf16 {" L64 "}, da, db, 1, 1, 1, 0, %66;\n}\n"
               : R64(d, 0) : "r"(da), "r"(db), "n"(TB));
}
template <int TB> __device__ __forceinline__ void mma_rs_n128(float (&d)[64], uint32_t a0, uint32_t a1, uint32_t a2, uint32_t a3, uint32_t db, int sd) {
  asm volatile("{\n.reg .pred p;\n.reg .b64 db;\nsetp.ne.b32 p, %69, 0;\nmov.b64 db, {%68, " DHI "};\n"
               "wgmma.mma_async.sync.aligned.m64n128k16.f32.bf16.bf16 {" L64 "}, {%64,%65,%66,%67}, db, p, 1, 1, %70;\n}\n"
               : R64(d, 0) : "r"(a0), "r"(a1), "r"(a2), "r"(a3), "r"(db), "r"(sd), "n"(TB));
}
template <int TB> __device__ __forceinline__ void mma_ss_n256(float (&d)[128], uint32_t da, uint32_t db) {
  asm volatile("{\n.reg .b64 da, db;\nmov.b64 da, {%128, " DHI "};\nmov.b64 db, {%129, " DHI "};\n"
               "wgmma.mma_async.sync.aligned.m64n256k16.f32.bf16.bf16 {" L128 "}, da, db, 1, 1, 1, 0, %130;\n}\n"
               : R64(d, 0), R64(d, 64) : "r"(da), "r"(db), "n"(TB));
}
#define W8(d, o) "=f"(d[o]), "=f"(d[o + 1]), "=f"(d[o + 2]), "=f"(d[o + 3]), "=f"(d[o + 4]), "=f"(d[o + 5]), "=f"(d[o + 6]), "=f"(d[o + 7])
#define W32(d, o) W8(d, o), W8(d, o + 8), W8(d, o + 16), W8(d, o + 24)
#define W64(d, o) W32(d, o), W32(d, o + 32)
template <int TB> __device__ __forceinline__ void mma_ss_n128_init(float (&d)[64], uint32_t da, uint32_t db) {
  asm volatile("{\n.reg .b64 da, db;\nmov.b64 da, {%64, " DHI "};\nmov.b64 db, {%65, " DHI "};\n"
               "wgmma.mma_async.sync.aligned.m64n128k16.f32.bf16.bf16 {" L64 "}, da, db, 0, 1, 1, 0, %66;\n}\n"
               : W64(d, 0) : "r"(da), "r"(db), "n"(TB));
}
template <int TB> __device__ __forceinline__ void mma_rs_n128_init(float (&d)[64], uint32_t a0, uint32_t a1, uint32_t a2, uint32_t a3, uint32_t db) {
  asm volatile("{\n.reg .b64 db;\nmov.b64 db, {%68, " DHI "};\n"
               "wgmma.mma_async.sync.aligned.m64n128k16.f32.bf16.bf16 {" L64 "}, {%64,%65,%66,%67}, db, 0, 1, 1, %69;\n}\n"
               : W64(d, 0) : "r"(a0), "r"(a1), "r"(a2), "r"(a3), "r"(db), "n"(TB));
}
template <int TB> __device__ __forceinline__ void mma_ss_n256_init(float (&d)[128], uint32_t da, uint32_t db) {
  asm volatile("{\n.reg .b64 da, db;\nmov.b64 da, {%128, " DHI "};\nmov.b64 db, {%129, " DHI "};\n"
               "wgmma.mma_async.sync.aligned.m64n256k16.f32.bf16.bf16 {" L128 "}, da, db, 0, 1, 1, 0, %130;\n}\n"
               : W64(d, 0), W64(d, 64) : "r"(da), "r"(db), "n"(TB));
}
#define L32 "%0,%1,%2,%3,%4,%5,%6,%7,%8,%9,%10,%11,%12,%13,%14,%15,%16,%17,%18,%19,%20,%21,%22,%23,%24,%25,%26,%27,%28,%29,%30,%31"
template <bool INIT> __device__ __forceinline__ void mma_rs_n64(float (&d)[32], uint32_t a0, uint32_t a1, uint32_t a2, uint32_t a3, uint32_t db) {
  if (INIT) asm volatile("{\n.reg .b64 db;\nmov.b64 db, {%36, " DHI "};\n"
               "wgmma.mma_async.sync.aligned.m64n64k16.f32.bf16.bf16 {" L32 "}, {%32,%33,%34,%35}, db, 0, 1, 1, 0;\n}\n"
               : W32(d, 0) : "r"(a0), "r"(a1), "r"(a2), "r"(a3), "r"(db));
  else asm volatile("{\n.reg .b64 db;\nmov.b64 db, {%36, " DHI "};\n"
               "wgmma.mma_async.sync.aligned.m64n64k16.f32.bf16.bf16 {" L32 "}, {%32,%33,%34,%35}, db, 1, 1, 1, 0;\n}\n"
               : R32(d, 0) : "r"(a0), "r"(a1), "r"(a2), "r"(a3), "r"(db));
}
#define L16 "%0,%1,%2,%3,%4,%5,%6,%7,%8,%9,%10,%11,%12,%13,%14,%15"
template <int O, bool INIT> __device__ __forceinline__ void mma_rs_n32(float (&d)[128], uint32_t a0, uint32_t a1, uint32_t a2, uint32_t a3, uint32_t db) {
  if (INIT) asm volatile("{\n.reg .b64 db;\nmov.b64 db, {%20, 0x00000008};\n"
               "wgmma.mma_async.sync.aligned.m64n32k16.f32.bf16.bf16 {" L16 "}, {%16,%17,%18,%19}, db, 0, 1, 1, 0;\n}\n"
               : W8(d, O), W8(d, O + 8) : "r"(a0), "r"(a1), "r"(a2), "r"(a3), "r"(db));
  else asm volatile("{\n.reg .b64 db;\nmov.b64 db, {%20, 0x00000008};\n"
               "wgmma.mma_async.sync.aligned.m64n32k16.f32.bf16.bf16 {" L16 "}, {%16,%17,%18,%19}, db, 1, 1, 1, 0;\n}\n"
               : R8(d, O), R8(d, O + 8) : "r"(a0), "r"(a1), "r"(a2), "r"(a3), "r"(db));
}
template <int S, int J> __device__ __forceinline__ void conv_step(float (&d)[128], const uint32_t (&a)[64], uint32_t db) {
  if constexpr (J >= 0 && J >= (S >> 1)) {
    mma_rs_n32<16 * J, S == 0>(d, a[4 * S], a[4 * S + 1], a[4 * S + 2], a[4 * S + 3], db + (uint32_t)((2 * J - S) * 16));
    conv_step<S, J - 1>(d, a, db);
  }
}
__device__ __forceinline__ void mma_ss_n8(float (&d)[4], uint32_t da, uint32_t db) {
  asm volatile("{\n.reg .b64 da, db;\nmov.b64 da, {%4, " DHI "};\nmov.b64 db, {%5, 0x00000008};\n"
               "wgmma.mma_async.sync.aligned.m64n8k16.f32.bf16.bf16 {%0,%1,%2,%3}, da, db, 1, 1, 1, 0, 0;\n}\n"
               : "+f"(d[0]), "+f"(d[1]), "+f"(d[2]), "+f"(d[3]) : "r"(da), "r"(db));
}
template <int N> __device__ __forceinline__ void reg_fence(float (&d)[N]) {
#pragma unroll
  for (int i = 0; i < N; i++) asm volatile("" : "+f"(d[i])::"memory");
}
template <int N> __device__ __forceinline__ void reg_fence(uint32_t (&d)[N]) {
#pragma unroll
  for (int i = 0; i < N; i++) asm volatile("" : "+r"(d[i])::"memory");
}

struct __align__(64) Params {
  unsigned* flags;
  int zero;
  uint8_t pref[128];
  const __nv_bfloat16 *gate_w, *ak, *av, *shk, *ssk, *ssd, *wukp, *wuvp;
  CUtensorMap x, c, wq, wuk, wuv, wo, x3, y3, out, w;
};

template <int O, int N, int M> __device__ __forceinline__ void pack_frag(const float (&acc)[N], uint32_t (&pk)[M]) {
#pragma unroll
  for (int i = 0; i < 32; i++) pk[i] = pack_bf16(acc[O + 2 * i], acc[O + 2 * i + 1]);
}
template <int J0 = 0, int J1 = 8, int M> __device__ __forceinline__ void stsm_frag(const uint32_t (&pk)[M], uint32_t a) {
#pragma unroll
  for (int jj = J0; jj < J1; jj++)
    asm volatile("stmatrix.sync.aligned.m8n8.x4.shared.b16 [%0], {%1,%2,%3,%4};" ::"r"((a ^ ((jj & 3) << 5)) + (jj >> 2) * 16384),
                 "r"(pk[4 * jj]), "r"(pk[4 * jj + 1]), "r"(pk[4 * jj + 2]), "r"(pk[4 * jj + 3]) : "memory");
}

template <int N> __device__ __forceinline__ void store_scaled(const float (&acc)[N], float s0, float s1, uint32_t a, uint32_t never_zero) {
  float t[8];
#pragma unroll
  for (int jj = 0; jj < 8; jj++) {
    float v = acc[8 * jj] * s0;
    if (jj >= RST) {
      v = t[jj - RST];
      asm("{\n.reg .pred p;\nsetp.ne.u32 p, %3, 0;\n@p mul.f32 %0, %1, %2;\n}\n" : "+f"(v) : "f"(acc[8 * jj]), "f"(s0), "r"(never_zero));
    }
    const uint32_t q = pack_bf16(v, acc[8 * jj + 1] * s0);
    t[jj] = __uint_as_float(q);
    asm volatile("stmatrix.sync.aligned.m8n8.x4.shared.b16 [%0], {%1,%2,%3,%4};" ::"r"((a ^ ((jj & 3) << 5)) + (jj >> 2) * 16384), "r"(q),
                 "r"(pack_bf16(acc[8 * jj + 2] * s1, acc[8 * jj + 3] * s1)), "r"(pack_bf16(acc[8 * jj + 4] * s0, acc[8 * jj + 5] * s0)),
                 "r"(pack_bf16(acc[8 * jj + 6] * s1, acc[8 * jj + 7] * s1)) : "memory");
  }
}

struct Cons {
  uint32_t sb;
  uint32_t pf;
  int wg, tid;
  __device__ __forceinline__ void wait_full(int g) { mbar_wait(sb + SM_BAR + (B_FULL + g) * 8, (pf >> g) & 1); pf ^= 1u << g; }
  uint32_t relb;
  __device__ __forceinline__ void release(int g, int n) {
    if (tid < 2 * n) asm volatile("mbarrier.arrive.shared::cluster.b64 _, [%0];" ::"r"(relb + g * 8) : "memory");
  }
  __device__ __forceinline__ void turn_begin() { bar_sync(1 + wg, 256); }
  __device__ __forceinline__ void turn_end() { bar_arrive(2 - wg, 256); }
  __device__ __forceinline__ void staged() { __syncwarp(); if ((tid & 31) == 0) mbar_arrive(sb + SM_BAR + (B_EV + wg) * 8); }
  int zero;
  uint32_t pfree;
  __device__ __forceinline__ void wait_stage_free() { mbar_wait(sb + SM_BAR + (B_FREE + wg) * 8, pfree); pfree ^= 1; }
  __device__ __forceinline__ bool try_full(int g) { return mbar_test(sb + SM_BAR + (B_FULL + g) * 8, (pf >> g) & 1); }
};

constexpr float SM_C = 0.08838834764831845f * 1.4426950408889634f;
struct SoftState { float m0, m1, l0, l1; int shifted; };
__device__ __forceinline__ void ex2_rot(float& t, float s, uint32_t never_zero) {
  asm("{\n.reg .pred p;\nsetp.ne.u32 p, %2, 0;\n@p ex2.approx.ftz.f32 %0, %1;\n}\n" : "+f"(t) : "f"(s), "r"(never_zero));
}
__device__ __forceinline__ void pin(float a, uint32_t never_zero) {
  asm volatile("{\n.reg .pred p;\nsetp.eq.u32 p, %1, 0;\n@p st.shared.f32 [%1], %0;\n}\n" ::"f"(a), "r"(never_zero) : "memory");
}
template <int O, int N> __device__ __forceinline__ void reg_fence_part(uint32_t (&d)[32]) {
#pragma unroll
  for (int i = O; i < O + N; i++) asm volatile("" : "+r"(d[i])::"memory");
}
template <int Q, int W, int N> __device__ __forceinline__ void exp_quarter(const float (&S)[N], uint32_t (&P)[32], float (&t)[ROT], float& s0, float& s1, uint32_t nz) {
#pragma unroll
  for (int i = 8 * Q; i < 8 * Q + 8; i++) {
    float& a = t[(2 * i) % ROT];
    float& b = t[(2 * i + 1) % ROT];
    if (2 * i < ROT) { a = ex2(S[2 * i]); b = ex2(S[2 * i + 1]); }
    else { ex2_rot(a, S[2 * i], nz); ex2_rot(b, S[2 * i + 1], nz); }
    if (i < 2) { if (i) s1 = a + b; else s0 = a + b; }
    else if (i & 1) { s1 += a; s1 += b; } else { s0 += a; s0 += b; }
    if (i == 8 * Q) { pin(Q ? s1 : s0, nz); wg_wait<W>(); reg_fence_part<8 * Q, 8>(P); }
    P[i] = pack_bf16(a, b);
  }
}
template <int N> __device__ __forceinline__ void shift_scores(float (&S)[N], float d0, float d1) {
#pragma unroll
  for (int i = 0; i < N; i++) S[i] -= (i & 2) ? d1 : d0;
}
__device__ __forceinline__ bool soft_high(float s0, float s1, float lim = SM_LIMIT) { return s0 > lim || s1 > lim; }
__device__ __forceinline__ bool soft_unsafe(float s0, float s1, bool first) {
  uint32_t b0 = __ballot_sync(0xffffffffu, s0 >= SM_LOW), b1 = __ballot_sync(0xffffffffu, s1 >= SM_LOW);
  b0 |= b0 >> 1; b0 |= b0 >> 2; b1 |= b1 >> 1; b1 |= b1 >> 2;
  return __any_sync(0xffffffffu, soft_high(s0, s1)) || (first && (b0 & b1 & 0x11111111u) != 0x11111111u);
}
template <int N> __device__ __forceinline__ void soft_fix(const float (&S)[N], float (&O)[64], SoftState& z, bool first, float& d0, float& d1) {
  d0 = d1 = first ? -INFINITY : 0.f;
#pragma unroll
  for (int j = 0; j < N / 4; j++) { d0 = fmaxf(d0, fmaxf(S[4 * j], S[4 * j + 1])); d1 = fmaxf(d1, fmaxf(S[4 * j + 2], S[4 * j + 3])); }
  d0 = fmaxf(d0, __shfl_xor_sync(0xffffffffu, d0, 1)); d1 = fmaxf(d1, __shfl_xor_sync(0xffffffffu, d1, 1));
  d0 = fmaxf(d0, __shfl_xor_sync(0xffffffffu, d0, 2)); d1 = fmaxf(d1, __shfl_xor_sync(0xffffffffu, d1, 2));
  const float sc0 = ex2(-fmaxf(d0, 0.f)), sc1 = ex2(-fmaxf(d1, 0.f));
  z.m0 += d0; z.m1 += d1; z.l0 *= sc0; z.l1 *= sc1; z.shifted = 1;
#pragma unroll
  for (int j = 0; j < 16; j++) { O[4 * j] *= sc0; O[4 * j + 1] *= sc0; O[4 * j + 2] *= sc1; O[4 * j + 3] *= sc1; }
}
template <int N> __device__ __forceinline__ void mask_diag(float (&S)[N], float nd) {
  asm volatile("" : "+f"(nd));
#pragma unroll
  for (int i = 0; i < 32; i++) {
    const float beyond = __saturatef(nd + (float)(8 * (i >> 2) + (i & 1) - 4 * (i & 2)));
    S[N - 32 + i] = fmaf(beyond, -3.0e38f, S[N - 32 + i]);
  }
}
__device__ __forceinline__ float quad_sum(float v) {
  v += __shfl_xor_sync(0xffffffffu, v, 1);
  v += __shfl_xor_sync(0xffffffffu, v, 2);
  return v;
}
__device__ __forceinline__ void issue_qk(float (&S)[64], const uint32_t (&Q)[32], uint32_t dk) {
  mma_rs_n128_init<0>(S, Q[0], Q[1], Q[2], Q[3], dk);
#pragma unroll
  for (int s = 1; s < 8; s++) mma_rs_n128<0>(S, Q[4 * s], Q[4 * s + 1], Q[4 * s + 2], Q[4 * s + 3], dk + (s >> 2) * 1024 + (s & 3) * 2, 1);
}
__device__ __forceinline__ void issue_qk(float (&S)[32], const uint32_t (&Q)[32], uint32_t dk) {
  mma_rs_n64<true>(S, Q[0], Q[1], Q[2], Q[3], dk);
#pragma unroll
  for (int s = 1; s < 8; s++) mma_rs_n64<false>(S, Q[4 * s], Q[4 * s + 1], Q[4 * s + 2], Q[4 * s + 3], dk + (s >> 2) * 1024 + (s & 3) * 2);
}
__device__ __forceinline__ void load_q(uint32_t (&Q)[32], uint32_t a) {
  __syncwarp();
#pragma unroll
  for (int jj = 0; jj < 8; jj++)
    asm volatile("ldmatrix.sync.aligned.m8n8.x4.shared.b16 {%0,%1,%2,%3}, [%4];" : "=r"(Q[4 * jj]), "=r"(Q[4 * jj + 1]), "=r"(Q[4 * jj + 2]), "=r"(Q[4 * jj + 3])
                 : "r"((a ^ ((jj & 3) << 5)) + (jj >> 2) * 16384) : "memory");
}
template <int H> __device__ __forceinline__ void issue_pv(float (&O)[64], const uint32_t (&P)[32], uint32_t dv, int acc, bool on) {
  if (on) {
#pragma unroll
    for (int s = 4 * H; s < 4 * H + 4; s++) {
      mma_rs_n128<1>(O, P[4 * s], P[4 * s + 1], P[4 * s + 2], P[4 * s + 3], dv + s * 128, s != 0 ? 1 : acc);
      if (s & 1) wg_commit();
    }
  } else { wg_commit(); wg_commit(); }
}
constexpr uint32_t DG = GR >> 4;
__device__ __forceinline__ void stage_q2(Cons& c, const float (&O)[64], uint32_t (&P)[32], uint32_t stg) {
  wg_commit(); wg_commit(); wg_commit(); wg_commit();
  c.turn_end();
  pack_frag<0>(O, P);
  stsm_frag(P, stg);
}
__device__ __forceinline__ void attn_half(Cons& c, float (&O)[64], uint32_t (&P)[32], uint32_t (&Q)[32], bool nextq, uint32_t stg, SoftState& z, uint32_t dkk, uint32_t dv0, float dmask, int last) {
  float S[32];
  c.turn_begin();
  wg_fence();
  issue_qk(S, Q, dkk + (last ? 8 : 2) * DG);
  wg_commit();
  issue_pv<0>(O, P, dv0 + 10 * DG, 1, last);
  issue_pv<1>(O, P, dv0 + 10 * DG, 1, last);
  c.turn_end();
  c.wait_full(last ? 12 : 4);
  wg_wait<4>();
  reg_fence(S);
  c.release(last ? 8 : 2, 2);
  reg_fence(Q);
  if (nextq) load_q(Q, stg);
  if (last) bar_sync(6, 256);
  mask_diag(S, dmask);
  float s0, s1, d0 = z.m0, d1 = z.m1;
#pragma unroll 1
  for (int pass = 0;; pass++) {
    if (z.shifted) shift_scores(S, d0, d1);
    float tr[ROT];
    exp_quarter<0, 3>(S, P, tr, s0, s1, c.sb);
    exp_quarter<1, 2>(S, P, tr, s0, s1, c.sb);
    pin(s1, c.sb); wg_wait<0>(); reg_fence_part<16, 16>(P); reg_fence(O);
    if (!soft_unsafe(s0, s1, !last) || pass) break;
    soft_fix(S, O, z, !last, d0, d1);
  }
  z.l0 += s0; z.l1 += s1;
  c.release(10, last ? 2 : 0);
  if (!last) c.wait_full(6);
}

template <int V> struct IC { static constexpr int value = V; };
__device__ __forceinline__ int conv_next(int g, bool spare) { return g >= NGR - 2 ? g - (NGR - 4) : !spare && g == 4 ? 1 : g + 2; }
__device__ __forceinline__ void conv_final(uint32_t rb, uint32_t yb, bool on) {
  const uint4 q0 = lds128(rb), q1 = lds128(rb + 4096), q2 = lds128(rb + 8192), q3 = lds128(rb + 12288);
  auto fin = [&](uint32_t x0, uint32_t x1, uint32_t x2, uint32_t x3) { return hadd2(hadd2(x0, x1), hadd2(x2, x3)); };
  asm volatile("{\n.reg .pred p;\nsetp.ne.b32 p, %5, 0;\n@p st.shared.v4.b32 [%0], {%1,%2,%3,%4};\n}\n" ::"r"(yb), "r"(fin(q0.x, q1.x, q2.x, q3.x)),
               "r"(fin(q0.y, q1.y, q2.y, q3.y)), "r"(fin(q0.z, q1.z, q2.z, q3.z)), "r"(fin(q0.w, q1.w, q2.w, q3.w)), "r"((int)on) : "memory");
}
__device__ __forceinline__ void conv_tasks(Cons& c, const Params& p, int ntask, bool spare, int ch, int chstep, int c5, uint32_t dd, uint32_t dkk, int w, int lane) {
  const uint32_t sb = c.sb;
  int g = 2 + c.wg;
  uint32_t rb = sb + g * GR;
  const uint32_t yb = sb + c.wg * 8192 + c.tid * 16;
  const int gt = 8 * w + (lane >> 2) + (lane & 3);
  uint32_t a[64], hb;
  auto lda = [&](int s) {
    a[4 * s] = lds32(hb + s * 256); a[4 * s + 1] = lds32(hb + s * 256 + 128);
    a[4 * s + 2] = lds32(hb + s * 256 + 16); a[4 * s + 3] = lds32(hb + s * 256 + 144);
  };
  auto first_a = [&]() {
    hb = sb + g * GR + WBYTES - 28 + gt * 4;
    lda(0); lda(15);
  };
  c.wait_full(g);
  first_a();
#pragma unroll 1
  for (int i = 0; i < ntask; i++) {
    const uint32_t base = sb + g * GR;
    lda(1); lda(14);
    a[0] = hadd2(a[0], gt == 7 ? dd : 0u); a[2] = hadd2(a[2], gt == 3 ? dd : 0u);
    float acc[128];
    const uint32_t db = dkk + ((WPL / 16 - 1) << 16) + g * DG + WZ / 16;
    c.turn_begin();
    auto pair = [&](auto kc) {
      constexpr int k = decltype(kc)::value;
      if (k < 7) wg_fence();
      if (k == 6) c.turn_end();
      conv_step<k, 7>(acc, a, db);
      conv_step<15 - k, 7>(acc, a, db);
      if (k < 6) { lda(k + 2); lda(13 - k); }
      if (k == 0) conv_final(rb, yb, i > 0);
      if (k == 1) {
        conv_final(rb + 2048, yb + 2048, i > 0);
        __syncwarp();
        if (lane == 0 && i > 0) mbar_arrive(sb + SM_BAR + (B_EV + c.wg) * 8);
      }
      if (k == 6) dd = __bfloat16_as_ushort(p.ssd[(ch + chstep + (i == 1 ? c5 : 0)) & (DM - 1)]);
    };
    pair(IC<0>()); pair(IC<1>()); pair(IC<2>()); pair(IC<3>()); pair(IC<4>()); pair(IC<5>()); pair(IC<6>()); pair(IC<7>());
    wg_commit();
    g = conv_next(g, spare);
    ch += chstep;
    rb = base + c.tid * 16;
    if (i + 1 < ntask) c.wait_full(g);
    const bool fr = mbar_test(sb + SM_BAR + (B_FREE + c.wg) * 8, c.pfree);
    wg_wait<0>();
    reg_fence(acc);
    reg_fence(a);
    bar_sync(3 + c.wg, 128);
    first_a();
    const int tw = (lane & 3) + w;
    const uint32_t xb = base + w * 4096 + tw * 32 + (lane >> 2) * 4;
    [[maybe_unused]] float t0[EROT + 1];
#pragma unroll
    for (int j = 0; j < 32; j++) {
      uint32_t ad = xb + j * 128;
      float v0 = acc[4 * j], v1 = acc[4 * j + 1];
      if (EROT && j > EROT) {
        v0 = t0[j % (EROT + 1)];
        asm("{\n.reg .pred p;\nsetp.ne.u32 p, %3, 0;\n@p add.f32 %0, %1, %2;\n}\n" : "+f"(v0) : "f"(acc[4 * j]), "f"(acc[j > 0 ? 4 * j - 2 : 0]), "r"(sb));
      } else if (j > 0) v0 += acc[j > 0 ? 4 * j - 2 : 0];
      if (j > 0) v1 += acc[j > 0 ? 4 * j - 1 : 0];
      uint32_t v = pack_bf16(v0, v1);
      t0[j % (EROT + 1)] = __uint_as_float(v);
      if (j == 31 && tw >= 4) { v = 0; ad -= 4096; }
      asm volatile("st.shared.b32 [%0], %1;" ::"r"(ad), "r"(v) : "memory");
    }
    if (!fr) c.wait_stage_free(); else c.pfree ^= 1;
  }
  bar_sync(3 + c.wg, 128);
  conv_final(rb, yb, true);
  conv_final(rb + 2048, yb + 2048, true);
  c.staged();
}

__global__ void __cluster_dims__(2, 1, 1) __launch_bounds__(NTHREADS, 1) mega_kernel(const __grid_constant__ Params p) {
  extern __shared__ __align__(1024) uint8_t smem_raw[];
  const uint32_t sb = smem_u32(smem_raw);
  if (threadIdx.x - 64 < 32) { prefetch_tm(&p.c); prefetch_tm(&p.wuk + (blockIdx.x & 1)); }
  const int wgi = __shfl_sync(0xffffffffu, threadIdx.x >> 7, 0);
  const int warp = __shfl_sync(0xffffffffu, threadIdx.x >> 5, 0);
  const uint32_t rank = blockIdx.x & 1;
  int slot;
  {
    uint32_t smid; asm volatile("mov.u32 %0, %smid;" : "=r"(smid));
    slot = p.pref[((smid >> 1) + (threadIdx.x & (smid >> 16))) & 127];
  }
  if (warp >= 3) {
    if (elect()) {
#pragma unroll
      for (int k = 0; k < 4; k++) mbar_init(sb + SM_BAR + ((warp - 3) * 4 + k) * 8, k == 1 && warp == 7 ? 11 : warp < (k ? 7 : 8) ? 1 : 4);
      if (warp == 7) { mbar_init(sb + SM_BAR + B_TICK * 8, 1); mbar_expect_tx(sb + SM_BAR + B_SLOT * 8, 8); mbar_expect_tx(sb + SM_BAR + B_TICK * 8, 4); }
      asm volatile("fence.mbarrier_init.release.cluster;" ::: "memory");
    }
    __syncwarp();
  }
  cluster_arrive();
  slot = __shfl_sync(0xffffffffu, slot, 0);
  const int pref = slot;
  if (warp < 4) {
    asm volatile("setmaxnreg.dec.sync.aligned.u32 40;");
    if (warp == 1 + 4 * rank) {
      unsigned taken = threadIdx.x == 32;
#pragma unroll 1
      for (int n = 0; n < NSLOT; n++) {
        asm volatile("{\n.reg .pred p;\nsetp.ne.b32 p, %0, 0;\n@p atom.relaxed.gpu.global.exch.b32 %0, [%1], 1;\n}\n" : "+r"(taken) : "l"(CLAIMP(slot)) : "memory");
        if (!__any_sync(0xffffffffu, taken)) break;
        slot = slot == NSLOT - 1 ? 0 : slot + 1;
      }
    }
    cluster_wait();
    if (threadIdx.x == 32) {
      send_both(sb + SM_BAR + B_SLOT * 8, (V_SLOT - B_SLOT) * 8 + rank * 4, slot | pref << 8);
    }
    if (warp == 2) {
#pragma unroll 1
      for (int kk = 0; kk < 4; kk++) {
        const int g0 = 2 + 3 * kk;
        const uint32_t fb = sb + SM_BAR + (B_FULL + g0) * 8;
        if (elect()) {
          mbar_expect_tx(fb, 3 * GR);
          tma2d(sb + g0 * GR, &p.c, kk * 64, (KV_ROW(pref & 7, 0) + rank) * 128, fb);
          tma3d_mc(sb + (g0 + 1 + rank) * GR, rank ? &p.wuv : &p.wuk, 0, kk * 64, ((pref & 56) >> 1) + 2 * KV_HEAD(pref & 7, 0), fb);
        }
        if (kk < 3) {
          uint32_t c0, c1;
          asm volatile("mov.u32 %0, %clock;" : "=r"(c0));
          do asm volatile("mov.u32 %0, %clock;" : "=r"(c1)); while (c1 - c0 < (kk ? X_D2 : X_DELAY));
        }
      }
      prefetch_tm(&p.x); prefetch_tm(&p.wq);
    }
  }
  int grp, idx, lb;
  int cn, cch, cstep;
  bool spare, redo;
  auto get_slot = [&]() {
    mbar_wait(sb + SM_BAR + B_SLOT * 8, 0);
    const uint32_t sv0 = __shfl_sync(0xffffffffu, lds32(sb + SM_BAR + V_SLOT * 8), 0), sv1 = __shfl_sync(0xffffffffu, lds32(sb + SM_BAR + V_SLOT * 8 + 4), 0);
    grp = (sv0 & 255) >> 3; idx = sv0 & 7; lb = (sv0 & 255) * 2 + rank;
    spare = grp == 8; redo = spare || sv0 != sv1;
    cn = CN_SPARE; cch = spare ? lb - NMAIN : 4 * CN_SPARE + 4 * lb; cstep = spare ? 4 : 1;
  };
  auto get_ticket = [&]() {
    mbar_wait(sb + SM_BAR + B_TICK * 8, 0);
    const int tk = __shfl_sync(0xffffffffu, lds32(sb + SM_BAR + V_TICK * 8), 0);
    cn = tk < NTICK ? 5 : 4;
    return 4 * NMAIN - 4 * lb - 4 + 2 * tk + rank;
  };

  if (wgi == 0) {
    asm volatile("setmaxnreg.dec.sync.aligned.u32 40;");
    const int lane = threadIdx.x & 31;
    cluster_arrive();
    get_slot();
    uint32_t pe = 0;
    auto acquire = [&](int g, int n, uint32_t m) {
      int i = g;
#pragma unroll 1
      do mbar_wait1(sb + SM_BAR + (B_EMPTY + i) * 8, (pe >> i) & 1); while (++i < g + n);
      pe ^= m << g;
    };
    if (warp == 3) {
      if (!spare) {
        const int s0 = lb * 16;
#pragma unroll 1
        for (int cg = 0; cg < 16; cg++) {
          if (cg == UP0 || cg == UP1) {
#pragma unroll 1
            for (int n = 0; n < 20 && !__any_sync(0xffffffffu, mbar_try(sb + SM_BAR + B_SLOT * 8, cg == UP0)); n++);
          } else if (cg < UP0) __nanosleep(US0);
          if (cg == UP1 && lane == rank * 32) send_both(sb + SM_BAR + B_TICK * 8, (V_TICK - B_TICK) * 8, atomicInc(FLAG(F_TICK), 0x7fffffffu));
          if (cg >= 5 && cg < 9) {
            unsigned l = lane;
            asm volatile("" : "+r"(l));
            const unsigned o = (idx * 8 + (l >> 2)) * (NH * HD) + (16 + 2 * grp) * HD + (l & 3) * 64;
            asm volatile("prefetch.global.L2 [%0];" ::"l"((rank ? p.wuvp : p.wukp) + (o + (cg - 1) * 64 * (NH * HD))));
          }
          const int ch = cg * 64 + 2 * lane;
          const uint32_t* kp = reinterpret_cast<const uint32_t*>(p.ak + (size_t)s0 * DM + ch);
          const uint32_t* vp = reinterpret_cast<const uint32_t*>(p.av + (size_t)s0 * DM + ch);
          const uint4 sw = __ldg(reinterpret_cast<const uint4*>(p.shk + ch * 4));
          uint32_t k3 = 0, k2 = 0, k1 = 0, k0 = 0, up = 0;
          if (lb > 0) { k3 = ldg_stream(kp - 4 * 512); k2 = ldg_stream(kp - 3 * 512); k1 = ldg_stream(kp - 2 * 512); k0 = ldg_stream(kp - 512); up = ldg_stream(vp - 512); }
          const uint32_t w0 = __byte_perm(sw.x, sw.z, 0x5410), w1 = __byte_perm(sw.x, sw.z, 0x7632);
          const uint32_t w2 = __byte_perm(sw.y, sw.w, 0x5410), w3 = __byte_perm(sw.y, sw.w, 0x7632);
          up = hmul2(hfma2(k0, w0, hfma2(k1, w1, hfma2(k2, w2, hmul2(k3, w3)))), up);
#pragma unroll 1
          for (int hb = 0; hb < 2; hb++) {
            uint32_t kk[8], u[8];
#pragma unroll
            for (int r = 0; r < 8; r++) { kk[r] = ldg_stream(kp + r * 512); u[r] = ldg_stream(vp + r * 512); }
#pragma unroll
            for (int r = 0; r < 8; r++) {
              k3 = k2; k2 = k1; k1 = k0; k0 = kk[r];
              u[r] = hmul2(hfma2(k0, w0, hfma2(k1, w1, hfma2(k2, w2, hmul2(k3, w3)))), u[r]);
            }
            if (lane == 0) asm volatile("cp.async.bulk.wait_group.read 0;" ::: "memory");
            __syncwarp();
            const uint32_t dst = sb + SM_UST + lane * 32 + ((lane & 4) << 2);
#pragma unroll
            for (int cc = 0; cc < 2; cc++) {
              const uint32_t sel = cc ? 0x7632 : 0x5410;
              asm volatile("st.shared.v4.b32 [%0], {%1,%2,%3,%4};" ::"r"(dst + cc * 1024), "r"(__byte_perm(u[6], u[5], sel)), "r"(__byte_perm(u[4], u[3], sel)),
                           "r"(__byte_perm(u[2], u[1], sel)), "r"(__byte_perm(u[0], up, sel)) : "memory");
              asm volatile("st.shared.v4.b32 [%0], {%1,%2,%3,%4};" ::"r"((dst ^ 16) + cc * 1024), "r"(__byte_perm(u[7], u[6], sel)), "r"(__byte_perm(u[5], u[4], sel)),
                           "r"(__byte_perm(u[3], u[2], sel)), "r"(__byte_perm(u[1], u[0], sel)) : "memory");
            }
            fence_async_smem();
            __syncwarp();
            if (lane == 0) {
              asm volatile("cp.async.bulk.tensor.3d.global.shared::cta.bulk_group.L2::cache_hint [%0, {%2, %3, %4}], [%1], %5;\ncp.async.bulk.commit_group;"
                           ::"l"(&p.w), "r"(sb + SM_UST), "r"(WZ / 2 + lb * 16 + (hb ^ 1) * (WPL / 2)), "r"(cg * 32), "r"(0), "l"(cg >= UP0 && cg < UP1 ? EV_FIRST : EV_NORMAL) : "memory");
            }
            up = u[7];
            kp += 8 * 512; vp += 8 * 512;
          }
          if ((cg & (cg + 1)) == 0 && lane == 0) {
            asm volatile("cp.async.bulk.wait_group 0;" ::: "memory");
            fence_release();
            flag_add(FLAG(F_U + 32 - __clz(cg)));
          }
        }
        prefetch_tm(&p.wo); prefetch_tm(&p.x3); prefetch_tm(&p.y3); prefetch_tm(&p.out);
      } else {
#pragma unroll 1
        for (int i = 0, g = 2; i < 32; i++) {
          acquire(g, 2, 3);
          if (elect()) {
            const uint32_t fb = sb + SM_BAR + (B_FULL + g) * 8;
            if (i == 0) { mbar_expect_tx(fb - 8, 2048); bulk_g2s(sb + GR, p.gate_w, 2048, fb - 8); }
            mbar_expect_tx(fb, 2 * GR);
            tma3d(sb + g * GR, &p.x3, 0, (lb - NMAIN) * 512 + (i >> 3) * 128, (i & 7) * 2, fb);
          }
          g = g == NGR - 2 ? 2 : g + 2;
        }
        bar_arrive(5, 64);
      }
      unsigned long long t0, t1;
      asm volatile("mov.u64 %0, %globaltimer;" : "=l"(t0));
      auto check = [&]() {
        asm volatile("mov.u64 %0, %globaltimer;" : "=l"(t1));
        if (t1 - t0 > 2000000000ull) __trap();
      };
      if (!spare) {
        unsigned v;
        do {
          __nanosleep(PSL);
          check();
          asm volatile("ld.acquire.gpu.global.u32 %0, [%1];" : "=r"(v) : "l"(FLAG(lane & 1 ? F_Y + idx : F_GATE)) : "memory");
        } while (__any_sync(0xffffffffu, v < (lane & 1 ? 128 : 32)));
        __syncwarp();
        if (lane == 0) mbar_arrive(sb + SM_BAR + B_SLOT * 8);
      }
      if (lane == 0) {
        while (!mbar_try(sb + SM_BAR + B_DONE * 8, 0)) check();
      }
    } else if (warp != 0) {
      const int w = warp - 1;
      int ne = 12 + (CN_SPARE + 1 - w) / 2, c5 = 0;
      int cg = 2 + w, ch = cch + w * cstep;
#pragma unroll 1
      for (int e = spare ? 12 : 0; e < ne; e++) {
        const int rnd = e >= 6, k = e - 6 * rnd, rt = k == 4 ? idx : 15 - idx;
        uint8_t* dst = k < 4 ? g_kv + (size_t)(((k & 1) * 16 + 2 * grp + KV_HEAD(idx, k >> 1)) * 16 + KV_ROW(idx, k >> 1) + rank) * 32768 + w * 8192
                     : k < 6 ? g_cimg + (size_t)(rt * 32 + 16 * rnd + 2 * grp + rank) * 32768 + (w ^ (k & 1)) * 8192
                             : g_w + (size_t)ch * WSTRIDE + WZ;
        const uint32_t src = sb + w * 8192;
        if (e == 11) { c5 = get_ticket(); ne = 12 + ((cn + 1 - w) >> 1); }
        if (e == 6) flag_wait(FLAG(F_AD + grp), 32);
        mbar_wait1(sb + SM_BAR + (B_EV + w) * 8, e & 1);
        if (lane < 4 && k >= 6 && (!spare || e < ne - 6)) mbar_arrive_cluster(sb + SM_BAR + (B_EMPTY + cg) * 8, lane & 1);
        fence_async_smem();
        if (elect()) {
          const uint32_t cs = k >= 6 ? 4096 : 1024;
#pragma unroll 1
          for (uint32_t i = 0; i < (k >= 6 ? 4096 : 16384); i += cs) {
            const uint32_t o = i + (i & 8192);
            asm volatile("cp.async.bulk.global.shared::cta.bulk_group.L2::cache_hint [%0], [%1], %2, %3;" ::"l"(dst + o), "r"(src + o), "r"(cs),
                         "l"(e == 4 || e == 5 || spare ? EV_FIRST : EV_NORMAL) : "memory");
            asm volatile("cp.async.bulk.commit_group;\ncp.async.bulk.wait_group.read 1;" ::: "memory");
          }
          asm volatile("cp.async.bulk.wait_group 0;" ::: "memory");
          mbar_arrive(sb + SM_BAR + (B_FREE + w) * 8);
        }
        __syncwarp();
        if (lane < (e == 11 || (e == ne - 1 && !spare) ? 2 : 0)) mbar_arrive_cluster(sb + SM_BAR + (B_EMPTY + (e == 11)) * 8, lane);
        if (k >= 3) {
          fence_release();
          const unsigned fl = k == 3 ? F_KV + rnd * 8 + grp : k < 6 ? F_CTX + rt * 2 + rnd : F_Y + ((unsigned)ch >> 7);
          if (lane <= (e == 5)) flag_add(FLAG(lane ? F_AD + grp : fl));
        }
        if (k >= 6) { cg = conv_next(cg, spare); ch += 2 * cstep + (k == 7 ? c5 : 0); }
      }
      if (lane == 0) mbar_arrive(sb + SM_BAR + B_DONE * 8);
    } else {
#pragma unroll 1
      for (int rnd = 0; rnd < (spare ? 0 : 2); rnd++) {
        const int hp = 16 * rnd + 2 * grp, head = hp + rank;
#pragma unroll 1
        for (int kk = rnd || redo ? 0 : 4; kk < 32; kk++) {
          const int g0 = 2 + 3 * (kk & 3);
          acquire(g0, kk < 4 ? 3 : 1, 7);
          if (elect()) {
            const uint32_t fb = sb + SM_BAR + (B_FULL + g0) * 8;
            mbar_expect_tx(fb, 3 * GR);
            if (kk < 16) {
              tma2d_p(sb + g0 * GR, &p.c, (kk & 7) * 64, (KV_ROW(idx, kk >> 3) + rank) * 128, fb, rnd);
              tma3d_mc_p(sb + (g0 + 1 + rank) * GR, rank ? &p.wuv : &p.wuk, 0, (kk & 7) * 64, (hp + KV_HEAD(idx, kk >> 3)) * 2, fb, kk >= 8);
            } else {
              tma2d_mc(sb + (g0 + rank) * GR, &p.x, (kk - 16) * 64, (rank ? 15 - idx : idx) * 128, fb);
              tma3d<true>(sb + (g0 + 2) * GR, &p.wq, 0, (kk - 16) * 64, head * 2, fb);
            }
          }
        }
        flag_wait(FLAG(F_KV + rnd * 8 + grp), 32);
        fence_async_all();
        int g0 = 2;
#pragma unroll 1
        for (int n = 0; n < 36; n += n == 0 || n == 33 ? 2 : 1) {
          const int it = (n >> 1) - (n & 1);
          const int blk = it & 15 ? (it <= idx ? it - 1 : 15 - it) : it ? 15 - idx : idx;
          acquire(g0, n < 7 ? 2 : 1, 3);
          if (elect()) {
            const uint32_t fb = sb + SM_BAR + (B_FULL + g0) * 8;
            if (n == 5) mbar_arrive(sb + SM_BAR + B_SLOT * 8);
            mbar_expect_tx(fb, 2 * GR);
            asm volatile("cp.async.bulk" TMA_MB ".L2::cache_hint [%0], [%1], %2, [%3], %4;" ::"r"(sb + g0 * GR), "l"(g_kv + (unsigned)((((n & 1) * 16 + (head & 15)) * 16 + blk) * 32768)),
                         "r"(2 * GR), "r"(fb), "l"(it >= 8 ? EV_FIRST : EV_NORMAL) : "memory");
          }
          g0 = g0 == 12 ? 2 : g0 + (n == 13 || n == 19 ? 4 : 2);
        }
      }
      int c5 = 0;
      if (spare) { bar_sync(5, 64); pe = 0x3FC0; }
      else c5 = get_ticket();
      auto conv_fill = [&](int g, int ch) {
        acquire(g, 1, 1);
        if (elect()) {
          const uint32_t fb = sb + SM_BAR + (B_FULL + g) * 8;
          mbar_expect_tx(fb, WBYTES + 4096);
          bulk_g2s<true>(sb + g * GR, g_w + (size_t)ch * WSTRIDE, WBYTES, fb);
          bulk_g2s<true>(sb + g * GR + WBYTES, p.ssk + (size_t)ch * SEQ, 4096, fb);
        }
      };
#pragma unroll 1
      for (int i = 0, g = 2; i < cn; i++) {
        if ((i & 15) == 0) { flag_wait(FLAG(F_U + (spare ? 32 - __clz(i >> 4) : 4)), NMAIN); fence_async_all(); }
        conv_fill(g + (i & 1), cch + i * cstep + (i == 4 ? c5 : 0));
        if (i & 1) g = conv_next(g, spare);
      }
      if (!spare) {
        const int rt = 2 * grp + rank, ct = idx;
        int g0 = P3G, top = 12;
        const uint8_t* src = g_cimg + (unsigned)((rt * 64 + 32) * GR);
#pragma unroll 1
        for (int kb = 0; kb < 64; kb++) {
          if (!(kb & 31)) { flag_wait(FLAG(F_CTX + rt * 2 + ((kb ^ 32) >> 5)), 32); fence_async_all(); if (kb) src -= 64 * GR; }
          acquire(g0, kb < 11 ? 2 : 1, 3);
          if (elect()) {
            const uint32_t fb = sb + SM_BAR + (B_FULL + g0) * 8;
            mbar_expect_tx(fb, 2 * GR);
            bulk_g2s<true>(sb + g0 * GR, src, GR, fb);
            tma2d_mc<true>(sb + (g0 + 1) * GR + rank * 8192, &p.wo, ct * 128 + rank * 64, (kb ^ 32) * 64, fb);
          }
          src += GR;
          g0 = g0 == (kb < XK ? 12 : kb < YK ? 10 : 8) ? (kb == 3 ? 2 : 0) : g0 + 2;
          if (kb == XK || (kb >= YK && top == P3Y && (kb == 63 || mbar_test(sb + SM_BAR + B_SLOT * 8, 1)))) {
            const bool j = kb != XK;
            if (j) { mbar_wait1(sb + SM_BAR + B_SLOT * 8, 1); fence_async_all(); }
            acquire(top, 1, 0);
            if (elect()) {
              const uint32_t fb = sb + SM_BAR + (B_FULL + top) * 8;
              mbar_expect_tx(fb, j ? 2 * GR + 512 : 2 * GR);
              if (j) bulk_g2s(sb + SM_GATE, g_gate + (unsigned)(rt * 128), 512, fb);
              tma3d(sb + top * GR, j ? &p.y3 : &p.x3, 0, (j ? ct : rt) * 128, (j ? rt : ct) * 2, fb);
            }
            top -= 2;
          }
        }
        unsigned n = 0;
        if (lane == 0) n = atomicInc(FLAG(F_EXIT), 0x7fffffffu);
        if (__any_sync(0xffffffffu, n == NMAIN - 1)) {
#pragma unroll
          for (int i = lane; i < 96; i += 32) *reinterpret_cast<uint2*>(FLAG(i)) = make_uint2(0, 0);
        }
      }
      if (lane == 0) mbar_arrive(sb + SM_BAR + B_DONE * 8);
    }
    __syncwarp();
    cluster_wait();
  } else {
    asm volatile("setmaxnreg.inc.sync.aligned.u32 232;");
    Cons c;
    c.sb = sb; c.pf = 0; c.wg = wgi - 1; c.tid = threadIdx.x & 127;
    const int lane = threadIdx.x & 31, t = lane & 3;
    const int row = c.wg * 64 + (warp & 3) * 16 + (lane >> 2);
    const uint32_t dkk = desc_k(sb), dk0 = dkk + c.wg * 512, dm0 = desc_mn<8192>(sb), dv0 = desc_mn<16384>(sb);
    const uint32_t dsw = DG + 512 - c.wg * 1024;
    if (c.wg == 1) bar_arrive(1, 256);
    c.pfree = 1;
    asm("mapa.shared::cluster.u32 %0, %1, %2;" : "=r"(c.relb) : "r"(sb + SM_BAR + (B_EMPTY + (c.tid >> 1)) * 8), "r"(c.tid & 1));
    c.zero = p.zero;
    const uint32_t stg = sb + (c.wg * 64 + (warp & 3) * 16 + ((lane >> 3) & 1) * 8 + (lane & 7)) * 128 + (((lane >> 4) ^ (lane & 7)) << 4);

    uint32_t dd0;
    auto load_dd = [&]() { asm volatile("ld.global.nc.u16 %0, [%1];" : "=r"(dd0) : "l"(p.ssd + (unsigned)(cch + c.wg * cstep + (lane & c.zero)))); };
    int pass = c.zero;
#pragma unroll 1
    do {
    if (pass) {
      load_dd();
#pragma unroll 1
      for (int g = 2; g < NGR; g += 3) { mbar_wait(sb + SM_BAR + (B_FULL + g) * 8, 0); c.release(g, 3); }
      c.pf = 0x924;
    if (spare) {
      c.wait_full(1);
      int g = 2;
#pragma unroll 1
      for (int r = 0; r < 4; r++) {
        float d[4] = {0.f, 0.f, 0.f, 0.f}, e[4] = {0.f, 0.f, 0.f, 0.f};
#pragma unroll 1
        for (int kb = 0; kb < 16; kb += 2) {
          c.wait_full(g);
          wg_fence();
#pragma unroll 1
          for (int k = 0; k < 4; k++) {
            mma_ss_n8(d, dk0 + g * DG + k * 2, dkk + DG + kb * 8 + k * 2);
            mma_ss_n8(e, dk0 + (g + 1) * DG + k * 2, dkk + DG + kb * 8 + 8 + k * 2);
          }
          wg_commit();
          wg_wait<0>();
          c.release(g, 2);
          g = g == NGR - 2 ? 2 : g + 2;
        }
        reg_fence(d); reg_fence(e);
        d[0] += e[0]; d[2] += e[2];
        if (t == 0) {
          float* gp = g_gate + (unsigned)((lb - NMAIN) * 512 + r * 128 + row);
          gp[0] = rcp(1.f + ex2(-1.4426950408889634f * d[0])); gp[8] = rcp(1.f + ex2(-1.4426950408889634f * d[2]));
        }
      }
      fence_release();
      __syncwarp();
      if (lane == 0) flag_add(FLAG(F_GATE));
    }
    } else cluster_wait();
    get_slot();
    } while (redo && !pass++);
    const float dmask = (float)(2 * t - (row & 63));
    int c5 = 0;
    uint32_t pv[32];
#pragma unroll 1
    for (int rnd = 0; rnd < (spare ? 0 : 2); rnd++) {
      float O[64];
      uint32_t Q[32];
      c.wait_full(2);
#pragma unroll 1
      for (int tile = c.zero; tile < 2; tile++) {
        float acc[128];
        const bool single = tile == 0;
        {
          const uint32_t a = dk0 + 2 * DG, b = dm0 + 3 * DG;
          c.turn_begin();
          wg_fence();
          mma_ss_n256_init<1>(acc, a, b);
#pragma unroll
          for (int k = 1; k < 4; k++) mma_ss_n256<1>(acc, a + k * 2, b + k * 128);
          wg_commit();
          if (single) c.turn_end();
        }
#pragma unroll 1
        for (int kb = 1; kb < 8; kb++) {
          const int g0 = 2 + 3 * (kb & 3);
          const uint32_t a = dk0 + g0 * DG, b = dm0 + (g0 + 1) * DG;
          const bool second = (kb == 1 && !single) || kb == 7;
          if (!second) { wg_wait<0>(); c.release(2 + 3 * ((kb - 1) & 3), 3); }
          c.wait_full(g0);
          if (!second) c.turn_begin();
          wg_fence();
#pragma unroll
          for (int k = 0; k < 4; k++) mma_ss_n256<1>(acc, a + k * 2, b + k * 128);
          wg_commit();
          if (kb != 6) c.turn_end();
          if (second) { wg_wait<1>(); c.release(2 + 3 * ((kb - 1) & 3), 3); }
          if (tile == 1 && kb == 3) { c.wait_stage_free(); stsm_frag<0, 4>(pv, stg); }
          if (tile == 1 && kb == 4) { stsm_frag<4, 8>(pv, stg); c.staged(); }
        }
        c.wait_stage_free();
        const bool nxt = c.try_full(2);
        wg_wait<0>();
        reg_fence(acc);
        c.release(11, 3);
        store_scaled(acc, SM_C, SM_C, stg, sb);
        c.staged();
        pack_frag<64>(acc, pv);
        if (!nxt) mbar_wait(sb + SM_BAR + (B_FULL + 2) * 8, (c.pf >> 2) & 1);
        c.pf ^= 4;
      }
      {
        float qa[64];
        float (&qb)[64] = O;
        {
          const uint32_t a = dk0 + 2 * DG, b = dm0 + 4 * DG;
          c.turn_begin();
          wg_fence();
          mma_ss_n128_init<1>(qa, a, b);
          mma_ss_n128_init<1>(qb, a + dsw, b);
#pragma unroll
          for (int k = 1; k < 4; k++) {
            mma_ss_n128<1>(qa, a + k * 2, b + k * 128);
            mma_ss_n128<1>(qb, a + dsw + k * 2, b + k * 128);
          }
          wg_commit();
        }
#pragma unroll 1
        for (int kb = 1; kb < 16; kb++) {
          const int g0 = 2 + 3 * (kb & 3);
          const uint32_t a = dk0 + g0 * DG, b = dm0 + (g0 + 2) * DG;
          const bool second = kb == 1 || kb == 15;
          if (!second) { wg_wait<0>(); c.release(2 + 3 * ((kb - 1) & 3), 3); }
          c.wait_full(g0);
          if (!second) c.turn_begin();
          wg_fence();
#pragma unroll
          for (int k = 0; k < 4; k++) {
            mma_ss_n128<1>(qa, a + k * 2, b + k * 128);
            mma_ss_n128<1>(qb, a + dsw + k * 2, b + k * 128);
          }
          wg_commit();
          if (kb != 14) c.turn_end();
          if (second) { wg_wait<1>(); c.release(2 + 3 * ((kb - 1) & 3), 3); }
          if (kb == QFLUSH) { c.wait_stage_free(); stsm_frag<0, 4>(pv, stg); }
          if (kb == QFLUSH + 1) { stsm_frag<4, 8>(pv, stg); c.staged(); }
        }
        c.wait_stage_free();
        const bool k0 = c.try_full(2);
        wg_wait<0>();
        reg_fence(qa); reg_fence(qb);
        c.release(11, 3);
        pack_frag<0>(qa, Q);
        if (c.wg == 0) {
          pack_frag<0>(qb, pv);
          stsm_frag(pv, stg);
        }
        if (!k0) c.wait_full(2); else c.pf ^= 4;
      }
      {
        const int nA = idx + 1;
        uint32_t (&P)[32] = pv;
        SoftState z;
        z.m0 = z.m1 = z.l0 = z.l1 = 0.f; z.shifted = c.zero;
#pragma unroll 1
        for (int seg = c.zero;; seg++) {
        if (c.wg == seg) attn_half(c, O, P, Q, nA == 1 && !seg, stg, z, dkk, dv0, dmask, seg);
        if (seg) break;
        int gk = c.wg ? 2 : 4, gv = c.wg ? 2 : 6;
        uint32_t dk = dkk + gk * DG;
#pragma unroll 1
        for (int it = 1 - c.wg; it < 17 - c.wg; it++) {
          float S[64];
          c.turn_begin();
          wg_fence();
          issue_qk(S, Q, dk);
          wg_commit();
          const uint32_t dv = dv0 + gv * DG;
          uint32_t relk = c.relb + gk * 8, relv = c.relb + gv * 8;
          gk = gv == 12 ? 2 : gv + (it == 6 || it == 9 ? 4 : 2);
          gv = it == 16 ? gk : gk == 12 ? 2 : gk + 2;
          uint32_t fk = sb + SM_BAR + (B_FULL + gk) * 8, fv = sb + SM_BAR + (B_FULL + gv) * 8, park = (c.pf >> gk) & 1, parv = (c.pf >> gv) & 1;
          c.pf ^= (1u << gk) | (1u << gv);
          dk = dkk + gk * DG;
          float lo0 = z.l0, lo1 = z.l1;
          const bool first = it == nA || it == 0;
          if (it == nA) {
            lo0 = rcp(quad_sum(lo0)); lo1 = rcp(quad_sum(lo1));
            z.m0 = z.m1 = z.l0 = z.l1 = 0.f; z.shifted = 0;
          }
          float s0, s1, d0 = z.m0, d1 = z.m1;
          int pre = z.shifted || (it & 15) == 0 || it + 1 == nA;
          float lim = first ? -1.f : SM_LIMIT;
          asm volatile("" : "+r"(relk), "+r"(relv), "+r"(fk), "+r"(fv), "+r"(park), "+r"(parv), "+r"(dk), "+r"(pre), "+f"(lim), "+f"(d0), "+f"(d1), "+f"(z.l0), "+f"(z.l1));
          if (it + c.wg > 1) {
            issue_pv<0>(O, P, dv, it != nA + 1 && it != 1, true);
            issue_pv<1>(O, P, dv, 1, true);
            c.turn_end();
          } else if (it) {
            issue_pv<0>(O, P, dv, 0, true);
            wg_commit(); wg_commit();
            c.turn_end();
            bar_sync(6, 256);
          } else stage_q2(c, O, P, stg);
          wg_wait<4>();
          reg_fence(S); reg_fence(Q);
          if (c.tid < 4) asm volatile("mbarrier.arrive.shared::cluster.b64 _, [%0];" ::"r"(relk) : "memory");
#pragma unroll 1
          for (int pass = 0;; pass++) {
            if (pre) {
              if (it + 1 == nA) load_q(Q, stg);
              if ((it & 15) == 0) mask_diag(S, dmask);
              if (z.shifted) shift_scores(S, d0, d1);
            }
            float tr[ROT];
            exp_quarter<0, 3>(S, P, tr, s0, s1, sb);
            exp_quarter<1, 2>(S, P, tr, s0, s1, sb);
            exp_quarter<2, 1>(S, P, tr, s0, s1, sb);
            exp_quarter<3, 0>(S, P, tr, s0, s1, sb);
            reg_fence(O);
            if (c.tid < (pass || !it ? 0 : 4)) asm volatile("mbarrier.arrive.shared::cluster.b64 _, [%0];" ::"r"(relv) : "memory");
            const bool ok = mbar_test(fk, park) & mbar_test(fv, parv);
            if (!ok) lim = -1.f;
            if (!__any_sync(0xffffffffu, !(s0 <= lim && s1 <= lim))) break;
            if (pass) break;
            if (it == nA) {
              store_scaled(O, lo0, lo1, stg, sb);
              c.staged();
            }
            if (!it) bar_arrive(6, 256);
            if (!ok) { mbar_wait(fk, park); mbar_wait(fv, parv); }
            if (!soft_unsafe(s0, s1, first)) break;
            soft_fix(S, O, z, first, d0, d1);
            pre = 1;
          }
          z.l0 += s0; z.l1 += s1;
        }
        if (!c.wg) bar_arrive(6, 256);
        }
        load_dd();
        c.turn_begin();
        wg_fence();
        issue_pv<0>(O, P, dv0 + 12 * DG, 1, true);
        issue_pv<1>(O, P, dv0 + 12 * DG, 1, !c.wg);
        c.turn_end();
        z.l0 = rcp(quad_sum(z.l0)); z.l1 = rcp(quad_sum(z.l1));
        c.wait_stage_free();
        if (rnd) c5 = get_ticket();
        wg_wait<0>();
        reg_fence(O); reg_fence(P);
        c.release(12, 2);
        store_scaled(O, z.l0, z.l1, stg, sb);
        c.staged();
      }
    }
    conv_tasks(c, p, (cn + 1 - c.wg) >> 1, spare, cch + c.wg * cstep, 2 * cstep, c5, dd0, dkk, warp & 3, lane);
    if (c.wg == 1) c.pf ^= 0x14;
    if (c.wg == (cn & 1)) c.turn_begin();
    if (!spare) {
      const int rt = 2 * grp + rank, ct = idx;
      float acc[64];
      int g0 = P3G + 2, pg = P3G;
      {
        c.wait_full(P3G);
        const uint32_t a = dk0 + P3G * DG, b = dm0 + (P3G + 1) * DG;
        wg_fence();
        mma_ss_n128_init<1>(acc, a, b);
#pragma unroll
        for (int k = 1; k < 4; k++) mma_ss_n128<1>(acc, a + k * 2, b + k * 128);
        wg_commit();
      }
#pragma unroll 1
      for (int kb = 1; kb < 64; kb++) {
        c.wait_full(g0);
        if (kb == STR && !c.wg) c.turn_begin();
        const uint32_t a = dk0 + g0 * DG, b = dm0 + (g0 + 1) * DG;
        wg_fence();
#pragma unroll
        for (int k = 0; k < 4; k++) mma_ss_n128<1>(acc, a + k * 2, b + k * 128);
        wg_commit();
        if (kb < STR) { wg_wait<1>(); c.release(pg, kb <= 59 ? 2 : 0); }
        pg = g0;
        g0 = g0 == (kb < XK ? 12 : kb < YK ? 10 : 8) ? (kb == 3 ? 2 : 0) : g0 + 2;
      }
      if (c.wg) c.turn_end();
      cluster_arrive();
      c.wait_full(P3X);
      c.wait_full(P3Y);
      const float g0f = __uint_as_float(lds32(sb + SM_GATE + row * 4)), g1f = __uint_as_float(lds32(sb + SM_GATE + row * 4 + 32));
      const uint32_t gp0 = pack_bf16(g0f, g0f), gp1 = pack_bf16(g1f, g1f);
      const float h0 = 1.f - g0f, h1 = 1.f - g1f;
      const int w = warp & 3;
      const uint32_t xa = stg + P3X * GR;
      const uint32_t ya = sb + P3Y * GR + c.wg * 16384 + ((lane >> 4) * 8 + (lane & 7)) * 128 + (((2 * w + ((lane >> 3) & 1)) ^ (lane & 7)) << 4);
      uint32_t xy[32];
      auto prep = [&](int j0, int j1) {
#pragma unroll
        for (int jj = j0; jj < j1; jj++) {
          uint32_t x[4], y[4];
          asm volatile("ldmatrix.sync.aligned.m8n8.x4.shared.b16 {%0,%1,%2,%3}, [%4];" : "=r"(x[0]), "=r"(x[1]), "=r"(x[2]), "=r"(x[3]) : "r"((xa ^ ((jj & 3) << 5)) + (jj >> 2) * 16384) : "memory");
          asm volatile("ldmatrix.sync.aligned.m8n8.x4.trans.shared.b16 {%0,%1,%2,%3}, [%4];" : "=r"(y[0]), "=r"(y[1]), "=r"(y[2]), "=r"(y[3]) : "r"(ya + jj * 2048) : "memory");
#pragma unroll
          for (int i = 0; i < 4; i++) xy[4 * jj + i] = hmul2(x[i], y[i]);
        }
      };
      prep(0, 4);
      wg_wait<0>();
      reg_fence(acc);
#pragma unroll
      for (int hf = 0; hf < 2; hf++) {
#pragma unroll
        for (int i = 16 * hf; i < 16 * hf + 16; i++) {
          const float h = (i & 1) ? h1 : h0;
          xy[i] = hfma2((i & 1) ? gp1 : gp0, xy[i], pack_bf16(acc[2 * i] * h, acc[2 * i + 1] * h));
        }
        if (hf) stsm_frag<4, 8>(xy, xa); else stsm_frag<0, 4>(xy, xa);
        fence_async_smem();
        __syncwarp();
        const int r0 = c.wg * 64 + w * 16;
        if (lane == 0) tma2d_store(&p.out, sb + (P3X + hf) * GR + r0 * 128, ct * 128 + hf * 64, rt * 128 + r0);
        if (!hf) prep(4, 8);
      }
      if (lane == 0) asm volatile("cp.async.bulk.commit_group;\ncp.async.bulk.wait_group.read 0;" ::: "memory");
    } else { cluster_arrive(); }
    if (lane == 0) mbar_arrive(sb + SM_BAR + B_DONE * 8);
    __syncwarp();
    cluster_wait();
  }
}

typedef CUresult (*EncFn)(CUtensorMap*, CUtensorMapDataType, cuuint32_t, void*, const cuuint64_t*, const cuuint64_t*, const cuuint32_t*,
                          const cuuint32_t*, CUtensorMapInterleave, CUtensorMapSwizzle, CUtensorMapL2promotion, CUtensorMapFloatOOBfill);

void enc2d(EncFn enc, CUtensorMap* tm, const void* base, uint64_t cols, uint64_t rows, uint32_t bc, uint32_t br) {
  cuuint64_t dims[2] = {cols, rows}; cuuint64_t strides[1] = {cols * 2}; cuuint32_t box[2] = {bc, br}; cuuint32_t es[2] = {1, 1};
  enc(tm, CU_TENSOR_MAP_DATA_TYPE_BFLOAT16, 2, const_cast<void*>(base), dims, strides, box, es, CU_TENSOR_MAP_INTERLEAVE_NONE,
      CU_TENSOR_MAP_SWIZZLE_128B, CU_TENSOR_MAP_L2_PROMOTION_L2_256B, CU_TENSOR_MAP_FLOAT_OOB_FILL_NONE);
}
void enc3d(EncFn enc, CUtensorMap* tm, const void* base, uint64_t K, uint64_t N, uint32_t bk = 64, uint64_t pitch = 0) {
  cuuint64_t dims[3] = {64, K, N / 64}; cuuint64_t strides[2] = {pitch ? pitch : N * 2, 128}; cuuint32_t box[3] = {64, bk, 2}; cuuint32_t es[3] = {1, 1, 1};
  enc(tm, CU_TENSOR_MAP_DATA_TYPE_BFLOAT16, 3, const_cast<void*>(base), dims, strides, box, es, CU_TENSOR_MAP_INTERLEAVE_NONE,
      CU_TENSOR_MAP_SWIZZLE_128B, CU_TENSOR_MAP_L2_PROMOTION_L2_256B, CU_TENSOR_MAP_FLOAT_OOB_FILL_NONE);
}

}

extern "C" void kernel_launch(void* const* d_in, const int* in_sizes, int n_in, void* d_out, int out_size) {
  (void)in_sizes; (void)n_in; (void)out_size;
  typedef const __nv_bfloat16* BP;
  BP xq = (BP)d_in[0], ak = (BP)d_in[1], av = (BP)d_in[2], shk = (BP)d_in[3], ssk = (BP)d_in[4], ssd = (BP)d_in[5];
  BP ckv = (BP)d_in[7], wq = (BP)d_in[8], wuk = (BP)d_in[9], wuv = (BP)d_in[10], wo = (BP)d_in[11], gw = (BP)d_in[12];

  static EncFn enc = nullptr;
  if (!enc) {
    cudaDriverEntryPointQueryResult qr;
    cudaGetDriverEntryPoint("cuTensorMapEncodeTiled", (void**)&enc, cudaEnableDefault, &qr);
    cudaFuncSetAttribute(mega_kernel, cudaFuncAttributeMaxDynamicSharedMemorySize, SMEM_BYTES);
  }
  Params p;
  enc2d(enc, &p.x, xq, DM, SEQ, 64, 128);
  enc2d(enc, &p.c, ckv, DC, SEQ, 64, 128);
  enc3d(enc, &p.wq, wq, DM, NH * HD);
  enc3d(enc, &p.wuk, wuk, DC, NH * HD);
  enc3d(enc, &p.wuv, wuv, DC, NH * HD);
  enc2d(enc, &p.wo, wo, DM, NH * HD, 64, 64);
  enc3d(enc, &p.x3, xq, SEQ, DM, 128);
  enc2d(enc, &p.out, d_out, DM, SEQ, 64, 16);
  {
    void* wp = nullptr;
    cudaGetSymbolAddress(&wp, g_w);
    enc3d(enc, &p.y3, (uint8_t*)wp + WZ, DM, SEQ, 128, WSTRIDE);
    cuuint64_t dims[3] = {WSTRIDE / 2, DM / 2, 2}; cuuint64_t strides[2] = {2 * WSTRIDE, WSTRIDE}; cuuint32_t box[3] = {16, 32, 2}; cuuint32_t es[3] = {1, 1, 1};
    enc(&p.w, CU_TENSOR_MAP_DATA_TYPE_BFLOAT16, 3, wp, dims, strides, box, es, CU_TENSOR_MAP_INTERLEAVE_NONE,
        CU_TENSOR_MAP_SWIZZLE_32B, CU_TENSOR_MAP_L2_PROMOTION_NONE, CU_TENSOR_MAP_FLOAT_OOB_FILL_NONE);
  }
  p.zero = 0;
  cudaGetSymbolAddress((void**)&p.flags, g_flags);
  for (int i = 0; i < 128; i++) {
    const int tp = i % NSLOT;
    p.pref[i] = tp < 32 ? (tp & 7) * 8 + (tp >> 3) : tp < 60 ? (1 + (tp - 32) % 7) * 8 + 4 + (tp - 32) / 7 : tp < 62 ? tp + 4 : tp - 58;
  }
  p.gate_w = gw; p.ak = ak; p.av = av; p.shk = shk; p.ssk = ssk; p.ssd = ssd; p.wukp = wuk; p.wuvp = wuv;

  mega_kernel<<<132, NTHREADS, SMEM_BYTES>>>(p);
}
```

```cpp
#include <cuda_runtime.h>
#include <cuda.h>
#include <cuda_bf16.h>
#include <stdint.h>

namespace {

constexpr int SEQ = 2048, DM = 1024, DC = 512, NH = 32, HD = 128;
constexpr int GR = 16384;
constexpr int NGR = 14;
constexpr int SM_BAR = NGR * GR;
constexpr int SM_GATE = SM_BAR + 512;
constexpr int SM_UST = SM_GATE + 512;
constexpr int SMEM_BYTES = SM_UST + 2048;
constexpr int NTHREADS = 384;
constexpr float SM_LIMIT = 1.0995116e12f;
constexpr float SM_LOW = 9.094947e-13f;
constexpr int CNS = 106;
constexpr int CN_SPARE = CNS, NTICK = 256 - 2 * CN_SPARE;
constexpr int XK = 57, YK = 62;
constexpr int STR = 61;
constexpr int P3G = 6, P3X = 12, P3Y = 10;
constexpr int NMAIN = 128;

constexpr int B_FULL = 0, B_FREE = 14, B_SLOT = 16, B_DONE = 17, B_EMPTY = 18, B_EV = 32, B_TICK = 36;
constexpr int V_SLOT = 37, V_TICK = 38;

__device__ __align__(1024) uint8_t g_kv[2 * 16 * 16 * 32768];
__device__ __align__(1024) uint8_t g_cimg[16 * NH * 32768];
__device__ __align__(1024) float g_gate[SEQ];
constexpr int WZ = 256, WPL = WZ + 4096, WBYTES = 2 * WPL + 32, WSTRIDE = 2 * WPL + 128;
__device__ __align__(1024) uint8_t g_w[DM * WSTRIDE];
__device__ __align__(32) unsigned g_flags[96 * 8];
constexpr int F_KV = 0, F_CTX = 16, F_U = 48, F_AD = 56, F_Y = 64, F_GATE = 72, F_EXIT = 73, F_TICK = 74;
constexpr int NSLOT = 66;
#define FLAG(i) (&g_flags[(i) * 8])
#define CLAIMP(i) (p.flags + (i) * 8 + 1)

constexpr int QFLUSH = 3;
constexpr int PSL = 200;
constexpr int US0 = 500;
constexpr int EROT = 6;
constexpr int RST = 2;
constexpr int UP0 = 4;
constexpr int UP1 = 11;
constexpr int X_DELAY = 1100;
constexpr int X_D2 = 500;
constexpr int ROT = 8;
#define KV_ROW(idx, t) (8 * (t) + 2 * ((idx) & 3))
#define KV_HEAD(idx, t) ((idx) >> 2)

__device__ __forceinline__ uint32_t smem_u32(const void* p) { return (uint32_t)__cvta_generic_to_shared(p); }
__device__ __forceinline__ void mbar_init(uint32_t bar, int cnt) { asm volatile("mbarrier.init.shared::cta.b64 [%0], %1;" ::"r"(bar), "r"(cnt) : "memory"); }
__device__ __forceinline__ void mbar_expect_tx(uint32_t bar, uint32_t bytes) { asm volatile("mbarrier.arrive.expect_tx.shared::cta.b64 _, [%0], %1;" ::"r"(bar), "r"(bytes) : "memory"); }
__device__ __forceinline__ void mbar_arrive(uint32_t bar) { asm volatile("mbarrier.arrive.shared::cta.b64 _, [%0];" ::"r"(bar) : "memory"); }
__device__ __forceinline__ void mbar_arrive_cluster(uint32_t bar, uint32_t cta) {
  asm volatile("{\n.reg .b32 r;\nmapa.shared::cluster.u32 r, %0, %1;\nmbarrier.arrive.shared::cluster.b64 _, [r];\n}\n" ::"r"(bar), "r"(cta) : "memory");
}
__device__ __forceinline__ void send_both(uint32_t bar, uint32_t off, uint32_t v) {
#pragma unroll
  for (int r = 0; r < 2; r++)
    asm volatile("{\n.reg .b32 a, b;\nmapa.shared::cluster.u32 a, %0, %1;\nadd.u32 b, a, %3;\nst.async.shared::cluster.mbarrier::complete_tx::bytes.u32 [b], %2, [a];\n}\n"
                 ::"r"(bar), "r"(r), "r"(v), "r"(off) : "memory");
}
__device__ __forceinline__ bool mbar_try(uint32_t bar, uint32_t parity) {
  uint32_t ok;
  asm volatile("{\n.reg .pred p;\nmbarrier.try_wait.parity.shared::cta.b64 p, [%1], %2, 20000;\nselp.u32 %0, 1, 0, p;\n}\n" : "=r"(ok) : "r"(bar), "r"(parity) : "memory");
  return ok;
}
__device__ __forceinline__ bool mbar_test(uint32_t bar, uint32_t parity) {
  uint32_t ok;
  asm volatile("{\n.reg .pred p;\nmbarrier.test_wait.parity.shared::cta.b64 p, [%1], %2;\nselp.u32 %0, 1, 0, p;\n}\n" : "=r"(ok) : "r"(bar), "r"(parity) : "memory");
  return ok;
}
__device__ __forceinline__ void mbar_wait(uint32_t bar, uint32_t parity) {
  asm volatile("{\n.reg .pred p;\nWAIT_LOOP:\nbar.warp.sync -1;\nmbarrier.try_wait.parity.shared::cta.b64 p, [%0], %1;\n@!p bra WAIT_LOOP;\n}\n" ::"r"(bar), "r"(parity) : "memory");
}
__device__ __forceinline__ void mbar_wait1(uint32_t bar, uint32_t parity) {
  asm volatile("{\n.reg .pred p;\nWAIT_LOOP:\nbar.warp.sync -1;\nmbarrier.try_wait.parity.shared::cta.b64 p, [%0], %1, 4000;\n@!p bra WAIT_LOOP;\n}\n" ::"r"(bar), "r"(parity) : "memory");
}
constexpr uint64_t EV_NORMAL = 0x1000000000000000ull, EV_FIRST = 0x12F0000000000000ull;
__device__ __forceinline__ uint32_t ldg_stream(const uint32_t* p) {
  uint32_t r; asm volatile("ld.global.nc.L1::no_allocate.L2::cache_hint.b32 %0, [%1], %2;" : "=r"(r) : "l"(p), "l"(EV_FIRST)); return r;
}
#define TMA_LD "cp.async.bulk.tensor."
#define TMA_MB ".shared::cluster.global.mbarrier::complete_tx::bytes"
__device__ __forceinline__ void tma2d(uint32_t dst, const CUtensorMap* tm, int c0, int c1, uint32_t bar) {
  asm volatile(TMA_LD "2d" TMA_MB " [%0], [%1, {%3, %4}], [%2];" ::"r"(dst), "l"(tm), "r"(bar), "r"(c0), "r"(c1) : "memory");
}
template <bool ONCE = false> __device__ __forceinline__ void tma2d_mc(uint32_t dst, const CUtensorMap* tm, int c0, int c1, uint32_t bar) {
  if (ONCE) asm volatile(TMA_LD "2d" TMA_MB ".multicast::cluster.L2::cache_hint [%0], [%1, {%3, %4}], [%2], %5, %6;"
                         ::"r"(dst), "l"(tm), "r"(bar), "r"(c0), "r"(c1), "h"((uint16_t)3), "l"(EV_FIRST) : "memory");
  else asm volatile(TMA_LD "2d" TMA_MB ".multicast::cluster [%0], [%1, {%3, %4}], [%2], %5;"
                    ::"r"(dst), "l"(tm), "r"(bar), "r"(c0), "r"(c1), "h"((uint16_t)3) : "memory");
}
__device__ __forceinline__ void tma2d_p(uint32_t dst, const CUtensorMap* tm, int c0, int c1, uint32_t bar, bool once) {
  asm volatile(TMA_LD "2d" TMA_MB ".L2::cache_hint [%0], [%1, {%3, %4}], [%2], %5;" ::"r"(dst), "l"(tm), "r"(bar), "r"(c0), "r"(c1), "l"(once ? EV_FIRST : EV_NORMAL) : "memory");
}
__device__ __forceinline__ void tma3d_mc_p(uint32_t dst, const CUtensorMap* tm, int c0, int c1, int c2, uint32_t bar, bool once) {
  asm volatile(TMA_LD "3d" TMA_MB ".multicast::cluster.L2::cache_hint [%0], [%1, {%3, %4, %5}], [%2], %6, %7;"
               ::"r"(dst), "l"(tm), "r"(bar), "r"(c0), "r"(c1), "r"(c2), "h"((uint16_t)3), "l"(once ? EV_FIRST : EV_NORMAL) : "memory");
}
template <bool ONCE = false> __device__ __forceinline__ void tma3d(uint32_t dst, const CUtensorMap* tm, int c0, int c1, int c2, uint32_t bar) {
  if (ONCE) asm volatile(TMA_LD "3d" TMA_MB ".L2::cache_hint [%0], [%1, {%3, %4, %5}], [%2], %6;" ::"r"(dst), "l"(tm), "r"(bar), "r"(c0), "r"(c1), "r"(c2), "l"(EV_FIRST) : "memory");
  else
  asm volatile(TMA_LD "3d" TMA_MB " [%0], [%1, {%3, %4, %5}], [%2];" ::"r"(dst), "l"(tm), "r"(bar), "r"(c0), "r"(c1), "r"(c2) : "memory");
}
__device__ __forceinline__ void tma3d_mc(uint32_t dst, const CUtensorMap* tm, int c0, int c1, int c2, uint32_t bar) {
  asm volatile(TMA_LD "3d" TMA_MB ".multicast::cluster [%0], [%1, {%3, %4, %5}], [%2], %6;"
               ::"r"(dst), "l"(tm), "r"(bar), "r"(c0), "r"(c1), "r"(c2), "h"((uint16_t)3) : "memory");
}
template <bool ONCE = false> __device__ __forceinline__ void bulk_g2s(uint32_t dst, const void* src, uint32_t bytes, uint32_t bar) {
  if (ONCE) asm volatile("cp.async.bulk" TMA_MB ".L2::cache_hint [%0], [%1], %2, [%3], %4;" ::"r"(dst), "l"(src), "r"(bytes), "r"(bar), "l"(EV_FIRST) : "memory");
  else asm volatile("cp.async.bulk" TMA_MB " [%0], [%1], %2, [%3];" ::"r"(dst), "l"(src), "r"(bytes), "r"(bar) : "memory");
}
__device__ __forceinline__ void tma2d_store(const CUtensorMap* tm, uint32_t src, int c0, int c1) {
  asm volatile("cp.async.bulk.tensor.2d.global.shared::cta.bulk_group [%0, {%2, %3}], [%1];" ::"l"(tm), "r"(src), "r"(c0), "r"(c1) : "memory");
}
__device__ __forceinline__ void prefetch_tm(const CUtensorMap* tm) { asm volatile("prefetch.tensormap [%0];" ::"l"(tm) : "memory"); }
__device__ __forceinline__ void wg_fence() { asm volatile("wgmma.fence.sync.aligned;" ::: "memory"); }
__device__ __forceinline__ void wg_commit() { asm volatile("wgmma.commit_group.sync.aligned;" ::: "memory"); }
template <int N> __device__ __forceinline__ void wg_wait() { asm volatile("wgmma.wait_group.sync.aligned %0;" ::"n"(N) : "memory"); }
__device__ __forceinline__ void bar_sync(int id, int n) { asm volatile("bar.sync %0, %1;" ::"r"(id), "r"(n) : "memory"); }
__device__ __forceinline__ void bar_arrive(int id, int n) { asm volatile("bar.arrive %0, %1;" ::"r"(id), "r"(n) : "memory"); }
__device__ __forceinline__ void fence_async_smem() { asm volatile("fence.proxy.async.shared::cta;" ::: "memory"); }
__device__ __forceinline__ void fence_async_all() { asm volatile("fence.proxy.async.global;" ::: "memory"); }
__device__ __forceinline__ uint32_t pack_bf16(float lo, float hi) { uint32_t r; asm("cvt.rn.bf16x2.f32 %0, %1, %2;" : "=r"(r) : "f"(hi), "f"(lo)); return r; }
__device__ __forceinline__ float ex2(float x) { float r; asm("ex2.approx.ftz.f32 %0, %1;" : "=f"(r) : "f"(x)); return r; }
__device__ __forceinline__ float rcp(float x) { float r; asm("rcp.approx.ftz.f32 %0, %1;" : "=f"(r) : "f"(x)); return r; }
__device__ __forceinline__ void flag_wait(const unsigned* f, unsigned target) {
  unsigned v;
  do { asm volatile("ld.acquire.gpu.global.u32 %0, [%1];" : "=r"(v) : "l"(f) : "memory"); } while (__any_sync(0xffffffffu, v < target));
}
__device__ __forceinline__ bool elect() {
  uint32_t r;
  asm volatile("{\n.reg .pred p;\nelect.sync _|p, -1;\nselp.u32 %0, 1, 0, p;\n}\n" : "=r"(r));
  return r;
}
__device__ __forceinline__ void fence_release() { asm volatile("fence.release.gpu;" ::: "memory"); }
__device__ __forceinline__ void flag_add(unsigned* f) { asm volatile("red.relaxed.gpu.global.inc.u32 [%0], 0x7fffffff;" ::"l"(f) : "memory"); }
__device__ __forceinline__ void cluster_arrive() { asm volatile("barrier.cluster.arrive.relaxed.aligned;" ::: "memory"); }
__device__ __forceinline__ void cluster_wait() { asm volatile("barrier.cluster.wait.aligned;" ::: "memory"); }
__device__ __forceinline__ uint32_t hmul2(uint32_t a, uint32_t b) { uint32_t r; asm("mul.rn.bf16x2 %0, %1, %2;" : "=r"(r) : "r"(a), "r"(b)); return r; }
__device__ __forceinline__ uint32_t hadd2(uint32_t a, uint32_t b) { uint32_t r; asm("add.rn.bf16x2 %0, %1, %2;" : "=r"(r) : "r"(a), "r"(b)); return r; }
__device__ __forceinline__ uint32_t hfma2(uint32_t a, uint32_t b, uint32_t c) { uint32_t r; asm("fma.rn.bf16x2 %0, %1, %2, %3;" : "=r"(r) : "r"(a), "r"(b), "r"(c)); return r; }
__device__ __forceinline__ uint32_t lds32(uint32_t a) { uint32_t r; asm volatile("ld.shared.b32 %0, [%1];" : "=r"(r) : "r"(a) : "memory"); return r; }
__device__ __forceinline__ uint4 lds128(uint32_t a) { uint4 r; asm volatile("ld.shared.v4.b32 {%0,%1,%2,%3}, [%4];" : "=r"(r.x), "=r"(r.y), "=r"(r.z), "=r"(r.w) : "r"(a) : "memory"); return r; }
__device__ __forceinline__ uint32_t desc_k(uint32_t addr) { return ((addr & 0x3FFFF) >> 4) | (1u << 16); }
template <int LBO> __device__ __forceinline__ uint32_t desc_mn(uint32_t addr) { return ((addr & 0x3FFFF) >> 4) | ((uint32_t)(LBO >> 4) << 16); }
#define DHI "0x40000040"

#define R8(d, o) "+f"(d[o]), "+f"(d[o + 1]), "+f"(d[o + 2]), "+f"(d[o + 3]), "+f"(d[o + 4]), "+f"(d[o + 5]), "+f"(d[o + 6]), "+f"(d[o + 7])
#define R32(d, o) R8(d, o), R8(d, o + 8), R8(d, o + 16), R8(d, o + 24)
#define R64(d, o) R32(d, o), R32(d, o + 32)
#define L64 "%0,%1,%2,%3,%4,%5,%6,%7,%8,%9,%10,%11,%12,%13,%14,%15,%16,%17,%18,%19,%20,%21,%22,%23,%24,%25,%26,%27,%28,%29,%30,%31," \
            "%32,%33,%34,%35,%36,%37,%38,%39,%40,%41,%42,%43,%44,%45,%46,%47,%48,%49,%50,%51,%52,%53,%54,%55,%56,%57,%58,%59,%60,%61,%62,%63"
#define L128 L64 ",%64,%65,%66,%67,%68,%69,%70,%71,%72,%73,%74,%75,%76,%77,%78,%79,%80,%81,%82,%83,%84,%85,%86,%87,%88,%89,%90,%91,%92,%93,%94,%95," \
            "%96,%97,%98,%99,%100,%101,%102,%103,%104,%105,%106,%107,%108,%109,%110,%111,%112,%113,%114,%115,%116,%117,%118,%119,%120,%121,%122,%123,%124,%125,%126,%127"

template <int TB> __device__ __forceinline__ void mma_ss_n128(float (&d)[64], uint32_t da, uint32_t db) {
  asm volatile("{\n.reg .b64 da, db;\nmov.b64 da, {%64, " DHI "};\nmov.b64 db, {%65, " DHI "};\n"
               "wgmma.mma_async.sync.aligned.m64n128k16.f32.bf16.bf16 {" L64 "}, da, db, 1, 1, 1, 0, %66;\n}\n"
               : R64(d, 0) : "r"(da), "r"(db), "n"(TB));
}
template <int TB> __device__ __forceinline__ void mma_rs_n128(float (&d)[64], uint32_t a0, uint32_t a1, uint32_t a2, uint32_t a3, uint32_t db, int sd) {
  asm volatile("{\n.reg .pred p;\n.reg .b64 db;\nsetp.ne.b32 p, %69, 0;\nmov.b64 db, {%68, " DHI "};\n"
               "wgmma.mma_async.sync.aligned.m64n128k16.f32.bf16.bf16 {" L64 "}, {%64,%65,%66,%67}, db, p, 1, 1, %70;\n}\n"
               : R64(d, 0) : "r"(a0), "r"(a1), "r"(a2), "r"(a3), "r"(db), "r"(sd), "n"(TB));
}
template <int TB> __device__ __forceinline__ void mma_ss_n256(float (&d)[128], uint32_t da, uint32_t db) {
  asm volatile("{\n.reg .b64 da, db;\nmov.b64 da, {%128, " DHI "};\nmov.b64 db, {%129, " DHI "};\n"
               "wgmma.mma_async.sync.aligned.m64n256k16.f32.bf16.bf16 {" L128 "}, da, db, 1, 1, 1, 0, %130;\n}\n"
               : R64(d, 0), R64(d, 64) : "r"(da), "r"(db), "n"(TB));
}
#define W8(d, o) "=f"(d[o]), "=f"(d[o + 1]), "=f"(d[o + 2]), "=f"(d[o + 3]), "=f"(d[o + 4]), "=f"(d[o + 5]), "=f"(d[o + 6]), "=f"(d[o + 7])
#define W32(d, o) W8(d, o), W8(d, o + 8), W8(d, o + 16), W8(d, o + 24)
#define W64(d, o) W32(d, o), W32(d, o + 32)
template <int TB> __device__ __forceinline__ void mma_ss_n128_init(float (&d)[64], uint32_t da, uint32_t db) {
  asm volatile("{\n.reg .b64 da, db;\nmov.b64 da, {%64, " DHI "};\nmov.b64 db, {%65, " DHI "};\n"
               "wgmma.mma_async.sync.aligned.m64n128k16.f32.bf16.bf16 {" L64 "}, da, db, 0, 1, 1, 0, %66;\n}\n"
               : W64(d, 0) : "r"(da), "r"(db), "n"(TB));
}
template <int TB> __device__ __forceinline__ void mma_rs_n128_init(float (&d)[64], uint32_t a0, uint32_t a1, uint32_t a2, uint32_t a3, uint32_t db) {
  asm volatile("{\n.reg .b64 db;\nmov.b64 db, {%68, " DHI "};\n"
               "wgmma.mma_async.sync.aligned.m64n128k16.f32.bf16.bf16 {" L64 "}, {%64,%65,%66,%67}, db, 0, 1, 1, %69;\n}\n"
               : W64(d, 0) : "r"(a0), "r"(a1), "r"(a2), "r"(a3), "r"(db), "n"(TB));
}
template <int TB> __device__ __forceinline__ void mma_ss_n256_init(float (&d)[128], uint32_t da, uint32_t db) {
  asm volatile("{\n.reg .b64 da, db;\nmov.b64 da, {%128, " DHI "};\nmov.b64 db, {%129, " DHI "};\n"
               "wgmma.mma_async.sync.aligned.m64n256k16.f32.bf16.bf16 {" L128 "}, da, db, 0, 1, 1, 0, %130;\n}\n"
               : W64(d, 0), W64(d, 64) : "r"(da), "r"(db), "n"(TB));
}
#define L32 "%0,%1,%2,%3,%4,%5,%6,%7,%8,%9,%10,%11,%12,%13,%14,%15,%16,%17,%18,%19,%20,%21,%22,%23,%24,%25,%26,%27,%28,%29,%30,%31"
template <bool INIT> __device__ __forceinline__ void mma_rs_n64(float (&d)[32], uint32_t a0, uint32_t a1, uint32_t a2, uint32_t a3, uint32_t db) {
  if (INIT) asm volatile("{\n.reg .b64 db;\nmov.b64 db, {%36, " DHI "};\n"
               "wgmma.mma_async.sync.aligned.m64n64k16.f32.bf16.bf16 {" L32 "}, {%32,%33,%34,%35}, db, 0, 1, 1, 0;\n}\n"
               : W32(d, 0) : "r"(a0), "r"(a1), "r"(a2), "r"(a3), "r"(db));
  else asm volatile("{\n.reg .b64 db;\nmov.b64 db, {%36, " DHI "};\n"
               "wgmma.mma_async.sync.aligned.m64n64k16.f32.bf16.bf16 {" L32 "}, {%32,%33,%34,%35}, db, 1, 1, 1, 0;\n}\n"
               : R32(d, 0) : "r"(a0), "r"(a1), "r"(a2), "r"(a3), "r"(db));
}
#define L16 "%0,%1,%2,%3,%4,%5,%6,%7,%8,%9,%10,%11,%12,%13,%14,%15"
template <int O, bool INIT> __device__ __forceinline__ void mma_rs_n32(float (&d)[128], uint32_t a0, uint32_t a1, uint32_t a2, uint32_t a3, uint32_t db) {
  if (INIT) asm volatile("{\n.reg .b64 db;\nmov.b64 db, {%20, 0x00000008};\n"
               "wgmma.mma_async.sync.aligned.m64n32k16.f32.bf16.bf16 {" L16 "}, {%16,%17,%18,%19}, db, 0, 1, 1, 0;\n}\n"
               : W8(d, O), W8(d, O + 8) : "r"(a0), "r"(a1), "r"(a2), "r"(a3), "r"(db));
  else asm volatile("{\n.reg .b64 db;\nmov.b64 db, {%20, 0x00000008};\n"
               "wgmma.mma_async.sync.aligned.m64n32k16.f32.bf16.bf16 {" L16 "}, {%16,%17,%18,%19}, db, 1, 1, 1, 0;\n}\n"
               : R8(d, O), R8(d, O + 8) : "r"(a0), "r"(a1), "r"(a2), "r"(a3), "r"(db));
}
template <int S, int J> __device__ __forceinline__ void conv_step(float (&d)[128], const uint32_t (&a)[64], uint32_t db) {
  if constexpr (J >= 0 && J >= (S >> 1)) {
    mma_rs_n32<16 * J, S == 0>(d, a[4 * S], a[4 * S + 1], a[4 * S + 2], a[4 * S + 3], db + (uint32_t)((2 * J - S) * 16));
    conv_step<S, J - 1>(d, a, db);
  }
}
__device__ __forceinline__ void mma_ss_n8(float (&d)[4], uint32_t da, uint32_t db) {
  asm volatile("{\n.reg .b64 da, db;\nmov.b64 da, {%4, " DHI "};\nmov.b64 db, {%5, 0x00000008};\n"
               "wgmma.mma_async.sync.aligned.m64n8k16.f32.bf16.bf16 {%0,%1,%2,%3}, da, db, 1, 1, 1, 0, 0;\n}\n"
               : "+f"(d[0]), "+f"(d[1]), "+f"(d[2]), "+f"(d[3]) : "r"(da), "r"(db));
}
template <int N> __device__ __forceinline__ void reg_fence(float (&d)[N]) {
#pragma unroll
  for (int i = 0; i < N; i++) asm volatile("" : "+f"(d[i])::"memory");
}
template <int N> __device__ __forceinline__ void reg_fence(uint32_t (&d)[N]) {
#pragma unroll
  for (int i = 0; i < N; i++) asm volatile("" : "+r"(d[i])::"memory");
}

struct __align__(64) Params {
  unsigned* flags;
  int zero;
  uint8_t pref[128];
  const __nv_bfloat16 *gate_w, *ak, *av, *shk, *ssk, *ssd, *wukp, *wuvp;
  CUtensorMap x, c, wq, wuk, wuv, wo, x3, y3, out, w;
};

template <int O, int N, int M> __device__ __forceinline__ void pack_frag(const float (&acc)[N], uint32_t (&pk)[M]) {
#pragma unroll
  for (int i = 0; i < 32; i++) pk[i] = pack_bf16(acc[O + 2 * i], acc[O + 2 * i + 1]);
}
template <int J0 = 0, int J1 = 8, int M> __device__ __forceinline__ void stsm_frag(const uint32_t (&pk)[M], uint32_t a) {
#pragma unroll
  for (int jj = J0; jj < J1; jj++)
    asm volatile("stmatrix.sync.aligned.m8n8.x4.shared.b16 [%0], {%1,%2,%3,%4};" ::"r"((a ^ ((jj & 3) << 5)) + (jj >> 2) * 16384),
                 "r"(pk[4 * jj]), "r"(pk[4 * jj + 1]), "r"(pk[4 * jj + 2]), "r"(pk[4 * jj + 3]) : "memory");
}

template <int N> __device__ __forceinline__ void store_scaled(const float (&acc)[N], float s0, float s1, uint32_t a, uint32_t never_zero) {
  float t[8];
#pragma unroll
  for (int jj = 0; jj < 8; jj++) {
    float v = acc[8 * jj] * s0;
    if (jj >= RST) {
      v = t[jj - RST];
      asm("{\n.reg .pred p;\nsetp.ne.u32 p, %3, 0;\n@p mul.f32 %0, %1, %2;\n}\n" : "+f"(v) : "f"(acc[8 * jj]), "f"(s0), "r"(never_zero));
    }
    const uint32_t q = pack_bf16(v, acc[8 * jj + 1] * s0);
    t[jj] = __uint_as_float(q);
    asm volatile("stmatrix.sync.aligned.m8n8.x4.shared.b16 [%0], {%1,%2,%3,%4};" ::"r"((a ^ ((jj & 3) << 5)) + (jj >> 2) * 16384), "r"(q),
                 "r"(pack_bf16(acc[8 * jj + 2] * s1, acc[8 * jj + 3] * s1)), "r"(pack_bf16(acc[8 * jj + 4] * s0, acc[8 * jj + 5] * s0)),
                 "r"(pack_bf16(acc[8 * jj + 6] * s1, acc[8 * jj + 7] * s1)) : "memory");
  }
}

struct Cons {
  uint32_t sb;
  uint32_t pf;
  int wg, tid;
  __device__ __forceinline__ void wait_full(int g) { mbar_wait(sb + SM_BAR + (B_FULL + g) * 8, (pf >> g) & 1); pf ^= 1u << g; }
  uint32_t relb;
  __device__ __forceinline__ void release(int g, int n) {
    if (tid < 2 * n) asm volatile("mbarrier.arrive.shared::cluster.b64 _, [%0];" ::"r"(relb + g * 8) : "memory");
  }
  __device__ __forceinline__ void turn_begin() { bar_sync(1 + wg, 256); }
  __device__ __forceinline__ void turn_end() { bar_arrive(2 - wg, 256); }
  __device__ __forceinline__ void staged() { __syncwarp(); if ((tid & 31) == 0) mbar_arrive(sb + SM_BAR + (B_EV + wg) * 8); }
  int zero;
  uint32_t pfree;
  __device__ __forceinline__ void wait_stage_free() { mbar_wait(sb + SM_BAR + (B_FREE + wg) * 8, pfree); pfree ^= 1; }
  __device__ __forceinline__ bool try_full(int g) { return mbar_test(sb + SM_BAR + (B_FULL + g) * 8, (pf >> g) & 1); }
};

constexpr float SM_C = 0.08838834764831845f * 1.4426950408889634f;
struct SoftState { float m0, m1, l0, l1; int shifted; };
__device__ __forceinline__ void ex2_rot(float& t, float s, uint32_t never_zero) {
  asm("{\n.reg .pred p;\nsetp.ne.u32 p, %2, 0;\n@p ex2.approx.ftz.f32 %0, %1;\n}\n" : "+f"(t) : "f"(s), "r"(never_zero));
}
__device__ __forceinline__ void pin(float a, uint32_t never_zero) {
  asm volatile("{\n.reg .pred p;\nsetp.eq.u32 p, %1, 0;\n@p st.shared.f32 [%1], %0;\n}\n" ::"f"(a), "r"(never_zero) : "memory");
}
template <int O, int N> __device__ __forceinline__ void reg_fence_part(uint32_t (&d)[32]) {
#pragma unroll
  for (int i = O; i < O + N; i++) asm volatile("" : "+r"(d[i])::"memory");
}
template <int Q, int W, int N> __device__ __forceinline__ void exp_quarter(const float (&S)[N], uint32_t (&P)[32], float (&t)[ROT], float& s0, float& s1, uint32_t nz) {
#pragma unroll
  for (int i = 8 * Q; i < 8 * Q + 8; i++) {
    float& a = t[(2 * i) % ROT];
    float& b = t[(2 * i + 1) % ROT];
    if (2 * i < ROT) { a = ex2(S[2 * i]); b = ex2(S[2 * i + 1]); }
    else { ex2_rot(a, S[2 * i], nz); ex2_rot(b, S[2 * i + 1], nz); }
    if (i < 2) { if (i) s1 = a + b; else s0 = a + b; }
    else if (i & 1) { s1 += a; s1 += b; } else { s0 += a; s0 += b; }
    if (i == 8 * Q) { pin(Q ? s1 : s0, nz); wg_wait<W>(); reg_fence_part<8 * Q, 8>(P); }
    P[i] = pack_bf16(a, b);
  }
}
template <int N> __device__ __forceinline__ void shift_scores(float (&S)[N], float d0, float d1) {
#pragma unroll
  for (int i = 0; i < N; i++) S[i] -= (i & 2) ? d1 : d0;
}
__device__ __forceinline__ bool soft_high(float s0, float s1, float lim = SM_LIMIT) { return s0 > lim || s1 > lim; }
__device__ __forceinline__ bool soft_unsafe(float s0, float s1, bool first) {
  uint32_t b0 = __ballot_sync(0xffffffffu, s0 >= SM_LOW), b1 = __ballot_sync(0xffffffffu, s1 >= SM_LOW);
  b0 |= b0 >> 1; b0 |= b0 >> 2; b1 |= b1 >> 1; b1 |= b1 >> 2;
  return __any_sync(0xffffffffu, soft_high(s0, s1)) || (first && (b0 & b1 & 0x11111111u) != 0x11111111u);
}
template <int N> __device__ __forceinline__ void soft_fix(const float (&S)[N], float (&O)[64], SoftState& z, bool first, float& d0, float& d1) {
  d0 = d1 = first ? -INFINITY : 0.f;
#pragma unroll
  for (int j = 0; j < N / 4; j++) { d0 = fmaxf(d0, fmaxf(S[4 * j], S[4 * j + 1])); d1 = fmaxf(d1, fmaxf(S[4 * j + 2], S[4 * j + 3])); }
  d0 = fmaxf(d0, __shfl_xor_sync(0xffffffffu, d0, 1)); d1 = fmaxf(d1, __shfl_xor_sync(0xffffffffu, d1, 1));
  d0 = fmaxf(d0, __shfl_xor_sync(0xffffffffu, d0, 2)); d1 = fmaxf(d1, __shfl_xor_sync(0xffffffffu, d1, 2));
  const float sc0 = ex2(-fmaxf(d0, 0.f)), sc1 = ex2(-fmaxf(d1, 0.f));
  z.m0 += d0; z.m1 += d1; z.l0 *= sc0; z.l1 *= sc1; z.shifted = 1;
#pragma unroll
  for (int j = 0; j < 16; j++) { O[4 * j] *= sc0; O[4 * j + 1] *= sc0; O[4 * j + 2] *= sc1; O[4 * j + 3] *= sc1; }
}
template <int N> __device__ __forceinline__ void mask_diag(float (&S)[N], float nd) {
  asm volatile("" : "+f"(nd));
#pragma unroll
  for (int i = 0; i < 32; i++) {
    const float beyond = __saturatef(nd + (float)(8 * (i >> 2) + (i & 1) - 4 * (i & 2)));
    S[N - 32 + i] = fmaf(beyond, -3.0e38f, S[N - 32 + i]);
  }
}
__device__ __forceinline__ float quad_sum(float v) {
  v += __shfl_xor_sync(0xffffffffu, v, 1);
  v += __shfl_xor_sync(0xffffffffu, v, 2);
  return v;
}
__device__ __forceinline__ void issue_qk(float (&S)[64], const uint32_t (&Q)[32], uint32_t dk) {
  mma_rs_n128_init<0>(S, Q[0], Q[1], Q[2], Q[3], dk);
#pragma unroll
  for (int s = 1; s < 8; s++) mma_rs_n128<0>(S, Q[4 * s], Q[4 * s + 1], Q[4 * s + 2], Q[4 * s + 3], dk + (s >> 2) * 1024 + (s & 3) * 2, 1);
}
__device__ __forceinline__ void issue_qk(float (&S)[32], const uint32_t (&Q)[32], uint32_t dk) {
  mma_rs_n64<true>(S, Q[0], Q[1], Q[2], Q[3], dk);
#pragma unroll
  for (int s = 1; s < 8; s++) mma_rs_n64<false>(S, Q[4 * s], Q[4 * s + 1], Q[4 * s + 2], Q[4 * s + 3], dk + (s >> 2) * 1024 + (s & 3) * 2);
}
__device__ __forceinline__ void load_q(uint32_t (&Q)[32], uint32_t a) {
  __syncwarp();
#pragma unroll
  for (int jj = 0; jj < 8; jj++)
    asm volatile("ldmatrix.sync.aligned.m8n8.x4.shared.b16 {%0,%1,%2,%3}, [%4];" : "=r"(Q[4 * jj]), "=r"(Q[4 * jj + 1]), "=r"(Q[4 * jj + 2]), "=r"(Q[4 * jj + 3])
                 : "r"((a ^ ((jj & 3) << 5)) + (jj >> 2) * 16384) : "memory");
}
template <int H> __device__ __forceinline__ void issue_pv(float (&O)[64], const uint32_t (&P)[32], uint32_t dv, int acc, bool on) {
  if (on) {
#pragma unroll
    for (int s = 4 * H; s < 4 * H + 4; s++) {
      mma_rs_n128<1>(O, P[4 * s], P[4 * s + 1], P[4 * s + 2], P[4 * s + 3], dv + s * 128, s != 0 ? 1 : acc);
      if (s & 1) wg_commit();
    }
  } else { wg_commit(); wg_commit(); }
}
constexpr uint32_t DG = GR >> 4;
__device__ __forceinline__ void stage_q2(Cons& c, const float (&O)[64], uint32_t (&P)[32], uint32_t stg) {
  wg_commit(); wg_commit(); wg_commit(); wg_commit();
  c.turn_end();
  pack_frag<0>(O, P);
  stsm_frag(P, stg);
}
__device__ __forceinline__ void attn_half(Cons& c, float (&O)[64], uint32_t (&P)[32], uint32_t (&Q)[32], bool nextq, uint32_t stg, SoftState& z, uint32_t dkk, uint32_t dv0, float dmask, int last) {
  float S[32];
  c.turn_begin();
  wg_fence();
  issue_qk(S, Q, dkk + (last ? 8 : 2) * DG);
  wg_commit();
  issue_pv<0>(O, P, dv0 + 10 * DG, 1, last);
  issue_pv<1>(O, P, dv0 + 10 * DG, 1, last);
  c.turn_end();
  c.wait_full(last ? 12 : 4);
  wg_wait<4>();
  reg_fence(S);
  c.release(last ? 8 : 2, 2);
  reg_fence(Q);
  if (nextq) load_q(Q, stg);
  if (last) bar_sync(6, 256);
  mask_diag(S, dmask);
  float s0, s1, d0 = z.m0, d1 = z.m1;
#pragma unroll 1
  for (int pass = 0;; pass++) {
    if (z.shifted) shift_scores(S, d0, d1);
    float tr[ROT];
    exp_quarter<0, 3>(S, P, tr, s0, s1, c.sb);
    exp_quarter<1, 2>(S, P, tr, s0, s1, c.sb);
    pin(s1, c.sb); wg_wait<0>(); reg_fence_part<16, 16>(P); reg_fence(O);
    if (!soft_unsafe(s0, s1, !last) || pass) break;
    soft_fix(S, O, z, !last, d0, d1);
  }
  z.l0 += s0; z.l1 += s1;
  c.release(10, last ? 2 : 0);
  if (!last) c.wait_full(6);
}

template <int V> struct IC { static constexpr int value = V; };
__device__ __forceinline__ int conv_next(int g, bool spare) { return g >= NGR - 2 ? g - (NGR - 4) : !spare && g == 4 ? 1 : g + 2; }
__device__ __forceinline__ void conv_final(uint32_t rb, uint32_t yb, bool on) {
  const uint4 q0 = lds128(rb), q1 = lds128(rb + 4096), q2 = lds128(rb + 8192), q3 = lds128(rb + 12288);
  auto fin = [&](uint32_t x0, uint32_t x1, uint32_t x2, uint32_t x3) { return hadd2(hadd2(x0, x1), hadd2(x2, x3)); };
  asm volatile("{\n.reg .pred p;\nsetp.ne.b32 p, %5, 0;\n@p st.shared.v4.b32 [%0], {%1,%2,%3,%4};\n}\n" ::"r"(yb), "r"(fin(q0.x, q1.x, q2.x, q3.x)),
               "r"(fin(q0.y, q1.y, q2.y, q3.y)), "r"(fin(q0.z, q1.z, q2.z, q3.z)), "r"(fin(q0.w, q1.w, q2.w, q3.w)), "r"((int)on) : "memory");
}
__device__ __forceinline__ void conv_tasks(Cons& c, const Params& p, int ntask, bool spare, int ch, int chstep, int c5, uint32_t dd, uint32_t dkk, int w, int lane) {
  const uint32_t sb = c.sb;
  int g = 2 + c.wg;
  uint32_t rb = sb + g * GR;
  const uint32_t yb = sb + c.wg * 8192 + c.tid * 16;
  const int gt = 8 * w + (lane >> 2) + (lane & 3);
  uint32_t a[64], hb;
  auto lda = [&](int s) {
    a[4 * s] = lds32(hb + s * 256); a[4 * s + 1] = lds32(hb + s * 256 + 128);
    a[4 * s + 2] = lds32(hb + s * 256 + 16); a[4 * s + 3] = lds32(hb + s * 256 + 144);
  };
  auto first_a = [&]() {
    hb = sb + g * GR + WBYTES - 28 + gt * 4;
    lda(0); lda(15);
  };
  c.wait_full(g);
  first_a();
#pragma unroll 1
  for (int i = 0; i < ntask; i++) {
    const uint32_t base = sb + g * GR;
    lda(1); lda(14);
    a[0] = hadd2(a[0], gt == 7 ? dd : 0u); a[2] = hadd2(a[2], gt == 3 ? dd : 0u);
    float acc[128];
    const uint32_t db = dkk + ((WPL / 16 - 1) << 16) + g * DG + WZ / 16;
    c.turn_begin();
    auto pair = [&](auto kc) {
      constexpr int k = decltype(kc)::value;
      if (k < 7) wg_fence();
      if (k == 6) c.turn_end();
      conv_step<k, 7>(acc, a, db);
      conv_step<15 - k, 7>(acc, a, db);
      if (k < 6) { lda(k + 2); lda(13 - k); }
      if (k == 0) conv_final(rb, yb, i > 0);
      if (k == 1) {
        conv_final(rb + 2048, yb + 2048, i > 0);
        __syncwarp();
        if (lane == 0 && i > 0) mbar_arrive(sb + SM_BAR + (B_EV + c.wg) * 8);
      }
      if (k == 6) dd = __bfloat16_as_ushort(p.ssd[(ch + chstep + (i == 1 ? c5 : 0)) & (DM - 1)]);
    };
    pair(IC<0>()); pair(IC<1>()); pair(IC<2>()); pair(IC<3>()); pair(IC<4>()); pair(IC<5>()); pair(IC<6>()); pair(IC<7>());
    wg_commit();
    g = conv_next(g, spare);
    ch += chstep;
    rb = base + c.tid * 16;
    if (i + 1 < ntask) c.wait_full(g);
    const bool fr = mbar_test(sb + SM_BAR + (B_FREE + c.wg) * 8, c.pfree);
    wg_wait<0>();
    reg_fence(acc);
    reg_fence(a);
    bar_sync(3 + c.wg, 128);
    first_a();
    const int tw = (lane & 3) + w;
    const uint32_t xb = base + w * 4096 + tw * 32 + (lane >> 2) * 4;
    [[maybe_unused]] float t0[EROT + 1];
#pragma unroll
    for (int j = 0; j < 32; j++) {
      uint32_t ad = xb + j * 128;
      float v0 = acc[4 * j], v1 = acc[4 * j + 1];
      if (EROT && j > EROT) {
        v0 = t0[j % (EROT + 1)];
        asm("{\n.reg .pred p;\nsetp.ne.u32 p, %3, 0;\n@p add.f32 %0, %1, %2;\n}\n" : "+f"(v0) : "f"(acc[4 * j]), "f"(acc[j > 0 ? 4 * j - 2 : 0]), "r"(sb));
      } else if (j > 0) v0 += acc[j > 0 ? 4 * j - 2 : 0];
      if (j > 0) v1 += acc[j > 0 ? 4 * j - 1 : 0];
      uint32_t v = pack_bf16(v0, v1);
      t0[j % (EROT + 1)] = __uint_as_float(v);
      if (j == 31 && tw >= 4) { v = 0; ad -= 4096; }
      asm volatile("st.shared.b32 [%0], %1;" ::"r"(ad), "r"(v) : "memory");
    }
    if (!fr) c.wait_stage_free(); else c.pfree ^= 1;
  }
  bar_sync(3 + c.wg, 128);
  conv_final(rb, yb, true);
  conv_final(rb + 2048, yb + 2048, true);
  c.staged();
}

__global__ void __cluster_dims__(2, 1, 1) __launch_bounds__(NTHREADS, 1) mega_kernel(const __grid_constant__ Params p) {
  extern __shared__ __align__(1024) uint8_t smem_raw[];
  const uint32_t sb = smem_u32(smem_raw);
  if (threadIdx.x - 64 < 32) { prefetch_tm(&p.c); prefetch_tm(&p.wuk + (blockIdx.x & 1)); }
  const int wgi = __shfl_sync(0xffffffffu, threadIdx.x >> 7, 0);
  const int warp = __shfl_sync(0xffffffffu, threadIdx.x >> 5, 0);
  const uint32_t rank = blockIdx.x & 1;
  int slot;
  {
    uint32_t smid; asm volatile("mov.u32 %0, %smid;" : "=r"(smid));
    slot = p.pref[((smid >> 1) + (threadIdx.x & (smid >> 16))) & 127];
  }
  if (warp >= 3) {
    if (elect()) {
#pragma unroll
      for (int k = 0; k < 4; k++) mbar_init(sb + SM_BAR + ((warp - 3) * 4 + k) * 8, k == 1 && warp == 7 ? 11 : warp < (k ? 7 : 8) ? 1 : 4);
      if (warp == 7) { mbar_init(sb + SM_BAR + B_TICK * 8, 1); mbar_expect_tx(sb + SM_BAR + B_SLOT * 8, 8); mbar_expect_tx(sb + SM_BAR + B_TICK * 8, 4); }
      asm volatile("fence.mbarrier_init.release.cluster;" ::: "memory");
    }
    __syncwarp();
  }
  cluster_arrive();
  slot = __shfl_sync(0xffffffffu, slot, 0);
  const int pref = slot;
  if (warp < 4) {
    asm volatile("setmaxnreg.dec.sync.aligned.u32 40;");
    if (warp == 1 + 4 * rank) {
      unsigned taken = threadIdx.x == 32;
#pragma unroll 1
      for (int n = 0; n < NSLOT; n++) {
        asm volatile("{\n.reg .pred p;\nsetp.ne.b32 p, %0, 0;\n@p atom.relaxed.gpu.global.exch.b32 %0, [%1], 1;\n}\n" : "+r"(taken) : "l"(CLAIMP(slot)) : "memory");
        if (!__any_sync(0xffffffffu, taken)) break;
        slot = slot == NSLOT - 1 ? 0 : slot + 1;
      }
    }
    cluster_wait();
    if (threadIdx.x == 32) {
      send_both(sb + SM_BAR + B_SLOT * 8, (V_SLOT - B_SLOT) * 8 + rank * 4, slot | pref << 8);
    }
    if (warp == 2) {
#pragma unroll 1
      for (int kk = 0; kk < 4; kk++) {
        const int g0 = 2 + 3 * kk;
        const uint32_t fb = sb + SM_BAR + (B_FULL + g0) * 8;
        if (elect()) {
          mbar_expect_tx(fb, 3 * GR);
          tma2d(sb + g0 * GR, &p.c, kk * 64, (KV_ROW(pref & 7, 0) + rank) * 128, fb);
          tma3d_mc(sb + (g0 + 1 + rank) * GR, rank ? &p.wuv : &p.wuk, 0, kk * 64, ((pref & 56) >> 1) + 2 * KV_HEAD(pref & 7, 0), fb);
        }
        if (kk < 3) {
          uint32_t c0, c1;
          asm volatile("mov.u32 %0, %clock;" : "=r"(c0));
          do asm volatile("mov.u32 %0, %clock;" : "=r"(c1)); while (c1 - c0 < (kk ? X_D2 : X_DELAY));
        }
      }
      prefetch_tm(&p.x); prefetch_tm(&p.wq);
    }
  }
  int grp, idx, lb;
  int cn, cch, cstep;
  bool spare, redo;
  auto get_slot = [&]() {
    mbar_wait(sb + SM_BAR + B_SLOT * 8, 0);
    const uint32_t sv0 = __shfl_sync(0xffffffffu, lds32(sb + SM_BAR + V_SLOT * 8), 0), sv1 = __shfl_sync(0xffffffffu, lds32(sb + SM_BAR + V_SLOT * 8 + 4), 0);
    grp = (sv0 & 255) >> 3; idx = sv0 & 7; lb = (sv0 & 255) * 2 + rank;
    spare = grp == 8; redo = spare || sv0 != sv1;
    cn = CN_SPARE; cch = spare ? lb - NMAIN : 4 * CN_SPARE + 4 * lb; cstep = spare ? 4 : 1;
  };
  auto get_ticket = [&]() {
    mbar_wait(sb + SM_BAR + B_TICK * 8, 0);
    const int tk = __shfl_sync(0xffffffffu, lds32(sb + SM_BAR + V_TICK * 8), 0);
    cn = tk < NTICK ? 5 : 4;
    return 4 * NMAIN - 4 * lb - 4 + 2 * tk + rank;
  };

  if (wgi == 0) {
    asm volatile("setmaxnreg.dec.sync.aligned.u32 40;");
    const int lane = threadIdx.x & 31;
    cluster_arrive();
    get_slot();
    uint32_t pe = 0;
    auto acquire = [&](int g, int n, uint32_t m) {
      int i = g;
#pragma unroll 1
      do mbar_wait1(sb + SM_BAR + (B_EMPTY + i) * 8, (pe >> i) & 1); while (++i < g + n);
      pe ^= m << g;
    };
    if (warp == 3) {
      if (!spare) {
        const int s0 = lb * 16;
#pragma unroll 1
        for (int cg = 0; cg < 16; cg++) {
          if (cg == UP0 || cg == UP1) {
#pragma unroll 1
            for (int n = 0; n < 20 && !__any_sync(0xffffffffu, mbar_try(sb + SM_BAR + B_SLOT * 8, cg == UP0)); n++);
          } else if (cg < UP0) __nanosleep(US0);
          if (cg == UP1 && lane == rank * 32) send_both(sb + SM_BAR + B_TICK * 8, (V_TICK - B_TICK) * 8, atomicInc(FLAG(F_TICK), 0x7fffffffu));
          if (cg >= 5 && cg < 9) {
            unsigned l = lane;
            asm volatile("" : "+r"(l));
            const unsigned o = (idx * 8 + (l >> 2)) * (NH * HD) + (16 + 2 * grp) * HD + (l & 3) * 64;
            asm volatile("prefetch.global.L2 [%0];" ::"l"((rank ? p.wuvp : p.wukp) + (o + (cg - 1) * 64 * (NH * HD))));
          }
          const int ch = cg * 64 + 2 * lane;
          const uint32_t* kp = reinterpret_cast<const uint32_t*>(p.ak + (size_t)s0 * DM + ch);
          const uint32_t* vp = reinterpret_cast<const uint32_t*>(p.av + (size_t)s0 * DM + ch);
          const uint4 sw = __ldg(reinterpret_cast<const uint4*>(p.shk + ch * 4));
          uint32_t k3 = 0, k2 = 0, k1 = 0, k0 = 0, up = 0;
          if (lb > 0) { k3 = ldg_stream(kp - 4 * 512); k2 = ldg_stream(kp - 3 * 512); k1 = ldg_stream(kp - 2 * 512); k0 = ldg_stream(kp - 512); up = ldg_stream(vp - 512); }
          const uint32_t w0 = __byte_perm(sw.x, sw.z, 0x5410), w1 = __byte_perm(sw.x, sw.z, 0x7632);
          const uint32_t w2 = __byte_perm(sw.y, sw.w, 0x5410), w3 = __byte_perm(sw.y, sw.w, 0x7632);
          up = hmul2(hfma2(k0, w0, hfma2(k1, w1, hfma2(k2, w2, hmul2(k3, w3)))), up);
#pragma unroll 1
          for (int hb = 0; hb < 2; hb++) {
            uint32_t kk[8], u[8];
#pragma unroll
            for (int r = 0; r < 8; r++) { kk[r] = ldg_stream(kp + r * 512); u[r] = ldg_stream(vp + r * 512); }
#pragma unroll
            for (int r = 0; r < 8; r++) {
              k3 = k2; k2 = k1; k1 = k0; k0 = kk[r];
              u[r] = hmul2(hfma2(k0, w0, hfma2(k1, w1, hfma2(k2, w2, hmul2(k3, w3)))), u[r]);
            }
            if (lane == 0) asm volatile("cp.async.bulk.wait_group.read 0;" ::: "memory");
            __syncwarp();
            const uint32_t dst = sb + SM_UST + lane * 32 + ((lane & 4) << 2);
#pragma unroll
            for (int cc = 0; cc < 2; cc++) {
              const uint32_t sel = cc ? 0x7632 : 0x5410;
              asm volatile("st.shared.v4.b32 [%0], {%1,%2,%3,%4};" ::"r"(dst + cc * 1024), "r"(__byte_perm(u[6], u[5], sel)), "r"(__byte_perm(u[4], u[3], sel)),
                           "r"(__byte_perm(u[2], u[1], sel)), "r"(__byte_perm(u[0], up, sel)) : "memory");
              asm volatile("st.shared.v4.b32 [%0], {%1,%2,%3,%4};" ::"r"((dst ^ 16) + cc * 1024), "r"(__byte_perm(u[7], u[6], sel)), "r"(__byte_perm(u[5], u[4], sel)),
                           "r"(__byte_perm(u[3], u[2], sel)), "r"(__byte_perm(u[1], u[0], sel)) : "memory");
            }
            fence_async_smem();
            __syncwarp();
            if (lane == 0) {
              asm volatile("cp.async.bulk.tensor.3d.global.shared::cta.bulk_group.L2::cache_hint [%0, {%2, %3, %4}], [%1], %5;\ncp.async.bulk.commit_group;"
                           ::"l"(&p.w), "r"(sb + SM_UST), "r"(WZ / 2 + lb * 16 + (hb ^ 1) * (WPL / 2)), "r"(cg * 32), "r"(0), "l"(cg >= UP0 && cg < UP1 ? EV_FIRST : EV_NORMAL) : "memory");
            }
            up = u[7];
            kp += 8 * 512; vp += 8 * 512;
          }
          if ((cg & (cg + 1)) == 0 && lane == 0) {
            asm volatile("cp.async.bulk.wait_group 0;" ::: "memory");
            fence_release();
            flag_add(FLAG(F_U + 32 - __clz(cg)));
          }
        }
        prefetch_tm(&p.wo); prefetch_tm(&p.x3); prefetch_tm(&p.y3); prefetch_tm(&p.out);
      } else {
#pragma unroll 1
        for (int i = 0, g = 2; i < 32; i++) {
          acquire(g, 2, 3);
          if (elect()) {
            const uint32_t fb = sb + SM_BAR + (B_FULL + g) * 8;
            if (i == 0) { mbar_expect_tx(fb - 8, 2048); bulk_g2s(sb + GR, p.gate_w, 2048, fb - 8); }
            mbar_expect_tx(fb, 2 * GR);
            tma3d(sb + g * GR, &p.x3, 0, (lb - NMAIN) * 512 + (i >> 3) * 128, (i & 7) * 2, fb);
          }
          g = g == NGR - 2 ? 2 : g + 2;
        }
        bar_arrive(5, 64);
      }
      unsigned long long t0, t1;
      asm volatile("mov.u64 %0, %globaltimer;" : "=l"(t0));
      auto check = [&]() {
        asm volatile("mov.u64 %0, %globaltimer;" : "=l"(t1));
        if (t1 - t0 > 2000000000ull) __trap();
      };
      if (!spare) {
        unsigned v;
        do {
          __nanosleep(PSL);
          check();
          asm volatile("ld.acquire.gpu.global.u32 %0, [%1];" : "=r"(v) : "l"(FLAG(lane & 1 ? F_Y + idx : F_GATE)) : "memory");
        } while (__any_sync(0xffffffffu, v < (lane & 1 ? 128 : 32)));
        __syncwarp();
        if (lane == 0) mbar_arrive(sb + SM_BAR + B_SLOT * 8);
      }
      if (lane == 0) {
        while (!mbar_try(sb + SM_BAR + B_DONE * 8, 0)) check();
      }
    } else if (warp != 0) {
      const int w = warp - 1;
      int ne = 12 + (CN_SPARE + 1 - w) / 2, c5 = 0;
      int cg = 2 + w, ch = cch + w * cstep;
#pragma unroll 1
      for (int e = spare ? 12 : 0; e < ne; e++) {
        const int rnd = e >= 6, k = e - 6 * rnd, rt = k == 4 ? idx : 15 - idx;
        uint8_t* dst = k < 4 ? g_kv + (size_t)(((k & 1) * 16 + 2 * grp + KV_HEAD(idx, k >> 1)) * 16 + KV_ROW(idx, k >> 1) + rank) * 32768 + w * 8192
                     : k < 6 ? g_cimg + (size_t)(rt * 32 + 16 * rnd + 2 * grp + rank) * 32768 + (w ^ (k & 1)) * 8192
                             : g_w + (size_t)ch * WSTRIDE + WZ;
        const uint32_t src = sb + w * 8192;
        if (e == 11) { c5 = get_ticket(); ne = 12 + ((cn + 1 - w) >> 1); }
        if (e == 6) flag_wait(FLAG(F_AD + grp), 32);
        mbar_wait1(sb + SM_BAR + (B_EV + w) * 8, e & 1);
        if (lane < 4 && k >= 6 && (!spare || e < ne - 6)) mbar_arrive_cluster(sb + SM_BAR + (B_EMPTY + cg) * 8, lane & 1);
        fence_async_smem();
        if (elect()) {
          const uint32_t cs = e >= 11 ? 4096 : 1024;
#pragma unroll 1
          for (uint32_t i = 0; i < (k >= 6 ? 4096 : 16384); i += cs) {
            const uint32_t o = (i + (i & 8192)) ^ (e == 11 ? 16384 : 0);
            asm volatile("cp.async.bulk.global.shared::cta.bulk_group.L2::cache_hint [%0], [%1], %2, %3;" ::"l"(dst + o), "r"(src + o), "r"(cs),
                         "l"(e == 4 || e == 5 || spare ? EV_FIRST : EV_NORMAL) : "memory");
            asm volatile("cp.async.bulk.commit_group;\ncp.async.bulk.wait_group.read 1;" ::: "memory");
            if (e == 11 && i == 8192) {
              mbar_arrive_cluster(sb + SM_BAR + (B_EMPTY + 1) * 8, 0); mbar_arrive_cluster(sb + SM_BAR + (B_EMPTY + 1) * 8, 1);
            }
          }
          asm volatile("cp.async.bulk.wait_group 0;" ::: "memory");
          mbar_arrive(sb + SM_BAR + (B_FREE + w) * 8);
        }
        __syncwarp();
        if (lane < (e == ne - 1 && !spare ? 2 : 0)) mbar_arrive_cluster(sb + SM_BAR + B_EMPTY * 8, lane);
        if (k >= 3) {
          fence_release();
          const unsigned fl = k == 3 ? F_KV + rnd * 8 + grp : k < 6 ? F_CTX + rt * 2 + rnd : F_Y + ((unsigned)ch >> 7);
          if (lane <= (e == 5)) flag_add(FLAG(lane ? F_AD + grp : fl));
        }
        if (k >= 6) { cg = conv_next(cg, spare); ch += 2 * cstep + (k == 7 ? c5 : 0); }
      }
      if (lane == 0) mbar_arrive(sb + SM_BAR + B_DONE * 8);
    } else {
#pragma unroll 1
      for (int rnd = 0; rnd < (spare ? 0 : 2); rnd++) {
        const int hp = 16 * rnd + 2 * grp, head = hp + rank;
#pragma unroll 1
        for (int kk = rnd || redo ? 0 : 4; kk < 32; kk++) {
          const int g0 = 2 + 3 * (kk & 3);
          acquire(g0, kk < 4 ? 3 : 1, 7);
          if (elect()) {
            const uint32_t fb = sb + SM_BAR + (B_FULL + g0) * 8;
            mbar_expect_tx(fb, 3 * GR);
            if (kk < 16) {
              tma2d_p(sb + g0 * GR, &p.c, (kk & 7) * 64, (KV_ROW(idx, kk >> 3) + rank) * 128, fb, rnd);
              tma3d_mc_p(sb + (g0 + 1 + rank) * GR, rank ? &p.wuv : &p.wuk, 0, (kk & 7) * 64, (hp + KV_HEAD(idx, kk >> 3)) * 2, fb, kk >= 8);
            } else {
              tma2d_mc(sb + (g0 + rank) * GR, &p.x, (kk - 16) * 64, (rank ? 15 - idx : idx) * 128, fb);
              tma3d<true>(sb + (g0 + 2) * GR, &p.wq, 0, (kk - 16) * 64, head * 2, fb);
            }
          }
        }
        flag_wait(FLAG(F_KV + rnd * 8 + grp), 32);
        fence_async_all();
        int g0 = 2;
#pragma unroll 1
        for (int n = 0; n < 36; n += n == 0 || n == 33 ? 2 : 1) {
          const int it = (n >> 1) - (n & 1);
          const int blk = it & 15 ? (it <= idx ? it - 1 : 15 - it) : it ? 15 - idx : idx;
          acquire(g0, n < 7 ? 2 : 1, 3);
          if (elect()) {
            const uint32_t fb = sb + SM_BAR + (B_FULL + g0) * 8;
            if (n == 5) mbar_arrive(sb + SM_BAR + B_SLOT * 8);
            mbar_expect_tx(fb, 2 * GR);
            asm volatile("cp.async.bulk" TMA_MB ".L2::cache_hint [%0], [%1], %2, [%3], %4;" ::"r"(sb + g0 * GR), "l"(g_kv + (unsigned)((((n & 1) * 16 + (head & 15)) * 16 + blk) * 32768)),
                         "r"(2 * GR), "r"(fb), "l"(it >= 8 ? EV_FIRST : EV_NORMAL) : "memory");
          }
          g0 = g0 == 12 ? 2 : g0 + (n == 13 || n == 19 ? 4 : 2);
        }
      }
      int c5 = 0;
      if (spare) { bar_sync(5, 64); pe = 0x3FC0; }
      else c5 = get_ticket();
      auto conv_fill = [&](int g, int ch) {
        acquire(g, 1, 1);
        if (elect()) {
          const uint32_t fb = sb + SM_BAR + (B_FULL + g) * 8;
          mbar_expect_tx(fb, WBYTES + 4096);
          bulk_g2s<true>(sb + g * GR, g_w + (size_t)ch * WSTRIDE, WBYTES, fb);
          bulk_g2s<true>(sb + g * GR + WBYTES, p.ssk + (size_t)ch * SEQ, 4096, fb);
        }
      };
#pragma unroll 1
      for (int i = 0, g = 2; i < cn; i++) {
        if ((i & 15) == 0) { flag_wait(FLAG(F_U + (spare ? 32 - __clz(i >> 4) : 4)), NMAIN); fence_async_all(); }
        conv_fill(g + (i & 1), cch + i * cstep + (i == 4 ? c5 : 0));
        if (i & 1) g = conv_next(g, spare);
      }
      if (!spare) {
        const int rt = grp + 8 * rank, ct = idx;
        int g0 = P3G, top = 12;
        const uint8_t* src = g_cimg + (unsigned)((rt * 64 + 32) * GR);
#pragma unroll 1
        for (int kb = 0; kb < 64; kb++) {
          if (!(kb & 31)) { flag_wait(FLAG(F_CTX + rt * 2 + ((kb ^ 32) >> 5)), 32); fence_async_all(); if (kb) src -= 64 * GR; }
          acquire(g0, kb < 11 ? 2 : 1, 3);
          if (elect()) {
            const uint32_t fb = sb + SM_BAR + (B_FULL + g0) * 8;
            mbar_expect_tx(fb, 2 * GR);
            bulk_g2s<true>(sb + g0 * GR, src, GR, fb);
            tma2d_mc<true>(sb + (g0 + 1) * GR + rank * 8192, &p.wo, ct * 128 + rank * 64, (kb ^ 32) * 64, fb);
          }
          src += GR;
          g0 = g0 == (kb < XK ? 12 : kb < YK ? 10 : 8) ? (kb == 3 ? 2 : 0) : g0 + 2;
          if (kb == XK || (kb >= YK && top == P3Y && (kb == 63 || mbar_test(sb + SM_BAR + B_SLOT * 8, 1)))) {
            const bool j = kb != XK;
            if (j) { mbar_wait1(sb + SM_BAR + B_SLOT * 8, 1); fence_async_all(); }
            acquire(top, 1, 0);
            if (elect()) {
              const uint32_t fb = sb + SM_BAR + (B_FULL + top) * 8;
              mbar_expect_tx(fb, j ? 2 * GR + 512 : 2 * GR);
              if (j) bulk_g2s(sb + SM_GATE, g_gate + (unsigned)(rt * 128), 512, fb);
              tma3d(sb + top * GR, j ? &p.y3 : &p.x3, 0, (j ? ct : rt) * 128, (j ? rt : ct) * 2, fb);
            }
            top -= 2;
          }
        }
        unsigned n = 0;
        if (lane == 0) n = atomicInc(FLAG(F_EXIT), 0x7fffffffu);
        if (__any_sync(0xffffffffu, n == NMAIN - 1)) {
#pragma unroll
          for (int i = lane; i < 96; i += 32) *reinterpret_cast<uint2*>(FLAG(i)) = make_uint2(0, 0);
        }
      }
      if (lane == 0) mbar_arrive(sb + SM_BAR + B_DONE * 8);
    }
    __syncwarp();
    cluster_wait();
  } else {
    asm volatile("setmaxnreg.inc.sync.aligned.u32 232;");
    Cons c;
    c.sb = sb; c.pf = 0; c.wg = wgi - 1; c.tid = threadIdx.x & 127;
    const int lane = threadIdx.x & 31, t = lane & 3;
    const int row = c.wg * 64 + (warp & 3) * 16 + (lane >> 2);
    const uint32_t dkk = desc_k(sb), dk0 = dkk + c.wg * 512, dm0 = desc_mn<8192>(sb), dv0 = desc_mn<16384>(sb);
    const uint32_t dsw = DG + 512 - c.wg * 1024;
    if (c.wg == 1) bar_arrive(1, 256);
    c.pfree = 1;
    asm("mapa.shared::cluster.u32 %0, %1, %2;" : "=r"(c.relb) : "r"(sb + SM_BAR + (B_EMPTY + (c.tid >> 1)) * 8), "r"(c.tid & 1));
    c.zero = p.zero;
    const uint32_t stg = sb + (c.wg * 64 + (warp & 3) * 16 + ((lane >> 3) & 1) * 8 + (lane & 7)) * 128 + (((lane >> 4) ^ (lane & 7)) << 4);

    uint32_t dd0;
    auto load_dd = [&]() { asm volatile("ld.global.nc.u16 %0, [%1];" : "=r"(dd0) : "l"(p.ssd + (unsigned)(cch + c.wg * cstep + (lane & c.zero)))); };
    int pass = c.zero;
#pragma unroll 1
    do {
    if (pass) {
      load_dd();
#pragma unroll 1
      for (int g = 2; g < NGR; g += 3) { mbar_wait(sb + SM_BAR + (B_FULL + g) * 8, 0); c.release(g, 3); }
      c.pf = 0x924;
    if (spare) {
      c.wait_full(1);
      int g = 2;
#pragma unroll 1
      for (int r = 0; r < 4; r++) {
        float d[4] = {0.f, 0.f, 0.f, 0.f}, e[4] = {0.f, 0.f, 0.f, 0.f};
#pragma unroll 1
        for (int kb = 0; kb < 16; kb += 2) {
          c.wait_full(g);
          wg_fence();
#pragma unroll 1
          for (int k = 0; k < 4; k++) {
            mma_ss_n8(d, dk0 + g * DG + k * 2, dkk + DG + kb * 8 + k * 2);
            mma_ss_n8(e, dk0 + (g + 1) * DG + k * 2, dkk + DG + kb * 8 + 8 + k * 2);
          }
          wg_commit();
          wg_wait<0>();
          c.release(g, 2);
          g = g == NGR - 2 ? 2 : g + 2;
        }
        reg_fence(d); reg_fence(e);
        d[0] += e[0]; d[2] += e[2];
        if (t == 0) {
          float* gp = g_gate + (unsigned)((lb - NMAIN) * 512 + r * 128 + row);
          gp[0] = rcp(1.f + ex2(-1.4426950408889634f * d[0])); gp[8] = rcp(1.f + ex2(-1.4426950408889634f * d[2]));
        }
      }
      fence_release();
      __syncwarp();
      if (lane == 0) flag_add(FLAG(F_GATE));
    }
    } else cluster_wait();
    get_slot();
    } while (redo && !pass++);
    const float dmask = (float)(2 * t - (row & 63));
    int c5 = 0;
    uint32_t pv[32];
#pragma unroll 1
    for (int rnd = 0; rnd < (spare ? 0 : 2); rnd++) {
      float O[64];
      uint32_t Q[32];
      c.wait_full(2);
#pragma unroll 1
      for (int tile = c.zero; tile < 2; tile++) {
        float acc[128];
        const bool single = tile == 0;
        {
          const uint32_t a = dk0 + 2 * DG, b = dm0 + 3 * DG;
          c.turn_begin();
          wg_fence();
          mma_ss_n256_init<1>(acc, a, b);
#pragma unroll
          for (int k = 1; k < 4; k++) mma_ss_n256<1>(acc, a + k * 2, b + k * 128);
          wg_commit();
          if (single) c.turn_end();
        }
#pragma unroll 1
        for (int kb = 1; kb < 8; kb++) {
          const int g0 = 2 + 3 * (kb & 3);
          const uint32_t a = dk0 + g0 * DG, b = dm0 + (g0 + 1) * DG;
          const bool second = (kb == 1 && !single) || kb == 7;
          if (!second) { wg_wait<0>(); c.release(2 + 3 * ((kb - 1) & 3), 3); }
          c.wait_full(g0);
          if (!second) c.turn_begin();
          wg_fence();
#pragma unroll
          for (int k = 0; k < 4; k++) mma_ss_n256<1>(acc, a + k * 2, b + k * 128);
          wg_commit();
          if (kb != 6) c.turn_end();
          if (second) { wg_wait<1>(); c.release(2 + 3 * ((kb - 1) & 3), 3); }
          if (tile == 1 && kb == 3) { c.wait_stage_free(); stsm_frag<0, 4>(pv, stg); }
          if (tile == 1 && kb == 4) { stsm_frag<4, 8>(pv, stg); c.staged(); }
        }
        c.wait_stage_free();
        const bool nxt = c.try_full(2);
        wg_wait<0>();
        reg_fence(acc);
        c.release(11, 3);
        store_scaled(acc, SM_C, SM_C, stg, sb);
        c.staged();
        pack_frag<64>(acc, pv);
        if (!nxt) mbar_wait(sb + SM_BAR + (B_FULL + 2) * 8, (c.pf >> 2) & 1);
        c.pf ^= 4;
      }
      {
        float qa[64];
        float (&qb)[64] = O;
        {
          const uint32_t a = dk0 + 2 * DG, b = dm0 + 4 * DG;
          c.turn_begin();
          wg_fence();
          mma_ss_n128_init<1>(qa, a, b);
          mma_ss_n128_init<1>(qb, a + dsw, b);
#pragma unroll
          for (int k = 1; k < 4; k++) {
            mma_ss_n128<1>(qa, a + k * 2, b + k * 128);
            mma_ss_n128<1>(qb, a + dsw + k * 2, b + k * 128);
          }
          wg_commit();
        }
#pragma unroll 1
        for (int kb = 1; kb < 16; kb++) {
          const int g0 = 2 + 3 * (kb & 3);
          const uint32_t a = dk0 + g0 * DG, b = dm0 + (g0 + 2) * DG;
          const bool second = kb == 1 || kb == 15;
          if (!second) { wg_wait<0>(); c.release(2 + 3 * ((kb - 1) & 3), 3); }
          c.wait_full(g0);
          if (!second) c.turn_begin();
          wg_fence();
#pragma unroll
          for (int k = 0; k < 4; k++) {
            mma_ss_n128<1>(qa, a + k * 2, b + k * 128);
            mma_ss_n128<1>(qb, a + dsw + k * 2, b + k * 128);
          }
          wg_commit();
          if (kb != 14) c.turn_end();
          if (second) { wg_wait<1>(); c.release(2 + 3 * ((kb - 1) & 3), 3); }
          if (kb == QFLUSH) { c.wait_stage_free(); stsm_frag<0, 4>(pv, stg); }
          if (kb == QFLUSH + 1) { stsm_frag<4, 8>(pv, stg); c.staged(); }
        }
        c.wait_stage_free();
        const bool k0 = c.try_full(2);
        wg_wait<0>();
        reg_fence(qa); reg_fence(qb);
        c.release(11, 3);
        pack_frag<0>(qa, Q);
        if (c.wg == 0) {
          pack_frag<0>(qb, pv);
          stsm_frag(pv, stg);
        }
        if (!k0) c.wait_full(2); else c.pf ^= 4;
      }
      {
        const int nA = idx + 1;
        uint32_t (&P)[32] = pv;
        SoftState z;
        z.m0 = z.m1 = z.l0 = z.l1 = 0.f; z.shifted = c.zero;
#pragma unroll 1
        for (int seg = c.zero;; seg++) {
        if (c.wg == seg) attn_half(c, O, P, Q, nA == 1 && !seg, stg, z, dkk, dv0, dmask, seg);
        if (seg) break;
        int gk = c.wg ? 2 : 4, gv = c.wg ? 2 : 6;
        uint32_t dk = dkk + gk * DG;
#pragma unroll 1
        for (int it = 1 - c.wg; it < 17 - c.wg; it++) {
          float S[64];
          c.turn_begin();
          wg_fence();
          issue_qk(S, Q, dk);
          wg_commit();
          const uint32_t dv = dv0 + gv * DG;
          uint32_t relk = c.relb + gk * 8, relv = c.relb + gv * 8;
          gk = gv == 12 ? 2 : gv + (it == 6 || it == 9 ? 4 : 2);
          gv = it == 16 ? gk : gk == 12 ? 2 : gk + 2;
          uint32_t fk = sb + SM_BAR + (B_FULL + gk) * 8, fv = sb + SM_BAR + (B_FULL + gv) * 8, park = (c.pf >> gk) & 1, parv = (c.pf >> gv) & 1;
          c.pf ^= (1u << gk) | (1u << gv);
          dk = dkk + gk * DG;
          float lo0 = z.l0, lo1 = z.l1;
          const bool first = it == nA || it == 0;
          if (it == nA) {
            lo0 = rcp(quad_sum(lo0)); lo1 = rcp(quad_sum(lo1));
            z.m0 = z.m1 = z.l0 = z.l1 = 0.f; z.shifted = 0;
          }
          float s0, s1, d0 = z.m0, d1 = z.m1;
          int pre = z.shifted || (it & 15) == 0 || it + 1 == nA;
          float lim = first ? -1.f : SM_LIMIT;
          asm volatile("" : "+r"(relk), "+r"(relv), "+r"(fk), "+r"(fv), "+r"(park), "+r"(parv), "+r"(dk), "+r"(pre), "+f"(lim), "+f"(d0), "+f"(d1), "+f"(z.l0), "+f"(z.l1));
          if (it + c.wg > 1) {
            issue_pv<0>(O, P, dv, it != nA + 1 && it != 1, true);
            issue_pv<1>(O, P, dv, 1, true);
            c.turn_end();
          } else if (it) {
            issue_pv<0>(O, P, dv, 0, true);
            wg_commit(); wg_commit();
            c.turn_end();
            bar_sync(6, 256);
          } else stage_q2(c, O, P, stg);
          wg_wait<4>();
          reg_fence(S); reg_fence(Q);
          if (c.tid < 4) asm volatile("mbarrier.arrive.shared::cluster.b64 _, [%0];" ::"r"(relk) : "memory");
#pragma unroll 1
          for (int pass = 0;; pass++) {
            if (pre) {
              if (it + 1 == nA) load_q(Q, stg);
              if ((it & 15) == 0) mask_diag(S, dmask);
              if (z.shifted) shift_scores(S, d0, d1);
            }
            float tr[ROT];
            exp_quarter<0, 3>(S, P, tr, s0, s1, sb);
            exp_quarter<1, 2>(S, P, tr, s0, s1, sb);
            exp_quarter<2, 1>(S, P, tr, s0, s1, sb);
            exp_quarter<3, 0>(S, P, tr, s0, s1, sb);
            reg_fence(O);
            if (c.tid < (pass || !it ? 0 : 4)) asm volatile("mbarrier.arrive.shared::cluster.b64 _, [%0];" ::"r"(relv) : "memory");
            const bool ok = mbar_test(fk, park) & mbar_test(fv, parv);
            if (!ok) lim = -1.f;
            if (!__any_sync(0xffffffffu, !(s0 <= lim && s1 <= lim))) break;
            if (pass) break;
            if (it == nA) {
              store_scaled(O, lo0, lo1, stg, sb);
              c.staged();
            }
            if (!it) bar_arrive(6, 256);
            if (!ok) { mbar_wait(fk, park); mbar_wait(fv, parv); }
            if (!soft_unsafe(s0, s1, first)) break;
            soft_fix(S, O, z, first, d0, d1);
            pre = 1;
          }
          z.l0 += s0; z.l1 += s1;
        }
        if (!c.wg) bar_arrive(6, 256);
        }
        load_dd();
        c.turn_begin();
        wg_fence();
        issue_pv<0>(O, P, dv0 + 12 * DG, 1, true);
        issue_pv<1>(O, P, dv0 + 12 * DG, 1, !c.wg);
        c.turn_end();
        z.l0 = rcp(quad_sum(z.l0)); z.l1 = rcp(quad_sum(z.l1));
        c.wait_stage_free();
        if (rnd) c5 = get_ticket();
        wg_wait<0>();
        reg_fence(O); reg_fence(P);
        c.release(12, 2);
        store_scaled(O, z.l0, z.l1, stg, sb);
        c.staged();
      }
    }
    conv_tasks(c, p, (cn + 1 - c.wg) >> 1, spare, cch + c.wg * cstep, 2 * cstep, c5, dd0, dkk, warp & 3, lane);
    if (c.wg == 1) c.pf ^= 0x14;
    if (c.wg == (cn & 1)) c.turn_begin();
    if (!spare) {
      const int rt = grp + 8 * rank, ct = idx;
      float acc[64];
      int g0 = P3G + 2, pg = P3G;
      {
        c.wait_full(P3G);
        const uint32_t a = dk0 + P3G * DG, b = dm0 + (P3G + 1) * DG;
        wg_fence();
        mma_ss_n128_init<1>(acc, a, b);
#pragma unroll
        for (int k = 1; k < 4; k++) mma_ss_n128<1>(acc, a + k * 2, b + k * 128);
        wg_commit();
      }
#pragma unroll 1
      for (int kb = 1; kb < 64; kb++) {
        c.wait_full(g0);
        if (kb == STR && !c.wg) c.turn_begin();
        const uint32_t a = dk0 + g0 * DG, b = dm0 + (g0 + 1) * DG;
        wg_fence();
#pragma unroll
        for (int k = 0; k < 4; k++) mma_ss_n128<1>(acc, a + k * 2, b + k * 128);
        wg_commit();
        if (kb < STR) { wg_wait<1>(); c.release(pg, kb <= 59 ? 2 : 0); }
        pg = g0;
        g0 = g0 == (kb < XK ? 12 : kb < YK ? 10 : 8) ? (kb == 3 ? 2 : 0) : g0 + 2;
      }
      if (c.wg) c.turn_end();
      cluster_arrive();
      c.wait_full(P3X);
      c.wait_full(P3Y);
      const float g0f = __uint_as_float(lds32(sb + SM_GATE + row * 4)), g1f = __uint_as_float(lds32(sb + SM_GATE + row * 4 + 32));
      const uint32_t gp0 = pack_bf16(g0f, g0f), gp1 = pack_bf16(g1f, g1f);
      const float h0 = 1.f - g0f, h1 = 1.f - g1f;
      const int w = warp & 3;
      const uint32_t xa = stg + P3X * GR;
      const uint32_t ya = sb + P3Y * GR + c.wg * 16384 + ((lane >> 4) * 8 + (lane & 7)) * 128 + (((2 * w + ((lane >> 3) & 1)) ^ (lane & 7)) << 4);
      uint32_t xy[32];
      auto prep = [&](int j0, int j1) {
#pragma unroll
        for (int jj = j0; jj < j1; jj++) {
          uint32_t x[4], y[4];
          asm volatile("ldmatrix.sync.aligned.m8n8.x4.shared.b16 {%0,%1,%2,%3}, [%4];" : "=r"(x[0]), "=r"(x[1]), "=r"(x[2]), "=r"(x[3]) : "r"((xa ^ ((jj & 3) << 5)) + (jj >> 2) * 16384) : "memory");
          asm volatile("ldmatrix.sync.aligned.m8n8.x4.trans.shared.b16 {%0,%1,%2,%3}, [%4];" : "=r"(y[0]), "=r"(y[1]), "=r"(y[2]), "=r"(y[3]) : "r"(ya + jj * 2048) : "memory");
#pragma unroll
          for (int i = 0; i < 4; i++) xy[4 * jj + i] = hmul2(x[i], y[i]);
        }
      };
      prep(0, 4);
      wg_wait<0>();
      reg_fence(acc);
#pragma unroll
      for (int hf = 0; hf < 2; hf++) {
#pragma unroll
        for (int i = 16 * hf; i < 16 * hf + 16; i++) {
          const float h = (i & 1) ? h1 : h0;
          xy[i] = hfma2((i & 1) ? gp1 : gp0, xy[i], pack_bf16(acc[2 * i] * h, acc[2 * i + 1] * h));
        }
        if (hf) stsm_frag<4, 8>(xy, xa); else stsm_frag<0, 4>(xy, xa);
        fence_async_smem();
        __syncwarp();
        const int r0 = c.wg * 64 + w * 16;
        if (lane == 0) tma2d_store(&p.out, sb + (P3X + hf) * GR + r0 * 128, ct * 128 + hf * 64, rt * 128 + r0);
        if (!hf) prep(4, 8);
      }
      if (lane == 0) asm volatile("cp.async.bulk.commit_group;\ncp.async.bulk.wait_group.read 0;" ::: "memory");
    } else { cluster_arrive(); }
    if (lane == 0) mbar_arrive(sb + SM_BAR + B_DONE * 8);
    __syncwarp();
    cluster_wait();
  }
}

typedef CUresult (*EncFn)(CUtensorMap*, CUtensorMapDataType, cuuint32_t, void*, const cuuint64_t*, const cuuint64_t*, const cuuint32_t*,
                          const cuuint32_t*, CUtensorMapInterleave, CUtensorMapSwizzle, CUtensorMapL2promotion, CUtensorMapFloatOOBfill);

void enc2d(EncFn enc, CUtensorMap* tm, const void* base, uint64_t cols, uint64_t rows, uint32_t bc, uint32_t br) {
  cuuint64_t dims[2] = {cols, rows}; cuuint64_t strides[1] = {cols * 2}; cuuint32_t box[2] = {bc, br}; cuuint32_t es[2] = {1, 1};
  enc(tm, CU_TENSOR_MAP_DATA_TYPE_BFLOAT16, 2, const_cast<void*>(base), dims, strides, box, es, CU_TENSOR_MAP_INTERLEAVE_NONE,
      CU_TENSOR_MAP_SWIZZLE_128B, CU_TENSOR_MAP_L2_PROMOTION_L2_128B, CU_TENSOR_MAP_FLOAT_OOB_FILL_NONE);
}
void enc3d(EncFn enc, CUtensorMap* tm, const void* base, uint64_t K, uint64_t N, uint32_t bk = 64, uint64_t pitch = 0) {
  cuuint64_t dims[3] = {64, K, N / 64}; cuuint64_t strides[2] = {pitch ? pitch : N * 2, 128}; cuuint32_t box[3] = {64, bk, 2}; cuuint32_t es[3] = {1, 1, 1};
  enc(tm, CU_TENSOR_MAP_DATA_TYPE_BFLOAT16, 3, const_cast<void*>(base), dims, strides, box, es, CU_TENSOR_MAP_INTERLEAVE_NONE,
      CU_TENSOR_MAP_SWIZZLE_128B, CU_TENSOR_MAP_L2_PROMOTION_L2_128B, CU_TENSOR_MAP_FLOAT_OOB_FILL_NONE);
}

}

extern "C" void kernel_launch(void* const* d_in, const int* in_sizes, int n_in, void* d_out, int out_size) {
  (void)in_sizes; (void)n_in; (void)out_size;
  typedef const __nv_bfloat16* BP;
  BP xq = (BP)d_in[0], ak = (BP)d_in[1], av = (BP)d_in[2], shk = (BP)d_in[3], ssk = (BP)d_in[4], ssd = (BP)d_in[5];
  BP ckv = (BP)d_in[7], wq = (BP)d_in[8], wuk = (BP)d_in[9], wuv = (BP)d_in[10], wo = (BP)d_in[11], gw = (BP)d_in[12];

  static EncFn enc = nullptr;
  if (!enc) {
    cudaDriverEntryPointQueryResult qr;
    cudaGetDriverEntryPoint("cuTensorMapEncodeTiled", (void**)&enc, cudaEnableDefault, &qr);
    cudaFuncSetAttribute(mega_kernel, cudaFuncAttributeMaxDynamicSharedMemorySize, SMEM_BYTES);
  }
  Params p;
  enc2d(enc, &p.x, xq, DM, SEQ, 64, 128);
  enc2d(enc, &p.c, ckv, DC, SEQ, 64, 128);
  enc3d(enc, &p.wq, wq, DM, NH * HD);
  enc3d(enc, &p.wuk, wuk, DC, NH * HD);
  enc3d(enc, &p.wuv, wuv, DC, NH * HD);
  enc2d(enc, &p.wo, wo, DM, NH * HD, 64, 64);
  enc3d(enc, &p.x3, xq, SEQ, DM, 128);
  enc2d(enc, &p.out, d_out, DM, SEQ, 64, 16);
  {
    void* wp = nullptr;
    cudaGetSymbolAddress(&wp, g_w);
    enc3d(enc, &p.y3, (uint8_t*)wp + WZ, DM, SEQ, 128, WSTRIDE);
    cuuint64_t dims[3] = {WSTRIDE / 2, DM / 2, 2}; cuuint64_t strides[2] = {2 * WSTRIDE, WSTRIDE}; cuuint32_t box[3] = {16, 32, 2}; cuuint32_t es[3] = {1, 1, 1};
    enc(&p.w, CU_TENSOR_MAP_DATA_TYPE_BFLOAT16, 3, wp, dims, strides, box, es, CU_TENSOR_MAP_INTERLEAVE_NONE,
        CU_TENSOR_MAP_SWIZZLE_32B, CU_TENSOR_MAP_L2_PROMOTION_NONE, CU_TENSOR_MAP_FLOAT_OOB_FILL_NONE);
  }
  p.zero = 0;
  cudaGetSymbolAddress((void**)&p.flags, g_flags);
  for (int i = 0; i < 128; i++) {
    const int tp = i % NSLOT;
    p.pref[i] = tp < 32 ? (tp & 7) * 8 + (tp >> 3) : tp < 60 ? (1 + (tp - 32) % 7) * 8 + 4 + (tp - 32) / 7 : tp < 62 ? tp + 4 : tp - 58;
  }
  p.gate_w = gw; p.ak = ak; p.av = av; p.shk = shk; p.ssk = ssk; p.ssd = ssd; p.wukp = wuk; p.wuvp = wuv;

  mega_kernel<<<132, NTHREADS, SMEM_BYTES>>>(p);
}
```

```cpp
#include <cuda_runtime.h>
#include <cuda.h>
#include <cuda_bf16.h>
#include <stdint.h>

namespace {

constexpr int SEQ = 2048, DM = 1024, DC = 512, NH = 32, HD = 128;
constexpr int GR = 16384;
constexpr int NGR = 14;
constexpr int SM_BAR = NGR * GR;
constexpr int SM_GATE = SM_BAR + 512;
constexpr int SM_UST = SM_GATE + 512;
constexpr int SMEM_BYTES = SM_UST + 2048;
constexpr int NTHREADS = 384;
constexpr float SM_LIMIT = 1.0995116e12f;
constexpr float SM_LOW = 9.094947e-13f;
constexpr int CNS = 109;
constexpr int CN_SPARE = CNS, NTICK = 256 - 2 * CN_SPARE;
constexpr int XK = 57, YK = 62;
constexpr int STR = 61;
constexpr int P3G = 6, P3X = 12, P3Y = 10;
constexpr int NMAIN = 128;

constexpr int B_FULL = 0, B_FREE = 14, B_SLOT = 16, B_DONE = 17, B_EMPTY = 18, B_EV = 32, B_TICK = 36;
constexpr int V_SLOT = 37, V_TICK = 38;

__device__ __align__(1024) uint8_t g_kv[2 * 16 * 16 * 32768];
__device__ __align__(1024) uint8_t g_cimg[16 * NH * 32768];
__device__ __align__(1024) float g_gate[SEQ];
constexpr int WZ = 256, WPL = WZ + 4096, WBYTES = 2 * WPL + 32, WSTRIDE = 2 * WPL + 128;
__device__ __align__(1024) uint8_t g_w[DM * WSTRIDE];
__device__ __align__(32) unsigned g_flags[96 * 8];
constexpr int F_KV = 0, F_CTX = 16, F_U = 48, F_AD = 56, F_Y = 64, F_GATE = 72, F_EXIT = 73, F_TICK = 74;
constexpr int NSLOT = 66;
#define FLAG(i) (&g_flags[(i) * 8])
#define CLAIMP(i) (p.flags + (i) * 8 + 1)

constexpr int QFLUSH = 3;
constexpr int PSL = 200;
constexpr int US0 = 900;
constexpr int EROT = 6;
constexpr int RST = 2;
constexpr int UP0 = 4;
constexpr int UP1 = 11;
constexpr int X_DELAY = 900;
constexpr int X_D2 = 500;
constexpr int ROT = 8;
#define KV_ROW(idx, t) (8 * (t) + 2 * ((idx) & 3))
#define KV_HEAD(idx, t) ((idx) >> 2)

__device__ __forceinline__ uint32_t smem_u32(const void* p) { return (uint32_t)__cvta_generic_to_shared(p); }
__device__ __forceinline__ void mbar_init(uint32_t bar, int cnt) { asm volatile("mbarrier.init.shared::cta.b64 [%0], %1;" ::"r"(bar), "r"(cnt) : "memory"); }
__device__ __forceinline__ void mbar_expect_tx(uint32_t bar, uint32_t bytes) { asm volatile("mbarrier.arrive.expect_tx.shared::cta.b64 _, [%0], %1;" ::"r"(bar), "r"(bytes) : "memory"); }
__device__ __forceinline__ void mbar_arrive(uint32_t bar) { asm volatile("mbarrier.arrive.shared::cta.b64 _, [%0];" ::"r"(bar) : "memory"); }
__device__ __forceinline__ void mbar_arrive_cluster(uint32_t bar, uint32_t cta) {
  asm volatile("{\n.reg .b32 r;\nmapa.shared::cluster.u32 r, %0, %1;\nmbarrier.arrive.shared::cluster.b64 _, [r];\n}\n" ::"r"(bar), "r"(cta) : "memory");
}
__device__ __forceinline__ void send_both(uint32_t bar, uint32_t off, uint32_t v) {
#pragma unroll
  for (int r = 0; r < 2; r++)
    asm volatile("{\n.reg .b32 a, b;\nmapa.shared::cluster.u32 a, %0, %1;\nadd.u32 b, a, %3;\nst.async.shared::cluster.mbarrier::complete_tx::bytes.u32 [b], %2, [a];\n}\n"
                 ::"r"(bar), "r"(r), "r"(v), "r"(off) : "memory");
}
__device__ __forceinline__ bool mbar_try(uint32_t bar, uint32_t parity) {
  uint32_t ok;
  asm volatile("{\n.reg .pred p;\nmbarrier.try_wait.parity.shared::cta.b64 p, [%1], %2, 20000;\nselp.u32 %0, 1, 0, p;\n}\n" : "=r"(ok) : "r"(bar), "r"(parity) : "memory");
  return ok;
}
__device__ __forceinline__ bool mbar_test(uint32_t bar, uint32_t parity) {
  uint32_t ok;
  asm volatile("{\n.reg .pred p;\nmbarrier.test_wait.parity.shared::cta.b64 p, [%1], %2;\nselp.u32 %0, 1, 0, p;\n}\n" : "=r"(ok) : "r"(bar), "r"(parity) : "memory");
  return ok;
}
__device__ __forceinline__ void mbar_wait(uint32_t bar, uint32_t parity) {
  asm volatile("{\n.reg .pred p;\nWAIT_LOOP:\nbar.warp.sync -1;\nmbarrier.try_wait.parity.shared::cta.b64 p, [%0], %1;\n@!p bra WAIT_LOOP;\n}\n" ::"r"(bar), "r"(parity) : "memory");
}
__device__ __forceinline__ void mbar_wait1(uint32_t bar, uint32_t parity) {
  asm volatile("{\n.reg .pred p;\nWAIT_LOOP:\nbar.warp.sync -1;\nmbarrier.try_wait.parity.shared::cta.b64 p, [%0], %1, 4000;\n@!p bra WAIT_LOOP;\n}\n" ::"r"(bar), "r"(parity) : "memory");
}
constexpr uint64_t EV_NORMAL = 0x1000000000000000ull, EV_FIRST = 0x12F0000000000000ull;
__device__ __forceinline__ uint32_t ldg_stream(const uint32_t* p) {
  uint32_t r; asm volatile("ld.global.nc.L1::no_allocate.L2::cache_hint.b32 %0, [%1], %2;" : "=r"(r) : "l"(p), "l"(EV_FIRST)); return r;
}
#define TMA_LD "cp.async.bulk.tensor."
#define TMA_MB ".shared::cluster.global.mbarrier::complete_tx::bytes"
__device__ __forceinline__ void tma2d(uint32_t dst, const CUtensorMap* tm, int c0, int c1, uint32_t bar) {
  asm volatile(TMA_LD "2d" TMA_MB " [%0], [%1, {%3, %4}], [%2];" ::"r"(dst), "l"(tm), "r"(bar), "r"(c0), "r"(c1) : "memory");
}
template <bool ONCE = false> __device__ __forceinline__ void tma2d_mc(uint32_t dst, const CUtensorMap* tm, int c0, int c1, uint32_t bar) {
  if (ONCE) asm volatile(TMA_LD "2d" TMA_MB ".multicast::cluster.L2::cache_hint [%0], [%1, {%3, %4}], [%2], %5, %6;"
                         ::"r"(dst), "l"(tm), "r"(bar), "r"(c0), "r"(c1), "h"((uint16_t)3), "l"(EV_FIRST) : "memory");
  else asm volatile(TMA_LD "2d" TMA_MB ".multicast::cluster [%0], [%1, {%3, %4}], [%2], %5;"
                    ::"r"(dst), "l"(tm), "r"(bar), "r"(c0), "r"(c1), "h"((uint16_t)3) : "memory");
}
__device__ __forceinline__ void tma2d_p(uint32_t dst, const CUtensorMap* tm, int c0, int c1, uint32_t bar, bool once) {
  asm volatile(TMA_LD "2d" TMA_MB ".L2::cache_hint [%0], [%1, {%3, %4}], [%2], %5;" ::"r"(dst), "l"(tm), "r"(bar), "r"(c0), "r"(c1), "l"(once ? EV_FIRST : EV_NORMAL) : "memory");
}
__device__ __forceinline__ void tma3d_mc_p(uint32_t dst, const CUtensorMap* tm, int c0, int c1, int c2, uint32_t bar, bool once) {
  asm volatile(TMA_LD "3d" TMA_MB ".multicast::cluster.L2::cache_hint [%0], [%1, {%3, %4, %5}], [%2], %6, %7;"
               ::"r"(dst), "l"(tm), "r"(bar), "r"(c0), "r"(c1), "r"(c2), "h"((uint16_t)3), "l"(once ? EV_FIRST : EV_NORMAL) : "memory");
}
template <bool ONCE = false> __device__ __forceinline__ void tma3d(uint32_t dst, const CUtensorMap* tm, int c0, int c1, int c2, uint32_t bar) {
  if (ONCE) asm volatile(TMA_LD "3d" TMA_MB ".L2::cache_hint [%0], [%1, {%3, %4, %5}], [%2], %6;" ::"r"(dst), "l"(tm), "r"(bar), "r"(c0), "r"(c1), "r"(c2), "l"(EV_FIRST) : "memory");
  else
  asm volatile(TMA_LD "3d" TMA_MB " [%0], [%1, {%3, %4, %5}], [%2];" ::"r"(dst), "l"(tm), "r"(bar), "r"(c0), "r"(c1), "r"(c2) : "memory");
}
__device__ __forceinline__ void tma3d_mc(uint32_t dst, const CUtensorMap* tm, int c0, int c1, int c2, uint32_t bar) {
  asm volatile(TMA_LD "3d" TMA_MB ".multicast::cluster [%0], [%1, {%3, %4, %5}], [%2], %6;"
               ::"r"(dst), "l"(tm), "r"(bar), "r"(c0), "r"(c1), "r"(c2), "h"((uint16_t)3) : "memory");
}
template <bool ONCE = false> __device__ __forceinline__ void bulk_g2s(uint32_t dst, const void* src, uint32_t bytes, uint32_t bar) {
  if (ONCE) asm volatile("cp.async.bulk" TMA_MB ".L2::cache_hint [%0], [%1], %2, [%3], %4;" ::"r"(dst), "l"(src), "r"(bytes), "r"(bar), "l"(EV_FIRST) : "memory");
  else asm volatile("cp.async.bulk" TMA_MB " [%0], [%1], %2, [%3];" ::"r"(dst), "l"(src), "r"(bytes), "r"(bar) : "memory");
}
__device__ __forceinline__ void tma2d_store(const CUtensorMap* tm, uint32_t src, int c0, int c1) {
  asm volatile("cp.async.bulk.tensor.2d.global.shared::cta.bulk_group [%0, {%2, %3}], [%1];" ::"l"(tm), "r"(src), "r"(c0), "r"(c1) : "memory");
}
__device__ __forceinline__ void prefetch_tm(const CUtensorMap* tm) { asm volatile("prefetch.tensormap [%0];" ::"l"(tm) : "memory"); }
__device__ __forceinline__ void wg_fence() { asm volatile("wgmma.fence.sync.aligned;" ::: "memory"); }
__device__ __forceinline__ void wg_commit() { asm volatile("wgmma.commit_group.sync.aligned;" ::: "memory"); }
template <int N> __device__ __forceinline__ void wg_wait() { asm volatile("wgmma.wait_group.sync.aligned %0;" ::"n"(N) : "memory"); }
__device__ __forceinline__ void bar_sync(int id, int n) { asm volatile("bar.sync %0, %1;" ::"r"(id), "r"(n) : "memory"); }
__device__ __forceinline__ void bar_arrive(int id, int n) { asm volatile("bar.arrive %0, %1;" ::"r"(id), "r"(n) : "memory"); }
__device__ __forceinline__ void fence_async_smem() { asm volatile("fence.proxy.async.shared::cta;" ::: "memory"); }
__device__ __forceinline__ void fence_async_all() { asm volatile("fence.proxy.async.global;" ::: "memory"); }
__device__ __forceinline__ uint32_t pack_bf16(float lo, float hi) { uint32_t r; asm("cvt.rn.bf16x2.f32 %0, %1, %2;" : "=r"(r) : "f"(hi), "f"(lo)); return r; }
__device__ __forceinline__ float ex2(float x) { float r; asm("ex2.approx.ftz.f32 %0, %1;" : "=f"(r) : "f"(x)); return r; }
__device__ __forceinline__ float rcp(float x) { float r; asm("rcp.approx.ftz.f32 %0, %1;" : "=f"(r) : "f"(x)); return r; }
__device__ __forceinline__ void flag_wait(const unsigned* f, unsigned target) {
  unsigned v;
  do { asm volatile("ld.acquire.gpu.global.u32 %0, [%1];" : "=r"(v) : "l"(f) : "memory"); } while (__any_sync(0xffffffffu, v < target));
}
__device__ __forceinline__ bool elect() {
  uint32_t r;
  asm volatile("{\n.reg .pred p;\nelect.sync _|p, -1;\nselp.u32 %0, 1, 0, p;\n}\n" : "=r"(r));
  return r;
}
__device__ __forceinline__ void fence_release() { asm volatile("fence.release.gpu;" ::: "memory"); }
__device__ __forceinline__ void flag_add(unsigned* f) { asm volatile("red.relaxed.gpu.global.inc.u32 [%0], 0x7fffffff;" ::"l"(f) : "memory"); }
__device__ __forceinline__ void cluster_arrive() { asm volatile("barrier.cluster.arrive.relaxed.aligned;" ::: "memory"); }
__device__ __forceinline__ void cluster_wait() { asm volatile("barrier.cluster.wait.aligned;" ::: "memory"); }
__device__ __forceinline__ uint32_t hmul2(uint32_t a, uint32_t b) { uint32_t r; asm("mul.rn.bf16x2 %0, %1, %2;" : "=r"(r) : "r"(a), "r"(b)); return r; }
__device__ __forceinline__ uint32_t hadd2(uint32_t a, uint32_t b) { uint32_t r; asm("add.rn.bf16x2 %0, %1, %2;" : "=r"(r) : "r"(a), "r"(b)); return r; }
__device__ __forceinline__ uint32_t hfma2(uint32_t a, uint32_t b, uint32_t c) { uint32_t r; asm("fma.rn.bf16x2 %0, %1, %2, %3;" : "=r"(r) : "r"(a), "r"(b), "r"(c)); return r; }
__device__ __forceinline__ uint32_t lds32(uint32_t a) { uint32_t r; asm volatile("ld.shared.b32 %0, [%1];" : "=r"(r) : "r"(a) : "memory"); return r; }
__device__ __forceinline__ uint4 lds128(uint32_t a) { uint4 r; asm volatile("ld.shared.v4.b32 {%0,%1,%2,%3}, [%4];" : "=r"(r.x), "=r"(r.y), "=r"(r.z), "=r"(r.w) : "r"(a) : "memory"); return r; }
__device__ __forceinline__ uint32_t desc_k(uint32_t addr) { return ((addr & 0x3FFFF) >> 4) | (1u << 16); }
template <int LBO> __device__ __forceinline__ uint32_t desc_mn(uint32_t addr) { return ((addr & 0x3FFFF) >> 4) | ((uint32_t)(LBO >> 4) << 16); }
#define DHI "0x40000040"

#define R8(d, o) "+f"(d[o]), "+f"(d[o + 1]), "+f"(d[o + 2]), "+f"(d[o + 3]), "+f"(d[o + 4]), "+f"(d[o + 5]), "+f"(d[o + 6]), "+f"(d[o + 7])
#define R32(d, o) R8(d, o), R8(d, o + 8), R8(d, o + 16), R8(d, o + 24)
#define R64(d, o) R32(d, o), R32(d, o + 32)
#define L64 "%0,%1,%2,%3,%4,%5,%6,%7,%8,%9,%10,%11,%12,%13,%14,%15,%16,%17,%18,%19,%20,%21,%22,%23,%24,%25,%26,%27,%28,%29,%30,%31," \
            "%32,%33,%34,%35,%36,%37,%38,%39,%40,%41,%42,%43,%44,%45,%46,%47,%48,%49,%50,%51,%52,%53,%54,%55,%56,%57,%58,%59,%60,%61,%62,%63"
#define L128 L64 ",%64,%65,%66,%67,%68,%69,%70,%71,%72,%73,%74,%75,%76,%77,%78,%79,%80,%81,%82,%83,%84,%85,%86,%87,%88,%89,%90,%91,%92,%93,%94,%95," \
            "%96,%97,%98,%99,%100,%101,%102,%103,%104,%105,%106,%107,%108,%109,%110,%111,%112,%113,%114,%115,%116,%117,%118,%119,%120,%121,%122,%123,%124,%125,%126,%127"

template <int TB> __device__ __forceinline__ void mma_ss_n128(float (&d)[64], uint32_t da, uint32_t db) {
  asm volatile("{\n.reg .b64 da, db;\nmov.b64 da, {%64, " DHI "};\nmov.b64 db, {%65, " DHI "};\n"
               "wgmma.mma_async.sync.aligned.m64n128k16.f32.bf16.bf16 {" L64 "}, da, db, 1, 1, 1, 0, %66;\n}\n"
               : R64(d, 0) : "r"(da), "r"(db), "n"(TB));
}
template <int TB> __device__ __forceinline__ void mma_rs_n128(float (&d)[64], uint32_t a0, uint32_t a1, uint32_t a2, uint32_t a3, uint32_t db, int sd) {
  asm volatile("{\n.reg .pred p;\n.reg .b64 db;\nsetp.ne.b32 p, %69, 0;\nmov.b64 db, {%68, " DHI "};\n"
               "wgmma.mma_async.sync.aligned.m64n128k16.f32.bf16.bf16 {" L64 "}, {%64,%65,%66,%67}, db, p, 1, 1, %70;\n}\n"
               : R64(d, 0) : "r"(a0), "r"(a1), "r"(a2), "r"(a3), "r"(db), "r"(sd), "n"(TB));
}
template <int TB> __device__ __forceinline__ void mma_ss_n256(float (&d)[128], uint32_t da, uint32_t db) {
  asm volatile("{\n.reg .b64 da, db;\nmov.b64 da, {%128, " DHI "};\nmov.b64 db, {%129, " DHI "};\n"
               "wgmma.mma_async.sync.aligned.m64n256k16.f32.bf16.bf16 {" L128 "}, da, db, 1, 1, 1, 0, %130;\n}\n"
               : R64(d, 0), R64(d, 64) : "r"(da), "r"(db), "n"(TB));
}
#define W8(d, o) "=f"(d[o]), "=f"(d[o + 1]), "=f"(d[o + 2]), "=f"(d[o + 3]), "=f"(d[o + 4]), "=f"(d[o + 5]), "=f"(d[o + 6]), "=f"(d[o + 7])
#define W32(d, o) W8(d, o), W8(d, o + 8), W8(d, o + 16), W8(d, o + 24)
#define W64(d, o) W32(d, o), W32(d, o + 32)
template <int TB> __device__ __forceinline__ void mma_ss_n128_init(float (&d)[64], uint32_t da, uint32_t db) {
  asm volatile("{\n.reg .b64 da, db;\nmov.b64 da, {%64, " DHI "};\nmov.b64 db, {%65, " DHI "};\n"
               "wgmma.mma_async.sync.aligned.m64n128k16.f32.bf16.bf16 {" L64 "}, da, db, 0, 1, 1, 0, %66;\n}\n"
               : W64(d, 0) : "r"(da), "r"(db), "n"(TB));
}
template <int TB> __device__ __forceinline__ void mma_rs_n128_init(float (&d)[64], uint32_t a0, uint32_t a1, uint32_t a2, uint32_t a3, uint32_t db) {
  asm volatile("{\n.reg .b64 db;\nmov.b64 db, {%68, " DHI "};\n"
               "wgmma.mma_async.sync.aligned.m64n128k16.f32.bf16.bf16 {" L64 "}, {%64,%65,%66,%67}, db, 0, 1, 1, %69;\n}\n"
               : W64(d, 0) : "r"(a0), "r"(a1), "r"(a2), "r"(a3), "r"(db), "n"(TB));
}
template <int TB> __device__ __forceinline__ void mma_ss_n256_init(float (&d)[128], uint32_t da, uint32_t db) {
  asm volatile("{\n.reg .b64 da, db;\nmov.b64 da, {%128, " DHI "};\nmov.b64 db, {%129, " DHI "};\n"
               "wgmma.mma_async.sync.aligned.m64n256k16.f32.bf16.bf16 {" L128 "}, da, db, 0, 1, 1, 0, %130;\n}\n"
               : W64(d, 0), W64(d, 64) : "r"(da), "r"(db), "n"(TB));
}
#define L32 "%0,%1,%2,%3,%4,%5,%6,%7,%8,%9,%10,%11,%12,%13,%14,%15,%16,%17,%18,%19,%20,%21,%22,%23,%24,%25,%26,%27,%28,%29,%30,%31"
template <bool INIT> __device__ __forceinline__ void mma_rs_n64(float (&d)[32], uint32_t a0, uint32_t a1, uint32_t a2, uint32_t a3, uint32_t db) {
  if (INIT) asm volatile("{\n.reg .b64 db;\nmov.b64 db, {%36, " DHI "};\n"
               "wgmma.mma_async.sync.aligned.m64n64k16.f32.bf16.bf16 {" L32 "}, {%32,%33,%34,%35}, db, 0, 1, 1, 0;\n}\n"
               : W32(d, 0) : "r"(a0), "r"(a1), "r"(a2), "r"(a3), "r"(db));
  else asm volatile("{\n.reg .b64 db;\nmov.b64 db, {%36, " DHI "};\n"
               "wgmma.mma_async.sync.aligned.m64n64k16.f32.bf16.bf16 {" L32 "}, {%32,%33,%34,%35}, db, 1, 1, 1, 0;\n}\n"
               : R32(d, 0) : "r"(a0), "r"(a1), "r"(a2), "r"(a3), "r"(db));
}
#define L16 "%0,%1,%2,%3,%4,%5,%6,%7,%8,%9,%10,%11,%12,%13,%14,%15"
template <int O, bool INIT> __device__ __forceinline__ void mma_rs_n32(float (&d)[128], uint32_t a0, uint32_t a1, uint32_t a2, uint32_t a3, uint32_t db) {
  if (INIT) asm volatile("{\n.reg .b64 db;\nmov.b64 db, {%20, 0x00000008};\n"
               "wgmma.mma_async.sync.aligned.m64n32k16.f32.bf16.bf16 {" L16 "}, {%16,%17,%18,%19}, db, 0, 1, 1, 0;\n}\n"
               : W8(d, O), W8(d, O + 8) : "r"(a0), "r"(a1), "r"(a2), "r"(a3), "r"(db));
  else asm volatile("{\n.reg .b64 db;\nmov.b64 db, {%20, 0x00000008};\n"
               "wgmma.mma_async.sync.aligned.m64n32k16.f32.bf16.bf16 {" L16 "}, {%16,%17,%18,%19}, db, 1, 1, 1, 0;\n}\n"
               : R8(d, O), R8(d, O + 8) : "r"(a0), "r"(a1), "r"(a2), "r"(a3), "r"(db));
}
template <int S, int J> __device__ __forceinline__ void conv_step(float (&d)[128], const uint32_t (&a)[64], uint32_t db) {
  if constexpr (J >= 0 && J >= (S >> 1)) {
    mma_rs_n32<16 * J, S == 0>(d, a[4 * S], a[4 * S + 1], a[4 * S + 2], a[4 * S + 3], db + (uint32_t)((2 * J - S) * 16));
    conv_step<S, J - 1>(d, a, db);
  }
}
__device__ __forceinline__ void mma_ss_n8(float (&d)[4], uint32_t da, uint32_t db) {
  asm volatile("{\n.reg .b64 da, db;\nmov.b64 da, {%4, " DHI "};\nmov.b64 db, {%5, 0x00000008};\n"
               "wgmma.mma_async.sync.aligned.m64n8k16.f32.bf16.bf16 {%0,%1,%2,%3}, da, db, 1, 1, 1, 0, 0;\n}\n"
               : "+f"(d[0]), "+f"(d[1]), "+f"(d[2]), "+f"(d[3]) : "r"(da), "r"(db));
}
template <int N> __device__ __forceinline__ void reg_fence(float (&d)[N]) {
#pragma unroll
  for (int i = 0; i < N; i++) asm volatile("" : "+f"(d[i])::"memory");
}
template <int N> __device__ __forceinline__ void reg_fence(uint32_t (&d)[N]) {
#pragma unroll
  for (int i = 0; i < N; i++) asm volatile("" : "+r"(d[i])::"memory");
}

struct __align__(64) Params {
  unsigned* flags;
  int zero;
  uint8_t pref[128];
  const __nv_bfloat16 *gate_w, *ak, *av, *shk, *ssk, *ssd, *wukp, *wuvp;
  CUtensorMap x, c, wq, wuk, wuv, wo, x3, y3, out, w;
};

template <int O, int N, int M> __device__ __forceinline__ void pack_frag(const float (&acc)[N], uint32_t (&pk)[M]) {
#pragma unroll
  for (int i = 0; i < 32; i++) pk[i] = pack_bf16(acc[O + 2 * i], acc[O + 2 * i + 1]);
}
template <int J0 = 0, int J1 = 8, int M> __device__ __forceinline__ void stsm_frag(const uint32_t (&pk)[M], uint32_t a) {
#pragma unroll
  for (int jj = J0; jj < J1; jj++)
    asm volatile("stmatrix.sync.aligned.m8n8.x4.shared.b16 [%0], {%1,%2,%3,%4};" ::"r"((a ^ ((jj & 3) << 5)) + (jj >> 2) * 16384),
                 "r"(pk[4 * jj]), "r"(pk[4 * jj + 1]), "r"(pk[4 * jj + 2]), "r"(pk[4 * jj + 3]) : "memory");
}

template <int N> __device__ __forceinline__ void store_scaled(const float (&acc)[N], float s0, float s1, uint32_t a, uint32_t never_zero) {
  float t[8];
#pragma unroll
  for (int jj = 0; jj < 8; jj++) {
    float v = acc[8 * jj] * s0;
    if (jj >= RST) {
      v = t[jj - RST];
      asm("{\n.reg .pred p;\nsetp.ne.u32 p, %3, 0;\n@p mul.f32 %0, %1, %2;\n}\n" : "+f"(v) : "f"(acc[8 * jj]), "f"(s0), "r"(never_zero));
    }
    const uint32_t q = pack_bf16(v, acc[8 * jj + 1] * s0);
    t[jj] = __uint_as_float(q);
    asm volatile("stmatrix.sync.aligned.m8n8.x4.shared.b16 [%0], {%1,%2,%3,%4};" ::"r"((a ^ ((jj & 3) << 5)) + (jj >> 2) * 16384), "r"(q),
                 "r"(pack_bf16(acc[8 * jj + 2] * s1, acc[8 * jj + 3] * s1)), "r"(pack_bf16(acc[8 * jj + 4] * s0, acc[8 * jj + 5] * s0)),
                 "r"(pack_bf16(acc[8 * jj + 6] * s1, acc[8 * jj + 7] * s1)) : "memory");
  }
}

struct Cons {
  uint32_t sb;
  uint32_t pf;
  int wg, tid;
  __device__ __forceinline__ void wait_full(int g) { mbar_wait(sb + SM_BAR + (B_FULL + g) * 8, (pf >> g) & 1); pf ^= 1u << g; }
  uint32_t relb;
  __device__ __forceinline__ void release(int g, int n) {
    if (tid < 2 * n) asm volatile("mbarrier.arrive.shared::cluster.b64 _, [%0];" ::"r"(relb + g * 8) : "memory");
  }
  __device__ __forceinline__ void turn_begin() { bar_sync(1 + wg, 256); }
  __device__ __forceinline__ void turn_end() { bar_arrive(2 - wg, 256); }
  __device__ __forceinline__ void staged() { __syncwarp(); if ((tid & 31) == 0) mbar_arrive(sb + SM_BAR + (B_EV + wg) * 8); }
  int zero;
  uint32_t pfree;
  __device__ __forceinline__ void wait_stage_free() { mbar_wait(sb + SM_BAR + (B_FREE + wg) * 8, pfree); pfree ^= 1; }
  __device__ __forceinline__ bool try_full(int g) { return mbar_test(sb + SM_BAR + (B_FULL + g) * 8, (pf >> g) & 1); }
};

constexpr float SM_C = 0.08838834764831845f * 1.4426950408889634f;
struct SoftState { float m0, m1, l0, l1; int shifted; };
__device__ __forceinline__ void ex2_rot(float& t, float s, uint32_t never_zero) {
  asm("{\n.reg .pred p;\nsetp.ne.u32 p, %2, 0;\n@p ex2.approx.ftz.f32 %0, %1;\n}\n" : "+f"(t) : "f"(s), "r"(never_zero));
}
__device__ __forceinline__ void pin(float a, uint32_t never_zero) {
  asm volatile("{\n.reg .pred p;\nsetp.eq.u32 p, %1, 0;\n@p st.shared.f32 [%1], %0;\n}\n" ::"f"(a), "r"(never_zero) : "memory");
}
template <int O, int N> __device__ __forceinline__ void reg_fence_part(uint32_t (&d)[32]) {
#pragma unroll
  for (int i = O; i < O + N; i++) asm volatile("" : "+r"(d[i])::"memory");
}
template <int Q, int W, int N> __device__ __forceinline__ void exp_quarter(const float (&S)[N], uint32_t (&P)[32], float (&t)[ROT], float& s0, float& s1, uint32_t nz) {
#pragma unroll
  for (int i = 8 * Q; i < 8 * Q + 8; i++) {
    float& a = t[(2 * i) % ROT];
    float& b = t[(2 * i + 1) % ROT];
    if (2 * i < ROT) { a = ex2(S[2 * i]); b = ex2(S[2 * i + 1]); }
    else { ex2_rot(a, S[2 * i], nz); ex2_rot(b, S[2 * i + 1], nz); }
    if (i < 2) { if (i) s1 = a + b; else s0 = a + b; }
    else if (i & 1) { s1 += a; s1 += b; } else { s0 += a; s0 += b; }
    if (i == 8 * Q) { pin(Q ? s1 : s0, nz); wg_wait<W>(); reg_fence_part<8 * Q, 8>(P); }
    P[i] = pack_bf16(a, b);
  }
}
template <int N> __device__ __forceinline__ void shift_scores(float (&S)[N], float d0, float d1) {
#pragma unroll
  for (int i = 0; i < N; i++) S[i] -= (i & 2) ? d1 : d0;
}
__device__ __forceinline__ bool soft_high(float s0, float s1, float lim = SM_LIMIT) { return s0 > lim || s1 > lim; }
__device__ __forceinline__ bool soft_unsafe(float s0, float s1, bool first) {
  uint32_t b0 = __ballot_sync(0xffffffffu, s0 >= SM_LOW), b1 = __ballot_sync(0xffffffffu, s1 >= SM_LOW);
  b0 |= b0 >> 1; b0 |= b0 >> 2; b1 |= b1 >> 1; b1 |= b1 >> 2;
  return __any_sync(0xffffffffu, soft_high(s0, s1)) || (first && (b0 & b1 & 0x11111111u) != 0x11111111u);
}
template <int N> __device__ __forceinline__ void soft_fix(const float (&S)[N], float (&O)[64], SoftState& z, bool first, float& d0, float& d1) {
  d0 = d1 = first ? -INFINITY : 0.f;
#pragma unroll
  for (int j = 0; j < N / 4; j++) { d0 = fmaxf(d0, fmaxf(S[4 * j], S[4 * j + 1])); d1 = fmaxf(d1, fmaxf(S[4 * j + 2], S[4 * j + 3])); }
  d0 = fmaxf(d0, __shfl_xor_sync(0xffffffffu, d0, 1)); d1 = fmaxf(d1, __shfl_xor_sync(0xffffffffu, d1, 1));
  d0 = fmaxf(d0, __shfl_xor_sync(0xffffffffu, d0, 2)); d1 = fmaxf(d1, __shfl_xor_sync(0xffffffffu, d1, 2));
  const float sc0 = ex2(-fmaxf(d0, 0.f)), sc1 = ex2(-fmaxf(d1, 0.f));
  z.m0 += d0; z.m1 += d1; z.l0 *= sc0; z.l1 *= sc1; z.shifted = 1;
#pragma unroll
  for (int j = 0; j < 16; j++) { O[4 * j] *= sc0; O[4 * j + 1] *= sc0; O[4 * j + 2] *= sc1; O[4 * j + 3] *= sc1; }
}
template <int N> __device__ __forceinline__ void mask_diag(float (&S)[N], float nd) {
  asm volatile("" : "+f"(nd));
#pragma unroll
  for (int i = 0; i < 32; i++) {
    const float beyond = __saturatef(nd + (float)(8 * (i >> 2) + (i & 1) - 4 * (i & 2)));
    S[N - 32 + i] = fmaf(beyond, -3.0e38f, S[N - 32 + i]);
  }
}
__device__ __forceinline__ float quad_sum(float v) {
  v += __shfl_xor_sync(0xffffffffu, v, 1);
  v += __shfl_xor_sync(0xffffffffu, v, 2);
  return v;
}
__device__ __forceinline__ void issue_qk(float (&S)[64], const uint32_t (&Q)[32], uint32_t dk) {
  mma_rs_n128_init<0>(S, Q[0], Q[1], Q[2], Q[3], dk);
#pragma unroll
  for (int s = 1; s < 8; s++) mma_rs_n128<0>(S, Q[4 * s], Q[4 * s + 1], Q[4 * s + 2], Q[4 * s + 3], dk + (s >> 2) * 1024 + (s & 3) * 2, 1);
}
__device__ __forceinline__ void issue_qk(float (&S)[32], const uint32_t (&Q)[32], uint32_t dk) {
  mma_rs_n64<true>(S, Q[0], Q[1], Q[2], Q[3], dk);
#pragma unroll
  for (int s = 1; s < 8; s++) mma_rs_n64<false>(S, Q[4 * s], Q[4 * s + 1], Q[4 * s + 2], Q[4 * s + 3], dk + (s >> 2) * 1024 + (s & 3) * 2);
}
__device__ __forceinline__ void load_q(uint32_t (&Q)[32], uint32_t a) {
  __syncwarp();
#pragma unroll
  for (int jj = 0; jj < 8; jj++)
    asm volatile("ldmatrix.sync.aligned.m8n8.x4.shared.b16 {%0,%1,%2,%3}, [%4];" : "=r"(Q[4 * jj]), "=r"(Q[4 * jj + 1]), "=r"(Q[4 * jj + 2]), "=r"(Q[4 * jj + 3])
                 : "r"((a ^ ((jj & 3) << 5)) + (jj >> 2) * 16384) : "memory");
}
template <int H> __device__ __forceinline__ void issue_pv(float (&O)[64], const uint32_t (&P)[32], uint32_t dv, int acc, bool on) {
  if (on) {
#pragma unroll
    for (int s = 4 * H; s < 4 * H + 4; s++) {
      mma_rs_n128<1>(O, P[4 * s], P[4 * s + 1], P[4 * s + 2], P[4 * s + 3], dv + s * 128, s != 0 ? 1 : acc);
      if (s & 1) wg_commit();
    }
  } else { wg_commit(); wg_commit(); }
}
constexpr uint32_t DG = GR >> 4;
__device__ __forceinline__ void stage_q2(Cons& c, const float (&O)[64], uint32_t (&P)[32], uint32_t stg) {
  wg_commit(); wg_commit(); wg_commit(); wg_commit();
  c.turn_end();
  pack_frag<0>(O, P);
  stsm_frag(P, stg);
}
__device__ __forceinline__ void attn_half(Cons& c, float (&O)[64], uint32_t (&P)[32], uint32_t (&Q)[32], bool nextq, uint32_t stg, SoftState& z, uint32_t dkk, uint32_t dv0, float dmask, int last) {
  float S[32];
  c.turn_begin();
  wg_fence();
  issue_qk(S, Q, dkk + (last ? 8 : 2) * DG);
  wg_commit();
  issue_pv<0>(O, P, dv0 + 10 * DG, 1, last);
  issue_pv<1>(O, P, dv0 + 10 * DG, 1, last);
  c.turn_end();
  c.wait_full(last ? 12 : 4);
  wg_wait<4>();
  reg_fence(S);
  c.release(last ? 8 : 2, 2);
  reg_fence(Q);
  if (nextq) load_q(Q, stg);
  if (last) bar_sync(6, 256);
  mask_diag(S, dmask);
  float s0, s1, d0 = z.m0, d1 = z.m1;
#pragma unroll 1
  for (int pass = 0;; pass++) {
    if (z.shifted) shift_scores(S, d0, d1);
    float tr[ROT];
    exp_quarter<0, 3>(S, P, tr, s0, s1, c.sb);
    exp_quarter<1, 2>(S, P, tr, s0, s1, c.sb);
    pin(s1, c.sb); wg_wait<0>(); reg_fence_part<16, 16>(P); reg_fence(O);
    if (!soft_unsafe(s0, s1, !last) || pass) break;
    soft_fix(S, O, z, !last, d0, d1);
  }
  z.l0 += s0; z.l1 += s1;
  c.release(10, last ? 2 : 0);
  if (!last) c.wait_full(6);
}

template <int V> struct IC { static constexpr int value = V; };
__device__ __forceinline__ int conv_next(int g, bool spare) { return g >= NGR - 2 ? g - (NGR - 4) : !spare && g == 4 ? 1 : g + 2; }
__device__ __forceinline__ void conv_final(uint32_t rb, uint32_t yb, bool on) {
  const uint4 q0 = lds128(rb), q1 = lds128(rb + 4096), q2 = lds128(rb + 8192), q3 = lds128(rb + 12288);
  auto fin = [&](uint32_t x0, uint32_t x1, uint32_t x2, uint32_t x3) { return hadd2(hadd2(x0, x1), hadd2(x2, x3)); };
  asm volatile("{\n.reg .pred p;\nsetp.ne.b32 p, %5, 0;\n@p st.shared.v4.b32 [%0], {%1,%2,%3,%4};\n}\n" ::"r"(yb), "r"(fin(q0.x, q1.x, q2.x, q3.x)),
               "r"(fin(q0.y, q1.y, q2.y, q3.y)), "r"(fin(q0.z, q1.z, q2.z, q3.z)), "r"(fin(q0.w, q1.w, q2.w, q3.w)), "r"((int)on) : "memory");
}
__device__ __forceinline__ void conv_tasks(Cons& c, const Params& p, int ntask, bool spare, int ch, int chstep, int c5, uint32_t dd, uint32_t dkk, int w, int lane) {
  const uint32_t sb = c.sb;
  int g = 2 + c.wg;
  uint32_t rb = sb + g * GR;
  const uint32_t yb = sb + c.wg * 8192 + c.tid * 16;
  const int gt = 8 * w + (lane >> 2) + (lane & 3);
  uint32_t a[64], hb;
  auto lda = [&](int s) {
    a[4 * s] = lds32(hb + s * 256); a[4 * s + 1] = lds32(hb + s * 256 + 128);
    a[4 * s + 2] = lds32(hb + s * 256 + 16); a[4 * s + 3] = lds32(hb + s * 256 + 144);
  };
  auto first_a = [&]() {
    hb = sb + g * GR + WBYTES - 28 + gt * 4;
    lda(0); lda(15);
  };
  c.wait_full(g);
  first_a();
#pragma unroll 1
  for (int i = 0; i < ntask; i++) {
    const uint32_t base = sb + g * GR;
    lda(1); lda(14);
    a[0] = hadd2(a[0], gt == 7 ? dd : 0u); a[2] = hadd2(a[2], gt == 3 ? dd : 0u);
    float acc[128];
    const uint32_t db = dkk + ((WPL / 16 - 1) << 16) + g * DG + WZ / 16;
    c.turn_begin();
    auto pair = [&](auto kc) {
      constexpr int k = decltype(kc)::value;
      if (k < 7) wg_fence();
      if (k == 6) c.turn_end();
      conv_step<k, 7>(acc, a, db);
      conv_step<15 - k, 7>(acc, a, db);
      if (k < 6) { lda(k + 2); lda(13 - k); }
      if (k == 0) conv_final(rb, yb, i > 0);
      if (k == 1) {
        conv_final(rb + 2048, yb + 2048, i > 0);
        __syncwarp();
        if (lane == 0 && i > 0) mbar_arrive(sb + SM_BAR + (B_EV + c.wg) * 8);
      }
      if (k == 6) dd = __bfloat16_as_ushort(p.ssd[(ch + chstep + (i == 1 ? c5 : 0)) & (DM - 1)]);
    };
    pair(IC<0>()); pair(IC<1>()); pair(IC<2>()); pair(IC<3>()); pair(IC<4>()); pair(IC<5>()); pair(IC<6>()); pair(IC<7>());
    wg_commit();
    g = conv_next(g, spare);
    ch += chstep;
    rb = base + c.tid * 16;
    if (i + 1 < ntask) c.wait_full(g);
    const bool fr = mbar_test(sb + SM_BAR + (B_FREE + c.wg) * 8, c.pfree);
    wg_wait<0>();
    reg_fence(acc);
    reg_fence(a);
    bar_sync(3 + c.wg, 128);
    first_a();
    const int tw = (lane & 3) + w;
    const uint32_t xb = base + w * 4096 + tw * 32 + (lane >> 2) * 4;
    [[maybe_unused]] float t0[EROT + 1];
#pragma unroll
    for (int j = 0; j < 32; j++) {
      uint32_t ad = xb + j * 128;
      float v0 = acc[4 * j], v1 = acc[4 * j + 1];
      if (EROT && j > EROT) {
        v0 = t0[j % (EROT + 1)];
        asm("{\n.reg .pred p;\nsetp.ne.u32 p, %3, 0;\n@p add.f32 %0, %1, %2;\n}\n" : "+f"(v0) : "f"(acc[4 * j]), "f"(acc[j > 0 ? 4 * j - 2 : 0]), "r"(sb));
      } else if (j > 0) v0 += acc[j > 0 ? 4 * j - 2 : 0];
      if (j > 0) v1 += acc[j > 0 ? 4 * j - 1 : 0];
      uint32_t v = pack_bf16(v0, v1);
      t0[j % (EROT + 1)] = __uint_as_float(v);
      if (j == 31 && tw >= 4) { v = 0; ad -= 4096; }
      asm volatile("st.shared.b32 [%0], %1;" ::"r"(ad), "r"(v) : "memory");
    }
    if (!fr) c.wait_stage_free(); else c.pfree ^= 1;
  }
  bar_sync(3 + c.wg, 128);
  conv_final(rb, yb, true);
  conv_final(rb + 2048, yb + 2048, true);
  c.staged();
}

__global__ void __cluster_dims__(2, 1, 1) __launch_bounds__(NTHREADS, 1) mega_kernel(const __grid_constant__ Params p) {
  extern __shared__ __align__(1024) uint8_t smem_raw[];
  const uint32_t sb = smem_u32(smem_raw);
  if (threadIdx.x - 64 < 32) { prefetch_tm(&p.c); prefetch_tm(&p.wuk + (blockIdx.x & 1)); }
  const int wgi = __shfl_sync(0xffffffffu, threadIdx.x >> 7, 0);
  const int warp = __shfl_sync(0xffffffffu, threadIdx.x >> 5, 0);
  const uint32_t rank = blockIdx.x & 1;
  int slot;
  {
    uint32_t smid; asm volatile("mov.u32 %0, %smid;" : "=r"(smid));
    slot = p.pref[((smid >> 1) + (threadIdx.x & (smid >> 16))) & 127];
  }
  if (warp >= 3) {
    if (elect()) {
#pragma unroll
      for (int k = 0; k < 4; k++) mbar_init(sb + SM_BAR + ((warp - 3) * 4 + k) * 8, k == 1 && warp == 7 ? 11 : warp < (k ? 7 : 8) ? 1 : 4);
      if (warp == 7) { mbar_init(sb + SM_BAR + B_TICK * 8, 1); mbar_expect_tx(sb + SM_BAR + B_SLOT * 8, 8); mbar_expect_tx(sb + SM_BAR + B_TICK * 8, 4); }
      asm volatile("fence.mbarrier_init.release.cluster;" ::: "memory");
    }
    __syncwarp();
  }
  cluster_arrive();
  slot = __shfl_sync(0xffffffffu, slot, 0);
  const int pref = slot;
  if (warp < 4) {
    asm volatile("setmaxnreg.dec.sync.aligned.u32 40;");
    if (warp == 1 + 4 * rank) {
      unsigned taken = threadIdx.x == 32;
#pragma unroll 1
      for (int n = 0; n < NSLOT; n++) {
        asm volatile("{\n.reg .pred p;\nsetp.ne.b32 p, %0, 0;\n@p atom.relaxed.gpu.global.exch.b32 %0, [%1], 1;\n}\n" : "+r"(taken) : "l"(CLAIMP(slot)) : "memory");
        if (!__any_sync(0xffffffffu, taken)) break;
        slot = slot == NSLOT - 1 ? 0 : slot + 1;
      }
    }
    cluster_wait();
    if (threadIdx.x == 32) {
      send_both(sb + SM_BAR + B_SLOT * 8, (V_SLOT - B_SLOT) * 8 + rank * 4, slot | pref << 8);
    }
    if (warp == 2) {
#pragma unroll 1
      for (int kk = 0; kk < 4; kk++) {
        const int g0 = 2 + 3 * kk;
        const uint32_t fb = sb + SM_BAR + (B_FULL + g0) * 8;
        if (elect()) {
          mbar_expect_tx(fb, 3 * GR);
          tma2d(sb + g0 * GR, &p.c, kk * 64, (KV_ROW(pref & 7, 0) + rank) * 128, fb);
          tma3d_mc(sb + (g0 + 1 + rank) * GR, rank ? &p.wuv : &p.wuk, 0, kk * 64, ((pref & 56) >> 1) + 2 * KV_HEAD(pref & 7, 0), fb);
        }
        if (kk < 3) {
          uint32_t c0, c1;
          asm volatile("mov.u32 %0, %clock;" : "=r"(c0));
          do asm volatile("mov.u32 %0, %clock;" : "=r"(c1)); while (c1 - c0 < (kk ? X_D2 : X_DELAY));
        }
      }
      prefetch_tm(&p.x); prefetch_tm(&p.wq);
    }
  }
  int grp, idx, lb;
  int cn, cch, cstep;
  bool spare, redo;
  auto get_slot = [&]() {
    mbar_wait(sb + SM_BAR + B_SLOT * 8, 0);
    const uint32_t sv0 = __shfl_sync(0xffffffffu, lds32(sb + SM_BAR + V_SLOT * 8), 0), sv1 = __shfl_sync(0xffffffffu, lds32(sb + SM_BAR + V_SLOT * 8 + 4), 0);
    grp = (sv0 & 255) >> 3; idx = sv0 & 7; lb = (sv0 & 255) * 2 + rank;
    spare = grp == 8; redo = spare || sv0 != sv1;
    cn = CN_SPARE; cch = spare ? lb - NMAIN : 4 * CN_SPARE + 4 * lb; cstep = spare ? 4 : 1;
  };
  auto get_ticket = [&]() {
    mbar_wait(sb + SM_BAR + B_TICK * 8, 0);
    const int tk = __shfl_sync(0xffffffffu, lds32(sb + SM_BAR + V_TICK * 8), 0);
    cn = tk < NTICK ? 5 : 4;
    return 4 * NMAIN - 4 * lb - 4 + 2 * tk + rank;
  };

  if (wgi == 0) {
    asm volatile("setmaxnreg.dec.sync.aligned.u32 40;");
    const int lane = threadIdx.x & 31;
    cluster_arrive();
    get_slot();
    uint32_t pe = 0;
    auto acquire = [&](int g, int n, uint32_t m) {
      int i = g;
#pragma unroll 1
      do mbar_wait1(sb + SM_BAR + (B_EMPTY + i) * 8, (pe >> i) & 1); while (++i < g + n);
      pe ^= m << g;
    };
    if (warp == 3) {
      if (!spare) {
        const int s0 = lb * 16;
#pragma unroll 1
        for (int cg = 0; cg < 16; cg++) {
          if (cg == UP0 || cg == UP1) {
#pragma unroll 1
            for (int n = 0; n < 20 && !__any_sync(0xffffffffu, mbar_try(sb + SM_BAR + B_SLOT * 8, cg == UP0)); n++);
          } else if (cg < UP0) __nanosleep(US0);
          if (cg == UP1 && lane == rank * 32) send_both(sb + SM_BAR + B_TICK * 8, (V_TICK - B_TICK) * 8, atomicInc(FLAG(F_TICK), 0x7fffffffu));
          if (cg >= 5 && cg < 9) {
            unsigned l = lane;
            asm volatile("" : "+r"(l));
            const unsigned o = (idx * 8 + (l >> 2)) * (NH * HD) + (16 + 2 * grp) * HD + (l & 3) * 64;
            asm volatile("prefetch.global.L2 [%0];" ::"l"((rank ? p.wuvp : p.wukp) + (o + (cg - 1) * 64 * (NH * HD))));
          }
          const int ch = cg * 64 + 2 * lane;
          const uint32_t* kp = reinterpret_cast<const uint32_t*>(p.ak + (size_t)s0 * DM + ch);
          const uint32_t* vp = reinterpret_cast<const uint32_t*>(p.av + (size_t)s0 * DM + ch);
          const uint4 sw = __ldg(reinterpret_cast<const uint4*>(p.shk + ch * 4));
          uint32_t k3 = 0, k2 = 0, k1 = 0, k0 = 0, up = 0;
          if (lb > 0) { k3 = ldg_stream(kp - 4 * 512); k2 = ldg_stream(kp - 3 * 512); k1 = ldg_stream(kp - 2 * 512); k0 = ldg_stream(kp - 512); up = ldg_stream(vp - 512); }
          const uint32_t w0 = __byte_perm(sw.x, sw.z, 0x5410), w1 = __byte_perm(sw.x, sw.z, 0x7632);
          const uint32_t w2 = __byte_perm(sw.y, sw.w, 0x5410), w3 = __byte_perm(sw.y, sw.w, 0x7632);
          up = hmul2(hfma2(k0, w0, hfma2(k1, w1, hfma2(k2, w2, hmul2(k3, w3)))), up);
#pragma unroll 1
          for (int hb = 0; hb < 2; hb++) {
            uint32_t kk[8], u[8];
#pragma unroll
            for (int r = 0; r < 8; r++) { kk[r] = ldg_stream(kp + r * 512); u[r] = ldg_stream(vp + r * 512); }
#pragma unroll
            for (int r = 0; r < 8; r++) {
              k3 = k2; k2 = k1; k1 = k0; k0 = kk[r];
              u[r] = hmul2(hfma2(k0, w0, hfma2(k1, w1, hfma2(k2, w2, hmul2(k3, w3)))), u[r]);
            }
            if (lane == 0) asm volatile("cp.async.bulk.wait_group.read 0;" ::: "memory");
            __syncwarp();
            const uint32_t dst = sb + SM_UST + lane * 32 + ((lane & 4) << 2);
#pragma unroll
            for (int cc = 0; cc < 2; cc++) {
              const uint32_t sel = cc ? 0x7632 : 0x5410;
              asm volatile("st.shared.v4.b32 [%0], {%1,%2,%3,%4};" ::"r"(dst + cc * 1024), "r"(__byte_perm(u[6], u[5], sel)), "r"(__byte_perm(u[4], u[3], sel)),
                           "r"(__byte_perm(u[2], u[1], sel)), "r"(__byte_perm(u[0], up, sel)) : "memory");
              asm volatile("st.shared.v4.b32 [%0], {%1,%2,%3,%4};" ::"r"((dst ^ 16) + cc * 1024), "r"(__byte_perm(u[7], u[6], sel)), "r"(__byte_perm(u[5], u[4], sel)),
                           "r"(__byte_perm(u[3], u[2], sel)), "r"(__byte_perm(u[1], u[0], sel)) : "memory");
            }
            fence_async_smem();
            __syncwarp();
            if (lane == 0) {
              asm volatile("cp.async.bulk.tensor.3d.global.shared::cta.bulk_group.L2::cache_hint [%0, {%2, %3, %4}], [%1], %5;\ncp.async.bulk.commit_group;"
                           ::"l"(&p.w), "r"(sb + SM_UST), "r"(WZ / 2 + lb * 16 + (hb ^ 1) * (WPL / 2)), "r"(cg * 32), "r"(0), "l"(cg >= UP0 && cg < UP1 ? EV_FIRST : EV_NORMAL) : "memory");
            }
            up = u[7];
            kp += 8 * 512; vp += 8 * 512;
          }
          if ((cg & (cg + 1)) == 0 && lane == 0) {
            asm volatile("cp.async.bulk.wait_group 0;" ::: "memory");
            fence_release();
            flag_add(FLAG(F_U + 32 - __clz(cg)));
          }
        }
        prefetch_tm(&p.wo); prefetch_tm(&p.x3); prefetch_tm(&p.y3); prefetch_tm(&p.out);
      } else {
#pragma unroll 1
        for (int i = 0, g = 2; i < 32; i++) {
          acquire(g, i < 6 ? 2 : 1, 3);
          if (elect()) {
            const uint32_t fb = sb + SM_BAR + (B_FULL + g) * 8;
            if (i == 0) { mbar_expect_tx(fb - 8, 2048); bulk_g2s(sb + GR, p.gate_w, 2048, fb - 8); }
            mbar_expect_tx(fb, 2 * GR);
            tma3d(sb + g * GR, &p.x3, 0, (lb - NMAIN) * 512 + (i >> 3) * 128, (i & 7) * 2, fb);
          }
          g = g == NGR - 2 ? 2 : g + 2;
        }
        bar_arrive(5, 64);
      }
      unsigned long long t0, t1;
      asm volatile("mov.u64 %0, %globaltimer;" : "=l"(t0));
      auto check = [&]() {
        asm volatile("mov.u64 %0, %globaltimer;" : "=l"(t1));
        if (t1 - t0 > 2000000000ull) __trap();
      };
      if (!spare) {
        unsigned v;
        do {
          __nanosleep(PSL);
          check();
          asm volatile("ld.acquire.gpu.global.u32 %0, [%1];" : "=r"(v) : "l"(FLAG(lane & 1 ? F_Y + idx : F_GATE)) : "memory");
        } while (__any_sync(0xffffffffu, v < (lane & 1 ? 128 : 8)));
        __syncwarp();
        if (lane == 0) mbar_arrive(sb + SM_BAR + B_SLOT * 8);
      }
      if (lane == 0) {
        while (!mbar_try(sb + SM_BAR + B_DONE * 8, 0)) check();
      }
    } else if (warp != 0) {
      const int w = warp - 1;
      int ne = 12 + (CN_SPARE + 1 - w) / 2, c5 = 0;
      int cg = 2 + w, ch = cch + w * cstep;
#pragma unroll 1
      for (int e = spare ? 12 : 0; e < ne; e++) {
        const int rnd = e >= 6, k = e - 6 * rnd, rt = k == 4 ? idx : 15 - idx;
        uint8_t* dst = k < 4 ? g_kv + (size_t)(((k & 1) * 16 + 2 * grp + KV_HEAD(idx, k >> 1)) * 16 + KV_ROW(idx, k >> 1) + rank) * 32768 + w * 8192
                     : k < 6 ? g_cimg + (size_t)(rt * 32 + 16 * rnd + 2 * grp + rank) * 32768 + (w ^ (k & 1)) * 8192
                             : g_w + (size_t)ch * WSTRIDE + WZ;
        const uint32_t src = sb + w * 8192;
        if (e == 11) { c5 = get_ticket(); ne = 12 + ((cn + 1 - w) >> 1); }
        if (e == 6) flag_wait(FLAG(F_AD + grp), 32);
        mbar_wait1(sb + SM_BAR + (B_EV + w) * 8, e & 1);
        if (lane < 4 && k >= 6 && (!spare || e < ne - 6)) mbar_arrive_cluster(sb + SM_BAR + (B_EMPTY + cg) * 8, lane & 1);
        fence_async_smem();
        if (elect()) {
          const uint32_t cs = e >= 11 ? 4096 : 1024;
#pragma unroll 1
          for (uint32_t i = 0; i < (k >= 6 ? 4096 : 16384); i += cs) {
            const uint32_t o = (i + (i & 8192)) ^ (e == 11 ? 16384 : 0);
            asm volatile("cp.async.bulk.global.shared::cta.bulk_group.L2::cache_hint [%0], [%1], %2, %3;" ::"l"(dst + o), "r"(src + o), "r"(cs),
                         "l"(e == 4 || e == 5 || spare ? EV_FIRST : EV_NORMAL) : "memory");
            asm volatile("cp.async.bulk.commit_group;\ncp.async.bulk.wait_group.read 1;" ::: "memory");
            if (e == 11 && i == 8192) {
              mbar_arrive_cluster(sb + SM_BAR + (B_EMPTY + 1) * 8, 0); mbar_arrive_cluster(sb + SM_BAR + (B_EMPTY + 1) * 8, 1);
            }
          }
          asm volatile("cp.async.bulk.wait_group 0;" ::: "memory");
          mbar_arrive(sb + SM_BAR + (B_FREE + w) * 8);
        }
        __syncwarp();
        if (lane < (e == ne - 1 && !spare ? 2 : 0)) mbar_arrive_cluster(sb + SM_BAR + B_EMPTY * 8, lane);
        if (k >= 3) {
          fence_release();
          const unsigned fl = k == 3 ? F_KV + rnd * 8 + grp : k < 6 ? F_CTX + rt * 2 + rnd : F_Y + ((unsigned)ch >> 7);
          if (lane <= (e == (spare ? 12 : 5))) flag_add(FLAG(lane ? (spare ? F_GATE : F_AD + grp) : fl));
        }
        if (k >= 6) { cg = conv_next(cg, spare); ch += 2 * cstep + (k == 7 ? c5 : 0); }
      }
      if (lane == 0) mbar_arrive(sb + SM_BAR + B_DONE * 8);
    } else {
#pragma unroll 1
      for (int rnd = 0; rnd < (spare ? 0 : 2); rnd++) {
        const int hp = 16 * rnd + 2 * grp, head = hp + rank;
#pragma unroll 1
        for (int kk = rnd || redo ? 0 : 4; kk < 32; kk++) {
          const int g0 = 2 + 3 * (kk & 3);
          acquire(g0, kk < 4 ? 3 : 1, 7);
          if (elect()) {
            const uint32_t fb = sb + SM_BAR + (B_FULL + g0) * 8;
            mbar_expect_tx(fb, 3 * GR);
            if (kk < 16) {
              tma2d_p(sb + g0 * GR, &p.c, (kk & 7) * 64, (KV_ROW(idx, kk >> 3) + rank) * 128, fb, rnd);
              tma3d_mc_p(sb + (g0 + 1 + rank) * GR, rank ? &p.wuv : &p.wuk, 0, (kk & 7) * 64, (hp + KV_HEAD(idx, kk >> 3)) * 2, fb, kk >= 8);
            } else {
              tma2d_mc(sb + (g0 + rank) * GR, &p.x, (kk - 16) * 64, (rank ? 15 - idx : idx) * 128, fb);
              tma3d<true>(sb + (g0 + 2) * GR, &p.wq, 0, (kk - 16) * 64, head * 2, fb);
            }
          }
        }
        flag_wait(FLAG(F_KV + rnd * 8 + grp), 32);
        fence_async_all();
        int g0 = 2;
#pragma unroll 1
        for (int n = 0; n < 36; n += n == 0 || n == 33 ? 2 : 1) {
          const int it = (n >> 1) - (n & 1);
          const int blk = it & 15 ? (it <= idx ? it - 1 : 15 - it) : it ? 15 - idx : idx;
          acquire(g0, n < 7 ? 2 : 1, 3);
          if (elect()) {
            const uint32_t fb = sb + SM_BAR + (B_FULL + g0) * 8;
            if (n == 5) mbar_arrive(sb + SM_BAR + B_SLOT * 8);
            mbar_expect_tx(fb, 2 * GR);
            asm volatile("cp.async.bulk" TMA_MB ".L2::cache_hint [%0], [%1], %2, [%3], %4;" ::"r"(sb + g0 * GR), "l"(g_kv + (unsigned)((((n & 1) * 16 + (head & 15)) * 16 + blk) * 32768)),
                         "r"(2 * GR), "r"(fb), "l"(it >= 8 ? EV_FIRST : EV_NORMAL) : "memory");
          }
          g0 = g0 == 12 ? 2 : g0 + (n == 13 || n == 19 ? 4 : 2);
        }
      }
      int c5 = 0;
      if (spare) { bar_sync(5, 64); pe = 0x3FC0; }
      else c5 = get_ticket();
      auto conv_fill = [&](int g, int ch) {
        acquire(g, 1, 1);
        if (elect()) {
          const uint32_t fb = sb + SM_BAR + (B_FULL + g) * 8;
          mbar_expect_tx(fb, WBYTES + 4096);
          bulk_g2s<true>(sb + g * GR, g_w + (size_t)ch * WSTRIDE, WBYTES, fb);
          bulk_g2s<true>(sb + g * GR + WBYTES, p.ssk + (size_t)ch * SEQ, 4096, fb);
        }
      };
#pragma unroll 1
      for (int i = 0, g = 2; i < cn; i++) {
        if ((i & 15) == 0) { flag_wait(FLAG(F_U + (spare ? 32 - __clz(i >> 4) : 4)), NMAIN); fence_async_all(); }
        conv_fill(g + (i & 1), cch + i * cstep + (i == 4 ? c5 : 0));
        if (i & 1) g = conv_next(g, spare);
      }
      if (!spare) {
        const int rt = grp + 8 * rank, ct = idx;
        int g0 = P3G, top = 12;
        const uint8_t* src = g_cimg + (unsigned)((rt * 64 + 32) * GR);
#pragma unroll 1
        for (int kb = 0; kb < 64; kb++) {
          if (!(kb & 31)) { flag_wait(FLAG(F_CTX + rt * 2 + ((kb ^ 32) >> 5)), 32); fence_async_all(); if (kb) src -= 64 * GR; }
          acquire(g0, kb < 11 ? 2 : 1, 3);
          if (elect()) {
            const uint32_t fb = sb + SM_BAR + (B_FULL + g0) * 8;
            mbar_expect_tx(fb, 2 * GR);
            bulk_g2s<true>(sb + g0 * GR, src, GR, fb);
            tma2d_mc<true>(sb + (g0 + 1) * GR + rank * 8192, &p.wo, ct * 128 + rank * 64, (kb ^ 32) * 64, fb);
          }
          src += GR;
          g0 = g0 == (kb < XK ? 12 : kb < YK ? 10 : 8) ? (kb == 3 ? 2 : 0) : g0 + 2;
          if (kb == XK || (kb >= YK && top == P3Y && (kb == 63 || mbar_test(sb + SM_BAR + B_SLOT * 8, 1)))) {
            const bool j = kb != XK;
            if (j) { mbar_wait1(sb + SM_BAR + B_SLOT * 8, 1); fence_async_all(); }
            acquire(top, 1, 0);
            if (elect()) {
              const uint32_t fb = sb + SM_BAR + (B_FULL + top) * 8;
              mbar_expect_tx(fb, j ? 2 * GR + 512 : 2 * GR);
              if (j) bulk_g2s(sb + SM_GATE, g_gate + (unsigned)(rt * 128), 512, fb);
              tma3d(sb + top * GR, j ? &p.y3 : &p.x3, 0, (j ? ct : rt) * 128, (j ? rt : ct) * 2, fb);
            }
            top -= 2;
          }
        }
        unsigned n = 0;
        if (lane == 0) n = atomicInc(FLAG(F_EXIT), 0x7fffffffu);
        if (__any_sync(0xffffffffu, n == NMAIN - 1)) {
#pragma unroll
          for (int i = lane; i < 96; i += 32) *reinterpret_cast<uint2*>(FLAG(i)) = make_uint2(0, 0);
        }
      }
      if (lane == 0) mbar_arrive(sb + SM_BAR + B_DONE * 8);
    }
    __syncwarp();
    cluster_wait();
  } else {
    asm volatile("setmaxnreg.inc.sync.aligned.u32 232;");
    Cons c;
    c.sb = sb; c.pf = 0; c.wg = wgi - 1; c.tid = threadIdx.x & 127;
    const int lane = threadIdx.x & 31, t = lane & 3;
    const int row = c.wg * 64 + (warp & 3) * 16 + (lane >> 2);
    const uint32_t dkk = desc_k(sb), dk0 = dkk + c.wg * 512, dm0 = desc_mn<8192>(sb), dv0 = desc_mn<16384>(sb);
    const uint32_t dsw = DG + 512 - c.wg * 1024;
    if (c.wg == 1) bar_arrive(1, 256);
    c.pfree = 1;
    asm("mapa.shared::cluster.u32 %0, %1, %2;" : "=r"(c.relb) : "r"(sb + SM_BAR + (B_EMPTY + (c.tid >> 1)) * 8), "r"(c.tid & 1));
    c.zero = p.zero;
    const uint32_t stg = sb + (c.wg * 64 + (warp & 3) * 16 + ((lane >> 3) & 1) * 8 + (lane & 7)) * 128 + (((lane >> 4) ^ (lane & 7)) << 4);

    uint32_t dd0;
    auto load_dd = [&]() { asm volatile("ld.global.nc.u16 %0, [%1];" : "=r"(dd0) : "l"(p.ssd + (unsigned)(cch + c.wg * cstep + (lane & c.zero)))); };
    int pass = c.zero;
#pragma unroll 1
    do {
    if (pass) {
      load_dd();
#pragma unroll 1
      for (int g = 2; g < NGR; g += 3) { mbar_wait(sb + SM_BAR + (B_FULL + g) * 8, 0); c.release(g, 3); }
      c.pf = 0x924;
    if (spare) {
      c.wait_full(1);
      int g = 2;
#pragma unroll 1
      for (int r = 0; r < 4; r++) {
        float d[4] = {0.f, 0.f, 0.f, 0.f}, e[4] = {0.f, 0.f, 0.f, 0.f}, f[4] = {0.f, 0.f, 0.f, 0.f}, h[4] = {0.f, 0.f, 0.f, 0.f};
#pragma unroll 1
        for (int kb = 0; kb < 16; kb += 2) {
          c.wait_full(g);
          wg_fence();
#pragma unroll
          for (int k = 0; k < 4; k += 2) {
            mma_ss_n8(d, dk0 + g * DG + k * 2, dkk + DG + kb * 8 + k * 2);
            mma_ss_n8(e, dk0 + (g + 1) * DG + k * 2, dkk + DG + kb * 8 + 8 + k * 2);
            mma_ss_n8(f, dk0 + g * DG + k * 2 + 2, dkk + DG + kb * 8 + k * 2 + 2);
            mma_ss_n8(h, dk0 + (g + 1) * DG + k * 2 + 2, dkk + DG + kb * 8 + 8 + k * 2 + 2);
          }
          wg_commit();
          wg_wait<0>();
          c.release(g, 2);
          g = g == NGR - 2 ? 2 : g + 2;
        }
        reg_fence(d); reg_fence(e); reg_fence(f); reg_fence(h);
        d[0] = (d[0] + e[0]) + (f[0] + h[0]); d[2] = (d[2] + e[2]) + (f[2] + h[2]);
        if (t == 0) {
          float* gp = g_gate + (unsigned)((lb - NMAIN) * 512 + r * 128 + row);
          gp[0] = rcp(1.f + ex2(-1.4426950408889634f * d[0])); gp[8] = rcp(1.f + ex2(-1.4426950408889634f * d[2]));
        }
      }
    }
    } else cluster_wait();
    get_slot();
    } while (redo && !pass++);
    const float dmask = (float)(2 * t - (row & 63));
    int c5 = 0;
    uint32_t pv[32];
#pragma unroll 1
    for (int rnd = 0; rnd < (spare ? 0 : 2); rnd++) {
      float O[64];
      uint32_t Q[32];
      c.wait_full(2);
#pragma unroll 1
      for (int tile = c.zero; tile < 2; tile++) {
        float acc[128];
        const bool single = tile == 0;
        {
          const uint32_t a = dk0 + 2 * DG, b = dm0 + 3 * DG;
          c.turn_begin();
          wg_fence();
          mma_ss_n256_init<1>(acc, a, b);
#pragma unroll
          for (int k = 1; k < 4; k++) mma_ss_n256<1>(acc, a + k * 2, b + k * 128);
          wg_commit();
          if (single) c.turn_end();
        }
#pragma unroll 1
        for (int kb = 1; kb < 8; kb++) {
          const int g0 = 2 + 3 * (kb & 3);
          const uint32_t a = dk0 + g0 * DG, b = dm0 + (g0 + 1) * DG;
          const bool second = (kb == 1 && !single) || kb == 7;
          if (!second) { wg_wait<0>(); c.release(2 + 3 * ((kb - 1) & 3), 3); }
          c.wait_full(g0);
          if (!second) c.turn_begin();
          wg_fence();
#pragma unroll
          for (int k = 0; k < 4; k++) mma_ss_n256<1>(acc, a + k * 2, b + k * 128);
          wg_commit();
          if (kb != 6) c.turn_end();
          if (second) { wg_wait<1>(); c.release(2 + 3 * ((kb - 1) & 3), 3); }
          if (tile == 1 && kb == 3) { c.wait_stage_free(); stsm_frag<0, 4>(pv, stg); }
          if (tile == 1 && kb == 4) { stsm_frag<4, 8>(pv, stg); c.staged(); }
        }
        c.wait_stage_free();
        const bool nxt = c.try_full(2);
        wg_wait<0>();
        reg_fence(acc);
        c.release(11, 3);
        store_scaled(acc, SM_C, SM_C, stg, sb);
        c.staged();
        pack_frag<64>(acc, pv);
        if (!nxt) mbar_wait(sb + SM_BAR + (B_FULL + 2) * 8, (c.pf >> 2) & 1);
        c.pf ^= 4;
      }
      {
        float qa[64];
        float (&qb)[64] = O;
        {
          const uint32_t a = dk0 + 2 * DG, b = dm0 + 4 * DG;
          c.turn_begin();
          wg_fence();
          mma_ss_n128_init<1>(qa, a, b);
          mma_ss_n128_init<1>(qb, a + dsw, b);
#pragma unroll
          for (int k = 1; k < 4; k++) {
            mma_ss_n128<1>(qa, a + k * 2, b + k * 128);
            mma_ss_n128<1>(qb, a + dsw + k * 2, b + k * 128);
          }
          wg_commit();
        }
#pragma unroll 1
        for (int kb = 1; kb < 16; kb++) {
          const int g0 = 2 + 3 * (kb & 3);
          const uint32_t a = dk0 + g0 * DG, b = dm0 + (g0 + 2) * DG;
          const bool second = kb == 1 || kb == 15;
          if (!second) { wg_wait<0>(); c.release(2 + 3 * ((kb - 1) & 3), 3); }
          c.wait_full(g0);
          if (!second) c.turn_begin();
          wg_fence();
#pragma unroll
          for (int k = 0; k < 4; k++) {
            mma_ss_n128<1>(qa, a + k * 2, b + k * 128);
            mma_ss_n128<1>(qb, a + dsw + k * 2, b + k * 128);
          }
          wg_commit();
          if (kb != 14) c.turn_end();
          if (second) { wg_wait<1>(); c.release(2 + 3 * ((kb - 1) & 3), 3); }
          if (kb == QFLUSH) { c.wait_stage_free(); stsm_frag<0, 4>(pv, stg); }
          if (kb == QFLUSH + 1) { stsm_frag<4, 8>(pv, stg); c.staged(); }
        }
        c.wait_stage_free();
        const bool k0 = c.try_full(2);
        wg_wait<0>();
        reg_fence(qa); reg_fence(qb);
        c.release(11, 3);
        pack_frag<0>(qa, Q);
        if (c.wg == 0) {
          pack_frag<0>(qb, pv);
          stsm_frag(pv, stg);
        }
        if (!k0) c.wait_full(2); else c.pf ^= 4;
      }
      {
        const int nA = idx + 1;
        uint32_t (&P)[32] = pv;
        SoftState z;
        z.m0 = z.m1 = z.l0 = z.l1 = 0.f; z.shifted = c.zero;
#pragma unroll 1
        for (int seg = c.zero;; seg++) {
        if (c.wg == seg) attn_half(c, O, P, Q, nA == 1 && !seg, stg, z, dkk, dv0, dmask, seg);
        if (seg) break;
        int gk = c.wg ? 2 : 4, gv = c.wg ? 2 : 6;
        uint32_t dk = dkk + gk * DG;
#pragma unroll 1
        for (int it = 1 - c.wg; it < 17 - c.wg; it++) {
          float S[64];
          c.turn_begin();
          wg_fence();
          issue_qk(S, Q, dk);
          wg_commit();
          const uint32_t dv = dv0 + gv * DG;
          uint32_t relk = c.relb + gk * 8, relv = c.relb + gv * 8;
          gk = gv == 12 ? 2 : gv + (it == 6 || it == 9 ? 4 : 2);
          gv = it == 16 ? gk : gk == 12 ? 2 : gk + 2;
          uint32_t fk = sb + SM_BAR + (B_FULL + gk) * 8, fv = sb + SM_BAR + (B_FULL + gv) * 8, park = (c.pf >> gk) & 1, parv = (c.pf >> gv) & 1;
          c.pf ^= (1u << gk) | (1u << gv);
          dk = dkk + gk * DG;
          float lo0 = z.l0, lo1 = z.l1;
          const bool first = it == nA || it == 0;
          if (it == nA) {
            lo0 = rcp(quad_sum(lo0)); lo1 = rcp(quad_sum(lo1));
            z.m0 = z.m1 = z.l0 = z.l1 = 0.f; z.shifted = 0;
          }
          float s0, s1, d0 = z.m0, d1 = z.m1;
          int pre = z.shifted || (it & 15) == 0 || it + 1 == nA;
          float lim = first ? -1.f : SM_LIMIT;
          asm volatile("" : "+r"(relk), "+r"(relv), "+r"(fk), "+r"(fv), "+r"(park), "+r"(parv), "+r"(dk), "+r"(pre), "+f"(lim), "+f"(d0), "+f"(d1), "+f"(z.l0), "+f"(z.l1));
          if (it + c.wg > 1) {
            issue_pv<0>(O, P, dv, it != nA + 1 && it != 1, true);
            issue_pv<1>(O, P, dv, 1, true);
            c.turn_end();
          } else if (it) {
            issue_pv<0>(O, P, dv, 0, true);
            wg_commit(); wg_commit();
            c.turn_end();
            bar_sync(6, 256);
          } else stage_q2(c, O, P, stg);
          wg_wait<4>();
          reg_fence(S); reg_fence(Q);
          if (c.tid < 4) asm volatile("mbarrier.arrive.shared::cluster.b64 _, [%0];" ::"r"(relk) : "memory");
#pragma unroll 1
          for (int pass = 0;; pass++) {
            if (pre) {
              if (it + 1 == nA) load_q(Q, stg);
              if ((it & 15) == 0) mask_diag(S, dmask);
              if (z.shifted) shift_scores(S, d0, d1);
            }
            float tr[ROT];
            exp_quarter<0, 3>(S, P, tr, s0, s1, sb);
            exp_quarter<1, 2>(S, P, tr, s0, s1, sb);
            exp_quarter<2, 1>(S, P, tr, s0, s1, sb);
            exp_quarter<3, 0>(S, P, tr, s0, s1, sb);
            reg_fence(O);
            if (c.tid < (pass || !it ? 0 : 4)) asm volatile("mbarrier.arrive.shared::cluster.b64 _, [%0];" ::"r"(relv) : "memory");
            const bool ok = mbar_test(fk, park) & mbar_test(fv, parv);
            if (!ok) lim = -1.f;
            if (!__any_sync(0xffffffffu, !(s0 <= lim && s1 <= lim))) break;
            if (pass) break;
            if (it == nA) {
              store_scaled(O, lo0, lo1, stg, sb);
              c.staged();
            }
            if (!it) bar_arrive(6, 256);
            if (!ok) { mbar_wait(fk, park); mbar_wait(fv, parv); }
            if (!soft_unsafe(s0, s1, first)) break;
            soft_fix(S, O, z, first, d0, d1);
            pre = 1;
          }
          z.l0 += s0; z.l1 += s1;
        }
        if (!c.wg) bar_arrive(6, 256);
        }
        load_dd();
        c.turn_begin();
        wg_fence();
        issue_pv<0>(O, P, dv0 + 12 * DG, 1, true);
        issue_pv<1>(O, P, dv0 + 12 * DG, 1, !c.wg);
        c.turn_end();
        z.l0 = rcp(quad_sum(z.l0)); z.l1 = rcp(quad_sum(z.l1));
        c.wait_stage_free();
        if (rnd) c5 = get_ticket();
        wg_wait<0>();
        reg_fence(O); reg_fence(P);
        c.release(12, 2);
        store_scaled(O, z.l0, z.l1, stg, sb);
        c.staged();
      }
    }
    conv_tasks(c, p, (cn + 1 - c.wg) >> 1, spare, cch + c.wg * cstep, 2 * cstep, c5, dd0, dkk, warp & 3, lane);
    if (c.wg == 1) c.pf ^= 0x14;
    if (c.wg == (cn & 1)) c.turn_begin();
    if (!spare) {
      const int rt = grp + 8 * rank, ct = idx;
      float acc[64];
      int g0 = P3G + 2, pg = P3G;
      {
        c.wait_full(P3G);
        const uint32_t a = dk0 + P3G * DG, b = dm0 + (P3G + 1) * DG;
        wg_fence();
        mma_ss_n128_init<1>(acc, a, b);
#pragma unroll
        for (int k = 1; k < 4; k++) mma_ss_n128<1>(acc, a + k * 2, b + k * 128);
        wg_commit();
      }
#pragma unroll 1
      for (int kb = 1; kb < 64; kb++) {
        c.wait_full(g0);
        if (kb == STR && !c.wg) c.turn_begin();
        const uint32_t a = dk0 + g0 * DG, b = dm0 + (g0 + 1) * DG;
        wg_fence();
#pragma unroll
        for (int k = 0; k < 4; k++) mma_ss_n128<1>(acc, a + k * 2, b + k * 128);
        wg_commit();
        if (kb < STR) { wg_wait<1>(); c.release(pg, kb <= 59 ? 2 : 0); }
        pg = g0;
        g0 = g0 == (kb < XK ? 12 : kb < YK ? 10 : 8) ? (kb == 3 ? 2 : 0) : g0 + 2;
      }
      if (c.wg) c.turn_end();
      cluster_arrive();
      c.wait_full(P3X);
      c.wait_full(P3Y);
      const float g0f = __uint_as_float(lds32(sb + SM_GATE + row * 4)), g1f = __uint_as_float(lds32(sb + SM_GATE + row * 4 + 32));
      const uint32_t gp0 = pack_bf16(g0f, g0f), gp1 = pack_bf16(g1f, g1f);
      const float h0 = 1.f - g0f, h1 = 1.f - g1f;
      const int w = warp & 3;
      const uint32_t xa = stg + P3X * GR;
      const uint32_t ya = sb + P3Y * GR + c.wg * 16384 + ((lane >> 4) * 8 + (lane & 7)) * 128 + (((2 * w + ((lane >> 3) & 1)) ^ (lane & 7)) << 4);
      uint32_t xy[32];
      auto prep = [&](int j0, int j1) {
#pragma unroll
        for (int jj = j0; jj < j1; jj++) {
          uint32_t x[4], y[4];
          asm volatile("ldmatrix.sync.aligned.m8n8.x4.shared.b16 {%0,%1,%2,%3}, [%4];" : "=r"(x[0]), "=r"(x[1]), "=r"(x[2]), "=r"(x[3]) : "r"((xa ^ ((jj & 3) << 5)) + (jj >> 2) * 16384) : "memory");
          asm volatile("ldmatrix.sync.aligned.m8n8.x4.trans.shared.b16 {%0,%1,%2,%3}, [%4];" : "=r"(y[0]), "=r"(y[1]), "=r"(y[2]), "=r"(y[3]) : "r"(ya + jj * 2048) : "memory");
#pragma unroll
          for (int i = 0; i < 4; i++) xy[4 * jj + i] = hmul2(x[i], y[i]);
        }
      };
      prep(0, 4);
      wg_wait<0>();
      reg_fence(acc);
#pragma unroll
      for (int hf = 0; hf < 2; hf++) {
#pragma unroll
        for (int i = 16 * hf; i < 16 * hf + 16; i++) {
          const float h = (i & 1) ? h1 : h0;
          xy[i] = hfma2((i & 1) ? gp1 : gp0, xy[i], pack_bf16(acc[2 * i] * h, acc[2 * i + 1] * h));
        }
        if (hf) stsm_frag<4, 8>(xy, xa); else stsm_frag<0, 4>(xy, xa);
        fence_async_smem();
        __syncwarp();
        const int r0 = c.wg * 64 + w * 16;
        if (lane == 0) tma2d_store(&p.out, sb + (P3X + hf) * GR + r0 * 128, ct * 128 + hf * 64, rt * 128 + r0);
        if (!hf) prep(4, 8);
      }
      if (lane == 0) asm volatile("cp.async.bulk.commit_group;\ncp.async.bulk.wait_group.read 0;" ::: "memory");
    } else { cluster_arrive(); }
    if (lane == 0) mbar_arrive(sb + SM_BAR + B_DONE * 8);
    __syncwarp();
    cluster_wait();
  }
}

typedef CUresult (*EncFn)(CUtensorMap*, CUtensorMapDataType, cuuint32_t, void*, const cuuint64_t*, const cuuint64_t*, const cuuint32_t*,
                          const cuuint32_t*, CUtensorMapInterleave, CUtensorMapSwizzle, CUtensorMapL2promotion, CUtensorMapFloatOOBfill);

void enc2d(EncFn enc, CUtensorMap* tm, const void* base, uint64_t cols, uint64_t rows, uint32_t bc, uint32_t br) {
  cuuint64_t dims[2] = {cols, rows}; cuuint64_t strides[1] = {cols * 2}; cuuint32_t box[2] = {bc, br}; cuuint32_t es[2] = {1, 1};
  enc(tm, CU_TENSOR_MAP_DATA_TYPE_BFLOAT16, 2, const_cast<void*>(base), dims, strides, box, es, CU_TENSOR_MAP_INTERLEAVE_NONE,
      CU_TENSOR_MAP_SWIZZLE_128B, CU_TENSOR_MAP_L2_PROMOTION_L2_128B, CU_TENSOR_MAP_FLOAT_OOB_FILL_NONE);
}
void enc3d(EncFn enc, CUtensorMap* tm, const void* base, uint64_t K, uint64_t N, uint32_t bk = 64, uint64_t pitch = 0) {
  cuuint64_t dims[3] = {64, K, N / 64}; cuuint64_t strides[2] = {pitch ? pitch : N * 2, 128}; cuuint32_t box[3] = {64, bk, 2}; cuuint32_t es[3] = {1, 1, 1};
  enc(tm, CU_TENSOR_MAP_DATA_TYPE_BFLOAT16, 3, const_cast<void*>(base), dims, strides, box, es, CU_TENSOR_MAP_INTERLEAVE_NONE,
      CU_TENSOR_MAP_SWIZZLE_128B, CU_TENSOR_MAP_L2_PROMOTION_L2_128B, CU_TENSOR_MAP_FLOAT_OOB_FILL_NONE);
}

}

extern "C" void kernel_launch(void* const* d_in, const int* in_sizes, int n_in, void* d_out, int out_size) {
  (void)in_sizes; (void)n_in; (void)out_size;
  typedef const __nv_bfloat16* BP;
  BP xq = (BP)d_in[0], ak = (BP)d_in[1], av = (BP)d_in[2], shk = (BP)d_in[3], ssk = (BP)d_in[4], ssd = (BP)d_in[5];
  BP ckv = (BP)d_in[7], wq = (BP)d_in[8], wuk = (BP)d_in[9], wuv = (BP)d_in[10], wo = (BP)d_in[11], gw = (BP)d_in[12];

  static EncFn enc = nullptr;
  if (!enc) {
    cudaDriverEntryPointQueryResult qr;
    cudaGetDriverEntryPoint("cuTensorMapEncodeTiled", (void**)&enc, cudaEnableDefault, &qr);
    cudaFuncSetAttribute(mega_kernel, cudaFuncAttributeMaxDynamicSharedMemorySize, SMEM_BYTES);
  }
  Params p;
  enc2d(enc, &p.x, xq, DM, SEQ, 64, 128);
  enc2d(enc, &p.c, ckv, DC, SEQ, 64, 128);
  enc3d(enc, &p.wq, wq, DM, NH * HD);
  enc3d(enc, &p.wuk, wuk, DC, NH * HD);
  enc3d(enc, &p.wuv, wuv, DC, NH * HD);
  enc2d(enc, &p.wo, wo, DM, NH * HD, 64, 64);
  enc3d(enc, &p.x3, xq, SEQ, DM, 128);
  enc2d(enc, &p.out, d_out, DM, SEQ, 64, 16);
  {
    void* wp = nullptr;
    cudaGetSymbolAddress(&wp, g_w);
    enc3d(enc, &p.y3, (uint8_t*)wp + WZ, DM, SEQ, 128, WSTRIDE);
    cuuint64_t dims[3] = {WSTRIDE / 2, DM / 2, 2}; cuuint64_t strides[2] = {2 * WSTRIDE, WSTRIDE}; cuuint32_t box[3] = {16, 32, 2}; cuuint32_t es[3] = {1, 1, 1};
    enc(&p.w, CU_TENSOR_MAP_DATA_TYPE_BFLOAT16, 3, wp, dims, strides, box, es, CU_TENSOR_MAP_INTERLEAVE_NONE,
        CU_TENSOR_MAP_SWIZZLE_32B, CU_TENSOR_MAP_L2_PROMOTION_NONE, CU_TENSOR_MAP_FLOAT_OOB_FILL_NONE);
  }
  p.zero = 0;
  cudaGetSymbolAddress((void**)&p.flags, g_flags);
  for (int i = 0; i < 128; i++) {
    const int tp = i % NSLOT;
    p.pref[i] = tp < 32 ? (tp & 7) * 8 + (tp >> 3) : tp < 60 ? (1 + (tp - 32) % 7) * 8 + 4 + (tp - 32) / 7 : tp < 62 ? tp + 4 : tp - 58;
  }
  p.gate_w = gw; p.ak = ak; p.av = av; p.shk = shk; p.ssk = ssk; p.ssd = ssd; p.wukp = wuk; p.wuvp = wuv;

  mega_kernel<<<132, NTHREADS, SMEM_BYTES>>>(p);
}
```

```cpp
#include <cuda_runtime.h>
#include <cuda.h>
#include <cuda_bf16.h>
#include <stdint.h>

namespace {

constexpr int SEQ = 2048, DM = 1024, DC = 512, NH = 32, HD = 128;
constexpr int GR = 16384;
constexpr int NGR = 14;
constexpr int SM_BAR = NGR * GR;
constexpr int SM_GATE = SM_BAR + 512;
constexpr int SM_UST = SM_GATE + 512;
constexpr int SMEM_BYTES = SM_UST + 2048;
constexpr int NTHREADS = 384;
constexpr float SM_LIMIT = 1.0995116e12f;
constexpr float SM_LOW = 9.094947e-13f;
constexpr int CNS = 112;
constexpr int CN_SPARE = CNS, NTICK = 256 - 2 * CN_SPARE;
constexpr int XK = 57, YK = 62;
constexpr int STR = 61;
constexpr int P3G = 6, P3X = 12, P3Y = 10;
constexpr int NMAIN = 128;

constexpr int B_FULL = 0, B_FREE = 14, B_SLOT = 16, B_DONE = 17, B_EMPTY = 18, B_EV = 32, B_TICK = 36;
constexpr int V_SLOT = 37, V_TICK = 38;

__device__ __align__(1024) uint8_t g_kv[2 * 16 * 16 * 32768];
__device__ __align__(1024) uint8_t g_cimg[16 * NH * 32768];
__device__ __align__(1024) float g_gate[SEQ];
constexpr int WZ = 256, WPL = WZ + 4096, WBYTES = 2 * WPL + 32, WSTRIDE = 2 * WPL + 128;
__device__ __align__(1024) uint8_t g_w[DM * WSTRIDE];
__device__ __align__(32) unsigned g_flags[96 * 8];
constexpr int F_KV = 0, F_CTX = 16, F_U = 48, F_AD = 56, F_Y = 64, F_GATE = 72, F_EXIT = 73, F_TICK = 74;
constexpr int NSLOT = 66;
#define FLAG(i) (&g_flags[(i) * 8])
#define CLAIMP(i) (p.flags + (i) * 8 + 1)

constexpr int QFLUSH = 3;
constexpr int PSL = 200;
constexpr int US0 = 900;
constexpr int EROT = 6;
constexpr int RST = 2;
constexpr int UP0 = 4;
constexpr int UP1 = 11;
constexpr int X_DELAY = 900;
constexpr int X_D2 = 500;
constexpr int ROT = 8;
#define KV_ROW(idx, t) (8 * (t) + 2 * ((idx) & 3))
#define KV_HEAD(idx, t) ((idx) >> 2)

__device__ __forceinline__ uint32_t smem_u32(const void* p) { return (uint32_t)__cvta_generic_to_shared(p); }
__device__ __forceinline__ void mbar_init(uint32_t bar, int cnt) { asm volatile("mbarrier.init.shared::cta.b64 [%0], %1;" ::"r"(bar), "r"(cnt) : "memory"); }
__device__ __forceinline__ void mbar_expect_tx(uint32_t bar, uint32_t bytes) { asm volatile("mbarrier.arrive.expect_tx.shared::cta.b64 _, [%0], %1;" ::"r"(bar), "r"(bytes) : "memory"); }
__device__ __forceinline__ void mbar_arrive(uint32_t bar) { asm volatile("mbarrier.arrive.shared::cta.b64 _, [%0];" ::"r"(bar) : "memory"); }
__device__ __forceinline__ void mbar_arrive_cluster(uint32_t bar, uint32_t cta) {
  asm volatile("{\n.reg .b32 r;\nmapa.shared::cluster.u32 r, %0, %1;\nmbarrier.arrive.shared::cluster.b64 _, [r];\n}\n" ::"r"(bar), "r"(cta) : "memory");
}
__device__ __forceinline__ void send_both(uint32_t bar, uint32_t off, uint32_t v) {
#pragma unroll
  for (int r = 0; r < 2; r++)
    asm volatile("{\n.reg .b32 a, b;\nmapa.shared::cluster.u32 a, %0, %1;\nadd.u32 b, a, %3;\nst.async.shared::cluster.mbarrier::complete_tx::bytes.u32 [b], %2, [a];\n}\n"
                 ::"r"(bar), "r"(r), "r"(v), "r"(off) : "memory");
}
__device__ __forceinline__ bool mbar_try(uint32_t bar, uint32_t parity) {
  uint32_t ok;
  asm volatile("{\n.reg .pred p;\nmbarrier.try_wait.parity.shared::cta.b64 p, [%1], %2, 20000;\nselp.u32 %0, 1, 0, p;\n}\n" : "=r"(ok) : "r"(bar), "r"(parity) : "memory");
  return ok;
}
__device__ __forceinline__ bool mbar_test(uint32_t bar, uint32_t parity) {
  uint32_t ok;
  asm volatile("{\n.reg .pred p;\nmbarrier.test_wait.parity.shared::cta.b64 p, [%1], %2;\nselp.u32 %0, 1, 0, p;\n}\n" : "=r"(ok) : "r"(bar), "r"(parity) : "memory");
  return ok;
}
__device__ __forceinline__ void mbar_wait(uint32_t bar, uint32_t parity) {
  asm volatile("{\n.reg .pred p;\nWAIT_LOOP:\nbar.warp.sync -1;\nmbarrier.try_wait.parity.shared::cta.b64 p, [%0], %1;\n@!p bra WAIT_LOOP;\n}\n" ::"r"(bar), "r"(parity) : "memory");
}
__device__ __forceinline__ void mbar_wait1(uint32_t bar, uint32_t parity) {
  asm volatile("{\n.reg .pred p;\nWAIT_LOOP:\nbar.warp.sync -1;\nmbarrier.try_wait.parity.shared::cta.b64 p, [%0], %1, 4000;\n@!p bra WAIT_LOOP;\n}\n" ::"r"(bar), "r"(parity) : "memory");
}
constexpr uint64_t EV_NORMAL = 0x1000000000000000ull, EV_FIRST = 0x12F0000000000000ull;
__device__ __forceinline__ uint32_t ldg_stream(const uint32_t* p) {
  uint32_t r; asm volatile("ld.global.nc.L1::no_allocate.L2::cache_hint.b32 %0, [%1], %2;" : "=r"(r) : "l"(p), "l"(EV_FIRST)); return r;
}
#define TMA_LD "cp.async.bulk.tensor."
#define TMA_MB ".shared::cluster.global.mbarrier::complete_tx::bytes"
__device__ __forceinline__ void tma2d(uint32_t dst, const CUtensorMap* tm, int c0, int c1, uint32_t bar) {
  asm volatile(TMA_LD "2d" TMA_MB " [%0], [%1, {%3, %4}], [%2];" ::"r"(dst), "l"(tm), "r"(bar), "r"(c0), "r"(c1) : "memory");
}
template <bool ONCE = false> __device__ __forceinline__ void tma2d_mc(uint32_t dst, const CUtensorMap* tm, int c0, int c1, uint32_t bar) {
  if (ONCE) asm volatile(TMA_LD "2d" TMA_MB ".multicast::cluster.L2::cache_hint [%0], [%1, {%3, %4}], [%2], %5, %6;"
                         ::"r"(dst), "l"(tm), "r"(bar), "r"(c0), "r"(c1), "h"((uint16_t)3), "l"(EV_FIRST) : "memory");
  else asm volatile(TMA_LD "2d" TMA_MB ".multicast::cluster [%0], [%1, {%3, %4}], [%2], %5;"
                    ::"r"(dst), "l"(tm), "r"(bar), "r"(c0), "r"(c1), "h"((uint16_t)3) : "memory");
}
__device__ __forceinline__ void tma2d_p(uint32_t dst, const CUtensorMap* tm, int c0, int c1, uint32_t bar, bool once) {
  asm volatile(TMA_LD "2d" TMA_MB ".L2::cache_hint [%0], [%1, {%3, %4}], [%2], %5;" ::"r"(dst), "l"(tm), "r"(bar), "r"(c0), "r"(c1), "l"(once ? EV_FIRST : EV_NORMAL) : "memory");
}
__device__ __forceinline__ void tma3d_mc_p(uint32_t dst, const CUtensorMap* tm, int c0, int c1, int c2, uint32_t bar, bool once) {
  asm volatile(TMA_LD "3d" TMA_MB ".multicast::cluster.L2::cache_hint [%0], [%1, {%3, %4, %5}], [%2], %6, %7;"
               ::"r"(dst), "l"(tm), "r"(bar), "r"(c0), "r"(c1), "r"(c2), "h"((uint16_t)3), "l"(once ? EV_FIRST : EV_NORMAL) : "memory");
}
template <bool ONCE = false> __device__ __forceinline__ void tma3d(uint32_t dst, const CUtensorMap* tm, int c0, int c1, int c2, uint32_t bar) {
  if (ONCE) asm volatile(TMA_LD "3d" TMA_MB ".L2::cache_hint [%0], [%1, {%3, %4, %5}], [%2], %6;" ::"r"(dst), "l"(tm), "r"(bar), "r"(c0), "r"(c1), "r"(c2), "l"(EV_FIRST) : "memory");
  else
  asm volatile(TMA_LD "3d" TMA_MB " [%0], [%1, {%3, %4, %5}], [%2];" ::"r"(dst), "l"(tm), "r"(bar), "r"(c0), "r"(c1), "r"(c2) : "memory");
}
__device__ __forceinline__ void tma3d_mc(uint32_t dst, const CUtensorMap* tm, int c0, int c1, int c2, uint32_t bar) {
  asm volatile(TMA_LD "3d" TMA_MB ".multicast::cluster [%0], [%1, {%3, %4, %5}], [%2], %6;"
               ::"r"(dst), "l"(tm), "r"(bar), "r"(c0), "r"(c1), "r"(c2), "h"((uint16_t)3) : "memory");
}
template <bool ONCE = false> __device__ __forceinline__ void bulk_g2s(uint32_t dst, const void* src, uint32_t bytes, uint32_t bar) {
  if (ONCE) asm volatile("cp.async.bulk" TMA_MB ".L2::cache_hint [%0], [%1], %2, [%3], %4;" ::"r"(dst), "l"(src), "r"(bytes), "r"(bar), "l"(EV_FIRST) : "memory");
  else asm volatile("cp.async.bulk" TMA_MB " [%0], [%1], %2, [%3];" ::"r"(dst), "l"(src), "r"(bytes), "r"(bar) : "memory");
}
__device__ __forceinline__ void tma2d_store(const CUtensorMap* tm, uint32_t src, int c0, int c1) {
  asm volatile("cp.async.bulk.tensor.2d.global.shared::cta.bulk_group [%0, {%2, %3}], [%1];" ::"l"(tm), "r"(src), "r"(c0), "r"(c1) : "memory");
}
__device__ __forceinline__ void prefetch_tm(const CUtensorMap* tm) { asm volatile("prefetch.tensormap [%0];" ::"l"(tm) : "memory"); }
__device__ __forceinline__ void wg_fence() { asm volatile("wgmma.fence.sync.aligned;" ::: "memory"); }
__device__ __forceinline__ void wg_commit() { asm volatile("wgmma.commit_group.sync.aligned;" ::: "memory"); }
template <int N> __device__ __forceinline__ void wg_wait() { asm volatile("wgmma.wait_group.sync.aligned %0;" ::"n"(N) : "memory"); }
__device__ __forceinline__ void bar_sync(int id, int n) { asm volatile("bar.sync %0, %1;" ::"r"(id), "r"(n) : "memory"); }
__device__ __forceinline__ void bar_arrive(int id, int n) { asm volatile("bar.arrive %0, %1;" ::"r"(id), "r"(n) : "memory"); }
__device__ __forceinline__ void fence_async_smem() { asm volatile("fence.proxy.async.shared::cta;" ::: "memory"); }
__device__ __forceinline__ void fence_async_all() { asm volatile("fence.proxy.async.global;" ::: "memory"); }
__device__ __forceinline__ uint32_t pack_bf16(float lo, float hi) { uint32_t r; asm("cvt.rn.bf16x2.f32 %0, %1, %2;" : "=r"(r) : "f"(hi), "f"(lo)); return r; }
__device__ __forceinline__ float ex2(float x) { float r; asm("ex2.approx.ftz.f32 %0, %1;" : "=f"(r) : "f"(x)); return r; }
__device__ __forceinline__ float rcp(float x) { float r; asm("rcp.approx.ftz.f32 %0, %1;" : "=f"(r) : "f"(x)); return r; }
__device__ __forceinline__ void flag_wait(const unsigned* f, unsigned target) {
  unsigned v;
  do { asm volatile("ld.acquire.gpu.global.u32 %0, [%1];" : "=r"(v) : "l"(f) : "memory"); } while (__any_sync(0xffffffffu, v < target));
}
__device__ __forceinline__ bool elect() {
  uint32_t r;
  asm volatile("{\n.reg .pred p;\nelect.sync _|p, -1;\nselp.u32 %0, 1, 0, p;\n}\n" : "=r"(r));
  return r;
}
__device__ __forceinline__ void fence_release() { asm volatile("fence.release.gpu;" ::: "memory"); }
__device__ __forceinline__ void flag_add(unsigned* f) { asm volatile("red.relaxed.gpu.global.inc.u32 [%0], 0x7fffffff;" ::"l"(f) : "memory"); }
__device__ __forceinline__ void cluster_arrive() { asm volatile("barrier.cluster.arrive.relaxed.aligned;" ::: "memory"); }
__device__ __forceinline__ void cluster_wait() { asm volatile("barrier.cluster.wait.aligned;" ::: "memory"); }
__device__ __forceinline__ uint32_t hmul2(uint32_t a, uint32_t b) { uint32_t r; asm("mul.rn.bf16x2 %0, %1, %2;" : "=r"(r) : "r"(a), "r"(b)); return r; }
__device__ __forceinline__ uint32_t hadd2(uint32_t a, uint32_t b) { uint32_t r; asm("add.rn.bf16x2 %0, %1, %2;" : "=r"(r) : "r"(a), "r"(b)); return r; }
__device__ __forceinline__ uint32_t hfma2(uint32_t a, uint32_t b, uint32_t c) { uint32_t r; asm("fma.rn.bf16x2 %0, %1, %2, %3;" : "=r"(r) : "r"(a), "r"(b), "r"(c)); return r; }
__device__ __forceinline__ uint32_t lds32(uint32_t a) { uint32_t r; asm volatile("ld.shared.b32 %0, [%1];" : "=r"(r) : "r"(a) : "memory"); return r; }
__device__ __forceinline__ uint4 lds128(uint32_t a) { uint4 r; asm volatile("ld.shared.v4.b32 {%0,%1,%2,%3}, [%4];" : "=r"(r.x), "=r"(r.y), "=r"(r.z), "=r"(r.w) : "r"(a) : "memory"); return r; }
__device__ __forceinline__ uint32_t desc_k(uint32_t addr) { return ((addr & 0x3FFFF) >> 4) | (1u << 16); }
template <int LBO> __device__ __forceinline__ uint32_t desc_mn(uint32_t addr) { return ((addr & 0x3FFFF) >> 4) | ((uint32_t)(LBO >> 4) << 16); }
#define DHI "0x40000040"

#define R8(d, o) "+f"(d[o]), "+f"(d[o + 1]), "+f"(d[o + 2]), "+f"(d[o + 3]), "+f"(d[o + 4]), "+f"(d[o + 5]), "+f"(d[o + 6]), "+f"(d[o + 7])
#define R32(d, o) R8(d, o), R8(d, o + 8), R8(d, o + 16), R8(d, o + 24)
#define R64(d, o) R32(d, o), R32(d, o + 32)
#define L64 "%0,%1,%2,%3,%4,%5,%6,%7,%8,%9,%10,%11,%12,%13,%14,%15,%16,%17,%18,%19,%20,%21,%22,%23,%24,%25,%26,%27,%28,%29,%30,%31," \
            "%32,%33,%34,%35,%36,%37,%38,%39,%40,%41,%42,%43,%44,%45,%46,%47,%48,%49,%50,%51,%52,%53,%54,%55,%56,%57,%58,%59,%60,%61,%62,%63"
#define L128 L64 ",%64,%65,%66,%67,%68,%69,%70,%71,%72,%73,%74,%75,%76,%77,%78,%79,%80,%81,%82,%83,%84,%85,%86,%87,%88,%89,%90,%91,%92,%93,%94,%95," \
            "%96,%97,%98,%99,%100,%101,%102,%103,%104,%105,%106,%107,%108,%109,%110,%111,%112,%113,%114,%115,%116,%117,%118,%119,%120,%121,%122,%123,%124,%125,%126,%127"

template <int TB> __device__ __forceinline__ void mma_ss_n128(float (&d)[64], uint32_t da, uint32_t db) {
  asm volatile("{\n.reg .b64 da, db;\nmov.b64 da, {%64, " DHI "};\nmov.b64 db, {%65, " DHI "};\n"
               "wgmma.mma_async.sync.aligned.m64n128k16.f32.bf16.bf16 {" L64 "}, da, db, 1, 1, 1, 0, %66;\n}\n"
               : R64(d, 0) : "r"(da), "r"(db), "n"(TB));
}
template <int TB> __device__ __forceinline__ void mma_rs_n128(float (&d)[64], uint32_t a0, uint32_t a1, uint32_t a2, uint32_t a3, uint32_t db, int sd) {
  asm volatile("{\n.reg .pred p;\n.reg .b64 db;\nsetp.ne.b32 p, %69, 0;\nmov.b64 db, {%68, " DHI "};\n"
               "wgmma.mma_async.sync.aligned.m64n128k16.f32.bf16.bf16 {" L64 "}, {%64,%65,%66,%67}, db, p, 1, 1, %70;\n}\n"
               : R64(d, 0) : "r"(a0), "r"(a1), "r"(a2), "r"(a3), "r"(db), "r"(sd), "n"(TB));
}
template <int TB> __device__ __forceinline__ void mma_ss_n256(float (&d)[128], uint32_t da, uint32_t db) {
  asm volatile("{\n.reg .b64 da, db;\nmov.b64 da, {%128, " DHI "};\nmov.b64 db, {%129, " DHI "};\n"
               "wgmma.mma_async.sync.aligned.m64n256k16.f32.bf16.bf16 {" L128 "}, da, db, 1, 1, 1, 0, %130;\n}\n"
               : R64(d, 0), R64(d, 64) : "r"(da), "r"(db), "n"(TB));
}
#define W8(d, o) "=f"(d[o]), "=f"(d[o + 1]), "=f"(d[o + 2]), "=f"(d[o + 3]), "=f"(d[o + 4]), "=f"(d[o + 5]), "=f"(d[o + 6]), "=f"(d[o + 7])
#define W32(d, o) W8(d, o), W8(d, o + 8), W8(d, o + 16), W8(d, o + 24)
#define W64(d, o) W32(d, o), W32(d, o + 32)
template <int TB> __device__ __forceinline__ void mma_ss_n128_init(float (&d)[64], uint32_t da, uint32_t db) {
  asm volatile("{\n.reg .b64 da, db;\nmov.b64 da, {%64, " DHI "};\nmov.b64 db, {%65, " DHI "};\n"
               "wgmma.mma_async.sync.aligned.m64n128k16.f32.bf16.bf16 {" L64 "}, da, db, 0, 1, 1, 0, %66;\n}\n"
               : W64(d, 0) : "r"(da), "r"(db), "n"(TB));
}
template <int TB> __device__ __forceinline__ void mma_rs_n128_init(float (&d)[64], uint32_t a0, uint32_t a1, uint32_t a2, uint32_t a3, uint32_t db) {
  asm volatile("{\n.reg .b64 db;\nmov.b64 db, {%68, " DHI "};\n"
               "wgmma.mma_async.sync.aligned.m64n128k16.f32.bf16.bf16 {" L64 "}, {%64,%65,%66,%67}, db, 0, 1, 1, %69;\n}\n"
               : W64(d, 0) : "r"(a0), "r"(a1), "r"(a2), "r"(a3), "r"(db), "n"(TB));
}
template <int TB> __device__ __forceinline__ void mma_ss_n256_init(float (&d)[128], uint32_t da, uint32_t db) {
  asm volatile("{\n.reg .b64 da, db;\nmov.b64 da, {%128, " DHI "};\nmov.b64 db, {%129, " DHI "};\n"
               "wgmma.mma_async.sync.aligned.m64n256k16.f32.bf16.bf16 {" L128 "}, da, db, 0, 1, 1, 0, %130;\n}\n"
               : W64(d, 0), W64(d, 64) : "r"(da), "r"(db), "n"(TB));
}
#define L32 "%0,%1,%2,%3,%4,%5,%6,%7,%8,%9,%10,%11,%12,%13,%14,%15,%16,%17,%18,%19,%20,%21,%22,%23,%24,%25,%26,%27,%28,%29,%30,%31"
template <bool INIT> __device__ __forceinline__ void mma_rs_n64(float (&d)[32], uint32_t a0, uint32_t a1, uint32_t a2, uint32_t a3, uint32_t db) {
  if (INIT) asm volatile("{\n.reg .b64 db;\nmov.b64 db, {%36, " DHI "};\n"
               "wgmma.mma_async.sync.aligned.m64n64k16.f32.bf16.bf16 {" L32 "}, {%32,%33,%34,%35}, db, 0, 1, 1, 0;\n}\n"
               : W32(d, 0) : "r"(a0), "r"(a1), "r"(a2), "r"(a3), "r"(db));
  else asm volatile("{\n.reg .b64 db;\nmov.b64 db, {%36, " DHI "};\n"
               "wgmma.mma_async.sync.aligned.m64n64k16.f32.bf16.bf16 {" L32 "}, {%32,%33,%34,%35}, db, 1, 1, 1, 0;\n}\n"
               : R32(d, 0) : "r"(a0), "r"(a1), "r"(a2), "r"(a3), "r"(db));
}
#define L16 "%0,%1,%2,%3,%4,%5,%6,%7,%8,%9,%10,%11,%12,%13,%14,%15"
template <int O, bool INIT> __device__ __forceinline__ void mma_rs_n32(float (&d)[128], uint32_t a0, uint32_t a1, uint32_t a2, uint32_t a3, uint32_t db) {
  if (INIT) asm volatile("{\n.reg .b64 db;\nmov.b64 db, {%20, 0x00000008};\n"
               "wgmma.mma_async.sync.aligned.m64n32k16.f32.bf16.bf16 {" L16 "}, {%16,%17,%18,%19}, db, 0, 1, 1, 0;\n}\n"
               : W8(d, O), W8(d, O + 8) : "r"(a0), "r"(a1), "r"(a2), "r"(a3), "r"(db));
  else asm volatile("{\n.reg .b64 db;\nmov.b64 db, {%20, 0x00000008};\n"
               "wgmma.mma_async.sync.aligned.m64n32k16.f32.bf16.bf16 {" L16 "}, {%16,%17,%18,%19}, db, 1, 1, 1, 0;\n}\n"
               : R8(d, O), R8(d, O + 8) : "r"(a0), "r"(a1), "r"(a2), "r"(a3), "r"(db));
}
template <int S, int J> __device__ __forceinline__ void conv_step(float (&d)[128], const uint32_t (&a)[64], uint32_t db) {
  if constexpr (J >= 0 && J >= (S >> 1)) {
    mma_rs_n32<16 * J, S == 0>(d, a[4 * S], a[4 * S + 1], a[4 * S + 2], a[4 * S + 3], db + (uint32_t)((2 * J - S) * 16));
    conv_step<S, J - 1>(d, a, db);
  }
}
__device__ __forceinline__ void mma_ss_n8(float (&d)[4], uint32_t da, uint32_t db) {
  asm volatile("{\n.reg .b64 da, db;\nmov.b64 da, {%4, " DHI "};\nmov.b64 db, {%5, 0x00000008};\n"
               "wgmma.mma_async.sync.aligned.m64n8k16.f32.bf16.bf16 {%0,%1,%2,%3}, da, db, 1, 1, 1, 0, 0;\n}\n"
               : "+f"(d[0]), "+f"(d[1]), "+f"(d[2]), "+f"(d[3]) : "r"(da), "r"(db));
}
template <int N> __device__ __forceinline__ void reg_fence(float (&d)[N]) {
#pragma unroll
  for (int i = 0; i < N; i++) asm volatile("" : "+f"(d[i])::"memory");
}
template <int N> __device__ __forceinline__ void reg_fence(uint32_t (&d)[N]) {
#pragma unroll
  for (int i = 0; i < N; i++) asm volatile("" : "+r"(d[i])::"memory");
}

struct __align__(64) Params {
  unsigned* flags;
  int zero;
  uint8_t pref[128];
  const __nv_bfloat16 *gate_w, *ak, *av, *shk, *ssk, *ssd, *wukp, *wuvp;
  CUtensorMap x, c, wq, wuk, wuv, wo, x3, y3, out, w;
};

template <int O, int N, int M> __device__ __forceinline__ void pack_frag(const float (&acc)[N], uint32_t (&pk)[M]) {
#pragma unroll
  for (int i = 0; i < 32; i++) pk[i] = pack_bf16(acc[O + 2 * i], acc[O + 2 * i + 1]);
}
template <int J0 = 0, int J1 = 8, int M> __device__ __forceinline__ void stsm_frag(const uint32_t (&pk)[M], uint32_t a) {
#pragma unroll
  for (int jj = J0; jj < J1; jj++)
    asm volatile("stmatrix.sync.aligned.m8n8.x4.shared.b16 [%0], {%1,%2,%3,%4};" ::"r"((a ^ ((jj & 3) << 5)) + (jj >> 2) * 16384),
                 "r"(pk[4 * jj]), "r"(pk[4 * jj + 1]), "r"(pk[4 * jj + 2]), "r"(pk[4 * jj + 3]) : "memory");
}

template <int N> __device__ __forceinline__ void store_scaled(const float (&acc)[N], float s0, float s1, uint32_t a, uint32_t never_zero) {
  float t[8];
#pragma unroll
  for (int jj = 0; jj < 8; jj++) {
    float v = acc[8 * jj] * s0;
    if (jj >= RST) {
      v = t[jj - RST];
      asm("{\n.reg .pred p;\nsetp.ne.u32 p, %3, 0;\n@p mul.f32 %0, %1, %2;\n}\n" : "+f"(v) : "f"(acc[8 * jj]), "f"(s0), "r"(never_zero));
    }
    const uint32_t q = pack_bf16(v, acc[8 * jj + 1] * s0);
    t[jj] = __uint_as_float(q);
    asm volatile("stmatrix.sync.aligned.m8n8.x4.shared.b16 [%0], {%1,%2,%3,%4};" ::"r"((a ^ ((jj & 3) << 5)) + (jj >> 2) * 16384), "r"(q),
                 "r"(pack_bf16(acc[8 * jj + 2] * s1, acc[8 * jj + 3] * s1)), "r"(pack_bf16(acc[8 * jj + 4] * s0, acc[8 * jj + 5] * s0)),
                 "r"(pack_bf16(acc[8 * jj + 6] * s1, acc[8 * jj + 7] * s1)) : "memory");
  }
}

struct Cons {
  uint32_t sb;
  uint32_t pf;
  int wg, tid;
  __device__ __forceinline__ void wait_full(int g) { mbar_wait(sb + SM_BAR + (B_FULL + g) * 8, (pf >> g) & 1); pf ^= 1u << g; }
  uint32_t relb;
  __device__ __forceinline__ void release(int g, int n) {
    if (tid < 2 * n) asm volatile("mbarrier.arrive.shared::cluster.b64 _, [%0];" ::"r"(relb + g * 8) : "memory");
  }
  __device__ __forceinline__ void turn_begin() { bar_sync(1 + wg, 256); }
  __device__ __forceinline__ void turn_end() { bar_arrive(2 - wg, 256); }
  __device__ __forceinline__ void staged() { __syncwarp(); if ((tid & 31) == 0) mbar_arrive(sb + SM_BAR + (B_EV + wg) * 8); }
  int zero;
  uint32_t pfree;
  __device__ __forceinline__ void wait_stage_free() { mbar_wait(sb + SM_BAR + (B_FREE + wg) * 8, pfree); pfree ^= 1; }
  __device__ __forceinline__ bool try_full(int g) { return mbar_test(sb + SM_BAR + (B_FULL + g) * 8, (pf >> g) & 1); }
};

constexpr float SM_C = 0.08838834764831845f * 1.4426950408889634f;
struct SoftState { float m0, m1, l0, l1; int shifted; };
__device__ __forceinline__ void ex2_rot(float& t, float s, uint32_t never_zero) {
  asm("{\n.reg .pred p;\nsetp.ne.u32 p, %2, 0;\n@p ex2.approx.ftz.f32 %0, %1;\n}\n" : "+f"(t) : "f"(s), "r"(never_zero));
}
__device__ __forceinline__ void pin(float a, uint32_t never_zero) {
  asm volatile("{\n.reg .pred p;\nsetp.eq.u32 p, %1, 0;\n@p st.shared.f32 [%1], %0;\n}\n" ::"f"(a), "r"(never_zero) : "memory");
}
template <int O, int N> __device__ __forceinline__ void reg_fence_part(uint32_t (&d)[32]) {
#pragma unroll
  for (int i = O; i < O + N; i++) asm volatile("" : "+r"(d[i])::"memory");
}
template <int Q, int W, int N> __device__ __forceinline__ void exp_quarter(const float (&S)[N], uint32_t (&P)[32], float (&t)[ROT], float& s0, float& s1, uint32_t nz) {
#pragma unroll
  for (int i = 8 * Q; i < 8 * Q + 8; i++) {
    float& a = t[(2 * i) % ROT];
    float& b = t[(2 * i + 1) % ROT];
    if (2 * i < ROT) { a = ex2(S[2 * i]); b = ex2(S[2 * i + 1]); }
    else { ex2_rot(a, S[2 * i], nz); ex2_rot(b, S[2 * i + 1], nz); }
    if (i < 2) { if (i) s1 = a + b; else s0 = a + b; }
    else if (i & 1) { s1 += a; s1 += b; } else { s0 += a; s0 += b; }
    if (i == 8 * Q) { pin(Q ? s1 : s0, nz); wg_wait<W>(); reg_fence_part<8 * Q, 8>(P); }
    P[i] = pack_bf16(a, b);
  }
}
template <int N> __device__ __forceinline__ void shift_scores(float (&S)[N], float d0, float d1) {
#pragma unroll
  for (int i = 0; i < N; i++) S[i] -= (i & 2) ? d1 : d0;
}
__device__ __forceinline__ bool soft_high(float s0, float s1, float lim = SM_LIMIT) { return s0 > lim || s1 > lim; }
__device__ __forceinline__ bool soft_unsafe(float s0, float s1, bool first) {
  uint32_t b0 = __ballot_sync(0xffffffffu, s0 >= SM_LOW), b1 = __ballot_sync(0xffffffffu, s1 >= SM_LOW);
  b0 |= b0 >> 1; b0 |= b0 >> 2; b1 |= b1 >> 1; b1 |= b1 >> 2;
  return __any_sync(0xffffffffu, soft_high(s0, s1)) || (first && (b0 & b1 & 0x11111111u) != 0x11111111u);
}
template <int N> __device__ __forceinline__ void soft_fix(const float (&S)[N], float (&O)[64], SoftState& z, bool first, float& d0, float& d1) {
  d0 = d1 = first ? -INFINITY : 0.f;
#pragma unroll
  for (int j = 0; j < N / 4; j++) { d0 = fmaxf(d0, fmaxf(S[4 * j], S[4 * j + 1])); d1 = fmaxf(d1, fmaxf(S[4 * j + 2], S[4 * j + 3])); }
  d0 = fmaxf(d0, __shfl_xor_sync(0xffffffffu, d0, 1)); d1 = fmaxf(d1, __shfl_xor_sync(0xffffffffu, d1, 1));
  d0 = fmaxf(d0, __shfl_xor_sync(0xffffffffu, d0, 2)); d1 = fmaxf(d1, __shfl_xor_sync(0xffffffffu, d1, 2));
  const float sc0 = ex2(-fmaxf(d0, 0.f)), sc1 = ex2(-fmaxf(d1, 0.f));
  z.m0 += d0; z.m1 += d1; z.l0 *= sc0; z.l1 *= sc1; z.shifted = 1;
#pragma unroll
  for (int j = 0; j < 16; j++) { O[4 * j] *= sc0; O[4 * j + 1] *= sc0; O[4 * j + 2] *= sc1; O[4 * j + 3] *= sc1; }
}
template <int N> __device__ __forceinline__ void mask_diag(float (&S)[N], float nd) {
  asm volatile("" : "+f"(nd));
#pragma unroll
  for (int i = 0; i < 32; i++) {
    const float beyond = __saturatef(nd + (float)(8 * (i >> 2) + (i & 1) - 4 * (i & 2)));
    S[N - 32 + i] = fmaf(beyond, -3.0e38f, S[N - 32 + i]);
  }
}
__device__ __forceinline__ float quad_sum(float v) {
  v += __shfl_xor_sync(0xffffffffu, v, 1);
  v += __shfl_xor_sync(0xffffffffu, v, 2);
  return v;
}
__device__ __forceinline__ void issue_qk(float (&S)[64], const uint32_t (&Q)[32], uint32_t dk) {
  mma_rs_n128_init<0>(S, Q[0], Q[1], Q[2], Q[3], dk);
#pragma unroll
  for (int s = 1; s < 8; s++) mma_rs_n128<0>(S, Q[4 * s], Q[4 * s + 1], Q[4 * s + 2], Q[4 * s + 3], dk + (s >> 2) * 1024 + (s & 3) * 2, 1);
}
__device__ __forceinline__ void issue_qk(float (&S)[32], const uint32_t (&Q)[32], uint32_t dk) {
  mma_rs_n64<true>(S, Q[0], Q[1], Q[2], Q[3], dk);
#pragma unroll
  for (int s = 1; s < 8; s++) mma_rs_n64<false>(S, Q[4 * s], Q[4 * s + 1], Q[4 * s + 2], Q[4 * s + 3], dk + (s >> 2) * 1024 + (s & 3) * 2);
}
__device__ __forceinline__ void load_q(uint32_t (&Q)[32], uint32_t a) {
  __syncwarp();
#pragma unroll
  for (int jj = 0; jj < 8; jj++)
    asm volatile("ldmatrix.sync.aligned.m8n8.x4.shared.b16 {%0,%1,%2,%3}, [%4];" : "=r"(Q[4 * jj]), "=r"(Q[4 * jj + 1]), "=r"(Q[4 * jj + 2]), "=r"(Q[4 * jj + 3])
                 : "r"((a ^ ((jj & 3) << 5)) + (jj >> 2) * 16384) : "memory");
}
template <int H> __device__ __forceinline__ void issue_pv(float (&O)[64], const uint32_t (&P)[32], uint32_t dv, int acc, bool on) {
  if (on) {
#pragma unroll
    for (int s = 4 * H; s < 4 * H + 4; s++) {
      mma_rs_n128<1>(O, P[4 * s], P[4 * s + 1], P[4 * s + 2], P[4 * s + 3], dv + s * 128, s != 0 ? 1 : acc);
      if (s & 1) wg_commit();
    }
  } else { wg_commit(); wg_commit(); }
}
constexpr uint32_t DG = GR >> 4;
__device__ __forceinline__ void stage_q2(Cons& c, const float (&O)[64], uint32_t (&P)[32], uint32_t stg) {
  wg_commit(); wg_commit(); wg_commit(); wg_commit();
  c.turn_end();
  pack_frag<0>(O, P);
  stsm_frag(P, stg);
}
__device__ __forceinline__ void attn_half(Cons& c, float (&O)[64], uint32_t (&P)[32], uint32_t (&Q)[32], bool nextq, uint32_t stg, SoftState& z, uint32_t dkk, uint32_t dv0, float dmask, int last) {
  float S[32];
  c.turn_begin();
  wg_fence();
  issue_qk(S, Q, dkk + (last ? 8 : 2) * DG);
  wg_commit();
  issue_pv<0>(O, P, dv0 + 10 * DG, 1, last);
  issue_pv<1>(O, P, dv0 + 10 * DG, 1, last);
  c.turn_end();
  c.wait_full(last ? 12 : 4);
  wg_wait<4>();
  reg_fence(S);
  c.release(last ? 8 : 2, 2);
  reg_fence(Q);
  if (nextq) load_q(Q, stg);
  if (last) bar_sync(6, 256);
  mask_diag(S, dmask);
  float s0, s1, d0 = z.m0, d1 = z.m1;
#pragma unroll 1
  for (int pass = 0;; pass++) {
    if (z.shifted) shift_scores(S, d0, d1);
    float tr[ROT];
    exp_quarter<0, 3>(S, P, tr, s0, s1, c.sb);
    exp_quarter<1, 2>(S, P, tr, s0, s1, c.sb);
    pin(s1, c.sb); wg_wait<0>(); reg_fence_part<16, 16>(P); reg_fence(O);
    if (!soft_unsafe(s0, s1, !last) || pass) break;
    soft_fix(S, O, z, !last, d0, d1);
  }
  z.l0 += s0; z.l1 += s1;
  c.release(10, last ? 2 : 0);
  if (!last) c.wait_full(6);
}

template <int V> struct IC { static constexpr int value = V; };
__device__ __forceinline__ int conv_next(int g, bool spare) { return g >= NGR - 2 ? g - (NGR - 4) : !spare && g == 4 ? 1 : g + 2; }
__device__ __forceinline__ void conv_final(uint32_t rb, uint32_t yb, bool on) {
  const uint4 q0 = lds128(rb), q1 = lds128(rb + 4096), q2 = lds128(rb + 8192), q3 = lds128(rb + 12288);
  auto fin = [&](uint32_t x0, uint32_t x1, uint32_t x2, uint32_t x3) { return hadd2(hadd2(x0, x1), hadd2(x2, x3)); };
  asm volatile("{\n.reg .pred p;\nsetp.ne.b32 p, %5, 0;\n@p st.shared.v4.b32 [%0], {%1,%2,%3,%4};\n}\n" ::"r"(yb), "r"(fin(q0.x, q1.x, q2.x, q3.x)),
               "r"(fin(q0.y, q1.y, q2.y, q3.y)), "r"(fin(q0.z, q1.z, q2.z, q3.z)), "r"(fin(q0.w, q1.w, q2.w, q3.w)), "r"((int)on) : "memory");
}
__device__ __forceinline__ void conv_tasks(Cons& c, const Params& p, int ntask, bool spare, int ch, int chstep, int c5, uint32_t dd, uint32_t dkk, int w, int lane) {
  const uint32_t sb = c.sb;
  int g = 2 + c.wg;
  uint32_t rb = sb + g * GR;
  const uint32_t yb = sb + c.wg * 8192 + c.tid * 16;
  const int gt = 8 * w + (lane >> 2) + (lane & 3);
  uint32_t a[64], hb;
  auto lda = [&](int s) {
    a[4 * s] = lds32(hb + s * 256); a[4 * s + 1] = lds32(hb + s * 256 + 128);
    a[4 * s + 2] = lds32(hb + s * 256 + 16); a[4 * s + 3] = lds32(hb + s * 256 + 144);
  };
  auto first_a = [&]() {
    hb = sb + g * GR + WBYTES - 28 + gt * 4;
    lda(0); lda(15);
  };
  c.wait_full(g);
  first_a();
#pragma unroll 1
  for (int i = 0; i < ntask; i++) {
    const uint32_t base = sb + g * GR;
    lda(1); lda(14);
    a[0] = hadd2(a[0], gt == 7 ? dd : 0u); a[2] = hadd2(a[2], gt == 3 ? dd : 0u);
    float acc[128];
    const uint32_t db = dkk + ((WPL / 16 - 1) << 16) + g * DG + WZ / 16;
    c.turn_begin();
    auto pair = [&](auto kc) {
      constexpr int k = decltype(kc)::value;
      if (k < 7) wg_fence();
      if (k == 6) c.turn_end();
      conv_step<k, 7>(acc, a, db);
      conv_step<15 - k, 7>(acc, a, db);
      if (k < 6) { lda(k + 2); lda(13 - k); }
      if (k == 0) conv_final(rb, yb, i > 0);
      if (k == 1) {
        conv_final(rb + 2048, yb + 2048, i > 0);
        __syncwarp();
        if (lane == 0 && i > 0) mbar_arrive(sb + SM_BAR + (B_EV + c.wg) * 8);
      }
      if (k == 6) dd = __bfloat16_as_ushort(p.ssd[(ch + chstep + (i == 1 ? c5 : 0)) & (DM - 1)]);
    };
    pair(IC<0>()); pair(IC<1>()); pair(IC<2>()); pair(IC<3>()); pair(IC<4>()); pair(IC<5>()); pair(IC<6>()); pair(IC<7>());
    wg_commit();
    g = conv_next(g, spare);
    ch += chstep;
    rb = base + c.tid * 16;
    if (i + 1 < ntask) c.wait_full(g);
    const bool fr = mbar_test(sb + SM_BAR + (B_FREE + c.wg) * 8, c.pfree);
    wg_wait<0>();
    reg_fence(acc);
    reg_fence(a);
    bar_sync(3 + c.wg, 128);
    first_a();
    const int tw = (lane & 3) + w;
    const uint32_t xb = base + w * 4096 + tw * 32 + (lane >> 2) * 4;
    [[maybe_unused]] float t0[EROT + 1];
#pragma unroll
    for (int j = 0; j < 32; j++) {
      uint32_t ad = xb + j * 128;
      float v0 = acc[4 * j], v1 = acc[4 * j + 1];
      if (EROT && j > EROT) {
        v0 = t0[j % (EROT + 1)];
        asm("{\n.reg .pred p;\nsetp.ne.u32 p, %3, 0;\n@p add.f32 %0, %1, %2;\n}\n" : "+f"(v0) : "f"(acc[4 * j]), "f"(acc[j > 0 ? 4 * j - 2 : 0]), "r"(sb));
      } else if (j > 0) v0 += acc[j > 0 ? 4 * j - 2 : 0];
      if (j > 0) v1 += acc[j > 0 ? 4 * j - 1 : 0];
      uint32_t v = pack_bf16(v0, v1);
      t0[j % (EROT + 1)] = __uint_as_float(v);
      if (j == 31 && tw >= 4) { v = 0; ad -= 4096; }
      asm volatile("st.shared.b32 [%0], %1;" ::"r"(ad), "r"(v) : "memory");
    }
    if (!fr) c.wait_stage_free(); else c.pfree ^= 1;
  }
  bar_sync(3 + c.wg, 128);
  conv_final(rb, yb, true);
  conv_final(rb + 2048, yb + 2048, true);
  c.staged();
}

__global__ void __cluster_dims__(2, 1, 1) __launch_bounds__(NTHREADS, 1) mega_kernel(const __grid_constant__ Params p) {
  extern __shared__ __align__(1024) uint8_t smem_raw[];
  const uint32_t sb = smem_u32(smem_raw);
  if (threadIdx.x - 64 < 32) { prefetch_tm(&p.c); prefetch_tm(&p.wuk + (blockIdx.x & 1)); }
  const int wgi = __shfl_sync(0xffffffffu, threadIdx.x >> 7, 0);
  const int warp = __shfl_sync(0xffffffffu, threadIdx.x >> 5, 0);
  const uint32_t rank = blockIdx.x & 1;
  int slot;
  {
    uint32_t smid; asm volatile("mov.u32 %0, %smid;" : "=r"(smid));
    slot = p.pref[((smid >> 1) + (threadIdx.x & (smid >> 16))) & 127];
  }
  if (warp >= 3) {
    if (elect()) {
#pragma unroll
      for (int k = 0; k < 4; k++) mbar_init(sb + SM_BAR + ((warp - 3) * 4 + k) * 8, k == 1 && warp == 7 ? 11 : warp < (k ? 7 : 8) ? 1 : 4);
      if (warp == 7) { mbar_init(sb + SM_BAR + B_TICK * 8, 1); mbar_expect_tx(sb + SM_BAR + B_SLOT * 8, 8); mbar_expect_tx(sb + SM_BAR + B_TICK * 8, 4); }
      asm volatile("fence.mbarrier_init.release.cluster;" ::: "memory");
    }
    __syncwarp();
  }
  cluster_arrive();
  slot = __shfl_sync(0xffffffffu, slot, 0);
  const int pref = slot;
  if (warp < 4) {
    asm volatile("setmaxnreg.dec.sync.aligned.u32 40;");
    if (warp == 1 + 4 * rank) {
      unsigned taken = threadIdx.x == 32;
#pragma unroll 1
      for (int n = 0; n < NSLOT; n++) {
        asm volatile("{\n.reg .pred p;\nsetp.ne.b32 p, %0, 0;\n@p atom.relaxed.gpu.global.exch.b32 %0, [%1], 1;\n}\n" : "+r"(taken) : "l"(CLAIMP(slot)) : "memory");
        if (!__any_sync(0xffffffffu, taken)) break;
        slot = slot == NSLOT - 1 ? 0 : slot + 1;
      }
    }
    cluster_wait();
    if (threadIdx.x == 32) {
      send_both(sb + SM_BAR + B_SLOT * 8, (V_SLOT - B_SLOT) * 8 + rank * 4, slot | pref << 8);
    }
    if (warp == 2) {
#pragma unroll 1
      for (int kk = 0; kk < 4; kk++) {
        const int g0 = 2 + 3 * kk;
        const uint32_t fb = sb + SM_BAR + (B_FULL + g0) * 8;
        if (elect()) {
          mbar_expect_tx(fb, 3 * GR);
          tma2d(sb + g0 * GR, &p.c, kk * 64, (KV_ROW(pref & 7, 0) + rank) * 128, fb);
          tma3d_mc(sb + (g0 + 1 + rank) * GR, rank ? &p.wuv : &p.wuk, 0, kk * 64, ((pref & 56) >> 1) + 2 * KV_HEAD(pref & 7, 0), fb);
        }
        if (kk < 3) {
          uint32_t c0, c1;
          asm volatile("mov.u32 %0, %clock;" : "=r"(c0));
          do asm volatile("mov.u32 %0, %clock;" : "=r"(c1)); while (c1 - c0 < (kk ? X_D2 : X_DELAY));
        }
      }
      prefetch_tm(&p.x); prefetch_tm(&p.wq);
    }
  }
  int grp, idx, lb;
  int cn, cch, cstep;
  bool spare, redo;
  auto get_slot = [&]() {
    mbar_wait(sb + SM_BAR + B_SLOT * 8, 0);
    const uint32_t sv0 = __shfl_sync(0xffffffffu, lds32(sb + SM_BAR + V_SLOT * 8), 0), sv1 = __shfl_sync(0xffffffffu, lds32(sb + SM_BAR + V_SLOT * 8 + 4), 0);
    grp = (sv0 & 255) >> 3; idx = sv0 & 7; lb = (sv0 & 255) * 2 + rank;
    spare = grp == 8; redo = spare || sv0 != sv1;
    cn = CN_SPARE; cch = spare ? lb - NMAIN : 4 * CN_SPARE + 4 * lb; cstep = spare ? 4 : 1;
  };
  auto get_ticket = [&]() {
    mbar_wait(sb + SM_BAR + B_TICK * 8, 0);
    const int tk = __shfl_sync(0xffffffffu, lds32(sb + SM_BAR + V_TICK * 8), 0);
    cn = tk < NTICK ? 5 : 4;
    return 4 * NMAIN - 4 * lb - 4 + 2 * tk + rank;
  };

  if (wgi == 0) {
    asm volatile("setmaxnreg.dec.sync.aligned.u32 40;");
    const int lane = threadIdx.x & 31;
    cluster_arrive();
    get_slot();
    uint32_t pe = 0;
    auto acquire = [&](int g, int n, uint32_t m) {
      int i = g;
#pragma unroll 1
      do mbar_wait1(sb + SM_BAR + (B_EMPTY + i) * 8, (pe >> i) & 1); while (++i < g + n);
      pe ^= m << g;
    };
    if (warp == 3) {
      if (!spare) {
        const int s0 = lb * 16;
#pragma unroll 1
        for (int cg = 0; cg < 16; cg++) {
          if (cg == UP0 || cg == UP1) {
#pragma unroll 1
            for (int n = 0; n < 20 && !__any_sync(0xffffffffu, mbar_try(sb + SM_BAR + B_SLOT * 8, cg == UP0)); n++);
          } else if (cg < UP0) __nanosleep(US0);
          if (cg == UP1 && lane == rank * 32) send_both(sb + SM_BAR + B_TICK * 8, (V_TICK - B_TICK) * 8, atomicInc(FLAG(F_TICK), 0x7fffffffu));
          if (cg >= 5 && cg < 9) {
            unsigned l = lane;
            asm volatile("" : "+r"(l));
            const unsigned o = (idx * 8 + (l >> 2)) * (NH * HD) + (16 + 2 * grp) * HD + (l & 3) * 64;
            asm volatile("prefetch.global.L2 [%0];" ::"l"((rank ? p.wuvp : p.wukp) + (o + (cg - 1) * 64 * (NH * HD))));
          }
          const int ch = cg * 64 + 2 * lane;
          const uint32_t* kp = reinterpret_cast<const uint32_t*>(p.ak + (size_t)s0 * DM + ch);
          const uint32_t* vp = reinterpret_cast<const uint32_t*>(p.av + (size_t)s0 * DM + ch);
          const uint4 sw = __ldg(reinterpret_cast<const uint4*>(p.shk + ch * 4));
          uint32_t k3 = 0, k2 = 0, k1 = 0, k0 = 0, up = 0;
          if (lb > 0) { k3 = ldg_stream(kp - 4 * 512); k2 = ldg_stream(kp - 3 * 512); k1 = ldg_stream(kp - 2 * 512); k0 = ldg_stream(kp - 512); up = ldg_stream(vp - 512); }
          const uint32_t w0 = __byte_perm(sw.x, sw.z, 0x5410), w1 = __byte_perm(sw.x, sw.z, 0x7632);
          const uint32_t w2 = __byte_perm(sw.y, sw.w, 0x5410), w3 = __byte_perm(sw.y, sw.w, 0x7632);
          up = hmul2(hfma2(k0, w0, hfma2(k1, w1, hfma2(k2, w2, hmul2(k3, w3)))), up);
#pragma unroll 1
          for (int hb = 0; hb < 2; hb++) {
            uint32_t kk[8], u[8];
#pragma unroll
            for (int r = 0; r < 8; r++) { kk[r] = ldg_stream(kp + r * 512); u[r] = ldg_stream(vp + r * 512); }
#pragma unroll
            for (int r = 0; r < 8; r++) {
              k3 = k2; k2 = k1; k1 = k0; k0 = kk[r];
              u[r] = hmul2(hfma2(k0, w0, hfma2(k1, w1, hfma2(k2, w2, hmul2(k3, w3)))), u[r]);
            }
            if (lane == 0) asm volatile("cp.async.bulk.wait_group.read 0;" ::: "memory");
            __syncwarp();
            const uint32_t dst = sb + SM_UST + lane * 32 + ((lane & 4) << 2);
#pragma unroll
            for (int cc = 0; cc < 2; cc++) {
              const uint32_t sel = cc ? 0x7632 : 0x5410;
              asm volatile("st.shared.v4.b32 [%0], {%1,%2,%3,%4};" ::"r"(dst + cc * 1024), "r"(__byte_perm(u[6], u[5], sel)), "r"(__byte_perm(u[4], u[3], sel)),
                           "r"(__byte_perm(u[2], u[1], sel)), "r"(__byte_perm(u[0], up, sel)) : "memory");
              asm volatile("st.shared.v4.b32 [%0], {%1,%2,%3,%4};" ::"r"((dst ^ 16) + cc * 1024), "r"(__byte_perm(u[7], u[6], sel)), "r"(__byte_perm(u[5], u[4], sel)),
                           "r"(__byte_perm(u[3], u[2], sel)), "r"(__byte_perm(u[1], u[0], sel)) : "memory");
            }
            fence_async_smem();
            __syncwarp();
            if (lane == 0) {
              asm volatile("cp.async.bulk.tensor.3d.global.shared::cta.bulk_group.L2::cache_hint [%0, {%2, %3, %4}], [%1], %5;\ncp.async.bulk.commit_group;"
                           ::"l"(&p.w), "r"(sb + SM_UST), "r"(WZ / 2 + lb * 16 + (hb ^ 1) * (WPL / 2)), "r"(cg * 32), "r"(0), "l"(cg >= UP0 && cg < UP1 ? EV_FIRST : EV_NORMAL) : "memory");
            }
            up = u[7];
            kp += 8 * 512; vp += 8 * 512;
          }
          if ((cg & (cg + 1)) == 0 && lane == 0) {
            asm volatile("cp.async.bulk.wait_group 0;" ::: "memory");
            fence_release();
            flag_add(FLAG(F_U + 32 - __clz(cg)));
          }
        }
        prefetch_tm(&p.wo); prefetch_tm(&p.x3); prefetch_tm(&p.y3); prefetch_tm(&p.out);
      } else {
#pragma unroll 1
        for (int i = 0, g = 2; i < 32; i++) {
          acquire(g, i < 6 ? 2 : 1, 3);
          if (elect()) {
            const uint32_t fb = sb + SM_BAR + (B_FULL + g) * 8;
            if (i == 0) { mbar_expect_tx(fb - 8, 2048); bulk_g2s(sb + GR, p.gate_w, 2048, fb - 8); }
            mbar_expect_tx(fb, 2 * GR);
            tma3d(sb + g * GR, &p.x3, 0, (lb - NMAIN) * 512 + (i >> 3) * 128, (i & 7) * 2, fb);
          }
          g = g == NGR - 2 ? 2 : g + 2;
        }
        bar_arrive(5, 64);
      }
      unsigned long long t0, t1;
      asm volatile("mov.u64 %0, %globaltimer;" : "=l"(t0));
      auto check = [&]() {
        asm volatile("mov.u64 %0, %globaltimer;" : "=l"(t1));
        if (t1 - t0 > 2000000000ull) __trap();
      };
      if (!spare) {
        unsigned v;
        do {
          __nanosleep(PSL);
          check();
          asm volatile("ld.acquire.gpu.global.u32 %0, [%1];" : "=r"(v) : "l"(FLAG(lane & 1 ? F_Y + idx : F_GATE)) : "memory");
        } while (__any_sync(0xffffffffu, v < (lane & 1 ? 128 : 8)));
        __syncwarp();
        if (lane == 0) mbar_arrive(sb + SM_BAR + B_SLOT * 8);
      }
      if (lane == 0) {
        while (!mbar_try(sb + SM_BAR + B_DONE * 8, 0)) check();
      }
    } else if (warp != 0) {
      const int w = warp - 1;
      int ne = 12 + (CN_SPARE + 1 - w) / 2, c5 = 0, pend = 0;
      int cg = 2 + w, ch = cch + w * cstep;
#pragma unroll 1
      for (int e = spare ? 12 : 0; e < ne; e++) {
        const int rnd = e >= 6, k = e - 6 * rnd, rt = k == 4 ? idx : 15 - idx;
        uint8_t* dst = k < 4 ? g_kv + (size_t)(((k & 1) * 16 + 2 * grp + KV_HEAD(idx, k >> 1)) * 16 + KV_ROW(idx, k >> 1) + rank) * 32768 + w * 8192
                     : k < 6 ? g_cimg + (size_t)(rt * 32 + 16 * rnd + 2 * grp + rank) * 32768 + (w ^ (k & 1)) * 8192
                             : g_w + (size_t)ch * WSTRIDE + WZ;
        const uint32_t src = sb + w * 8192;
        if (e == 11) { c5 = get_ticket(); ne = 12 + ((cn + 1 - w) >> 1); }
        if (e == 6) flag_wait(FLAG(F_AD + grp), 32);
        mbar_wait1(sb + SM_BAR + (B_EV + w) * 8, e & 1);
        if (lane < 4 && k >= 6 && (!spare || e < ne - 6)) mbar_arrive_cluster(sb + SM_BAR + (B_EMPTY + cg) * 8, lane & 1);
        fence_async_smem();
        if (elect()) {
          const uint32_t cs = e >= 11 ? 4096 : 1024;
#pragma unroll 1
          for (uint32_t i = 0; i < (k >= 6 ? 4096 : 16384); i += cs) {
            const uint32_t o = (i + (i & 8192)) ^ (e == 11 ? 16384 : 0);
            asm volatile("cp.async.bulk.global.shared::cta.bulk_group.L2::cache_hint [%0], [%1], %2, %3;" ::"l"(dst + o), "r"(src + o), "r"(cs),
                         "l"(e == 4 || e == 5 || spare ? EV_FIRST : EV_NORMAL) : "memory");
            asm volatile("cp.async.bulk.commit_group;\ncp.async.bulk.wait_group.read 1;" ::: "memory");
            if (e == 11 && i == 8192) {
              mbar_arrive_cluster(sb + SM_BAR + (B_EMPTY + 1) * 8, 0); mbar_arrive_cluster(sb + SM_BAR + (B_EMPTY + 1) * 8, 1);
            }
          }
          asm volatile("cp.async.bulk.wait_group 0;" ::: "memory");
          mbar_arrive(sb + SM_BAR + (B_FREE + w) * 8);
        }
        __syncwarp();
        if (lane < (e == ne - 1 && !spare ? 2 : 0)) mbar_arrive_cluster(sb + SM_BAR + B_EMPTY * 8, lane);
        const int nch = ch + 2 * cstep + (k == 7 ? c5 : 0);
        pend++;
        if (k >= 3 && (e <= (spare ? 12 : 11) || e == ne - 1 || (nch ^ ch) >= 128)) {
          fence_release();
          const unsigned fl = k == 3 ? F_KV + rnd * 8 + grp : k < 6 ? F_CTX + rt * 2 + rnd : F_Y + ((unsigned)ch >> 7);
          if (lane <= (e == (spare ? 12 : 5)))
            asm volatile("red.relaxed.gpu.global.add.u32 [%0], %1;" ::"l"(FLAG(lane ? (spare ? F_GATE : F_AD + grp) : fl)), "r"(k >= 6 ? pend : 1) : "memory");
          pend = 0;
        }
        if (k >= 6) { cg = conv_next(cg, spare); ch = nch; }
      }
      if (lane == 0) mbar_arrive(sb + SM_BAR + B_DONE * 8);
    } else {
#pragma unroll 1
      for (int rnd = 0; rnd < (spare ? 0 : 2); rnd++) {
        const int hp = 16 * rnd + 2 * grp, head = hp + rank;
#pragma unroll 1
        for (int kk = rnd || redo ? 0 : 4; kk < 32; kk++) {
          const int g0 = 2 + 3 * (kk & 3);
          acquire(g0, kk < 4 ? 3 : 1, 7);
          if (elect()) {
            const uint32_t fb = sb + SM_BAR + (B_FULL + g0) * 8;
            mbar_expect_tx(fb, 3 * GR);
            if (kk < 16) {
              tma2d_p(sb + g0 * GR, &p.c, (kk & 7) * 64, (KV_ROW(idx, kk >> 3) + rank) * 128, fb, rnd);
              tma3d_mc_p(sb + (g0 + 1 + rank) * GR, rank ? &p.wuv : &p.wuk, 0, (kk & 7) * 64, (hp + KV_HEAD(idx, kk >> 3)) * 2, fb, kk >= 8);
            } else {
              tma2d_mc(sb + (g0 + rank) * GR, &p.x, (kk - 16) * 64, (rank ? 15 - idx : idx) * 128, fb);
              tma3d<true>(sb + (g0 + 2) * GR, &p.wq, 0, (kk - 16) * 64, head * 2, fb);
            }
          }
        }
        flag_wait(FLAG(F_KV + rnd * 8 + grp), 32);
        fence_async_all();
        int g0 = 2;
#pragma unroll 1
        for (int n = 0; n < 36; n += n == 0 || n == 33 ? 2 : 1) {
          const int it = (n >> 1) - (n & 1);
          const int blk = it & 15 ? (it <= idx ? it - 1 : 15 - it) : it ? 15 - idx : idx;
          acquire(g0, n < 7 ? 2 : 1, 3);
          if (elect()) {
            const uint32_t fb = sb + SM_BAR + (B_FULL + g0) * 8;
            if (n == 5) mbar_arrive(sb + SM_BAR + B_SLOT * 8);
            mbar_expect_tx(fb, 2 * GR);
            asm volatile("cp.async.bulk" TMA_MB ".L2::cache_hint [%0], [%1], %2, [%3], %4;" ::"r"(sb + g0 * GR), "l"(g_kv + (unsigned)((((n & 1) * 16 + (head & 15)) * 16 + blk) * 32768)),
                         "r"(2 * GR), "r"(fb), "l"(it >= 8 ? EV_FIRST : EV_NORMAL) : "memory");
          }
          g0 = g0 == 12 ? 2 : g0 + (n == 13 || n == 19 ? 4 : 2);
        }
      }
      int c5 = 0;
      if (spare) { bar_sync(5, 64); pe = 0x3FC0; }
      else c5 = get_ticket();
      auto conv_fill = [&](int g, int ch) {
        acquire(g, 1, 1);
        if (elect()) {
          const uint32_t fb = sb + SM_BAR + (B_FULL + g) * 8;
          mbar_expect_tx(fb, WBYTES + 4096);
          bulk_g2s<true>(sb + g * GR, g_w + (size_t)ch * WSTRIDE, WBYTES, fb);
          bulk_g2s<true>(sb + g * GR + WBYTES, p.ssk + (size_t)ch * SEQ, 4096, fb);
        }
      };
#pragma unroll 1
      for (int i = 0, g = 2; i < cn; i++) {
        if ((i & 15) == 0) { flag_wait(FLAG(F_U + (spare ? 32 - __clz(i >> 4) : 4)), NMAIN); fence_async_all(); }
        conv_fill(g + (i & 1), cch + i * cstep + (i == 4 ? c5 : 0));
        if (i & 1) g = conv_next(g, spare);
      }
      if (!spare) {
        const int rt = grp + 8 * rank, ct = idx;
        int g0 = P3G, top = 12;
        const uint8_t* src = g_cimg + (unsigned)((rt * 64 + 32) * GR);
#pragma unroll 1
        for (int kb = 0; kb < 64; kb++) {
          if (!(kb & 31)) { flag_wait(FLAG(F_CTX + rt * 2 + ((kb ^ 32) >> 5)), 32); fence_async_all(); if (kb) src -= 64 * GR; }
          acquire(g0, kb < 11 ? 2 : 1, 3);
          if (elect()) {
            const uint32_t fb = sb + SM_BAR + (B_FULL + g0) * 8;
            mbar_expect_tx(fb, 2 * GR);
            bulk_g2s<true>(sb + g0 * GR, src, GR, fb);
            tma2d_mc<true>(sb + (g0 + 1) * GR + rank * 8192, &p.wo, ct * 128 + rank * 64, (kb ^ 32) * 64, fb);
          }
          src += GR;
          g0 = g0 == (kb < XK ? 12 : kb < YK ? 10 : 8) ? (kb == 3 ? 2 : 0) : g0 + 2;
          if (kb == XK || (kb >= YK && top == P3Y && (kb == 63 || mbar_test(sb + SM_BAR + B_SLOT * 8, 1)))) {
            const bool j = kb != XK;
            if (j) { mbar_wait1(sb + SM_BAR + B_SLOT * 8, 1); fence_async_all(); }
            acquire(top, 1, 0);
            if (elect()) {
              const uint32_t fb = sb + SM_BAR + (B_FULL + top) * 8;
              mbar_expect_tx(fb, j ? 2 * GR + 512 : 2 * GR);
              if (j) bulk_g2s(sb + SM_GATE, g_gate + (unsigned)(rt * 128), 512, fb);
              tma3d(sb + top * GR, j ? &p.y3 : &p.x3, 0, (j ? ct : rt) * 128, (j ? rt : ct) * 2, fb);
            }
            top -= 2;
          }
        }
        unsigned n = 0;
        if (lane == 0) n = atomicInc(FLAG(F_EXIT), 0x7fffffffu);
        if (__any_sync(0xffffffffu, n == NMAIN - 1)) {
#pragma unroll
          for (int i = lane; i < 96; i += 32) *reinterpret_cast<uint2*>(FLAG(i)) = make_uint2(0, 0);
        }
      }
      if (lane == 0) mbar_arrive(sb + SM_BAR + B_DONE * 8);
    }
    __syncwarp();
    cluster_wait();
  } else {
    asm volatile("setmaxnreg.inc.sync.aligned.u32 232;");
    Cons c;
    c.sb = sb; c.pf = 0; c.wg = wgi - 1; c.tid = threadIdx.x & 127;
    const int lane = threadIdx.x & 31, t = lane & 3;
    const int row = c.wg * 64 + (warp & 3) * 16 + (lane >> 2);
    const uint32_t dkk = desc_k(sb), dk0 = dkk + c.wg * 512, dm0 = desc_mn<8192>(sb), dv0 = desc_mn<16384>(sb);
    const uint32_t dsw = DG + 512 - c.wg * 1024;
    if (c.wg == 1) bar_arrive(1, 256);
    c.pfree = 1;
    asm("mapa.shared::cluster.u32 %0, %1, %2;" : "=r"(c.relb) : "r"(sb + SM_BAR + (B_EMPTY + (c.tid >> 1)) * 8), "r"(c.tid & 1));
    c.zero = p.zero;
    const uint32_t stg = sb + (c.wg * 64 + (warp & 3) * 16 + ((lane >> 3) & 1) * 8 + (lane & 7)) * 128 + (((lane >> 4) ^ (lane & 7)) << 4);

    uint32_t dd0;
    auto load_dd = [&]() { asm volatile("ld.global.nc.u16 %0, [%1];" : "=r"(dd0) : "l"(p.ssd + (unsigned)(cch + c.wg * cstep + (lane & c.zero)))); };
    int pass = c.zero;
#pragma unroll 1
    do {
    if (pass) {
      load_dd();
#pragma unroll 1
      for (int g = 2; g < NGR; g += 3) { mbar_wait(sb + SM_BAR + (B_FULL + g) * 8, 0); c.release(g, 3); }
      c.pf = 0x924;
    if (spare) {
      c.wait_full(1);
      int g = 2;
#pragma unroll 1
      for (int r = 0; r < 4; r++) {
        float d[4] = {0.f, 0.f, 0.f, 0.f}, e[4] = {0.f, 0.f, 0.f, 0.f}, f[4] = {0.f, 0.f, 0.f, 0.f}, h[4] = {0.f, 0.f, 0.f, 0.f};
#pragma unroll 1
        for (int kb = 0; kb < 16; kb += 2) {
          c.wait_full(g);
          wg_fence();
#pragma unroll
          for (int k = 0; k < 4; k += 2) {
            mma_ss_n8(d, dk0 + g * DG + k * 2, dkk + DG + kb * 8 + k * 2);
            mma_ss_n8(e, dk0 + (g + 1) * DG + k * 2, dkk + DG + kb * 8 + 8 + k * 2);
            mma_ss_n8(f, dk0 + g * DG + k * 2 + 2, dkk + DG + kb * 8 + k * 2 + 2);
            mma_ss_n8(h, dk0 + (g + 1) * DG + k * 2 + 2, dkk + DG + kb * 8 + 8 + k * 2 + 2);
          }
          wg_commit();
          wg_wait<0>();
          c.release(g, 2);
          g = g == NGR - 2 ? 2 : g + 2;
        }
        reg_fence(d); reg_fence(e); reg_fence(f); reg_fence(h);
        d[0] = (d[0] + e[0]) + (f[0] + h[0]); d[2] = (d[2] + e[2]) + (f[2] + h[2]);
        if (t == 0) {
          float* gp = g_gate + (unsigned)((lb - NMAIN) * 512 + r * 128 + row);
          gp[0] = rcp(1.f + ex2(-1.4426950408889634f * d[0])); gp[8] = rcp(1.f + ex2(-1.4426950408889634f * d[2]));
        }
      }
    }
    } else cluster_wait();
    get_slot();
    } while (redo && !pass++);
    const float dmask = (float)(2 * t - (row & 63));
    int c5 = 0;
    uint32_t pv[32];
#pragma unroll 1
    for (int rnd = 0; rnd < (spare ? 0 : 2); rnd++) {
      float O[64];
      uint32_t Q[32];
      c.wait_full(2);
#pragma unroll 1
      for (int tile = c.zero; tile < 2; tile++) {
        float acc[128];
        const bool single = tile == 0;
        {
          const uint32_t a = dk0 + 2 * DG, b = dm0 + 3 * DG;
          c.turn_begin();
          wg_fence();
          mma_ss_n256_init<1>(acc, a, b);
#pragma unroll
          for (int k = 1; k < 4; k++) mma_ss_n256<1>(acc, a + k * 2, b + k * 128);
          wg_commit();
          if (single) c.turn_end();
        }
#pragma unroll 1
        for (int kb = 1; kb < 8; kb++) {
          const int g0 = 2 + 3 * (kb & 3);
          const uint32_t a = dk0 + g0 * DG, b = dm0 + (g0 + 1) * DG;
          const bool second = (kb == 1 && !single) || kb == 7;
          if (!second) { wg_wait<0>(); c.release(2 + 3 * ((kb - 1) & 3), 3); }
          c.wait_full(g0);
          if (!second) c.turn_begin();
          wg_fence();
#pragma unroll
          for (int k = 0; k < 4; k++) mma_ss_n256<1>(acc, a + k * 2, b + k * 128);
          wg_commit();
          if (kb != 6) c.turn_end();
          if (second) { wg_wait<1>(); c.release(2 + 3 * ((kb - 1) & 3), 3); }
          if (tile == 1 && kb == 3) { c.wait_stage_free(); stsm_frag<0, 4>(pv, stg); }
          if (tile == 1 && kb == 4) { stsm_frag<4, 8>(pv, stg); c.staged(); }
        }
        c.wait_stage_free();
        const bool nxt = c.try_full(2);
        wg_wait<0>();
        reg_fence(acc);
        c.release(11, 3);
        store_scaled(acc, SM_C, SM_C, stg, sb);
        c.staged();
        pack_frag<64>(acc, pv);
        if (!nxt) mbar_wait(sb + SM_BAR + (B_FULL + 2) * 8, (c.pf >> 2) & 1);
        c.pf ^= 4;
      }
      {
        float qa[64];
        float (&qb)[64] = O;
        {
          const uint32_t a = dk0 + 2 * DG, b = dm0 + 4 * DG;
          c.turn_begin();
          wg_fence();
          mma_ss_n128_init<1>(qa, a, b);
          mma_ss_n128_init<1>(qb, a + dsw, b);
#pragma unroll
          for (int k = 1; k < 4; k++) {
            mma_ss_n128<1>(qa, a + k * 2, b + k * 128);
            mma_ss_n128<1>(qb, a + dsw + k * 2, b + k * 128);
          }
          wg_commit();
        }
#pragma unroll 1
        for (int kb = 1; kb < 16; kb++) {
          const int g0 = 2 + 3 * (kb & 3);
          const uint32_t a = dk0 + g0 * DG, b = dm0 + (g0 + 2) * DG;
          const bool second = kb == 1 || kb == 15;
          if (!second) { wg_wait<0>(); c.release(2 + 3 * ((kb - 1) & 3), 3); }
          c.wait_full(g0);
          if (!second) c.turn_begin();
          wg_fence();
#pragma unroll
          for (int k = 0; k < 4; k++) {
            mma_ss_n128<1>(qa, a + k * 2, b + k * 128);
            mma_ss_n128<1>(qb, a + dsw + k * 2, b + k * 128);
          }
          wg_commit();
          if (kb != 14) c.turn_end();
          if (second) { wg_wait<1>(); c.release(2 + 3 * ((kb - 1) & 3), 3); }
          if (kb == QFLUSH) { c.wait_stage_free(); stsm_frag<0, 4>(pv, stg); }
          if (kb == QFLUSH + 1) { stsm_frag<4, 8>(pv, stg); c.staged(); }
        }
        c.wait_stage_free();
        const bool k0 = c.try_full(2);
        wg_wait<0>();
        reg_fence(qa); reg_fence(qb);
        c.release(11, 3);
        pack_frag<0>(qa, Q);
        if (c.wg == 0) {
          pack_frag<0>(qb, pv);
          stsm_frag(pv, stg);
        }
        if (!k0) c.wait_full(2); else c.pf ^= 4;
      }
      {
        const int nA = idx + 1;
        uint32_t (&P)[32] = pv;
        SoftState z;
        z.m0 = z.m1 = z.l0 = z.l1 = 0.f; z.shifted = c.zero;
#pragma unroll 1
        for (int seg = c.zero;; seg++) {
        if (c.wg == seg) attn_half(c, O, P, Q, nA == 1 && !seg, stg, z, dkk, dv0, dmask, seg);
        if (seg) break;
        int gk = c.wg ? 2 : 4, gv = c.wg ? 2 : 6;
        uint32_t dk = dkk + gk * DG;
#pragma unroll 1
        for (int it = 1 - c.wg; it < 17 - c.wg; it++) {
          float S[64];
          c.turn_begin();
          wg_fence();
          issue_qk(S, Q, dk);
          wg_commit();
          const uint32_t dv = dv0 + gv * DG;
          uint32_t relk = c.relb + gk * 8, relv = c.relb + gv * 8;
          gk = gv == 12 ? 2 : gv + (it == 6 || it == 9 ? 4 : 2);
          gv = it == 16 ? gk : gk == 12 ? 2 : gk + 2;
          uint32_t fk = sb + SM_BAR + (B_FULL + gk) * 8, fv = sb + SM_BAR + (B_FULL + gv) * 8, park = (c.pf >> gk) & 1, parv = (c.pf >> gv) & 1;
          c.pf ^= (1u << gk) | (1u << gv);
          dk = dkk + gk * DG;
          float lo0 = z.l0, lo1 = z.l1;
          const bool first = it == nA || it == 0;
          if (it == nA) {
            lo0 = rcp(quad_sum(lo0)); lo1 = rcp(quad_sum(lo1));
            z.m0 = z.m1 = z.l0 = z.l1 = 0.f; z.shifted = 0;
          }
          float s0, s1, d0 = z.m0, d1 = z.m1;
          int pre = z.shifted || (it & 15) == 0 || it + 1 == nA;
          float lim = first ? -1.f : SM_LIMIT;
          asm volatile("" : "+r"(relk), "+r"(relv), "+r"(fk), "+r"(fv), "+r"(park), "+r"(parv), "+r"(dk), "+r"(pre), "+f"(lim), "+f"(d0), "+f"(d1), "+f"(z.l0), "+f"(z.l1));
          if (it + c.wg > 1) {
            issue_pv<0>(O, P, dv, it != nA + 1 && it != 1, true);
            issue_pv<1>(O, P, dv, 1, true);
            c.turn_end();
          } else if (it) {
            issue_pv<0>(O, P, dv, 0, true);
            wg_commit(); wg_commit();
            c.turn_end();
            bar_sync(6, 256);
          } else stage_q2(c, O, P, stg);
          wg_wait<4>();
          reg_fence(S); reg_fence(Q);
          if (c.tid < 4) asm volatile("mbarrier.arrive.shared::cluster.b64 _, [%0];" ::"r"(relk) : "memory");
#pragma unroll 1
          for (int pass = 0;; pass++) {
            if (pre) {
              if (it + 1 == nA) load_q(Q, stg);
              if ((it & 15) == 0) mask_diag(S, dmask);
              if (z.shifted) shift_scores(S, d0, d1);
            }
            float tr[ROT];
            exp_quarter<0, 3>(S, P, tr, s0, s1, sb);
            exp_quarter<1, 2>(S, P, tr, s0, s1, sb);
            exp_quarter<2, 1>(S, P, tr, s0, s1, sb);
            exp_quarter<3, 0>(S, P, tr, s0, s1, sb);
            reg_fence(O);
            if (c.tid < (pass || !it ? 0 : 4)) asm volatile("mbarrier.arrive.shared::cluster.b64 _, [%0];" ::"r"(relv) : "memory");
            const bool ok = mbar_test(fk, park) & mbar_test(fv, parv);
            if (!ok) lim = -1.f;
            if (!__any_sync(0xffffffffu, !(s0 <= lim && s1 <= lim))) break;
            if (pass) break;
            if (it == nA) {
              store_scaled(O, lo0, lo1, stg, sb);
              c.staged();
            }
            if (!it) bar_arrive(6, 256);
            if (!ok) { mbar_wait(fk, park); mbar_wait(fv, parv); }
            if (!soft_unsafe(s0, s1, first)) break;
            soft_fix(S, O, z, first, d0, d1);
            pre = 1;
          }
          z.l0 += s0; z.l1 += s1;
        }
        if (!c.wg) bar_arrive(6, 256);
        }
        load_dd();
        c.turn_begin();
        wg_fence();
        issue_pv<0>(O, P, dv0 + 12 * DG, 1, true);
        issue_pv<1>(O, P, dv0 + 12 * DG, 1, !c.wg);
        c.turn_end();
        z.l0 = rcp(quad_sum(z.l0)); z.l1 = rcp(quad_sum(z.l1));
        c.wait_stage_free();
        if (rnd) c5 = get_ticket();
        wg_wait<0>();
        reg_fence(O); reg_fence(P);
        c.release(12, 2);
        store_scaled(O, z.l0, z.l1, stg, sb);
        c.staged();
      }
    }
    conv_tasks(c, p, (cn + 1 - c.wg) >> 1, spare, cch + c.wg * cstep, 2 * cstep, c5, dd0, dkk, warp & 3, lane);
    if (c.wg == 1) c.pf ^= 0x14;
    if (c.wg == (cn & 1)) c.turn_begin();
    if (!spare) {
      const int rt = grp + 8 * rank, ct = idx;
      float acc[64];
      int g0 = P3G + 2, pg = P3G;
      {
        c.wait_full(P3G);
        const uint32_t a = dk0 + P3G * DG, b = dm0 + (P3G + 1) * DG;
        wg_fence();
        mma_ss_n128_init<1>(acc, a, b);
#pragma unroll
        for (int k = 1; k < 4; k++) mma_ss_n128<1>(acc, a + k * 2, b + k * 128);
        wg_commit();
      }
#pragma unroll 1
      for (int kb = 1; kb < 64; kb++) {
        c.wait_full(g0);
        if (kb == STR && !c.wg) c.turn_begin();
        const uint32_t a = dk0 + g0 * DG, b = dm0 + (g0 + 1) * DG;
        wg_fence();
#pragma unroll
        for (int k = 0; k < 4; k++) mma_ss_n128<1>(acc, a + k * 2, b + k * 128);
        wg_commit();
        if (kb < STR) { wg_wait<1>(); c.release(pg, kb <= 59 ? 2 : 0); }
        pg = g0;
        g0 = g0 == (kb < XK ? 12 : kb < YK ? 10 : 8) ? (kb == 3 ? 2 : 0) : g0 + 2;
      }
      if (c.wg) c.turn_end();
      cluster_arrive();
      c.wait_full(P3X);
      c.wait_full(P3Y);
      const float g0f = __uint_as_float(lds32(sb + SM_GATE + row * 4)), g1f = __uint_as_float(lds32(sb + SM_GATE + row * 4 + 32));
      const uint32_t gp0 = pack_bf16(g0f, g0f), gp1 = pack_bf16(g1f, g1f);
      const float h0 = 1.f - g0f, h1 = 1.f - g1f;
      const int w = warp & 3;
      const uint32_t xa = stg + P3X * GR;
      const uint32_t ya = sb + P3Y * GR + c.wg * 16384 + ((lane >> 4) * 8 + (lane & 7)) * 128 + (((2 * w + ((lane >> 3) & 1)) ^ (lane & 7)) << 4);
      uint32_t xy[32];
      auto prep = [&](int j0, int j1) {
#pragma unroll
        for (int jj = j0; jj < j1; jj++) {
          uint32_t x[4], y[4];
          asm volatile("ldmatrix.sync.aligned.m8n8.x4.shared.b16 {%0,%1,%2,%3}, [%4];" : "=r"(x[0]), "=r"(x[1]), "=r"(x[2]), "=r"(x[3]) : "r"((xa ^ ((jj & 3) << 5)) + (jj >> 2) * 16384) : "memory");
          asm volatile("ldmatrix.sync.aligned.m8n8.x4.trans.shared.b16 {%0,%1,%2,%3}, [%4];" : "=r"(y[0]), "=r"(y[1]), "=r"(y[2]), "=r"(y[3]) : "r"(ya + jj * 2048) : "memory");
#pragma unroll
          for (int i = 0; i < 4; i++) xy[4 * jj + i] = hmul2(x[i], y[i]);
        }
      };
      prep(0, 4);
      wg_wait<0>();
      reg_fence(acc);
#pragma unroll
      for (int hf = 0; hf < 2; hf++) {
#pragma unroll
        for (int i = 16 * hf; i < 16 * hf + 16; i++) {
          const float h = (i & 1) ? h1 : h0;
          xy[i] = hfma2((i & 1) ? gp1 : gp0, xy[i], pack_bf16(acc[2 * i] * h, acc[2 * i + 1] * h));
        }
        if (hf) stsm_frag<4, 8>(xy, xa); else stsm_frag<0, 4>(xy, xa);
        fence_async_smem();
        __syncwarp();
        const int r0 = c.wg * 64 + w * 16;
        if (lane == 0) tma2d_store(&p.out, sb + (P3X + hf) * GR + r0 * 128, ct * 128 + hf * 64, rt * 128 + r0);
        if (!hf) prep(4, 8);
      }
      if (lane == 0) asm volatile("cp.async.bulk.commit_group;\ncp.async.bulk.wait_group.read 0;" ::: "memory");
    } else { cluster_arrive(); }
    if (lane == 0) mbar_arrive(sb + SM_BAR + B_DONE * 8);
    __syncwarp();
    cluster_wait();
  }
}

typedef CUresult (*EncFn)(CUtensorMap*, CUtensorMapDataType, cuuint32_t, void*, const cuuint64_t*, const cuuint64_t*, const cuuint32_t*,
                          const cuuint32_t*, CUtensorMapInterleave, CUtensorMapSwizzle, CUtensorMapL2promotion, CUtensorMapFloatOOBfill);

void enc2d(EncFn enc, CUtensorMap* tm, const void* base, uint64_t cols, uint64_t rows, uint32_t bc, uint32_t br) {
  cuuint64_t dims[2] = {cols, rows}; cuuint64_t strides[1] = {cols * 2}; cuuint32_t box[2] = {bc, br}; cuuint32_t es[2] = {1, 1};
  enc(tm, CU_TENSOR_MAP_DATA_TYPE_BFLOAT16, 2, const_cast<void*>(base), dims, strides, box, es, CU_TENSOR_MAP_INTERLEAVE_NONE,
      CU_TENSOR_MAP_SWIZZLE_128B, CU_TENSOR_MAP_L2_PROMOTION_L2_128B, CU_TENSOR_MAP_FLOAT_OOB_FILL_NONE);
}
void enc3d(EncFn enc, CUtensorMap* tm, const void* base, uint64_t K, uint64_t N, uint32_t bk = 64, uint64_t pitch = 0) {
  cuuint64_t dims[3] = {64, K, N / 64}; cuuint64_t strides[2] = {pitch ? pitch : N * 2, 128}; cuuint32_t box[3] = {64, bk, 2}; cuuint32_t es[3] = {1, 1, 1};
  enc(tm, CU_TENSOR_MAP_DATA_TYPE_BFLOAT16, 3, const_cast<void*>(base), dims, strides, box, es, CU_TENSOR_MAP_INTERLEAVE_NONE,
      CU_TENSOR_MAP_SWIZZLE_128B, CU_TENSOR_MAP_L2_PROMOTION_L2_128B, CU_TENSOR_MAP_FLOAT_OOB_FILL_NONE);
}

}

extern "C" void kernel_launch(void* const* d_in, const int* in_sizes, int n_in, void* d_out, int out_size) {
  (void)in_sizes; (void)n_in; (void)out_size;
  typedef const __nv_bfloat16* BP;
  BP xq = (BP)d_in[0], ak = (BP)d_in[1], av = (BP)d_in[2], shk = (BP)d_in[3], ssk = (BP)d_in[4], ssd = (BP)d_in[5];
  BP ckv = (BP)d_in[7], wq = (BP)d_in[8], wuk = (BP)d_in[9], wuv = (BP)d_in[10], wo = (BP)d_in[11], gw = (BP)d_in[12];

  static EncFn enc = nullptr;
  if (!enc) {
    cudaDriverEntryPointQueryResult qr;
    cudaGetDriverEntryPoint("cuTensorMapEncodeTiled", (void**)&enc, cudaEnableDefault, &qr);
    cudaFuncSetAttribute(mega_kernel, cudaFuncAttributeMaxDynamicSharedMemorySize, SMEM_BYTES);
  }
  Params p;
  enc2d(enc, &p.x, xq, DM, SEQ, 64, 128);
  enc2d(enc, &p.c, ckv, DC, SEQ, 64, 128);
  enc3d(enc, &p.wq, wq, DM, NH * HD);
  enc3d(enc, &p.wuk, wuk, DC, NH * HD);
  enc3d(enc, &p.wuv, wuv, DC, NH * HD);
  enc2d(enc, &p.wo, wo, DM, NH * HD, 64, 64);
  enc3d(enc, &p.x3, xq, SEQ, DM, 128);
  enc2d(enc, &p.out, d_out, DM, SEQ, 64, 16);
  {
    void* wp = nullptr;
    cudaGetSymbolAddress(&wp, g_w);
    enc3d(enc, &p.y3, (uint8_t*)wp + WZ, DM, SEQ, 128, WSTRIDE);
    cuuint64_t dims[3] = {WSTRIDE / 2, DM / 2, 2}; cuuint64_t strides[2] = {2 * WSTRIDE, WSTRIDE}; cuuint32_t box[3] = {16, 32, 2}; cuuint32_t es[3] = {1, 1, 1};
    enc(&p.w, CU_TENSOR_MAP_DATA_TYPE_BFLOAT16, 3, wp, dims, strides, box, es, CU_TENSOR_MAP_INTERLEAVE_NONE,
        CU_TENSOR_MAP_SWIZZLE_32B, CU_TENSOR_MAP_L2_PROMOTION_NONE, CU_TENSOR_MAP_FLOAT_OOB_FILL_NONE);
  }
  p.zero = 0;
  cudaGetSymbolAddress((void**)&p.flags, g_flags);
  for (int i = 0; i < 128; i++) {
    const int tp = i % NSLOT;
    p.pref[i] = tp < 32 ? (tp & 7) * 8 + (tp >> 3) : tp < 60 ? (1 + (tp - 32) % 7) * 8 + 4 + (tp - 32) / 7 : tp < 62 ? tp + 4 : tp - 58;
  }
  p.gate_w = gw; p.ak = ak; p.av = av; p.shk = shk; p.ssk = ssk; p.ssd = ssd; p.wukp = wuk; p.wuvp = wuv;

  mega_kernel<<<132, NTHREADS, SMEM_BYTES>>>(p);
}
```

```cpp
#include <cuda_runtime.h>
#include <cuda.h>
#include <cuda_bf16.h>
#include <stdint.h>

namespace {

constexpr int SEQ = 2048, DM = 1024, DC = 512, NH = 32, HD = 128;
constexpr int GR = 16384;
constexpr int NGR = 14;
constexpr int SM_BAR = NGR * GR;
constexpr int SM_GATE = SM_BAR + 512;
constexpr int SM_UST = SM_GATE + 512;
constexpr int SMEM_BYTES = SM_UST + 2048;
constexpr int NTHREADS = 384;
constexpr float SM_LIMIT = 1.0995116e12f;
constexpr float SM_LOW = 9.094947e-13f;
constexpr int CNS = 112;
constexpr int CN_SPARE = CNS, NTICK = 256 - 2 * CN_SPARE;
constexpr int XK = 57, YK = 62;
constexpr int STR = 61;
constexpr int P3G = 6, P3X = 12, P3Y = 10;
constexpr int NMAIN = 128;

constexpr int B_FULL = 0, B_FREE = 14, B_SLOT = 16, B_DONE = 17, B_EMPTY = 18, B_EV = 32, B_TICK = 36;
constexpr int V_TICK = 37, V_SLOT = 38;

__device__ __align__(1024) uint8_t g_kv[2 * 16 * 16 * 32768];
__device__ __align__(1024) uint8_t g_cimg[16 * NH * 32768];
__device__ __align__(1024) float g_gate[SEQ];
constexpr int WZ = 256, WPL = WZ + 4096, WBYTES = 2 * WPL + 32, WSTRIDE = 2 * WPL + 128;
__device__ __align__(1024) uint8_t g_w[DM * WSTRIDE];
__device__ __align__(32) unsigned g_flags[96 * 8];
constexpr int F_KV = 0, F_CTX = 16, F_U = 48, F_AD = 56, F_Y = 64, F_GATE = 72, F_EXIT = 73, F_TICK = 74;
constexpr int NSLOT = 66;
#define FLAG(i) (&g_flags[(i) * 8])
#define CLAIMP(i) (p.flags + (i) * 8 + 1)

constexpr int QFLUSH = 3;
constexpr int PSL = 200;
constexpr int US0 = 900;
constexpr int EROT = 6;
constexpr int RST = 2;
constexpr int UP0 = 4;
constexpr int UP1 = 11;
constexpr int X_DELAY = 800;
constexpr int X_D2 = 500;
constexpr int ROT = 8;
#define KV_ROW(idx, t) (8 * (t) + 2 * ((idx) & 3))
#define KV_HEAD(idx, t) ((idx) >> 2)

__device__ __forceinline__ uint32_t smem_u32(const void* p) { return (uint32_t)__cvta_generic_to_shared(p); }
__device__ __forceinline__ void mbar_init(uint32_t bar, int cnt) { asm volatile("mbarrier.init.shared::cta.b64 [%0], %1;" ::"r"(bar), "r"(cnt) : "memory"); }
__device__ __forceinline__ void mbar_expect_tx(uint32_t bar, uint32_t bytes) { asm volatile("mbarrier.arrive.expect_tx.shared::cta.b64 _, [%0], %1;" ::"r"(bar), "r"(bytes) : "memory"); }
__device__ __forceinline__ void mbar_arrive(uint32_t bar) { asm volatile("mbarrier.arrive.shared::cta.b64 _, [%0];" ::"r"(bar) : "memory"); }
__device__ __forceinline__ void mbar_arrive_cluster(uint32_t bar, uint32_t cta) {
  asm volatile("{\n.reg .b32 r;\nmapa.shared::cluster.u32 r, %0, %1;\nmbarrier.arrive.shared::cluster.b64 _, [r];\n}\n" ::"r"(bar), "r"(cta) : "memory");
}
__device__ __forceinline__ void send_both(uint32_t bar, uint32_t off, uint32_t v) {
#pragma unroll
  for (int r = 0; r < 2; r++)
    asm volatile("{\n.reg .b32 a, b;\nmapa.shared::cluster.u32 a, %0, %1;\nadd.u32 b, a, %3;\nst.async.shared::cluster.mbarrier::complete_tx::bytes.u32 [b], %2, [a];\n}\n"
                 ::"r"(bar), "r"(r), "r"(v), "r"(off) : "memory");
}
__device__ __forceinline__ bool mbar_try(uint32_t bar, uint32_t parity) {
  uint32_t ok;
  asm volatile("{\n.reg .pred p;\nmbarrier.try_wait.parity.shared::cta.b64 p, [%1], %2, 20000;\nselp.u32 %0, 1, 0, p;\n}\n" : "=r"(ok) : "r"(bar), "r"(parity) : "memory");
  return ok;
}
__device__ __forceinline__ bool mbar_test(uint32_t bar, uint32_t parity) {
  uint32_t ok;
  asm volatile("{\n.reg .pred p;\nmbarrier.test_wait.parity.shared::cta.b64 p, [%1], %2;\nselp.u32 %0, 1, 0, p;\n}\n" : "=r"(ok) : "r"(bar), "r"(parity) : "memory");
  return ok;
}
__device__ __forceinline__ void mbar_wait(uint32_t bar, uint32_t parity) {
  asm volatile("{\n.reg .pred p;\nWAIT_LOOP:\nbar.warp.sync -1;\nmbarrier.try_wait.parity.shared::cta.b64 p, [%0], %1;\n@!p bra WAIT_LOOP;\n}\n" ::"r"(bar), "r"(parity) : "memory");
}
__device__ __forceinline__ void mbar_wait1(uint32_t bar, uint32_t parity) {
  asm volatile("{\n.reg .pred p;\nWAIT_LOOP:\nbar.warp.sync -1;\nmbarrier.try_wait.parity.shared::cta.b64 p, [%0], %1, 4000;\n@!p bra WAIT_LOOP;\n}\n" ::"r"(bar), "r"(parity) : "memory");
}
constexpr uint64_t EV_NORMAL = 0x1000000000000000ull, EV_FIRST = 0x12F0000000000000ull;
__device__ __forceinline__ uint32_t ldg_stream(const uint32_t* p) {
  uint32_t r; asm volatile("ld.global.nc.L1::no_allocate.L2::cache_hint.b32 %0, [%1], %2;" : "=r"(r) : "l"(p), "l"(EV_FIRST)); return r;
}
#define TMA_LD "cp.async.bulk.tensor."
#define TMA_MB ".shared::cluster.global.mbarrier::complete_tx::bytes"
__device__ __forceinline__ void tma2d(uint32_t dst, const CUtensorMap* tm, int c0, int c1, uint32_t bar) {
  asm volatile(TMA_LD "2d" TMA_MB " [%0], [%1, {%3, %4}], [%2];" ::"r"(dst), "l"(tm), "r"(bar), "r"(c0), "r"(c1) : "memory");
}
template <bool ONCE = false> __device__ __forceinline__ void tma2d_mc(uint32_t dst, const CUtensorMap* tm, int c0, int c1, uint32_t bar) {
  if (ONCE) asm volatile(TMA_LD "2d" TMA_MB ".multicast::cluster.L2::cache_hint [%0], [%1, {%3, %4}], [%2], %5, %6;"
                         ::"r"(dst), "l"(tm), "r"(bar), "r"(c0), "r"(c1), "h"((uint16_t)3), "l"(EV_FIRST) : "memory");
  else asm volatile(TMA_LD "2d" TMA_MB ".multicast::cluster [%0], [%1, {%3, %4}], [%2], %5;"
                    ::"r"(dst), "l"(tm), "r"(bar), "r"(c0), "r"(c1), "h"((uint16_t)3) : "memory");
}
__device__ __forceinline__ void tma2d_p(uint32_t dst, const CUtensorMap* tm, int c0, int c1, uint32_t bar, bool once) {
  asm volatile(TMA_LD "2d" TMA_MB ".L2::cache_hint [%0], [%1, {%3, %4}], [%2], %5;" ::"r"(dst), "l"(tm), "r"(bar), "r"(c0), "r"(c1), "l"(once ? EV_FIRST : EV_NORMAL) : "memory");
}
__device__ __forceinline__ void tma3d_mc_p(uint32_t dst, const CUtensorMap* tm, int c0, int c1, int c2, uint32_t bar, bool once) {
  asm volatile(TMA_LD "3d" TMA_MB ".multicast::cluster.L2::cache_hint [%0], [%1, {%3, %4, %5}], [%2], %6, %7;"
               ::"r"(dst), "l"(tm), "r"(bar), "r"(c0), "r"(c1), "r"(c2), "h"((uint16_t)3), "l"(once ? EV_FIRST : EV_NORMAL) : "memory");
}
template <bool ONCE = false> __device__ __forceinline__ void tma3d(uint32_t dst, const CUtensorMap* tm, int c0, int c1, int c2, uint32_t bar) {
  if (ONCE) asm volatile(TMA_LD "3d" TMA_MB ".L2::cache_hint [%0], [%1, {%3, %4, %5}], [%2], %6;" ::"r"(dst), "l"(tm), "r"(bar), "r"(c0), "r"(c1), "r"(c2), "l"(EV_FIRST) : "memory");
  else
  asm volatile(TMA_LD "3d" TMA_MB " [%0], [%1, {%3, %4, %5}], [%2];" ::"r"(dst), "l"(tm), "r"(bar), "r"(c0), "r"(c1), "r"(c2) : "memory");
}
__device__ __forceinline__ void tma3d_mc(uint32_t dst, const CUtensorMap* tm, int c0, int c1, int c2, uint32_t bar) {
  asm volatile(TMA_LD "3d" TMA_MB ".multicast::cluster [%0], [%1, {%3, %4, %5}], [%2], %6;"
               ::"r"(dst), "l"(tm), "r"(bar), "r"(c0), "r"(c1), "r"(c2), "h"((uint16_t)3) : "memory");
}
template <bool ONCE = false> __device__ __forceinline__ void bulk_g2s(uint32_t dst, const void* src, uint32_t bytes, uint32_t bar) {
  if (ONCE) asm volatile("cp.async.bulk" TMA_MB ".L2::cache_hint [%0], [%1], %2, [%3], %4;" ::"r"(dst), "l"(src), "r"(bytes), "r"(bar), "l"(EV_FIRST) : "memory");
  else asm volatile("cp.async.bulk" TMA_MB " [%0], [%1], %2, [%3];" ::"r"(dst), "l"(src), "r"(bytes), "r"(bar) : "memory");
}
__device__ __forceinline__ void tma2d_store(const CUtensorMap* tm, uint32_t src, int c0, int c1) {
  asm volatile("cp.async.bulk.tensor.2d.global.shared::cta.bulk_group [%0, {%2, %3}], [%1];" ::"l"(tm), "r"(src), "r"(c0), "r"(c1) : "memory");
}
__device__ __forceinline__ void prefetch_tm(const CUtensorMap* tm) { asm volatile("prefetch.tensormap [%0];" ::"l"(tm) : "memory"); }
__device__ __forceinline__ void wg_fence() { asm volatile("wgmma.fence.sync.aligned;" ::: "memory"); }
__device__ __forceinline__ void wg_commit() { asm volatile("wgmma.commit_group.sync.aligned;" ::: "memory"); }
template <int N> __device__ __forceinline__ void wg_wait() { asm volatile("wgmma.wait_group.sync.aligned %0;" ::"n"(N) : "memory"); }
__device__ __forceinline__ void bar_sync(int id, int n) { asm volatile("bar.sync %0, %1;" ::"r"(id), "r"(n) : "memory"); }
__device__ __forceinline__ void bar_arrive(int id, int n) { asm volatile("bar.arrive %0, %1;" ::"r"(id), "r"(n) : "memory"); }
__device__ __forceinline__ void fence_async_smem() { asm volatile("fence.proxy.async.shared::cta;" ::: "memory"); }
__device__ __forceinline__ void fence_async_all() { asm volatile("fence.proxy.async.global;" ::: "memory"); }
__device__ __forceinline__ uint32_t pack_bf16(float lo, float hi) { uint32_t r; asm("cvt.rn.bf16x2.f32 %0, %1, %2;" : "=r"(r) : "f"(hi), "f"(lo)); return r; }
__device__ __forceinline__ float ex2(float x) { float r; asm("ex2.approx.ftz.f32 %0, %1;" : "=f"(r) : "f"(x)); return r; }
__device__ __forceinline__ float rcp(float x) { float r; asm("rcp.approx.ftz.f32 %0, %1;" : "=f"(r) : "f"(x)); return r; }
__device__ __forceinline__ void flag_wait(const unsigned* f, unsigned target) {
  unsigned v;
  do { asm volatile("ld.acquire.gpu.global.u32 %0, [%1];" : "=r"(v) : "l"(f) : "memory"); } while (__any_sync(0xffffffffu, v < target));
}
__device__ __forceinline__ bool elect() {
  uint32_t r;
  asm volatile("{\n.reg .pred p;\nelect.sync _|p, -1;\nselp.u32 %0, 1, 0, p;\n}\n" : "=r"(r));
  return r;
}
__device__ __forceinline__ void fence_release() { asm volatile("fence.release.gpu;" ::: "memory"); }
__device__ __forceinline__ void flag_add(unsigned* f) { asm volatile("red.relaxed.gpu.global.inc.u32 [%0], 0x7fffffff;" ::"l"(f) : "memory"); }
__device__ __forceinline__ void cluster_arrive() { asm volatile("barrier.cluster.arrive.relaxed.aligned;" ::: "memory"); }
__device__ __forceinline__ void cluster_wait() { asm volatile("barrier.cluster.wait.aligned;" ::: "memory"); }
__device__ __forceinline__ uint32_t hmul2(uint32_t a, uint32_t b) { uint32_t r; asm("mul.rn.bf16x2 %0, %1, %2;" : "=r"(r) : "r"(a), "r"(b)); return r; }
__device__ __forceinline__ uint32_t hadd2(uint32_t a, uint32_t b) { uint32_t r; asm("add.rn.bf16x2 %0, %1, %2;" : "=r"(r) : "r"(a), "r"(b)); return r; }
__device__ __forceinline__ uint32_t hfma2(uint32_t a, uint32_t b, uint32_t c) { uint32_t r; asm("fma.rn.bf16x2 %0, %1, %2, %3;" : "=r"(r) : "r"(a), "r"(b), "r"(c)); return r; }
__device__ __forceinline__ uint32_t lds32(uint32_t a) { uint32_t r; asm volatile("ld.shared.b32 %0, [%1];" : "=r"(r) : "r"(a) : "memory"); return r; }
__device__ __forceinline__ uint4 lds128(uint32_t a) { uint4 r; asm volatile("ld.shared.v4.b32 {%0,%1,%2,%3}, [%4];" : "=r"(r.x), "=r"(r.y), "=r"(r.z), "=r"(r.w) : "r"(a) : "memory"); return r; }
__device__ __forceinline__ uint32_t desc_k(uint32_t addr) { return ((addr & 0x3FFFF) >> 4) | (1u << 16); }
template <int LBO> __device__ __forceinline__ uint32_t desc_mn(uint32_t addr) { return ((addr & 0x3FFFF) >> 4) | ((uint32_t)(LBO >> 4) << 16); }
#define DHI "0x40000040"

#define R8(d, o) "+f"(d[o]), "+f"(d[o + 1]), "+f"(d[o + 2]), "+f"(d[o + 3]), "+f"(d[o + 4]), "+f"(d[o + 5]), "+f"(d[o + 6]), "+f"(d[o + 7])
#define R32(d, o) R8(d, o), R8(d, o + 8), R8(d, o + 16), R8(d, o + 24)
#define R64(d, o) R32(d, o), R32(d, o + 32)
#define L64 "%0,%1,%2,%3,%4,%5,%6,%7,%8,%9,%10,%11,%12,%13,%14,%15,%16,%17,%18,%19,%20,%21,%22,%23,%24,%25,%26,%27,%28,%29,%30,%31," \
            "%32,%33,%34,%35,%36,%37,%38,%39,%40,%41,%42,%43,%44,%45,%46,%47,%48,%49,%50,%51,%52,%53,%54,%55,%56,%57,%58,%59,%60,%61,%62,%63"
#define L128 L64 ",%64,%65,%66,%67,%68,%69,%70,%71,%72,%73,%74,%75,%76,%77,%78,%79,%80,%81,%82,%83,%84,%85,%86,%87,%88,%89,%90,%91,%92,%93,%94,%95," \
            "%96,%97,%98,%99,%100,%101,%102,%103,%104,%105,%106,%107,%108,%109,%110,%111,%112,%113,%114,%115,%116,%117,%118,%119,%120,%121,%122,%123,%124,%125,%126,%127"

template <int TB> __device__ __forceinline__ void mma_ss_n128(float (&d)[64], uint32_t da, uint32_t db) {
  asm volatile("{\n.reg .b64 da, db;\nmov.b64 da, {%64, " DHI "};\nmov.b64 db, {%65, " DHI "};\n"
               "wgmma.mma_async.sync.aligned.m64n128k16.f32.bf16.bf16 {" L64 "}, da, db, 1, 1, 1, 0, %66;\n}\n"
               : R64(d, 0) : "r"(da), "r"(db), "n"(TB));
}
template <int TB> __device__ __forceinline__ void mma_rs_n128(float (&d)[64], uint32_t a0, uint32_t a1, uint32_t a2, uint32_t a3, uint32_t db, int sd) {
  asm volatile("{\n.reg .pred p;\n.reg .b64 db;\nsetp.ne.b32 p, %69, 0;\nmov.b64 db, {%68, " DHI "};\n"
               "wgmma.mma_async.sync.aligned.m64n128k16.f32.bf16.bf16 {" L64 "}, {%64,%65,%66,%67}, db, p, 1, 1, %70;\n}\n"
               : R64(d, 0) : "r"(a0), "r"(a1), "r"(a2), "r"(a3), "r"(db), "r"(sd), "n"(TB));
}
template <int TB> __device__ __forceinline__ void mma_ss_n256(float (&d)[128], uint32_t da, uint32_t db) {
  asm volatile("{\n.reg .b64 da, db;\nmov.b64 da, {%128, " DHI "};\nmov.b64 db, {%129, " DHI "};\n"
               "wgmma.mma_async.sync.aligned.m64n256k16.f32.bf16.bf16 {" L128 "}, da, db, 1, 1, 1, 0, %130;\n}\n"
               : R64(d, 0), R64(d, 64) : "r"(da), "r"(db), "n"(TB));
}
#define W8(d, o) "=f"(d[o]), "=f"(d[o + 1]), "=f"(d[o + 2]), "=f"(d[o + 3]), "=f"(d[o + 4]), "=f"(d[o + 5]), "=f"(d[o + 6]), "=f"(d[o + 7])
#define W32(d, o) W8(d, o), W8(d, o + 8), W8(d, o + 16), W8(d, o + 24)
#define W64(d, o) W32(d, o), W32(d, o + 32)
template <int TB> __device__ __forceinline__ void mma_ss_n128_init(float (&d)[64], uint32_t da, uint32_t db) {
  asm volatile("{\n.reg .b64 da, db;\nmov.b64 da, {%64, " DHI "};\nmov.b64 db, {%65, " DHI "};\n"
               "wgmma.mma_async.sync.aligned.m64n128k16.f32.bf16.bf16 {" L64 "}, da, db, 0, 1, 1, 0, %66;\n}\n"
               : W64(d, 0) : "r"(da), "r"(db), "n"(TB));
}
template <int TB> __device__ __forceinline__ void mma_rs_n128_init(float (&d)[64], uint32_t a0, uint32_t a1, uint32_t a2, uint32_t a3, uint32_t db) {
  asm volatile("{\n.reg .b64 db;\nmov.b64 db, {%68, " DHI "};\n"
               "wgmma.mma_async.sync.aligned.m64n128k16.f32.bf16.bf16 {" L64 "}, {%64,%65,%66,%67}, db, 0, 1, 1, %69;\n}\n"
               : W64(d, 0) : "r"(a0), "r"(a1), "r"(a2), "r"(a3), "r"(db), "n"(TB));
}
template <int TB> __device__ __forceinline__ void mma_ss_n256_init(float (&d)[128], uint32_t da, uint32_t db) {
  asm volatile("{\n.reg .b64 da, db;\nmov.b64 da, {%128, " DHI "};\nmov.b64 db, {%129, " DHI "};\n"
               "wgmma.mma_async.sync.aligned.m64n256k16.f32.bf16.bf16 {" L128 "}, da, db, 0, 1, 1, 0, %130;\n}\n"
               : W64(d, 0), W64(d, 64) : "r"(da), "r"(db), "n"(TB));
}
#define L32 "%0,%1,%2,%3,%4,%5,%6,%7,%8,%9,%10,%11,%12,%13,%14,%15,%16,%17,%18,%19,%20,%21,%22,%23,%24,%25,%26,%27,%28,%29,%30,%31"
template <bool INIT> __device__ __forceinline__ void mma_rs_n64(float (&d)[32], uint32_t a0, uint32_t a1, uint32_t a2, uint32_t a3, uint32_t db) {
  if (INIT) asm volatile("{\n.reg .b64 db;\nmov.b64 db, {%36, " DHI "};\n"
               "wgmma.mma_async.sync.aligned.m64n64k16.f32.bf16.bf16 {" L32 "}, {%32,%33,%34,%35}, db, 0, 1, 1, 0;\n}\n"
               : W32(d, 0) : "r"(a0), "r"(a1), "r"(a2), "r"(a3), "r"(db));
  else asm volatile("{\n.reg .b64 db;\nmov.b64 db, {%36, " DHI "};\n"
               "wgmma.mma_async.sync.aligned.m64n64k16.f32.bf16.bf16 {" L32 "}, {%32,%33,%34,%35}, db, 1, 1, 1, 0;\n}\n"
               : R32(d, 0) : "r"(a0), "r"(a1), "r"(a2), "r"(a3), "r"(db));
}
#define L16 "%0,%1,%2,%3,%4,%5,%6,%7,%8,%9,%10,%11,%12,%13,%14,%15"
template <int O, bool INIT> __device__ __forceinline__ void mma_rs_n32(float (&d)[128], uint32_t a0, uint32_t a1, uint32_t a2, uint32_t a3, uint32_t db) {
  if (INIT) asm volatile("{\n.reg .b64 db;\nmov.b64 db, {%20, 0x00000008};\n"
               "wgmma.mma_async.sync.aligned.m64n32k16.f32.bf16.bf16 {" L16 "}, {%16,%17,%18,%19}, db, 0, 1, 1, 0;\n}\n"
               : W8(d, O), W8(d, O + 8) : "r"(a0), "r"(a1), "r"(a2), "r"(a3), "r"(db));
  else asm volatile("{\n.reg .b64 db;\nmov.b64 db, {%20, 0x00000008};\n"
               "wgmma.mma_async.sync.aligned.m64n32k16.f32.bf16.bf16 {" L16 "}, {%16,%17,%18,%19}, db, 1, 1, 1, 0;\n}\n"
               : R8(d, O), R8(d, O + 8) : "r"(a0), "r"(a1), "r"(a2), "r"(a3), "r"(db));
}
template <int S, int J> __device__ __forceinline__ void conv_step(float (&d)[128], const uint32_t (&a)[64], uint32_t db) {
  if constexpr (J >= 0 && J >= (S >> 1)) {
    mma_rs_n32<16 * J, S == 0>(d, a[4 * S], a[4 * S + 1], a[4 * S + 2], a[4 * S + 3], db + (uint32_t)((2 * J - S) * 16));
    conv_step<S, J - 1>(d, a, db);
  }
}
__device__ __forceinline__ void mma_ss_n8(float (&d)[4], uint32_t da, uint32_t db) {
  asm volatile("{\n.reg .b64 da, db;\nmov.b64 da, {%4, " DHI "};\nmov.b64 db, {%5, 0x00000008};\n"
               "wgmma.mma_async.sync.aligned.m64n8k16.f32.bf16.bf16 {%0,%1,%2,%3}, da, db, 1, 1, 1, 0, 0;\n}\n"
               : "+f"(d[0]), "+f"(d[1]), "+f"(d[2]), "+f"(d[3]) : "r"(da), "r"(db));
}
template <int N> __device__ __forceinline__ void reg_fence(float (&d)[N]) {
#pragma unroll
  for (int i = 0; i < N; i++) asm volatile("" : "+f"(d[i])::"memory");
}
template <int N> __device__ __forceinline__ void reg_fence(uint32_t (&d)[N]) {
#pragma unroll
  for (int i = 0; i < N; i++) asm volatile("" : "+r"(d[i])::"memory");
}

struct __align__(64) Params {
  unsigned* flags;
  int zero;
  uint8_t pref[128];
  const __nv_bfloat16 *gate_w, *ak, *av, *shk, *ssk, *ssd, *wukp, *wuvp;
  CUtensorMap x, c, wq, wuk, wuv, wo, x3, y3, out, w;
};

template <int O, int N, int M> __device__ __forceinline__ void pack_frag(const float (&acc)[N], uint32_t (&pk)[M]) {
#pragma unroll
  for (int i = 0; i < 32; i++) pk[i] = pack_bf16(acc[O + 2 * i], acc[O + 2 * i + 1]);
}
template <int J0 = 0, int J1 = 8, int M> __device__ __forceinline__ void stsm_frag(const uint32_t (&pk)[M], uint32_t a) {
#pragma unroll
  for (int jj = J0; jj < J1; jj++)
    asm volatile("stmatrix.sync.aligned.m8n8.x4.shared.b16 [%0], {%1,%2,%3,%4};" ::"r"((a ^ ((jj & 3) << 5)) + (jj >> 2) * 16384),
                 "r"(pk[4 * jj]), "r"(pk[4 * jj + 1]), "r"(pk[4 * jj + 2]), "r"(pk[4 * jj + 3]) : "memory");
}

template <int N> __device__ __forceinline__ void store_scaled(const float (&acc)[N], float s0, float s1, uint32_t a, uint32_t never_zero) {
  float t[8];
#pragma unroll
  for (int jj = 0; jj < 8; jj++) {
    float v = acc[8 * jj] * s0;
    if (jj >= RST) {
      v = t[jj - RST];
      asm("{\n.reg .pred p;\nsetp.ne.u32 p, %3, 0;\n@p mul.f32 %0, %1, %2;\n}\n" : "+f"(v) : "f"(acc[8 * jj]), "f"(s0), "r"(never_zero));
    }
    const uint32_t q = pack_bf16(v, acc[8 * jj + 1] * s0);
    t[jj] = __uint_as_float(q);
    asm volatile("stmatrix.sync.aligned.m8n8.x4.shared.b16 [%0], {%1,%2,%3,%4};" ::"r"((a ^ ((jj & 3) << 5)) + (jj >> 2) * 16384), "r"(q),
                 "r"(pack_bf16(acc[8 * jj + 2] * s1, acc[8 * jj + 3] * s1)), "r"(pack_bf16(acc[8 * jj + 4] * s0, acc[8 * jj + 5] * s0)),
                 "r"(pack_bf16(acc[8 * jj + 6] * s1, acc[8 * jj + 7] * s1)) : "memory");
  }
}

struct Cons {
  uint32_t sb;
  uint32_t pf;
  int wg, tid;
  __device__ __forceinline__ void wait_full(int g) { mbar_wait(sb + SM_BAR + (B_FULL + g) * 8, (pf >> g) & 1); pf ^= 1u << g; }
  uint32_t relb;
  __device__ __forceinline__ void release(int g, int n) {
    if (tid < 2 * n) asm volatile("mbarrier.arrive.shared::cluster.b64 _, [%0];" ::"r"(relb + g * 8) : "memory");
  }
  __device__ __forceinline__ void turn_begin() { bar_sync(1 + wg, 256); }
  __device__ __forceinline__ void turn_end() { bar_arrive(2 - wg, 256); }
  __device__ __forceinline__ void staged() { __syncwarp(); if ((tid & 31) == 0) mbar_arrive(sb + SM_BAR + (B_EV + wg) * 8); }
  int zero;
  uint32_t pfree;
  __device__ __forceinline__ void wait_stage_free() { mbar_wait(sb + SM_BAR + (B_FREE + wg) * 8, pfree); pfree ^= 1; }
  __device__ __forceinline__ bool try_full(int g) { return mbar_test(sb + SM_BAR + (B_FULL + g) * 8, (pf >> g) & 1); }
};

constexpr float SM_C = 0.08838834764831845f * 1.4426950408889634f;
struct SoftState { float m0, m1, l0, l1; int shifted; };
__device__ __forceinline__ void ex2_rot(float& t, float s, uint32_t never_zero) {
  asm("{\n.reg .pred p;\nsetp.ne.u32 p, %2, 0;\n@p ex2.approx.ftz.f32 %0, %1;\n}\n" : "+f"(t) : "f"(s), "r"(never_zero));
}
__device__ __forceinline__ void pin(float a, uint32_t never_zero) {
  asm volatile("{\n.reg .pred p;\nsetp.eq.u32 p, %1, 0;\n@p st.shared.f32 [%1], %0;\n}\n" ::"f"(a), "r"(never_zero) : "memory");
}
template <int O, int N> __device__ __forceinline__ void reg_fence_part(uint32_t (&d)[32]) {
#pragma unroll
  for (int i = O; i < O + N; i++) asm volatile("" : "+r"(d[i])::"memory");
}
template <int Q, int W, int N> __device__ __forceinline__ void exp_quarter(const float (&S)[N], uint32_t (&P)[32], float (&t)[ROT], float& s0, float& s1, uint32_t nz) {
#pragma unroll
  for (int i = 8 * Q; i < 8 * Q + 8; i++) {
    float& a = t[(2 * i) % ROT];
    float& b = t[(2 * i + 1) % ROT];
    if (2 * i < ROT) { a = ex2(S[2 * i]); b = ex2(S[2 * i + 1]); }
    else { ex2_rot(a, S[2 * i], nz); ex2_rot(b, S[2 * i + 1], nz); }
    if (i < 2) { if (i) s1 = a + b; else s0 = a + b; }
    else if (i & 1) { s1 += a; s1 += b; } else { s0 += a; s0 += b; }
    if (i == 8 * Q) { pin(Q ? s1 : s0, nz); wg_wait<W>(); reg_fence_part<8 * Q, 8>(P); }
    P[i] = pack_bf16(a, b);
  }
}
template <int N> __device__ __forceinline__ void shift_scores(float (&S)[N], float d0, float d1) {
#pragma unroll
  for (int i = 0; i < N; i++) S[i] -= (i & 2) ? d1 : d0;
}
__device__ __forceinline__ bool soft_high(float s0, float s1, float lim = SM_LIMIT) { return s0 > lim || s1 > lim; }
__device__ __forceinline__ bool soft_unsafe(float s0, float s1, bool first) {
  uint32_t b0 = __ballot_sync(0xffffffffu, s0 >= SM_LOW), b1 = __ballot_sync(0xffffffffu, s1 >= SM_LOW);
  b0 |= b0 >> 1; b0 |= b0 >> 2; b1 |= b1 >> 1; b1 |= b1 >> 2;
  return __any_sync(0xffffffffu, soft_high(s0, s1)) || (first && (b0 & b1 & 0x11111111u) != 0x11111111u);
}
template <int N> __device__ __forceinline__ void soft_fix(const float (&S)[N], float (&O)[64], SoftState& z, bool first, float& d0, float& d1) {
  d0 = d1 = first ? -INFINITY : 0.f;
#pragma unroll
  for (int j = 0; j < N / 4; j++) { d0 = fmaxf(d0, fmaxf(S[4 * j], S[4 * j + 1])); d1 = fmaxf(d1, fmaxf(S[4 * j + 2], S[4 * j + 3])); }
  d0 = fmaxf(d0, __shfl_xor_sync(0xffffffffu, d0, 1)); d1 = fmaxf(d1, __shfl_xor_sync(0xffffffffu, d1, 1));
  d0 = fmaxf(d0, __shfl_xor_sync(0xffffffffu, d0, 2)); d1 = fmaxf(d1, __shfl_xor_sync(0xffffffffu, d1, 2));
  const float sc0 = ex2(-fmaxf(d0, 0.f)), sc1 = ex2(-fmaxf(d1, 0.f));
  z.m0 += d0; z.m1 += d1; z.l0 *= sc0; z.l1 *= sc1; z.shifted = 1;
#pragma unroll
  for (int j = 0; j < 16; j++) { O[4 * j] *= sc0; O[4 * j + 1] *= sc0; O[4 * j + 2] *= sc1; O[4 * j + 3] *= sc1; }
}
template <int N> __device__ __forceinline__ void mask_diag(float (&S)[N], float nd) {
  asm volatile("" : "+f"(nd));
#pragma unroll
  for (int i = 0; i < 32; i++) {
    const float beyond = __saturatef(nd + (float)(8 * (i >> 2) + (i & 1) - 4 * (i & 2)));
    S[N - 32 + i] = fmaf(beyond, -3.0e38f, S[N - 32 + i]);
  }
}
__device__ __forceinline__ float quad_sum(float v) {
  v += __shfl_xor_sync(0xffffffffu, v, 1);
  v += __shfl_xor_sync(0xffffffffu, v, 2);
  return v;
}
__device__ __forceinline__ void issue_qk(float (&S)[64], const uint32_t (&Q)[32], uint32_t dk) {
  mma_rs_n128_init<0>(S, Q[0], Q[1], Q[2], Q[3], dk);
#pragma unroll
  for (int s = 1; s < 8; s++) mma_rs_n128<0>(S, Q[4 * s], Q[4 * s + 1], Q[4 * s + 2], Q[4 * s + 3], dk + (s >> 2) * 1024 + (s & 3) * 2, 1);
}
__device__ __forceinline__ void issue_qk(float (&S)[32], const uint32_t (&Q)[32], uint32_t dk) {
  mma_rs_n64<true>(S, Q[0], Q[1], Q[2], Q[3], dk);
#pragma unroll
  for (int s = 1; s < 8; s++) mma_rs_n64<false>(S, Q[4 * s], Q[4 * s + 1], Q[4 * s + 2], Q[4 * s + 3], dk + (s >> 2) * 1024 + (s & 3) * 2);
}
__device__ __forceinline__ void load_q(uint32_t (&Q)[32], uint32_t a) {
  __syncwarp();
#pragma unroll
  for (int jj = 0; jj < 8; jj++)
    asm volatile("ldmatrix.sync.aligned.m8n8.x4.shared.b16 {%0,%1,%2,%3}, [%4];" : "=r"(Q[4 * jj]), "=r"(Q[4 * jj + 1]), "=r"(Q[4 * jj + 2]), "=r"(Q[4 * jj + 3])
                 : "r"((a ^ ((jj & 3) << 5)) + (jj >> 2) * 16384) : "memory");
}
template <int H> __device__ __forceinline__ void issue_pv(float (&O)[64], const uint32_t (&P)[32], uint32_t dv, int acc, bool on) {
  if (on) {
#pragma unroll
    for (int s = 4 * H; s < 4 * H + 4; s++) {
      mma_rs_n128<1>(O, P[4 * s], P[4 * s + 1], P[4 * s + 2], P[4 * s + 3], dv + s * 128, s != 0 ? 1 : acc);
      if (s & 1) wg_commit();
    }
  } else { wg_commit(); wg_commit(); }
}
constexpr uint32_t DG = GR >> 4;
__device__ __forceinline__ void stage_q2(Cons& c, const float (&O)[64], uint32_t (&P)[32], uint32_t stg) {
  wg_commit(); wg_commit(); wg_commit(); wg_commit();
  c.turn_end();
  pack_frag<0>(O, P);
  stsm_frag(P, stg);
}
__device__ __forceinline__ void attn_half(Cons& c, float (&O)[64], uint32_t (&P)[32], uint32_t (&Q)[32], bool nextq, uint32_t stg, SoftState& z, uint32_t dkk, uint32_t dv0, float dmask, int last) {
  float S[32];
  c.turn_begin();
  wg_fence();
  issue_qk(S, Q, dkk + (last ? 8 : 2) * DG);
  wg_commit();
  issue_pv<0>(O, P, dv0 + 10 * DG, 1, last);
  issue_pv<1>(O, P, dv0 + 10 * DG, 1, last);
  c.turn_end();
  c.wait_full(last ? 12 : 4);
  wg_wait<4>();
  reg_fence(S);
  c.release(last ? 8 : 2, 2);
  reg_fence(Q);
  if (nextq) load_q(Q, stg);
  if (last) bar_sync(6, 256);
  mask_diag(S, dmask);
  float s0, s1, d0 = z.m0, d1 = z.m1;
#pragma unroll 1
  for (int pass = 0;; pass++) {
    if (z.shifted) shift_scores(S, d0, d1);
    float tr[ROT];
    exp_quarter<0, 3>(S, P, tr, s0, s1, c.sb);
    exp_quarter<1, 2>(S, P, tr, s0, s1, c.sb);
    pin(s1, c.sb); wg_wait<0>(); reg_fence_part<16, 16>(P); reg_fence(O);
    if (!soft_unsafe(s0, s1, !last) || pass) break;
    soft_fix(S, O, z, !last, d0, d1);
  }
  z.l0 += s0; z.l1 += s1;
  c.release(10, last ? 2 : 0);
  if (!last) c.wait_full(6);
}

template <int V> struct IC { static constexpr int value = V; };
__device__ __forceinline__ int conv_next(int g, bool spare) { return g >= NGR - 2 ? g - (NGR - 4) : !spare && g == 4 ? 1 : g + 2; }
__device__ __forceinline__ void conv_final(uint32_t rb, uint32_t yb, bool on) {
  const uint4 q0 = lds128(rb), q1 = lds128(rb + 4096), q2 = lds128(rb + 8192), q3 = lds128(rb + 12288);
  auto fin = [&](uint32_t x0, uint32_t x1, uint32_t x2, uint32_t x3) { return hadd2(hadd2(x0, x1), hadd2(x2, x3)); };
  asm volatile("{\n.reg .pred p;\nsetp.ne.b32 p, %5, 0;\n@p st.shared.v4.b32 [%0], {%1,%2,%3,%4};\n}\n" ::"r"(yb), "r"(fin(q0.x, q1.x, q2.x, q3.x)),
               "r"(fin(q0.y, q1.y, q2.y, q3.y)), "r"(fin(q0.z, q1.z, q2.z, q3.z)), "r"(fin(q0.w, q1.w, q2.w, q3.w)), "r"((int)on) : "memory");
}
__device__ __forceinline__ void conv_tasks(Cons& c, const Params& p, int ntask, bool spare, int ch, int chstep, int c5, uint32_t dd, uint32_t dkk, int w, int lane) {
  const uint32_t sb = c.sb;
  int g = 2 + c.wg;
  uint32_t rb = sb + g * GR;
  const uint32_t yb = sb + c.wg * 8192 + c.tid * 16;
  const int gt = 8 * w + (lane >> 2) + (lane & 3);
  uint32_t a[64], hb;
  auto lda = [&](int s) {
    a[4 * s] = lds32(hb + s * 256); a[4 * s + 1] = lds32(hb + s * 256 + 128);
    a[4 * s + 2] = lds32(hb + s * 256 + 16); a[4 * s + 3] = lds32(hb + s * 256 + 144);
  };
  auto first_a = [&]() {
    hb = sb + g * GR + WBYTES - 28 + gt * 4;
    lda(0); lda(15);
  };
  c.wait_full(g);
  first_a();
#pragma unroll 1
  for (int i = 0; i < ntask; i++) {
    const uint32_t base = sb + g * GR;
    lda(1); lda(14);
    a[0] = hadd2(a[0], gt == 7 ? dd : 0u); a[2] = hadd2(a[2], gt == 3 ? dd : 0u);
    float acc[128];
    const uint32_t db = dkk + ((WPL / 16 - 1) << 16) + g * DG + WZ / 16;
    c.turn_begin();
    auto pair = [&](auto kc) {
      constexpr int k = decltype(kc)::value;
      if (k < 7) wg_fence();
      if (k == 6) c.turn_end();
      conv_step<k, 7>(acc, a, db);
      conv_step<15 - k, 7>(acc, a, db);
      if (k < 6) { lda(k + 2); lda(13 - k); }
      if (k == 0) conv_final(rb, yb, i > 0);
      if (k == 1) {
        conv_final(rb + 2048, yb + 2048, i > 0);
        __syncwarp();
        if (lane == 0 && i > 0) mbar_arrive(sb + SM_BAR + (B_EV + c.wg) * 8);
      }
      if (k == 6) dd = __bfloat16_as_ushort(p.ssd[(ch + chstep + (i == 1 ? c5 : 0)) & (DM - 1)]);
    };
    pair(IC<0>()); pair(IC<1>()); pair(IC<2>()); pair(IC<3>()); pair(IC<4>()); pair(IC<5>()); pair(IC<6>()); pair(IC<7>());
    wg_commit();
    g = conv_next(g, spare);
    ch += chstep;
    rb = base + c.tid * 16;
    if (i + 1 < ntask) c.wait_full(g);
    const bool fr = mbar_test(sb + SM_BAR + (B_FREE + c.wg) * 8, c.pfree);
    wg_wait<0>();
    reg_fence(acc);
    reg_fence(a);
    bar_sync(3 + c.wg, 128);
    first_a();
    const int tw = (lane & 3) + w;
    const uint32_t xb = base + w * 4096 + tw * 32 + (lane >> 2) * 4;
    [[maybe_unused]] float t0[EROT + 1];
#pragma unroll
    for (int j = 0; j < 32; j++) {
      uint32_t ad = xb + j * 128;
      float v0 = acc[4 * j], v1 = acc[4 * j + 1];
      if (EROT && j > EROT) {
        v0 = t0[j % (EROT + 1)];
        asm("{\n.reg .pred p;\nsetp.ne.u32 p, %3, 0;\n@p add.f32 %0, %1, %2;\n}\n" : "+f"(v0) : "f"(acc[4 * j]), "f"(acc[j > 0 ? 4 * j - 2 : 0]), "r"(sb));
      } else if (j > 0) v0 += acc[j > 0 ? 4 * j - 2 : 0];
      if (j > 0) v1 += acc[j > 0 ? 4 * j - 1 : 0];
      uint32_t v = pack_bf16(v0, v1);
      t0[j % (EROT + 1)] = __uint_as_float(v);
      if (j == 31 && tw >= 4) { v = 0; ad -= 4096; }
      asm volatile("st.shared.b32 [%0], %1;" ::"r"(ad), "r"(v) : "memory");
    }
    if (!fr) c.wait_stage_free(); else c.pfree ^= 1;
  }
  bar_sync(3 + c.wg, 128);
  conv_final(rb, yb, true);
  conv_final(rb + 2048, yb + 2048, true);
  c.staged();
}

__global__ void __cluster_dims__(2, 1, 1) __launch_bounds__(NTHREADS, 1) mega_kernel(const __grid_constant__ Params p) {
  extern __shared__ __align__(1024) uint8_t smem_raw[];
  const uint32_t sb = smem_u32(smem_raw);
  if (threadIdx.x - 64 < 32) { prefetch_tm(&p.c); prefetch_tm(&p.wuk + (blockIdx.x & 1)); }
  const int wgi = __shfl_sync(0xffffffffu, threadIdx.x >> 7, 0);
  const int warp = __shfl_sync(0xffffffffu, threadIdx.x >> 5, 0);
  const uint32_t rank = blockIdx.x & 1;
  int slot;
  {
    uint32_t smid; asm volatile("mov.u32 %0, %smid;" : "=r"(smid));
    slot = p.pref[((smid >> 1) + (threadIdx.x & (smid >> 16))) & 127];
  }
  if (warp >= 3) {
    if (elect()) {
#pragma unroll
      for (int k = 0; k < 4; k++) mbar_init(sb + SM_BAR + ((warp - 3) * 4 + k) * 8, k == 1 && warp == 7 ? 11 : warp < (k ? 7 : 8) ? 1 : 4);
      if (warp == 7) { mbar_init(sb + SM_BAR + B_TICK * 8, 1); mbar_expect_tx(sb + SM_BAR + B_SLOT * 8, 12); mbar_expect_tx(sb + SM_BAR + B_TICK * 8, 4); }
      asm volatile("fence.mbarrier_init.release.cluster;" ::: "memory");
    }
    __syncwarp();
  }
  cluster_arrive();
  slot = __shfl_sync(0xffffffffu, slot, 0);
  const int pref = slot;
  if (warp < 4) {
    asm volatile("setmaxnreg.dec.sync.aligned.u32 40;");
    if (warp == 1 + 4 * rank) {
      unsigned taken = threadIdx.x == 32;
#pragma unroll 1
      for (int n = 0; n < NSLOT; n++) {
        asm volatile("{\n.reg .pred p;\nsetp.ne.b32 p, %0, 0;\n@p atom.relaxed.gpu.global.exch.b32 %0, [%1], 1;\n}\n" : "+r"(taken) : "l"(CLAIMP(slot)) : "memory");
        if (!__any_sync(0xffffffffu, taken)) break;
        slot = slot == NSLOT - 1 ? 0 : slot + 1;
      }
    }
    cluster_wait();
    if (threadIdx.x == 32 + 128 * rank) send_both(sb + SM_BAR + B_SLOT * 8, (V_SLOT - B_SLOT) * 8 + 8, slot);
    if (warp == 2) {
#pragma unroll 1
      for (int kk = 0; kk < 4; kk++) {
        const int g0 = 2 + 3 * kk;
        const uint32_t fb = sb + SM_BAR + (B_FULL + g0) * 8;
        if (elect()) {
          mbar_expect_tx(fb, 3 * GR);
          tma2d(sb + g0 * GR, &p.c, kk * 64, (KV_ROW(pref & 7, 0) + rank) * 128, fb);
          tma3d_mc(sb + (g0 + 1 + rank) * GR, rank ? &p.wuv : &p.wuk, 0, kk * 64, ((pref & 56) >> 1) + 2 * KV_HEAD(pref & 7, 0), fb);
        }
        if (threadIdx.x == 64 + 128 * kk) send_both(sb + SM_BAR + B_SLOT * 8, (V_SLOT - B_SLOT) * 8 + rank * 4, pref);
        if (kk < 3) {
          uint32_t c0, c1;
          asm volatile("mov.u32 %0, %clock;" : "=r"(c0));
          do asm volatile("mov.u32 %0, %clock;" : "=r"(c1)); while (c1 - c0 < (kk ? X_D2 : X_DELAY));
        }
      }
      prefetch_tm(&p.x); prefetch_tm(&p.wq);
    }
  }
  int grp, idx, lb;
  int cn, cch, cstep;
  bool spare, redo;
  auto get_slot = [&]() {
    mbar_wait(sb + SM_BAR + B_SLOT * 8, 0);
    const uint4 sv = lds128(sb + SM_BAR + V_SLOT * 8);
    const uint32_t sl = __shfl_sync(0xffffffffu, sv.z, 0), miss = __shfl_sync(0xffffffffu, (sv.x ^ sv.z) | (sv.y ^ sv.z), 0);
    grp = (sl & 255) >> 3; idx = sl & 7; lb = (sl & 255) * 2 + rank;
    spare = grp == 8; redo = spare || miss;
    cn = CN_SPARE; cch = spare ? lb - NMAIN : 4 * CN_SPARE + 4 * lb; cstep = spare ? 4 : 1;
  };
  auto get_ticket = [&]() {
    mbar_wait(sb + SM_BAR + B_TICK * 8, 0);
    const int tk = __shfl_sync(0xffffffffu, lds32(sb + SM_BAR + V_TICK * 8), 0);
    cn = tk < NTICK ? 5 : 4;
    return 4 * NMAIN - 4 * lb - 4 + 2 * tk + rank;
  };

  if (wgi == 0) {
    asm volatile("setmaxnreg.dec.sync.aligned.u32 40;");
    const int lane = threadIdx.x & 31;
    cluster_arrive();
    get_slot();
    uint32_t pe = 0;
    auto acquire = [&](int g, int n, uint32_t m) {
      int i = g;
#pragma unroll 1
      do mbar_wait1(sb + SM_BAR + (B_EMPTY + i) * 8, (pe >> i) & 1); while (++i < g + n);
      pe ^= m << g;
    };
    if (warp == 3) {
      if (!spare) {
        const int s0 = lb * 16;
#pragma unroll 1
        for (int cg = 0; cg < 16; cg++) {
          if (cg == UP0 || cg == UP1) {
#pragma unroll 1
            for (int n = 0; n < 20 && !__any_sync(0xffffffffu, mbar_try(sb + SM_BAR + B_SLOT * 8, cg == UP0)); n++);
          } else if (cg < UP0) __nanosleep(US0);
          if (cg == UP1 && lane == rank * 32) send_both(sb + SM_BAR + B_TICK * 8, (V_TICK - B_TICK) * 8, atomicInc(FLAG(F_TICK), 0x7fffffffu));
          if (cg >= 5 && cg < 9) {
            unsigned l = lane;
            asm volatile("" : "+r"(l));
            const unsigned o = (idx * 8 + (l >> 2)) * (NH * HD) + (16 + 2 * grp) * HD + (l & 3) * 64;
            asm volatile("prefetch.global.L2 [%0];" ::"l"((rank ? p.wuvp : p.wukp) + (o + (cg - 1) * 64 * (NH * HD))));
          }
          const int ch = cg * 64 + 2 * lane;
          const uint32_t* kp = reinterpret_cast<const uint32_t*>(p.ak + (size_t)s0 * DM + ch);
          const uint32_t* vp = reinterpret_cast<const uint32_t*>(p.av + (size_t)s0 * DM + ch);
          const uint4 sw = __ldg(reinterpret_cast<const uint4*>(p.shk + ch * 4));
          uint32_t k3 = 0, k2 = 0, k1 = 0, k0 = 0, up = 0;
          if (lb > 0) { k3 = ldg_stream(kp - 4 * 512); k2 = ldg_stream(kp - 3 * 512); k1 = ldg_stream(kp - 2 * 512); k0 = ldg_stream(kp - 512); up = ldg_stream(vp - 512); }
          const uint32_t w0 = __byte_perm(sw.x, sw.z, 0x5410), w1 = __byte_perm(sw.x, sw.z, 0x7632);
          const uint32_t w2 = __byte_perm(sw.y, sw.w, 0x5410), w3 = __byte_perm(sw.y, sw.w, 0x7632);
          up = hmul2(hfma2(k0, w0, hfma2(k1, w1, hfma2(k2, w2, hmul2(k3, w3)))), up);
#pragma unroll 1
          for (int hb = 0; hb < 2; hb++) {
            uint32_t kk[8], u[8];
#pragma unroll
            for (int r = 0; r < 8; r++) { kk[r] = ldg_stream(kp + r * 512); u[r] = ldg_stream(vp + r * 512); }
#pragma unroll
            for (int r = 0; r < 8; r++) {
              k3 = k2; k2 = k1; k1 = k0; k0 = kk[r];
              u[r] = hmul2(hfma2(k0, w0, hfma2(k1, w1, hfma2(k2, w2, hmul2(k3, w3)))), u[r]);
            }
            if (lane == 0) asm volatile("cp.async.bulk.wait_group.read 0;" ::: "memory");
            __syncwarp();
            const uint32_t dst = sb + SM_UST + lane * 32 + ((lane & 4) << 2);
#pragma unroll
            for (int cc = 0; cc < 2; cc++) {
              const uint32_t sel = cc ? 0x7632 : 0x5410;
              asm volatile("st.shared.v4.b32 [%0], {%1,%2,%3,%4};" ::"r"(dst + cc * 1024), "r"(__byte_perm(u[6], u[5], sel)), "r"(__byte_perm(u[4], u[3], sel)),
                           "r"(__byte_perm(u[2], u[1], sel)), "r"(__byte_perm(u[0], up, sel)) : "memory");
              asm volatile("st.shared.v4.b32 [%0], {%1,%2,%3,%4};" ::"r"((dst ^ 16) + cc * 1024), "r"(__byte_perm(u[7], u[6], sel)), "r"(__byte_perm(u[5], u[4], sel)),
                           "r"(__byte_perm(u[3], u[2], sel)), "r"(__byte_perm(u[1], u[0], sel)) : "memory");
            }
            fence_async_smem();
            __syncwarp();
            if (lane == 0) {
              asm volatile("cp.async.bulk.tensor.3d.global.shared::cta.bulk_group.L2::cache_hint [%0, {%2, %3, %4}], [%1], %5;\ncp.async.bulk.commit_group;"
                           ::"l"(&p.w), "r"(sb + SM_UST), "r"(WZ / 2 + lb * 16 + (hb ^ 1) * (WPL / 2)), "r"(cg * 32), "r"(0), "l"(cg >= UP0 && cg < UP1 ? EV_FIRST : EV_NORMAL) : "memory");
            }
            up = u[7];
            kp += 8 * 512; vp += 8 * 512;
          }
          if ((cg & (cg + 1)) == 0 && lane == 0) {
            asm volatile("cp.async.bulk.wait_group 0;" ::: "memory");
            fence_release();
            flag_add(FLAG(F_U + 32 - __clz(cg)));
          }
        }
        prefetch_tm(&p.wo); prefetch_tm(&p.x3); prefetch_tm(&p.y3); prefetch_tm(&p.out);
      } else {
#pragma unroll 1
        for (int i = 0, g = 2; i < 32; i++) {
          acquire(g, i < 6 ? 2 : 1, 3);
          if (elect()) {
            const uint32_t fb = sb + SM_BAR + (B_FULL + g) * 8;
            if (i == 0) { mbar_expect_tx(fb - 8, 2048); bulk_g2s(sb + GR, p.gate_w, 2048, fb - 8); }
            mbar_expect_tx(fb, 2 * GR);
            tma3d(sb + g * GR, &p.x3, 0, (lb - NMAIN) * 512 + (i >> 3) * 128, (i & 7) * 2, fb);
          }
          g = g == NGR - 2 ? 2 : g + 2;
        }
        bar_arrive(5, 64);
      }
      unsigned long long t0, t1;
      asm volatile("mov.u64 %0, %globaltimer;" : "=l"(t0));
      auto check = [&]() {
        asm volatile("mov.u64 %0, %globaltimer;" : "=l"(t1));
        if (t1 - t0 > 2000000000ull) __trap();
      };
      if (!spare) {
        unsigned v;
        do {
          __nanosleep(PSL);
          check();
          asm volatile("ld.acquire.gpu.global.u32 %0, [%1];" : "=r"(v) : "l"(FLAG(lane & 1 ? F_Y + idx : F_GATE)) : "memory");
        } while (__any_sync(0xffffffffu, v < (lane & 1 ? 128 : 8)));
        __syncwarp();
        if (lane == 0) mbar_arrive(sb + SM_BAR + B_SLOT * 8);
      }
      if (lane == 0) {
        while (!mbar_try(sb + SM_BAR + B_DONE * 8, 0)) check();
      }
    } else if (warp != 0) {
      const int w = warp - 1;
      int ne = 12 + (CN_SPARE + 1 - w) / 2, c5 = 0, pend = 0;
      int cg = 2 + w, ch = cch + w * cstep;
#pragma unroll 1
      for (int e = spare ? 12 : 0; e < ne; e++) {
        const int rnd = e >= 6, k = e - 6 * rnd, rt = k == 4 ? idx : 15 - idx;
        uint8_t* dst = k < 4 ? g_kv + (size_t)(((k & 1) * 16 + 2 * grp + KV_HEAD(idx, k >> 1)) * 16 + KV_ROW(idx, k >> 1) + rank) * 32768 + w * 8192
                     : k < 6 ? g_cimg + (size_t)(rt * 32 + 16 * rnd + 2 * grp + rank) * 32768 + (w ^ (k & 1)) * 8192
                             : g_w + (size_t)ch * WSTRIDE + WZ;
        const uint32_t src = sb + w * 8192;
        if (e == 11) { c5 = get_ticket(); ne = 12 + ((cn + 1 - w) >> 1); }
        if (e == 6) flag_wait(FLAG(F_AD + grp), 32);
        mbar_wait1(sb + SM_BAR + (B_EV + w) * 8, e & 1);
        if (lane < 4 && k >= 6 && (!spare || e < ne - 6)) mbar_arrive_cluster(sb + SM_BAR + (B_EMPTY + cg) * 8, lane & 1);
        fence_async_smem();
        if (elect()) {
          const uint32_t cs = e >= 11 ? 4096 : 1024;
#pragma unroll 1
          for (uint32_t i = 0; i < (k >= 6 ? 4096 : 16384); i += cs) {
            const uint32_t o = (i + (i & 8192)) ^ (e == 11 ? 16384 : 0);
            asm volatile("cp.async.bulk.global.shared::cta.bulk_group.L2::cache_hint [%0], [%1], %2, %3;" ::"l"(dst + o), "r"(src + o), "r"(cs),
                         "l"(e == 4 || e == 5 || spare ? EV_FIRST : EV_NORMAL) : "memory");
            asm volatile("cp.async.bulk.commit_group;\ncp.async.bulk.wait_group.read 1;" ::: "memory");
            if (e == 11 && i == 8192) {
              mbar_arrive_cluster(sb + SM_BAR + (B_EMPTY + 1) * 8, 0); mbar_arrive_cluster(sb + SM_BAR + (B_EMPTY + 1) * 8, 1);
            }
          }
          asm volatile("cp.async.bulk.wait_group 0;" ::: "memory");
          mbar_arrive(sb + SM_BAR + (B_FREE + w) * 8);
        }
        __syncwarp();
        if (lane < (e == ne - 1 && !spare ? 2 : 0)) mbar_arrive_cluster(sb + SM_BAR + B_EMPTY * 8, lane);
        const int nch = ch + 2 * cstep + (k == 7 ? c5 : 0);
        pend++;
        if (k >= 3 && (e <= (spare ? 12 : 11) || e == ne - 1 || (nch ^ ch) >= 128)) {
          fence_release();
          const unsigned fl = k == 3 ? F_KV + rnd * 8 + grp : k < 6 ? F_CTX + rt * 2 + rnd : F_Y + ((unsigned)ch >> 7);
          if (lane <= (e == (spare ? 12 : 5)))
            asm volatile("red.relaxed.gpu.global.add.u32 [%0], %1;" ::"l"(FLAG(lane ? (spare ? F_GATE : F_AD + grp) : fl)), "r"(k >= 6 ? pend : 1) : "memory");
          pend = 0;
        }
        if (k >= 6) { cg = conv_next(cg, spare); ch = nch; }
      }
      if (lane == 0) mbar_arrive(sb + SM_BAR + B_DONE * 8);
    } else {
#pragma unroll 1
      for (int rnd = 0; rnd < (spare ? 0 : 2); rnd++) {
        const int hp = 16 * rnd + 2 * grp, head = hp + rank;
#pragma unroll 1
        for (int kk = rnd || redo ? 0 : 4; kk < 32; kk++) {
          const int g0 = 2 + 3 * (kk & 3);
          acquire(g0, kk < 4 ? 3 : 1, 7);
          if (elect()) {
            const uint32_t fb = sb + SM_BAR + (B_FULL + g0) * 8;
            mbar_expect_tx(fb, 3 * GR);
            if (kk < 16) {
              tma2d_p(sb + g0 * GR, &p.c, (kk & 7) * 64, (KV_ROW(idx, kk >> 3) + rank) * 128, fb, rnd);
              tma3d_mc_p(sb + (g0 + 1 + rank) * GR, rank ? &p.wuv : &p.wuk, 0, (kk & 7) * 64, (hp + KV_HEAD(idx, kk >> 3)) * 2, fb, kk >= 8);
            } else {
              tma2d_mc(sb + (g0 + rank) * GR, &p.x, (kk - 16) * 64, (rank ? 15 - idx : idx) * 128, fb);
              tma3d<true>(sb + (g0 + 2) * GR, &p.wq, 0, (kk - 16) * 64, head * 2, fb);
            }
          }
        }
        flag_wait(FLAG(F_KV + rnd * 8 + grp), 32);
        fence_async_all();
        int g0 = 2;
#pragma unroll 1
        for (int n = 0; n < 36; n += n == 0 || n == 33 ? 2 : 1) {
          const int it = (n >> 1) - (n & 1);
          const int blk = it & 15 ? (it <= idx ? it - 1 : 15 - it) : it ? 15 - idx : idx;
          acquire(g0, n < 7 ? 2 : 1, 3);
          if (elect()) {
            const uint32_t fb = sb + SM_BAR + (B_FULL + g0) * 8;
            if (n == 5) mbar_arrive(sb + SM_BAR + B_SLOT * 8);
            mbar_expect_tx(fb, 2 * GR);
            asm volatile("cp.async.bulk" TMA_MB ".L2::cache_hint [%0], [%1], %2, [%3], %4;" ::"r"(sb + g0 * GR), "l"(g_kv + (unsigned)((((n & 1) * 16 + (head & 15)) * 16 + blk) * 32768)),
                         "r"(2 * GR), "r"(fb), "l"(it >= 8 ? EV_FIRST : EV_NORMAL) : "memory");
          }
          g0 = g0 == 12 ? 2 : g0 + (n == 13 || n == 19 ? 4 : 2);
        }
      }
      int c5 = 0;
      if (spare) { bar_sync(5, 64); pe = 0x3FC0; }
      else c5 = get_ticket();
      auto conv_fill = [&](int g, int ch) {
        acquire(g, 1, 1);
        if (elect()) {
          const uint32_t fb = sb + SM_BAR + (B_FULL + g) * 8;
          mbar_expect_tx(fb, WBYTES + 4096);
          bulk_g2s<true>(sb + g * GR, g_w + (size_t)ch * WSTRIDE, WBYTES, fb);
          bulk_g2s<true>(sb + g * GR + WBYTES, p.ssk + (size_t)ch * SEQ, 4096, fb);
        }
      };
#pragma unroll 1
      for (int i = 0, g = 2; i < cn; i++) {
        if ((i & 15) == 0) { flag_wait(FLAG(F_U + (spare ? 32 - __clz(i >> 4) : 4)), NMAIN); fence_async_all(); }
        conv_fill(g + (i & 1), cch + i * cstep + (i == 4 ? c5 : 0));
        if (i & 1) g = conv_next(g, spare);
      }
      if (!spare) {
        const int rt = grp + 8 * rank, ct = idx;
        int g0 = P3G, top = 12;
        const uint8_t* src = g_cimg + (unsigned)((rt * 64 + 32) * GR);
#pragma unroll 1
        for (int kb = 0; kb < 64; kb++) {
          if (!(kb & 31)) { flag_wait(FLAG(F_CTX + rt * 2 + ((kb ^ 32) >> 5)), 32); fence_async_all(); if (kb) src -= 64 * GR; }
          acquire(g0, kb < 11 ? 2 : 1, 3);
          if (elect()) {
            const uint32_t fb = sb + SM_BAR + (B_FULL + g0) * 8;
            mbar_expect_tx(fb, 2 * GR);
            bulk_g2s<true>(sb + g0 * GR, src, GR, fb);
            tma2d_mc<true>(sb + (g0 + 1) * GR + rank * 8192, &p.wo, ct * 128 + rank * 64, (kb ^ 32) * 64, fb);
          }
          src += GR;
          g0 = g0 == (kb < XK ? 12 : kb < YK ? 10 : 8) ? (kb == 3 ? 2 : 0) : g0 + 2;
          if (kb == XK || (kb >= YK && top == P3Y && (kb == 63 || mbar_test(sb + SM_BAR + B_SLOT * 8, 1)))) {
            const bool j = kb != XK;
            if (j) { mbar_wait1(sb + SM_BAR + B_SLOT * 8, 1); fence_async_all(); }
            acquire(top, 1, 0);
            if (elect()) {
              const uint32_t fb = sb + SM_BAR + (B_FULL + top) * 8;
              mbar_expect_tx(fb, j ? 2 * GR + 512 : 2 * GR);
              if (j) bulk_g2s(sb + SM_GATE, g_gate + (unsigned)(rt * 128), 512, fb);
              tma3d(sb + top * GR, j ? &p.y3 : &p.x3, 0, (j ? ct : rt) * 128, (j ? rt : ct) * 2, fb);
            }
            top -= 2;
          }
        }
        unsigned n = 0;
        if (lane == 0) n = atomicInc(FLAG(F_EXIT), 0x7fffffffu);
        if (__any_sync(0xffffffffu, n == NMAIN - 1)) {
#pragma unroll
          for (int i = lane; i < 96; i += 32) *reinterpret_cast<uint2*>(FLAG(i)) = make_uint2(0, 0);
        }
      }
      if (lane == 0) mbar_arrive(sb + SM_BAR + B_DONE * 8);
    }
    __syncwarp();
    cluster_wait();
  } else {
    asm volatile("setmaxnreg.inc.sync.aligned.u32 232;");
    Cons c;
    c.sb = sb; c.pf = 0; c.wg = wgi - 1; c.tid = threadIdx.x & 127;
    const int lane = threadIdx.x & 31, t = lane & 3;
    const int row = c.wg * 64 + (warp & 3) * 16 + (lane >> 2);
    const uint32_t dkk = desc_k(sb), dk0 = dkk + c.wg * 512, dm0 = desc_mn<8192>(sb), dv0 = desc_mn<16384>(sb);
    const uint32_t dsw = DG + 512 - c.wg * 1024;
    if (c.wg == 1) bar_arrive(1, 256);
    c.pfree = 1;
    asm("mapa.shared::cluster.u32 %0, %1, %2;" : "=r"(c.relb) : "r"(sb + SM_BAR + (B_EMPTY + (c.tid >> 1)) * 8), "r"(c.tid & 1));
    c.zero = p.zero;
    const uint32_t stg = sb + (c.wg * 64 + (warp & 3) * 16 + ((lane >> 3) & 1) * 8 + (lane & 7)) * 128 + (((lane >> 4) ^ (lane & 7)) << 4);

    uint32_t dd0;
    auto load_dd = [&]() { asm volatile("ld.global.nc.u16 %0, [%1];" : "=r"(dd0) : "l"(p.ssd + (unsigned)(cch + c.wg * cstep + (lane & c.zero)))); };
    int pass = c.zero;
#pragma unroll 1
    do {
    if (pass) {
      load_dd();
#pragma unroll 1
      for (int g = 2; g < NGR; g += 3) { mbar_wait(sb + SM_BAR + (B_FULL + g) * 8, 0); c.release(g, 3); }
      c.pf = 0x924;
    if (spare) {
      c.wait_full(1);
      int g = 2;
#pragma unroll 1
      for (int r = 0; r < 4; r++) {
        float d[4] = {0.f, 0.f, 0.f, 0.f}, e[4] = {0.f, 0.f, 0.f, 0.f}, f[4] = {0.f, 0.f, 0.f, 0.f}, h[4] = {0.f, 0.f, 0.f, 0.f};
#pragma unroll 1
        for (int kb = 0; kb < 16; kb += 2) {
          c.wait_full(g);
          wg_fence();
#pragma unroll
          for (int k = 0; k < 4; k += 2) {
            mma_ss_n8(d, dk0 + g * DG + k * 2, dkk + DG + kb * 8 + k * 2);
            mma_ss_n8(e, dk0 + (g + 1) * DG + k * 2, dkk + DG + kb * 8 + 8 + k * 2);
            mma_ss_n8(f, dk0 + g * DG + k * 2 + 2, dkk + DG + kb * 8 + k * 2 + 2);
            mma_ss_n8(h, dk0 + (g + 1) * DG + k * 2 + 2, dkk + DG + kb * 8 + 8 + k * 2 + 2);
          }
          wg_commit();
          wg_wait<0>();
          c.release(g, 2);
          g = g == NGR - 2 ? 2 : g + 2;
        }
        reg_fence(d); reg_fence(e); reg_fence(f); reg_fence(h);
        d[0] = (d[0] + e[0]) + (f[0] + h[0]); d[2] = (d[2] + e[2]) + (f[2] + h[2]);
        if (t == 0) {
          float* gp = g_gate + (unsigned)((lb - NMAIN) * 512 + r * 128 + row);
          gp[0] = rcp(1.f + ex2(-1.4426950408889634f * d[0])); gp[8] = rcp(1.f + ex2(-1.4426950408889634f * d[2]));
        }
      }
    }
    } else cluster_wait();
    get_slot();
    } while (redo && !pass++);
    const float dmask = (float)(2 * t - (row & 63));
    int c5 = 0;
    uint32_t pv[32];
#pragma unroll 1
    for (int rnd = 0; rnd < (spare ? 0 : 2); rnd++) {
      float O[64];
      uint32_t Q[32];
      c.wait_full(2);
#pragma unroll 1
      for (int tile = c.zero; tile < 2; tile++) {
        float acc[128];
        const bool single = tile == 0;
        {
          const uint32_t a = dk0 + 2 * DG, b = dm0 + 3 * DG;
          c.turn_begin();
          wg_fence();
          mma_ss_n256_init<1>(acc, a, b);
#pragma unroll
          for (int k = 1; k < 4; k++) mma_ss_n256<1>(acc, a + k * 2, b + k * 128);
          wg_commit();
          if (single) c.turn_end();
        }
#pragma unroll 1
        for (int kb = 1; kb < 8; kb++) {
          const int g0 = 2 + 3 * (kb & 3);
          const uint32_t a = dk0 + g0 * DG, b = dm0 + (g0 + 1) * DG;
          const bool second = (kb == 1 && !single) || kb == 7;
          if (!second) { wg_wait<0>(); c.release(2 + 3 * ((kb - 1) & 3), 3); }
          c.wait_full(g0);
          if (!second) c.turn_begin();
          wg_fence();
#pragma unroll
          for (int k = 0; k < 4; k++) mma_ss_n256<1>(acc, a + k * 2, b + k * 128);
          wg_commit();
          if (kb != 6) c.turn_end();
          if (second) { wg_wait<1>(); c.release(2 + 3 * ((kb - 1) & 3), 3); }
          if (tile == 1 && kb == 3) { c.wait_stage_free(); stsm_frag<0, 4>(pv, stg); }
          if (tile == 1 && kb == 4) { stsm_frag<4, 8>(pv, stg); c.staged(); }
        }
        c.wait_stage_free();
        const bool nxt = c.try_full(2);
        wg_wait<0>();
        reg_fence(acc);
        c.release(11, 3);
        store_scaled(acc, SM_C, SM_C, stg, sb);
        c.staged();
        pack_frag<64>(acc, pv);
        if (!nxt) mbar_wait(sb + SM_BAR + (B_FULL + 2) * 8, (c.pf >> 2) & 1);
        c.pf ^= 4;
      }
      {
        float qa[64];
        float (&qb)[64] = O;
        {
          const uint32_t a = dk0 + 2 * DG, b = dm0 + 4 * DG;
          c.turn_begin();
          wg_fence();
          mma_ss_n128_init<1>(qa, a, b);
          mma_ss_n128_init<1>(qb, a + dsw, b);
#pragma unroll
          for (int k = 1; k < 4; k++) {
            mma_ss_n128<1>(qa, a + k * 2, b + k * 128);
            mma_ss_n128<1>(qb, a + dsw + k * 2, b + k * 128);
          }
          wg_commit();
        }
#pragma unroll 1
        for (int kb = 1; kb < 16; kb++) {
          const int g0 = 2 + 3 * (kb & 3);
          const uint32_t a = dk0 + g0 * DG, b = dm0 + (g0 + 2) * DG;
          const bool second = kb == 1 || kb == 15;
          if (!second) { wg_wait<0>(); c.release(2 + 3 * ((kb - 1) & 3), 3); }
          c.wait_full(g0);
          if (!second) c.turn_begin();
          wg_fence();
#pragma unroll
          for (int k = 0; k < 4; k++) {
            mma_ss_n128<1>(qa, a + k * 2, b + k * 128);
            mma_ss_n128<1>(qb, a + dsw + k * 2, b + k * 128);
          }
          wg_commit();
          if (kb != 14) c.turn_end();
          if (second) { wg_wait<1>(); c.release(2 + 3 * ((kb - 1) & 3), 3); }
          if (kb == QFLUSH) { c.wait_stage_free(); stsm_frag<0, 4>(pv, stg); }
          if (kb == QFLUSH + 1) { stsm_frag<4, 8>(pv, stg); c.staged(); }
        }
        c.wait_stage_free();
        const bool k0 = c.try_full(2);
        wg_wait<0>();
        reg_fence(qa); reg_fence(qb);
        c.release(11, 3);
        pack_frag<0>(qa, Q);
        if (c.wg == 0) {
          pack_frag<0>(qb, pv);
          stsm_frag(pv, stg);
        }
        if (!k0) c.wait_full(2); else c.pf ^= 4;
      }
      {
        const int nA = idx + 1;
        uint32_t (&P)[32] = pv;
        SoftState z;
        z.m0 = z.m1 = z.l0 = z.l1 = 0.f; z.shifted = c.zero;
#pragma unroll 1
        for (int seg = c.zero;; seg++) {
        if (c.wg == seg) attn_half(c, O, P, Q, nA == 1 && !seg, stg, z, dkk, dv0, dmask, seg);
        if (seg) break;
        int gk = c.wg ? 2 : 4, gv = c.wg ? 2 : 6;
        uint32_t dk = dkk + gk * DG;
#pragma unroll 1
        for (int it = 1 - c.wg; it < 17 - c.wg; it++) {
          float S[64];
          c.turn_begin();
          wg_fence();
          issue_qk(S, Q, dk);
          wg_commit();
          const uint32_t dv = dv0 + gv * DG;
          uint32_t relk = c.relb + gk * 8, relv = c.relb + gv * 8;
          gk = gv == 12 ? 2 : gv + (it == 6 || it == 9 ? 4 : 2);
          gv = it == 16 ? gk : gk == 12 ? 2 : gk + 2;
          uint32_t fk = sb + SM_BAR + (B_FULL + gk) * 8, fv = sb + SM_BAR + (B_FULL + gv) * 8, park = (c.pf >> gk) & 1, parv = (c.pf >> gv) & 1;
          c.pf ^= (1u << gk) | (1u << gv);
          dk = dkk + gk * DG;
          float lo0 = z.l0, lo1 = z.l1;
          const bool first = it == nA || it == 0;
          if (it == nA) {
            lo0 = rcp(quad_sum(lo0)); lo1 = rcp(quad_sum(lo1));
            z.m0 = z.m1 = z.l0 = z.l1 = 0.f; z.shifted = 0;
          }
          float s0, s1, d0 = z.m0, d1 = z.m1;
          int pre = z.shifted || (it & 15) == 0 || it + 1 == nA;
          float lim = first ? -1.f : SM_LIMIT;
          asm volatile("" : "+r"(relk), "+r"(relv), "+r"(fk), "+r"(fv), "+r"(park), "+r"(parv), "+r"(dk), "+r"(pre), "+f"(lim), "+f"(d0), "+f"(d1), "+f"(z.l0), "+f"(z.l1));
          if (it + c.wg > 1) {
            issue_pv<0>(O, P, dv, it != nA + 1 && it != 1, true);
            issue_pv<1>(O, P, dv, 1, true);
            c.turn_end();
          } else if (it) {
            issue_pv<0>(O, P, dv, 0, true);
            wg_commit(); wg_commit();
            c.turn_end();
            bar_sync(6, 256);
          } else stage_q2(c, O, P, stg);
          wg_wait<4>();
          reg_fence(S); reg_fence(Q);
          if (c.tid < 4) asm volatile("mbarrier.arrive.shared::cluster.b64 _, [%0];" ::"r"(relk) : "memory");
#pragma unroll 1
          for (int pass = 0;; pass++) {
            if (pre) {
              if (it + 1 == nA) load_q(Q, stg);
              if ((it & 15) == 0) mask_diag(S, dmask);
              if (z.shifted) shift_scores(S, d0, d1);
            }
            float tr[ROT];
            exp_quarter<0, 3>(S, P, tr, s0, s1, sb);
            exp_quarter<1, 2>(S, P, tr, s0, s1, sb);
            exp_quarter<2, 1>(S, P, tr, s0, s1, sb);
            exp_quarter<3, 0>(S, P, tr, s0, s1, sb);
            reg_fence(O);
            if (c.tid < (pass || !it ? 0 : 4)) asm volatile("mbarrier.arrive.shared::cluster.b64 _, [%0];" ::"r"(relv) : "memory");
            const bool ok = mbar_test(fk, park) & mbar_test(fv, parv);
            if (!ok) lim = -1.f;
            if (!__any_sync(0xffffffffu, !(s0 <= lim && s1 <= lim))) break;
            if (pass) break;
            if (it == nA) {
              store_scaled(O, lo0, lo1, stg, sb);
              c.staged();
            }
            if (!it) bar_arrive(6, 256);
            if (!ok) { mbar_wait(fk, park); mbar_wait(fv, parv); }
            if (!soft_unsafe(s0, s1, first)) break;
            soft_fix(S, O, z, first, d0, d1);
            pre = 1;
          }
          z.l0 += s0; z.l1 += s1;
        }
        if (!c.wg) bar_arrive(6, 256);
        }
        load_dd();
        c.turn_begin();
        wg_fence();
        issue_pv<0>(O, P, dv0 + 12 * DG, 1, true);
        issue_pv<1>(O, P, dv0 + 12 * DG, 1, !c.wg);
        c.turn_end();
        z.l0 = rcp(quad_sum(z.l0)); z.l1 = rcp(quad_sum(z.l1));
        c.wait_stage_free();
        if (rnd) c5 = get_ticket();
        wg_wait<0>();
        reg_fence(O); reg_fence(P);
        c.release(12, 2);
        store_scaled(O, z.l0, z.l1, stg, sb);
        c.staged();
      }
    }
    conv_tasks(c, p, (cn + 1 - c.wg) >> 1, spare, cch + c.wg * cstep, 2 * cstep, c5, dd0, dkk, warp & 3, lane);
    if (c.wg == 1) c.pf ^= 0x14;
    if (c.wg == (cn & 1)) c.turn_begin();
    if (!spare) {
      const int rt = grp + 8 * rank, ct = idx;
      float acc[64];
      int g0 = P3G + 2, pg = P3G;
      {
        c.wait_full(P3G);
        const uint32_t a = dk0 + P3G * DG, b = dm0 + (P3G + 1) * DG;
        wg_fence();
        mma_ss_n128_init<1>(acc, a, b);
#pragma unroll
        for (int k = 1; k < 4; k++) mma_ss_n128<1>(acc, a + k * 2, b + k * 128);
        wg_commit();
      }
#pragma unroll 1
      for (int kb = 1; kb < 64; kb++) {
        c.wait_full(g0);
        if (kb == STR && !c.wg) c.turn_begin();
        const uint32_t a = dk0 + g0 * DG, b = dm0 + (g0 + 1) * DG;
        wg_fence();
#pragma unroll
        for (int k = 0; k < 4; k++) mma_ss_n128<1>(acc, a + k * 2, b + k * 128);
        wg_commit();
        if (kb < STR) { wg_wait<1>(); c.release(pg, kb <= 59 ? 2 : 0); }
        pg = g0;
        g0 = g0 == (kb < XK ? 12 : kb < YK ? 10 : 8) ? (kb == 3 ? 2 : 0) : g0 + 2;
      }
      if (c.wg) c.turn_end();
      cluster_arrive();
      c.wait_full(P3X);
      c.wait_full(P3Y);
      const float g0f = __uint_as_float(lds32(sb + SM_GATE + row * 4)), g1f = __uint_as_float(lds32(sb + SM_GATE + row * 4 + 32));
      const uint32_t gp0 = pack_bf16(g0f, g0f), gp1 = pack_bf16(g1f, g1f);
      const float h0 = 1.f - g0f, h1 = 1.f - g1f;
      const int w = warp & 3;
      const uint32_t xa = stg + P3X * GR;
      const uint32_t ya = sb + P3Y * GR + c.wg * 16384 + ((lane >> 4) * 8 + (lane & 7)) * 128 + (((2 * w + ((lane >> 3) & 1)) ^ (lane & 7)) << 4);
      uint32_t xy[32];
      auto prep = [&](int j0, int j1) {
#pragma unroll
        for (int jj = j0; jj < j1; jj++) {
          uint32_t x[4], y[4];
          asm volatile("ldmatrix.sync.aligned.m8n8.x4.shared.b16 {%0,%1,%2,%3}, [%4];" : "=r"(x[0]), "=r"(x[1]), "=r"(x[2]), "=r"(x[3]) : "r"((xa ^ ((jj & 3) << 5)) + (jj >> 2) * 16384) : "memory");
          asm volatile("ldmatrix.sync.aligned.m8n8.x4.trans.shared.b16 {%0,%1,%2,%3}, [%4];" : "=r"(y[0]), "=r"(y[1]), "=r"(y[2]), "=r"(y[3]) : "r"(ya + jj * 2048) : "memory");
#pragma unroll
          for (int i = 0; i < 4; i++) xy[4 * jj + i] = hmul2(x[i], y[i]);
        }
      };
      prep(0, 4);
      wg_wait<0>();
      reg_fence(acc);
#pragma unroll
      for (int hf = 0; hf < 2; hf++) {
#pragma unroll
        for (int i = 16 * hf; i < 16 * hf + 16; i++) {
          const float h = (i & 1) ? h1 : h0;
          xy[i] = hfma2((i & 1) ? gp1 : gp0, xy[i], pack_bf16(acc[2 * i] * h, acc[2 * i + 1] * h));
        }
        if (hf) stsm_frag<4, 8>(xy, xa); else stsm_frag<0, 4>(xy, xa);
        fence_async_smem();
        __syncwarp();
        const int r0 = c.wg * 64 + w * 16;
        if (lane == 0) tma2d_store(&p.out, sb + (P3X + hf) * GR + r0 * 128, ct * 128 + hf * 64, rt * 128 + r0);
        if (!hf) prep(4, 8);
      }
      if (lane == 0) asm volatile("cp.async.bulk.commit_group;\ncp.async.bulk.wait_group.read 0;" ::: "memory");
    } else { cluster_arrive(); }
    if (lane == 0) mbar_arrive(sb + SM_BAR + B_DONE * 8);
    __syncwarp();
    cluster_wait();
  }
}

typedef CUresult (*EncFn)(CUtensorMap*, CUtensorMapDataType, cuuint32_t, void*, const cuuint64_t*, const cuuint64_t*, const cuuint32_t*,
                          const cuuint32_t*, CUtensorMapInterleave, CUtensorMapSwizzle, CUtensorMapL2promotion, CUtensorMapFloatOOBfill);

void enc2d(EncFn enc, CUtensorMap* tm, const void* base, uint64_t cols, uint64_t rows, uint32_t bc, uint32_t br) {
  cuuint64_t dims[2] = {cols, rows}; cuuint64_t strides[1] = {cols * 2}; cuuint32_t box[2] = {bc, br}; cuuint32_t es[2] = {1, 1};
  enc(tm, CU_TENSOR_MAP_DATA_TYPE_BFLOAT16, 2, const_cast<void*>(base), dims, strides, box, es, CU_TENSOR_MAP_INTERLEAVE_NONE,
      CU_TENSOR_MAP_SWIZZLE_128B, CU_TENSOR_MAP_L2_PROMOTION_L2_128B, CU_TENSOR_MAP_FLOAT_OOB_FILL_NONE);
}
void enc3d(EncFn enc, CUtensorMap* tm, const void* base, uint64_t K, uint64_t N, uint32_t bk = 64, uint64_t pitch = 0) {
  cuuint64_t dims[3] = {64, K, N / 64}; cuuint64_t strides[2] = {pitch ? pitch : N * 2, 128}; cuuint32_t box[3] = {64, bk, 2}; cuuint32_t es[3] = {1, 1, 1};
  enc(tm, CU_TENSOR_MAP_DATA_TYPE_BFLOAT16, 3, const_cast<void*>(base), dims, strides, box, es, CU_TENSOR_MAP_INTERLEAVE_NONE,
      CU_TENSOR_MAP_SWIZZLE_128B, CU_TENSOR_MAP_L2_PROMOTION_L2_128B, CU_TENSOR_MAP_FLOAT_OOB_FILL_NONE);
}

}

extern "C" void kernel_launch(void* const* d_in, const int* in_sizes, int n_in, void* d_out, int out_size) {
  (void)in_sizes; (void)n_in; (void)out_size;
  typedef const __nv_bfloat16* BP;
  BP xq = (BP)d_in[0], ak = (BP)d_in[1], av = (BP)d_in[2], shk = (BP)d_in[3], ssk = (BP)d_in[4], ssd = (BP)d_in[5];
  BP ckv = (BP)d_in[7], wq = (BP)d_in[8], wuk = (BP)d_in[9], wuv = (BP)d_in[10], wo = (BP)d_in[11], gw = (BP)d_in[12];

  static EncFn enc = nullptr;
  if (!enc) {
    cudaDriverEntryPointQueryResult qr;
    cudaGetDriverEntryPoint("cuTensorMapEncodeTiled", (void**)&enc, cudaEnableDefault, &qr);
    cudaFuncSetAttribute(mega_kernel, cudaFuncAttributeMaxDynamicSharedMemorySize, SMEM_BYTES);
  }
  Params p;
  enc2d(enc, &p.x, xq, DM, SEQ, 64, 128);
  enc2d(enc, &p.c, ckv, DC, SEQ, 64, 128);
  enc3d(enc, &p.wq, wq, DM, NH * HD);
  enc3d(enc, &p.wuk, wuk, DC, NH * HD);
  enc3d(enc, &p.wuv, wuv, DC, NH * HD);
  enc2d(enc, &p.wo, wo, DM, NH * HD, 64, 64);
  enc3d(enc, &p.x3, xq, SEQ, DM, 128);
  enc2d(enc, &p.out, d_out, DM, SEQ, 64, 16);
  {
    void* wp = nullptr;
    cudaGetSymbolAddress(&wp, g_w);
    enc3d(enc, &p.y3, (uint8_t*)wp + WZ, DM, SEQ, 128, WSTRIDE);
    cuuint64_t dims[3] = {WSTRIDE / 2, DM / 2, 2}; cuuint64_t strides[2] = {2 * WSTRIDE, WSTRIDE}; cuuint32_t box[3] = {16, 32, 2}; cuuint32_t es[3] = {1, 1, 1};
    enc(&p.w, CU_TENSOR_MAP_DATA_TYPE_BFLOAT16, 3, wp, dims, strides, box, es, CU_TENSOR_MAP_INTERLEAVE_NONE,
        CU_TENSOR_MAP_SWIZZLE_32B, CU_TENSOR_MAP_L2_PROMOTION_NONE, CU_TENSOR_MAP_FLOAT_OOB_FILL_NONE);
  }
  p.zero = 0;
  cudaGetSymbolAddress((void**)&p.flags, g_flags);
  for (int i = 0; i < 128; i++) {
    const int tp = i % NSLOT;
    p.pref[i] = tp < 32 ? (tp & 7) * 8 + (tp >> 3) : tp < 60 ? (1 + (tp - 32) % 7) * 8 + 4 + (tp - 32) / 7 : tp < 62 ? tp + 4 : tp - 58;
  }
  p.gate_w = gw; p.ak = ak; p.av = av; p.shk = shk; p.ssk = ssk; p.ssd = ssd; p.wukp = wuk; p.wuvp = wuv;

  mega_kernel<<<132, NTHREADS, SMEM_BYTES>>>(p);
}
```
